```python
import torch

def _softmax(x, axis=-1):
    return torch.softmax(x, dim=axis)
def _gelu(x):
    return torch.nn.functional.gelu(x, approximate="tanh")
def _silu(x):
    return torch.nn.functional.silu(x)
def _sigmoid(x):
    return torch.sigmoid(x)
def _layernorm(x, axis=-1, eps=1e-5):
    m = x.mean(dim=axis, keepdim=True)
    v = x.var(dim=axis, keepdim=True, unbiased=False)
    return (x - m) / torch.sqrt(v + eps)
def _scatter_add(tgt, idx, src, axis=0):
    return tgt.clone().index_add_(axis, idx, src)
def _segment_sum(src, seg, n):
    out = torch.zeros((n,) + src.shape[1:], dtype=src.dtype)
    return out.index_add_(0, seg, src)
def _pad(x, pw):
    flat = tuple(v for pair in reversed(pw) for v in pair)
    return torch.nn.functional.pad(x, flat)

kernel_name = 'sequential_preLN__linear_kernel_hedgehog__glu_gated_bilinear__prompt'

def setup_inputs():

    _w = (lambda a: (lambda t: t.to(torch.bfloat16) if t.is_floating_point() else t)(torch.as_tensor(a)))
    def _A_setup():
        B, S, D, H = 1, 2048, 512, 32
        Dh = D // H
        return {
            "x": _w((lambda *s: torch.randn(*s, dtype=torch.bfloat16) * 0.05)(B, S, D)),
            "wqkv": _w((lambda *s: torch.randn(*s, dtype=torch.bfloat16) * 0.2)(D, 3 * D)),
            "w_phi": _w((lambda *s: torch.randn(*s, dtype=torch.bfloat16) * 0.2)(H, Dh, Dh) * (Dh ** -0.5)),
            "wo": _w((lambda *s: torch.randn(*s, dtype=torch.bfloat16) * 0.05)(D, D)),
        }
    _A_in = _A_setup()

    def _B_setup():
        B, S, D, F = 1, 2048, 512, 1376
        return {
            "x": _w((lambda *s: torch.randn(*s, dtype=torch.bfloat16) * 0.05)(B, S, D)),
            "w_gate": _w((lambda *s: torch.randn(*s, dtype=torch.bfloat16) * 0.4)(D, F) * (D ** -0.5)),
            "w_up": _w((lambda *s: torch.randn(*s, dtype=torch.bfloat16) * 0.4)(D, F) * (D ** -0.5)),
            "w_down": _w((lambda *s: torch.randn(*s, dtype=torch.bfloat16) * 0.4)(F, D) * (F ** -0.5)),
        }
    _B_in = _B_setup()

    return {
        "A_x": _A_in["x"],
        "A_wqkv": _A_in["wqkv"],
        "A_w_phi": _A_in["w_phi"],
        "A_wo": _A_in["wo"],
        "B_x": _B_in["x"],
        "B_w_gate": _B_in["w_gate"],
        "B_w_up": _B_in["w_up"],
        "B_w_down": _B_in["w_down"],
    }

def reference(A_x, A_wqkv, A_w_phi, A_wo, B_x, B_w_gate, B_w_up, B_w_down):
    def _A_ref(x, wqkv, w_phi, wo):
        B, S, D = x.shape
        H = 32; Dh = D // H
        qkv = (lambda x, *d: x.permute(*d))((x @ wqkv).reshape(B, S, 3, H, Dh), 2, 0, 3, 1, 4)
        q, k, v = qkv[0], qkv[1], qkv[2]
        pq = torch.einsum("bhsd,hdf->bhsf", q, w_phi)
        pk = torch.einsum("bhsd,hdf->bhsf", k, w_phi)
        phi_q = torch.concatenate([_softmax(pq, axis=-1), _softmax(-pq, axis=-1)], axis=-1)
        phi_k = torch.concatenate([_softmax(pk, axis=-1), _softmax(-pk, axis=-1)], axis=-1)
        kv = torch.einsum("bhsf,bhsd->bhfd", phi_k, v)
        z  = torch.einsum("bhsf->bhf", phi_k)
        num = torch.einsum("bhqf,bhfd->bhqd", phi_q, kv)
        den = torch.einsum("bhqf,bhf->bhq", phi_q, z)[..., None] + 1e-6
        o = num / den
        return (lambda x, *d: x.permute(*d))(o, 0, 2, 1, 3).reshape(B, S, D) @ wo

    def _B_ref(x, w_gate, w_up, w_down):
        g = torch.einsum("bsd,df->bsf", x, w_gate)
        u = torch.einsum("bsd,df->bsf", x, w_up)
        h = g * u
        return torch.einsum("bsf,fd->bsd", h, w_down)

    x = A_x
    h = x + _A_ref(_layernorm(x, axis=-1), A_wqkv, A_w_phi, A_wo)
    h2 = h + _B_ref(_layernorm(h, axis=-1), B_w_gate, B_w_up, B_w_down)
    return h2
```

```cpp
#include <cuda_runtime.h>
#include <cuda_bf16.h>
#include <cuda.h>
#include <stdint.h>

#define PROF 0

namespace {

constexpr int NCTA   = 128;
constexpr int SLOT   = 24576;
constexpr int NSLOT  = 9;
constexpr int NSTAGE = 47;

constexpr int ST_X0   = 0;
constexpr int ST_WK   = 3;
constexpr int ST_X1   = 6;
constexpr int ST_SCR0 = 9;
constexpr int ST_WV   = 10;
constexpr int ST_SCR1 = 13;
constexpr int ST_WQ   = 14;
constexpr int ST_WO   = 17;
constexpr int ST_GU   = 23;
constexpr int ST_D    = 39;

__host__ __device__ constexpr bool st_is_x(int s)   { return (s >= 0 && s < 3) || (s >= 6 && s < 9); }
__host__ __device__ constexpr bool st_is_scr(int s) { return s == ST_SCR0 || s == ST_SCR1; }
__host__ __device__ constexpr bool st_is_mc(int s)  { return st_is_x(s) || s >= ST_WO; }
__host__ __device__ constexpr int  st_issuer(int s) { return s < 3 ? (s & 1) : ((s + 1) & 1); }
__host__ __device__ constexpr int  st_bytes(int s)  {
  return s >= ST_D ? 22528 : ((s == ST_WO + 4 || s == ST_WO + 5) ? 16384 : 24576);
}
__host__ __device__ constexpr int  st_base_cnt(int d) {
  return st_is_x(d) ? 4 : (st_is_scr(d) || (d >= ST_WO && d < ST_GU)) ? 1 : 2;
}
__host__ __device__ constexpr int  st_empty_cnt(int d) { return st_base_cnt(d) * (st_is_mc(d + NSLOT) ? 2 : 1); }

constexpr int SM_ONES = NSLOT * SLOT;
constexpr int SM_WPHI = SM_ONES + 2048;
constexpr int SM_KVS  = SM_WPHI + 2048;
constexpr int SM_BAR  = SM_KVS + 6144;
constexpr int SM_FULL  = SM_BAR;
constexpr int SM_EMPTY = SM_BAR + NSTAGE * 8;
constexpr int SM_MISCB = SM_BAR + 2 * NSTAGE * 8;
constexpr int SM_KVB   = SM_MISCB + 8;
constexpr int SM_EPOCH = SM_KVB + 8;
constexpr int SM_TOTAL = SM_BAR + 1024;

static_assert(SM_TOTAL == 232448, "smem budget");

struct Maps { CUtensorMap x, w, wo96, wo64, g, u, g7, u7, d; };

__device__ uint4    g_o[2][32][8][4][4][32];
__device__ uint4    g_h[2][32][8][4][4][32];
__device__ uint2    g_st[2][2048][8];
__device__ uint4    g_part[32][8][8][4][4][32];
__device__ float    g_kv[2][32 * 32 * 16];
__device__ float    g_z[2][32 * 32];
__device__ unsigned g_kvcnt[8 * 32];
__device__ unsigned g_start;

__device__ __forceinline__ uint32_t smem_u32(const void* p) { return (uint32_t)__cvta_generic_to_shared(p); }
__device__ __forceinline__ void mbar_init(uint32_t bar, int cnt) {
  asm volatile("mbarrier.init.shared::cta.b64 [%0], %1;" ::"r"(bar), "r"(cnt) : "memory");
}
__device__ __forceinline__ void mbar_expect_tx(uint32_t bar, uint32_t bytes) {
  asm volatile("mbarrier.arrive.expect_tx.shared::cta.b64 _, [%0], %1;" ::"r"(bar), "r"(bytes) : "memory");
}
__device__ __forceinline__ void mbar_arrive(uint32_t bar) {
  asm volatile("mbarrier.arrive.shared::cta.b64 _, [%0];" ::"r"(bar) : "memory");
}
__device__ __forceinline__ void mbar_arrive_cluster(uint32_t bar, uint32_t rank) {
  asm volatile("{\n.reg .b32 ra;\nmapa.shared::cluster.u32 ra, %0, %1;\n"
               "mbarrier.arrive.shared::cluster.b64 _, [ra];\n}" ::"r"(bar), "r"(rank) : "memory");
}
__device__ __forceinline__ bool mbar_try(uint32_t bar) {
  uint32_t ok;
  asm volatile("{\n.reg .pred p;\nmbarrier.try_wait.parity.shared::cta.b64 p, [%1], 0;\nselp.u32 %0, 1, 0, p;\n}"
               : "=r"(ok) : "r"(bar) : "memory");
  return ok != 0;
}
__device__ __forceinline__ void mbar_wait(uint32_t bar) {
  int it = 0;
  while (!mbar_try(bar)) {
    if (++it > (1 << 20)) __trap();
  }
}
__device__ __forceinline__ void bar_sync(int id, int n)   { asm volatile("bar.sync %0, %1;" ::"r"(id), "r"(n) : "memory"); }
__device__ __forceinline__ void bar_arrive(int id, int n) { asm volatile("bar.arrive %0, %1;" ::"r"(id), "r"(n) : "memory"); }
__device__ __forceinline__ void fence_async_smem() { asm volatile("fence.proxy.async.shared::cta;" ::: "memory"); }
__device__ __forceinline__ void wg_fence()  { asm volatile("wgmma.fence.sync.aligned;" ::: "memory"); }
__device__ __forceinline__ void wg_commit() { asm volatile("wgmma.commit_group.sync.aligned;" ::: "memory"); }
template <int N> __device__ __forceinline__ void wg_wait() { asm volatile("wgmma.wait_group.sync.aligned %0;" ::"n"(N) : "memory"); }
__device__ __forceinline__ uint64_t mk_desc(uint32_t addr, uint32_t lbo, uint32_t sbo) {
  return (uint64_t)((addr & 0x3FFFF) >> 4) | ((uint64_t)((lbo & 0x3FFFF) >> 4) << 16) | ((uint64_t)(sbo >> 4) << 32) | (1ull << 62);
}
__device__ __forceinline__ void tma2d(uint32_t dst, const CUtensorMap* m, int c0, int c1, uint32_t bar) {
  asm volatile("cp.async.bulk.tensor.2d.shared::cluster.global.mbarrier::complete_tx::bytes [%0], [%1, {%3, %4}], [%2];"
               ::"r"(dst), "l"(m), "r"(bar), "r"(c0), "r"(c1) : "memory");
}
__device__ __forceinline__ void tma2d_mc(uint32_t dst, const CUtensorMap* m, int c0, int c1, uint32_t bar) {
  asm volatile("cp.async.bulk.tensor.2d.shared::cluster.global.mbarrier::complete_tx::bytes.multicast::cluster [%0], [%1, {%3, %4}], [%2], %5;"
               ::"r"(dst), "l"(m), "r"(bar), "r"(c0), "r"(c1), "h"((uint16_t)3) : "memory");
}
__device__ __forceinline__ void tma3d_mc(uint32_t dst, const CUtensorMap* m, int c0, int c1, int c2, uint32_t bar) {
  asm volatile("cp.async.bulk.tensor.3d.shared::cluster.global.mbarrier::complete_tx::bytes.multicast::cluster [%0], [%1, {%3, %4, %5}], [%2], %6;"
               ::"r"(dst), "l"(m), "r"(bar), "r"(c0), "r"(c1), "r"(c2), "h"((uint16_t)3) : "memory");
}
__device__ __forceinline__ void ldsm4(uint32_t (&r)[4], uint32_t addr) {
  asm volatile("ldmatrix.sync.aligned.m8n8.x4.shared.b16 {%0,%1,%2,%3}, [%4];"
               : "=r"(r[0]), "=r"(r[1]), "=r"(r[2]), "=r"(r[3]) : "r"(addr) : "memory");
}
__device__ __forceinline__ void ldsm4t(uint32_t (&r)[4], uint32_t addr) {
  asm volatile("ldmatrix.sync.aligned.m8n8.x4.trans.shared.b16 {%0,%1,%2,%3}, [%4];"
               : "=r"(r[0]), "=r"(r[1]), "=r"(r[2]), "=r"(r[3]) : "r"(addr) : "memory");
}
__device__ __forceinline__ void stsm4(uint32_t addr, uint32_t r0, uint32_t r1, uint32_t r2, uint32_t r3) {
  asm volatile("stmatrix.sync.aligned.m8n8.x4.shared.b16 [%0], {%1,%2,%3,%4};"
               ::"r"(addr), "r"(r0), "r"(r1), "r"(r2), "r"(r3) : "memory");
}
__device__ __forceinline__ void mma16816(float (&c)[4], const uint32_t (&a)[4], uint32_t b0, uint32_t b1) {
  asm volatile("mma.sync.aligned.m16n8k16.row.col.f32.bf16.bf16.f32 {%0,%1,%2,%3},{%4,%5,%6,%7},{%8,%9},{%0,%1,%2,%3};"
               : "+f"(c[0]), "+f"(c[1]), "+f"(c[2]), "+f"(c[3])
               : "r"(a[0]), "r"(a[1]), "r"(a[2]), "r"(a[3]), "r"(b0), "r"(b1));
}
__device__ __forceinline__ uint32_t pack2(float lo, float hi) {
  uint32_t r; asm("cvt.rn.bf16x2.f32 %0, %1, %2;" : "=r"(r) : "f"(hi), "f"(lo)); return r;
}
__device__ __forceinline__ float blo(uint32_t w) { return __uint_as_float(w << 16); }
__device__ __forceinline__ float bhi(uint32_t w) { return __uint_as_float(w & 0xFFFF0000u); }
__device__ __forceinline__ uint32_t hsub2(uint32_t a, uint32_t b) { uint32_t r; asm("sub.rn.bf16x2 %0, %1, %2;" : "=r"(r) : "r"(a), "r"(b)); return r; }
__device__ __forceinline__ uint32_t hmax2(uint32_t a, uint32_t b) { uint32_t r; asm("max.bf16x2 %0, %1, %2;" : "=r"(r) : "r"(a), "r"(b)); return r; }
__device__ __forceinline__ uint32_t hmin2(uint32_t a, uint32_t b) { uint32_t r; asm("min.bf16x2 %0, %1, %2;" : "=r"(r) : "r"(a), "r"(b)); return r; }
__device__ __forceinline__ float ex2(float x) { float r; asm("ex2.approx.ftz.f32 %0, %1;" : "=f"(r) : "f"(x)); return r; }
__device__ __forceinline__ float rcp(float x) { float r; asm("rcp.approx.ftz.f32 %0, %1;" : "=f"(r) : "f"(x)); return r; }
__device__ __forceinline__ void ld_rlx4(uint32_t (&r)[4], const uint4* p) {
  asm volatile("ld.relaxed.gpu.global.v4.b32 {%0,%1,%2,%3}, [%4];"
               : "=r"(r[0]), "=r"(r[1]), "=r"(r[2]), "=r"(r[3]) : "l"(p) : "memory");
}
__device__ __forceinline__ void st_rlx4(uint4* p, uint32_t a, uint32_t b, uint32_t c, uint32_t d) {
  asm volatile("st.relaxed.gpu.global.v4.b32 [%0], {%1,%2,%3,%4};" ::"l"(p), "r"(a), "r"(b), "r"(c), "r"(d) : "memory");
}
__device__ __forceinline__ void st_rlx2(uint2* p, uint32_t a, uint32_t b) {
  asm volatile("st.relaxed.gpu.global.v2.b32 [%0], {%1,%2};" ::"l"(p), "r"(a), "r"(b) : "memory");
}
__device__ __forceinline__ uint32_t nz(uint32_t w) { return max(w, 1u); }
__device__ __forceinline__ uint32_t min4(const uint32_t (&r)[4]) { return min(min(r[0], r[1]), min(r[2], r[3])); }

__device__ __forceinline__ void ld_chunk(uint32_t (&a)[4][4], const uint4* p) {
#pragma unroll
  for (int s = 0; s < 4; s++) ld_rlx4(a[s], p + s * 32);
}
__device__ __forceinline__ void chk_chunk(uint32_t (&a)[4][4], const uint4* p) {
  uint32_t m = min(min(min4(a[0]), min4(a[1])), min(min4(a[2]), min4(a[3])));
  if (__any_sync(0xffffffffu, m == 0)) {
    int it = 0;
    do {
      ld_chunk(a, p);
      m = min(min(min4(a[0]), min4(a[1])), min(min4(a[2]), min4(a[3])));
      if (++it > (1 << 18)) break;
    } while (__any_sync(0xffffffffu, m == 0));
  }
}

__device__ __forceinline__ void wgmma_rs_n64(float (&d)[32], const uint32_t (&a)[4], uint64_t descB, int scaleD) {
  asm volatile("{\n.reg .pred p;\nsetp.ne.b32 p, %37, 0;\n"
    "wgmma.mma_async.sync.aligned.m64n64k16.f32.bf16.bf16 {%0,%1,%2,%3,%4,%5,%6,%7,%8,%9,%10,%11,%12,%13,%14,%15,%16,%17,%18,%19,%20,%21,%22,%23,%24,%25,%26,%27,%28,%29,%30,%31}, {%32,%33,%34,%35}, %36, p, 1, 1, 1;\n}\n"
    : "+f"(d[0]),"+f"(d[1]),"+f"(d[2]),"+f"(d[3]),"+f"(d[4]),"+f"(d[5]),"+f"(d[6]),"+f"(d[7]),"+f"(d[8]),"+f"(d[9]),"+f"(d[10]),"+f"(d[11]),"+f"(d[12]),"+f"(d[13]),"+f"(d[14]),"+f"(d[15]),"+f"(d[16]),"+f"(d[17]),"+f"(d[18]),"+f"(d[19]),"+f"(d[20]),"+f"(d[21]),"+f"(d[22]),"+f"(d[23]),"+f"(d[24]),"+f"(d[25]),"+f"(d[26]),"+f"(d[27]),"+f"(d[28]),"+f"(d[29]),"+f"(d[30]),"+f"(d[31])
    : "r"(a[0]), "r"(a[1]), "r"(a[2]), "r"(a[3]), "l"(descB), "r"(scaleD));
}
__device__ __forceinline__ void wgmma_rs_n128(float (&d)[64], const uint32_t (&a)[4], uint64_t descB, int scaleD) {
  asm volatile("{\n.reg .pred p;\nsetp.ne.b32 p, %69, 0;\n"
    "wgmma.mma_async.sync.aligned.m64n128k16.f32.bf16.bf16 {%0,%1,%2,%3,%4,%5,%6,%7,%8,%9,%10,%11,%12,%13,%14,%15,%16,%17,%18,%19,%20,%21,%22,%23,%24,%25,%26,%27,%28,%29,%30,%31,%32,%33,%34,%35,%36,%37,%38,%39,%40,%41,%42,%43,%44,%45,%46,%47,%48,%49,%50,%51,%52,%53,%54,%55,%56,%57,%58,%59,%60,%61,%62,%63}, {%64,%65,%66,%67}, %68, p, 1, 1, 1;\n}\n"
    : "+f"(d[0]),"+f"(d[1]),"+f"(d[2]),"+f"(d[3]),"+f"(d[4]),"+f"(d[5]),"+f"(d[6]),"+f"(d[7]),"+f"(d[8]),"+f"(d[9]),"+f"(d[10]),"+f"(d[11]),"+f"(d[12]),"+f"(d[13]),"+f"(d[14]),"+f"(d[15]),"+f"(d[16]),"+f"(d[17]),"+f"(d[18]),"+f"(d[19]),"+f"(d[20]),"+f"(d[21]),"+f"(d[22]),"+f"(d[23]),"+f"(d[24]),"+f"(d[25]),"+f"(d[26]),"+f"(d[27]),"+f"(d[28]),"+f"(d[29]),"+f"(d[30]),"+f"(d[31]),"+f"(d[32]),"+f"(d[33]),"+f"(d[34]),"+f"(d[35]),"+f"(d[36]),"+f"(d[37]),"+f"(d[38]),"+f"(d[39]),"+f"(d[40]),"+f"(d[41]),"+f"(d[42]),"+f"(d[43]),"+f"(d[44]),"+f"(d[45]),"+f"(d[46]),"+f"(d[47]),"+f"(d[48]),"+f"(d[49]),"+f"(d[50]),"+f"(d[51]),"+f"(d[52]),"+f"(d[53]),"+f"(d[54]),"+f"(d[55]),"+f"(d[56]),"+f"(d[57]),"+f"(d[58]),"+f"(d[59]),"+f"(d[60]),"+f"(d[61]),"+f"(d[62]),"+f"(d[63])
    : "r"(a[0]), "r"(a[1]), "r"(a[2]), "r"(a[3]), "l"(descB), "r"(scaleD));
}
__device__ __forceinline__ void wgmma_rs_n176(float (&d)[88], const uint32_t (&a)[4], uint64_t descB, int scaleD) {
  asm volatile("{\n.reg .pred p;\nsetp.ne.b32 p, %93, 0;\n"
    "wgmma.mma_async.sync.aligned.m64n176k16.f32.bf16.bf16 {%0,%1,%2,%3,%4,%5,%6,%7,%8,%9,%10,%11,%12,%13,%14,%15,%16,%17,%18,%19,%20,%21,%22,%23,%24,%25,%26,%27,%28,%29,%30,%31,%32,%33,%34,%35,%36,%37,%38,%39,%40,%41,%42,%43,%44,%45,%46,%47,%48,%49,%50,%51,%52,%53,%54,%55,%56,%57,%58,%59,%60,%61,%62,%63,%64,%65,%66,%67,%68,%69,%70,%71,%72,%73,%74,%75,%76,%77,%78,%79,%80,%81,%82,%83,%84,%85,%86,%87}, {%88,%89,%90,%91}, %92, p, 1, 1, 1;\n}\n"
    : "+f"(d[0]),"+f"(d[1]),"+f"(d[2]),"+f"(d[3]),"+f"(d[4]),"+f"(d[5]),"+f"(d[6]),"+f"(d[7]),"+f"(d[8]),"+f"(d[9]),"+f"(d[10]),"+f"(d[11]),"+f"(d[12]),"+f"(d[13]),"+f"(d[14]),"+f"(d[15]),"+f"(d[16]),"+f"(d[17]),"+f"(d[18]),"+f"(d[19]),"+f"(d[20]),"+f"(d[21]),"+f"(d[22]),"+f"(d[23]),"+f"(d[24]),"+f"(d[25]),"+f"(d[26]),"+f"(d[27]),"+f"(d[28]),"+f"(d[29]),"+f"(d[30]),"+f"(d[31]),"+f"(d[32]),"+f"(d[33]),"+f"(d[34]),"+f"(d[35]),"+f"(d[36]),"+f"(d[37]),"+f"(d[38]),"+f"(d[39]),"+f"(d[40]),"+f"(d[41]),"+f"(d[42]),"+f"(d[43]),"+f"(d[44]),"+f"(d[45]),"+f"(d[46]),"+f"(d[47]),"+f"(d[48]),"+f"(d[49]),"+f"(d[50]),"+f"(d[51]),"+f"(d[52]),"+f"(d[53]),"+f"(d[54]),"+f"(d[55]),"+f"(d[56]),"+f"(d[57]),"+f"(d[58]),"+f"(d[59]),"+f"(d[60]),"+f"(d[61]),"+f"(d[62]),"+f"(d[63]),"+f"(d[64]),"+f"(d[65]),"+f"(d[66]),"+f"(d[67]),"+f"(d[68]),"+f"(d[69]),"+f"(d[70]),"+f"(d[71]),"+f"(d[72]),"+f"(d[73]),"+f"(d[74]),"+f"(d[75]),"+f"(d[76]),"+f"(d[77]),"+f"(d[78]),"+f"(d[79]),"+f"(d[80]),"+f"(d[81]),"+f"(d[82]),"+f"(d[83]),"+f"(d[84]),"+f"(d[85]),"+f"(d[86]),"+f"(d[87])
    : "r"(a[0]), "r"(a[1]), "r"(a[2]), "r"(a[3]), "l"(descB), "r"(scaleD));
}
__device__ __forceinline__ void wgmma_ss_n72_t11(float (&d)[36], uint64_t descA, uint64_t descB, int scaleD) {
  asm volatile("{\n.reg .pred p;\nsetp.ne.b32 p, %38, 0;\n"
    "wgmma.mma_async.sync.aligned.m64n72k16.f32.bf16.bf16 {%0,%1,%2,%3,%4,%5,%6,%7,%8,%9,%10,%11,%12,%13,%14,%15,%16,%17,%18,%19,%20,%21,%22,%23,%24,%25,%26,%27,%28,%29,%30,%31,%32,%33,%34,%35}, %36, %37, p, 1, 1, 1, 1;\n}\n"
    : "+f"(d[0]),"+f"(d[1]),"+f"(d[2]),"+f"(d[3]),"+f"(d[4]),"+f"(d[5]),"+f"(d[6]),"+f"(d[7]),"+f"(d[8]),"+f"(d[9]),"+f"(d[10]),"+f"(d[11]),"+f"(d[12]),"+f"(d[13]),"+f"(d[14]),"+f"(d[15]),"+f"(d[16]),"+f"(d[17]),"+f"(d[18]),"+f"(d[19]),"+f"(d[20]),"+f"(d[21]),"+f"(d[22]),"+f"(d[23]),"+f"(d[24]),"+f"(d[25]),"+f"(d[26]),"+f"(d[27]),"+f"(d[28]),"+f"(d[29]),"+f"(d[30]),"+f"(d[31]),"+f"(d[32]),"+f"(d[33]),"+f"(d[34]),"+f"(d[35])
    : "l"(descA), "l"(descB), "r"(scaleD));
}

#define TSTAMP(i) do {} while (0)

constexpr float LOG2E = 1.4426950408889634f;

__device__ __forceinline__ void feat_exp(const float (&p0)[4], const float (&p1)[4], float (&e)[16]) {
  uint32_t P0 = pack2(p0[0], p0[1]), P1 = pack2(p0[2], p0[3]), P2 = pack2(p1[0], p1[1]), P3 = pack2(p1[2], p1[3]);
  uint32_t a = hmax2(P0, P2), b = hmax2(P1, P3);
  uint32_t mx = hmax2(__byte_perm(a, b, 0x5410), __byte_perm(a, b, 0x7632));
  a = hmin2(P0, P2); b = hmin2(P1, P3);
  uint32_t mn = hmin2(__byte_perm(a, b, 0x5410), __byte_perm(a, b, 0x7632));
  mx = hmax2(mx, __shfl_xor_sync(0xffffffffu, mx, 1));
  mn = hmin2(mn, __shfl_xor_sync(0xffffffffu, mn, 1));
  mx = hmax2(mx, __shfl_xor_sync(0xffffffffu, mx, 2));
  mn = hmin2(mn, __shfl_xor_sync(0xffffffffu, mn, 2));
  float mx0 = -blo(mx) * LOG2E, mx1 = -bhi(mx) * LOG2E, mn0 = blo(mn) * LOG2E, mn1 = bhi(mn) * LOG2E;
  float v[8] = {blo(P0), bhi(P0), blo(P1), bhi(P1), blo(P2), bhi(P2), blo(P3), bhi(P3)};
#pragma unroll
  for (int i = 0; i < 8; i++) {
    bool r1 = (i >> 1) & 1;
    e[i]     = ex2(fmaf(v[i],  LOG2E, r1 ? mx1 : mx0));
    e[8 + i] = ex2(fmaf(v[i], -LOG2E, r1 ? mn1 : mn0));
  }
}

__global__ void __cluster_dims__(2, 1, 1) __launch_bounds__(384, 1)
fused_kernel(const __grid_constant__ Maps maps, const __nv_bfloat16* __restrict__ x, const __nv_bfloat16* __restrict__ wphi,
             const __nv_bfloat16* __restrict__ wo, const __nv_bfloat16* __restrict__ wg_, const __nv_bfloat16* __restrict__ wu_,
             const __nv_bfloat16* __restrict__ wd_, __nv_bfloat16* __restrict__ out) {
  extern __shared__ __align__(1024) unsigned char smem[];
  const uint32_t sb = smem_u32(smem);
  const int tid = threadIdx.x, warp = tid >> 5, lane = tid & 31;
  const uint32_t rank = blockIdx.x & 1;
  const int cl = blockIdx.x >> 1;
  const int grp = cl & 7, mem = cl >> 3;
  const int rb = 2 * grp + (mem >> 2), hp = mem & 3;
  const int hg = 2 * hp + rank;
  const int rh2 = 2 * rb + rank, cq = hp;
  const int rb3 = 2 * grp + rank, jf = mem;

  if (tid < NSTAGE) {
    mbar_init(sb + SM_FULL + tid * 8, 1);
    mbar_init(sb + SM_EMPTY + tid * 8, st_empty_cnt(tid));
    mbar_expect_tx(sb + SM_FULL + tid * 8, st_bytes(tid));
  } else if (tid == NSTAGE) {
    mbar_init(sb + SM_MISCB, 3);
    mbar_init(sb + SM_KVB, 3);
  }
  asm volatile("fence.mbarrier_init.release.cluster;" ::: "memory");
  __syncthreads();
  asm volatile("barrier.cluster.arrive.relaxed.aligned;" ::: "memory");

  if (warp >= 8) {
    asm volatile("setmaxnreg.dec.sync.aligned.u32 24;");
    if (warp == 8) {
      asm volatile("barrier.cluster.wait.aligned;" ::: "memory");
      if (lane == 0) {
        const CUtensorMap* mg = jf == 7 ? &maps.g7 : &maps.g;
        const CUtensorMap* mu = jf == 7 ? &maps.u7 : &maps.u;
        const int jc = jf == 7 ? 0 : jf;
#pragma unroll
        for (int s = 0; s < NSTAGE; s++) {
          if (st_is_scr(s)) continue;
          if (st_is_mc(s) && st_issuer(s) != (int)rank) continue;
          if (s >= NSLOT) mbar_wait(sb + SM_EMPTY + (s - NSLOT) * 8);
          const uint32_t dst = sb + (s % NSLOT) * SLOT, bar = sb + SM_FULL + s * 8;
          if (st_is_x(s)) {
            const int w = s >= ST_X1 ? 1 : 0, p = s - (w ? ST_X1 : ST_X0);
            tma3d_mc(dst, &maps.x, 0, rb * 128 + w * 64, 3 * p, bar);
          } else if (s < ST_WO) {
            const int part = s < ST_X1 ? 1 : (s < ST_WQ ? 2 : 0);
            const int i = s < ST_X1 ? s - ST_WK : (s < ST_WQ ? s - ST_WV : s - ST_WQ);
            tma2d(dst, &maps.w, part * 512 + hg * 64, i * 192, bar);
          } else if (s < ST_GU) {
            const int i = s - ST_WO, w = i & 1, p = i >> 1;
            tma3d_mc(dst, p < 2 ? &maps.wo96 : &maps.wo64, 0, w * 256 + p * 96, cq * 2, bar);
          } else if (s < ST_D) {
            const int i = s - ST_GU, c = i >> 1;
            const CUtensorMap* m = (i & 1) ? mu : mg;
#pragma unroll
            for (int b = 0; b < 3; b++) tma3d_mc(dst + b * 8192, m, b * 64, jc, c * 64, bar);
          } else {
            const int c = (jf + 1 + (s - ST_D)) & 7;
            tma2d_mc(dst, &maps.d, c * 64, jf * 176, bar);
          }
        }
      }
      __syncwarp();
    } else {
      const int ht = tid - 288;
      if (ht == 0) {
        unsigned old = atomicAdd(&g_start, 1u);
        *reinterpret_cast<volatile unsigned*>(smem + SM_EPOCH) = old / NCTA;
      }
      for (int i = ht; i < 128; i += 96) {
        reinterpret_cast<uint4*>(smem + SM_ONES)[i] = make_uint4(0x3F803F80u, 0x3F803F80u, 0x3F803F80u, 0x3F803F80u);
        reinterpret_cast<uint4*>(smem + SM_WPHI)[i] = __ldg(reinterpret_cast<const uint4*>(wphi + hg * 1024) + i);
      }
      fence_async_smem();
      __syncwarp();
      if (lane == 0) mbar_arrive(sb + SM_MISCB);
      asm volatile("barrier.cluster.wait.aligned;" ::: "memory");
      mbar_wait(sb + SM_MISCB);
      const unsigned epoch = *reinterpret_cast<volatile unsigned*>(smem + SM_EPOCH);
      const int par = epoch & 1;
      for (int i = ht; i < 136; i += 96) {
        if (i < 128) g_kv[par ^ 1][blockIdx.x * 128 + i] = 0.f;
        else g_z[par ^ 1][blockIdx.x * 8 + (i - 128)] = 0.f;
      }
      if (warp == 11) {
        mbar_wait(sb + SM_FULL + (ST_X1 + 2) * 8);
        if (lane < 4) {
          const char* p; uint32_t n;
          if (lane == 0) { p = (const char*)wo + blockIdx.x * 4096; n = 4096; }
          else { p = (const char*)(lane == 1 ? wg_ : lane == 2 ? wu_ : wd_) + blockIdx.x * 11008; n = 11008; }
          asm volatile("cp.async.bulk.prefetch.L2.global [%0], %1;" ::"l"(p), "r"(n) : "memory");
        }
        __syncwarp();
      } else {
        bar_sync(6 + (warp - 9), 160);
        if (lane == 0) {
          asm volatile("fence.acq_rel.gpu;" ::: "memory");
          asm volatile("red.relaxed.gpu.global.add.u32 [%0], 1;" ::"l"(&g_kvcnt[hg * 32]) : "memory");
        }
        __syncwarp();
      }
      if (lane == 0) {
        const unsigned target = (epoch + 1) * 32;
        unsigned v; int it = 0;
        do {
          asm volatile("ld.acquire.gpu.global.u32 %0, [%1];" : "=r"(v) : "l"(&g_kvcnt[hg * 32]) : "memory");
          if (++it > (1 << 18)) break;
        } while ((int)(v - target) < 0);
      }
      __syncwarp();
      {
        const float4* src = reinterpret_cast<const float4*>(&g_kv[par][hg * 2048]);
        float4 v[6];
#pragma unroll
        for (int i = 0; i < 6; i++) {
          int idx = ht + i * 96;
          if (idx < 512) v[i] = __ldcg(src + idx);
        }
        float z0 = __ldcg(&g_z[par][hg * 128 + ht]);
        float z1 = ht < 32 ? __ldcg(&g_z[par][hg * 128 + 96 + ht]) : 0.f;
#pragma unroll
        for (int i = 0; i < 6; i++) {
          int idx = ht + i * 96;
          if (idx < 512)
            *reinterpret_cast<uint2*>(smem + SM_KVS + (idx >> 2) * 48 + (idx & 3) * 8) =
                make_uint2(pack2(v[i].x, v[i].y), pack2(v[i].z, v[i].w));
        }
        uint32_t zz = pack2(z0, 1.0f);
        *reinterpret_cast<uint4*>(smem + SM_KVS + ht * 48 + 32) = make_uint4(zz, zz, zz, zz);
        if (ht < 32) {
          zz = pack2(z1, 1.0f);
          *reinterpret_cast<uint4*>(smem + SM_KVS + (96 + ht) * 48 + 32) = make_uint4(zz, zz, zz, zz);
        }
      }
      __syncwarp();
      if (lane == 0) mbar_arrive(sb + SM_KVB);
    }
    asm volatile("barrier.cluster.arrive.relaxed.aligned;" ::: "memory");
    asm volatile("barrier.cluster.wait.aligned;" ::: "memory");
  } else {
    asm volatile("setmaxnreg.inc.sync.aligned.u32 240;");
    asm volatile("barrier.cluster.wait.aligned;" ::: "memory");
    const int wg = warp >> 2, wq = warp & 3, g = lane >> 2, t = lane & 3;
    const bool lead = (tid & 127) == 0;
    auto release = [&](int d) {
      if (d + NSLOT < NSTAGE) {
        if (st_is_mc(d + NSLOT)) mbar_arrive_cluster(sb + SM_EMPTY + d * 8, st_issuer(d + NSLOT));
        else mbar_arrive(sb + SM_EMPTY + d * 8);
      }
    };
    const uint32_t lrow = (uint32_t)(wq * 16 + (lane & 7) + ((lane >> 3) & 1) * 8) * 128;
    const uint32_t lx = lane & 7, lhi = lane >> 4;
    if (wg == 1) bar_arrive(4, 256);
    TSTAMP(0);

    float r0, r1;
    uint32_t E[4][8];
    int par;
    {
      uint32_t A[32][4];
      float s0 = 0.f, s1 = 0.f, q0 = 0.f, q1 = 0.f;
#pragma unroll
      for (int p = 0; p < 3; p++) {
        const int sA = ST_X0 + p, sB = ST_X1 + p;
        mbar_wait(sb + SM_FULL + (wg ? sB : sA) * 8);
        const uint32_t base = sb + (wg ? (sB % NSLOT) : (sA % NSLOT)) * SLOT + lrow;
#pragma unroll
        for (int cc = 0; cc < (p < 2 ? 3 : 2); cc++)
#pragma unroll
          for (int kk = 0; kk < 4; kk++) ldsm4(A[(3 * p + cc) * 4 + kk], base + cc * 8192 + (((2 * kk + lhi) ^ lx) << 4));
        __syncwarp();
        if (lane == 0) { if (wg) release(sB); else release(sA); }
#pragma unroll
        for (int i = 0; i < (p < 2 ? 12 : 8); i++) {
          const int ks = 12 * p + i;
          float a = blo(A[ks][0]), b = bhi(A[ks][0]), c = blo(A[ks][2]), d = bhi(A[ks][2]);
          s0 += (a + b) + (c + d);
          q0 = fmaf(a, a, q0); q0 = fmaf(b, b, q0); q0 = fmaf(c, c, q0); q0 = fmaf(d, d, q0);
          a = blo(A[ks][1]); b = bhi(A[ks][1]); c = blo(A[ks][3]); d = bhi(A[ks][3]);
          s1 += (a + b) + (c + d);
          q1 = fmaf(a, a, q1); q1 = fmaf(b, b, q1); q1 = fmaf(c, c, q1); q1 = fmaf(d, d, q1);
        }
      }
      s0 += __shfl_xor_sync(0xffffffffu, s0, 1); s1 += __shfl_xor_sync(0xffffffffu, s1, 1);
      q0 += __shfl_xor_sync(0xffffffffu, q0, 1); q1 += __shfl_xor_sync(0xffffffffu, q1, 1);
      s0 += __shfl_xor_sync(0xffffffffu, s0, 2); s1 += __shfl_xor_sync(0xffffffffu, s1, 2);
      q0 += __shfl_xor_sync(0xffffffffu, q0, 2); q1 += __shfl_xor_sync(0xffffffffu, q1, 2);
      s0 *= (1.f / 512.f); s1 *= (1.f / 512.f);
      r0 = rsqrtf(fmaxf(q0 * (1.f / 512.f) - s0 * s0, 0.f) + 1e-5f);
      r1 = rsqrtf(fmaxf(q1 * (1.f / 512.f) - s1 * s1, 0.f) + 1e-5f);
      const uint32_t m0 = pack2(s0, s0), m1 = pack2(s1, s1);
#pragma unroll
      for (int ks = 0; ks < 32; ks++) {
        A[ks][0] = hsub2(A[ks][0], m0); A[ks][1] = hsub2(A[ks][1], m1);
        A[ks][2] = hsub2(A[ks][2], m0); A[ks][3] = hsub2(A[ks][3], m1);
      }
      TSTAMP(1);

      float acc[32];
      auto pass = [&](int st0, bool hand_over) {
        bar_sync(4 + wg, 256);
#pragma unroll
        for (int i = 0; i < 3; i++) {
          mbar_wait(sb + SM_FULL + (st0 + i) * 8);
          const uint32_t base = sb + ((st0 + i) % NSLOT) * SLOT;
          wg_fence();
#pragma unroll
          for (int kk = 0; kk < (i < 2 ? 12 : 8); kk++)
            wgmma_rs_n64(acc, A[12 * i + kk], mk_desc(base + kk * 2048, 8192, 1024), (i | kk) != 0);
          wg_commit();
          if (i > 0) { wg_wait<1>(); if (lead) release(st0 + i - 1); }
        }
        if (hand_over) bar_arrive(4 + (wg ^ 1), 256);
        wg_wait<0>();
        if (lead) release(st0 + 2);
      };
      auto project = [&](float (&pp)[4][2][4]) {
#pragma unroll
        for (int h = 0; h < 4; h++) {
          uint32_t a[4] = {pack2(acc[8 * h + 0] * r0, acc[8 * h + 1] * r0), pack2(acc[8 * h + 2] * r1, acc[8 * h + 3] * r1),
                           pack2(acc[8 * h + 4] * r0, acc[8 * h + 5] * r0), pack2(acc[8 * h + 6] * r1, acc[8 * h + 7] * r1)};
          uint32_t b[4];
          ldsm4t(b, sb + SM_WPHI + h * 512 + ((lane & 7) + ((lane >> 3) & 1) * 8) * 32 + lhi * 16);
#pragma unroll
          for (int i = 0; i < 4; i++) { pp[h][0][i] = 0.f; pp[h][1][i] = 0.f; }
          mma16816(pp[h][0], a, b[0], b[1]);
          mma16816(pp[h][1], a, b[2], b[3]);
        }
      };

      pass(ST_WK, true);
      TSTAMP(2);
      mbar_wait(sb + SM_MISCB);
      par = *reinterpret_cast<volatile unsigned*>(smem + SM_EPOCH) & 1;
      const uint32_t scr = sb + (wg ? (ST_SCR1 % NSLOT) : (ST_SCR0 % NSLOT)) * SLOT;
      {
        float pp[4][2][4];
        project(pp);
        mbar_wait(sb + SM_EMPTY + (wg ? ST_SCR1 - NSLOT : ST_SCR0 - NSLOT) * 8);
#pragma unroll
        for (int h = 0; h < 4; h++) {
          float e[16];
          feat_exp(pp[h][0], pp[h][1], e);
          float sp0 = (e[0] + e[1]) + (e[4] + e[5]), sp1 = (e[2] + e[3]) + (e[6] + e[7]);
          float sn0 = (e[8] + e[9]) + (e[12] + e[13]), sn1 = (e[10] + e[11]) + (e[14] + e[15]);
          sp0 += __shfl_xor_sync(0xffffffffu, sp0, 1); sp1 += __shfl_xor_sync(0xffffffffu, sp1, 1);
          sn0 += __shfl_xor_sync(0xffffffffu, sn0, 1); sn1 += __shfl_xor_sync(0xffffffffu, sn1, 1);
          sp0 += __shfl_xor_sync(0xffffffffu, sp0, 2); sp1 += __shfl_xor_sync(0xffffffffu, sp1, 2);
          sn0 += __shfl_xor_sync(0xffffffffu, sn0, 2); sn1 += __shfl_xor_sync(0xffffffffu, sn1, 2);
          sp0 = rcp(sp0); sp1 = rcp(sp1); sn0 = rcp(sn0); sn1 = rcp(sn1);
          const uint32_t dst = scr + (h >> 1) * 8192 + lrow;
          stsm4(dst + ((((h & 1) * 4 + lhi) ^ lx) << 4), pack2(e[0] * sp0, e[1] * sp0), pack2(e[2] * sp1, e[3] * sp1),
                pack2(e[4] * sp0, e[5] * sp0), pack2(e[6] * sp1, e[7] * sp1));
          stsm4(dst + ((((h & 1) * 4 + 2 + lhi) ^ lx) << 4), pack2(e[8] * sn0, e[9] * sn0), pack2(e[10] * sn1, e[11] * sn1),
                pack2(e[12] * sn0, e[13] * sn0), pack2(e[14] * sn1, e[15] * sn1));
        }
      }
      TSTAMP(3);
      pass(ST_WV, true);
      TSTAMP(4);
      {
#pragma unroll
        for (int h = 0; h < 4; h++)
          stsm4(scr + 16384 + lrow + (((2 * h + lhi) ^ lx) << 4),
                pack2(acc[8 * h + 0] * r0, acc[8 * h + 1] * r0), pack2(acc[8 * h + 2] * r1, acc[8 * h + 3] * r1),
                pack2(acc[8 * h + 4] * r0, acc[8 * h + 5] * r0), pack2(acc[8 * h + 6] * r1, acc[8 * h + 7] * r1));
        fence_async_smem();
        bar_sync(1 + wg, 128);
        float kv0[36], kv1[36];
        wg_fence();
#pragma unroll
        for (int ks = 0; ks < 4; ks++) {
          const uint32_t vb = scr + 16384 + ks * 2048;
          const uint64_t db = mk_desc(vb, sb + SM_ONES - vb, 1024);
          wgmma_ss_n72_t11(kv0, mk_desc(scr + ks * 2048, 8192, 1024), db, ks != 0);
          wgmma_ss_n72_t11(kv1, mk_desc(scr + 8192 + ks * 2048, 8192, 1024), db, ks != 0);
        }
        wg_commit();
        wg_wait<0>();
        if (lead) { if (wg) release(ST_SCR1); else release(ST_SCR0); }
        const bool up = wq >= 2;
        const int f = (wq & 1) * 16 + g;
        float* kvp = &g_kv[par][((hg * 4 + (wq >> 1)) * 32 + f) * 16 + 2 * t];
        float* zp = &g_z[par][(hg * 4 + (wq >> 1)) * 32 + f];
#pragma unroll
        for (int b = 0; b < 2; b++) {
#pragma unroll
          for (int n = 0; n < 2; n++) {
            float c0, c1, c2, c3;
            if (b == 0) {
              c0 = up ? kv0[8 + 4 * n + 0] : kv0[4 * n + 0]; c1 = up ? kv0[8 + 4 * n + 1] : kv0[4 * n + 1];
              c2 = up ? kv0[8 + 4 * n + 2] : kv0[4 * n + 2]; c3 = up ? kv0[8 + 4 * n + 3] : kv0[4 * n + 3];
            } else {
              c0 = up ? kv1[24 + 4 * n + 0] : kv1[16 + 4 * n + 0]; c1 = up ? kv1[24 + 4 * n + 1] : kv1[16 + 4 * n + 1];
              c2 = up ? kv1[24 + 4 * n + 2] : kv1[16 + 4 * n + 2]; c3 = up ? kv1[24 + 4 * n + 3] : kv1[16 + 4 * n + 3];
            }
            float* p = kvp + b * 1024 + n * 8;
            asm volatile("red.relaxed.gpu.global.add.v2.f32 [%0], {%1,%2};" ::"l"(p), "f"(c0), "f"(c1) : "memory");
            asm volatile("red.relaxed.gpu.global.add.v2.f32 [%0], {%1,%2};" ::"l"(p + 128), "f"(c2), "f"(c3) : "memory");
          }
          if (t == 0) {
            asm volatile("red.relaxed.gpu.global.add.f32 [%0], %1;" ::"l"(zp + b * 64), "f"(b ? kv1[32] : kv0[32]) : "memory");
            asm volatile("red.relaxed.gpu.global.add.f32 [%0], %1;" ::"l"(zp + b * 64 + 8), "f"(b ? kv1[34] : kv0[34]) : "memory");
          }
        }
        bar_arrive(6 + wg, 160);
      }
      TSTAMP(5);
      pass(ST_WQ, wg == 0);
      TSTAMP(6);
      {
        float pp[4][2][4];
        project(pp);
#pragma unroll
        for (int h = 0; h < 4; h++) {
          float e[16];
          feat_exp(pp[h][0], pp[h][1], e);
#pragma unroll
          for (int i = 0; i < 8; i++) E[h][i] = pack2(e[2 * i], e[2 * i + 1]);
        }
      }
    }
    TSTAMP(7);
    uint32_t xr[16];
    {
      const uint32_t* xp = reinterpret_cast<const uint32_t*>(x + (size_t)(rh2 * 64 + wq * 16 + g) * 512 + cq * 128 + wg * 64 + 2 * t);
#pragma unroll
      for (int i = 0; i < 8; i++) { xr[2 * i] = __ldg(xp + 4 * i); xr[2 * i + 1] = __ldg(xp + 8 * 256 + 4 * i); }
    }
    mbar_wait(sb + SM_KVB);
    TSTAMP(8);
    {
      uint4* op = &g_o[par][2 * rb + wg][hg][wq][0][lane];
      uint4* oz = &g_o[par ^ 1][2 * rb + wg][hg][wq][0][lane];
#pragma unroll
      for (int h = 0; h < 4; h++) {
        uint32_t b0[4], b1[4], b2[4];
        const uint32_t kb = sb + SM_KVS + (h * 32 + lane) * 48;
        ldsm4t(b0, kb); ldsm4t(b1, kb + 16); ldsm4t(b2, kb + 32);
        const uint32_t ep[4] = {E[h][0], E[h][1], E[h][2], E[h][3]}, en[4] = {E[h][4], E[h][5], E[h][6], E[h][7]};
        float np0[4] = {0, 0, 0, 0}, np1[4] = {0, 0, 0, 0}, nn0[4] = {0, 0, 0, 0}, nn1[4] = {0, 0, 0, 0}, dp[4] = {0, 0, 0, 0}, dn[4] = {0, 0, 0, 0};
        mma16816(dp, ep, b2[0], b2[1]);  mma16816(dn, en, b2[2], b2[3]);
        mma16816(np0, ep, b0[0], b0[1]); mma16816(nn0, en, b0[2], b0[3]);
        mma16816(np1, ep, b1[0], b1[1]); mma16816(nn1, en, b1[2], b1[3]);
        const float i0 = rcp(fmaf(dp[0], dn[1], fmaf(dn[0], dp[1], 1e-6f * dp[1] * dn[1])));
        const float i1 = rcp(fmaf(dp[2], dn[3], fmaf(dn[2], dp[3], 1e-6f * dp[3] * dn[3])));
        const float cp0 = dn[1] * i0, cn0 = dp[1] * i0, cp1 = dn[3] * i1, cn1 = dp[3] * i1;
        st_rlx4(op + h * 32,
                nz(pack2(fmaf(np0[0], cp0, nn0[0] * cn0), fmaf(np0[1], cp0, nn0[1] * cn0))),
                nz(pack2(fmaf(np0[2], cp1, nn0[2] * cn1), fmaf(np0[3], cp1, nn0[3] * cn1))),
                nz(pack2(fmaf(np1[0], cp0, nn1[0] * cn0), fmaf(np1[1], cp0, nn1[1] * cn0))),
                nz(pack2(fmaf(np1[2], cp1, nn1[2] * cn1), fmaf(np1[3], cp1, nn1[3] * cn1))));
      }
#pragma unroll
      for (int h = 0; h < 4; h++) st_rlx4(oz + h * 32, 0, 0, 0, 0);
    }
    TSTAMP(9);

    {
      uint32_t A[4][4][4];
      const uint4* op = &g_o[par][rh2][wg * 4][wq][0][lane];
#pragma unroll
      for (int c = 0; c < 4; c++) ld_chunk(A[c], op + c * 512);
      float acc[64];
#pragma unroll
      for (int c = 0; c < 4; c++) {
        chk_chunk(A[c], op + c * 512);
#pragma unroll
        for (int s = 0; s < 4; s++) {
          const int ks = 4 * c + s, p = ks / 6, kk = ks - 6 * p;
          const int sA = ST_WO + 2 * p, sB = sA + 1;
          if (kk == 0) mbar_wait(sb + SM_FULL + (wg ? sB : sA) * 8);
          if (s == 0 || kk == 0) wg_fence();
          const uint32_t base = sb + (wg ? (sB % NSLOT) : (sA % NSLOT)) * SLOT;
          wgmma_rs_n128(acc, A[c][s], mk_desc(base + kk * 2048, p < 2 ? 12288 : 8192, 1024), ks != 0);
        }
        wg_commit();
      }
      wg_wait<0>();
      if (lead) {
        if (wg) { release(ST_WO + 1); release(ST_WO + 3); } else { release(ST_WO); release(ST_WO + 2); }
      }
      TSTAMP(10);
      bar_sync(1 + wg, 128);
      float4* ex_w = reinterpret_cast<float4*>(smem + (wg ? ((ST_WO + 5) % NSLOT) : ((ST_WO + 4) % NSLOT)) * SLOT) + (tid & 127);
      const float4* ex_r = reinterpret_cast<const float4*>(smem + (wg ? ((ST_WO + 4) % NSLOT) : ((ST_WO + 5) % NSLOT)) * SLOT) + (tid & 127);
#pragma unroll
      for (int i = 0; i < 8; i++)
        ex_w[i * 128] = wg ? make_float4(acc[4 * i], acc[4 * i + 1], acc[4 * i + 2], acc[4 * i + 3])
                           : make_float4(acc[32 + 4 * i], acc[32 + 4 * i + 1], acc[32 + 4 * i + 2], acc[32 + 4 * i + 3]);
      fence_async_smem();
      bar_sync(3, 256);
      uint32_t hw[16];
      float s0 = 0.f, s1 = 0.f, q0 = 0.f, q1 = 0.f;
#pragma unroll
      for (int i = 0; i < 8; i++) {
        const float4 o = ex_r[i * 128];
        const float a0 = (wg ? acc[32 + 4 * i] : acc[4 * i]) + o.x, a1 = (wg ? acc[32 + 4 * i + 1] : acc[4 * i + 1]) + o.y;
        const float a2 = (wg ? acc[32 + 4 * i + 2] : acc[4 * i + 2]) + o.z, a3 = (wg ? acc[32 + 4 * i + 3] : acc[4 * i + 3]) + o.w;
        hw[2 * i]     = pack2(blo(xr[2 * i]) + a0, bhi(xr[2 * i]) + a1);
        hw[2 * i + 1] = pack2(blo(xr[2 * i + 1]) + a2, bhi(xr[2 * i + 1]) + a3);
      }
      const int ch = cq * 2 + wg;
      uint4* hp_ = &g_h[par][rh2][ch][wq][0][lane];
#pragma unroll
      for (int s = 0; s < 4; s++) st_rlx4(hp_ + s * 32, nz(hw[4 * s]), nz(hw[4 * s + 1]), nz(hw[4 * s + 2]), nz(hw[4 * s + 3]));
#pragma unroll
      for (int i = 0; i < 8; i++) {
        float a = blo(hw[2 * i]), b = bhi(hw[2 * i]);
        s0 += a + b; q0 = fmaf(a, a, q0); q0 = fmaf(b, b, q0);
        a = blo(hw[2 * i + 1]); b = bhi(hw[2 * i + 1]);
        s1 += a + b; q1 = fmaf(a, a, q1); q1 = fmaf(b, b, q1);
      }
      s0 += __shfl_xor_sync(0xffffffffu, s0, 1); s1 += __shfl_xor_sync(0xffffffffu, s1, 1);
      q0 += __shfl_xor_sync(0xffffffffu, q0, 1); q1 += __shfl_xor_sync(0xffffffffu, q1, 1);
      s0 += __shfl_xor_sync(0xffffffffu, s0, 2); s1 += __shfl_xor_sync(0xffffffffu, s1, 2);
      q0 += __shfl_xor_sync(0xffffffffu, q0, 2); q1 += __shfl_xor_sync(0xffffffffu, q1, 2);
      {
        const int row = rh2 * 64 + wq * 16 + g + (t & 1) * 8;
        if (t < 2) st_rlx2(&g_st[par][row][ch], nz(__float_as_uint(t ? s1 : s0)), nz(__float_as_uint(t ? q1 : q0)));
        else st_rlx2(&g_st[par ^ 1][row][ch], 0, 0);
      }
      uint4* hz = &g_h[par ^ 1][rh2][ch][wq][0][lane];
#pragma unroll
      for (int s = 0; s < 4; s++) st_rlx4(hz + s * 32, 0, 0, 0, 0);
      fence_async_smem();
      bar_sync(1 + wg, 128);
      if (lead) { if (wg) release(ST_WO + 4); else release(ST_WO + 5); }
    }
    TSTAMP(11);

    const int rh3 = 2 * rb3 + wg;
    uint32_t HH[11][4];
    {
      uint32_t A[2][4][4];
      const uint4* hp_ = &g_h[par][rh3][0][wq][0][lane];
      ld_chunk(A[0], hp_);
      ld_chunk(A[1], hp_ + 512);
      uint32_t m0, m1;
      {
        const uint4* sp = reinterpret_cast<const uint4*>(&g_st[par][rh3 * 64 + wq * 16 + g][2 * t]);
        uint32_t a[4], b[4];
        int it = 0;
        do {
          ld_rlx4(a, sp); ld_rlx4(b, sp + 8 * 4);
          if (++it > (1 << 18)) break;
        } while (__any_sync(0xffffffffu, min(min4(a), min4(b)) == 0));
        float s0 = __uint_as_float(a[0]) + __uint_as_float(a[2]), q0 = __uint_as_float(a[1]) + __uint_as_float(a[3]);
        float s1 = __uint_as_float(b[0]) + __uint_as_float(b[2]), q1 = __uint_as_float(b[1]) + __uint_as_float(b[3]);
        s0 += __shfl_xor_sync(0xffffffffu, s0, 1); s1 += __shfl_xor_sync(0xffffffffu, s1, 1);
        q0 += __shfl_xor_sync(0xffffffffu, q0, 1); q1 += __shfl_xor_sync(0xffffffffu, q1, 1);
        s0 += __shfl_xor_sync(0xffffffffu, s0, 2); s1 += __shfl_xor_sync(0xffffffffu, s1, 2);
        q0 += __shfl_xor_sync(0xffffffffu, q0, 2); q1 += __shfl_xor_sync(0xffffffffu, q1, 2);
        s0 *= (1.f / 512.f); s1 *= (1.f / 512.f);
        r0 = 1.f / (fmaxf(q0 * (1.f / 512.f) - s0 * s0, 0.f) + 1e-5f);
        r1 = 1.f / (fmaxf(q1 * (1.f / 512.f) - s1 * s1, 0.f) + 1e-5f);
        m0 = pack2(s0, s0); m1 = pack2(s1, s1);
      }
      TSTAMP(12);
      float ag[88], au[88];
#pragma unroll
      for (int c = 0; c < 8; c++) {
        const int sG = ST_GU + 2 * c, sU = sG + 1;
        chk_chunk(A[c & 1], hp_ + c * 512);
#pragma unroll
        for (int s = 0; s < 4; s++) {
          A[c & 1][s][0] = hsub2(A[c & 1][s][0], m0); A[c & 1][s][1] = hsub2(A[c & 1][s][1], m1);
          A[c & 1][s][2] = hsub2(A[c & 1][s][2], m0); A[c & 1][s][3] = hsub2(A[c & 1][s][3], m1);
        }
        mbar_wait(sb + SM_FULL + sG * 8);
        wg_fence();
#pragma unroll
        for (int s = 0; s < 4; s++)
          wgmma_rs_n176(ag, A[c & 1][s], mk_desc(sb + (sG % NSLOT) * SLOT + s * 2048, 8192, 1024), (c | s) != 0);
        wg_commit();
        if (c > 0) {
          wg_wait<1>();
          if (lead) release(sG - 1);
          if (c < 7) ld_chunk(A[(c + 1) & 1], hp_ + (c + 1) * 512);
        }
        mbar_wait(sb + SM_FULL + sU * 8);
        wg_fence();
#pragma unroll
        for (int s = 0; s < 4; s++)
          wgmma_rs_n176(au, A[c & 1][s], mk_desc(sb + (sU % NSLOT) * SLOT + s * 2048, 8192, 1024), (c | s) != 0);
        wg_commit();
        wg_wait<1>();
        if (lead) release(sG);
      }
      wg_wait<0>();
      if (lead) release(ST_GU + 15);
      TSTAMP(13);
#pragma unroll
      for (int s = 0; s < 11; s++) {
        HH[s][0] = pack2(ag[8 * s + 0] * au[8 * s + 0] * r0, ag[8 * s + 1] * au[8 * s + 1] * r0);
        HH[s][1] = pack2(ag[8 * s + 2] * au[8 * s + 2] * r1, ag[8 * s + 3] * au[8 * s + 3] * r1);
        HH[s][2] = pack2(ag[8 * s + 4] * au[8 * s + 4] * r0, ag[8 * s + 5] * au[8 * s + 5] * r0);
        HH[s][3] = pack2(ag[8 * s + 6] * au[8 * s + 6] * r1, ag[8 * s + 7] * au[8 * s + 7] * r1);
      }
    }
    TSTAMP(14);

    {
      float acc[2][32], sum[32];
      uint32_t in[2][4][4];
      ld_chunk(in[0], &g_h[par][rh3][jf][wq][0][lane]);
#pragma unroll
      for (int s = 0; s < 4; s++)
#pragma unroll
        for (int r = 0; r < 4; r++) {
          sum[8 * s + (r >> 1) * 4 + (r & 1) * 2]     = blo(in[0][s][r]);
          sum[8 * s + (r >> 1) * 4 + (r & 1) * 2 + 1] = bhi(in[0][s][r]);
        }
      auto in_ptr = [&](int q) { return &g_part[rh3][jf][(jf - 1 - q) & 7][wq][0][lane]; };
      auto consume = [&](int q) {
        uint4* p = in_ptr(q);
        chk_chunk(in[q & 1], p);
#pragma unroll
        for (int s = 0; s < 4; s++) {
          st_rlx4(p + s * 32, 0, 0, 0, 0);
#pragma unroll
          for (int r = 0; r < 4; r++) {
            sum[8 * s + (r >> 1) * 4 + (r & 1) * 2]     += blo(in[q & 1][s][r]);
            sum[8 * s + (r >> 1) * 4 + (r & 1) * 2 + 1] += bhi(in[q & 1][s][r]);
          }
        }
      };
#pragma unroll
      for (int st = 0; st < 8; st++) {
        const int sD = ST_D + st;
        mbar_wait(sb + SM_FULL + sD * 8);
        wg_fence();
#pragma unroll
        for (int s = 0; s < 11; s++)
          wgmma_rs_n64(acc[st & 1], HH[s], mk_desc(sb + (sD % NSLOT) * SLOT + s * 2048, 8192, 1024), s != 0);
        wg_commit();
        if (st > 0) {
          wg_wait<1>();
          const float (&a)[32] = acc[(st - 1) & 1];
          uint4* p = &g_part[rh3][(jf + st) & 7][jf][wq][0][lane];
#pragma unroll
          for (int s = 0; s < 4; s++)
            st_rlx4(p + s * 32, nz(pack2(a[8 * s + 0], a[8 * s + 1])), nz(pack2(a[8 * s + 2], a[8 * s + 3])),
                    nz(pack2(a[8 * s + 4], a[8 * s + 5])), nz(pack2(a[8 * s + 6], a[8 * s + 7])));
        }
        if (st >= 4) consume(st - 4);
        if (st >= 3) ld_chunk(in[(st - 3) & 1], in_ptr(st - 3));
      }
      ld_chunk(in[1], in_ptr(5));
      consume(4);
      wg_wait<0>();
      TSTAMP(15);
      ld_chunk(in[0], in_ptr(6));
      consume(5);
      consume(6);
      uint32_t* op = reinterpret_cast<uint32_t*>(out + (size_t)(rh3 * 64 + wq * 16 + g) * 512 + jf * 64 + 2 * t);
#pragma unroll
      for (int i = 0; i < 8; i++) {
        op[4 * i]           = pack2(sum[4 * i] + acc[1][4 * i], sum[4 * i + 1] + acc[1][4 * i + 1]);
        op[8 * 256 + 4 * i] = pack2(sum[4 * i + 2] + acc[1][4 * i + 2], sum[4 * i + 3] + acc[1][4 * i + 3]);
      }
    }
    TSTAMP(16);
    asm volatile("barrier.cluster.arrive.relaxed.aligned;" ::: "memory");
    asm volatile("barrier.cluster.wait.aligned;" ::: "memory");
  }
}

typedef CUresult (*EncodeFn)(CUtensorMap*, CUtensorMapDataType, cuuint32_t, void*, const cuuint64_t*, const cuuint64_t*,
                             const cuuint32_t*, const cuuint32_t*, CUtensorMapInterleave, CUtensorMapSwizzle,
                             CUtensorMapL2promotion, CUtensorMapFloatOOBfill);

void encode(EncodeFn fn, CUtensorMap* m, const void* base, int rank, const cuuint64_t* dims, const cuuint64_t* strides,
            const cuuint32_t* box) {
  cuuint32_t es[3] = {1, 1, 1};
  fn(m, CU_TENSOR_MAP_DATA_TYPE_BFLOAT16, (cuuint32_t)rank, const_cast<void*>(base), dims, strides, box, es,
     CU_TENSOR_MAP_INTERLEAVE_NONE, CU_TENSOR_MAP_SWIZZLE_128B, CU_TENSOR_MAP_L2_PROMOTION_L2_256B,
     CU_TENSOR_MAP_FLOAT_OOB_FILL_NONE);
}

}

extern "C" void kernel_launch(void* const* d_in, const int* in_sizes, int n_in, void* d_out, int out_size) {
  (void)in_sizes; (void)n_in; (void)out_size;
  const __nv_bfloat16* x    = (const __nv_bfloat16*)d_in[0];
  const __nv_bfloat16* wqkv = (const __nv_bfloat16*)d_in[1];
  const __nv_bfloat16* wphi = (const __nv_bfloat16*)d_in[2];
  const __nv_bfloat16* wo   = (const __nv_bfloat16*)d_in[3];
  const __nv_bfloat16* wg   = (const __nv_bfloat16*)d_in[5];
  const __nv_bfloat16* wu   = (const __nv_bfloat16*)d_in[6];
  const __nv_bfloat16* wd   = (const __nv_bfloat16*)d_in[7];

  static EncodeFn fn = nullptr;
  if (!fn) {
    void* p = nullptr;
    cudaDriverEntryPointQueryResult qr;
    cudaGetDriverEntryPoint("cuTensorMapEncodeTiled", &p, cudaEnableDefault, &qr);
    fn = (EncodeFn)p;
    cudaFuncSetAttribute(fused_kernel, cudaFuncAttributeMaxDynamicSharedMemorySize, SM_TOTAL);
  }
  Maps maps;
  {
    cuuint64_t d[3] = {64, 2048, 8}, s[2] = {1024, 128}; cuuint32_t b[3] = {64, 64, 3};
    encode(fn, &maps.x, x, 3, d, s, b);
  }
  {
    cuuint64_t d[2] = {1536, 512}, s[1] = {3072}; cuuint32_t b[2] = {64, 192};
    encode(fn, &maps.w, wqkv, 2, d, s, b);
  }
  {
    cuuint64_t d[3] = {64, 512, 8}, s[2] = {1024, 128}; cuuint32_t b[3] = {64, 96, 2}, b2[3] = {64, 64, 2};
    encode(fn, &maps.wo96, wo, 3, d, s, b);
    encode(fn, &maps.wo64, wo, 3, d, s, b2);
  }
  {
    cuuint64_t d[3] = {176, 7, 512}, d7[3] = {144, 1, 512}, s[2] = {352, 2752}; cuuint32_t b[3] = {64, 1, 64};
    encode(fn, &maps.g, wg, 3, d, s, b);
    encode(fn, &maps.u, wu, 3, d, s, b);
    encode(fn, &maps.g7, wg + 1232, 3, d7, s, b);
    encode(fn, &maps.u7, wu + 1232, 3, d7, s, b);
  }
  {
    cuuint64_t d[2] = {512, 1376}, s[1] = {1024}; cuuint32_t b[2] = {64, 176};
    encode(fn, &maps.d, wd, 2, d, s, b);
  }
  fused_kernel<<<NCTA, 384, SM_TOTAL>>>(maps, x, wphi, wo, wg, wu, wd, (__nv_bfloat16*)d_out);
}
```

```cpp
#include <cuda_runtime.h>
#include <cuda_bf16.h>
#include <cuda.h>
#include <stdint.h>

#define PROF 0

namespace {

constexpr int NCTA   = 128;
constexpr int SLOT   = 24576;
constexpr int NSLOT  = 9;
constexpr int NSTAGE = 47;

constexpr int ST_X0   = 0;
constexpr int ST_WK   = 3;
constexpr int ST_X1   = 6;
constexpr int ST_SCR0 = 9;
constexpr int ST_WV   = 10;
constexpr int ST_SCR1 = 13;
constexpr int ST_WQ   = 14;
constexpr int ST_WO   = 17;
constexpr int ST_GU   = 23;
constexpr int ST_D    = 39;

__host__ __device__ constexpr bool st_is_x(int s)   { return (s >= 0 && s < 3) || (s >= 6 && s < 9); }
__host__ __device__ constexpr bool st_is_scr(int s) { return s == ST_SCR0 || s == ST_SCR1; }
__host__ __device__ constexpr bool st_is_mc(int s)  { return st_is_x(s) || s >= ST_WO; }
__host__ __device__ constexpr int  st_bytes(int s)  {
  return s >= ST_D ? 22528 : ((s == ST_WO + 4 || s == ST_WO + 5) ? 16384 : 24576);
}
__host__ __device__ constexpr int  st_base_cnt(int d) {
  return st_is_x(d) ? 4 : (st_is_scr(d) || (d >= ST_WO && d < ST_GU)) ? 1 : 2;
}
__host__ __device__ constexpr int  st_empty_cnt(int d) { return st_base_cnt(d) * (st_is_mc(d + NSLOT) ? 2 : 1); }

constexpr int SM_ONES = NSLOT * SLOT;
constexpr int SM_WPHI = SM_ONES + 2048;
constexpr int SM_KVS  = SM_WPHI + 2048;
constexpr int SM_BAR  = SM_KVS + 6144;
constexpr int SM_FULL  = SM_BAR;
constexpr int SM_EMPTY = SM_BAR + NSTAGE * 8;
constexpr int SM_MISCB = SM_BAR + 2 * NSTAGE * 8;
constexpr int SM_KVB   = SM_MISCB + 8;
constexpr int SM_EPOCH = SM_KVB + 8;
constexpr int SM_TOTAL = SM_BAR + 1024;

static_assert(SM_TOTAL == 232448, "smem budget");

struct Maps { CUtensorMap x, w, wo96, wo64, g, u, g7, u7, d; };

__device__ uint4    g_o[32][8][4][4][32];
__device__ uint4    g_h[32][8][4][4][32];
__device__ uint32_t g_hx[32][8][4][32];
__device__ uint2    g_st[2048][8];
__device__ uint4    g_part[32][8][8][4][4][32];
__device__ float    g_kv[2][32 * 32 * 16];
__device__ float    g_z[2][32 * 32];
__device__ unsigned g_kvcnt[8 * 32];
__device__ unsigned g_start;

__device__ __forceinline__ uint32_t smem_u32(const void* p) { return (uint32_t)__cvta_generic_to_shared(p); }
__device__ __forceinline__ void mbar_init(uint32_t bar, int cnt) {
  asm volatile("mbarrier.init.shared::cta.b64 [%0], %1;" ::"r"(bar), "r"(cnt) : "memory");
}
__device__ __forceinline__ void mbar_expect_tx(uint32_t bar, uint32_t bytes) {
  asm volatile("mbarrier.arrive.expect_tx.shared::cta.b64 _, [%0], %1;" ::"r"(bar), "r"(bytes) : "memory");
}
__device__ __forceinline__ void mbar_arrive(uint32_t bar) {
  asm volatile("mbarrier.arrive.shared::cta.b64 _, [%0];" ::"r"(bar) : "memory");
}
__device__ __forceinline__ void mbar_arrive_cluster(uint32_t bar, uint32_t rank) {
  asm volatile("{\n.reg .b32 ra;\nmapa.shared::cluster.u32 ra, %0, %1;\n"
               "mbarrier.arrive.shared::cluster.b64 _, [ra];\n}" ::"r"(bar), "r"(rank) : "memory");
}
__device__ __forceinline__ bool mbar_try(uint32_t bar) {
  uint32_t ok;
  asm volatile("{\n.reg .pred p;\nmbarrier.try_wait.parity.shared::cta.b64 p, [%1], 0;\nselp.u32 %0, 1, 0, p;\n}"
               : "=r"(ok) : "r"(bar) : "memory");
  return ok != 0;
}
__device__ __forceinline__ void mbar_wait(uint32_t bar) {
  int it = 0;
#pragma unroll 1
  while (!mbar_try(bar)) {
    if (++it > (1 << 20)) __trap();
  }
}
__device__ __forceinline__ void bar_sync(int id, int n)   { asm volatile("bar.sync %0, %1;" ::"r"(id), "r"(n) : "memory"); }
__device__ __forceinline__ void bar_arrive(int id, int n) { asm volatile("bar.arrive %0, %1;" ::"r"(id), "r"(n) : "memory"); }
__device__ __forceinline__ void fence_async_smem() { asm volatile("fence.proxy.async.shared::cta;" ::: "memory"); }
__device__ __forceinline__ void wg_fence()  { asm volatile("wgmma.fence.sync.aligned;" ::: "memory"); }
__device__ __forceinline__ void wg_commit() { asm volatile("wgmma.commit_group.sync.aligned;" ::: "memory"); }
template <int N> __device__ __forceinline__ void wg_wait() { asm volatile("wgmma.wait_group.sync.aligned %0;" ::"n"(N) : "memory"); }
__device__ __forceinline__ uint64_t mk_desc(uint32_t addr, uint32_t lbo, uint32_t sbo) {
  return (uint64_t)((addr & 0x3FFFF) >> 4) | ((uint64_t)((lbo & 0x3FFFF) >> 4) << 16) | ((uint64_t)(sbo >> 4) << 32) | (1ull << 62);
}
__device__ __forceinline__ void tma2d(uint32_t dst, const CUtensorMap* m, int c0, int c1, uint32_t bar) {
  asm volatile("cp.async.bulk.tensor.2d.shared::cluster.global.mbarrier::complete_tx::bytes [%0], [%1, {%3, %4}], [%2];"
               ::"r"(dst), "l"(m), "r"(bar), "r"(c0), "r"(c1) : "memory");
}
__device__ __forceinline__ void tma2d_mc(uint32_t dst, const CUtensorMap* m, int c0, int c1, uint32_t bar) {
  asm volatile("cp.async.bulk.tensor.2d.shared::cluster.global.mbarrier::complete_tx::bytes.multicast::cluster [%0], [%1, {%3, %4}], [%2], %5;"
               ::"r"(dst), "l"(m), "r"(bar), "r"(c0), "r"(c1), "h"((uint16_t)3) : "memory");
}
__device__ __forceinline__ void tma3d_mc(uint32_t dst, const CUtensorMap* m, int c0, int c1, int c2, uint32_t bar) {
  asm volatile("cp.async.bulk.tensor.3d.shared::cluster.global.mbarrier::complete_tx::bytes.multicast::cluster [%0], [%1, {%3, %4, %5}], [%2], %6;"
               ::"r"(dst), "l"(m), "r"(bar), "r"(c0), "r"(c1), "r"(c2), "h"((uint16_t)3) : "memory");
}
__device__ __forceinline__ void ldsm4(uint32_t (&r)[4], uint32_t addr) {
  asm volatile("ldmatrix.sync.aligned.m8n8.x4.shared.b16 {%0,%1,%2,%3}, [%4];"
               : "=r"(r[0]), "=r"(r[1]), "=r"(r[2]), "=r"(r[3]) : "r"(addr) : "memory");
}
__device__ __forceinline__ void ldsm4t(uint32_t (&r)[4], uint32_t addr) {
  asm volatile("ldmatrix.sync.aligned.m8n8.x4.trans.shared.b16 {%0,%1,%2,%3}, [%4];"
               : "=r"(r[0]), "=r"(r[1]), "=r"(r[2]), "=r"(r[3]) : "r"(addr) : "memory");
}
__device__ __forceinline__ void stsm4(uint32_t addr, uint32_t r0, uint32_t r1, uint32_t r2, uint32_t r3) {
  asm volatile("stmatrix.sync.aligned.m8n8.x4.shared.b16 [%0], {%1,%2,%3,%4};"
               ::"r"(addr), "r"(r0), "r"(r1), "r"(r2), "r"(r3) : "memory");
}
__device__ __forceinline__ void mma16816(float (&c)[4], const uint32_t (&a)[4], uint32_t b0, uint32_t b1) {
  asm volatile("mma.sync.aligned.m16n8k16.row.col.f32.bf16.bf16.f32 {%0,%1,%2,%3},{%4,%5,%6,%7},{%8,%9},{%0,%1,%2,%3};"
               : "+f"(c[0]), "+f"(c[1]), "+f"(c[2]), "+f"(c[3])
               : "r"(a[0]), "r"(a[1]), "r"(a[2]), "r"(a[3]), "r"(b0), "r"(b1));
}
__device__ __forceinline__ uint32_t pack2(float lo, float hi) {
  uint32_t r; asm("cvt.rn.bf16x2.f32 %0, %1, %2;" : "=r"(r) : "f"(hi), "f"(lo)); return r;
}
__device__ __forceinline__ float blo(uint32_t w) { return __uint_as_float(w << 16); }
__device__ __forceinline__ float bhi(uint32_t w) { return __uint_as_float(w & 0xFFFF0000u); }
__device__ __forceinline__ uint32_t hsub2(uint32_t a, uint32_t b) { uint32_t r; asm("sub.rn.bf16x2 %0, %1, %2;" : "=r"(r) : "r"(a), "r"(b)); return r; }
__device__ __forceinline__ uint32_t hmax2(uint32_t a, uint32_t b) { uint32_t r; asm("max.bf16x2 %0, %1, %2;" : "=r"(r) : "r"(a), "r"(b)); return r; }
__device__ __forceinline__ uint32_t hmin2(uint32_t a, uint32_t b) { uint32_t r; asm("min.bf16x2 %0, %1, %2;" : "=r"(r) : "r"(a), "r"(b)); return r; }
__device__ __forceinline__ float ex2(float x) { float r; asm("ex2.approx.ftz.f32 %0, %1;" : "=f"(r) : "f"(x)); return r; }
__device__ __forceinline__ float rcp(float x) { float r; asm("rcp.approx.ftz.f32 %0, %1;" : "=f"(r) : "f"(x)); return r; }
__device__ __forceinline__ void ld_rlx4(uint32_t (&r)[4], const uint4* p) {
  asm volatile("ld.relaxed.gpu.global.v4.b32 {%0,%1,%2,%3}, [%4];"
               : "=r"(r[0]), "=r"(r[1]), "=r"(r[2]), "=r"(r[3]) : "l"(p) : "memory");
}
__device__ __forceinline__ void st_rlx4(uint4* p, uint32_t a, uint32_t b, uint32_t c, uint32_t d) {
  asm volatile("st.relaxed.gpu.global.v4.b32 [%0], {%1,%2,%3,%4};" ::"l"(p), "r"(a), "r"(b), "r"(c), "r"(d) : "memory");
}
__device__ __forceinline__ void st_rlx2(uint2* p, uint32_t a, uint32_t b) {
  asm volatile("st.relaxed.gpu.global.v2.b32 [%0], {%1,%2};" ::"l"(p), "r"(a), "r"(b) : "memory");
}
__device__ __forceinline__ uint32_t ld_rlx1(const uint32_t* p) {
  uint32_t r; asm volatile("ld.relaxed.gpu.global.b32 %0, [%1];" : "=r"(r) : "l"(p) : "memory"); return r;
}
__device__ __forceinline__ void st_rlx1(uint32_t* p, uint32_t a) {
  asm volatile("st.relaxed.gpu.global.b32 [%0], %1;" ::"l"(p), "r"(a) : "memory");
}
__device__ __forceinline__ uint32_t tg(uint32_t w, uint32_t T) { return (w & 0xFFFFFFFEu) | T; }
__device__ __forceinline__ uint32_t bad4(const uint32_t (&r)[4], uint32_t T) { return (r[0] ^ T) | (r[1] ^ T) | (r[2] ^ T) | (r[3] ^ T); }

__device__ __forceinline__ void ld_chunk(uint32_t (&a)[4][4], const uint4* p) {
#pragma unroll
  for (int s = 0; s < 4; s++) ld_rlx4(a[s], p + s * 32);
}
__device__ __forceinline__ void chk_chunk(uint32_t (&a)[4][4], const uint4* p, uint32_t T) {
  int it = 0;
#pragma unroll 1
  while (__any_sync(0xffffffffu, (bad4(a[0], T) | bad4(a[1], T) | bad4(a[2], T) | bad4(a[3], T)) & 1)) {
    ld_chunk(a, p);
    if (++it > (1 << 18)) break;
  }
}

__device__ __forceinline__ void wgmma_rs_n64(float (&d)[32], const uint32_t (&a)[4], uint64_t descB, int scaleD) {
  asm volatile("{\n.reg .pred p;\nsetp.ne.b32 p, %37, 0;\n"
    "wgmma.mma_async.sync.aligned.m64n64k16.f32.bf16.bf16 {%0,%1,%2,%3,%4,%5,%6,%7,%8,%9,%10,%11,%12,%13,%14,%15,%16,%17,%18,%19,%20,%21,%22,%23,%24,%25,%26,%27,%28,%29,%30,%31}, {%32,%33,%34,%35}, %36, p, 1, 1, 1;\n}\n"
    : "+f"(d[0]),"+f"(d[1]),"+f"(d[2]),"+f"(d[3]),"+f"(d[4]),"+f"(d[5]),"+f"(d[6]),"+f"(d[7]),"+f"(d[8]),"+f"(d[9]),"+f"(d[10]),"+f"(d[11]),"+f"(d[12]),"+f"(d[13]),"+f"(d[14]),"+f"(d[15]),"+f"(d[16]),"+f"(d[17]),"+f"(d[18]),"+f"(d[19]),"+f"(d[20]),"+f"(d[21]),"+f"(d[22]),"+f"(d[23]),"+f"(d[24]),"+f"(d[25]),"+f"(d[26]),"+f"(d[27]),"+f"(d[28]),"+f"(d[29]),"+f"(d[30]),"+f"(d[31])
    : "r"(a[0]), "r"(a[1]), "r"(a[2]), "r"(a[3]), "l"(descB), "r"(scaleD));
}
__device__ __forceinline__ void wgmma_rs_n128(float (&d)[64], const uint32_t (&a)[4], uint64_t descB, int scaleD) {
  asm volatile("{\n.reg .pred p;\nsetp.ne.b32 p, %69, 0;\n"
    "wgmma.mma_async.sync.aligned.m64n128k16.f32.bf16.bf16 {%0,%1,%2,%3,%4,%5,%6,%7,%8,%9,%10,%11,%12,%13,%14,%15,%16,%17,%18,%19,%20,%21,%22,%23,%24,%25,%26,%27,%28,%29,%30,%31,%32,%33,%34,%35,%36,%37,%38,%39,%40,%41,%42,%43,%44,%45,%46,%47,%48,%49,%50,%51,%52,%53,%54,%55,%56,%57,%58,%59,%60,%61,%62,%63}, {%64,%65,%66,%67}, %68, p, 1, 1, 1;\n}\n"
    : "+f"(d[0]),"+f"(d[1]),"+f"(d[2]),"+f"(d[3]),"+f"(d[4]),"+f"(d[5]),"+f"(d[6]),"+f"(d[7]),"+f"(d[8]),"+f"(d[9]),"+f"(d[10]),"+f"(d[11]),"+f"(d[12]),"+f"(d[13]),"+f"(d[14]),"+f"(d[15]),"+f"(d[16]),"+f"(d[17]),"+f"(d[18]),"+f"(d[19]),"+f"(d[20]),"+f"(d[21]),"+f"(d[22]),"+f"(d[23]),"+f"(d[24]),"+f"(d[25]),"+f"(d[26]),"+f"(d[27]),"+f"(d[28]),"+f"(d[29]),"+f"(d[30]),"+f"(d[31]),"+f"(d[32]),"+f"(d[33]),"+f"(d[34]),"+f"(d[35]),"+f"(d[36]),"+f"(d[37]),"+f"(d[38]),"+f"(d[39]),"+f"(d[40]),"+f"(d[41]),"+f"(d[42]),"+f"(d[43]),"+f"(d[44]),"+f"(d[45]),"+f"(d[46]),"+f"(d[47]),"+f"(d[48]),"+f"(d[49]),"+f"(d[50]),"+f"(d[51]),"+f"(d[52]),"+f"(d[53]),"+f"(d[54]),"+f"(d[55]),"+f"(d[56]),"+f"(d[57]),"+f"(d[58]),"+f"(d[59]),"+f"(d[60]),"+f"(d[61]),"+f"(d[62]),"+f"(d[63])
    : "r"(a[0]), "r"(a[1]), "r"(a[2]), "r"(a[3]), "l"(descB), "r"(scaleD));
}
__device__ __forceinline__ void wgmma_rs_n176(float (&d)[88], const uint32_t (&a)[4], uint64_t descB, int scaleD) {
  asm volatile("{\n.reg .pred p;\nsetp.ne.b32 p, %93, 0;\n"
    "wgmma.mma_async.sync.aligned.m64n176k16.f32.bf16.bf16 {%0,%1,%2,%3,%4,%5,%6,%7,%8,%9,%10,%11,%12,%13,%14,%15,%16,%17,%18,%19,%20,%21,%22,%23,%24,%25,%26,%27,%28,%29,%30,%31,%32,%33,%34,%35,%36,%37,%38,%39,%40,%41,%42,%43,%44,%45,%46,%47,%48,%49,%50,%51,%52,%53,%54,%55,%56,%57,%58,%59,%60,%61,%62,%63,%64,%65,%66,%67,%68,%69,%70,%71,%72,%73,%74,%75,%76,%77,%78,%79,%80,%81,%82,%83,%84,%85,%86,%87}, {%88,%89,%90,%91}, %92, p, 1, 1, 1;\n}\n"
    : "+f"(d[0]),"+f"(d[1]),"+f"(d[2]),"+f"(d[3]),"+f"(d[4]),"+f"(d[5]),"+f"(d[6]),"+f"(d[7]),"+f"(d[8]),"+f"(d[9]),"+f"(d[10]),"+f"(d[11]),"+f"(d[12]),"+f"(d[13]),"+f"(d[14]),"+f"(d[15]),"+f"(d[16]),"+f"(d[17]),"+f"(d[18]),"+f"(d[19]),"+f"(d[20]),"+f"(d[21]),"+f"(d[22]),"+f"(d[23]),"+f"(d[24]),"+f"(d[25]),"+f"(d[26]),"+f"(d[27]),"+f"(d[28]),"+f"(d[29]),"+f"(d[30]),"+f"(d[31]),"+f"(d[32]),"+f"(d[33]),"+f"(d[34]),"+f"(d[35]),"+f"(d[36]),"+f"(d[37]),"+f"(d[38]),"+f"(d[39]),"+f"(d[40]),"+f"(d[41]),"+f"(d[42]),"+f"(d[43]),"+f"(d[44]),"+f"(d[45]),"+f"(d[46]),"+f"(d[47]),"+f"(d[48]),"+f"(d[49]),"+f"(d[50]),"+f"(d[51]),"+f"(d[52]),"+f"(d[53]),"+f"(d[54]),"+f"(d[55]),"+f"(d[56]),"+f"(d[57]),"+f"(d[58]),"+f"(d[59]),"+f"(d[60]),"+f"(d[61]),"+f"(d[62]),"+f"(d[63]),"+f"(d[64]),"+f"(d[65]),"+f"(d[66]),"+f"(d[67]),"+f"(d[68]),"+f"(d[69]),"+f"(d[70]),"+f"(d[71]),"+f"(d[72]),"+f"(d[73]),"+f"(d[74]),"+f"(d[75]),"+f"(d[76]),"+f"(d[77]),"+f"(d[78]),"+f"(d[79]),"+f"(d[80]),"+f"(d[81]),"+f"(d[82]),"+f"(d[83]),"+f"(d[84]),"+f"(d[85]),"+f"(d[86]),"+f"(d[87])
    : "r"(a[0]), "r"(a[1]), "r"(a[2]), "r"(a[3]), "l"(descB), "r"(scaleD));
}
__device__ __forceinline__ void wgmma_ss_n72_t11(float (&d)[36], uint64_t descA, uint64_t descB, int scaleD) {
  asm volatile("{\n.reg .pred p;\nsetp.ne.b32 p, %38, 0;\n"
    "wgmma.mma_async.sync.aligned.m64n72k16.f32.bf16.bf16 {%0,%1,%2,%3,%4,%5,%6,%7,%8,%9,%10,%11,%12,%13,%14,%15,%16,%17,%18,%19,%20,%21,%22,%23,%24,%25,%26,%27,%28,%29,%30,%31,%32,%33,%34,%35}, %36, %37, p, 1, 1, 1, 1;\n}\n"
    : "+f"(d[0]),"+f"(d[1]),"+f"(d[2]),"+f"(d[3]),"+f"(d[4]),"+f"(d[5]),"+f"(d[6]),"+f"(d[7]),"+f"(d[8]),"+f"(d[9]),"+f"(d[10]),"+f"(d[11]),"+f"(d[12]),"+f"(d[13]),"+f"(d[14]),"+f"(d[15]),"+f"(d[16]),"+f"(d[17]),"+f"(d[18]),"+f"(d[19]),"+f"(d[20]),"+f"(d[21]),"+f"(d[22]),"+f"(d[23]),"+f"(d[24]),"+f"(d[25]),"+f"(d[26]),"+f"(d[27]),"+f"(d[28]),"+f"(d[29]),"+f"(d[30]),"+f"(d[31]),"+f"(d[32]),"+f"(d[33]),"+f"(d[34]),"+f"(d[35])
    : "l"(descA), "l"(descB), "r"(scaleD));
}

#define TSTAMP(i) do {} while (0)

constexpr float LOG2E = 1.4426950408889634f;

__device__ __forceinline__ void feat_exp(const float (&p0)[4], const float (&p1)[4], float (&e)[16]) {
  uint32_t P0 = pack2(p0[0], p0[1]), P1 = pack2(p0[2], p0[3]), P2 = pack2(p1[0], p1[1]), P3 = pack2(p1[2], p1[3]);
  uint32_t a = hmax2(P0, P2), b = hmax2(P1, P3);
  uint32_t mx = hmax2(__byte_perm(a, b, 0x5410), __byte_perm(a, b, 0x7632));
  a = hmin2(P0, P2); b = hmin2(P1, P3);
  uint32_t mn = hmin2(__byte_perm(a, b, 0x5410), __byte_perm(a, b, 0x7632));
  mx = hmax2(mx, __shfl_xor_sync(0xffffffffu, mx, 1));
  mn = hmin2(mn, __shfl_xor_sync(0xffffffffu, mn, 1));
  mx = hmax2(mx, __shfl_xor_sync(0xffffffffu, mx, 2));
  mn = hmin2(mn, __shfl_xor_sync(0xffffffffu, mn, 2));
  float mx0 = -blo(mx) * LOG2E, mx1 = -bhi(mx) * LOG2E, mn0 = blo(mn) * LOG2E, mn1 = bhi(mn) * LOG2E;
  float v[8] = {blo(P0), bhi(P0), blo(P1), bhi(P1), blo(P2), bhi(P2), blo(P3), bhi(P3)};
#pragma unroll
  for (int i = 0; i < 8; i++) {
    bool r1 = (i >> 1) & 1;
    e[i]     = ex2(fmaf(v[i],  LOG2E, r1 ? mx1 : mx0));
    e[8 + i] = ex2(fmaf(v[i], -LOG2E, r1 ? mn1 : mn0));
  }
}

__global__ void __cluster_dims__(2, 1, 1) __launch_bounds__(384, 1)
fused_kernel(const __grid_constant__ Maps maps, const __nv_bfloat16* __restrict__ x, const __nv_bfloat16* __restrict__ wphi,
             const __nv_bfloat16* __restrict__ wo, const __nv_bfloat16* __restrict__ wg_, const __nv_bfloat16* __restrict__ wu_,
             const __nv_bfloat16* __restrict__ wd_, __nv_bfloat16* __restrict__ out) {
  extern __shared__ __align__(1024) unsigned char smem[];
  const uint32_t sb = smem_u32(smem);
  const int tid = threadIdx.x, lane = tid & 31;
  const int warp = __shfl_sync(0xffffffffu, tid >> 5, 0);
  const uint32_t rank = blockIdx.x & 1;
  const int cl = blockIdx.x >> 1;
  const int grp = cl & 7, mem = cl >> 3;
  const int rb = 2 * grp + (mem >> 2), hp = mem & 3;
  const int hg = 2 * hp + rank;
  const int rh2 = 2 * rb + rank, cq = hp;
  const int rb3 = 2 * grp + rank, jf = mem;

  if (lane == 0) {
    if (warp == 8) {
      asm volatile("prefetch.tensormap [%0];" ::"l"(&maps.x) : "memory");
      asm volatile("prefetch.tensormap [%0];" ::"l"(&maps.w) : "memory");
    }
#pragma unroll
    for (int i = 0; i < 4; i++) {
      const int s = warp * 4 + i;
      if (s < NSTAGE) {
        mbar_init(sb + SM_FULL + s * 8, 1);
        mbar_init(sb + SM_EMPTY + s * 8, st_empty_cnt(s));
        mbar_expect_tx(sb + SM_FULL + s * 8, st_bytes(s));
      } else {
        mbar_init(sb + SM_MISCB, 3);
        mbar_init(sb + SM_KVB, 3);
      }
    }
    asm volatile("fence.mbarrier_init.release.cluster;" ::: "memory");
  }
  __syncthreads();
  asm volatile("barrier.cluster.arrive.relaxed.aligned;" ::: "memory");

  if (warp >= 8) {
    asm volatile("setmaxnreg.dec.sync.aligned.u32 24;");
    if (warp == 8) {
      asm volatile("barrier.cluster.wait.aligned;" ::: "memory");
      if (lane == 0) {
        tma3d_mc(sb + rank * SLOT, &maps.x, 0, rb * 128, 3 * rank, sb + SM_FULL + rank * 8);
        if (rank == 0) tma3d_mc(sb + 2 * SLOT, &maps.x, 0, rb * 128, 6, sb + SM_FULL + 2 * 8);
#pragma unroll 1
        for (int i = 0; i < 3; i++) tma2d(sb + (ST_WK + i) * SLOT, &maps.w, 512 + hg * 64, i * 192, sb + SM_FULL + (ST_WK + i) * 8);
        tma3d_mc(sb + (ST_X1 + 1 - rank) * SLOT, &maps.x, 0, rb * 128 + 64, 3 - 3 * rank, sb + SM_FULL + (ST_X1 + 1 - rank) * 8);
        if (rank == 1) tma3d_mc(sb + (ST_X1 + 2) * SLOT, &maps.x, 0, rb * 128 + 64, 6, sb + SM_FULL + (ST_X1 + 2) * 8);
        const CUtensorMap* mgu = rank ? (jf == 7 ? &maps.u7 : &maps.u) : (jf == 7 ? &maps.g7 : &maps.g);
        asm volatile("prefetch.tensormap [%0];" ::"l"(&maps.wo96) : "memory");
        asm volatile("prefetch.tensormap [%0];" ::"l"(&maps.wo64) : "memory");
        asm volatile("prefetch.tensormap [%0];" ::"l"(mgu) : "memory");
        asm volatile("prefetch.tensormap [%0];" ::"l"(&maps.d) : "memory");
#pragma unroll 1
        for (int s = ST_WV; s < ST_WO; s++) {
          if (s == ST_SCR1) continue;
          mbar_wait(sb + SM_EMPTY + (s - NSLOT) * 8);
          tma2d(sb + (s - NSLOT) * SLOT, &maps.w, (s < ST_WQ ? 1024 : 0) + hg * 64, (s < ST_WQ ? s - ST_WV : s - ST_WQ) * 192,
                sb + SM_FULL + s * 8);
        }
        const int jc = jf == 7 ? 0 : jf;
        int slot = (ST_WO + rank) % NSLOT;
#pragma unroll 1
        for (int s = ST_WO + rank; s < NSTAGE; s += 2) {
          mbar_wait(sb + SM_EMPTY + (s - NSLOT) * 8);
          const uint32_t dst = sb + slot * SLOT, bar = sb + SM_FULL + s * 8;
          if (s < ST_GU) {
            const int p = (s - ST_WO) >> 1;
            tma3d_mc(dst, p < 2 ? &maps.wo96 : &maps.wo64, 0, rank * 256 + p * 96, cq * 2, bar);
          } else if (s < ST_D) {
            const int c = (s - ST_GU) >> 1;
#pragma unroll
            for (int b = 0; b < 3; b++) tma3d_mc(dst + b * 8192, mgu, b * 64, jc, c * 64, bar);
          } else {
            tma2d_mc(dst, &maps.d, ((jf + 1 + (s - ST_D)) & 7) * 64, jf * 176, bar);
          }
          slot += 2; if (slot >= NSLOT) slot -= NSLOT;
        }
      }
      __syncwarp();
    } else {
      const int ht = tid - 288;
      if (ht == 0) {
        unsigned old = atomicAdd(&g_start, 1u);
        *reinterpret_cast<volatile unsigned*>(smem + SM_EPOCH) = old / NCTA;
      }
#pragma unroll 1
      for (int i = ht; i < 128; i += 96) {
        reinterpret_cast<uint4*>(smem + SM_ONES)[i] = make_uint4(0x3F803F80u, 0x3F803F80u, 0x3F803F80u, 0x3F803F80u);
        reinterpret_cast<uint4*>(smem + SM_WPHI)[i] = __ldg(reinterpret_cast<const uint4*>(wphi + hg * 1024) + i);
      }
      fence_async_smem();
      __syncwarp();
      if (lane == 0) mbar_arrive(sb + SM_MISCB);
      asm volatile("barrier.cluster.wait.aligned;" ::: "memory");
      mbar_wait(sb + SM_MISCB);
      const unsigned epoch = *reinterpret_cast<volatile unsigned*>(smem + SM_EPOCH);
      const int par = epoch & 1;
      if (ht < 32) reinterpret_cast<float4*>(&g_kv[par ^ 1][blockIdx.x * 128])[ht] = make_float4(0.f, 0.f, 0.f, 0.f);
      else if (ht < 40) g_z[par ^ 1][blockIdx.x * 8 + (ht - 32)] = 0.f;
      if (warp == 11) {
        mbar_wait(sb + SM_FULL + (ST_X1 + 2) * 8);
        if (lane == 0) {
          asm volatile("cp.async.bulk.prefetch.L2.global [%0], 4096;" ::"l"((const char*)wo + blockIdx.x * 4096) : "memory");
          asm volatile("cp.async.bulk.prefetch.L2.global [%0], 11008;" ::"l"((const char*)wg_ + blockIdx.x * 11008) : "memory");
          asm volatile("cp.async.bulk.prefetch.L2.global [%0], 11008;" ::"l"((const char*)wu_ + blockIdx.x * 11008) : "memory");
          asm volatile("cp.async.bulk.prefetch.L2.global [%0], 11008;" ::"l"((const char*)wd_ + blockIdx.x * 11008) : "memory");
        }
        __syncwarp();
      } else {
        bar_sync(6 + (warp - 9), 160);
        if (lane == 0) {
          asm volatile("fence.acq_rel.gpu;" ::: "memory");
          asm volatile("red.relaxed.gpu.global.add.u32 [%0], 1;" ::"l"(&g_kvcnt[hg * 32]) : "memory");
        }
        __syncwarp();
      }
      if (lane == 0) {
        const unsigned target = (epoch + 1) * 32;
        int it = 0;
#pragma unroll 1
        while ((int)(ld_rlx1(&g_kvcnt[hg * 32]) - target) < 0) {
          if (++it > (1 << 18)) break;
        }
        asm volatile("fence.acq_rel.gpu;" ::: "memory");
      }
      __syncwarp();
      {
        const float4* src = reinterpret_cast<const float4*>(&g_kv[par][hg * 2048]);
#pragma unroll 1
        for (int r = ht; r < 128; r += 96) {
          const float4 a = __ldcg(src + r * 4), b = __ldcg(src + r * 4 + 1), c = __ldcg(src + r * 4 + 2), d = __ldcg(src + r * 4 + 3);
          const uint32_t zz = pack2(__ldcg(&g_z[par][hg * 128 + r]), 1.0f);
          uint4* dst = reinterpret_cast<uint4*>(smem + SM_KVS + r * 48);
          dst[0] = make_uint4(pack2(a.x, a.y), pack2(a.z, a.w), pack2(b.x, b.y), pack2(b.z, b.w));
          dst[1] = make_uint4(pack2(c.x, c.y), pack2(c.z, c.w), pack2(d.x, d.y), pack2(d.z, d.w));
          dst[2] = make_uint4(zz, zz, zz, zz);
        }
      }
      __syncwarp();
      if (lane == 0) mbar_arrive(sb + SM_KVB);
    }
    asm volatile("barrier.cluster.arrive.relaxed.aligned;" ::: "memory");
    asm volatile("barrier.cluster.wait.aligned;" ::: "memory");
  } else {
    asm volatile("setmaxnreg.inc.sync.aligned.u32 240;");
    asm volatile("barrier.cluster.wait.aligned;" ::: "memory");
    const int wg = warp >> 2, wq = warp & 3, g = lane >> 2, t = lane & 3;
    const bool lead = (tid & 127) == 0;
    auto release = [&](int d) {
      const int s = d + NSLOT;
      if (s < NSTAGE) mbar_arrive_cluster(sb + SM_EMPTY + d * 8, s >= ST_WO ? (uint32_t)((s + 1) & 1) : rank);
    };
    const uint32_t lrow = (uint32_t)(wq * 16 + (lane & 7) + ((lane >> 3) & 1) * 8) * 128;
    const uint32_t lx = lane & 7, lhi = lane >> 4;
    if (wg == 1) bar_arrive(4, 256);
    TSTAMP(0);

    float r0, r1;
    uint32_t E[4][8];
    uint32_t T = 0;
    {
      uint32_t A[32][4];
      const int sx = wg ? ST_X1 : ST_X0;
      uint32_t m0, m1;
      {
        float s = 0.f, q = 0.f;
        const uint32_t rr = lane >> 1;
        const uint32_t sbase = sb + sx * SLOT + (wq * 16 + rr) * 128;
#pragma unroll 1
        for (int c = 0; c < 8; c++) {
          if (c == 0 || c == 3 || c == 6) mbar_wait(sb + SM_FULL + (sx + c / 3) * 8);
#pragma unroll
          for (int i = 0; i < 4; i++) {
            uint32_t v[4];
            asm volatile("ld.shared.v4.b32 {%0,%1,%2,%3}, [%4];" : "=r"(v[0]), "=r"(v[1]), "=r"(v[2]), "=r"(v[3])
                         : "r"(sbase + c * 8192 + ((((lane & 1) * 4 + i) ^ (rr & 7)) << 4)) : "memory");
#pragma unroll
            for (int k = 0; k < 4; k++) {
              const float a = blo(v[k]), b = bhi(v[k]);
              s += a + b; q = fmaf(a, a, q); q = fmaf(b, b, q);
            }
          }
        }
        s += __shfl_xor_sync(0xffffffffu, s, 1); q += __shfl_xor_sync(0xffffffffu, q, 1);
        s *= (1.f / 512.f);
        const float r = rsqrtf(fmaxf(q * (1.f / 512.f) - s * s, 0.f) + 1e-5f);
        const uint32_t m = pack2(s, s);
        m0 = __shfl_sync(0xffffffffu, m, 2 * g); m1 = __shfl_sync(0xffffffffu, m, 2 * g + 16);
        r0 = __shfl_sync(0xffffffffu, r, 2 * g); r1 = __shfl_sync(0xffffffffu, r, 2 * g + 16);
      }
      TSTAMP(17);
      {
        const uint32_t base = sb + sx * SLOT + lrow;
#pragma unroll
        for (int ks = 0; ks < 32; ks++) {
          ldsm4(A[ks], base + (ks >> 2) * 8192 + (((2 * (ks & 3) + lhi) ^ lx) << 4));
          A[ks][0] = hsub2(A[ks][0], m0); A[ks][1] = hsub2(A[ks][1], m1);
          A[ks][2] = hsub2(A[ks][2], m0); A[ks][3] = hsub2(A[ks][3], m1);
        }
        __syncwarp();
        if (lane < 3) release(sx + lane);
      }
      TSTAMP(1);

      const uint32_t scr = sb + (wg ? (ST_SCR1 % NSLOT) : (ST_SCR0 % NSLOT)) * SLOT;
#pragma unroll 1
      for (int ps = 0; ps < 3; ps++) {
        const int st0 = ps == 0 ? ST_WK : (ps == 1 ? ST_WV : ST_WQ);
        const uint32_t wbase = sb + (ps == 0 ? ST_WK % NSLOT : (ps == 1 ? ST_WV % NSLOT : ST_WQ % NSLOT)) * SLOT;
        float acc[32];
        bar_sync(4 + wg, 256);
#pragma unroll
        for (int i = 0; i < 3; i++) {
          mbar_wait(sb + SM_FULL + (st0 + i) * 8);
          wg_fence();
#pragma unroll
          for (int kk = 0; kk < (i < 2 ? 12 : 8); kk++)
            wgmma_rs_n64(acc, A[12 * i + kk], mk_desc(wbase + i * SLOT + kk * 2048, 8192, 1024), (i | kk) != 0);
          wg_commit();
          if (i > 0) { wg_wait<1>(); if (lead) release(st0 + i - 1); }
        }
        if (ps < 2 || wg == 0) bar_arrive(4 + (wg ^ 1), 256);
        wg_wait<0>();
        if (lead) release(st0 + 2);
        TSTAMP(2 + 2 * ps);
        uint32_t a[4][4];
#pragma unroll
        for (int h = 0; h < 4; h++) {
          a[h][0] = pack2(acc[8 * h + 0] * r0, acc[8 * h + 1] * r0); a[h][1] = pack2(acc[8 * h + 2] * r1, acc[8 * h + 3] * r1);
          a[h][2] = pack2(acc[8 * h + 4] * r0, acc[8 * h + 5] * r0); a[h][3] = pack2(acc[8 * h + 6] * r1, acc[8 * h + 7] * r1);
        }
        if (ps != 1) {
          if (ps == 0) {
            mbar_wait(sb + SM_MISCB);
            T = (*reinterpret_cast<volatile unsigned*>(smem + SM_EPOCH) & 1) ^ 1;
            mbar_wait(sb + SM_EMPTY + (wg ? ST_SCR1 - NSLOT : ST_SCR0 - NSLOT) * 8);
          }
          float pp[4][2][4];
#pragma unroll
          for (int h = 0; h < 4; h++) {
            uint32_t b[4];
            ldsm4t(b, sb + SM_WPHI + h * 512 + ((lane & 7) + ((lane >> 3) & 1) * 8) * 32 + lhi * 16);
#pragma unroll
            for (int i = 0; i < 4; i++) { pp[h][0][i] = 0.f; pp[h][1][i] = 0.f; }
            mma16816(pp[h][0], a[h], b[0], b[1]);
            mma16816(pp[h][1], a[h], b[2], b[3]);
          }
          float e[4][16];
#pragma unroll
          for (int h = 0; h < 4; h++) feat_exp(pp[h][0], pp[h][1], e[h]);
          if (ps == 0) {
#pragma unroll
            for (int h = 0; h < 4; h++) {
              const float (&f)[16] = e[h];
              float sp0 = (f[0] + f[1]) + (f[4] + f[5]), sp1 = (f[2] + f[3]) + (f[6] + f[7]);
              float sn0 = (f[8] + f[9]) + (f[12] + f[13]), sn1 = (f[10] + f[11]) + (f[14] + f[15]);
              sp0 += __shfl_xor_sync(0xffffffffu, sp0, 1); sp1 += __shfl_xor_sync(0xffffffffu, sp1, 1);
              sn0 += __shfl_xor_sync(0xffffffffu, sn0, 1); sn1 += __shfl_xor_sync(0xffffffffu, sn1, 1);
              sp0 += __shfl_xor_sync(0xffffffffu, sp0, 2); sp1 += __shfl_xor_sync(0xffffffffu, sp1, 2);
              sn0 += __shfl_xor_sync(0xffffffffu, sn0, 2); sn1 += __shfl_xor_sync(0xffffffffu, sn1, 2);
              sp0 = rcp(sp0); sp1 = rcp(sp1); sn0 = rcp(sn0); sn1 = rcp(sn1);
              const uint32_t dst = scr + (h >> 1) * 8192 + lrow;
              stsm4(dst + ((((h & 1) * 4 + lhi) ^ lx) << 4), pack2(f[0] * sp0, f[1] * sp0), pack2(f[2] * sp1, f[3] * sp1),
                    pack2(f[4] * sp0, f[5] * sp0), pack2(f[6] * sp1, f[7] * sp1));
              stsm4(dst + ((((h & 1) * 4 + 2 + lhi) ^ lx) << 4), pack2(f[8] * sn0, f[9] * sn0), pack2(f[10] * sn1, f[11] * sn1),
                    pack2(f[12] * sn0, f[13] * sn0), pack2(f[14] * sn1, f[15] * sn1));
            }
          } else {
#pragma unroll
            for (int h = 0; h < 4; h++)
#pragma unroll
              for (int i = 0; i < 8; i++) A[2 * h + (i >> 2)][i & 3] = pack2(e[h][2 * i], e[h][2 * i + 1]);
          }
        } else {
#pragma unroll
          for (int h = 0; h < 4; h++) stsm4(scr + 16384 + lrow + (((2 * h + lhi) ^ lx) << 4), a[h][0], a[h][1], a[h][2], a[h][3]);
          fence_async_smem();
          bar_sync(1 + wg, 128);
          float kv0[36], kv1[36];
          wg_fence();
#pragma unroll
          for (int ks = 0; ks < 4; ks++) {
            const uint32_t vb = scr + 16384 + ks * 2048;
            const uint64_t db = mk_desc(vb, sb + SM_ONES - vb, 1024);
            wgmma_ss_n72_t11(kv0, mk_desc(scr + ks * 2048, 8192, 1024), db, ks != 0);
            wgmma_ss_n72_t11(kv1, mk_desc(scr + 8192 + ks * 2048, 8192, 1024), db, ks != 0);
          }
          wg_commit();
          wg_wait<0>();
          if (lead) release(wg ? ST_SCR1 : ST_SCR0);
          const bool up = wq >= 2;
          const int f = (wq & 1) * 16 + g;
          float* kvp = &g_kv[T ^ 1][((hg * 4 + (wq >> 1)) * 32 + f) * 16 + 2 * t];
          float* zp = &g_z[T ^ 1][(hg * 4 + (wq >> 1)) * 32 + f];
#pragma unroll
          for (int b = 0; b < 2; b++) {
#pragma unroll
            for (int n = 0; n < 2; n++) {
              float c0, c1, c2, c3;
              if (b == 0) {
                c0 = up ? kv0[8 + 4 * n + 0] : kv0[4 * n + 0]; c1 = up ? kv0[8 + 4 * n + 1] : kv0[4 * n + 1];
                c2 = up ? kv0[8 + 4 * n + 2] : kv0[4 * n + 2]; c3 = up ? kv0[8 + 4 * n + 3] : kv0[4 * n + 3];
              } else {
                c0 = up ? kv1[24 + 4 * n + 0] : kv1[16 + 4 * n + 0]; c1 = up ? kv1[24 + 4 * n + 1] : kv1[16 + 4 * n + 1];
                c2 = up ? kv1[24 + 4 * n + 2] : kv1[16 + 4 * n + 2]; c3 = up ? kv1[24 + 4 * n + 3] : kv1[16 + 4 * n + 3];
              }
              float* p = kvp + b * 1024 + n * 8;
              asm volatile("red.relaxed.gpu.global.add.v2.f32 [%0], {%1,%2};" ::"l"(p), "f"(c0), "f"(c1) : "memory");
              asm volatile("red.relaxed.gpu.global.add.v2.f32 [%0], {%1,%2};" ::"l"(p + 128), "f"(c2), "f"(c3) : "memory");
            }
            if (t == 0) {
              asm volatile("red.relaxed.gpu.global.add.f32 [%0], %1;" ::"l"(zp + b * 64), "f"(b ? kv1[32] : kv0[32]) : "memory");
              asm volatile("red.relaxed.gpu.global.add.f32 [%0], %1;" ::"l"(zp + b * 64 + 8), "f"(b ? kv1[34] : kv0[34]) : "memory");
            }
          }
          bar_arrive(6 + wg, 160);
        }
        TSTAMP(3 + 2 * ps);
      }
#pragma unroll
      for (int i = 0; i < 32; i++) E[i >> 3][i & 7] = A[i >> 2][i & 3];
    }
    uint32_t xr[16];
    {
      const uint32_t* xp = reinterpret_cast<const uint32_t*>(x + (size_t)(rh2 * 64 + wq * 16 + g) * 512 + cq * 128 + wg * 64 + 2 * t);
#pragma unroll
      for (int i = 0; i < 8; i++) { xr[2 * i] = __ldg(xp + 4 * i); xr[2 * i + 1] = __ldg(xp + 8 * 256 + 4 * i); }
    }
    mbar_wait(sb + SM_KVB);
    TSTAMP(8);
    {
      uint4* op = &g_o[2 * rb + wg][hg][wq][0][lane];
#pragma unroll
      for (int h = 0; h < 4; h++) {
        uint32_t b0[4], b1[4], b2[4];
        const uint32_t kb = sb + SM_KVS + (h * 32 + lane) * 48;
        ldsm4t(b0, kb); ldsm4t(b1, kb + 16); ldsm4t(b2, kb + 32);
        const uint32_t ep[4] = {E[h][0], E[h][1], E[h][2], E[h][3]}, en[4] = {E[h][4], E[h][5], E[h][6], E[h][7]};
        float np0[4] = {0, 0, 0, 0}, np1[4] = {0, 0, 0, 0}, nn0[4] = {0, 0, 0, 0}, nn1[4] = {0, 0, 0, 0}, dp[4] = {0, 0, 0, 0}, dn[4] = {0, 0, 0, 0};
        mma16816(dp, ep, b2[0], b2[1]);  mma16816(dn, en, b2[2], b2[3]);
        mma16816(np0, ep, b0[0], b0[1]); mma16816(nn0, en, b0[2], b0[3]);
        mma16816(np1, ep, b1[0], b1[1]); mma16816(nn1, en, b1[2], b1[3]);
        const float i0 = rcp(fmaf(dp[0], dn[1], fmaf(dn[0], dp[1], 1e-6f * dp[1] * dn[1])));
        const float i1 = rcp(fmaf(dp[2], dn[3], fmaf(dn[2], dp[3], 1e-6f * dp[3] * dn[3])));
        const float cp0 = dn[1] * i0, cn0 = dp[1] * i0, cp1 = dn[3] * i1, cn1 = dp[3] * i1;
        st_rlx4(op + h * 32,
                tg(pack2(fmaf(np0[0], cp0, nn0[0] * cn0), fmaf(np0[1], cp0, nn0[1] * cn0)), T),
                tg(pack2(fmaf(np0[2], cp1, nn0[2] * cn1), fmaf(np0[3], cp1, nn0[3] * cn1)), T),
                tg(pack2(fmaf(np1[0], cp0, nn1[0] * cn0), fmaf(np1[1], cp0, nn1[1] * cn0)), T),
                tg(pack2(fmaf(np1[2], cp1, nn1[2] * cn1), fmaf(np1[3], cp1, nn1[3] * cn1)), T));
      }
    }
    TSTAMP(9);

    {
      uint32_t A[4][4][4];
      const uint4* op = &g_o[rh2][wg * 4][wq][0][lane];
#pragma unroll
      for (int c = 0; c < 4; c++) ld_chunk(A[c], op + c * 512);
      float acc[64];
#pragma unroll
      for (int c = 0; c < 4; c++) {
        chk_chunk(A[c], op + c * 512, T);
#pragma unroll
        for (int s = 0; s < 4; s++) {
          const int ks = 4 * c + s, p = ks / 6, kk = ks - 6 * p;
          const int sA = ST_WO + 2 * p, sB = sA + 1;
          if (kk == 0) mbar_wait(sb + SM_FULL + (sA + wg) * 8);
          if (s == 0 || kk == 0) wg_fence();
          const uint32_t base = sb + (wg ? (sB % NSLOT) : (sA % NSLOT)) * SLOT;
          wgmma_rs_n128(acc, A[c][s], mk_desc(base + kk * 2048, p < 2 ? 12288 : 8192, 1024), ks != 0);
        }
        wg_commit();
      }
      wg_wait<0>();
      if (lead) { release(ST_WO + wg); release(ST_WO + 2 + wg); }
      TSTAMP(10);
      bar_sync(1 + wg, 128);
      float4* ex_w = reinterpret_cast<float4*>(smem + (wg ? ((ST_WO + 5) % NSLOT) : ((ST_WO + 4) % NSLOT)) * SLOT) + (tid & 127);
      const float4* ex_r = reinterpret_cast<const float4*>(smem + (wg ? ((ST_WO + 4) % NSLOT) : ((ST_WO + 5) % NSLOT)) * SLOT) + (tid & 127);
#pragma unroll
      for (int i = 0; i < 8; i++)
        ex_w[i * 128] = wg ? make_float4(acc[4 * i], acc[4 * i + 1], acc[4 * i + 2], acc[4 * i + 3])
                           : make_float4(acc[32 + 4 * i], acc[32 + 4 * i + 1], acc[32 + 4 * i + 2], acc[32 + 4 * i + 3]);
      fence_async_smem();
      bar_sync(3, 256);
      uint32_t hw[16];
      float s0 = 0.f, s1 = 0.f, q0 = 0.f, q1 = 0.f;
#pragma unroll
      for (int i = 0; i < 8; i++) {
        const float4 o = ex_r[i * 128];
        const float a0 = (wg ? acc[32 + 4 * i] : acc[4 * i]) + o.x, a1 = (wg ? acc[32 + 4 * i + 1] : acc[4 * i + 1]) + o.y;
        const float a2 = (wg ? acc[32 + 4 * i + 2] : acc[4 * i + 2]) + o.z, a3 = (wg ? acc[32 + 4 * i + 3] : acc[4 * i + 3]) + o.w;
        hw[2 * i]     = pack2(blo(xr[2 * i]) + a0, bhi(xr[2 * i]) + a1);
        hw[2 * i + 1] = pack2(blo(xr[2 * i + 1]) + a2, bhi(xr[2 * i + 1]) + a3);
      }
#pragma unroll
      for (int i = 0; i < 8; i++) {
        float a = blo(hw[2 * i]), b = bhi(hw[2 * i]);
        s0 += a + b; q0 = fmaf(a, a, q0); q0 = fmaf(b, b, q0);
        a = blo(hw[2 * i + 1]); b = bhi(hw[2 * i + 1]);
        s1 += a + b; q1 = fmaf(a, a, q1); q1 = fmaf(b, b, q1);
      }
      s0 += __shfl_xor_sync(0xffffffffu, s0, 1); s1 += __shfl_xor_sync(0xffffffffu, s1, 1);
      q0 += __shfl_xor_sync(0xffffffffu, q0, 1); q1 += __shfl_xor_sync(0xffffffffu, q1, 1);
      s0 += __shfl_xor_sync(0xffffffffu, s0, 2); s1 += __shfl_xor_sync(0xffffffffu, s1, 2);
      q0 += __shfl_xor_sync(0xffffffffu, q0, 2); q1 += __shfl_xor_sync(0xffffffffu, q1, 2);
      const int ch = cq * 2 + wg;
      if (t < 2) st_rlx2(&g_st[rh2 * 64 + wq * 16 + g + t * 8][ch], tg(__float_as_uint(t ? s1 : s0), T), tg(__float_as_uint(t ? q1 : q0), T));
      uint4* hp_ = &g_h[rh2][ch][wq][0][lane];
#pragma unroll
      for (int s = 0; s < 4; s++) st_rlx4(hp_ + s * 32, tg(hw[4 * s], T), tg(hw[4 * s + 1], T), tg(hw[4 * s + 2], T), tg(hw[4 * s + 3], T));
      uint32_t hx = T;
#pragma unroll
      for (int i = 0; i < 16; i++) hx |= (hw[i] & 1u) << (i + 1);
      st_rlx1(&g_hx[rh2][ch][wq][lane], hx);
      fence_async_smem();
      bar_sync(1 + wg, 128);
      if (lead) release(ST_WO + 5 - wg);
    }
    TSTAMP(11);

    const int rh3 = 2 * rb3 + wg;
    uint32_t HH[11][4];
    {
      uint32_t A[2][4][4];
      const uint4* hp_ = &g_h[rh3][0][wq][0][lane];
      ld_chunk(A[0], hp_);
      uint32_t m0, m1;
      {
        const uint4* sp = reinterpret_cast<const uint4*>(&g_st[rh3 * 64 + wq * 16 + g][2 * t]);
        uint32_t a[4], b[4];
        int it = 0;
#pragma unroll 1
        do {
          ld_rlx4(a, sp); ld_rlx4(b, sp + 8 * 4);
          if (++it > (1 << 18)) break;
        } while (__any_sync(0xffffffffu, (bad4(a, T) | bad4(b, T)) & 1));
        float s0 = __uint_as_float(a[0]) + __uint_as_float(a[2]), q0 = __uint_as_float(a[1]) + __uint_as_float(a[3]);
        float s1 = __uint_as_float(b[0]) + __uint_as_float(b[2]), q1 = __uint_as_float(b[1]) + __uint_as_float(b[3]);
        s0 += __shfl_xor_sync(0xffffffffu, s0, 1); s1 += __shfl_xor_sync(0xffffffffu, s1, 1);
        q0 += __shfl_xor_sync(0xffffffffu, q0, 1); q1 += __shfl_xor_sync(0xffffffffu, q1, 1);
        s0 += __shfl_xor_sync(0xffffffffu, s0, 2); s1 += __shfl_xor_sync(0xffffffffu, s1, 2);
        q0 += __shfl_xor_sync(0xffffffffu, q0, 2); q1 += __shfl_xor_sync(0xffffffffu, q1, 2);
        s0 *= (1.f / 512.f); s1 *= (1.f / 512.f);
        r0 = 1.f / (fmaxf(q0 * (1.f / 512.f) - s0 * s0, 0.f) + 1e-5f);
        r1 = 1.f / (fmaxf(q1 * (1.f / 512.f) - s1 * s1, 0.f) + 1e-5f);
        m0 = pack2(s0, s0); m1 = pack2(s1, s1);
      }
      TSTAMP(12);
      float ag[88], au[88];
      int slot = ST_GU % NSLOT;
#pragma unroll 1
      for (int c2 = 0; c2 < 8; c2 += 2) {
#pragma unroll
        for (int b = 0; b < 2; b++) {
          const int c = c2 + b, sG = ST_GU + 2 * c;
          chk_chunk(A[b], hp_ + c * 512, T);
#pragma unroll
          for (int s = 0; s < 4; s++) {
            A[b][s][0] = hsub2(A[b][s][0], m0); A[b][s][1] = hsub2(A[b][s][1], m1);
            A[b][s][2] = hsub2(A[b][s][2], m0); A[b][s][3] = hsub2(A[b][s][3], m1);
          }
          mbar_wait(sb + SM_FULL + sG * 8);
          wg_fence();
#pragma unroll
          for (int s = 0; s < 4; s++)
            wgmma_rs_n176(ag, A[b][s], mk_desc(sb + slot * SLOT + s * 2048, 8192, 1024), (c | s) != 0);
          wg_commit();
          if (++slot == NSLOT) slot = 0;
          wg_wait<1>();
          if (lead && c > 0) release(sG - 1);
          if (c < 7) ld_chunk(A[b ^ 1], hp_ + (c + 1) * 512);
          mbar_wait(sb + SM_FULL + (sG + 1) * 8);
          wg_fence();
#pragma unroll
          for (int s = 0; s < 4; s++)
            wgmma_rs_n176(au, A[b][s], mk_desc(sb + slot * SLOT + s * 2048, 8192, 1024), (c | s) != 0);
          wg_commit();
          if (++slot == NSLOT) slot = 0;
          wg_wait<1>();
          if (lead) release(sG);
        }
      }
      wg_wait<0>();
      TSTAMP(13);
#pragma unroll
      for (int s = 0; s < 11; s++) {
        HH[s][0] = pack2(ag[8 * s + 0] * au[8 * s + 0] * r0, ag[8 * s + 1] * au[8 * s + 1] * r0);
        HH[s][1] = pack2(ag[8 * s + 2] * au[8 * s + 2] * r1, ag[8 * s + 3] * au[8 * s + 3] * r1);
        HH[s][2] = pack2(ag[8 * s + 4] * au[8 * s + 4] * r0, ag[8 * s + 5] * au[8 * s + 5] * r0);
        HH[s][3] = pack2(ag[8 * s + 6] * au[8 * s + 6] * r1, ag[8 * s + 7] * au[8 * s + 7] * r1);
      }
    }
    TSTAMP(14);

    {
      float acc[32], sum[32];
      uint32_t in[4][4];
      ld_chunk(in, &g_h[rh3][jf][wq][0][lane]);
      {
        uint32_t hx; int it = 0;
#pragma unroll 1
        do {
          hx = ld_rlx1(&g_hx[rh3][jf][wq][lane]);
          if (++it > (1 << 18)) break;
        } while (__any_sync(0xffffffffu, (hx ^ T) & 1));
#pragma unroll
        for (int i = 0; i < 16; i++) {
          sum[2 * i]     = blo((in[i >> 2][i & 3] & 0xFFFEu) | ((hx >> (i + 1)) & 1u));
          sum[2 * i + 1] = bhi(in[i >> 2][i & 3]);
        }
      }
      const uint4* inb = &g_part[rh3][jf][0][wq][0][lane];
      uint4* outb = &g_part[rh3][0][jf][wq][0][lane];
      int slot = ST_D % NSLOT;
#pragma unroll 1
      for (int st = 0; st < 10; st++) {
        if (st < 8) {
          mbar_wait(sb + SM_FULL + (ST_D + st) * 8);
          wg_fence();
#pragma unroll
          for (int s = 0; s < 11; s++)
            wgmma_rs_n64(acc, HH[s], mk_desc(sb + slot * SLOT + s * 2048, 8192, 1024), s != 0);
          wg_commit();
          if (++slot == NSLOT) slot = 0;
        }
        if (st >= 3) {
          chk_chunk(in, inb + ((jf + 2 - st) & 7) * 512, T);
#pragma unroll
          for (int i = 0; i < 16; i++) { sum[2 * i] += blo(in[i >> 2][i & 3]); sum[2 * i + 1] += bhi(in[i >> 2][i & 3]); }
        }
        if (st >= 2 && st < 9) ld_chunk(in, inb + ((jf + 1 - st) & 7) * 512);
        wg_wait<0>();
        if (st < 7) {
          uint4* p = outb + ((jf + 1 + st) & 7) * 4096;
#pragma unroll
          for (int s = 0; s < 4; s++)
            st_rlx4(p + s * 32, tg(pack2(acc[8 * s + 0], acc[8 * s + 1]), T), tg(pack2(acc[8 * s + 2], acc[8 * s + 3]), T),
                    tg(pack2(acc[8 * s + 4], acc[8 * s + 5]), T), tg(pack2(acc[8 * s + 6], acc[8 * s + 7]), T));
        }
        if (st == 7) TSTAMP(15);
      }
      uint32_t* op = reinterpret_cast<uint32_t*>(out + (size_t)(rh3 * 64 + wq * 16 + g) * 512 + jf * 64 + 2 * t);
#pragma unroll
      for (int i = 0; i < 8; i++) {
        op[4 * i]           = pack2(sum[4 * i] + acc[4 * i], sum[4 * i + 1] + acc[4 * i + 1]);
        op[8 * 256 + 4 * i] = pack2(sum[4 * i + 2] + acc[4 * i + 2], sum[4 * i + 3] + acc[4 * i + 3]);
      }
    }
    TSTAMP(16);
    asm volatile("barrier.cluster.arrive.relaxed.aligned;" ::: "memory");
    asm volatile("barrier.cluster.wait.aligned;" ::: "memory");
  }
}

typedef CUresult (*EncodeFn)(CUtensorMap*, CUtensorMapDataType, cuuint32_t, void*, const cuuint64_t*, const cuuint64_t*,
                             const cuuint32_t*, const cuuint32_t*, CUtensorMapInterleave, CUtensorMapSwizzle,
                             CUtensorMapL2promotion, CUtensorMapFloatOOBfill);

void encode(EncodeFn fn, CUtensorMap* m, const void* base, int rank, const cuuint64_t* dims, const cuuint64_t* strides,
            const cuuint32_t* box) {
  cuuint32_t es[3] = {1, 1, 1};
  fn(m, CU_TENSOR_MAP_DATA_TYPE_BFLOAT16, (cuuint32_t)rank, const_cast<void*>(base), dims, strides, box, es,
     CU_TENSOR_MAP_INTERLEAVE_NONE, CU_TENSOR_MAP_SWIZZLE_128B, CU_TENSOR_MAP_L2_PROMOTION_L2_256B,
     CU_TENSOR_MAP_FLOAT_OOB_FILL_NONE);
}

}

extern "C" void kernel_launch(void* const* d_in, const int* in_sizes, int n_in, void* d_out, int out_size) {
  (void)in_sizes; (void)n_in; (void)out_size;
  const __nv_bfloat16* x    = (const __nv_bfloat16*)d_in[0];
  const __nv_bfloat16* wqkv = (const __nv_bfloat16*)d_in[1];
  const __nv_bfloat16* wphi = (const __nv_bfloat16*)d_in[2];
  const __nv_bfloat16* wo   = (const __nv_bfloat16*)d_in[3];
  const __nv_bfloat16* wg   = (const __nv_bfloat16*)d_in[5];
  const __nv_bfloat16* wu   = (const __nv_bfloat16*)d_in[6];
  const __nv_bfloat16* wd   = (const __nv_bfloat16*)d_in[7];

  static EncodeFn fn = nullptr;
  if (!fn) {
    void* p = nullptr;
    cudaDriverEntryPointQueryResult qr;
    cudaGetDriverEntryPoint("cuTensorMapEncodeTiled", &p, cudaEnableDefault, &qr);
    fn = (EncodeFn)p;
    cudaFuncSetAttribute(fused_kernel, cudaFuncAttributeMaxDynamicSharedMemorySize, SM_TOTAL);
  }
  Maps maps;
  {
    cuuint64_t d[3] = {64, 2048, 8}, s[2] = {1024, 128}; cuuint32_t b[3] = {64, 64, 3};
    encode(fn, &maps.x, x, 3, d, s, b);
  }
  {
    cuuint64_t d[2] = {1536, 512}, s[1] = {3072}; cuuint32_t b[2] = {64, 192};
    encode(fn, &maps.w, wqkv, 2, d, s, b);
  }
  {
    cuuint64_t d[3] = {64, 512, 8}, s[2] = {1024, 128}; cuuint32_t b[3] = {64, 96, 2}, b2[3] = {64, 64, 2};
    encode(fn, &maps.wo96, wo, 3, d, s, b);
    encode(fn, &maps.wo64, wo, 3, d, s, b2);
  }
  {
    cuuint64_t d[3] = {176, 7, 512}, d7[3] = {144, 1, 512}, s[2] = {352, 2752}; cuuint32_t b[3] = {64, 1, 64};
    encode(fn, &maps.g, wg, 3, d, s, b);
    encode(fn, &maps.u, wu, 3, d, s, b);
    encode(fn, &maps.g7, wg + 1232, 3, d7, s, b);
    encode(fn, &maps.u7, wu + 1232, 3, d7, s, b);
  }
  {
    cuuint64_t d[2] = {512, 1376}, s[1] = {1024}; cuuint32_t b[2] = {64, 176};
    encode(fn, &maps.d, wd, 2, d, s, b);
  }
  fused_kernel<<<NCTA, 384, SM_TOTAL>>>(maps, x, wphi, wo, wg, wu, wd, (__nv_bfloat16*)d_out);
}
```

```cpp
#include <cuda_runtime.h>
#include <cuda_bf16.h>
#include <cuda.h>
#include <stdint.h>

#define PROF 0

namespace {

constexpr int NCTA   = 128;
constexpr int SLOT   = 24576;
constexpr int NSLOT  = 9;
constexpr int NSTAGE = 44;

constexpr int ST_X0   = 0;
constexpr int ST_WK   = 3;
constexpr int ST_X1   = 6;
constexpr int ST_SCR0 = 9;
constexpr int ST_WV   = 10;
constexpr int ST_SCR1 = 13;
constexpr int ST_WQ   = 14;
constexpr int ST_WO   = 17;
constexpr int ST_GU   = 20;
constexpr int ST_D    = 36;

__host__ __device__ constexpr bool st_is_x(int s)   { return (s >= 0 && s < 3) || (s >= 6 && s < 9); }
__host__ __device__ constexpr int  st_bytes(int s)  { return s >= ST_D ? 22528 : 24576; }
__host__ __device__ constexpr int  st_empty_cnt(int d) {
  return (st_is_x(d) ? 4 : (d == ST_SCR0 || d == ST_SCR1) ? 1 : 2) * (d + NSLOT >= ST_WO ? 2 : 1);
}

constexpr int SM_ONES = NSLOT * SLOT;
constexpr int SM_WPHI = SM_ONES + 2048;
constexpr int SM_KVS  = SM_WPHI + 2048;
constexpr int SM_BAR  = SM_KVS + 6144;
constexpr int SM_FULL  = SM_BAR;
constexpr int SM_EMPTY = SM_BAR + NSTAGE * 8;
constexpr int SM_MISCB = SM_BAR + 2 * NSTAGE * 8;
constexpr int SM_KVB   = SM_MISCB + 8;
constexpr int SM_EPOCH = SM_KVB + 8;
constexpr int SM_TOTAL = SM_BAR + 1024;

static_assert(SM_TOTAL == 232448, "smem budget");

struct Maps { CUtensorMap x, w, wo, g, u, g7, u7, d; };

__device__ uint4    g_o[32][8][4][4][32];
__device__ uint4    g_h[32][8][4][4][32];
__device__ uint2    g_st[2048][8];
__device__ uint4    g_part[32][8][8][4][4][32];
__device__ float    g_kv[2][32 * 32 * 16];
__device__ float    g_z[2][32 * 32];
__device__ unsigned g_kvcnt[8 * 32];
__device__ unsigned g_start;

__device__ __forceinline__ uint32_t smem_u32(const void* p) { return (uint32_t)__cvta_generic_to_shared(p); }
__device__ __forceinline__ void mbar_init(uint32_t bar, int cnt) {
  asm volatile("mbarrier.init.shared::cta.b64 [%0], %1;" ::"r"(bar), "r"(cnt) : "memory");
}
__device__ __forceinline__ void mbar_expect_tx(uint32_t bar, uint32_t bytes) {
  asm volatile("mbarrier.arrive.expect_tx.shared::cta.b64 _, [%0], %1;" ::"r"(bar), "r"(bytes) : "memory");
}
__device__ __forceinline__ void mbar_arrive(uint32_t bar) {
  asm volatile("mbarrier.arrive.shared::cta.b64 _, [%0];" ::"r"(bar) : "memory");
}
__device__ __forceinline__ void mbar_arrive_cluster(uint32_t bar, uint32_t rank) {
  asm volatile("{\n.reg .b32 ra;\nmapa.shared::cluster.u32 ra, %0, %1;\n"
               "mbarrier.arrive.shared::cluster.b64 _, [ra];\n}" ::"r"(bar), "r"(rank) : "memory");
}
__device__ __forceinline__ bool mbar_try(uint32_t bar) {
  uint32_t ok;
  asm volatile("{\n.reg .pred p;\nmbarrier.try_wait.parity.shared::cta.b64 p, [%1], 0;\nselp.u32 %0, 1, 0, p;\n}"
               : "=r"(ok) : "r"(bar) : "memory");
  return ok != 0;
}
__device__ __forceinline__ void mbar_wait(uint32_t bar) {
  int it = 0;
#pragma unroll 1
  while (!mbar_try(bar)) {
    if (++it > (1 << 20)) __trap();
  }
}
__device__ __forceinline__ void bar_sync(int id, int n)   { asm volatile("bar.sync %0, %1;" ::"r"(id), "r"(n) : "memory"); }
__device__ __forceinline__ void bar_arrive(int id, int n) { asm volatile("bar.arrive %0, %1;" ::"r"(id), "r"(n) : "memory"); }
__device__ __forceinline__ void fence_async_smem() { asm volatile("fence.proxy.async.shared::cta;" ::: "memory"); }
__device__ __forceinline__ void wg_fence()  { asm volatile("wgmma.fence.sync.aligned;" ::: "memory"); }
__device__ __forceinline__ void wg_commit() { asm volatile("wgmma.commit_group.sync.aligned;" ::: "memory"); }
template <int N> __device__ __forceinline__ void wg_wait() { asm volatile("wgmma.wait_group.sync.aligned %0;" ::"n"(N) : "memory"); }
__device__ __forceinline__ uint64_t mk_desc(uint32_t addr, uint32_t lbo, uint32_t sbo) {
  return (uint64_t)((addr & 0x3FFFF) >> 4) | ((uint64_t)((lbo & 0x3FFFF) >> 4) << 16) | ((uint64_t)(sbo >> 4) << 32) | (1ull << 62);
}
__device__ __forceinline__ void tma2d(uint32_t dst, const CUtensorMap* m, int c0, int c1, uint32_t bar) {
  asm volatile("cp.async.bulk.tensor.2d.shared::cluster.global.mbarrier::complete_tx::bytes [%0], [%1, {%3, %4}], [%2];"
               ::"r"(dst), "l"(m), "r"(bar), "r"(c0), "r"(c1) : "memory");
}
__device__ __forceinline__ void tma2d_mc(uint32_t dst, const CUtensorMap* m, int c0, int c1, uint32_t bar) {
  asm volatile("cp.async.bulk.tensor.2d.shared::cluster.global.mbarrier::complete_tx::bytes.multicast::cluster [%0], [%1, {%3, %4}], [%2], %5;"
               ::"r"(dst), "l"(m), "r"(bar), "r"(c0), "r"(c1), "h"((uint16_t)3) : "memory");
}
__device__ __forceinline__ void tma3d(uint32_t dst, const CUtensorMap* m, int c0, int c1, int c2, uint32_t bar) {
  asm volatile("cp.async.bulk.tensor.3d.shared::cluster.global.mbarrier::complete_tx::bytes [%0], [%1, {%3, %4, %5}], [%2];"
               ::"r"(dst), "l"(m), "r"(bar), "r"(c0), "r"(c1), "r"(c2) : "memory");
}
__device__ __forceinline__ void tma3d_mc(uint32_t dst, const CUtensorMap* m, int c0, int c1, int c2, uint32_t bar) {
  asm volatile("cp.async.bulk.tensor.3d.shared::cluster.global.mbarrier::complete_tx::bytes.multicast::cluster [%0], [%1, {%3, %4, %5}], [%2], %6;"
               ::"r"(dst), "l"(m), "r"(bar), "r"(c0), "r"(c1), "r"(c2), "h"((uint16_t)3) : "memory");
}
__device__ __forceinline__ void ldsm4(uint32_t (&r)[4], uint32_t addr) {
  asm volatile("ldmatrix.sync.aligned.m8n8.x4.shared.b16 {%0,%1,%2,%3}, [%4];"
               : "=r"(r[0]), "=r"(r[1]), "=r"(r[2]), "=r"(r[3]) : "r"(addr) : "memory");
}
__device__ __forceinline__ void ldsm4t(uint32_t (&r)[4], uint32_t addr) {
  asm volatile("ldmatrix.sync.aligned.m8n8.x4.trans.shared.b16 {%0,%1,%2,%3}, [%4];"
               : "=r"(r[0]), "=r"(r[1]), "=r"(r[2]), "=r"(r[3]) : "r"(addr) : "memory");
}
__device__ __forceinline__ void stsm4(uint32_t addr, uint32_t r0, uint32_t r1, uint32_t r2, uint32_t r3) {
  asm volatile("stmatrix.sync.aligned.m8n8.x4.shared.b16 [%0], {%1,%2,%3,%4};"
               ::"r"(addr), "r"(r0), "r"(r1), "r"(r2), "r"(r3) : "memory");
}
__device__ __forceinline__ void mma16816(float (&c)[4], const uint32_t (&a)[4], uint32_t b0, uint32_t b1) {
  asm volatile("mma.sync.aligned.m16n8k16.row.col.f32.bf16.bf16.f32 {%0,%1,%2,%3},{%4,%5,%6,%7},{%8,%9},{%0,%1,%2,%3};"
               : "+f"(c[0]), "+f"(c[1]), "+f"(c[2]), "+f"(c[3])
               : "r"(a[0]), "r"(a[1]), "r"(a[2]), "r"(a[3]), "r"(b0), "r"(b1));
}
__device__ __forceinline__ uint32_t pack2(float lo, float hi) {
  uint32_t r; asm("cvt.rn.bf16x2.f32 %0, %1, %2;" : "=r"(r) : "f"(hi), "f"(lo)); return r;
}
__device__ __forceinline__ float blo(uint32_t w) { return __uint_as_float(w << 16); }
__device__ __forceinline__ float bhi(uint32_t w) { return __uint_as_float(w & 0xFFFF0000u); }
__device__ __forceinline__ uint32_t hsub2(uint32_t a, uint32_t b) { uint32_t r; asm("sub.rn.bf16x2 %0, %1, %2;" : "=r"(r) : "r"(a), "r"(b)); return r; }
__device__ __forceinline__ uint32_t hmax2(uint32_t a, uint32_t b) { uint32_t r; asm("max.bf16x2 %0, %1, %2;" : "=r"(r) : "r"(a), "r"(b)); return r; }
__device__ __forceinline__ uint32_t hmin2(uint32_t a, uint32_t b) { uint32_t r; asm("min.bf16x2 %0, %1, %2;" : "=r"(r) : "r"(a), "r"(b)); return r; }
__device__ __forceinline__ float ex2(float x) { float r; asm("ex2.approx.ftz.f32 %0, %1;" : "=f"(r) : "f"(x)); return r; }
__device__ __forceinline__ float rcp(float x) { float r; asm("rcp.approx.ftz.f32 %0, %1;" : "=f"(r) : "f"(x)); return r; }
__device__ __forceinline__ void ld_rlx4(uint32_t (&r)[4], const uint4* p) {
  asm volatile("ld.relaxed.gpu.global.v4.b32 {%0,%1,%2,%3}, [%4];"
               : "=r"(r[0]), "=r"(r[1]), "=r"(r[2]), "=r"(r[3]) : "l"(p) : "memory");
}
__device__ __forceinline__ void st_rlx4(uint4* p, uint32_t a, uint32_t b, uint32_t c, uint32_t d) {
  asm volatile("st.relaxed.gpu.global.v4.b32 [%0], {%1,%2,%3,%4};" ::"l"(p), "r"(a), "r"(b), "r"(c), "r"(d) : "memory");
}
__device__ __forceinline__ void st_rlx2(uint2* p, uint32_t a, uint32_t b) {
  asm volatile("st.relaxed.gpu.global.v2.b32 [%0], {%1,%2};" ::"l"(p), "r"(a), "r"(b) : "memory");
}
__device__ __forceinline__ uint32_t ld_rlx1(const uint32_t* p) {
  uint32_t r; asm volatile("ld.relaxed.gpu.global.b32 %0, [%1];" : "=r"(r) : "l"(p) : "memory"); return r;
}
__device__ __forceinline__ uint32_t tg(uint32_t w, uint32_t T) { return (w & 0xFFFFFFFEu) | T; }
__device__ __forceinline__ uint32_t bad4(const uint32_t (&r)[4], uint32_t T) { return (r[0] ^ T) | (r[1] ^ T) | (r[2] ^ T) | (r[3] ^ T); }

__device__ __forceinline__ void ld_chunk(uint32_t (&a)[4][4], const uint4* p) {
#pragma unroll
  for (int s = 0; s < 4; s++) ld_rlx4(a[s], p + s * 32);
}
__device__ __forceinline__ void chk_chunk(uint32_t (&a)[4][4], const uint4* p, uint32_t T) {
  int it = 0;
#pragma unroll 1
  while (__any_sync(0xffffffffu, (bad4(a[0], T) | bad4(a[1], T) | bad4(a[2], T) | bad4(a[3], T)) & 1)) {
    ld_chunk(a, p);
    if (++it > (1 << 18)) break;
  }
}

__device__ __forceinline__ void wgmma_rs_n64(float (&d)[32], const uint32_t (&a)[4], uint64_t descB, int scaleD) {
  asm volatile("{\n.reg .pred p;\nsetp.ne.b32 p, %37, 0;\n"
    "wgmma.mma_async.sync.aligned.m64n64k16.f32.bf16.bf16 {%0,%1,%2,%3,%4,%5,%6,%7,%8,%9,%10,%11,%12,%13,%14,%15,%16,%17,%18,%19,%20,%21,%22,%23,%24,%25,%26,%27,%28,%29,%30,%31}, {%32,%33,%34,%35}, %36, p, 1, 1, 1;\n}\n"
    : "+f"(d[0]),"+f"(d[1]),"+f"(d[2]),"+f"(d[3]),"+f"(d[4]),"+f"(d[5]),"+f"(d[6]),"+f"(d[7]),"+f"(d[8]),"+f"(d[9]),"+f"(d[10]),"+f"(d[11]),"+f"(d[12]),"+f"(d[13]),"+f"(d[14]),"+f"(d[15]),"+f"(d[16]),"+f"(d[17]),"+f"(d[18]),"+f"(d[19]),"+f"(d[20]),"+f"(d[21]),"+f"(d[22]),"+f"(d[23]),"+f"(d[24]),"+f"(d[25]),"+f"(d[26]),"+f"(d[27]),"+f"(d[28]),"+f"(d[29]),"+f"(d[30]),"+f"(d[31])
    : "r"(a[0]), "r"(a[1]), "r"(a[2]), "r"(a[3]), "l"(descB), "r"(scaleD));
}
__device__ __forceinline__ void wgmma_rs_n176(float (&d)[88], const uint32_t (&a)[4], uint64_t descB, int scaleD) {
  asm volatile("{\n.reg .pred p;\nsetp.ne.b32 p, %93, 0;\n"
    "wgmma.mma_async.sync.aligned.m64n176k16.f32.bf16.bf16 {%0,%1,%2,%3,%4,%5,%6,%7,%8,%9,%10,%11,%12,%13,%14,%15,%16,%17,%18,%19,%20,%21,%22,%23,%24,%25,%26,%27,%28,%29,%30,%31,%32,%33,%34,%35,%36,%37,%38,%39,%40,%41,%42,%43,%44,%45,%46,%47,%48,%49,%50,%51,%52,%53,%54,%55,%56,%57,%58,%59,%60,%61,%62,%63,%64,%65,%66,%67,%68,%69,%70,%71,%72,%73,%74,%75,%76,%77,%78,%79,%80,%81,%82,%83,%84,%85,%86,%87}, {%88,%89,%90,%91}, %92, p, 1, 1, 1;\n}\n"
    : "+f"(d[0]),"+f"(d[1]),"+f"(d[2]),"+f"(d[3]),"+f"(d[4]),"+f"(d[5]),"+f"(d[6]),"+f"(d[7]),"+f"(d[8]),"+f"(d[9]),"+f"(d[10]),"+f"(d[11]),"+f"(d[12]),"+f"(d[13]),"+f"(d[14]),"+f"(d[15]),"+f"(d[16]),"+f"(d[17]),"+f"(d[18]),"+f"(d[19]),"+f"(d[20]),"+f"(d[21]),"+f"(d[22]),"+f"(d[23]),"+f"(d[24]),"+f"(d[25]),"+f"(d[26]),"+f"(d[27]),"+f"(d[28]),"+f"(d[29]),"+f"(d[30]),"+f"(d[31]),"+f"(d[32]),"+f"(d[33]),"+f"(d[34]),"+f"(d[35]),"+f"(d[36]),"+f"(d[37]),"+f"(d[38]),"+f"(d[39]),"+f"(d[40]),"+f"(d[41]),"+f"(d[42]),"+f"(d[43]),"+f"(d[44]),"+f"(d[45]),"+f"(d[46]),"+f"(d[47]),"+f"(d[48]),"+f"(d[49]),"+f"(d[50]),"+f"(d[51]),"+f"(d[52]),"+f"(d[53]),"+f"(d[54]),"+f"(d[55]),"+f"(d[56]),"+f"(d[57]),"+f"(d[58]),"+f"(d[59]),"+f"(d[60]),"+f"(d[61]),"+f"(d[62]),"+f"(d[63]),"+f"(d[64]),"+f"(d[65]),"+f"(d[66]),"+f"(d[67]),"+f"(d[68]),"+f"(d[69]),"+f"(d[70]),"+f"(d[71]),"+f"(d[72]),"+f"(d[73]),"+f"(d[74]),"+f"(d[75]),"+f"(d[76]),"+f"(d[77]),"+f"(d[78]),"+f"(d[79]),"+f"(d[80]),"+f"(d[81]),"+f"(d[82]),"+f"(d[83]),"+f"(d[84]),"+f"(d[85]),"+f"(d[86]),"+f"(d[87])
    : "r"(a[0]), "r"(a[1]), "r"(a[2]), "r"(a[3]), "l"(descB), "r"(scaleD));
}
__device__ __forceinline__ void wgmma_ss_n72_t11(float (&d)[36], uint64_t descA, uint64_t descB, int scaleD) {
  asm volatile("{\n.reg .pred p;\nsetp.ne.b32 p, %38, 0;\n"
    "wgmma.mma_async.sync.aligned.m64n72k16.f32.bf16.bf16 {%0,%1,%2,%3,%4,%5,%6,%7,%8,%9,%10,%11,%12,%13,%14,%15,%16,%17,%18,%19,%20,%21,%22,%23,%24,%25,%26,%27,%28,%29,%30,%31,%32,%33,%34,%35}, %36, %37, p, 1, 1, 1, 1;\n}\n"
    : "+f"(d[0]),"+f"(d[1]),"+f"(d[2]),"+f"(d[3]),"+f"(d[4]),"+f"(d[5]),"+f"(d[6]),"+f"(d[7]),"+f"(d[8]),"+f"(d[9]),"+f"(d[10]),"+f"(d[11]),"+f"(d[12]),"+f"(d[13]),"+f"(d[14]),"+f"(d[15]),"+f"(d[16]),"+f"(d[17]),"+f"(d[18]),"+f"(d[19]),"+f"(d[20]),"+f"(d[21]),"+f"(d[22]),"+f"(d[23]),"+f"(d[24]),"+f"(d[25]),"+f"(d[26]),"+f"(d[27]),"+f"(d[28]),"+f"(d[29]),"+f"(d[30]),"+f"(d[31]),"+f"(d[32]),"+f"(d[33]),"+f"(d[34]),"+f"(d[35])
    : "l"(descA), "l"(descB), "r"(scaleD));
}

#define TSTAMP(i) do {} while (0)
#define TS2(w, i) do {} while (0)

constexpr float LOG2E = 1.4426950408889634f;

__device__ __forceinline__ void feat_exp(const float (&p0)[4], const float (&p1)[4], float (&e)[16]) {
  uint32_t P0 = pack2(p0[0], p0[1]), P1 = pack2(p0[2], p0[3]), P2 = pack2(p1[0], p1[1]), P3 = pack2(p1[2], p1[3]);
  uint32_t a = hmax2(P0, P2), b = hmax2(P1, P3);
  uint32_t mx = hmax2(__byte_perm(a, b, 0x5410), __byte_perm(a, b, 0x7632));
  a = hmin2(P0, P2); b = hmin2(P1, P3);
  uint32_t mn = hmin2(__byte_perm(a, b, 0x5410), __byte_perm(a, b, 0x7632));
  mx = hmax2(mx, __shfl_xor_sync(0xffffffffu, mx, 1));
  mn = hmin2(mn, __shfl_xor_sync(0xffffffffu, mn, 1));
  mx = hmax2(mx, __shfl_xor_sync(0xffffffffu, mx, 2));
  mn = hmin2(mn, __shfl_xor_sync(0xffffffffu, mn, 2));
  float mx0 = -blo(mx) * LOG2E, mx1 = -bhi(mx) * LOG2E, mn0 = blo(mn) * LOG2E, mn1 = bhi(mn) * LOG2E;
  float v[8] = {blo(P0), bhi(P0), blo(P1), bhi(P1), blo(P2), bhi(P2), blo(P3), bhi(P3)};
#pragma unroll
  for (int i = 0; i < 8; i++) {
    bool r1 = (i >> 1) & 1;
    e[i]     = ex2(fmaf(v[i],  LOG2E, r1 ? mx1 : mx0));
    e[8 + i] = ex2(fmaf(v[i], -LOG2E, r1 ? mn1 : mn0));
  }
}

__global__ void __cluster_dims__(2, 1, 1) __launch_bounds__(384, 1)
fused_kernel(const __grid_constant__ Maps maps, const __nv_bfloat16* __restrict__ x, const __nv_bfloat16* __restrict__ wphi,
             const __nv_bfloat16* __restrict__ wo, const __nv_bfloat16* __restrict__ wg_, const __nv_bfloat16* __restrict__ wu_,
             const __nv_bfloat16* __restrict__ wd_, __nv_bfloat16* __restrict__ out) {
  extern __shared__ __align__(1024) unsigned char smem[];
  const uint32_t sb = smem_u32(smem);
  const int tid = threadIdx.x, lane = tid & 31;
  const int warp = __shfl_sync(0xffffffffu, tid >> 5, 0);
  const uint32_t rank = blockIdx.x & 1;
  const int cl = blockIdx.x >> 1;
  int quad, qi;
  if (cl < 4) { quad = 15; qi = cl; }
  else if (cl < 36) { quad = (cl - 4) & 7; qi = (cl - 4) >> 3; }
  else { qi = (cl - 36) / 7; quad = 8 + (cl - 36) - 7 * qi; }
  const int rb = 4 * (quad >> 2) + qi, hg = 2 * (quad & 3) + rank;
  const int rb3 = (quad & ~1) + rank, jf = 4 * (quad & 1) + qi;

  if (lane == 0) {
    if (warp >= 8) {
      if (warp < 11) {
        const int s0 = 3 * (warp - 8);
#pragma unroll
        for (int i = 0; i < 3; i++) { mbar_init(sb + SM_FULL + (s0 + i) * 8, 1); mbar_expect_tx(sb + SM_FULL + (s0 + i) * 8, SLOT); }
        asm volatile("fence.mbarrier_init.release.cluster;" ::: "memory");
        fence_async_smem();
#pragma unroll
        for (int i = 0; i < 3; i++) {
          if (warp == 9) tma2d(sb + (s0 + i) * SLOT, &maps.w, 512 + hg * 64, i * 192, sb + SM_FULL + (s0 + i) * 8);
          else tma3d(sb + (s0 + i) * SLOT, &maps.x, 0, rb * 128 + (warp - 8) * 32, 3 * i, sb + SM_FULL + (s0 + i) * 8);
        }
      } else {
        mbar_init(sb + SM_MISCB, 3);
        mbar_init(sb + SM_KVB, 3);
        asm volatile("fence.mbarrier_init.release.cluster;" ::: "memory");
      }
    } else {
#pragma unroll
      for (int i = 0; i < 5; i++) {
        const int d = warp * 5 + i;
        if (d + NSLOT < NSTAGE) {
          mbar_init(sb + SM_EMPTY + d * 8, st_empty_cnt(d));
          mbar_init(sb + SM_FULL + (d + NSLOT) * 8, 1);
          mbar_expect_tx(sb + SM_FULL + (d + NSLOT) * 8, st_bytes(d + NSLOT));
        }
      }
      asm volatile("fence.mbarrier_init.release.cluster;" ::: "memory");
    }
  }
  if (tid == 256) TS2(0, 18);
  __syncthreads();
  if (tid == 256) TS2(1, 18);
  asm volatile("barrier.cluster.arrive.relaxed.aligned;" ::: "memory");

  if (warp >= 8) {
    asm volatile("setmaxnreg.dec.sync.aligned.u32 24;");
    if (warp == 8) {
      asm volatile("barrier.cluster.wait.aligned;" ::: "memory");
      if (lane == 0) {
        const CUtensorMap* mgu = rank ? (jf == 7 ? &maps.u7 : &maps.u) : (jf == 7 ? &maps.g7 : &maps.g);
        asm volatile("prefetch.tensormap [%0];" ::"l"(&maps.wo) : "memory");
        asm volatile("prefetch.tensormap [%0];" ::"l"(mgu) : "memory");
        asm volatile("prefetch.tensormap [%0];" ::"l"(&maps.d) : "memory");
#pragma unroll 1
        for (int s = ST_WV; s < ST_WO; s++) {
          if (s == ST_SCR1) continue;
          mbar_wait(sb + SM_EMPTY + (s - NSLOT) * 8);
          tma2d(sb + (s - NSLOT) * SLOT, &maps.w, (s < ST_WQ ? 1024 : 0) + hg * 64, (s < ST_WQ ? s - ST_WV : s - ST_WQ) * 192,
                sb + SM_FULL + s * 8);
        }
        const int jc = jf == 7 ? 0 : jf;
        int slot = (ST_WO + 1 - rank) % NSLOT;
#pragma unroll 1
        for (int s = ST_WO + 1 - rank; s < NSTAGE; s += 2) {
          mbar_wait(sb + SM_EMPTY + (s - NSLOT) * 8);
          const uint32_t dst = sb + slot * SLOT, bar = sb + SM_FULL + s * 8;
          if (s < ST_GU) {
            tma2d_mc(dst, &maps.wo, jf * 64, (s - ST_WO) * 192, bar);
          } else if (s < ST_D) {
            const int c = (s - ST_GU) >> 1;
#pragma unroll
            for (int b = 0; b < 3; b++) tma3d_mc(dst + b * 8192, mgu, b * 64, jc, c * 64, bar);
          } else {
            tma2d_mc(dst, &maps.d, ((jf + 1 + (s - ST_D)) & 7) * 64, jf * 176, bar);
          }
          slot += 2; if (slot >= NSLOT) slot -= NSLOT;
        }
      }
      __syncwarp();
    } else {
      const int ht = tid - 288;
      if (ht == 0) {
        unsigned old = atomicAdd(&g_start, 1u);
        *reinterpret_cast<volatile unsigned*>(smem + SM_EPOCH) = old / NCTA;
      }
#pragma unroll 1
      for (int i = ht; i < 128; i += 96) {
        reinterpret_cast<uint4*>(smem + SM_ONES)[i] = make_uint4(0x3F803F80u, 0x3F803F80u, 0x3F803F80u, 0x3F803F80u);
        reinterpret_cast<uint4*>(smem + SM_WPHI)[i] = __ldg(reinterpret_cast<const uint4*>(wphi + hg * 1024) + i);
      }
      fence_async_smem();
      __syncwarp();
      if (lane == 0) mbar_arrive(sb + SM_MISCB);
      asm volatile("barrier.cluster.wait.aligned;" ::: "memory");
      mbar_wait(sb + SM_MISCB);
      const unsigned epoch = *reinterpret_cast<volatile unsigned*>(smem + SM_EPOCH);
      const int par = epoch & 1;
      if (ht < 32) reinterpret_cast<float4*>(&g_kv[par ^ 1][blockIdx.x * 128])[ht] = make_float4(0.f, 0.f, 0.f, 0.f);
      else if (ht < 40) g_z[par ^ 1][blockIdx.x * 8 + (ht - 32)] = 0.f;
      if (warp == 11) {
        mbar_wait(sb + SM_FULL + (ST_X1 + 2) * 8);
        if (lane == 0) {
          asm volatile("cp.async.bulk.prefetch.L2.global [%0], 4096;" ::"l"((const char*)wo + blockIdx.x * 4096) : "memory");
          asm volatile("cp.async.bulk.prefetch.L2.global [%0], 11008;" ::"l"((const char*)wg_ + blockIdx.x * 11008) : "memory");
          asm volatile("cp.async.bulk.prefetch.L2.global [%0], 11008;" ::"l"((const char*)wu_ + blockIdx.x * 11008) : "memory");
          asm volatile("cp.async.bulk.prefetch.L2.global [%0], 11008;" ::"l"((const char*)wd_ + blockIdx.x * 11008) : "memory");
        }
        __syncwarp();
      } else {
        bar_sync(6 + (warp - 9), 160);
        if (lane == 0) {
          asm volatile("fence.acq_rel.gpu;" ::: "memory");
          TS2(warp - 9, 25);
          asm volatile("red.relaxed.gpu.global.add.u32 [%0], 1;" ::"l"(&g_kvcnt[hg * 32]) : "memory");
        }
        __syncwarp();
      }
      if (lane == 0) {
        const unsigned target = (epoch + 1) * 32;
        unsigned v; int it = 0;
#pragma unroll 1
        do {
          asm volatile("ld.acquire.gpu.global.u32 %0, [%1];" : "=r"(v) : "l"(&g_kvcnt[hg * 32]) : "memory");
          if (++it > (1 << 18)) break;
        } while ((int)(v - target) < 0);
        if (warp == 9) TS2(0, 26);
      }
      __syncwarp();
      {
        const float4* src = reinterpret_cast<const float4*>(&g_kv[par][hg * 2048]);
#pragma unroll 1
        for (int r = ht; r < 128; r += 96) {
          const float4 a = __ldcg(src + r * 4), b = __ldcg(src + r * 4 + 1), c = __ldcg(src + r * 4 + 2), d = __ldcg(src + r * 4 + 3);
          const uint32_t zz = pack2(__ldcg(&g_z[par][hg * 128 + r]), 1.0f);
          uint4* dst = reinterpret_cast<uint4*>(smem + SM_KVS + r * 48);
          dst[0] = make_uint4(pack2(a.x, a.y), pack2(a.z, a.w), pack2(b.x, b.y), pack2(b.z, b.w));
          dst[1] = make_uint4(pack2(c.x, c.y), pack2(c.z, c.w), pack2(d.x, d.y), pack2(d.z, d.w));
          dst[2] = make_uint4(zz, zz, zz, zz);
        }
      }
      __syncwarp();
      if (lane == 0) mbar_arrive(sb + SM_KVB);
    }
    asm volatile("barrier.cluster.arrive.relaxed.aligned;" ::: "memory");
    asm volatile("barrier.cluster.wait.aligned;" ::: "memory");
  } else {
    asm volatile("setmaxnreg.inc.sync.aligned.u32 240;");
    asm volatile("barrier.cluster.wait.aligned;" ::: "memory");
    const int wg = warp >> 2, wq = warp & 3, g = lane >> 2, t = lane & 3;
    const bool lead = (tid & 127) == 0;
    auto release = [&](int d) {
      const int s = d + NSLOT;
      if (s < NSTAGE) mbar_arrive_cluster(sb + SM_EMPTY + d * 8, s >= ST_WO ? (uint32_t)(s & 1) : rank);
    };
    const uint32_t lrow = (uint32_t)(wq * 16 + (lane & 7) + ((lane >> 3) & 1) * 8) * 128;
    const uint32_t lx = lane & 7, lhi = lane >> 4;
    if (wg == 1) bar_arrive(4, 256);
    TSTAMP(0);

    float r0, r1;
    uint32_t E[4][8];
    uint32_t T = 0;
    {
      uint32_t A[32][4];
      const int sx = wg ? ST_X1 : ST_X0;
      uint32_t m0, m1;
      {
        float sa[4] = {0.f, 0.f, 0.f, 0.f}, qa[4] = {0.f, 0.f, 0.f, 0.f}, qb[4] = {0.f, 0.f, 0.f, 0.f};
        const uint32_t rr = lane >> 1;
        const uint32_t sbase = sb + sx * SLOT + (wq * 16 + rr) * 128;
#pragma unroll 1
        for (int c = 0; c < 8; c++) {
          if (c == 0 || c == 3 || c == 6) mbar_wait(sb + SM_FULL + (sx + c / 3) * 8);
          uint32_t v[4][4];
#pragma unroll
          for (int i = 0; i < 4; i++)
            asm volatile("ld.shared.v4.b32 {%0,%1,%2,%3}, [%4];" : "=r"(v[i][0]), "=r"(v[i][1]), "=r"(v[i][2]), "=r"(v[i][3])
                         : "r"(sbase + c * 8192 + ((((lane & 1) * 4 + i) ^ (rr & 7)) << 4)) : "memory");
#pragma unroll
          for (int i = 0; i < 4; i++)
#pragma unroll
            for (int k = 0; k < 4; k++) {
              const float a = blo(v[i][k]), b = bhi(v[i][k]);
              sa[k] += a + b; qa[k] = fmaf(a, a, qa[k]); qb[k] = fmaf(b, b, qb[k]);
            }
        }
        float s = (sa[0] + sa[1]) + (sa[2] + sa[3]);
        float q = ((qa[0] + qa[1]) + (qa[2] + qa[3])) + ((qb[0] + qb[1]) + (qb[2] + qb[3]));
        s += __shfl_xor_sync(0xffffffffu, s, 1); q += __shfl_xor_sync(0xffffffffu, q, 1);
        s *= (1.f / 512.f);
        const float r = rsqrtf(fmaxf(q * (1.f / 512.f) - s * s, 0.f) + 1e-5f);
        const uint32_t m = pack2(s, s);
        m0 = __shfl_sync(0xffffffffu, m, 2 * g); m1 = __shfl_sync(0xffffffffu, m, 2 * g + 16);
        r0 = __shfl_sync(0xffffffffu, r, 2 * g); r1 = __shfl_sync(0xffffffffu, r, 2 * g + 16);
      }
      TSTAMP(17);
      {
        const uint32_t base = sb + sx * SLOT + lrow;
#pragma unroll
        for (int ks = 0; ks < 32; ks++) {
          ldsm4(A[ks], base + (ks >> 2) * 8192 + (((2 * (ks & 3) + lhi) ^ lx) << 4));
          A[ks][0] = hsub2(A[ks][0], m0); A[ks][1] = hsub2(A[ks][1], m1);
          A[ks][2] = hsub2(A[ks][2], m0); A[ks][3] = hsub2(A[ks][3], m1);
        }
        __syncwarp();
        if (lane < 3) release(sx + lane);
      }
      TSTAMP(1);

      const uint32_t scr = sb + (wg ? (ST_SCR1 % NSLOT) : (ST_SCR0 % NSLOT)) * SLOT;
#pragma unroll 1
      for (int ps = 0; ps < 3; ps++) {
        const int st0 = ps == 0 ? ST_WK : (ps == 1 ? ST_WV : ST_WQ);
        const uint32_t wbase = sb + (ps == 0 ? ST_WK % NSLOT : (ps == 1 ? ST_WV % NSLOT : ST_WQ % NSLOT)) * SLOT;
        float acc[32];
        bar_sync(4 + wg, 256);
#pragma unroll
        for (int i = 0; i < 3; i++) {
          mbar_wait(sb + SM_FULL + (st0 + i) * 8);
          wg_fence();
#pragma unroll
          for (int kk = 0; kk < (i < 2 ? 12 : 8); kk++)
            wgmma_rs_n64(acc, A[12 * i + kk], mk_desc(wbase + i * SLOT + kk * 2048, 8192, 1024), (i | kk) != 0);
          wg_commit();
          if (i > 0) { wg_wait<1>(); if (lead) release(st0 + i - 1); }
        }
        if (ps < 2 || wg == 0) bar_arrive(4 + (wg ^ 1), 256);
        wg_wait<0>();
        if (lead) release(st0 + 2);
        TSTAMP(2 + 2 * ps);
        uint32_t a[4][4];
#pragma unroll
        for (int h = 0; h < 4; h++) {
          a[h][0] = pack2(acc[8 * h + 0] * r0, acc[8 * h + 1] * r0); a[h][1] = pack2(acc[8 * h + 2] * r1, acc[8 * h + 3] * r1);
          a[h][2] = pack2(acc[8 * h + 4] * r0, acc[8 * h + 5] * r0); a[h][3] = pack2(acc[8 * h + 6] * r1, acc[8 * h + 7] * r1);
        }
        if (ps != 1) {
          if (ps == 0) {
            mbar_wait(sb + SM_MISCB);
            T = (*reinterpret_cast<volatile unsigned*>(smem + SM_EPOCH) & 1) ^ 1;
            mbar_wait(sb + SM_EMPTY + (wg ? ST_SCR1 - NSLOT : ST_SCR0 - NSLOT) * 8);
          }
          float pp[4][2][4];
#pragma unroll
          for (int h = 0; h < 4; h++) {
            uint32_t b[4];
            ldsm4t(b, sb + SM_WPHI + h * 512 + ((lane & 7) + ((lane >> 3) & 1) * 8) * 32 + lhi * 16);
#pragma unroll
            for (int i = 0; i < 4; i++) { pp[h][0][i] = 0.f; pp[h][1][i] = 0.f; }
            mma16816(pp[h][0], a[h], b[0], b[1]);
            mma16816(pp[h][1], a[h], b[2], b[3]);
          }
          float e[4][16];
#pragma unroll
          for (int h = 0; h < 4; h++) feat_exp(pp[h][0], pp[h][1], e[h]);
          if (ps == 0) {
#pragma unroll
            for (int h = 0; h < 4; h++) {
              const float (&f)[16] = e[h];
              float sp0 = (f[0] + f[1]) + (f[4] + f[5]), sp1 = (f[2] + f[3]) + (f[6] + f[7]);
              float sn0 = (f[8] + f[9]) + (f[12] + f[13]), sn1 = (f[10] + f[11]) + (f[14] + f[15]);
              sp0 += __shfl_xor_sync(0xffffffffu, sp0, 1); sp1 += __shfl_xor_sync(0xffffffffu, sp1, 1);
              sn0 += __shfl_xor_sync(0xffffffffu, sn0, 1); sn1 += __shfl_xor_sync(0xffffffffu, sn1, 1);
              sp0 += __shfl_xor_sync(0xffffffffu, sp0, 2); sp1 += __shfl_xor_sync(0xffffffffu, sp1, 2);
              sn0 += __shfl_xor_sync(0xffffffffu, sn0, 2); sn1 += __shfl_xor_sync(0xffffffffu, sn1, 2);
              sp0 = rcp(sp0); sp1 = rcp(sp1); sn0 = rcp(sn0); sn1 = rcp(sn1);
              const uint32_t dst = scr + (h >> 1) * 8192 + lrow;
              stsm4(dst + ((((h & 1) * 4 + lhi) ^ lx) << 4), pack2(f[0] * sp0, f[1] * sp0), pack2(f[2] * sp1, f[3] * sp1),
                    pack2(f[4] * sp0, f[5] * sp0), pack2(f[6] * sp1, f[7] * sp1));
              stsm4(dst + ((((h & 1) * 4 + 2 + lhi) ^ lx) << 4), pack2(f[8] * sn0, f[9] * sn0), pack2(f[10] * sn1, f[11] * sn1),
                    pack2(f[12] * sn0, f[13] * sn0), pack2(f[14] * sn1, f[15] * sn1));
            }
          } else {
#pragma unroll
            for (int h = 0; h < 4; h++)
#pragma unroll
              for (int i = 0; i < 8; i++) A[2 * h + (i >> 2)][i & 3] = pack2(e[h][2 * i], e[h][2 * i + 1]);
          }
        } else {
#pragma unroll
          for (int h = 0; h < 4; h++) stsm4(scr + 16384 + lrow + (((2 * h + lhi) ^ lx) << 4), a[h][0], a[h][1], a[h][2], a[h][3]);
          fence_async_smem();
          bar_sync(1 + wg, 128);
          float kv0[36], kv1[36];
          wg_fence();
#pragma unroll
          for (int ks = 0; ks < 4; ks++) {
            const uint32_t vb = scr + 16384 + ks * 2048;
            const uint64_t db = mk_desc(vb, sb + SM_ONES - vb, 1024);
            wgmma_ss_n72_t11(kv0, mk_desc(scr + ks * 2048, 8192, 1024), db, ks != 0);
            wgmma_ss_n72_t11(kv1, mk_desc(scr + 8192 + ks * 2048, 8192, 1024), db, ks != 0);
          }
          wg_commit();
          wg_wait<0>();
          if (lead) release(wg ? ST_SCR1 : ST_SCR0);
          const bool up = wq >= 2;
          const int f = (wq & 1) * 16 + g;
          float* kvp = &g_kv[T ^ 1][((hg * 4 + (wq >> 1)) * 32 + f) * 16 + 2 * t];
          float* zp = &g_z[T ^ 1][(hg * 4 + (wq >> 1)) * 32 + f];
#pragma unroll
          for (int b = 0; b < 2; b++) {
#pragma unroll
            for (int n = 0; n < 2; n++) {
              float c0, c1, c2, c3;
              if (b == 0) {
                c0 = up ? kv0[8 + 4 * n + 0] : kv0[4 * n + 0]; c1 = up ? kv0[8 + 4 * n + 1] : kv0[4 * n + 1];
                c2 = up ? kv0[8 + 4 * n + 2] : kv0[4 * n + 2]; c3 = up ? kv0[8 + 4 * n + 3] : kv0[4 * n + 3];
              } else {
                c0 = up ? kv1[24 + 4 * n + 0] : kv1[16 + 4 * n + 0]; c1 = up ? kv1[24 + 4 * n + 1] : kv1[16 + 4 * n + 1];
                c2 = up ? kv1[24 + 4 * n + 2] : kv1[16 + 4 * n + 2]; c3 = up ? kv1[24 + 4 * n + 3] : kv1[16 + 4 * n + 3];
              }
              float* p = kvp + b * 1024 + n * 8;
              asm volatile("red.relaxed.gpu.global.add.v2.f32 [%0], {%1,%2};" ::"l"(p), "f"(c0), "f"(c1) : "memory");
              asm volatile("red.relaxed.gpu.global.add.v2.f32 [%0], {%1,%2};" ::"l"(p + 128), "f"(c2), "f"(c3) : "memory");
            }
            if (t == 0) {
              asm volatile("red.relaxed.gpu.global.add.f32 [%0], %1;" ::"l"(zp + b * 64), "f"(b ? kv1[32] : kv0[32]) : "memory");
              asm volatile("red.relaxed.gpu.global.add.f32 [%0], %1;" ::"l"(zp + b * 64 + 8), "f"(b ? kv1[34] : kv0[34]) : "memory");
            }
          }
          bar_arrive(6 + wg, 160);
        }
        TSTAMP(3 + 2 * ps);
      }
#pragma unroll
      for (int i = 0; i < 32; i++) E[i >> 3][i & 7] = A[i >> 2][i & 3];
    }
    const int rh3 = 2 * rb3 + wg;
    uint32_t xr[16];
    {
      const uint32_t* xp = reinterpret_cast<const uint32_t*>(x + (size_t)(rh3 * 64 + wq * 16 + g) * 512 + jf * 64 + 2 * t);
#pragma unroll
      for (int i = 0; i < 8; i++) { xr[2 * i] = __ldg(xp + 4 * i); xr[2 * i + 1] = __ldg(xp + 8 * 256 + 4 * i); }
    }
    mbar_wait(sb + SM_KVB);
    TSTAMP(8);
    {
      uint4* op = &g_o[2 * rb + wg][hg][wq][0][lane];
#pragma unroll
      for (int h = 0; h < 4; h++) {
        uint32_t b0[4], b1[4], b2[4];
        const uint32_t kb = sb + SM_KVS + (h * 32 + lane) * 48;
        ldsm4t(b0, kb); ldsm4t(b1, kb + 16); ldsm4t(b2, kb + 32);
        const uint32_t ep[4] = {E[h][0], E[h][1], E[h][2], E[h][3]}, en[4] = {E[h][4], E[h][5], E[h][6], E[h][7]};
        float np0[4] = {0, 0, 0, 0}, np1[4] = {0, 0, 0, 0}, nn0[4] = {0, 0, 0, 0}, nn1[4] = {0, 0, 0, 0}, dp[4] = {0, 0, 0, 0}, dn[4] = {0, 0, 0, 0};
        mma16816(dp, ep, b2[0], b2[1]);  mma16816(dn, en, b2[2], b2[3]);
        mma16816(np0, ep, b0[0], b0[1]); mma16816(nn0, en, b0[2], b0[3]);
        mma16816(np1, ep, b1[0], b1[1]); mma16816(nn1, en, b1[2], b1[3]);
        const float i0 = rcp(fmaf(dp[0], dn[1], fmaf(dn[0], dp[1], 1e-6f * dp[1] * dn[1])));
        const float i1 = rcp(fmaf(dp[2], dn[3], fmaf(dn[2], dp[3], 1e-6f * dp[3] * dn[3])));
        const float cp0 = dn[1] * i0, cn0 = dp[1] * i0, cp1 = dn[3] * i1, cn1 = dp[3] * i1;
        st_rlx4(op + h * 32,
                tg(pack2(fmaf(np0[0], cp0, nn0[0] * cn0), fmaf(np0[1], cp0, nn0[1] * cn0)), T),
                tg(pack2(fmaf(np0[2], cp1, nn0[2] * cn1), fmaf(np0[3], cp1, nn0[3] * cn1)), T),
                tg(pack2(fmaf(np1[0], cp0, nn1[0] * cn0), fmaf(np1[1], cp0, nn1[1] * cn0)), T),
                tg(pack2(fmaf(np1[2], cp1, nn1[2] * cn1), fmaf(np1[3], cp1, nn1[3] * cn1)), T));
      }
    }
    TSTAMP(9);

    {
      uint32_t A[8][4][4];
      const uint4* op = &g_o[rh3][0][wq][0][lane];
      {
        const uint32_t* pw = reinterpret_cast<const uint32_t*>(&g_o[rh3][lane & 7][wq][3][31]) + 3;
        int it = 0;
#pragma unroll 1
        while (__any_sync(0xffffffffu, (ld_rlx1(pw) ^ T) & 1)) { if (++it > (1 << 18)) break; }
      }
      TSTAMP(27);
#pragma unroll
      for (int c = 0; c < 8; c++) ld_chunk(A[c], op + c * 512);
      float acc[32];
#pragma unroll
      for (int c = 0; c < 8; c++) {
        chk_chunk(A[c], op + c * 512, T);
        if (c % 3 == 0) mbar_wait(sb + SM_FULL + (ST_WO + c / 3) * 8);
        wg_fence();
#pragma unroll
        for (int s = 0; s < 4; s++)
          wgmma_rs_n64(acc, A[c][s], mk_desc(sb + ((ST_WO + c / 3) % NSLOT) * SLOT + ((c % 3) * 4 + s) * 2048, 8192, 1024), (c | s) != 0);
        wg_commit();
      }
      wg_wait<0>();
      if ((tid & 127) < 3) release(ST_WO + (tid & 127));
      TSTAMP(10);
      uint32_t hw[16];
      float s0 = 0.f, s1 = 0.f, q0 = 0.f, q1 = 0.f;
#pragma unroll
      for (int i = 0; i < 8; i++) {
        hw[2 * i]     = pack2(blo(xr[2 * i]) + acc[4 * i], bhi(xr[2 * i]) + acc[4 * i + 1]);
        hw[2 * i + 1] = pack2(blo(xr[2 * i + 1]) + acc[4 * i + 2], bhi(xr[2 * i + 1]) + acc[4 * i + 3]);
      }
      uint4* hp_ = &g_h[rh3][jf][wq][0][lane];
#pragma unroll
      for (int s = 0; s < 4; s++) st_rlx4(hp_ + s * 32, tg(hw[4 * s], T), tg(hw[4 * s + 1], T), tg(hw[4 * s + 2], T), tg(hw[4 * s + 3], T));
#pragma unroll
      for (int i = 0; i < 8; i++) {
        float a = blo(hw[2 * i]), b = bhi(hw[2 * i]);
        s0 += a + b; q0 = fmaf(a, a, q0); q0 = fmaf(b, b, q0);
        a = blo(hw[2 * i + 1]); b = bhi(hw[2 * i + 1]);
        s1 += a + b; q1 = fmaf(a, a, q1); q1 = fmaf(b, b, q1);
      }
      s0 += __shfl_xor_sync(0xffffffffu, s0, 1); s1 += __shfl_xor_sync(0xffffffffu, s1, 1);
      q0 += __shfl_xor_sync(0xffffffffu, q0, 1); q1 += __shfl_xor_sync(0xffffffffu, q1, 1);
      s0 += __shfl_xor_sync(0xffffffffu, s0, 2); s1 += __shfl_xor_sync(0xffffffffu, s1, 2);
      q0 += __shfl_xor_sync(0xffffffffu, q0, 2); q1 += __shfl_xor_sync(0xffffffffu, q1, 2);
      if (t < 2) st_rlx2(&g_st[rh3 * 64 + wq * 16 + g + t * 8][jf], tg(__float_as_uint(t ? s1 : s0), T), tg(__float_as_uint(t ? q1 : q0), T));
      uint32_t hx = 0;
#pragma unroll
      for (int i = 0; i < 16; i++) hx |= (hw[i] & 1u) << i;
      reinterpret_cast<uint32_t*>(smem + SM_ONES)[tid] = hx;
    }
    TSTAMP(11);

    uint32_t HH[11][4];
    {
      uint32_t A[2][4][4];
      const uint4* hp_ = &g_h[rh3][0][wq][0][lane];
      uint32_t m0, m1;
      {
        const uint4* sp = reinterpret_cast<const uint4*>(&g_st[rh3 * 64 + wq * 16 + g][2 * t]);
        uint32_t a[4], b[4];
        int it = 0;
#pragma unroll 1
        do {
          ld_rlx4(a, sp); ld_rlx4(b, sp + 8 * 4);
          if (++it > (1 << 18)) break;
        } while (__any_sync(0xffffffffu, (bad4(a, T) | bad4(b, T)) & 1));
        ld_chunk(A[0], hp_);
        float s0 = __uint_as_float(a[0]) + __uint_as_float(a[2]), q0 = __uint_as_float(a[1]) + __uint_as_float(a[3]);
        float s1 = __uint_as_float(b[0]) + __uint_as_float(b[2]), q1 = __uint_as_float(b[1]) + __uint_as_float(b[3]);
        s0 += __shfl_xor_sync(0xffffffffu, s0, 1); s1 += __shfl_xor_sync(0xffffffffu, s1, 1);
        q0 += __shfl_xor_sync(0xffffffffu, q0, 1); q1 += __shfl_xor_sync(0xffffffffu, q1, 1);
        s0 += __shfl_xor_sync(0xffffffffu, s0, 2); s1 += __shfl_xor_sync(0xffffffffu, s1, 2);
        q0 += __shfl_xor_sync(0xffffffffu, q0, 2); q1 += __shfl_xor_sync(0xffffffffu, q1, 2);
        s0 *= (1.f / 512.f); s1 *= (1.f / 512.f);
        r0 = 1.f / (fmaxf(q0 * (1.f / 512.f) - s0 * s0, 0.f) + 1e-5f);
        r1 = 1.f / (fmaxf(q1 * (1.f / 512.f) - s1 * s1, 0.f) + 1e-5f);
        m0 = pack2(s0, s0); m1 = pack2(s1, s1);
      }
      TSTAMP(12);
      float ag[88], au[88];
      int slot = ST_GU % NSLOT;
#pragma unroll 1
      for (int c2 = 0; c2 < 8; c2 += 2) {
#pragma unroll
        for (int b = 0; b < 2; b++) {
          const int c = c2 + b, sG = ST_GU + 2 * c;
          chk_chunk(A[b], hp_ + c * 512, T);
#pragma unroll
          for (int s = 0; s < 4; s++) {
            A[b][s][0] = hsub2(A[b][s][0], m0); A[b][s][1] = hsub2(A[b][s][1], m1);
            A[b][s][2] = hsub2(A[b][s][2], m0); A[b][s][3] = hsub2(A[b][s][3], m1);
          }
          mbar_wait(sb + SM_FULL + sG * 8);
          wg_fence();
#pragma unroll
          for (int s = 0; s < 4; s++)
            wgmma_rs_n176(ag, A[b][s], mk_desc(sb + slot * SLOT + s * 2048, 8192, 1024), (c | s) != 0);
          wg_commit();
          if (++slot == NSLOT) slot = 0;
          wg_wait<1>();
          if (lead && c > 0) release(sG - 1);
          if (c < 7) ld_chunk(A[b ^ 1], hp_ + (c + 1) * 512);
          mbar_wait(sb + SM_FULL + (sG + 1) * 8);
          wg_fence();
#pragma unroll
          for (int s = 0; s < 4; s++)
            wgmma_rs_n176(au, A[b][s], mk_desc(sb + slot * SLOT + s * 2048, 8192, 1024), (c | s) != 0);
          wg_commit();
          if (++slot == NSLOT) slot = 0;
          wg_wait<1>();
          if (lead) release(sG);
        }
      }
      wg_wait<0>();
      TSTAMP(13);
#pragma unroll
      for (int s = 0; s < 11; s++) {
        HH[s][0] = pack2(ag[8 * s + 0] * au[8 * s + 0] * r0, ag[8 * s + 1] * au[8 * s + 1] * r0);
        HH[s][1] = pack2(ag[8 * s + 2] * au[8 * s + 2] * r1, ag[8 * s + 3] * au[8 * s + 3] * r1);
        HH[s][2] = pack2(ag[8 * s + 4] * au[8 * s + 4] * r0, ag[8 * s + 5] * au[8 * s + 5] * r0);
        HH[s][3] = pack2(ag[8 * s + 6] * au[8 * s + 6] * r1, ag[8 * s + 7] * au[8 * s + 7] * r1);
      }
    }
    TSTAMP(14);

    {
      float acc[32], sum[32];
      uint32_t in[4][4];
      ld_chunk(in, &g_h[rh3][jf][wq][0][lane]);
      {
        const uint32_t hx = reinterpret_cast<const uint32_t*>(smem + SM_ONES)[tid];
#pragma unroll
        for (int i = 0; i < 16; i++) {
          sum[2 * i]     = blo((in[i >> 2][i & 3] & 0xFFFEu) | ((hx >> i) & 1u));
          sum[2 * i + 1] = bhi(in[i >> 2][i & 3]);
        }
      }
      const uint4* inb = &g_part[rh3][jf][0][wq][0][lane];
      uint4* outb = &g_part[rh3][0][jf][wq][0][lane];
      int slot = ST_D % NSLOT, q = 0, it = 0;
#pragma unroll 1
      for (int st = 0; q < 7; st++) {
        if (st < 8) {
          mbar_wait(sb + SM_FULL + (ST_D + st) * 8);
          wg_fence();
#pragma unroll
          for (int s = 0; s < 11; s++)
            wgmma_rs_n64(acc, HH[s], mk_desc(sb + slot * SLOT + s * 2048, 8192, 1024), s != 0);
          wg_commit();
          if (++slot == NSLOT) slot = 0;
        }
        if (st >= 4) {
          if (!__any_sync(0xffffffffu, (bad4(in[0], T) | bad4(in[1], T) | bad4(in[2], T) | bad4(in[3], T)) & 1) || ++it > (1 << 18)) {
#pragma unroll
            for (int i = 0; i < 16; i++) { sum[2 * i] += blo(in[i >> 2][i & 3]); sum[2 * i + 1] += bhi(in[i >> 2][i & 3]); }
            q++;
          }
        }
        if (st >= 3 && q < 7) ld_chunk(in, inb + ((jf - 1 - q) & 7) * 512);
        if (st < 8) wg_wait<0>();
        if (st < 7) {
          uint4* p = outb + ((jf + 1 + st) & 7) * 4096;
#pragma unroll
          for (int s = 0; s < 4; s++)
            st_rlx4(p + s * 32, tg(pack2(acc[8 * s + 0], acc[8 * s + 1]), T), tg(pack2(acc[8 * s + 2], acc[8 * s + 3]), T),
                    tg(pack2(acc[8 * s + 4], acc[8 * s + 5]), T), tg(pack2(acc[8 * s + 6], acc[8 * s + 7]), T));
        }
        if (st == 7) TSTAMP(15);
      }
      uint32_t* op = reinterpret_cast<uint32_t*>(out + (size_t)(rh3 * 64 + wq * 16 + g) * 512 + jf * 64 + 2 * t);
#pragma unroll
      for (int i = 0; i < 8; i++) {
        op[4 * i]           = pack2(sum[4 * i] + acc[4 * i], sum[4 * i + 1] + acc[4 * i + 1]);
        op[8 * 256 + 4 * i] = pack2(sum[4 * i + 2] + acc[4 * i + 2], sum[4 * i + 3] + acc[4 * i + 3]);
      }
    }
    TSTAMP(16);
    asm volatile("barrier.cluster.arrive.relaxed.aligned;" ::: "memory");
    asm volatile("barrier.cluster.wait.aligned;" ::: "memory");
  }
}

typedef CUresult (*EncodeFn)(CUtensorMap*, CUtensorMapDataType, cuuint32_t, void*, const cuuint64_t*, const cuuint64_t*,
                             const cuuint32_t*, const cuuint32_t*, CUtensorMapInterleave, CUtensorMapSwizzle,
                             CUtensorMapL2promotion, CUtensorMapFloatOOBfill);

void encode(EncodeFn fn, CUtensorMap* m, const void* base, int rank, const cuuint64_t* dims, const cuuint64_t* strides,
            const cuuint32_t* box) {
  cuuint32_t es[3] = {1, 1, 1};
  fn(m, CU_TENSOR_MAP_DATA_TYPE_BFLOAT16, (cuuint32_t)rank, const_cast<void*>(base), dims, strides, box, es,
     CU_TENSOR_MAP_INTERLEAVE_NONE, CU_TENSOR_MAP_SWIZZLE_128B, CU_TENSOR_MAP_L2_PROMOTION_L2_256B,
     CU_TENSOR_MAP_FLOAT_OOB_FILL_NONE);
}

}

extern "C" void kernel_launch(void* const* d_in, const int* in_sizes, int n_in, void* d_out, int out_size) {
  (void)in_sizes; (void)n_in; (void)out_size;
  const __nv_bfloat16* x    = (const __nv_bfloat16*)d_in[0];
  const __nv_bfloat16* wqkv = (const __nv_bfloat16*)d_in[1];
  const __nv_bfloat16* wphi = (const __nv_bfloat16*)d_in[2];
  const __nv_bfloat16* wo   = (const __nv_bfloat16*)d_in[3];
  const __nv_bfloat16* wg   = (const __nv_bfloat16*)d_in[5];
  const __nv_bfloat16* wu   = (const __nv_bfloat16*)d_in[6];
  const __nv_bfloat16* wd   = (const __nv_bfloat16*)d_in[7];

  static EncodeFn fn = nullptr;
  if (!fn) {
    void* p = nullptr;
    cudaDriverEntryPointQueryResult qr;
    cudaGetDriverEntryPoint("cuTensorMapEncodeTiled", &p, cudaEnableDefault, &qr);
    fn = (EncodeFn)p;
    cudaFuncSetAttribute(fused_kernel, cudaFuncAttributeMaxDynamicSharedMemorySize, SM_TOTAL);
  }
  Maps maps;
  {
    cuuint64_t d[3] = {64, 2048, 8}, s[2] = {1024, 128}; cuuint32_t b[3] = {64, 64, 3};
    encode(fn, &maps.x, x, 3, d, s, b);
  }
  {
    cuuint64_t d[2] = {1536, 512}, s[1] = {3072}; cuuint32_t b[2] = {64, 192};
    encode(fn, &maps.w, wqkv, 2, d, s, b);
  }
  {
    cuuint64_t d[2] = {512, 512}, s[1] = {1024}; cuuint32_t b[2] = {64, 192};
    encode(fn, &maps.wo, wo, 2, d, s, b);
  }
  {
    cuuint64_t d[3] = {176, 7, 512}, d7[3] = {144, 1, 512}, s[2] = {352, 2752}; cuuint32_t b[3] = {64, 1, 64};
    encode(fn, &maps.g, wg, 3, d, s, b);
    encode(fn, &maps.u, wu, 3, d, s, b);
    encode(fn, &maps.g7, wg + 1232, 3, d7, s, b);
    encode(fn, &maps.u7, wu + 1232, 3, d7, s, b);
  }
  {
    cuuint64_t d[2] = {512, 1376}, s[1] = {1024}; cuuint32_t b[2] = {64, 176};
    encode(fn, &maps.d, wd, 2, d, s, b);
  }
  fused_kernel<<<NCTA, 384, SM_TOTAL>>>(maps, x, wphi, wo, wg, wu, wd, (__nv_bfloat16*)d_out);
}
```

```cpp
#include <cuda_runtime.h>
#include <cuda_bf16.h>
#include <cuda.h>
#include <stdint.h>

#define PROF 0

namespace {

constexpr int NCTA   = 128;
constexpr int SLOT   = 24576;
constexpr int NSLOT  = 9;
constexpr int NSTAGE = 50;

constexpr int ST_X0   = 0;
constexpr int ST_WK   = 3;
constexpr int ST_X1   = 6;
constexpr int ST_SCR0 = 9;
constexpr int ST_WV   = 10;
constexpr int ST_SCR1 = 13;
constexpr int ST_WQ   = 14;
constexpr int ST_WO   = 17;
constexpr int ST_O0   = 20;
constexpr int ST_O1   = 23;
constexpr int ST_GU   = 26;
constexpr int ST_D    = 42;

__host__ __device__ constexpr int st_next(int d) { return d < ST_WQ ? d + 9 : d < ST_O0 ? d + 12 : d < ST_O1 ? d + 3 : d + 9; }
__host__ __device__ constexpr int st_bytes(int s) { return s >= ST_D ? 22528 : (s == ST_O0 + 2 || s == ST_O1 + 2) ? 16384 : 24576; }
__host__ __device__ constexpr int st_empty_cnt(int d) {
  return ((d < 3 || (d >= 6 && d < 9) || (d >= ST_O0 && d < ST_GU)) ? 4 : (d == ST_SCR0 || d == ST_SCR1) ? 1 : 2) *
         (st_next(d) >= ST_GU ? 2 : 1);
}

constexpr int SM_ONES = NSLOT * SLOT;
constexpr int SM_WPHI = SM_ONES + 2048;
constexpr int SM_KVS  = SM_WPHI + 2048;
constexpr int SM_BAR  = SM_KVS + 6144;
constexpr int SM_FULL  = SM_BAR;
constexpr int SM_EMPTY = SM_BAR + NSTAGE * 8;
constexpr int SM_MISCB = SM_BAR + 2 * NSTAGE * 8;
constexpr int SM_KVB   = SM_MISCB + 8;
constexpr int SM_EPOCH = SM_KVB + 8;
constexpr int SM_TOTAL = SM_BAR + 1024;

static_assert(SM_TOTAL == 232448, "smem budget");

struct Maps { CUtensorMap x, w, wo, g, u, g7, u7, d; };

__device__ uint4    g_o[32][8][4][4][32];
__device__ uint4    g_h[32][8][4][4][32];
__device__ uint32_t g_hx[32][8][4][32];
__device__ uint2    g_st[32][8][64];
__device__ uint4    g_part[32][8][8][4][4][32];
__device__ float    g_kv[2][32 * 32 * 16];
__device__ float    g_z[2][32 * 32];
__device__ unsigned g_kvcnt[8 * 32];
__device__ unsigned g_start;

__device__ __forceinline__ uint32_t smem_u32(const void* p) { return (uint32_t)__cvta_generic_to_shared(p); }
__device__ __forceinline__ void mbar_init(uint32_t bar, int cnt) {
  asm volatile("mbarrier.init.shared::cta.b64 [%0], %1;" ::"r"(bar), "r"(cnt) : "memory");
}
__device__ __forceinline__ void mbar_expect_tx(uint32_t bar, uint32_t bytes) {
  asm volatile("mbarrier.arrive.expect_tx.shared::cta.b64 _, [%0], %1;" ::"r"(bar), "r"(bytes) : "memory");
}
__device__ __forceinline__ void mbar_arrive(uint32_t bar) {
  asm volatile("mbarrier.arrive.shared::cta.b64 _, [%0];" ::"r"(bar) : "memory");
}
__device__ __forceinline__ void mbar_arrive_cluster(uint32_t bar, uint32_t rank) {
  asm volatile("{\n.reg .b32 ra;\nmapa.shared::cluster.u32 ra, %0, %1;\n"
               "mbarrier.arrive.shared::cluster.b64 _, [ra];\n}" ::"r"(bar), "r"(rank) : "memory");
}
__device__ __forceinline__ bool mbar_try(uint32_t bar) {
  uint32_t ok;
  asm volatile("{\n.reg .pred p;\nmbarrier.try_wait.parity.shared::cta.b64 p, [%1], 0;\nselp.u32 %0, 1, 0, p;\n}"
               : "=r"(ok) : "r"(bar) : "memory");
  return ok != 0;
}
__device__ __forceinline__ void mbar_wait(uint32_t bar) {
  int it = 0;
#pragma unroll 1
  while (!mbar_try(bar)) {
    if (++it > (1 << 20)) __trap();
  }
}
__device__ __forceinline__ void bar_sync(int id, int n)   { asm volatile("bar.sync %0, %1;" ::"r"(id), "r"(n) : "memory"); }
__device__ __forceinline__ void bar_arrive(int id, int n) { asm volatile("bar.arrive %0, %1;" ::"r"(id), "r"(n) : "memory"); }
__device__ __forceinline__ void fence_async_smem() { asm volatile("fence.proxy.async.shared::cta;" ::: "memory"); }
__device__ __forceinline__ void wg_fence()  { asm volatile("wgmma.fence.sync.aligned;" ::: "memory"); }
__device__ __forceinline__ void wg_commit() { asm volatile("wgmma.commit_group.sync.aligned;" ::: "memory"); }
template <int N> __device__ __forceinline__ void wg_wait() { asm volatile("wgmma.wait_group.sync.aligned %0;" ::"n"(N) : "memory"); }
__device__ __forceinline__ uint64_t mk_desc(uint32_t addr, uint32_t lbo, uint32_t sbo) {
  return (uint64_t)((addr & 0x3FFFF) >> 4) | ((uint64_t)((lbo & 0x3FFFF) >> 4) << 16) | ((uint64_t)(sbo >> 4) << 32) | (1ull << 62);
}
__device__ __forceinline__ void tma2d(uint32_t dst, const CUtensorMap* m, int c0, int c1, uint32_t bar) {
  asm volatile("cp.async.bulk.tensor.2d.shared::cluster.global.mbarrier::complete_tx::bytes [%0], [%1, {%3, %4}], [%2];"
               ::"r"(dst), "l"(m), "r"(bar), "r"(c0), "r"(c1) : "memory");
}
__device__ __forceinline__ void tma2d_mc(uint32_t dst, const CUtensorMap* m, int c0, int c1, uint32_t bar) {
  asm volatile("cp.async.bulk.tensor.2d.shared::cluster.global.mbarrier::complete_tx::bytes.multicast::cluster [%0], [%1, {%3, %4}], [%2], %5;"
               ::"r"(dst), "l"(m), "r"(bar), "r"(c0), "r"(c1), "h"((uint16_t)3) : "memory");
}
__device__ __forceinline__ void tma3d(uint32_t dst, const CUtensorMap* m, int c0, int c1, int c2, uint32_t bar) {
  asm volatile("cp.async.bulk.tensor.3d.shared::cluster.global.mbarrier::complete_tx::bytes [%0], [%1, {%3, %4, %5}], [%2];"
               ::"r"(dst), "l"(m), "r"(bar), "r"(c0), "r"(c1), "r"(c2) : "memory");
}
__device__ __forceinline__ void tma3d_mc(uint32_t dst, const CUtensorMap* m, int c0, int c1, int c2, uint32_t bar) {
  asm volatile("cp.async.bulk.tensor.3d.shared::cluster.global.mbarrier::complete_tx::bytes.multicast::cluster [%0], [%1, {%3, %4, %5}], [%2], %6;"
               ::"r"(dst), "l"(m), "r"(bar), "r"(c0), "r"(c1), "r"(c2), "h"((uint16_t)3) : "memory");
}
__device__ __forceinline__ void ldsm4(uint32_t (&r)[4], uint32_t addr) {
  asm volatile("ldmatrix.sync.aligned.m8n8.x4.shared.b16 {%0,%1,%2,%3}, [%4];"
               : "=r"(r[0]), "=r"(r[1]), "=r"(r[2]), "=r"(r[3]) : "r"(addr) : "memory");
}
__device__ __forceinline__ void ldsm4t(uint32_t (&r)[4], uint32_t addr) {
  asm volatile("ldmatrix.sync.aligned.m8n8.x4.trans.shared.b16 {%0,%1,%2,%3}, [%4];"
               : "=r"(r[0]), "=r"(r[1]), "=r"(r[2]), "=r"(r[3]) : "r"(addr) : "memory");
}
__device__ __forceinline__ void stsm4(uint32_t addr, uint32_t r0, uint32_t r1, uint32_t r2, uint32_t r3) {
  asm volatile("stmatrix.sync.aligned.m8n8.x4.shared.b16 [%0], {%1,%2,%3,%4};"
               ::"r"(addr), "r"(r0), "r"(r1), "r"(r2), "r"(r3) : "memory");
}
__device__ __forceinline__ void mma16816(float (&c)[4], const uint32_t (&a)[4], uint32_t b0, uint32_t b1) {
  asm volatile("mma.sync.aligned.m16n8k16.row.col.f32.bf16.bf16.f32 {%0,%1,%2,%3},{%4,%5,%6,%7},{%8,%9},{%0,%1,%2,%3};"
               : "+f"(c[0]), "+f"(c[1]), "+f"(c[2]), "+f"(c[3])
               : "r"(a[0]), "r"(a[1]), "r"(a[2]), "r"(a[3]), "r"(b0), "r"(b1));
}
__device__ __forceinline__ uint32_t pack2(float lo, float hi) {
  uint32_t r; asm("cvt.rn.bf16x2.f32 %0, %1, %2;" : "=r"(r) : "f"(hi), "f"(lo)); return r;
}
__device__ __forceinline__ float blo(uint32_t w) { return __uint_as_float(w << 16); }
__device__ __forceinline__ float bhi(uint32_t w) { return __uint_as_float(w & 0xFFFF0000u); }
__device__ __forceinline__ uint32_t hsub2(uint32_t a, uint32_t b) { uint32_t r; asm("sub.rn.bf16x2 %0, %1, %2;" : "=r"(r) : "r"(a), "r"(b)); return r; }
__device__ __forceinline__ uint32_t hmax2(uint32_t a, uint32_t b) { uint32_t r; asm("max.bf16x2 %0, %1, %2;" : "=r"(r) : "r"(a), "r"(b)); return r; }
__device__ __forceinline__ uint32_t hmin2(uint32_t a, uint32_t b) { uint32_t r; asm("min.bf16x2 %0, %1, %2;" : "=r"(r) : "r"(a), "r"(b)); return r; }
__device__ __forceinline__ float ex2(float x) { float r; asm("ex2.approx.ftz.f32 %0, %1;" : "=f"(r) : "f"(x)); return r; }
__device__ __forceinline__ float rcp(float x) { float r; asm("rcp.approx.ftz.f32 %0, %1;" : "=f"(r) : "f"(x)); return r; }
__device__ __forceinline__ void ld_rlx4(uint32_t (&r)[4], const uint4* p) {
  asm volatile("ld.relaxed.gpu.global.v4.b32 {%0,%1,%2,%3}, [%4];"
               : "=r"(r[0]), "=r"(r[1]), "=r"(r[2]), "=r"(r[3]) : "l"(p) : "memory");
}
__device__ __forceinline__ void st_rlx4(uint4* p, uint32_t a, uint32_t b, uint32_t c, uint32_t d) {
  asm volatile("st.relaxed.gpu.global.v4.b32 [%0], {%1,%2,%3,%4};" ::"l"(p), "r"(a), "r"(b), "r"(c), "r"(d) : "memory");
}
__device__ __forceinline__ void st_rlx2(uint2* p, uint32_t a, uint32_t b) {
  asm volatile("st.relaxed.gpu.global.v2.b32 [%0], {%1,%2};" ::"l"(p), "r"(a), "r"(b) : "memory");
}
__device__ __forceinline__ uint32_t ld_rlx1(const uint32_t* p) {
  uint32_t r; asm volatile("ld.relaxed.gpu.global.b32 %0, [%1];" : "=r"(r) : "l"(p) : "memory"); return r;
}
__device__ __forceinline__ void st_rlx1(uint32_t* p, uint32_t a) {
  asm volatile("st.relaxed.gpu.global.b32 [%0], %1;" ::"l"(p), "r"(a) : "memory");
}
__device__ __forceinline__ void ld_rlx2(uint32_t& a, uint32_t& b, const uint2* p) {
  asm volatile("ld.relaxed.gpu.global.v2.b32 {%0,%1}, [%2];" : "=r"(a), "=r"(b) : "l"(p) : "memory");
}
__device__ __forceinline__ void bulk_g2s(uint32_t dst, const void* src, uint32_t bytes, uint32_t bar) {
  asm volatile("cp.async.bulk.shared::cluster.global.mbarrier::complete_tx::bytes [%0], [%1], %2, [%3];"
               ::"r"(dst), "l"(src), "r"(bytes), "r"(bar) : "memory");
}
__device__ __forceinline__ uint32_t tg(uint32_t w, uint32_t T) { return (w & 0xFFFFFFFEu) | T; }
__device__ __forceinline__ uint32_t bad4(const uint32_t (&r)[4], uint32_t T) { return (r[0] ^ T) | (r[1] ^ T) | (r[2] ^ T) | (r[3] ^ T); }

__device__ __forceinline__ void ld_chunk(uint32_t (&a)[4][4], const uint4* p) {
#pragma unroll
  for (int s = 0; s < 4; s++) ld_rlx4(a[s], p + s * 32);
}
__device__ __forceinline__ void chk_chunk(uint32_t (&a)[4][4], const uint4* p, uint32_t T) {
  int it = 0;
#pragma unroll 1
  while (__any_sync(0xffffffffu, (bad4(a[0], T) | bad4(a[1], T) | bad4(a[2], T) | bad4(a[3], T)) & 1)) {
    ld_chunk(a, p);
    if (++it > (1 << 18)) break;
  }
}

__device__ __forceinline__ void wgmma_rs_n64(float (&d)[32], const uint32_t (&a)[4], uint64_t descB, int scaleD) {
  asm volatile("{\n.reg .pred p;\nsetp.ne.b32 p, %37, 0;\n"
    "wgmma.mma_async.sync.aligned.m64n64k16.f32.bf16.bf16 {%0,%1,%2,%3,%4,%5,%6,%7,%8,%9,%10,%11,%12,%13,%14,%15,%16,%17,%18,%19,%20,%21,%22,%23,%24,%25,%26,%27,%28,%29,%30,%31}, {%32,%33,%34,%35}, %36, p, 1, 1, 1;\n}\n"
    : "+f"(d[0]),"+f"(d[1]),"+f"(d[2]),"+f"(d[3]),"+f"(d[4]),"+f"(d[5]),"+f"(d[6]),"+f"(d[7]),"+f"(d[8]),"+f"(d[9]),"+f"(d[10]),"+f"(d[11]),"+f"(d[12]),"+f"(d[13]),"+f"(d[14]),"+f"(d[15]),"+f"(d[16]),"+f"(d[17]),"+f"(d[18]),"+f"(d[19]),"+f"(d[20]),"+f"(d[21]),"+f"(d[22]),"+f"(d[23]),"+f"(d[24]),"+f"(d[25]),"+f"(d[26]),"+f"(d[27]),"+f"(d[28]),"+f"(d[29]),"+f"(d[30]),"+f"(d[31])
    : "r"(a[0]), "r"(a[1]), "r"(a[2]), "r"(a[3]), "l"(descB), "r"(scaleD));
}
__device__ __forceinline__ void wgmma_rs_n176(float (&d)[88], const uint32_t (&a)[4], uint64_t descB, int scaleD) {
  asm volatile("{\n.reg .pred p;\nsetp.ne.b32 p, %93, 0;\n"
    "wgmma.mma_async.sync.aligned.m64n176k16.f32.bf16.bf16 {%0,%1,%2,%3,%4,%5,%6,%7,%8,%9,%10,%11,%12,%13,%14,%15,%16,%17,%18,%19,%20,%21,%22,%23,%24,%25,%26,%27,%28,%29,%30,%31,%32,%33,%34,%35,%36,%37,%38,%39,%40,%41,%42,%43,%44,%45,%46,%47,%48,%49,%50,%51,%52,%53,%54,%55,%56,%57,%58,%59,%60,%61,%62,%63,%64,%65,%66,%67,%68,%69,%70,%71,%72,%73,%74,%75,%76,%77,%78,%79,%80,%81,%82,%83,%84,%85,%86,%87}, {%88,%89,%90,%91}, %92, p, 1, 1, 1;\n}\n"
    : "+f"(d[0]),"+f"(d[1]),"+f"(d[2]),"+f"(d[3]),"+f"(d[4]),"+f"(d[5]),"+f"(d[6]),"+f"(d[7]),"+f"(d[8]),"+f"(d[9]),"+f"(d[10]),"+f"(d[11]),"+f"(d[12]),"+f"(d[13]),"+f"(d[14]),"+f"(d[15]),"+f"(d[16]),"+f"(d[17]),"+f"(d[18]),"+f"(d[19]),"+f"(d[20]),"+f"(d[21]),"+f"(d[22]),"+f"(d[23]),"+f"(d[24]),"+f"(d[25]),"+f"(d[26]),"+f"(d[27]),"+f"(d[28]),"+f"(d[29]),"+f"(d[30]),"+f"(d[31]),"+f"(d[32]),"+f"(d[33]),"+f"(d[34]),"+f"(d[35]),"+f"(d[36]),"+f"(d[37]),"+f"(d[38]),"+f"(d[39]),"+f"(d[40]),"+f"(d[41]),"+f"(d[42]),"+f"(d[43]),"+f"(d[44]),"+f"(d[45]),"+f"(d[46]),"+f"(d[47]),"+f"(d[48]),"+f"(d[49]),"+f"(d[50]),"+f"(d[51]),"+f"(d[52]),"+f"(d[53]),"+f"(d[54]),"+f"(d[55]),"+f"(d[56]),"+f"(d[57]),"+f"(d[58]),"+f"(d[59]),"+f"(d[60]),"+f"(d[61]),"+f"(d[62]),"+f"(d[63]),"+f"(d[64]),"+f"(d[65]),"+f"(d[66]),"+f"(d[67]),"+f"(d[68]),"+f"(d[69]),"+f"(d[70]),"+f"(d[71]),"+f"(d[72]),"+f"(d[73]),"+f"(d[74]),"+f"(d[75]),"+f"(d[76]),"+f"(d[77]),"+f"(d[78]),"+f"(d[79]),"+f"(d[80]),"+f"(d[81]),"+f"(d[82]),"+f"(d[83]),"+f"(d[84]),"+f"(d[85]),"+f"(d[86]),"+f"(d[87])
    : "r"(a[0]), "r"(a[1]), "r"(a[2]), "r"(a[3]), "l"(descB), "r"(scaleD));
}
__device__ __forceinline__ void wgmma_ss_n72_t11(float (&d)[36], uint64_t descA, uint64_t descB, int scaleD) {
  asm volatile("{\n.reg .pred p;\nsetp.ne.b32 p, %38, 0;\n"
    "wgmma.mma_async.sync.aligned.m64n72k16.f32.bf16.bf16 {%0,%1,%2,%3,%4,%5,%6,%7,%8,%9,%10,%11,%12,%13,%14,%15,%16,%17,%18,%19,%20,%21,%22,%23,%24,%25,%26,%27,%28,%29,%30,%31,%32,%33,%34,%35}, %36, %37, p, 1, 1, 1, 1;\n}\n"
    : "+f"(d[0]),"+f"(d[1]),"+f"(d[2]),"+f"(d[3]),"+f"(d[4]),"+f"(d[5]),"+f"(d[6]),"+f"(d[7]),"+f"(d[8]),"+f"(d[9]),"+f"(d[10]),"+f"(d[11]),"+f"(d[12]),"+f"(d[13]),"+f"(d[14]),"+f"(d[15]),"+f"(d[16]),"+f"(d[17]),"+f"(d[18]),"+f"(d[19]),"+f"(d[20]),"+f"(d[21]),"+f"(d[22]),"+f"(d[23]),"+f"(d[24]),"+f"(d[25]),"+f"(d[26]),"+f"(d[27]),"+f"(d[28]),"+f"(d[29]),"+f"(d[30]),"+f"(d[31]),"+f"(d[32]),"+f"(d[33]),"+f"(d[34]),"+f"(d[35])
    : "l"(descA), "l"(descB), "r"(scaleD));
}

#define TSTAMP(i) do {} while (0)
#define TS2(w, i) do {} while (0)

constexpr float LOG2E = 1.4426950408889634f;

__device__ __forceinline__ void feat_exp(const float (&p0)[4], const float (&p1)[4], float (&e)[16]) {
  uint32_t P0 = pack2(p0[0], p0[1]), P1 = pack2(p0[2], p0[3]), P2 = pack2(p1[0], p1[1]), P3 = pack2(p1[2], p1[3]);
  uint32_t a = hmax2(P0, P2), b = hmax2(P1, P3);
  uint32_t mx = hmax2(__byte_perm(a, b, 0x5410), __byte_perm(a, b, 0x7632));
  a = hmin2(P0, P2); b = hmin2(P1, P3);
  uint32_t mn = hmin2(__byte_perm(a, b, 0x5410), __byte_perm(a, b, 0x7632));
  mx = hmax2(mx, __shfl_xor_sync(0xffffffffu, mx, 1));
  mn = hmin2(mn, __shfl_xor_sync(0xffffffffu, mn, 1));
  mx = hmax2(mx, __shfl_xor_sync(0xffffffffu, mx, 2));
  mn = hmin2(mn, __shfl_xor_sync(0xffffffffu, mn, 2));
  float mx0 = -blo(mx) * LOG2E, mx1 = -bhi(mx) * LOG2E, mn0 = blo(mn) * LOG2E, mn1 = bhi(mn) * LOG2E;
  float v[8] = {blo(P0), bhi(P0), blo(P1), bhi(P1), blo(P2), bhi(P2), blo(P3), bhi(P3)};
#pragma unroll
  for (int i = 0; i < 8; i++) {
    bool r1 = (i >> 1) & 1;
    e[i]     = ex2(fmaf(v[i],  LOG2E, r1 ? mx1 : mx0));
    e[8 + i] = ex2(fmaf(v[i], -LOG2E, r1 ? mn1 : mn0));
  }
}

__global__ void __cluster_dims__(2, 1, 1) __launch_bounds__(384, 1)
fused_kernel(const __grid_constant__ Maps maps, const __nv_bfloat16* __restrict__ x, const __nv_bfloat16* __restrict__ wphi,
             const __nv_bfloat16* __restrict__ wo, const __nv_bfloat16* __restrict__ wg_, const __nv_bfloat16* __restrict__ wu_,
             const __nv_bfloat16* __restrict__ wd_, __nv_bfloat16* __restrict__ out) {
  extern __shared__ __align__(1024) unsigned char smem[];
  const uint32_t sb = smem_u32(smem);
  const int tid = threadIdx.x, lane = tid & 31;
  const int warp = __shfl_sync(0xffffffffu, tid >> 5, 0);
  const uint32_t rank = blockIdx.x & 1;
  const int cl = blockIdx.x >> 1;
  int quad, qi;
  if (cl < 4) { quad = 15; qi = cl; }
  else if (cl < 36) { quad = (cl - 4) & 7; qi = (cl - 4) >> 3; }
  else { qi = (cl - 36) / 7; quad = 8 + (cl - 36) - 7 * qi; }
  const int rb = quad, hg = 2 * qi + rank;
  const int rb3 = (quad & ~1) + rank, jf = 4 * (quad & 1) + qi;

  if (lane == 0) {
    if (warp == 8) {
#pragma unroll
      for (int s = 0; s < 9; s++) {
        const uint32_t bar = sb + SM_FULL + s * 8;
        mbar_init(bar, 1);
        mbar_expect_tx(bar, SLOT);
        if (s >= 3 && s < 6) tma2d(sb + s * SLOT, &maps.w, 512 + hg * 64, (s - 3) * 192, bar);
        else tma3d(sb + s * SLOT, &maps.x, 0, rb * 128 + (s >= 6 ? 64 : 0), 3 * (s % 3), bar);
      }
    } else if (warp == 9) {
      mbar_init(sb + SM_MISCB, 2);
      mbar_init(sb + SM_KVB, 1);
      mbar_expect_tx(sb + SM_MISCB, 2048);
      bulk_g2s(sb + SM_WPHI, wphi + hg * 1024, 2048, sb + SM_MISCB);
    } else if (warp < 8) {
#pragma unroll
      for (int i = 0; i < 6; i++) {
        const int d = warp * 6 + i;
        if (d + 9 < NSTAGE) {
          mbar_init(sb + SM_EMPTY + d * 8, st_empty_cnt(d));
          mbar_init(sb + SM_FULL + (d + 9) * 8, 1);
          mbar_expect_tx(sb + SM_FULL + (d + 9) * 8, st_bytes(d + 9));
        }
      }
    }
    asm volatile("fence.mbarrier_init.release.cluster;" ::: "memory");
  }
  if (tid == 256) TS2(0, 18);
  __syncthreads();
  if (tid == 256) TS2(1, 18);
  asm volatile("barrier.cluster.arrive.relaxed.aligned;" ::: "memory");

  if (warp >= 8) {
    asm volatile("setmaxnreg.dec.sync.aligned.u32 24;");
    if (warp == 8) {
      asm volatile("barrier.cluster.wait.aligned;" ::: "memory");
      if (lane == 0) {
        const CUtensorMap* mgu = rank ? (jf == 7 ? &maps.u7 : &maps.u) : (jf == 7 ? &maps.g7 : &maps.g);
        asm volatile("prefetch.tensormap [%0];" ::"l"(&maps.wo) : "memory");
        asm volatile("prefetch.tensormap [%0];" ::"l"(mgu) : "memory");
        asm volatile("prefetch.tensormap [%0];" ::"l"(&maps.d) : "memory");
#pragma unroll 1
        for (int s = ST_WV; s < ST_O0; s++) {
          if (s == ST_SCR1) continue;
          mbar_wait(sb + SM_EMPTY + (s - 9) * 8);
          const uint32_t dst = sb + (s >= 18 ? s - 18 : s - 9) * SLOT, bar = sb + SM_FULL + s * 8;
          if (s < ST_WO) tma2d(dst, &maps.w, (s < ST_WQ ? 1024 : 0) + hg * 64, (s < ST_WQ ? s - ST_WV : s - ST_WQ) * 192, bar);
          else { mbar_wait(bar - 8); tma2d(dst, &maps.wo, hg * 64, (s - ST_WO) * 192, bar); }
        }
        const int jc = jf == 7 ? 0 : jf;
        int slot = 5 + rank;
#pragma unroll 1
        for (int s = ST_GU + rank; s < NSTAGE; s += 2) {
          mbar_wait(sb + SM_EMPTY + (s < ST_GU + 6 ? s - 12 : s - 9) * 8);
          if (s > ST_GU && s < ST_GU + NSLOT) mbar_wait(sb + SM_FULL + (s - 1) * 8);
          const uint32_t dst = sb + slot * SLOT, bar = sb + SM_FULL + s * 8;
          if (s < ST_D) {
            const int c = (s - ST_GU) >> 1;
#pragma unroll
            for (int b = 0; b < 3; b++) tma3d_mc(dst + b * 8192, mgu, b * 64, jc, c * 64, bar);
          } else {
            tma2d_mc(dst, &maps.d, ((jf + 1 + (s - ST_D)) & 7) * 64, jf * 176, bar);
          }
          slot += 2; if (slot >= NSLOT) slot -= NSLOT;
        }
      }
      __syncwarp();
    } else {
      if (warp == 11) {
        if (lane == 0) *reinterpret_cast<volatile unsigned*>(smem + SM_EPOCH) = atomicAdd(&g_start, 1u) / NCTA;
#pragma unroll
        for (int i = 0; i < 4; i++)
          reinterpret_cast<uint4*>(smem + SM_ONES)[lane + 32 * i] = make_uint4(0x3F803F80u, 0x3F803F80u, 0x3F803F80u, 0x3F803F80u);
        fence_async_smem();
        __syncwarp();
        if (lane == 0) { mbar_arrive(sb + SM_MISCB); TS2(0, 19); }
      }
      asm volatile("barrier.cluster.wait.aligned;" ::: "memory");
      mbar_wait(sb + SM_MISCB);
      const unsigned epoch = *reinterpret_cast<volatile unsigned*>(smem + SM_EPOCH);
      if (warp == 11) {
        reinterpret_cast<float4*>(&g_kv[(epoch & 1) ^ 1][blockIdx.x * 128])[lane] = make_float4(0.f, 0.f, 0.f, 0.f);
        if (lane < 8) g_z[(epoch & 1) ^ 1][blockIdx.x * 8 + lane] = 0.f;
        mbar_wait(sb + SM_FULL + (ST_X1 + 2) * 8);
        if (lane == 0) {
          asm volatile("cp.async.bulk.prefetch.L2.global [%0], 4096;" ::"l"((const char*)wo + blockIdx.x * 4096) : "memory");
          asm volatile("cp.async.bulk.prefetch.L2.global [%0], 11008;" ::"l"((const char*)wg_ + blockIdx.x * 11008) : "memory");
          asm volatile("cp.async.bulk.prefetch.L2.global [%0], 11008;" ::"l"((const char*)wu_ + blockIdx.x * 11008) : "memory");
          asm volatile("cp.async.bulk.prefetch.L2.global [%0], 11008;" ::"l"((const char*)wd_ + blockIdx.x * 11008) : "memory");
          const unsigned target = (epoch + 1) * 32;
          unsigned v; int it = 0;
#pragma unroll 1
          do {
            asm volatile("ld.acquire.gpu.global.u32 %0, [%1];" : "=r"(v) : "l"(&g_kvcnt[hg * 32]) : "memory");
            if (++it > (1 << 18)) break;
          } while ((int)(v - target) < 0);
          mbar_arrive(sb + SM_KVB);
          TS2(0, 26);
        }
        __syncwarp();
      } else {
        const int w = warp - 9;
        bar_sync(6 + w, 160);
        if (lane == 0) {
          asm volatile("fence.acq_rel.gpu;" ::: "memory");
          TS2(w, 25);
          asm volatile("red.relaxed.gpu.global.add.u32 [%0], 1;" ::"l"(&g_kvcnt[hg * 32]) : "memory");
        }
        mbar_wait(sb + SM_KVB);
        const uint32_t T = (epoch & 1) ^ 1;
        const uint32_t* pw = reinterpret_cast<const uint32_t*>(&g_o[2 * rb + w][lane >> 2][lane & 3][3][31]) + 3;
        int it = 0;
#pragma unroll 1
        while (__any_sync(0xffffffffu, (ld_rlx1(pw) ^ T) & 1)) { if (++it > (1 << 18)) break; }
        if (lane == 0) {
          TS2(w, 27);
          asm volatile("fence.proxy.async.global;" ::: "memory");
#pragma unroll 1
          for (int i = 0; i < 3; i++) {
            mbar_wait(sb + SM_EMPTY + (w ? ST_O0 + i : ST_O0 - 9 + i) * 8);
            bulk_g2s(sb + (2 + i) * SLOT, &g_o[2 * rb + w][3 * i][0][0][0], i < 2 ? 24576 : 16384, sb + SM_FULL + (ST_O0 + 3 * w + i) * 8);
          }
        }
        __syncwarp();
      }
    }
    asm volatile("barrier.cluster.arrive.relaxed.aligned;" ::: "memory");
    asm volatile("barrier.cluster.wait.aligned;" ::: "memory");
  } else {
    asm volatile("setmaxnreg.inc.sync.aligned.u32 240;");
    const int wg = warp >> 2, wq = warp & 3, g = lane >> 2, t = lane & 3;
    const bool lead = (tid & 127) == 0;
    auto release = [&](int d) {
      const int s = st_next(d);
      if (s < NSTAGE) mbar_arrive_cluster(sb + SM_EMPTY + d * 8, s >= ST_GU ? (uint32_t)(s & 1) : rank);
    };
    const uint32_t lrow = (uint32_t)(wq * 16 + (lane & 7) + ((lane >> 3) & 1) * 8) * 128;
    const uint32_t lx = lane & 7, lhi = lane >> 4;
    if (wg == 1) bar_arrive(4, 256);
    TSTAMP(0);

    float r0, r1;
    uint32_t E[4][8];
    uint32_t T = 0;
    {
      uint32_t A[32][4];
      const int sx = wg ? ST_X1 : ST_X0;
      uint32_t m0, m1;
      {
        float sa[4] = {0.f, 0.f, 0.f, 0.f}, qa[4] = {0.f, 0.f, 0.f, 0.f}, qb[4] = {0.f, 0.f, 0.f, 0.f};
        const uint32_t rr = lane >> 1;
        const uint32_t sbase = sb + sx * SLOT + (wq * 16 + rr) * 128;
#pragma unroll 1
        for (int c = 0; c < 8; c++) {
          if (c == 0 || c == 3 || c == 6) mbar_wait(sb + SM_FULL + (sx + c / 3) * 8);
          uint32_t v[4][4];
#pragma unroll
          for (int i = 0; i < 4; i++)
            asm volatile("ld.shared.v4.b32 {%0,%1,%2,%3}, [%4];" : "=r"(v[i][0]), "=r"(v[i][1]), "=r"(v[i][2]), "=r"(v[i][3])
                         : "r"(sbase + c * 8192 + ((((lane & 1) * 4 + i) ^ (rr & 7)) << 4)) : "memory");
#pragma unroll
          for (int i = 0; i < 4; i++)
#pragma unroll
            for (int k = 0; k < 4; k++) {
              const float a = blo(v[i][k]), b = bhi(v[i][k]);
              sa[k] += a + b; qa[k] = fmaf(a, a, qa[k]); qb[k] = fmaf(b, b, qb[k]);
            }
        }
        float s = (sa[0] + sa[1]) + (sa[2] + sa[3]);
        float q = ((qa[0] + qa[1]) + (qa[2] + qa[3])) + ((qb[0] + qb[1]) + (qb[2] + qb[3]));
        s += __shfl_xor_sync(0xffffffffu, s, 1); q += __shfl_xor_sync(0xffffffffu, q, 1);
        s *= (1.f / 512.f);
        const float r = rsqrtf(fmaxf(q * (1.f / 512.f) - s * s, 0.f) + 1e-5f);
        const uint32_t m = pack2(s, s);
        m0 = __shfl_sync(0xffffffffu, m, 2 * g); m1 = __shfl_sync(0xffffffffu, m, 2 * g + 16);
        r0 = __shfl_sync(0xffffffffu, r, 2 * g); r1 = __shfl_sync(0xffffffffu, r, 2 * g + 16);
      }
      TSTAMP(17);
      {
        const uint32_t base = sb + sx * SLOT + lrow;
#pragma unroll
        for (int ks = 0; ks < 32; ks++) {
          ldsm4(A[ks], base + (ks >> 2) * 8192 + (((2 * (ks & 3) + lhi) ^ lx) << 4));
          A[ks][0] = hsub2(A[ks][0], m0); A[ks][1] = hsub2(A[ks][1], m1);
          A[ks][2] = hsub2(A[ks][2], m0); A[ks][3] = hsub2(A[ks][3], m1);
        }
        asm volatile("barrier.cluster.wait.aligned;" ::: "memory");
        if (lane < 3) release(sx + lane);
      }
      TSTAMP(1);

      const uint32_t scr = sb + (wg ? (ST_SCR1 % NSLOT) : (ST_SCR0 % NSLOT)) * SLOT;
#pragma unroll 1
      for (int ps = 0; ps < 3; ps++) {
        const int st0 = ps == 0 ? ST_WK : (ps == 1 ? ST_WV : ST_WQ);
        const uint32_t wbase = sb + (ps == 0 ? ST_WK % NSLOT : (ps == 1 ? ST_WV % NSLOT : ST_WQ % NSLOT)) * SLOT;
        float acc[32];
        bar_sync(4 + wg, 256);
#pragma unroll
        for (int i = 0; i < 3; i++) {
          mbar_wait(sb + SM_FULL + (st0 + i) * 8);
          wg_fence();
#pragma unroll
          for (int kk = 0; kk < (i < 2 ? 12 : 8); kk++)
            wgmma_rs_n64(acc, A[12 * i + kk], mk_desc(wbase + i * SLOT + kk * 2048, 8192, 1024), (i | kk) != 0);
          wg_commit();
          if (i > 0) { wg_wait<1>(); if (lead) release(st0 + i - 1); }
        }
        if (ps < 2 || wg == 0) bar_arrive(4 + (wg ^ 1), 256);
        wg_wait<0>();
        if (lead) release(st0 + 2);
        TSTAMP(2 + 2 * ps);
        uint32_t a[4][4];
#pragma unroll
        for (int h = 0; h < 4; h++) {
          a[h][0] = pack2(acc[8 * h + 0] * r0, acc[8 * h + 1] * r0); a[h][1] = pack2(acc[8 * h + 2] * r1, acc[8 * h + 3] * r1);
          a[h][2] = pack2(acc[8 * h + 4] * r0, acc[8 * h + 5] * r0); a[h][3] = pack2(acc[8 * h + 6] * r1, acc[8 * h + 7] * r1);
        }
        if (ps != 1) {
          if (ps == 0) {
            mbar_wait(sb + SM_MISCB);
            T = (*reinterpret_cast<volatile unsigned*>(smem + SM_EPOCH) & 1) ^ 1;
            mbar_wait(sb + SM_EMPTY + (wg ? ST_SCR1 - NSLOT : ST_SCR0 - NSLOT) * 8);
          }
          float pp[4][2][4];
#pragma unroll
          for (int h = 0; h < 4; h++) {
            uint32_t b[4];
            ldsm4t(b, sb + SM_WPHI + h * 512 + ((lane & 7) + ((lane >> 3) & 1) * 8) * 32 + lhi * 16);
#pragma unroll
            for (int i = 0; i < 4; i++) { pp[h][0][i] = 0.f; pp[h][1][i] = 0.f; }
            mma16816(pp[h][0], a[h], b[0], b[1]);
            mma16816(pp[h][1], a[h], b[2], b[3]);
          }
          float e[4][16];
#pragma unroll
          for (int h = 0; h < 4; h++) feat_exp(pp[h][0], pp[h][1], e[h]);
          if (ps == 0) {
#pragma unroll
            for (int h = 0; h < 4; h++) {
              const float (&f)[16] = e[h];
              float sp0 = (f[0] + f[1]) + (f[4] + f[5]), sp1 = (f[2] + f[3]) + (f[6] + f[7]);
              float sn0 = (f[8] + f[9]) + (f[12] + f[13]), sn1 = (f[10] + f[11]) + (f[14] + f[15]);
              sp0 += __shfl_xor_sync(0xffffffffu, sp0, 1); sp1 += __shfl_xor_sync(0xffffffffu, sp1, 1);
              sn0 += __shfl_xor_sync(0xffffffffu, sn0, 1); sn1 += __shfl_xor_sync(0xffffffffu, sn1, 1);
              sp0 += __shfl_xor_sync(0xffffffffu, sp0, 2); sp1 += __shfl_xor_sync(0xffffffffu, sp1, 2);
              sn0 += __shfl_xor_sync(0xffffffffu, sn0, 2); sn1 += __shfl_xor_sync(0xffffffffu, sn1, 2);
              sp0 = rcp(sp0); sp1 = rcp(sp1); sn0 = rcp(sn0); sn1 = rcp(sn1);
              const uint32_t dst = scr + (h >> 1) * 8192 + lrow;
              stsm4(dst + ((((h & 1) * 4 + lhi) ^ lx) << 4), pack2(f[0] * sp0, f[1] * sp0), pack2(f[2] * sp1, f[3] * sp1),
                    pack2(f[4] * sp0, f[5] * sp0), pack2(f[6] * sp1, f[7] * sp1));
              stsm4(dst + ((((h & 1) * 4 + 2 + lhi) ^ lx) << 4), pack2(f[8] * sn0, f[9] * sn0), pack2(f[10] * sn1, f[11] * sn1),
                    pack2(f[12] * sn0, f[13] * sn0), pack2(f[14] * sn1, f[15] * sn1));
            }
          } else {
#pragma unroll
            for (int h = 0; h < 4; h++)
#pragma unroll
              for (int i = 0; i < 8; i++) A[2 * h + (i >> 2)][i & 3] = pack2(e[h][2 * i], e[h][2 * i + 1]);
          }
        } else {
#pragma unroll
          for (int h = 0; h < 4; h++) stsm4(scr + 16384 + lrow + (((2 * h + lhi) ^ lx) << 4), a[h][0], a[h][1], a[h][2], a[h][3]);
          fence_async_smem();
          bar_sync(1 + wg, 128);
          float kv0[36], kv1[36];
          wg_fence();
#pragma unroll
          for (int ks = 0; ks < 4; ks++) {
            const uint32_t vb = scr + 16384 + ks * 2048;
            const uint64_t db = mk_desc(vb, sb + SM_ONES - vb, 1024);
            wgmma_ss_n72_t11(kv0, mk_desc(scr + ks * 2048, 8192, 1024), db, ks != 0);
            wgmma_ss_n72_t11(kv1, mk_desc(scr + 8192 + ks * 2048, 8192, 1024), db, ks != 0);
          }
          wg_commit();
          wg_wait<0>();
          if (lead) release(wg ? ST_SCR1 : ST_SCR0);
          const bool up = wq >= 2;
          const int f = (wq & 1) * 16 + g;
          float* kvp = &g_kv[T ^ 1][((hg * 4 + (wq >> 1)) * 32 + f) * 16 + 2 * t];
          float* zp = &g_z[T ^ 1][(hg * 4 + (wq >> 1)) * 32 + f];
#pragma unroll
          for (int b = 0; b < 2; b++) {
#pragma unroll
            for (int n = 0; n < 2; n++) {
              float c0, c1, c2, c3;
              if (b == 0) {
                c0 = up ? kv0[8 + 4 * n + 0] : kv0[4 * n + 0]; c1 = up ? kv0[8 + 4 * n + 1] : kv0[4 * n + 1];
                c2 = up ? kv0[8 + 4 * n + 2] : kv0[4 * n + 2]; c3 = up ? kv0[8 + 4 * n + 3] : kv0[4 * n + 3];
              } else {
                c0 = up ? kv1[24 + 4 * n + 0] : kv1[16 + 4 * n + 0]; c1 = up ? kv1[24 + 4 * n + 1] : kv1[16 + 4 * n + 1];
                c2 = up ? kv1[24 + 4 * n + 2] : kv1[16 + 4 * n + 2]; c3 = up ? kv1[24 + 4 * n + 3] : kv1[16 + 4 * n + 3];
              }
              float* p = kvp + b * 1024 + n * 8;
              asm volatile("red.relaxed.gpu.global.add.v2.f32 [%0], {%1,%2};" ::"l"(p), "f"(c0), "f"(c1) : "memory");
              asm volatile("red.relaxed.gpu.global.add.v2.f32 [%0], {%1,%2};" ::"l"(p + 128), "f"(c2), "f"(c3) : "memory");
            }
            if (t == 0) {
              asm volatile("red.relaxed.gpu.global.add.f32 [%0], %1;" ::"l"(zp + b * 64), "f"(b ? kv1[32] : kv0[32]) : "memory");
              asm volatile("red.relaxed.gpu.global.add.f32 [%0], %1;" ::"l"(zp + b * 64 + 8), "f"(b ? kv1[34] : kv0[34]) : "memory");
            }
          }
          bar_arrive(6 + wg, 160);
        }
        TSTAMP(3 + 2 * ps);
      }
#pragma unroll
      for (int i = 0; i < 32; i++) E[i >> 3][i & 7] = A[i >> 2][i & 3];
    }
    const int rh = 2 * rb + wg;
    uint32_t xr[16];
    {
      const uint32_t* xp = reinterpret_cast<const uint32_t*>(x + (size_t)(rh * 64 + wq * 16 + g) * 512 + hg * 64 + 2 * t);
#pragma unroll
      for (int i = 0; i < 8; i++) { xr[2 * i] = __ldg(xp + 4 * i); xr[2 * i + 1] = __ldg(xp + 8 * 256 + 4 * i); }
    }
    mbar_wait(sb + SM_KVB);
    {
      const int r = tid & 127;
      const float4* src = reinterpret_cast<const float4*>(&g_kv[T ^ 1][hg * 2048 + r * 16]);
      const float4 a = __ldcg(src), b = __ldcg(src + 1), c = __ldcg(src + 2), d = __ldcg(src + 3);
      const uint32_t zz = pack2(__ldcg(&g_z[T ^ 1][hg * 128 + r]), 1.0f);
      uint4* dst = reinterpret_cast<uint4*>(smem + SM_KVS + r * 48);
      dst[0] = make_uint4(pack2(a.x, a.y), pack2(a.z, a.w), pack2(b.x, b.y), pack2(b.z, b.w));
      dst[1] = make_uint4(pack2(c.x, c.y), pack2(c.z, c.w), pack2(d.x, d.y), pack2(d.z, d.w));
      dst[2] = make_uint4(zz, zz, zz, zz);
      bar_sync(1 + wg, 128);
    }
    TSTAMP(8);
    {
      uint4* op = &g_o[rh][hg][wq][0][lane];
#pragma unroll
      for (int h = 0; h < 4; h++) {
        uint32_t b0[4], b1[4], b2[4];
        const uint32_t kb = sb + SM_KVS + (h * 32 + lane) * 48;
        ldsm4t(b0, kb); ldsm4t(b1, kb + 16); ldsm4t(b2, kb + 32);
        const uint32_t ep[4] = {E[h][0], E[h][1], E[h][2], E[h][3]}, en[4] = {E[h][4], E[h][5], E[h][6], E[h][7]};
        float np0[4] = {0, 0, 0, 0}, np1[4] = {0, 0, 0, 0}, nn0[4] = {0, 0, 0, 0}, nn1[4] = {0, 0, 0, 0}, dp[4] = {0, 0, 0, 0}, dn[4] = {0, 0, 0, 0};
        mma16816(dp, ep, b2[0], b2[1]);  mma16816(dn, en, b2[2], b2[3]);
        mma16816(np0, ep, b0[0], b0[1]); mma16816(nn0, en, b0[2], b0[3]);
        mma16816(np1, ep, b1[0], b1[1]); mma16816(nn1, en, b1[2], b1[3]);
        const float i0 = rcp(fmaf(dp[0], dn[1], fmaf(dn[0], dp[1], 1e-6f * dp[1] * dn[1])));
        const float i1 = rcp(fmaf(dp[2], dn[3], fmaf(dn[2], dp[3], 1e-6f * dp[3] * dn[3])));
        const float cp0 = dn[1] * i0, cn0 = dp[1] * i0, cp1 = dn[3] * i1, cn1 = dp[3] * i1;
        st_rlx4(op + h * 32,
                tg(pack2(fmaf(np0[0], cp0, nn0[0] * cn0), fmaf(np0[1], cp0, nn0[1] * cn0)), T),
                tg(pack2(fmaf(np0[2], cp1, nn0[2] * cn1), fmaf(np0[3], cp1, nn0[3] * cn1)), T),
                tg(pack2(fmaf(np1[0], cp0, nn1[0] * cn0), fmaf(np1[1], cp0, nn1[1] * cn0)), T),
                tg(pack2(fmaf(np1[2], cp1, nn1[2] * cn1), fmaf(np1[3], cp1, nn1[3] * cn1)), T));
      }
    }
    TSTAMP(9);

    {
      uint32_t A[8][4][4];
      const uint4* op = &g_o[rh][0][wq][0][lane];
      const uint32_t ob = sb + 2 * SLOT + wq * 2048 + lane * 16;
      float acc[32];
#pragma unroll
      for (int p = 0; p < 3; p++) {
        mbar_wait(sb + SM_FULL + (ST_O0 + 3 * wg + p) * 8);
#pragma unroll
        for (int c = 3 * p; c < (p < 2 ? 3 * p + 3 : 8); c++)
#pragma unroll
          for (int s = 0; s < 4; s++)
            asm volatile("ld.shared.v4.b32 {%0,%1,%2,%3}, [%4];" : "=r"(A[c][s][0]), "=r"(A[c][s][1]), "=r"(A[c][s][2]), "=r"(A[c][s][3])
                         : "r"(ob + c * 8192 + s * 512) : "memory");
        __syncwarp();
        if (lane == 0) release(ST_O0 + 3 * wg + p);
        mbar_wait(sb + SM_FULL + (ST_WO + p) * 8);
#pragma unroll
        for (int c = 3 * p; c < (p < 2 ? 3 * p + 3 : 8); c++) {
          chk_chunk(A[c], op + c * 512, T);
          wg_fence();
#pragma unroll
          for (int s = 0; s < 4; s++)
            wgmma_rs_n64(acc, A[c][s], mk_desc(sb + ((ST_WO + p) % NSLOT) * SLOT + ((c % 3) * 4 + s) * 2048, 8192, 1024), (c | s) != 0);
          wg_commit();
        }
      }
      wg_wait<0>();
      if ((tid & 127) < 3) release(ST_WO + (tid & 127));
      TSTAMP(10);
      uint32_t hw[16];
      float s0 = 0.f, s1 = 0.f, q0 = 0.f, q1 = 0.f;
#pragma unroll
      for (int i = 0; i < 8; i++) {
        hw[2 * i]     = pack2(blo(xr[2 * i]) + acc[4 * i], bhi(xr[2 * i]) + acc[4 * i + 1]);
        hw[2 * i + 1] = pack2(blo(xr[2 * i + 1]) + acc[4 * i + 2], bhi(xr[2 * i + 1]) + acc[4 * i + 3]);
      }
      uint4* hp_ = &g_h[rh][hg][wq][0][lane];
#pragma unroll
      for (int s = 0; s < 4; s++) st_rlx4(hp_ + s * 32, tg(hw[4 * s], T), tg(hw[4 * s + 1], T), tg(hw[4 * s + 2], T), tg(hw[4 * s + 3], T));
#pragma unroll
      for (int i = 0; i < 8; i++) {
        float a = blo(hw[2 * i]), b = bhi(hw[2 * i]);
        s0 += a + b; q0 = fmaf(a, a, q0); q0 = fmaf(b, b, q0);
        a = blo(hw[2 * i + 1]); b = bhi(hw[2 * i + 1]);
        s1 += a + b; q1 = fmaf(a, a, q1); q1 = fmaf(b, b, q1);
      }
      s0 += __shfl_xor_sync(0xffffffffu, s0, 1); s1 += __shfl_xor_sync(0xffffffffu, s1, 1);
      q0 += __shfl_xor_sync(0xffffffffu, q0, 1); q1 += __shfl_xor_sync(0xffffffffu, q1, 1);
      s0 += __shfl_xor_sync(0xffffffffu, s0, 2); s1 += __shfl_xor_sync(0xffffffffu, s1, 2);
      q0 += __shfl_xor_sync(0xffffffffu, q0, 2); q1 += __shfl_xor_sync(0xffffffffu, q1, 2);
      if (t < 2) st_rlx2(&g_st[rh][hg][wq * 16 + g + t * 8], tg(__float_as_uint(t ? s1 : s0), T), tg(__float_as_uint(t ? q1 : q0), T));
      uint32_t hx = T;
#pragma unroll
      for (int i = 0; i < 16; i++) hx |= (hw[i] & 1u) << (i + 1);
      st_rlx1(&g_hx[rh][hg][wq][lane], hx);
    }
    TSTAMP(11);

    const int rh3 = 2 * rb3 + wg;
    uint32_t HH[11][4];
    {
      uint32_t A[2][4][4];
      const uint4* hp_ = &g_h[rh3][0][wq][0][lane];
      uint32_t m0, m1;
      {
        const uint2* sp = &g_st[rh3][2 * t][wq * 16 + g];
        uint32_t a[4], b[4];
        int it = 0;
#pragma unroll 1
        do {
          ld_rlx2(a[0], a[1], sp); ld_rlx2(a[2], a[3], sp + 64); ld_rlx2(b[0], b[1], sp + 8); ld_rlx2(b[2], b[3], sp + 72);
          if (++it > (1 << 18)) break;
        } while (__any_sync(0xffffffffu, (bad4(a, T) | bad4(b, T)) & 1));
        ld_chunk(A[0], hp_);
        float s0 = __uint_as_float(a[0]) + __uint_as_float(a[2]), q0 = __uint_as_float(a[1]) + __uint_as_float(a[3]);
        float s1 = __uint_as_float(b[0]) + __uint_as_float(b[2]), q1 = __uint_as_float(b[1]) + __uint_as_float(b[3]);
        s0 += __shfl_xor_sync(0xffffffffu, s0, 1); s1 += __shfl_xor_sync(0xffffffffu, s1, 1);
        q0 += __shfl_xor_sync(0xffffffffu, q0, 1); q1 += __shfl_xor_sync(0xffffffffu, q1, 1);
        s0 += __shfl_xor_sync(0xffffffffu, s0, 2); s1 += __shfl_xor_sync(0xffffffffu, s1, 2);
        q0 += __shfl_xor_sync(0xffffffffu, q0, 2); q1 += __shfl_xor_sync(0xffffffffu, q1, 2);
        s0 *= (1.f / 512.f); s1 *= (1.f / 512.f);
        r0 = 1.f / (fmaxf(q0 * (1.f / 512.f) - s0 * s0, 0.f) + 1e-5f);
        r1 = 1.f / (fmaxf(q1 * (1.f / 512.f) - s1 * s1, 0.f) + 1e-5f);
        m0 = pack2(s0, s0); m1 = pack2(s1, s1);
      }
      TSTAMP(12);
      float ag[88], au[88];
      int slot = 5;
#pragma unroll 1
      for (int c2 = 0; c2 < 8; c2 += 2) {
#pragma unroll
        for (int b = 0; b < 2; b++) {
          const int c = c2 + b, sG = ST_GU + 2 * c;
          chk_chunk(A[b], hp_ + c * 512, T);
#pragma unroll
          for (int s = 0; s < 4; s++) {
            A[b][s][0] = hsub2(A[b][s][0], m0); A[b][s][1] = hsub2(A[b][s][1], m1);
            A[b][s][2] = hsub2(A[b][s][2], m0); A[b][s][3] = hsub2(A[b][s][3], m1);
          }
          mbar_wait(sb + SM_FULL + sG * 8);
          wg_fence();
#pragma unroll
          for (int s = 0; s < 4; s++)
            wgmma_rs_n176(ag, A[b][s], mk_desc(sb + slot * SLOT + s * 2048, 8192, 1024), (c | s) != 0);
          wg_commit();
          if (++slot == NSLOT) slot = 0;
          wg_wait<1>();
          if (lead && c > 0) release(sG - 1);
          if (c < 7) ld_chunk(A[b ^ 1], hp_ + (c + 1) * 512);
          mbar_wait(sb + SM_FULL + (sG + 1) * 8);
          wg_fence();
#pragma unroll
          for (int s = 0; s < 4; s++)
            wgmma_rs_n176(au, A[b][s], mk_desc(sb + slot * SLOT + s * 2048, 8192, 1024), (c | s) != 0);
          wg_commit();
          if (++slot == NSLOT) slot = 0;
          wg_wait<1>();
          if (lead) release(sG);
        }
      }
      wg_wait<0>();
      TSTAMP(13);
#pragma unroll
      for (int s = 0; s < 11; s++) {
        HH[s][0] = pack2(ag[8 * s + 0] * au[8 * s + 0] * r0, ag[8 * s + 1] * au[8 * s + 1] * r0);
        HH[s][1] = pack2(ag[8 * s + 2] * au[8 * s + 2] * r1, ag[8 * s + 3] * au[8 * s + 3] * r1);
        HH[s][2] = pack2(ag[8 * s + 4] * au[8 * s + 4] * r0, ag[8 * s + 5] * au[8 * s + 5] * r0);
        HH[s][3] = pack2(ag[8 * s + 6] * au[8 * s + 6] * r1, ag[8 * s + 7] * au[8 * s + 7] * r1);
      }
    }
    TSTAMP(14);

    {
      float acc[32], sum[32];
      uint32_t in[4][4];
      ld_chunk(in, &g_h[rh3][jf][wq][0][lane]);
      {
        uint32_t hx; int it = 0;
#pragma unroll 1
        do {
          hx = ld_rlx1(&g_hx[rh3][jf][wq][lane]);
          if (++it > (1 << 18)) break;
        } while (__any_sync(0xffffffffu, (hx ^ T) & 1));
#pragma unroll
        for (int i = 0; i < 16; i++) {
          sum[2 * i]     = blo((in[i >> 2][i & 3] & 0xFFFEu) | ((hx >> (i + 1)) & 1u));
          sum[2 * i + 1] = bhi(in[i >> 2][i & 3]);
        }
      }
      const uint4* inb = &g_part[rh3][jf][0][wq][0][lane];
      uint4* outb = &g_part[rh3][0][jf][wq][0][lane];
      int slot = (5 + 16) % NSLOT, q = 0, it = 0;
#pragma unroll 1
      for (int st = 0; q < 7; st++) {
        if (st < 8) {
          mbar_wait(sb + SM_FULL + (ST_D + st) * 8);
          wg_fence();
#pragma unroll
          for (int s = 0; s < 11; s++)
            wgmma_rs_n64(acc, HH[s], mk_desc(sb + slot * SLOT + s * 2048, 8192, 1024), s != 0);
          wg_commit();
          if (++slot == NSLOT) slot = 0;
        }
        if (st >= 4) {
          if (!__any_sync(0xffffffffu, (bad4(in[0], T) | bad4(in[1], T) | bad4(in[2], T) | bad4(in[3], T)) & 1) || ++it > (1 << 18)) {
#pragma unroll
            for (int i = 0; i < 16; i++) { sum[2 * i] += blo(in[i >> 2][i & 3]); sum[2 * i + 1] += bhi(in[i >> 2][i & 3]); }
            q++;
          }
        }
        if (st >= 3 && q < 7) ld_chunk(in, inb + ((jf - 1 - q) & 7) * 512);
        if (st < 8) wg_wait<0>();
        if (st < 7) {
          uint4* p = outb + ((jf + 1 + st) & 7) * 4096;
#pragma unroll
          for (int s = 0; s < 4; s++)
            st_rlx4(p + s * 32, tg(pack2(acc[8 * s + 0], acc[8 * s + 1]), T), tg(pack2(acc[8 * s + 2], acc[8 * s + 3]), T),
                    tg(pack2(acc[8 * s + 4], acc[8 * s + 5]), T), tg(pack2(acc[8 * s + 6], acc[8 * s + 7]), T));
        }
        if (st == 7) TSTAMP(15);
      }
      uint32_t* op = reinterpret_cast<uint32_t*>(out + (size_t)(rh3 * 64 + wq * 16 + g) * 512 + jf * 64 + 2 * t);
#pragma unroll
      for (int i = 0; i < 8; i++) {
        op[4 * i]           = pack2(sum[4 * i] + acc[4 * i], sum[4 * i + 1] + acc[4 * i + 1]);
        op[8 * 256 + 4 * i] = pack2(sum[4 * i + 2] + acc[4 * i + 2], sum[4 * i + 3] + acc[4 * i + 3]);
      }
    }
    TSTAMP(16);
    asm volatile("barrier.cluster.arrive.relaxed.aligned;" ::: "memory");
    asm volatile("barrier.cluster.wait.aligned;" ::: "memory");
  }
}

typedef CUresult (*EncodeFn)(CUtensorMap*, CUtensorMapDataType, cuuint32_t, void*, const cuuint64_t*, const cuuint64_t*,
                             const cuuint32_t*, const cuuint32_t*, CUtensorMapInterleave, CUtensorMapSwizzle,
                             CUtensorMapL2promotion, CUtensorMapFloatOOBfill);

void encode(EncodeFn fn, CUtensorMap* m, const void* base, int rank, const cuuint64_t* dims, const cuuint64_t* strides,
            const cuuint32_t* box) {
  cuuint32_t es[3] = {1, 1, 1};
  fn(m, CU_TENSOR_MAP_DATA_TYPE_BFLOAT16, (cuuint32_t)rank, const_cast<void*>(base), dims, strides, box, es,
     CU_TENSOR_MAP_INTERLEAVE_NONE, CU_TENSOR_MAP_SWIZZLE_128B, CU_TENSOR_MAP_L2_PROMOTION_L2_256B,
     CU_TENSOR_MAP_FLOAT_OOB_FILL_NONE);
}

}

extern "C" void kernel_launch(void* const* d_in, const int* in_sizes, int n_in, void* d_out, int out_size) {
  (void)in_sizes; (void)n_in; (void)out_size;
  const __nv_bfloat16* x    = (const __nv_bfloat16*)d_in[0];
  const __nv_bfloat16* wqkv = (const __nv_bfloat16*)d_in[1];
  const __nv_bfloat16* wphi = (const __nv_bfloat16*)d_in[2];
  const __nv_bfloat16* wo   = (const __nv_bfloat16*)d_in[3];
  const __nv_bfloat16* wg   = (const __nv_bfloat16*)d_in[5];
  const __nv_bfloat16* wu   = (const __nv_bfloat16*)d_in[6];
  const __nv_bfloat16* wd   = (const __nv_bfloat16*)d_in[7];

  static EncodeFn fn = nullptr;
  if (!fn) {
    void* p = nullptr;
    cudaDriverEntryPointQueryResult qr;
    cudaGetDriverEntryPoint("cuTensorMapEncodeTiled", &p, cudaEnableDefault, &qr);
    fn = (EncodeFn)p;
    cudaFuncSetAttribute(fused_kernel, cudaFuncAttributeMaxDynamicSharedMemorySize, SM_TOTAL);
  }
  Maps maps;
  {
    cuuint64_t d[3] = {64, 2048, 8}, s[2] = {1024, 128}; cuuint32_t b[3] = {64, 64, 3};
    encode(fn, &maps.x, x, 3, d, s, b);
  }
  {
    cuuint64_t d[2] = {1536, 512}, s[1] = {3072}; cuuint32_t b[2] = {64, 192};
    encode(fn, &maps.w, wqkv, 2, d, s, b);
  }
  {
    cuuint64_t d[2] = {512, 512}, s[1] = {1024}; cuuint32_t b[2] = {64, 192};
    encode(fn, &maps.wo, wo, 2, d, s, b);
  }
  {
    cuuint64_t d[3] = {176, 7, 512}, d7[3] = {144, 1, 512}, s[2] = {352, 2752}; cuuint32_t b[3] = {64, 1, 64};
    encode(fn, &maps.g, wg, 3, d, s, b);
    encode(fn, &maps.u, wu, 3, d, s, b);
    encode(fn, &maps.g7, wg + 1232, 3, d7, s, b);
    encode(fn, &maps.u7, wu + 1232, 3, d7, s, b);
  }
  {
    cuuint64_t d[2] = {512, 1376}, s[1] = {1024}; cuuint32_t b[2] = {64, 176};
    encode(fn, &maps.d, wd, 2, d, s, b);
  }
  fused_kernel<<<NCTA, 384, SM_TOTAL>>>(maps, x, wphi, wo, wg, wu, wd, (__nv_bfloat16*)d_out);
}
```

```cpp
#include <cuda_runtime.h>
#include <cuda_bf16.h>
#include <cuda.h>
#include <stdint.h>

#define PROF 0

namespace {

constexpr int NCTA   = 128;
constexpr int SLOT   = 24576;
constexpr int NSLOT  = 9;
constexpr int NSTAGE = 50;

constexpr int ST_X0   = 0;
constexpr int ST_WK   = 3;
constexpr int ST_X1   = 6;
constexpr int ST_SCR0 = 9;
constexpr int ST_WV   = 10;
constexpr int ST_SCR1 = 13;
constexpr int ST_WQ   = 14;
constexpr int ST_WO   = 17;
constexpr int ST_O0   = 20;
constexpr int ST_O1   = 23;
constexpr int ST_GU   = 26;
constexpr int ST_D    = 42;

__host__ __device__ constexpr int st_next(int d) { return d < ST_WQ ? d + 9 : d < ST_O0 ? d + 12 : d < ST_O1 ? d + 3 : d + 9; }
__host__ __device__ constexpr int st_bytes(int s) { return s >= ST_D ? 22528 : (s == ST_O0 + 2 || s == ST_O1 + 2) ? 16384 : 24576; }
__host__ __device__ constexpr int st_empty_cnt(int d) {
  return ((d < 3 || (d >= 6 && d < 9) || (d >= ST_O0 && d < ST_GU)) ? 4 : (d == ST_SCR0 || d == ST_SCR1) ? 1 : 2) *
         (st_next(d) >= ST_GU ? 2 : 1);
}

constexpr int SM_ONES = NSLOT * SLOT;
constexpr int SM_WPHI = SM_ONES + 2048;
constexpr int SM_KVS  = SM_WPHI + 2048;
constexpr int SM_KV32 = 4 * SLOT + 16384;
constexpr int SM_BAR  = SM_KVS + 6144;
constexpr int SM_FULL  = SM_BAR;
constexpr int SM_EMPTY = SM_BAR + NSTAGE * 8;
constexpr int SM_MISCB = SM_BAR + 2 * NSTAGE * 8;
constexpr int SM_KVB   = SM_MISCB + 8;
constexpr int SM_EPOCH = SM_KVB + 8;
constexpr int SM_TOTAL = SM_BAR + 1024;

static_assert(SM_TOTAL == 232448, "smem budget");

struct Maps { CUtensorMap x, w, wo, g, u, g7, u7, d; };

__device__ uint4    g_o[32][8][4][4][32];
__device__ uint4    g_h[32][8][4][4][32];
__device__ uint32_t g_hx[32][8][4][32];
__device__ uint2    g_st[32][8][64];
__device__ uint4    g_part[32][8][8][4][4][32];
__device__ float    g_kv[2][32 * 32 * 16];
__device__ float    g_z[2][32 * 32];
__device__ unsigned g_kvcnt[8 * 32];
__device__ unsigned g_start;

__device__ __forceinline__ uint32_t smem_u32(const void* p) { return (uint32_t)__cvta_generic_to_shared(p); }
__device__ __forceinline__ void mbar_init(uint32_t bar, int cnt) {
  asm volatile("mbarrier.init.shared::cta.b64 [%0], %1;" ::"r"(bar), "r"(cnt) : "memory");
}
__device__ __forceinline__ void mbar_expect_tx(uint32_t bar, uint32_t bytes) {
  asm volatile("mbarrier.arrive.expect_tx.shared::cta.b64 _, [%0], %1;" ::"r"(bar), "r"(bytes) : "memory");
}
__device__ __forceinline__ void mbar_arrive(uint32_t bar) {
  asm volatile("mbarrier.arrive.shared::cta.b64 _, [%0];" ::"r"(bar) : "memory");
}
__device__ __forceinline__ void mbar_arrive_cluster(uint32_t bar, uint32_t rank) {
  asm volatile("{\n.reg .b32 ra;\nmapa.shared::cluster.u32 ra, %0, %1;\n"
               "mbarrier.arrive.shared::cluster.b64 _, [ra];\n}" ::"r"(bar), "r"(rank) : "memory");
}
__device__ __forceinline__ bool mbar_try(uint32_t bar) {
  uint32_t ok;
  asm volatile("{\n.reg .pred p;\nmbarrier.try_wait.parity.shared::cta.b64 p, [%1], 0;\nselp.u32 %0, 1, 0, p;\n}"
               : "=r"(ok) : "r"(bar) : "memory");
  return ok != 0;
}
__device__ __forceinline__ void mbar_wait(uint32_t bar) {
  int it = 0;
#pragma unroll 1
  while (!mbar_try(bar)) {
    if (++it > (1 << 20)) __trap();
  }
}
__device__ __forceinline__ void bar_sync(int id, int n)   { asm volatile("bar.sync %0, %1;" ::"r"(id), "r"(n) : "memory"); }
__device__ __forceinline__ void bar_arrive(int id, int n) { asm volatile("bar.arrive %0, %1;" ::"r"(id), "r"(n) : "memory"); }
__device__ __forceinline__ void fence_async_smem() { asm volatile("fence.proxy.async.shared::cta;" ::: "memory"); }
__device__ __forceinline__ void wg_fence()  { asm volatile("wgmma.fence.sync.aligned;" ::: "memory"); }
__device__ __forceinline__ void wg_commit() { asm volatile("wgmma.commit_group.sync.aligned;" ::: "memory"); }
template <int N> __device__ __forceinline__ void wg_wait() { asm volatile("wgmma.wait_group.sync.aligned %0;" ::"n"(N) : "memory"); }
#define DESC(off) (db + ((uint32_t)(off) >> 4))
__device__ __forceinline__ void tma2d(uint32_t dst, const CUtensorMap* m, int c0, int c1, uint32_t bar) {
  asm volatile("cp.async.bulk.tensor.2d.shared::cluster.global.mbarrier::complete_tx::bytes [%0], [%1, {%3, %4}], [%2];"
               ::"r"(dst), "l"(m), "r"(bar), "r"(c0), "r"(c1) : "memory");
}
__device__ __forceinline__ void tma2d_mc(uint32_t dst, const CUtensorMap* m, int c0, int c1, uint32_t bar) {
  asm volatile("cp.async.bulk.tensor.2d.shared::cluster.global.mbarrier::complete_tx::bytes.multicast::cluster [%0], [%1, {%3, %4}], [%2], %5;"
               ::"r"(dst), "l"(m), "r"(bar), "r"(c0), "r"(c1), "h"((uint16_t)3) : "memory");
}
__device__ __forceinline__ void tma3d(uint32_t dst, const CUtensorMap* m, int c0, int c1, int c2, uint32_t bar) {
  asm volatile("cp.async.bulk.tensor.3d.shared::cluster.global.mbarrier::complete_tx::bytes [%0], [%1, {%3, %4, %5}], [%2];"
               ::"r"(dst), "l"(m), "r"(bar), "r"(c0), "r"(c1), "r"(c2) : "memory");
}
__device__ __forceinline__ void tma3d_mc(uint32_t dst, const CUtensorMap* m, int c0, int c1, int c2, uint32_t bar) {
  asm volatile("cp.async.bulk.tensor.3d.shared::cluster.global.mbarrier::complete_tx::bytes.multicast::cluster [%0], [%1, {%3, %4, %5}], [%2], %6;"
               ::"r"(dst), "l"(m), "r"(bar), "r"(c0), "r"(c1), "r"(c2), "h"((uint16_t)3) : "memory");
}
__device__ __forceinline__ void ldsm4(uint32_t (&r)[4], uint32_t addr) {
  asm volatile("ldmatrix.sync.aligned.m8n8.x4.shared.b16 {%0,%1,%2,%3}, [%4];"
               : "=r"(r[0]), "=r"(r[1]), "=r"(r[2]), "=r"(r[3]) : "r"(addr) : "memory");
}
__device__ __forceinline__ void ldsm4t(uint32_t (&r)[4], uint32_t addr) {
  asm volatile("ldmatrix.sync.aligned.m8n8.x4.trans.shared.b16 {%0,%1,%2,%3}, [%4];"
               : "=r"(r[0]), "=r"(r[1]), "=r"(r[2]), "=r"(r[3]) : "r"(addr) : "memory");
}
__device__ __forceinline__ void stsm4(uint32_t addr, uint32_t r0, uint32_t r1, uint32_t r2, uint32_t r3) {
  asm volatile("stmatrix.sync.aligned.m8n8.x4.shared.b16 [%0], {%1,%2,%3,%4};"
               ::"r"(addr), "r"(r0), "r"(r1), "r"(r2), "r"(r3) : "memory");
}
__device__ __forceinline__ void mma16816(float (&c)[4], const uint32_t (&a)[4], uint32_t b0, uint32_t b1) {
  asm volatile("mma.sync.aligned.m16n8k16.row.col.f32.bf16.bf16.f32 {%0,%1,%2,%3},{%4,%5,%6,%7},{%8,%9},{%0,%1,%2,%3};"
               : "+f"(c[0]), "+f"(c[1]), "+f"(c[2]), "+f"(c[3])
               : "r"(a[0]), "r"(a[1]), "r"(a[2]), "r"(a[3]), "r"(b0), "r"(b1));
}
__device__ __forceinline__ uint32_t pack2(float lo, float hi) {
  uint32_t r; asm("cvt.rn.bf16x2.f32 %0, %1, %2;" : "=r"(r) : "f"(hi), "f"(lo)); return r;
}
__device__ __forceinline__ float blo(uint32_t w) { return __uint_as_float(w << 16); }
__device__ __forceinline__ float bhi(uint32_t w) { return __uint_as_float(w & 0xFFFF0000u); }
__device__ __forceinline__ uint32_t hsub2(uint32_t a, uint32_t b) { uint32_t r; asm("sub.rn.bf16x2 %0, %1, %2;" : "=r"(r) : "r"(a), "r"(b)); return r; }
__device__ __forceinline__ uint32_t hadd2(uint32_t a, uint32_t b) { uint32_t r; asm("add.rn.bf16x2 %0, %1, %2;" : "=r"(r) : "r"(a), "r"(b)); return r; }
__device__ __forceinline__ uint32_t hmul2(uint32_t a, uint32_t b) { uint32_t r; asm("mul.rn.bf16x2 %0, %1, %2;" : "=r"(r) : "r"(a), "r"(b)); return r; }
__device__ __forceinline__ uint32_t hfma2(uint32_t a, uint32_t b, uint32_t c) { uint32_t r; asm("fma.rn.bf16x2 %0, %1, %2, %3;" : "=r"(r) : "r"(a), "r"(b), "r"(c)); return r; }
__device__ __forceinline__ uint32_t hmax2(uint32_t a, uint32_t b) { uint32_t r; asm("max.bf16x2 %0, %1, %2;" : "=r"(r) : "r"(a), "r"(b)); return r; }
__device__ __forceinline__ uint32_t hmin2(uint32_t a, uint32_t b) { uint32_t r; asm("min.bf16x2 %0, %1, %2;" : "=r"(r) : "r"(a), "r"(b)); return r; }
__device__ __forceinline__ float ex2(float x) { float r; asm("ex2.approx.ftz.f32 %0, %1;" : "=f"(r) : "f"(x)); return r; }
__device__ __forceinline__ float rcp(float x) { float r; asm("rcp.approx.ftz.f32 %0, %1;" : "=f"(r) : "f"(x)); return r; }
__device__ __forceinline__ void ld_rlx4(uint32_t (&r)[4], const uint4* p) {
  asm volatile("ld.relaxed.gpu.global.v4.b32 {%0,%1,%2,%3}, [%4];"
               : "=r"(r[0]), "=r"(r[1]), "=r"(r[2]), "=r"(r[3]) : "l"(p) : "memory");
}
__device__ __forceinline__ void st_rlx4(uint4* p, uint32_t a, uint32_t b, uint32_t c, uint32_t d) {
  asm volatile("st.relaxed.gpu.global.v4.b32 [%0], {%1,%2,%3,%4};" ::"l"(p), "r"(a), "r"(b), "r"(c), "r"(d) : "memory");
}
__device__ __forceinline__ void st_rlx2(uint2* p, uint32_t a, uint32_t b) {
  asm volatile("st.relaxed.gpu.global.v2.b32 [%0], {%1,%2};" ::"l"(p), "r"(a), "r"(b) : "memory");
}
__device__ __forceinline__ uint32_t ld_rlx1(const uint32_t* p) {
  uint32_t r; asm volatile("ld.relaxed.gpu.global.b32 %0, [%1];" : "=r"(r) : "l"(p) : "memory"); return r;
}
__device__ __forceinline__ void st_rlx1(uint32_t* p, uint32_t a) {
  asm volatile("st.relaxed.gpu.global.b32 [%0], %1;" ::"l"(p), "r"(a) : "memory");
}
__device__ __forceinline__ void ld_rlx2(uint32_t& a, uint32_t& b, const uint2* p) {
  asm volatile("ld.relaxed.gpu.global.v2.b32 {%0,%1}, [%2];" : "=r"(a), "=r"(b) : "l"(p) : "memory");
}
__device__ __forceinline__ void bulk_g2s(uint32_t dst, const void* src, uint32_t bytes, uint32_t bar) {
  asm volatile("cp.async.bulk.shared::cluster.global.mbarrier::complete_tx::bytes [%0], [%1], %2, [%3];"
               ::"r"(dst), "l"(src), "r"(bytes), "r"(bar) : "memory");
}
__device__ __forceinline__ uint32_t tg(uint32_t w, uint32_t T) { return (w & 0xFFFFFFFEu) | T; }
__device__ __forceinline__ uint32_t bad4(const uint32_t (&r)[4], uint32_t T) { return (r[0] ^ T) | (r[1] ^ T) | (r[2] ^ T) | (r[3] ^ T); }

__device__ __forceinline__ void ld_chunk(uint32_t (&a)[4][4], const uint4* p) {
#pragma unroll
  for (int s = 0; s < 4; s++) ld_rlx4(a[s], p + s * 32);
}
__device__ __forceinline__ void chk_chunk(uint32_t (&a)[4][4], const uint4* p, uint32_t T) {
  int it = 0;
#pragma unroll 1
  while (__any_sync(0xffffffffu, (bad4(a[0], T) | bad4(a[1], T) | bad4(a[2], T) | bad4(a[3], T)) & 1)) {
    ld_chunk(a, p);
    if (++it > (1 << 18)) break;
  }
}

__device__ __forceinline__ void wgmma_rs_n64(float (&d)[32], const uint32_t (&a)[4], uint32_t descB, int scaleD) {
  asm volatile("{\n.reg .pred p;\n.reg .b64 db;\nsetp.ne.b32 p, %37, 0;\nmov.b64 db, {%36, 0x40000040};\n"
    "wgmma.mma_async.sync.aligned.m64n64k16.f32.bf16.bf16 {%0,%1,%2,%3,%4,%5,%6,%7,%8,%9,%10,%11,%12,%13,%14,%15,%16,%17,%18,%19,%20,%21,%22,%23,%24,%25,%26,%27,%28,%29,%30,%31}, {%32,%33,%34,%35}, db, p, 1, 1, 1;\n}\n"
    : "+f"(d[0]),"+f"(d[1]),"+f"(d[2]),"+f"(d[3]),"+f"(d[4]),"+f"(d[5]),"+f"(d[6]),"+f"(d[7]),"+f"(d[8]),"+f"(d[9]),"+f"(d[10]),"+f"(d[11]),"+f"(d[12]),"+f"(d[13]),"+f"(d[14]),"+f"(d[15]),"+f"(d[16]),"+f"(d[17]),"+f"(d[18]),"+f"(d[19]),"+f"(d[20]),"+f"(d[21]),"+f"(d[22]),"+f"(d[23]),"+f"(d[24]),"+f"(d[25]),"+f"(d[26]),"+f"(d[27]),"+f"(d[28]),"+f"(d[29]),"+f"(d[30]),"+f"(d[31])
    : "r"(a[0]), "r"(a[1]), "r"(a[2]), "r"(a[3]), "r"(descB), "r"(scaleD));
}
__device__ __forceinline__ void wgmma_rs_n176(float (&d)[88], const uint32_t (&a)[4], uint32_t descB, int scaleD) {
  asm volatile("{\n.reg .pred p;\n.reg .b64 db;\nsetp.ne.b32 p, %93, 0;\nmov.b64 db, {%92, 0x40000040};\n"
    "wgmma.mma_async.sync.aligned.m64n176k16.f32.bf16.bf16 {%0,%1,%2,%3,%4,%5,%6,%7,%8,%9,%10,%11,%12,%13,%14,%15,%16,%17,%18,%19,%20,%21,%22,%23,%24,%25,%26,%27,%28,%29,%30,%31,%32,%33,%34,%35,%36,%37,%38,%39,%40,%41,%42,%43,%44,%45,%46,%47,%48,%49,%50,%51,%52,%53,%54,%55,%56,%57,%58,%59,%60,%61,%62,%63,%64,%65,%66,%67,%68,%69,%70,%71,%72,%73,%74,%75,%76,%77,%78,%79,%80,%81,%82,%83,%84,%85,%86,%87}, {%88,%89,%90,%91}, db, p, 1, 1, 1;\n}\n"
    : "+f"(d[0]),"+f"(d[1]),"+f"(d[2]),"+f"(d[3]),"+f"(d[4]),"+f"(d[5]),"+f"(d[6]),"+f"(d[7]),"+f"(d[8]),"+f"(d[9]),"+f"(d[10]),"+f"(d[11]),"+f"(d[12]),"+f"(d[13]),"+f"(d[14]),"+f"(d[15]),"+f"(d[16]),"+f"(d[17]),"+f"(d[18]),"+f"(d[19]),"+f"(d[20]),"+f"(d[21]),"+f"(d[22]),"+f"(d[23]),"+f"(d[24]),"+f"(d[25]),"+f"(d[26]),"+f"(d[27]),"+f"(d[28]),"+f"(d[29]),"+f"(d[30]),"+f"(d[31]),"+f"(d[32]),"+f"(d[33]),"+f"(d[34]),"+f"(d[35]),"+f"(d[36]),"+f"(d[37]),"+f"(d[38]),"+f"(d[39]),"+f"(d[40]),"+f"(d[41]),"+f"(d[42]),"+f"(d[43]),"+f"(d[44]),"+f"(d[45]),"+f"(d[46]),"+f"(d[47]),"+f"(d[48]),"+f"(d[49]),"+f"(d[50]),"+f"(d[51]),"+f"(d[52]),"+f"(d[53]),"+f"(d[54]),"+f"(d[55]),"+f"(d[56]),"+f"(d[57]),"+f"(d[58]),"+f"(d[59]),"+f"(d[60]),"+f"(d[61]),"+f"(d[62]),"+f"(d[63]),"+f"(d[64]),"+f"(d[65]),"+f"(d[66]),"+f"(d[67]),"+f"(d[68]),"+f"(d[69]),"+f"(d[70]),"+f"(d[71]),"+f"(d[72]),"+f"(d[73]),"+f"(d[74]),"+f"(d[75]),"+f"(d[76]),"+f"(d[77]),"+f"(d[78]),"+f"(d[79]),"+f"(d[80]),"+f"(d[81]),"+f"(d[82]),"+f"(d[83]),"+f"(d[84]),"+f"(d[85]),"+f"(d[86]),"+f"(d[87])
    : "r"(a[0]), "r"(a[1]), "r"(a[2]), "r"(a[3]), "r"(descB), "r"(scaleD));
}
__device__ __forceinline__ void wgmma_ss_n72_t11(float (&d)[36], uint32_t descA, uint32_t descB, int scaleD) {
  asm volatile("{\n.reg .pred p;\n.reg .b64 da, db;\nsetp.ne.b32 p, %38, 0;\nmov.b64 da, {%36, 0x40000040};\nmov.b64 db, {%37, 0x40000040};\n"
    "wgmma.mma_async.sync.aligned.m64n72k16.f32.bf16.bf16 {%0,%1,%2,%3,%4,%5,%6,%7,%8,%9,%10,%11,%12,%13,%14,%15,%16,%17,%18,%19,%20,%21,%22,%23,%24,%25,%26,%27,%28,%29,%30,%31,%32,%33,%34,%35}, da, db, p, 1, 1, 1, 1;\n}\n"
    : "+f"(d[0]),"+f"(d[1]),"+f"(d[2]),"+f"(d[3]),"+f"(d[4]),"+f"(d[5]),"+f"(d[6]),"+f"(d[7]),"+f"(d[8]),"+f"(d[9]),"+f"(d[10]),"+f"(d[11]),"+f"(d[12]),"+f"(d[13]),"+f"(d[14]),"+f"(d[15]),"+f"(d[16]),"+f"(d[17]),"+f"(d[18]),"+f"(d[19]),"+f"(d[20]),"+f"(d[21]),"+f"(d[22]),"+f"(d[23]),"+f"(d[24]),"+f"(d[25]),"+f"(d[26]),"+f"(d[27]),"+f"(d[28]),"+f"(d[29]),"+f"(d[30]),"+f"(d[31]),"+f"(d[32]),"+f"(d[33]),"+f"(d[34]),"+f"(d[35])
    : "r"(descA), "r"(descB), "r"(scaleD));
}

#define TSTAMP(i) do {} while (0)
#define TS2(w, i) do {} while (0)

constexpr float LOG2E = 1.4426950408889634f;

__device__ __forceinline__ void feat_exp(const float (&p0)[4], const float (&p1)[4], float (&e)[16]) {
  uint32_t P0 = pack2(p0[0], p0[1]), P1 = pack2(p0[2], p0[3]), P2 = pack2(p1[0], p1[1]), P3 = pack2(p1[2], p1[3]);
  uint32_t a = hmax2(P0, P2), b = hmax2(P1, P3);
  uint32_t mx = hmax2(__byte_perm(a, b, 0x5410), __byte_perm(a, b, 0x7632));
  a = hmin2(P0, P2); b = hmin2(P1, P3);
  uint32_t mn = hmin2(__byte_perm(a, b, 0x5410), __byte_perm(a, b, 0x7632));
  mx = hmax2(mx, __shfl_xor_sync(0xffffffffu, mx, 1));
  mn = hmin2(mn, __shfl_xor_sync(0xffffffffu, mn, 1));
  mx = hmax2(mx, __shfl_xor_sync(0xffffffffu, mx, 2));
  mn = hmin2(mn, __shfl_xor_sync(0xffffffffu, mn, 2));
  float mx0 = -blo(mx) * LOG2E, mx1 = -bhi(mx) * LOG2E, mn0 = blo(mn) * LOG2E, mn1 = bhi(mn) * LOG2E;
  float v[8] = {blo(P0), bhi(P0), blo(P1), bhi(P1), blo(P2), bhi(P2), blo(P3), bhi(P3)};
#pragma unroll
  for (int i = 0; i < 8; i++) {
    bool r1 = (i >> 1) & 1;
    e[i]     = ex2(fmaf(v[i],  LOG2E, r1 ? mx1 : mx0));
    e[8 + i] = ex2(fmaf(v[i], -LOG2E, r1 ? mn1 : mn0));
  }
}

__global__ void __cluster_dims__(2, 1, 1) __launch_bounds__(384, 1)
fused_kernel(const __grid_constant__ Maps maps, const __nv_bfloat16* __restrict__ x, const __nv_bfloat16* __restrict__ wphi,
             const __nv_bfloat16* __restrict__ wo, const __nv_bfloat16* __restrict__ wg_, const __nv_bfloat16* __restrict__ wu_,
             const __nv_bfloat16* __restrict__ wd_, __nv_bfloat16* __restrict__ out) {
  extern __shared__ __align__(1024) unsigned char smem[];
  const uint32_t sb = smem_u32(smem);
  const int tid = threadIdx.x, lane = tid & 31;
  const int warp = __shfl_sync(0xffffffffu, tid >> 5, 0);
  const uint32_t rank = blockIdx.x & 1;
  const int cl = blockIdx.x >> 1;
  int quad, qi;
  if (cl < 4) { quad = 15; qi = cl; }
  else if (cl < 36) { quad = (cl - 4) & 7; qi = (cl - 4) >> 3; }
  else { qi = (cl - 36) / 7; quad = 8 + (cl - 36) - 7 * qi; }
  const int rb = quad, hg = 2 * qi + rank;
  const int rb3 = (quad & ~1) + rank, jf = 4 * (quad & 1) + qi;

  if (warp >= 8) {
    asm volatile("setmaxnreg.dec.sync.aligned.u32 24;");
    if (lane == 0) {
      if (warp == 8) {
#pragma unroll
        for (int s = 0; s < 9; s++) {
          const uint32_t bar = sb + SM_FULL + s * 8;
          mbar_init(bar, 1);
          mbar_expect_tx(bar, SLOT);
          if (s >= 3 && s < 6) tma2d(sb + s * SLOT, &maps.w, 512 + hg * 64, (s - 3) * 192, bar);
          else tma3d(sb + s * SLOT, &maps.x, 0, rb * 128 + (s >= 6 ? 64 : 0), 3 * (s % 3), bar);
        }
      } else if (warp == 9) {
        mbar_init(sb + SM_MISCB, 2);
        mbar_init(sb + SM_KVB, 1);
        mbar_expect_tx(sb + SM_MISCB, 2048);
        mbar_expect_tx(sb + SM_KVB, 8192 + 512);
        bulk_g2s(sb + SM_WPHI, wphi + hg * 1024, 2048, sb + SM_MISCB);
      } else if (warp == 11) {
        *reinterpret_cast<volatile unsigned*>(smem + SM_EPOCH) = atomicAdd(&g_start, 1u) / NCTA;
      }
      asm volatile("fence.mbarrier_init.release.cluster;" ::: "memory");
    }
    if (tid == 256) TS2(0, 18);
    __syncwarp();
    if (warp != 11) bar_sync(0, 352);
    asm volatile("barrier.cluster.arrive.relaxed.aligned;" ::: "memory");
    if (warp == 8) {
      asm volatile("barrier.cluster.wait.aligned;" ::: "memory");
      if (lane == 0) {
        const CUtensorMap* mgu = rank ? (jf == 7 ? &maps.u7 : &maps.u) : (jf == 7 ? &maps.g7 : &maps.g);
        asm volatile("prefetch.tensormap [%0];" ::"l"(&maps.wo) : "memory");
        asm volatile("prefetch.tensormap [%0];" ::"l"(mgu) : "memory");
        asm volatile("prefetch.tensormap [%0];" ::"l"(&maps.d) : "memory");
#pragma unroll 1
        for (int s = ST_WV; s < ST_O0; s++) {
          if (s == ST_SCR1) continue;
          mbar_wait(sb + SM_EMPTY + (s - 9) * 8);
          const uint32_t dst = sb + (s >= 18 ? s - 18 : s - 9) * SLOT, bar = sb + SM_FULL + s * 8;
          if (s < ST_WO) tma2d(dst, &maps.w, (s < ST_WQ ? 1024 : 0) + hg * 64, (s < ST_WQ ? s - ST_WV : s - ST_WQ) * 192, bar);
          else { mbar_wait(bar - 8); tma2d(dst, &maps.wo, hg * 64, (s - ST_WO) * 192, bar); }
        }
        const int jc = jf == 7 ? 0 : jf;
        int slot = 5 + rank;
#pragma unroll 1
        for (int s = ST_GU + rank; s < NSTAGE; s += 2) {
          mbar_wait(sb + SM_EMPTY + (s < ST_GU + 6 ? s - 12 : s - 9) * 8);
          if (s > ST_GU && s < ST_GU + NSLOT) mbar_wait(sb + SM_FULL + (s - 1) * 8);
          const uint32_t dst = sb + slot * SLOT, bar = sb + SM_FULL + s * 8;
          if (s < ST_D) {
            const int c = (s - ST_GU) >> 1;
#pragma unroll
            for (int b = 0; b < 3; b++) tma3d_mc(dst + b * 8192, mgu, b * 64, jc, c * 64, bar);
          } else {
            tma2d_mc(dst, &maps.d, ((jf + 1 + (s - ST_D)) & 7) * 64, jf * 176, bar);
          }
          slot += 2; if (slot >= NSLOT) slot -= NSLOT;
        }
      }
      __syncwarp();
    } else {
      asm volatile("barrier.cluster.wait.aligned;" ::: "memory");
      if (warp == 11) {
#pragma unroll
        for (int i = 0; i < 4; i++)
          reinterpret_cast<uint4*>(smem + SM_ONES)[lane + 32 * i] = make_uint4(0x3F803F80u, 0x3F803F80u, 0x3F803F80u, 0x3F803F80u);
        fence_async_smem();
        __syncwarp();
        if (lane == 0) { mbar_arrive(sb + SM_MISCB); TS2(0, 19); }
      }
      mbar_wait(sb + SM_MISCB);
      const unsigned epoch = *reinterpret_cast<volatile unsigned*>(smem + SM_EPOCH);
      const uint32_t T = (epoch & 1) ^ 1;
      if (warp == 11) {
        reinterpret_cast<float4*>(&g_kv[T][blockIdx.x * 128])[lane] = make_float4(0.f, 0.f, 0.f, 0.f);
        if (lane < 8) g_z[T][blockIdx.x * 8 + lane] = 0.f;
        mbar_wait(sb + SM_FULL + (ST_X1 + 2) * 8);
        if (lane == 0) {
          asm volatile("cp.async.bulk.prefetch.L2.global [%0], 4096;" ::"l"((const char*)wo + blockIdx.x * 4096) : "memory");
          asm volatile("cp.async.bulk.prefetch.L2.global [%0], 11008;" ::"l"((const char*)wg_ + blockIdx.x * 11008) : "memory");
          asm volatile("cp.async.bulk.prefetch.L2.global [%0], 11008;" ::"l"((const char*)wu_ + blockIdx.x * 11008) : "memory");
          asm volatile("cp.async.bulk.prefetch.L2.global [%0], 11008;" ::"l"((const char*)wd_ + blockIdx.x * 11008) : "memory");
          const unsigned target = (epoch + 1) * 32;
          unsigned v; int it = 0;
#pragma unroll 1
          do {
            asm volatile("ld.acquire.gpu.global.u32 %0, [%1];" : "=r"(v) : "l"(&g_kvcnt[hg * 32]) : "memory");
            if (++it > (1 << 18)) break;
          } while ((int)(v - target) < 0);
          TS2(0, 26);
          asm volatile("fence.proxy.async;" ::: "memory");
          bulk_g2s(sb + SM_KV32, &g_kv[T ^ 1][hg * 2048], 8192, sb + SM_KVB);
          bulk_g2s(sb + SM_ONES, &g_z[T ^ 1][hg * 128], 512, sb + SM_KVB);
          TS2(1, 26);
        }
        __syncwarp();
      } else {
        const int w = warp - 9;
        st_rlx4(reinterpret_cast<uint4*>(&g_st[2 * rb + w][hg][0]) + lane, T ^ 1, T ^ 1, T ^ 1, T ^ 1);
        if (lane < 8) st_rlx4(&g_o[2 * rb + w][hg][lane >> 1][3][30 + (lane & 1)], T ^ 1, T ^ 1, T ^ 1, T ^ 1);
        bar_sync(6 + w, 160);
        if (lane == 0) {
          asm volatile("fence.acq_rel.gpu;" ::: "memory");
          TS2(w, 25);
          asm volatile("red.relaxed.gpu.global.add.u32 [%0], 1;" ::"l"(&g_kvcnt[hg * 32]) : "memory");
        }
        mbar_wait(sb + SM_KVB);
        const uint32_t* pw = reinterpret_cast<const uint32_t*>(&g_o[2 * rb + w][lane >> 2][lane & 3][3][31]) + 3;
        int it = 0;
#pragma unroll 1
        while (__any_sync(0xffffffffu, (ld_rlx1(pw) ^ T) & 1)) { if (++it > (1 << 18)) break; }
        if (lane == 0) {
          TS2(w, 27);
#pragma unroll 1
          for (int i = 0; i < 3; i++) {
            mbar_wait(sb + SM_EMPTY + (w ? ST_O0 + i : ST_O0 - 9 + i) * 8);
            bulk_g2s(sb + (2 + i) * SLOT, &g_o[2 * rb + w][3 * i][0][0][0], i < 2 ? 24576 : 16384, sb + SM_FULL + (ST_O0 + 3 * w + i) * 8);
          }
        }
        __syncwarp();
      }
    }
    asm volatile("barrier.cluster.arrive.relaxed.aligned;" ::: "memory");
    asm volatile("barrier.cluster.wait.aligned;" ::: "memory");
  } else {
    asm volatile("setmaxnreg.inc.sync.aligned.u32 240;");
    if (lane == 0) {
#pragma unroll 1
      for (int d = warp; d + 9 < NSTAGE; d += 8) {
        mbar_init(sb + SM_EMPTY + d * 8, st_empty_cnt(d));
        mbar_init(sb + SM_FULL + (d + 9) * 8, 1);
        mbar_expect_tx(sb + SM_FULL + (d + 9) * 8, st_bytes(d + 9));
      }
      asm volatile("fence.mbarrier_init.release.cluster;" ::: "memory");
    }
    __syncwarp();
    bar_sync(0, 352);
    asm volatile("barrier.cluster.arrive.relaxed.aligned;" ::: "memory");
    const int wg = warp >> 2, wq = warp & 3, g = lane >> 2, t = lane & 3;
    const bool lead = (tid & 127) == 0;
    const uint32_t db = ((sb & 0x3FFFF) >> 4) | (512u << 16);
    auto release = [&](int d) {
      const int s = st_next(d);
      if (s < NSTAGE) mbar_arrive_cluster(sb + SM_EMPTY + d * 8, s >= ST_GU ? (uint32_t)(s & 1) : rank);
    };
    const uint32_t lrow = (uint32_t)(wq * 16 + (lane & 7) + ((lane >> 3) & 1) * 8) * 128;
    const uint32_t lx = lane & 7, lhi = lane >> 4;
    if (wg == 1) bar_arrive(4, 256);
    TSTAMP(0);

    float r0, r1;
    uint32_t E[4][8];
    uint32_t T = 0;
    {
      uint32_t A[32][4];
      const int sx = wg ? ST_X1 : ST_X0;
      {
        const uint32_t base = sb + sx * SLOT + lrow;
        float s0 = 0.f, s1 = 0.f;
#pragma unroll
        for (int c = 0; c < 8; c++) {
          if (c % 3 == 0) mbar_wait(sb + SM_FULL + (sx + c / 3) * 8);
#pragma unroll
          for (int k = 0; k < 4; k++) ldsm4(A[4 * c + k], base + c * 8192 + (((2 * k + lhi) ^ lx) << 4));
          const uint32_t u0 = hadd2(hadd2(hadd2(A[4 * c][0], A[4 * c][2]), hadd2(A[4 * c + 1][0], A[4 * c + 1][2])),
                                    hadd2(hadd2(A[4 * c + 2][0], A[4 * c + 2][2]), hadd2(A[4 * c + 3][0], A[4 * c + 3][2])));
          const uint32_t u1 = hadd2(hadd2(hadd2(A[4 * c][1], A[4 * c][3]), hadd2(A[4 * c + 1][1], A[4 * c + 1][3])),
                                    hadd2(hadd2(A[4 * c + 2][1], A[4 * c + 2][3]), hadd2(A[4 * c + 3][1], A[4 * c + 3][3])));
          s0 += blo(u0) + bhi(u0); s1 += blo(u1) + bhi(u1);
        }
        s0 += __shfl_xor_sync(0xffffffffu, s0, 1); s1 += __shfl_xor_sync(0xffffffffu, s1, 1);
        s0 += __shfl_xor_sync(0xffffffffu, s0, 2); s1 += __shfl_xor_sync(0xffffffffu, s1, 2);
        TSTAMP(17);
        asm volatile("barrier.cluster.wait.aligned;" ::: "memory");
        if (lane < 3) release(sx + lane);
        s0 *= (1.f / 512.f); s1 *= (1.f / 512.f);
        const uint32_t m0 = pack2(s0, s0), m1 = pack2(s1, s1);
        float q0 = 0.f, q1 = 0.f;
#pragma unroll
        for (int ks = 0; ks < 32; ks += 2) {
          uint32_t v0, v1;
          A[ks][0] = hsub2(A[ks][0], m0); A[ks][1] = hsub2(A[ks][1], m1);
          A[ks][2] = hsub2(A[ks][2], m0); A[ks][3] = hsub2(A[ks][3], m1);
          A[ks + 1][0] = hsub2(A[ks + 1][0], m0); A[ks + 1][1] = hsub2(A[ks + 1][1], m1);
          A[ks + 1][2] = hsub2(A[ks + 1][2], m0); A[ks + 1][3] = hsub2(A[ks + 1][3], m1);
          v0 = hfma2(A[ks][2], A[ks][2], hmul2(A[ks][0], A[ks][0]));
          v1 = hfma2(A[ks][3], A[ks][3], hmul2(A[ks][1], A[ks][1]));
          v0 = hfma2(A[ks + 1][2], A[ks + 1][2], hfma2(A[ks + 1][0], A[ks + 1][0], v0));
          v1 = hfma2(A[ks + 1][3], A[ks + 1][3], hfma2(A[ks + 1][1], A[ks + 1][1], v1));
          q0 += blo(v0) + bhi(v0); q1 += blo(v1) + bhi(v1);
        }
        q0 += __shfl_xor_sync(0xffffffffu, q0, 1); q1 += __shfl_xor_sync(0xffffffffu, q1, 1);
        q0 += __shfl_xor_sync(0xffffffffu, q0, 2); q1 += __shfl_xor_sync(0xffffffffu, q1, 2);
        s0 -= blo(m0); s1 -= blo(m1);
        r0 = rsqrtf(fmaxf(q0 * (1.f / 512.f) - s0 * s0, 0.f) + 1e-5f);
        r1 = rsqrtf(fmaxf(q1 * (1.f / 512.f) - s1 * s1, 0.f) + 1e-5f);
      }
      TSTAMP(1);

      const uint32_t so = (wg ? (ST_SCR1 % NSLOT) : (ST_SCR0 % NSLOT)) * SLOT, scr = sb + so;
#pragma unroll 1
      for (int ps = 0; ps < 3; ps++) {
        const int st0 = ps == 0 ? ST_WK : (ps == 1 ? ST_WV : ST_WQ);
        const uint32_t wdesc = DESC((ps == 0 ? ST_WK % NSLOT : (ps == 1 ? ST_WV % NSLOT : ST_WQ % NSLOT)) * SLOT);
        float acc[32];
        bar_sync(4 + wg, 256);
#pragma unroll
        for (int i = 0; i < 3; i++) {
          mbar_wait(sb + SM_FULL + (st0 + i) * 8);
          wg_fence();
#pragma unroll
          for (int kk = 0; kk < (i < 2 ? 12 : 8); kk++)
            wgmma_rs_n64(acc, A[12 * i + kk], wdesc + ((i * SLOT + kk * 2048) >> 4), (i | kk) != 0);
          wg_commit();
          if (i > 0) { wg_wait<1>(); if (lead) release(st0 + i - 1); }
        }
        if (ps < 2 || wg == 0) bar_arrive(4 + (wg ^ 1), 256);
        wg_wait<0>();
        if (lead) release(st0 + 2);
        TSTAMP(2 + 2 * ps);
        uint32_t a[4][4];
#pragma unroll
        for (int h = 0; h < 4; h++) {
          a[h][0] = pack2(acc[8 * h + 0] * r0, acc[8 * h + 1] * r0); a[h][1] = pack2(acc[8 * h + 2] * r1, acc[8 * h + 3] * r1);
          a[h][2] = pack2(acc[8 * h + 4] * r0, acc[8 * h + 5] * r0); a[h][3] = pack2(acc[8 * h + 6] * r1, acc[8 * h + 7] * r1);
        }
        if (ps != 1) {
          if (ps == 0) {
            mbar_wait(sb + SM_MISCB);
            T = (*reinterpret_cast<volatile unsigned*>(smem + SM_EPOCH) & 1) ^ 1;
            mbar_wait(sb + SM_EMPTY + (wg ? ST_SCR1 - NSLOT : ST_SCR0 - NSLOT) * 8);
          }
          float pp[4][2][4];
#pragma unroll
          for (int h = 0; h < 4; h++) {
            uint32_t b[4];
            ldsm4t(b, sb + SM_WPHI + h * 512 + ((lane & 7) + ((lane >> 3) & 1) * 8) * 32 + lhi * 16);
#pragma unroll
            for (int i = 0; i < 4; i++) { pp[h][0][i] = 0.f; pp[h][1][i] = 0.f; }
            mma16816(pp[h][0], a[h], b[0], b[1]);
            mma16816(pp[h][1], a[h], b[2], b[3]);
          }
          float e[4][16];
#pragma unroll
          for (int h = 0; h < 4; h++) feat_exp(pp[h][0], pp[h][1], e[h]);
          if (ps == 0) {
#pragma unroll
            for (int h = 0; h < 4; h++) {
              const float (&f)[16] = e[h];
              float sp0 = (f[0] + f[1]) + (f[4] + f[5]), sp1 = (f[2] + f[3]) + (f[6] + f[7]);
              float sn0 = (f[8] + f[9]) + (f[12] + f[13]), sn1 = (f[10] + f[11]) + (f[14] + f[15]);
              sp0 += __shfl_xor_sync(0xffffffffu, sp0, 1); sp1 += __shfl_xor_sync(0xffffffffu, sp1, 1);
              sn0 += __shfl_xor_sync(0xffffffffu, sn0, 1); sn1 += __shfl_xor_sync(0xffffffffu, sn1, 1);
              sp0 += __shfl_xor_sync(0xffffffffu, sp0, 2); sp1 += __shfl_xor_sync(0xffffffffu, sp1, 2);
              sn0 += __shfl_xor_sync(0xffffffffu, sn0, 2); sn1 += __shfl_xor_sync(0xffffffffu, sn1, 2);
              sp0 = rcp(sp0); sp1 = rcp(sp1); sn0 = rcp(sn0); sn1 = rcp(sn1);
              const uint32_t dst = scr + (h >> 1) * 8192 + lrow;
              stsm4(dst + ((((h & 1) * 4 + lhi) ^ lx) << 4), pack2(f[0] * sp0, f[1] * sp0), pack2(f[2] * sp1, f[3] * sp1),
                    pack2(f[4] * sp0, f[5] * sp0), pack2(f[6] * sp1, f[7] * sp1));
              stsm4(dst + ((((h & 1) * 4 + 2 + lhi) ^ lx) << 4), pack2(f[8] * sn0, f[9] * sn0), pack2(f[10] * sn1, f[11] * sn1),
                    pack2(f[12] * sn0, f[13] * sn0), pack2(f[14] * sn1, f[15] * sn1));
            }
          } else {
#pragma unroll
            for (int h = 0; h < 4; h++)
#pragma unroll
              for (int i = 0; i < 8; i++) A[2 * h + (i >> 2)][i & 3] = pack2(e[h][2 * i], e[h][2 * i + 1]);
          }
        } else {
#pragma unroll
          for (int h = 0; h < 4; h++) stsm4(scr + 16384 + lrow + (((2 * h + lhi) ^ lx) << 4), a[h][0], a[h][1], a[h][2], a[h][3]);
          fence_async_smem();
          bar_sync(1 + wg, 128);
          float kv0[36], kv1[36];
          wg_fence();
#pragma unroll
          for (int ks = 0; ks < 4; ks++) {
            const uint32_t vo = so + 16384 + ks * 2048;
            const uint32_t dv = (DESC(vo) & 0xFFFFu) | (((SM_ONES - vo) >> 4) << 16);
            wgmma_ss_n72_t11(kv0, DESC(so + ks * 2048), dv, ks != 0);
            wgmma_ss_n72_t11(kv1, DESC(so + 8192 + ks * 2048), dv, ks != 0);
          }
          wg_commit();
          wg_wait<0>();
          if (lead) release(wg ? ST_SCR1 : ST_SCR0);
          const bool up = wq >= 2;
          const int f = (wq & 1) * 16 + g;
          float* kvp = &g_kv[T ^ 1][((hg * 4 + (wq >> 1)) * 32 + f) * 16 + 2 * t];
          float* zp = &g_z[T ^ 1][(hg * 4 + (wq >> 1)) * 32 + f];
#pragma unroll
          for (int b = 0; b < 2; b++) {
#pragma unroll
            for (int n = 0; n < 2; n++) {
              float c0, c1, c2, c3;
              if (b == 0) {
                c0 = up ? kv0[8 + 4 * n + 0] : kv0[4 * n + 0]; c1 = up ? kv0[8 + 4 * n + 1] : kv0[4 * n + 1];
                c2 = up ? kv0[8 + 4 * n + 2] : kv0[4 * n + 2]; c3 = up ? kv0[8 + 4 * n + 3] : kv0[4 * n + 3];
              } else {
                c0 = up ? kv1[24 + 4 * n + 0] : kv1[16 + 4 * n + 0]; c1 = up ? kv1[24 + 4 * n + 1] : kv1[16 + 4 * n + 1];
                c2 = up ? kv1[24 + 4 * n + 2] : kv1[16 + 4 * n + 2]; c3 = up ? kv1[24 + 4 * n + 3] : kv1[16 + 4 * n + 3];
              }
              float* p = kvp + b * 1024 + n * 8;
              asm volatile("red.relaxed.gpu.global.add.v2.f32 [%0], {%1,%2};" ::"l"(p), "f"(c0), "f"(c1) : "memory");
              asm volatile("red.relaxed.gpu.global.add.v2.f32 [%0], {%1,%2};" ::"l"(p + 128), "f"(c2), "f"(c3) : "memory");
            }
            if (t == 0) {
              asm volatile("red.relaxed.gpu.global.add.f32 [%0], %1;" ::"l"(zp + b * 64), "f"(b ? kv1[32] : kv0[32]) : "memory");
              asm volatile("red.relaxed.gpu.global.add.f32 [%0], %1;" ::"l"(zp + b * 64 + 8), "f"(b ? kv1[34] : kv0[34]) : "memory");
            }
          }
          bar_arrive(6 + wg, 160);
        }
        TSTAMP(3 + 2 * ps);
      }
#pragma unroll
      for (int i = 0; i < 32; i++) E[i >> 3][i & 7] = A[i >> 2][i & 3];
    }
    const int rh = 2 * rb + wg;
    mbar_wait(sb + SM_KVB);
    {
      const int r = tid & 127;
      const float4* src = reinterpret_cast<const float4*>(smem + SM_KV32) + r;
#pragma unroll
      for (int i = 0; i < 4; i++) {
        const float4 a = src[i * 128];
        *reinterpret_cast<uint2*>(smem + SM_KVS + (i * 32 + (r >> 2)) * 48 + (r & 3) * 8) = make_uint2(pack2(a.x, a.y), pack2(a.z, a.w));
      }
      const uint32_t zz = pack2(reinterpret_cast<const float*>(smem + SM_ONES)[r], 1.0f);
      *reinterpret_cast<uint4*>(smem + SM_KVS + r * 48 + 32) = make_uint4(zz, zz, zz, zz);
      bar_sync(1 + wg, 128);
    }
    TSTAMP(8);
    {
      uint4* op = &g_o[rh][hg][wq][0][lane];
#pragma unroll
      for (int h = 0; h < 4; h++) {
        uint32_t b0[4], b1[4], b2[4];
        const uint32_t kb = sb + SM_KVS + (h * 32 + lane) * 48;
        ldsm4t(b0, kb); ldsm4t(b1, kb + 16); ldsm4t(b2, kb + 32);
        const uint32_t ep[4] = {E[h][0], E[h][1], E[h][2], E[h][3]}, en[4] = {E[h][4], E[h][5], E[h][6], E[h][7]};
        float np0[4] = {0, 0, 0, 0}, np1[4] = {0, 0, 0, 0}, nn0[4] = {0, 0, 0, 0}, nn1[4] = {0, 0, 0, 0}, dp[4] = {0, 0, 0, 0}, dn[4] = {0, 0, 0, 0};
        mma16816(dp, ep, b2[0], b2[1]);  mma16816(dn, en, b2[2], b2[3]);
        mma16816(np0, ep, b0[0], b0[1]); mma16816(nn0, en, b0[2], b0[3]);
        mma16816(np1, ep, b1[0], b1[1]); mma16816(nn1, en, b1[2], b1[3]);
        const float i0 = rcp(fmaf(dp[0], dn[1], fmaf(dn[0], dp[1], 1e-6f * dp[1] * dn[1])));
        const float i1 = rcp(fmaf(dp[2], dn[3], fmaf(dn[2], dp[3], 1e-6f * dp[3] * dn[3])));
        const float cp0 = dn[1] * i0, cn0 = dp[1] * i0, cp1 = dn[3] * i1, cn1 = dp[3] * i1;
        st_rlx4(op + h * 32,
                tg(pack2(fmaf(np0[0], cp0, nn0[0] * cn0), fmaf(np0[1], cp0, nn0[1] * cn0)), T),
                tg(pack2(fmaf(np0[2], cp1, nn0[2] * cn1), fmaf(np0[3], cp1, nn0[3] * cn1)), T),
                tg(pack2(fmaf(np1[0], cp0, nn1[0] * cn0), fmaf(np1[1], cp0, nn1[1] * cn0)), T),
                tg(pack2(fmaf(np1[2], cp1, nn1[2] * cn1), fmaf(np1[3], cp1, nn1[3] * cn1)), T));
      }
    }
    TSTAMP(9);

    {
      uint32_t xr[16];
      {
        const uint32_t* xp = reinterpret_cast<const uint32_t*>(x + (size_t)(rh * 64 + wq * 16 + g) * 512 + hg * 64 + 2 * t);
#pragma unroll
        for (int i = 0; i < 8; i++) { xr[2 * i] = __ldg(xp + 4 * i); xr[2 * i + 1] = __ldg(xp + 8 * 256 + 4 * i); }
      }
      uint32_t A[8][4][4];
      const uint4* op = &g_o[rh][0][wq][0][lane];
      const uint32_t ob = sb + 2 * SLOT + wq * 2048 + lane * 16;
      float acc[32];
#pragma unroll
      for (int p = 0; p < 3; p++) {
        mbar_wait(sb + SM_FULL + (ST_O0 + 3 * wg + p) * 8);
#pragma unroll
        for (int c = 3 * p; c < (p < 2 ? 3 * p + 3 : 8); c++)
#pragma unroll
          for (int s = 0; s < 4; s++)
            asm volatile("ld.shared.v4.b32 {%0,%1,%2,%3}, [%4];" : "=r"(A[c][s][0]), "=r"(A[c][s][1]), "=r"(A[c][s][2]), "=r"(A[c][s][3])
                         : "r"(ob + c * 8192 + s * 512) : "memory");
        __syncwarp();
        if (lane == 0) release(ST_O0 + 3 * wg + p);
        mbar_wait(sb + SM_FULL + (ST_WO + p) * 8);
#pragma unroll
        for (int c = 3 * p; c < (p < 2 ? 3 * p + 3 : 8); c++) {
          chk_chunk(A[c], op + c * 512, T);
          wg_fence();
#pragma unroll
          for (int s = 0; s < 4; s++)
            wgmma_rs_n64(acc, A[c][s], DESC(((ST_WO + p) % NSLOT) * SLOT + ((c % 3) * 4 + s) * 2048), (c | s) != 0);
          wg_commit();
        }
      }
      wg_wait<0>();
      if ((tid & 127) < 3) release(ST_WO + (tid & 127));
      TSTAMP(10);
      uint32_t hw[16];
      float s0 = 0.f, s1 = 0.f, q0 = 0.f, q1 = 0.f;
#pragma unroll
      for (int i = 0; i < 8; i++) {
        hw[2 * i]     = pack2(blo(xr[2 * i]) + acc[4 * i], bhi(xr[2 * i]) + acc[4 * i + 1]);
        hw[2 * i + 1] = pack2(blo(xr[2 * i + 1]) + acc[4 * i + 2], bhi(xr[2 * i + 1]) + acc[4 * i + 3]);
      }
      uint4* hp_ = &g_h[rh][hg][wq][0][lane];
#pragma unroll
      for (int s = 0; s < 4; s++) st_rlx4(hp_ + s * 32, tg(hw[4 * s], T), tg(hw[4 * s + 1], T), tg(hw[4 * s + 2], T), tg(hw[4 * s + 3], T));
#pragma unroll
      for (int i = 0; i < 8; i++) {
        float a = blo(hw[2 * i]), b = bhi(hw[2 * i]);
        s0 += a + b; q0 = fmaf(a, a, q0); q0 = fmaf(b, b, q0);
        a = blo(hw[2 * i + 1]); b = bhi(hw[2 * i + 1]);
        s1 += a + b; q1 = fmaf(a, a, q1); q1 = fmaf(b, b, q1);
      }
      s0 += __shfl_xor_sync(0xffffffffu, s0, 1); s1 += __shfl_xor_sync(0xffffffffu, s1, 1);
      q0 += __shfl_xor_sync(0xffffffffu, q0, 1); q1 += __shfl_xor_sync(0xffffffffu, q1, 1);
      s0 += __shfl_xor_sync(0xffffffffu, s0, 2); s1 += __shfl_xor_sync(0xffffffffu, s1, 2);
      q0 += __shfl_xor_sync(0xffffffffu, q0, 2); q1 += __shfl_xor_sync(0xffffffffu, q1, 2);
      if (t < 2) st_rlx2(&g_st[rh][hg][wq * 16 + g + t * 8], tg(__float_as_uint(t ? s1 : s0), T), tg(__float_as_uint(t ? q1 : q0), T));
      uint32_t hx = T;
#pragma unroll
      for (int i = 0; i < 16; i++) hx |= (hw[i] & 1u) << (i + 1);
      st_rlx1(&g_hx[rh][hg][wq][lane], hx);
    }
    TSTAMP(11);

    const int rh3 = 2 * rb3 + wg;
    uint32_t HH[11][4];
    {
      uint32_t A[2][4][4];
      const uint4* hp_ = &g_h[rh3][0][wq][0][lane];
      uint32_t m0, m1;
      {
        const uint2* sp = &g_st[rh3][2 * t][wq * 16 + g];
        uint32_t a[4], b[4];
        int it = 0;
#pragma unroll 1
        do {
          ld_rlx2(a[0], a[1], sp); ld_rlx2(a[2], a[3], sp + 64); ld_rlx2(b[0], b[1], sp + 8); ld_rlx2(b[2], b[3], sp + 72);
          if (++it > (1 << 18)) break;
        } while (__any_sync(0xffffffffu, (bad4(a, T) | bad4(b, T)) & 1));
        ld_chunk(A[0], hp_);
        float s0 = __uint_as_float(a[0]) + __uint_as_float(a[2]), q0 = __uint_as_float(a[1]) + __uint_as_float(a[3]);
        float s1 = __uint_as_float(b[0]) + __uint_as_float(b[2]), q1 = __uint_as_float(b[1]) + __uint_as_float(b[3]);
        s0 += __shfl_xor_sync(0xffffffffu, s0, 1); s1 += __shfl_xor_sync(0xffffffffu, s1, 1);
        q0 += __shfl_xor_sync(0xffffffffu, q0, 1); q1 += __shfl_xor_sync(0xffffffffu, q1, 1);
        s0 += __shfl_xor_sync(0xffffffffu, s0, 2); s1 += __shfl_xor_sync(0xffffffffu, s1, 2);
        q0 += __shfl_xor_sync(0xffffffffu, q0, 2); q1 += __shfl_xor_sync(0xffffffffu, q1, 2);
        s0 *= (1.f / 512.f); s1 *= (1.f / 512.f);
        r0 = 1.f / (fmaxf(q0 * (1.f / 512.f) - s0 * s0, 0.f) + 1e-5f);
        r1 = 1.f / (fmaxf(q1 * (1.f / 512.f) - s1 * s1, 0.f) + 1e-5f);
        m0 = pack2(s0, s0); m1 = pack2(s1, s1);
      }
      TSTAMP(12);
      float ag[88], au[88];
      int slot = 5;
#pragma unroll 1
      for (int c2 = 0; c2 < 8; c2 += 2) {
#pragma unroll
        for (int b = 0; b < 2; b++) {
          const int c = c2 + b, sG = ST_GU + 2 * c;
          chk_chunk(A[b], hp_ + c * 512, T);
#pragma unroll
          for (int s = 0; s < 4; s++) {
            A[b][s][0] = hsub2(A[b][s][0], m0); A[b][s][1] = hsub2(A[b][s][1], m1);
            A[b][s][2] = hsub2(A[b][s][2], m0); A[b][s][3] = hsub2(A[b][s][3], m1);
          }
          mbar_wait(sb + SM_FULL + sG * 8);
          wg_fence();
#pragma unroll
          for (int s = 0; s < 4; s++)
            wgmma_rs_n176(ag, A[b][s], db + slot * (SLOT >> 4) + s * 128, (c | s) != 0);
          wg_commit();
          if (++slot == NSLOT) slot = 0;
          wg_wait<1>();
          if (lead && c > 0) release(sG - 1);
          if (c < 7) ld_chunk(A[b ^ 1], hp_ + (c + 1) * 512);
          mbar_wait(sb + SM_FULL + (sG + 1) * 8);
          wg_fence();
#pragma unroll
          for (int s = 0; s < 4; s++)
            wgmma_rs_n176(au, A[b][s], db + slot * (SLOT >> 4) + s * 128, (c | s) != 0);
          wg_commit();
          if (++slot == NSLOT) slot = 0;
          wg_wait<1>();
          if (lead) release(sG);
        }
      }
      wg_wait<0>();
      TSTAMP(13);
#pragma unroll
      for (int s = 0; s < 11; s++) {
        HH[s][0] = pack2(ag[8 * s + 0] * au[8 * s + 0] * r0, ag[8 * s + 1] * au[8 * s + 1] * r0);
        HH[s][1] = pack2(ag[8 * s + 2] * au[8 * s + 2] * r1, ag[8 * s + 3] * au[8 * s + 3] * r1);
        HH[s][2] = pack2(ag[8 * s + 4] * au[8 * s + 4] * r0, ag[8 * s + 5] * au[8 * s + 5] * r0);
        HH[s][3] = pack2(ag[8 * s + 6] * au[8 * s + 6] * r1, ag[8 * s + 7] * au[8 * s + 7] * r1);
      }
    }
    TSTAMP(14);

    {
      float acc[32], sum[32];
      uint32_t in[4][4];
      ld_chunk(in, &g_h[rh3][jf][wq][0][lane]);
      {
        uint32_t hx; int it = 0;
#pragma unroll 1
        do {
          hx = ld_rlx1(&g_hx[rh3][jf][wq][lane]);
          if (++it > (1 << 18)) break;
        } while (__any_sync(0xffffffffu, (hx ^ T) & 1));
#pragma unroll
        for (int i = 0; i < 16; i++) {
          sum[2 * i]     = blo((in[i >> 2][i & 3] & 0xFFFEu) | ((hx >> (i + 1)) & 1u));
          sum[2 * i + 1] = bhi(in[i >> 2][i & 3]);
        }
      }
      const uint4* inb = &g_part[rh3][jf][0][wq][0][lane];
      uint4* outb = &g_part[rh3][0][jf][wq][0][lane];
      int slot = (5 + 16) % NSLOT, q = 0, it = 0;
#pragma unroll 1
      for (int st = 0; q < 7; st++) {
        if (st < 8) {
          mbar_wait(sb + SM_FULL + (ST_D + st) * 8);
          wg_fence();
#pragma unroll
          for (int s = 0; s < 11; s++)
            wgmma_rs_n64(acc, HH[s], db + slot * (SLOT >> 4) + s * 128, s != 0);
          wg_commit();
          if (++slot == NSLOT) slot = 0;
        }
        if (st >= 4) {
          if (!__any_sync(0xffffffffu, (bad4(in[0], T) | bad4(in[1], T) | bad4(in[2], T) | bad4(in[3], T)) & 1) || ++it > (1 << 18)) {
#pragma unroll
            for (int i = 0; i < 16; i++) { sum[2 * i] += blo(in[i >> 2][i & 3]); sum[2 * i + 1] += bhi(in[i >> 2][i & 3]); }
            q++;
          }
        }
        if (st >= 3 && q < 7) ld_chunk(in, inb + ((jf - 1 - q) & 7) * 512);
        if (st < 8) wg_wait<0>();
        if (st < 7) {
          uint4* p = outb + ((jf + 1 + st) & 7) * 4096;
#pragma unroll
          for (int s = 0; s < 4; s++)
            st_rlx4(p + s * 32, tg(pack2(acc[8 * s + 0], acc[8 * s + 1]), T), tg(pack2(acc[8 * s + 2], acc[8 * s + 3]), T),
                    tg(pack2(acc[8 * s + 4], acc[8 * s + 5]), T), tg(pack2(acc[8 * s + 6], acc[8 * s + 7]), T));
        }
        if (st == 7) TSTAMP(15);
      }
      uint32_t* op = reinterpret_cast<uint32_t*>(out + (size_t)(rh3 * 64 + wq * 16 + g) * 512 + jf * 64 + 2 * t);
#pragma unroll
      for (int i = 0; i < 8; i++) {
        op[4 * i]           = pack2(sum[4 * i] + acc[4 * i], sum[4 * i + 1] + acc[4 * i + 1]);
        op[8 * 256 + 4 * i] = pack2(sum[4 * i + 2] + acc[4 * i + 2], sum[4 * i + 3] + acc[4 * i + 3]);
      }
    }
    TSTAMP(16);
    asm volatile("barrier.cluster.arrive.relaxed.aligned;" ::: "memory");
    asm volatile("barrier.cluster.wait.aligned;" ::: "memory");
  }
}

typedef CUresult (*EncodeFn)(CUtensorMap*, CUtensorMapDataType, cuuint32_t, void*, const cuuint64_t*, const cuuint64_t*,
                             const cuuint32_t*, const cuuint32_t*, CUtensorMapInterleave, CUtensorMapSwizzle,
                             CUtensorMapL2promotion, CUtensorMapFloatOOBfill);

void encode(EncodeFn fn, CUtensorMap* m, const void* base, int rank, const cuuint64_t* dims, const cuuint64_t* strides,
            const cuuint32_t* box) {
  cuuint32_t es[3] = {1, 1, 1};
  fn(m, CU_TENSOR_MAP_DATA_TYPE_BFLOAT16, (cuuint32_t)rank, const_cast<void*>(base), dims, strides, box, es,
     CU_TENSOR_MAP_INTERLEAVE_NONE, CU_TENSOR_MAP_SWIZZLE_128B, CU_TENSOR_MAP_L2_PROMOTION_L2_256B,
     CU_TENSOR_MAP_FLOAT_OOB_FILL_NONE);
}

}

extern "C" void kernel_launch(void* const* d_in, const int* in_sizes, int n_in, void* d_out, int out_size) {
  (void)in_sizes; (void)n_in; (void)out_size;
  const __nv_bfloat16* x    = (const __nv_bfloat16*)d_in[0];
  const __nv_bfloat16* wqkv = (const __nv_bfloat16*)d_in[1];
  const __nv_bfloat16* wphi = (const __nv_bfloat16*)d_in[2];
  const __nv_bfloat16* wo   = (const __nv_bfloat16*)d_in[3];
  const __nv_bfloat16* wg   = (const __nv_bfloat16*)d_in[5];
  const __nv_bfloat16* wu   = (const __nv_bfloat16*)d_in[6];
  const __nv_bfloat16* wd   = (const __nv_bfloat16*)d_in[7];

  static EncodeFn fn = nullptr;
  if (!fn) {
    void* p = nullptr;
    cudaDriverEntryPointQueryResult qr;
    cudaGetDriverEntryPoint("cuTensorMapEncodeTiled", &p, cudaEnableDefault, &qr);
    fn = (EncodeFn)p;
    cudaFuncSetAttribute(fused_kernel, cudaFuncAttributeMaxDynamicSharedMemorySize, SM_TOTAL);
  }
  Maps maps;
  {
    cuuint64_t d[3] = {64, 2048, 8}, s[2] = {1024, 128}; cuuint32_t b[3] = {64, 64, 3};
    encode(fn, &maps.x, x, 3, d, s, b);
  }
  {
    cuuint64_t d[2] = {1536, 512}, s[1] = {3072}; cuuint32_t b[2] = {64, 192};
    encode(fn, &maps.w, wqkv, 2, d, s, b);
  }
  {
    cuuint64_t d[2] = {512, 512}, s[1] = {1024}; cuuint32_t b[2] = {64, 192};
    encode(fn, &maps.wo, wo, 2, d, s, b);
  }
  {
    cuuint64_t d[3] = {176, 7, 512}, d7[3] = {144, 1, 512}, s[2] = {352, 2752}; cuuint32_t b[3] = {64, 1, 64};
    encode(fn, &maps.g, wg, 3, d, s, b);
    encode(fn, &maps.u, wu, 3, d, s, b);
    encode(fn, &maps.g7, wg + 1232, 3, d7, s, b);
    encode(fn, &maps.u7, wu + 1232, 3, d7, s, b);
  }
  {
    cuuint64_t d[2] = {512, 1376}, s[1] = {1024}; cuuint32_t b[2] = {64, 176};
    encode(fn, &maps.d, wd, 2, d, s, b);
  }
  fused_kernel<<<NCTA, 384, SM_TOTAL>>>(maps, x, wphi, wo, wg, wu, wd, (__nv_bfloat16*)d_out);
}
```

```cpp
#include <cuda_runtime.h>
#include <cuda_bf16.h>
#include <cuda.h>
#include <stdint.h>

#define PROF 0

namespace {

constexpr int NCTA   = 128;
constexpr int SLOT   = 24576;
constexpr int NSLOT  = 9;
constexpr int NSTAGE = 50;

constexpr int ST_X0   = 0;
constexpr int ST_WK   = 3;
constexpr int ST_X1   = 6;
constexpr int ST_SCR0 = 9;
constexpr int ST_WV   = 10;
constexpr int ST_SCR1 = 13;
constexpr int ST_WQ   = 14;
constexpr int ST_WO   = 17;
constexpr int ST_O0   = 20;
constexpr int ST_O1   = 23;
constexpr int ST_GU   = 26;
constexpr int ST_D    = 42;

__host__ __device__ constexpr int st_next(int d) { return d < ST_WQ ? d + 9 : d < ST_O0 ? d + 12 : d < ST_O1 ? d + 3 : d + 9; }
__host__ __device__ constexpr int st_bytes(int s) { return s >= ST_D ? 22528 : (s == ST_O0 + 2 || s == ST_O1 + 2) ? 16384 : 24576; }
__host__ __device__ constexpr int st_empty_cnt(int d) {
  return ((d < 3 || (d >= 6 && d < 9) || (d >= ST_O0 && d < ST_GU)) ? 4 : (d == ST_SCR0 || d == ST_SCR1) ? 1 : 2) *
         (st_next(d) >= ST_GU ? 2 : 1);
}

constexpr int SM_ONES = NSLOT * SLOT;
constexpr int SM_WPHI = SM_ONES + 2048;
constexpr int SM_KVS  = SM_WPHI + 2048;
constexpr int SM_KV32 = 4 * SLOT + 16384;
constexpr int SM_BAR  = SM_KVS + 6144;
constexpr int SM_FULL  = SM_BAR;
constexpr int SM_EMPTY = SM_BAR + NSTAGE * 8;
constexpr int SM_MISCB = SM_BAR + 2 * NSTAGE * 8;
constexpr int SM_KVB   = SM_MISCB + 8;
constexpr int SM_EPOCH = SM_KVB + 8;
constexpr int SM_TOTAL = SM_BAR + 1024;

static_assert(SM_TOTAL == 232448, "smem budget");

struct Maps { CUtensorMap x, w, wo, g, u, g7, u7, d; };

__device__ uint4    g_o[32][8][4][4][32];
__device__ uint4    g_h[32][8][4][4][32];
__device__ uint32_t g_hx[32][8][4][32];
__device__ uint2    g_st[32][8][64];
__device__ uint4    g_part[32][8][8][4][4][32];
__device__ float    g_kv[2][32 * 32 * 16];
__device__ float    g_z[2][32 * 32];
__device__ unsigned g_kvcnt[8 * 32];
__device__ unsigned g_start;

__device__ __forceinline__ uint32_t smem_u32(const void* p) { return (uint32_t)__cvta_generic_to_shared(p); }
__device__ __forceinline__ void mbar_init(uint32_t bar, int cnt) {
  asm volatile("mbarrier.init.shared::cta.b64 [%0], %1;" ::"r"(bar), "r"(cnt) : "memory");
}
__device__ __forceinline__ void mbar_expect_tx(uint32_t bar, uint32_t bytes) {
  asm volatile("mbarrier.arrive.expect_tx.shared::cta.b64 _, [%0], %1;" ::"r"(bar), "r"(bytes) : "memory");
}
__device__ __forceinline__ void mbar_arrive(uint32_t bar) {
  asm volatile("mbarrier.arrive.shared::cta.b64 _, [%0];" ::"r"(bar) : "memory");
}
__device__ __forceinline__ void mbar_arrive_cluster(uint32_t bar, uint32_t rank) {
  asm volatile("{\n.reg .b32 ra;\nmapa.shared::cluster.u32 ra, %0, %1;\n"
               "mbarrier.arrive.shared::cluster.b64 _, [ra];\n}" ::"r"(bar), "r"(rank) : "memory");
}
__device__ __forceinline__ bool mbar_try(uint32_t bar) {
  uint32_t ok;
  asm volatile("{\n.reg .pred p;\nmbarrier.try_wait.parity.shared::cta.b64 p, [%1], 0;\nselp.u32 %0, 1, 0, p;\n}"
               : "=r"(ok) : "r"(bar) : "memory");
  return ok != 0;
}
__device__ __forceinline__ void mbar_wait(uint32_t bar) {
  int it = 0;
#pragma unroll 1
  while (!mbar_try(bar)) {
    if (++it > (1 << 20)) __trap();
  }
}
__device__ __forceinline__ void bar_sync(int id, int n)   { asm volatile("bar.sync %0, %1;" ::"r"(id), "r"(n) : "memory"); }
__device__ __forceinline__ void bar_arrive(int id, int n) { asm volatile("bar.arrive %0, %1;" ::"r"(id), "r"(n) : "memory"); }
__device__ __forceinline__ void fence_async_smem() { asm volatile("fence.proxy.async.shared::cta;" ::: "memory"); }
__device__ __forceinline__ void wg_fence()  { asm volatile("wgmma.fence.sync.aligned;" ::: "memory"); }
__device__ __forceinline__ void wg_commit() { asm volatile("wgmma.commit_group.sync.aligned;" ::: "memory"); }
template <int N> __device__ __forceinline__ void wg_wait() { asm volatile("wgmma.wait_group.sync.aligned %0;" ::"n"(N) : "memory"); }
#define DESC(off) (db + ((uint32_t)(off) >> 4))
__device__ __forceinline__ void tma2d(uint32_t dst, const CUtensorMap* m, int c0, int c1, uint32_t bar) {
  asm volatile("cp.async.bulk.tensor.2d.shared::cluster.global.mbarrier::complete_tx::bytes [%0], [%1, {%3, %4}], [%2];"
               ::"r"(dst), "l"(m), "r"(bar), "r"(c0), "r"(c1) : "memory");
}
__device__ __forceinline__ void tma2d_mc(uint32_t dst, const CUtensorMap* m, int c0, int c1, uint32_t bar) {
  asm volatile("cp.async.bulk.tensor.2d.shared::cluster.global.mbarrier::complete_tx::bytes.multicast::cluster [%0], [%1, {%3, %4}], [%2], %5;"
               ::"r"(dst), "l"(m), "r"(bar), "r"(c0), "r"(c1), "h"((uint16_t)3) : "memory");
}
__device__ __forceinline__ void tma3d(uint32_t dst, const CUtensorMap* m, int c0, int c1, int c2, uint32_t bar) {
  asm volatile("cp.async.bulk.tensor.3d.shared::cluster.global.mbarrier::complete_tx::bytes [%0], [%1, {%3, %4, %5}], [%2];"
               ::"r"(dst), "l"(m), "r"(bar), "r"(c0), "r"(c1), "r"(c2) : "memory");
}
__device__ __forceinline__ void tma3d_mc(uint32_t dst, const CUtensorMap* m, int c0, int c1, int c2, uint32_t bar) {
  asm volatile("cp.async.bulk.tensor.3d.shared::cluster.global.mbarrier::complete_tx::bytes.multicast::cluster [%0], [%1, {%3, %4, %5}], [%2], %6;"
               ::"r"(dst), "l"(m), "r"(bar), "r"(c0), "r"(c1), "r"(c2), "h"((uint16_t)3) : "memory");
}
__device__ __forceinline__ void ldsm4(uint32_t (&r)[4], uint32_t addr) {
  asm volatile("ldmatrix.sync.aligned.m8n8.x4.shared.b16 {%0,%1,%2,%3}, [%4];"
               : "=r"(r[0]), "=r"(r[1]), "=r"(r[2]), "=r"(r[3]) : "r"(addr) : "memory");
}
__device__ __forceinline__ void ldsm4t(uint32_t (&r)[4], uint32_t addr) {
  asm volatile("ldmatrix.sync.aligned.m8n8.x4.trans.shared.b16 {%0,%1,%2,%3}, [%4];"
               : "=r"(r[0]), "=r"(r[1]), "=r"(r[2]), "=r"(r[3]) : "r"(addr) : "memory");
}
__device__ __forceinline__ void stsm4(uint32_t addr, uint32_t r0, uint32_t r1, uint32_t r2, uint32_t r3) {
  asm volatile("stmatrix.sync.aligned.m8n8.x4.shared.b16 [%0], {%1,%2,%3,%4};"
               ::"r"(addr), "r"(r0), "r"(r1), "r"(r2), "r"(r3) : "memory");
}
__device__ __forceinline__ void mma16816(float (&c)[4], const uint32_t (&a)[4], uint32_t b0, uint32_t b1) {
  asm volatile("mma.sync.aligned.m16n8k16.row.col.f32.bf16.bf16.f32 {%0,%1,%2,%3},{%4,%5,%6,%7},{%8,%9},{%0,%1,%2,%3};"
               : "+f"(c[0]), "+f"(c[1]), "+f"(c[2]), "+f"(c[3])
               : "r"(a[0]), "r"(a[1]), "r"(a[2]), "r"(a[3]), "r"(b0), "r"(b1));
}
__device__ __forceinline__ uint32_t pack2(float lo, float hi) {
  uint32_t r; asm("cvt.rn.bf16x2.f32 %0, %1, %2;" : "=r"(r) : "f"(hi), "f"(lo)); return r;
}
__device__ __forceinline__ float blo(uint32_t w) { return __uint_as_float(w << 16); }
__device__ __forceinline__ float bhi(uint32_t w) { return __uint_as_float(w & 0xFFFF0000u); }
__device__ __forceinline__ uint32_t hsub2(uint32_t a, uint32_t b) { uint32_t r; asm("sub.rn.bf16x2 %0, %1, %2;" : "=r"(r) : "r"(a), "r"(b)); return r; }
__device__ __forceinline__ uint32_t hadd2(uint32_t a, uint32_t b) { uint32_t r; asm("add.rn.bf16x2 %0, %1, %2;" : "=r"(r) : "r"(a), "r"(b)); return r; }
__device__ __forceinline__ uint32_t hmul2(uint32_t a, uint32_t b) { uint32_t r; asm("mul.rn.bf16x2 %0, %1, %2;" : "=r"(r) : "r"(a), "r"(b)); return r; }
__device__ __forceinline__ uint32_t hfma2(uint32_t a, uint32_t b, uint32_t c) { uint32_t r; asm("fma.rn.bf16x2 %0, %1, %2, %3;" : "=r"(r) : "r"(a), "r"(b), "r"(c)); return r; }
__device__ __forceinline__ uint32_t hmax2(uint32_t a, uint32_t b) { uint32_t r; asm("max.bf16x2 %0, %1, %2;" : "=r"(r) : "r"(a), "r"(b)); return r; }
__device__ __forceinline__ uint32_t hmin2(uint32_t a, uint32_t b) { uint32_t r; asm("min.bf16x2 %0, %1, %2;" : "=r"(r) : "r"(a), "r"(b)); return r; }
__device__ __forceinline__ float ex2(float x) { float r; asm("ex2.approx.ftz.f32 %0, %1;" : "=f"(r) : "f"(x)); return r; }
__device__ __forceinline__ float rcp(float x) { float r; asm("rcp.approx.ftz.f32 %0, %1;" : "=f"(r) : "f"(x)); return r; }
__device__ __forceinline__ void ld_rlx4(uint32_t (&r)[4], const uint4* p) {
  asm volatile("{\n.reg .b128 v;\nld.relaxed.gpu.global.b128 v, [%4];\nmov.b128 {%0,%1,%2,%3}, v;\n}"
               : "=r"(r[0]), "=r"(r[1]), "=r"(r[2]), "=r"(r[3]) : "l"(p) : "memory");
}
__device__ __forceinline__ void st_rlx4(uint4* p, uint32_t a, uint32_t b, uint32_t c, uint32_t d) {
  asm volatile("{\n.reg .b128 v;\nmov.b128 v, {%1,%2,%3,%4};\nst.relaxed.gpu.global.b128 [%0], v;\n}"
               ::"l"(p), "r"(a), "r"(b), "r"(c), "r"(d) : "memory");
}
__device__ __forceinline__ void st_rlx2(uint2* p, uint32_t a, uint32_t b) {
  asm volatile("{\n.reg .b64 v;\nmov.b64 v, {%1,%2};\nst.relaxed.gpu.global.b64 [%0], v;\n}" ::"l"(p), "r"(a), "r"(b) : "memory");
}
__device__ __forceinline__ uint32_t ld_rlx1(const uint32_t* p) {
  uint32_t r; asm volatile("ld.relaxed.gpu.global.b32 %0, [%1];" : "=r"(r) : "l"(p) : "memory"); return r;
}
__device__ __forceinline__ void st_rlx1(uint32_t* p, uint32_t a) {
  asm volatile("st.relaxed.gpu.global.b32 [%0], %1;" ::"l"(p), "r"(a) : "memory");
}
__device__ __forceinline__ void ld_rlx2(uint32_t& a, uint32_t& b, const uint2* p) {
  asm volatile("{\n.reg .b64 v;\nld.relaxed.gpu.global.b64 v, [%2];\nmov.b64 {%0,%1}, v;\n}" : "=r"(a), "=r"(b) : "l"(p) : "memory");
}
__device__ __forceinline__ void bulk_g2s(uint32_t dst, const void* src, uint32_t bytes, uint32_t bar) {
  asm volatile("cp.async.bulk.shared::cluster.global.mbarrier::complete_tx::bytes [%0], [%1], %2, [%3];"
               ::"r"(dst), "l"(src), "r"(bytes), "r"(bar) : "memory");
}
__device__ __forceinline__ uint32_t tg(uint32_t w, uint32_t T) { return (w & 0xFFFFFFFEu) | T; }
__device__ __forceinline__ uint32_t bad4(uint32_t a, uint32_t b, uint32_t c, uint32_t d, uint32_t T) {
  uint32_t u, v;
  asm("lop3.b32 %0, %1, %2, %3, 0x7E;" : "=r"(u) : "r"(a), "r"(b), "r"(T));
  asm("lop3.b32 %0, %1, %2, %3, 0x7E;" : "=r"(v) : "r"(c), "r"(d), "r"(T));
  return u | v;
}

__device__ __forceinline__ void ld_chunk(uint32_t (&a)[4][4], const uint4* p) {
#pragma unroll
  for (int s = 0; s < 4; s++) ld_rlx4(a[s], p + s * 32);
}
__device__ __forceinline__ void chk_chunk(uint32_t (&a)[4][4], const uint4* p, uint32_t T) {
  int it = 0;
#pragma unroll 1
  while (__any_sync(0xffffffffu, bad4(a[0][0], a[1][0], a[2][0], a[3][0], T) & 1)) {
    ld_chunk(a, p);
    if (++it > (1 << 18)) break;
  }
}

__device__ __forceinline__ void wgmma_rs_n64(float (&d)[32], const uint32_t (&a)[4], uint32_t descB, int scaleD) {
  asm volatile("{\n.reg .pred p;\n.reg .b64 db;\nsetp.ne.b32 p, %37, 0;\nmov.b64 db, {%36, 0x40000040};\n"
    "wgmma.mma_async.sync.aligned.m64n64k16.f32.bf16.bf16 {%0,%1,%2,%3,%4,%5,%6,%7,%8,%9,%10,%11,%12,%13,%14,%15,%16,%17,%18,%19,%20,%21,%22,%23,%24,%25,%26,%27,%28,%29,%30,%31}, {%32,%33,%34,%35}, db, p, 1, 1, 1;\n}\n"
    : "+f"(d[0]),"+f"(d[1]),"+f"(d[2]),"+f"(d[3]),"+f"(d[4]),"+f"(d[5]),"+f"(d[6]),"+f"(d[7]),"+f"(d[8]),"+f"(d[9]),"+f"(d[10]),"+f"(d[11]),"+f"(d[12]),"+f"(d[13]),"+f"(d[14]),"+f"(d[15]),"+f"(d[16]),"+f"(d[17]),"+f"(d[18]),"+f"(d[19]),"+f"(d[20]),"+f"(d[21]),"+f"(d[22]),"+f"(d[23]),"+f"(d[24]),"+f"(d[25]),"+f"(d[26]),"+f"(d[27]),"+f"(d[28]),"+f"(d[29]),"+f"(d[30]),"+f"(d[31])
    : "r"(a[0]), "r"(a[1]), "r"(a[2]), "r"(a[3]), "r"(descB), "r"(scaleD));
}
__device__ __forceinline__ void wgmma_rs_n176(float (&d)[88], const uint32_t (&a)[4], uint32_t descB, int scaleD) {
  asm volatile("{\n.reg .pred p;\n.reg .b64 db;\nsetp.ne.b32 p, %93, 0;\nmov.b64 db, {%92, 0x40000040};\n"
    "wgmma.mma_async.sync.aligned.m64n176k16.f32.bf16.bf16 {%0,%1,%2,%3,%4,%5,%6,%7,%8,%9,%10,%11,%12,%13,%14,%15,%16,%17,%18,%19,%20,%21,%22,%23,%24,%25,%26,%27,%28,%29,%30,%31,%32,%33,%34,%35,%36,%37,%38,%39,%40,%41,%42,%43,%44,%45,%46,%47,%48,%49,%50,%51,%52,%53,%54,%55,%56,%57,%58,%59,%60,%61,%62,%63,%64,%65,%66,%67,%68,%69,%70,%71,%72,%73,%74,%75,%76,%77,%78,%79,%80,%81,%82,%83,%84,%85,%86,%87}, {%88,%89,%90,%91}, db, p, 1, 1, 1;\n}\n"
    : "+f"(d[0]),"+f"(d[1]),"+f"(d[2]),"+f"(d[3]),"+f"(d[4]),"+f"(d[5]),"+f"(d[6]),"+f"(d[7]),"+f"(d[8]),"+f"(d[9]),"+f"(d[10]),"+f"(d[11]),"+f"(d[12]),"+f"(d[13]),"+f"(d[14]),"+f"(d[15]),"+f"(d[16]),"+f"(d[17]),"+f"(d[18]),"+f"(d[19]),"+f"(d[20]),"+f"(d[21]),"+f"(d[22]),"+f"(d[23]),"+f"(d[24]),"+f"(d[25]),"+f"(d[26]),"+f"(d[27]),"+f"(d[28]),"+f"(d[29]),"+f"(d[30]),"+f"(d[31]),"+f"(d[32]),"+f"(d[33]),"+f"(d[34]),"+f"(d[35]),"+f"(d[36]),"+f"(d[37]),"+f"(d[38]),"+f"(d[39]),"+f"(d[40]),"+f"(d[41]),"+f"(d[42]),"+f"(d[43]),"+f"(d[44]),"+f"(d[45]),"+f"(d[46]),"+f"(d[47]),"+f"(d[48]),"+f"(d[49]),"+f"(d[50]),"+f"(d[51]),"+f"(d[52]),"+f"(d[53]),"+f"(d[54]),"+f"(d[55]),"+f"(d[56]),"+f"(d[57]),"+f"(d[58]),"+f"(d[59]),"+f"(d[60]),"+f"(d[61]),"+f"(d[62]),"+f"(d[63]),"+f"(d[64]),"+f"(d[65]),"+f"(d[66]),"+f"(d[67]),"+f"(d[68]),"+f"(d[69]),"+f"(d[70]),"+f"(d[71]),"+f"(d[72]),"+f"(d[73]),"+f"(d[74]),"+f"(d[75]),"+f"(d[76]),"+f"(d[77]),"+f"(d[78]),"+f"(d[79]),"+f"(d[80]),"+f"(d[81]),"+f"(d[82]),"+f"(d[83]),"+f"(d[84]),"+f"(d[85]),"+f"(d[86]),"+f"(d[87])
    : "r"(a[0]), "r"(a[1]), "r"(a[2]), "r"(a[3]), "r"(descB), "r"(scaleD));
}
__device__ __forceinline__ void wgmma_ss_n72_t11(float (&d)[36], uint32_t descA, uint32_t descB, int scaleD) {
  asm volatile("{\n.reg .pred p;\n.reg .b64 da, db;\nsetp.ne.b32 p, %38, 0;\nmov.b64 da, {%36, 0x40000040};\nmov.b64 db, {%37, 0x40000040};\n"
    "wgmma.mma_async.sync.aligned.m64n72k16.f32.bf16.bf16 {%0,%1,%2,%3,%4,%5,%6,%7,%8,%9,%10,%11,%12,%13,%14,%15,%16,%17,%18,%19,%20,%21,%22,%23,%24,%25,%26,%27,%28,%29,%30,%31,%32,%33,%34,%35}, da, db, p, 1, 1, 1, 1;\n}\n"
    : "+f"(d[0]),"+f"(d[1]),"+f"(d[2]),"+f"(d[3]),"+f"(d[4]),"+f"(d[5]),"+f"(d[6]),"+f"(d[7]),"+f"(d[8]),"+f"(d[9]),"+f"(d[10]),"+f"(d[11]),"+f"(d[12]),"+f"(d[13]),"+f"(d[14]),"+f"(d[15]),"+f"(d[16]),"+f"(d[17]),"+f"(d[18]),"+f"(d[19]),"+f"(d[20]),"+f"(d[21]),"+f"(d[22]),"+f"(d[23]),"+f"(d[24]),"+f"(d[25]),"+f"(d[26]),"+f"(d[27]),"+f"(d[28]),"+f"(d[29]),"+f"(d[30]),"+f"(d[31]),"+f"(d[32]),"+f"(d[33]),"+f"(d[34]),"+f"(d[35])
    : "r"(descA), "r"(descB), "r"(scaleD));
}

#define TSTAMP(i) do {} while (0)
#define TS2(w, i) do {} while (0)

constexpr float LOG2E = 1.4426950408889634f;

__device__ __forceinline__ void feat_exp(const float (&p0)[4], const float (&p1)[4], float (&e)[16]) {
  uint32_t P0 = pack2(p0[0], p0[1]), P1 = pack2(p0[2], p0[3]), P2 = pack2(p1[0], p1[1]), P3 = pack2(p1[2], p1[3]);
  uint32_t a = hmax2(P0, P2), b = hmax2(P1, P3);
  uint32_t mx = hmax2(__byte_perm(a, b, 0x5410), __byte_perm(a, b, 0x7632));
  a = hmin2(P0, P2); b = hmin2(P1, P3);
  uint32_t mn = hmin2(__byte_perm(a, b, 0x5410), __byte_perm(a, b, 0x7632));
  mx = hmax2(mx, __shfl_xor_sync(0xffffffffu, mx, 1));
  mn = hmin2(mn, __shfl_xor_sync(0xffffffffu, mn, 1));
  mx = hmax2(mx, __shfl_xor_sync(0xffffffffu, mx, 2));
  mn = hmin2(mn, __shfl_xor_sync(0xffffffffu, mn, 2));
  float mx0 = -blo(mx) * LOG2E, mx1 = -bhi(mx) * LOG2E, mn0 = blo(mn) * LOG2E, mn1 = bhi(mn) * LOG2E;
  float v[8] = {blo(P0), bhi(P0), blo(P1), bhi(P1), blo(P2), bhi(P2), blo(P3), bhi(P3)};
#pragma unroll
  for (int i = 0; i < 8; i++) {
    bool r1 = (i >> 1) & 1;
    e[i]     = ex2(fmaf(v[i],  LOG2E, r1 ? mx1 : mx0));
    e[8 + i] = ex2(fmaf(v[i], -LOG2E, r1 ? mn1 : mn0));
  }
}

__global__ void __cluster_dims__(2, 1, 1) __launch_bounds__(384, 1)
fused_kernel(const __grid_constant__ Maps maps, const __nv_bfloat16* __restrict__ x, const __nv_bfloat16* __restrict__ wphi,
             const __nv_bfloat16* __restrict__ wo, const __nv_bfloat16* __restrict__ wg_, const __nv_bfloat16* __restrict__ wu_,
             const __nv_bfloat16* __restrict__ wd_, __nv_bfloat16* __restrict__ out) {
  extern __shared__ __align__(1024) unsigned char smem[];
  const uint32_t sb = smem_u32(smem);
  const int tid = threadIdx.x, lane = tid & 31;
  const int warp = __shfl_sync(0xffffffffu, tid >> 5, 0);
  const uint32_t rank = blockIdx.x & 1;
  const int cl = blockIdx.x >> 1;
  int quad, qi;
  if (cl < 4) { quad = 15; qi = cl; }
  else if (cl < 36) { quad = (cl - 4) & 7; qi = (cl - 4) >> 3; }
  else { qi = (cl - 36) / 7; quad = 8 + (cl - 36) - 7 * qi; }
  const int rb = quad, hg = 2 * qi + rank;
  const int rb3 = (quad & ~1) + rank, jf = 4 * (quad & 1) + qi;

  if (warp >= 8) {
    asm volatile("setmaxnreg.dec.sync.aligned.u32 24;");
    if (lane == 0) {
      if (warp == 8) {
#pragma unroll
        for (int k = 0; k < 9; k++) {
          const int s = k < 3 ? k : (k < 6 ? k + 3 : k - 3);
          const uint32_t bar = sb + SM_FULL + s * 8;
          mbar_init(bar, 1);
          mbar_expect_tx(bar, SLOT);
          if (s >= 3 && s < 6) tma2d(sb + s * SLOT, &maps.w, 512 + hg * 64, (s - 3) * 192, bar);
          else tma3d(sb + s * SLOT, &maps.x, 0, rb * 128 + (s >= 6 ? 64 : 0), 3 * (s % 3), bar);
        }
      } else if (warp == 9) {
        mbar_init(sb + SM_MISCB, 2);
        mbar_init(sb + SM_KVB, 32);
        mbar_expect_tx(sb + SM_MISCB, 2048);
        bulk_g2s(sb + SM_WPHI, wphi + hg * 1024, 2048, sb + SM_MISCB);
      } else if (warp == 11) {
        *reinterpret_cast<volatile unsigned*>(smem + SM_EPOCH) = atomicAdd(&g_start, 1u) / NCTA;
      }
      asm volatile("fence.mbarrier_init.release.cluster;" ::: "memory");
    }
    if (tid == 256) TS2(0, 18);
    __syncwarp();
    if (warp != 11) bar_sync(0, 352);
    asm volatile("barrier.cluster.arrive.relaxed.aligned;" ::: "memory");
    if (warp == 8) {
      asm volatile("barrier.cluster.wait.aligned;" ::: "memory");
      if (lane == 0) {
        const CUtensorMap* mgu = rank ? (jf == 7 ? &maps.u7 : &maps.u) : (jf == 7 ? &maps.g7 : &maps.g);
        asm volatile("prefetch.tensormap [%0];" ::"l"(&maps.wo) : "memory");
        asm volatile("prefetch.tensormap [%0];" ::"l"(mgu) : "memory");
        asm volatile("prefetch.tensormap [%0];" ::"l"(&maps.d) : "memory");
#pragma unroll 1
        for (int s = ST_WV; s < ST_O0; s++) {
          if (s == ST_SCR1) continue;
          mbar_wait(sb + SM_EMPTY + (s - 9) * 8);
          const uint32_t dst = sb + (s >= 18 ? s - 18 : s - 9) * SLOT, bar = sb + SM_FULL + s * 8;
          if (s < ST_WO) tma2d(dst, &maps.w, (s < ST_WQ ? 1024 : 0) + hg * 64, (s < ST_WQ ? s - ST_WV : s - ST_WQ) * 192, bar);
          else { mbar_wait(bar - 8); tma2d(dst, &maps.wo, hg * 64, (s - ST_WO) * 192, bar); }
        }
        const int jc = jf == 7 ? 0 : jf;
        int slot = 5 + rank;
#pragma unroll 1
        for (int s = ST_GU + rank; s < NSTAGE; s += 2) {
          mbar_wait(sb + SM_EMPTY + (s < ST_GU + 6 ? s - 12 : s - 9) * 8);
          if (s > ST_GU && s < ST_GU + NSLOT) mbar_wait(sb + SM_FULL + (s - 1) * 8);
          const uint32_t dst = sb + slot * SLOT, bar = sb + SM_FULL + s * 8;
          if (s < ST_D) {
            const int c = (s - ST_GU) >> 1;
#pragma unroll
            for (int b = 0; b < 3; b++) tma3d_mc(dst + b * 8192, mgu, b * 64, jc, c * 64, bar);
          } else {
            tma2d_mc(dst, &maps.d, ((jf + 1 + (s - ST_D)) & 7) * 64, jf * 176, bar);
          }
          slot += 2; if (slot >= NSLOT) slot -= NSLOT;
        }
      }
      __syncwarp();
    } else {
      asm volatile("barrier.cluster.wait.aligned;" ::: "memory");
      if (warp == 11) {
#pragma unroll
        for (int i = 0; i < 4; i++)
          reinterpret_cast<uint4*>(smem + SM_ONES)[lane + 32 * i] = make_uint4(0x3F803F80u, 0x3F803F80u, 0x3F803F80u, 0x3F803F80u);
        fence_async_smem();
        __syncwarp();
        if (lane == 0) { mbar_arrive(sb + SM_MISCB); TS2(0, 19); }
      }
      mbar_wait(sb + SM_MISCB);
      const unsigned epoch = *reinterpret_cast<volatile unsigned*>(smem + SM_EPOCH);
      const uint32_t T = (epoch & 1) ^ 1;
      if (warp == 11) {
        reinterpret_cast<float4*>(&g_kv[T][blockIdx.x * 128])[lane] = make_float4(0.f, 0.f, 0.f, 0.f);
        if (lane < 8) g_z[T][blockIdx.x * 8 + lane] = 0.f;
        mbar_wait(sb + SM_FULL + (ST_WK + 2) * 8);
        if (lane == 0) {
          asm volatile("cp.async.bulk.prefetch.L2.global [%0], 4096;" ::"l"((const char*)wo + blockIdx.x * 4096) : "memory");
          asm volatile("cp.async.bulk.prefetch.L2.global [%0], 11008;" ::"l"((const char*)wg_ + blockIdx.x * 11008) : "memory");
          asm volatile("cp.async.bulk.prefetch.L2.global [%0], 11008;" ::"l"((const char*)wu_ + blockIdx.x * 11008) : "memory");
          asm volatile("cp.async.bulk.prefetch.L2.global [%0], 11008;" ::"l"((const char*)wd_ + blockIdx.x * 11008) : "memory");
          const unsigned target = (epoch + 1) * 32;
          unsigned v; int it = 0;
#pragma unroll 1
          do {
            asm volatile("ld.acquire.gpu.global.u32 %0, [%1];" : "=r"(v) : "l"(&g_kvcnt[hg * 32]) : "memory");
            if (++it > (1 << 18)) break;
          } while ((int)(v - target) < 0);
          TS2(0, 26);
        }
        __syncwarp();
        {
          const char* src = reinterpret_cast<const char*>(&g_kv[T ^ 1][hg * 2048]) + lane * 16;
#pragma unroll
          for (int i = 0; i < 16; i++)
            asm volatile("cp.async.cg.shared.global [%0], [%1], 16;" ::"r"(sb + SM_KV32 + lane * 16 + i * 512), "l"(src + i * 512) : "memory");
          asm volatile("cp.async.cg.shared.global [%0], [%1], 16;" ::"r"(sb + SM_ONES + lane * 16), "l"(&g_z[T ^ 1][hg * 128 + lane * 4]) : "memory");
          asm volatile("cp.async.mbarrier.arrive.noinc.shared::cta.b64 [%0];" ::"r"(sb + SM_KVB) : "memory");
        }
      } else {
        const int w = warp - 9;
        st_rlx4(reinterpret_cast<uint4*>(&g_st[2 * rb + w][hg][0]) + lane, T ^ 1, T ^ 1, T ^ 1, T ^ 1);
        if (lane < 8) st_rlx4(&g_o[2 * rb + w][hg][lane >> 1][3][30 + (lane & 1)], T ^ 1, T ^ 1, T ^ 1, T ^ 1);
        st_rlx4(&g_part[2 * rb3 + w][lane >> 2][jf][lane & 3][3][30], T ^ 1, T ^ 1, T ^ 1, T ^ 1);
        st_rlx4(&g_part[2 * rb3 + w][lane >> 2][jf][lane & 3][3][31], T ^ 1, T ^ 1, T ^ 1, T ^ 1);
        bar_sync(6 + w, 160);
        if (lane == 0) {
          asm volatile("fence.acq_rel.gpu;" ::: "memory");
          TS2(w, 25);
          asm volatile("red.relaxed.gpu.global.add.u32 [%0], 1;" ::"l"(&g_kvcnt[hg * 32]) : "memory");
        }
        mbar_wait(sb + SM_KVB);
        const uint32_t* pw = reinterpret_cast<const uint32_t*>(&g_o[2 * rb + w][lane >> 2][lane & 3][3][31]);
        int it = 0;
#pragma unroll 1
        while (__any_sync(0xffffffffu, (ld_rlx1(pw) ^ T) & 1)) { if (++it > (1 << 18)) break; }
        if (lane == 0) {
          TS2(w, 27);
#pragma unroll 1
          for (int i = 0; i < 3; i++) {
            mbar_wait(sb + SM_EMPTY + (w ? ST_O0 + i : ST_O0 - 9 + i) * 8);
            bulk_g2s(sb + (2 + i) * SLOT, &g_o[2 * rb + w][3 * i][0][0][0], i < 2 ? 24576 : 16384, sb + SM_FULL + (ST_O0 + 3 * w + i) * 8);
          }
        }
        __syncwarp();
      }
    }
    asm volatile("barrier.cluster.arrive.relaxed.aligned;" ::: "memory");
    asm volatile("barrier.cluster.wait.aligned;" ::: "memory");
  } else {
    asm volatile("setmaxnreg.inc.sync.aligned.u32 240;");
    if (lane == 0) {
#pragma unroll 1
      for (int d = warp; d + 9 < NSTAGE; d += 8) {
        mbar_init(sb + SM_EMPTY + d * 8, st_empty_cnt(d));
        mbar_init(sb + SM_FULL + (d + 9) * 8, 1);
        mbar_expect_tx(sb + SM_FULL + (d + 9) * 8, st_bytes(d + 9));
      }
      asm volatile("fence.mbarrier_init.release.cluster;" ::: "memory");
    }
    __syncwarp();
    bar_sync(0, 352);
    asm volatile("barrier.cluster.arrive.relaxed.aligned;" ::: "memory");
    const int wg = warp >> 2, wq = warp & 3, g = lane >> 2, t = lane & 3;
    const bool lead = (tid & 127) == 0;
    const uint32_t db = ((sb & 0x3FFFF) >> 4) | (512u << 16);
    auto release = [&](int d) {
      const int s = st_next(d);
      if (s < NSTAGE) mbar_arrive_cluster(sb + SM_EMPTY + d * 8, s >= ST_GU ? (uint32_t)(s & 1) : rank);
    };
    const uint32_t lrow = (uint32_t)(wq * 16 + (lane & 7) + ((lane >> 3) & 1) * 8) * 128;
    const uint32_t lx = lane & 7, lhi = lane >> 4;
    if (wg == 1) bar_arrive(4, 256);
    TSTAMP(0);

    float r0, r1;
    uint32_t E[4][8];
    uint32_t T = 0;
    {
      uint32_t A[32][4];
      const int sx = wg ? ST_X1 : ST_X0;
      {
        const uint32_t base = sb + sx * SLOT + lrow;
        float s0 = 0.f, s1 = 0.f;
#pragma unroll
        for (int c = 0; c < 8; c++) {
          if (c % 3 == 0) mbar_wait(sb + SM_FULL + (sx + c / 3) * 8);
#pragma unroll
          for (int k = 0; k < 4; k++) ldsm4(A[4 * c + k], base + c * 8192 + (((2 * k + lhi) ^ lx) << 4));
          const uint32_t u0 = hadd2(hadd2(hadd2(A[4 * c][0], A[4 * c][2]), hadd2(A[4 * c + 1][0], A[4 * c + 1][2])),
                                    hadd2(hadd2(A[4 * c + 2][0], A[4 * c + 2][2]), hadd2(A[4 * c + 3][0], A[4 * c + 3][2])));
          const uint32_t u1 = hadd2(hadd2(hadd2(A[4 * c][1], A[4 * c][3]), hadd2(A[4 * c + 1][1], A[4 * c + 1][3])),
                                    hadd2(hadd2(A[4 * c + 2][1], A[4 * c + 2][3]), hadd2(A[4 * c + 3][1], A[4 * c + 3][3])));
          s0 += blo(u0) + bhi(u0); s1 += blo(u1) + bhi(u1);
        }
        s0 += __shfl_xor_sync(0xffffffffu, s0, 1); s1 += __shfl_xor_sync(0xffffffffu, s1, 1);
        s0 += __shfl_xor_sync(0xffffffffu, s0, 2); s1 += __shfl_xor_sync(0xffffffffu, s1, 2);
        TSTAMP(17);
        asm volatile("barrier.cluster.wait.aligned;" ::: "memory");
        if (lane < 3) release(sx + lane);
        s0 *= (1.f / 512.f); s1 *= (1.f / 512.f);
        const uint32_t m0 = pack2(s0, s0), m1 = pack2(s1, s1);
        float q0 = 0.f, q1 = 0.f;
#pragma unroll
        for (int ks = 0; ks < 32; ks += 2) {
          uint32_t v0, v1;
          A[ks][0] = hsub2(A[ks][0], m0); A[ks][1] = hsub2(A[ks][1], m1);
          A[ks][2] = hsub2(A[ks][2], m0); A[ks][3] = hsub2(A[ks][3], m1);
          A[ks + 1][0] = hsub2(A[ks + 1][0], m0); A[ks + 1][1] = hsub2(A[ks + 1][1], m1);
          A[ks + 1][2] = hsub2(A[ks + 1][2], m0); A[ks + 1][3] = hsub2(A[ks + 1][3], m1);
          v0 = hfma2(A[ks][2], A[ks][2], hmul2(A[ks][0], A[ks][0]));
          v1 = hfma2(A[ks][3], A[ks][3], hmul2(A[ks][1], A[ks][1]));
          v0 = hfma2(A[ks + 1][2], A[ks + 1][2], hfma2(A[ks + 1][0], A[ks + 1][0], v0));
          v1 = hfma2(A[ks + 1][3], A[ks + 1][3], hfma2(A[ks + 1][1], A[ks + 1][1], v1));
          q0 += blo(v0) + bhi(v0); q1 += blo(v1) + bhi(v1);
        }
        q0 += __shfl_xor_sync(0xffffffffu, q0, 1); q1 += __shfl_xor_sync(0xffffffffu, q1, 1);
        q0 += __shfl_xor_sync(0xffffffffu, q0, 2); q1 += __shfl_xor_sync(0xffffffffu, q1, 2);
        s0 -= blo(m0); s1 -= blo(m1);
        r0 = rsqrtf(fmaxf(q0 * (1.f / 512.f) - s0 * s0, 0.f) + 1e-5f);
        r1 = rsqrtf(fmaxf(q1 * (1.f / 512.f) - s1 * s1, 0.f) + 1e-5f);
      }
      TSTAMP(1);

      const uint32_t so = (wg ? (ST_SCR1 % NSLOT) : (ST_SCR0 % NSLOT)) * SLOT, scr = sb + so;
#pragma unroll 1
      for (int ps = 0; ps < 3; ps++) {
        const int st0 = ps == 0 ? ST_WK : (ps == 1 ? ST_WV : ST_WQ);
        const uint32_t wdesc = DESC((ps == 0 ? ST_WK % NSLOT : (ps == 1 ? ST_WV % NSLOT : ST_WQ % NSLOT)) * SLOT);
        float acc[32];
        bar_sync(4 + wg, 256);
#pragma unroll
        for (int i = 0; i < 3; i++) {
          mbar_wait(sb + SM_FULL + (st0 + i) * 8);
          wg_fence();
#pragma unroll
          for (int kk = 0; kk < (i < 2 ? 12 : 8); kk++)
            wgmma_rs_n64(acc, A[12 * i + kk], wdesc + ((i * SLOT + kk * 2048) >> 4), (i | kk) != 0);
          wg_commit();
          if (i > 0) { wg_wait<1>(); if (lead) release(st0 + i - 1); }
        }
        if (ps < 2 || wg == 0) bar_arrive(4 + (wg ^ 1), 256);
        wg_wait<0>();
        if (lead) release(st0 + 2);
        TSTAMP(2 + 2 * ps);
        uint32_t a[4][4];
#pragma unroll
        for (int h = 0; h < 4; h++) {
          a[h][0] = pack2(acc[8 * h + 0] * r0, acc[8 * h + 1] * r0); a[h][1] = pack2(acc[8 * h + 2] * r1, acc[8 * h + 3] * r1);
          a[h][2] = pack2(acc[8 * h + 4] * r0, acc[8 * h + 5] * r0); a[h][3] = pack2(acc[8 * h + 6] * r1, acc[8 * h + 7] * r1);
        }
        if (ps != 1) {
          if (ps == 0) {
            mbar_wait(sb + SM_MISCB);
            T = (*reinterpret_cast<volatile unsigned*>(smem + SM_EPOCH) & 1) ^ 1;
            mbar_wait(sb + SM_EMPTY + (wg ? ST_SCR1 - NSLOT : ST_SCR0 - NSLOT) * 8);
          }
          float pp[4][2][4];
#pragma unroll
          for (int h = 0; h < 4; h++) {
            uint32_t b[4];
            ldsm4t(b, sb + SM_WPHI + h * 512 + ((lane & 7) + ((lane >> 3) & 1) * 8) * 32 + lhi * 16);
#pragma unroll
            for (int i = 0; i < 4; i++) { pp[h][0][i] = 0.f; pp[h][1][i] = 0.f; }
            mma16816(pp[h][0], a[h], b[0], b[1]);
            mma16816(pp[h][1], a[h], b[2], b[3]);
          }
          float e[4][16];
#pragma unroll
          for (int h = 0; h < 4; h++) feat_exp(pp[h][0], pp[h][1], e[h]);
          if (ps == 0) {
#pragma unroll
            for (int h = 0; h < 4; h++) {
              const float (&f)[16] = e[h];
              float sp0 = (f[0] + f[1]) + (f[4] + f[5]), sp1 = (f[2] + f[3]) + (f[6] + f[7]);
              float sn0 = (f[8] + f[9]) + (f[12] + f[13]), sn1 = (f[10] + f[11]) + (f[14] + f[15]);
              sp0 += __shfl_xor_sync(0xffffffffu, sp0, 1); sp1 += __shfl_xor_sync(0xffffffffu, sp1, 1);
              sn0 += __shfl_xor_sync(0xffffffffu, sn0, 1); sn1 += __shfl_xor_sync(0xffffffffu, sn1, 1);
              sp0 += __shfl_xor_sync(0xffffffffu, sp0, 2); sp1 += __shfl_xor_sync(0xffffffffu, sp1, 2);
              sn0 += __shfl_xor_sync(0xffffffffu, sn0, 2); sn1 += __shfl_xor_sync(0xffffffffu, sn1, 2);
              sp0 = rcp(sp0); sp1 = rcp(sp1); sn0 = rcp(sn0); sn1 = rcp(sn1);
              const uint32_t dst = scr + (h >> 1) * 8192 + lrow;
              stsm4(dst + ((((h & 1) * 4 + lhi) ^ lx) << 4), pack2(f[0] * sp0, f[1] * sp0), pack2(f[2] * sp1, f[3] * sp1),
                    pack2(f[4] * sp0, f[5] * sp0), pack2(f[6] * sp1, f[7] * sp1));
              stsm4(dst + ((((h & 1) * 4 + 2 + lhi) ^ lx) << 4), pack2(f[8] * sn0, f[9] * sn0), pack2(f[10] * sn1, f[11] * sn1),
                    pack2(f[12] * sn0, f[13] * sn0), pack2(f[14] * sn1, f[15] * sn1));
            }
          } else {
#pragma unroll
            for (int h = 0; h < 4; h++)
#pragma unroll
              for (int i = 0; i < 8; i++) A[2 * h + (i >> 2)][i & 3] = pack2(e[h][2 * i], e[h][2 * i + 1]);
          }
        } else {
#pragma unroll
          for (int h = 0; h < 4; h++) stsm4(scr + 16384 + lrow + (((2 * h + lhi) ^ lx) << 4), a[h][0], a[h][1], a[h][2], a[h][3]);
          fence_async_smem();
          bar_sync(1 + wg, 128);
          float kv0[36], kv1[36];
          wg_fence();
#pragma unroll
          for (int ks = 0; ks < 4; ks++) {
            const uint32_t vo = so + 16384 + ks * 2048;
            const uint32_t dv = (DESC(vo) & 0xFFFFu) | (((SM_ONES - vo) >> 4) << 16);
            wgmma_ss_n72_t11(kv0, DESC(so + ks * 2048), dv, ks != 0);
            wgmma_ss_n72_t11(kv1, DESC(so + 8192 + ks * 2048), dv, ks != 0);
          }
          wg_commit();
          wg_wait<0>();
          if (lead) release(wg ? ST_SCR1 : ST_SCR0);
          const bool up = wq >= 2;
          const int f = (wq & 1) * 16 + g;
          float* kvp = &g_kv[T ^ 1][((hg * 4 + (wq >> 1)) * 32 + f) * 16 + 2 * t];
          float* zp = &g_z[T ^ 1][(hg * 4 + (wq >> 1)) * 32 + f];
#pragma unroll
          for (int b = 0; b < 2; b++) {
#pragma unroll
            for (int n = 0; n < 2; n++) {
              float c0, c1, c2, c3;
              if (b == 0) {
                c0 = up ? kv0[8 + 4 * n + 0] : kv0[4 * n + 0]; c1 = up ? kv0[8 + 4 * n + 1] : kv0[4 * n + 1];
                c2 = up ? kv0[8 + 4 * n + 2] : kv0[4 * n + 2]; c3 = up ? kv0[8 + 4 * n + 3] : kv0[4 * n + 3];
              } else {
                c0 = up ? kv1[24 + 4 * n + 0] : kv1[16 + 4 * n + 0]; c1 = up ? kv1[24 + 4 * n + 1] : kv1[16 + 4 * n + 1];
                c2 = up ? kv1[24 + 4 * n + 2] : kv1[16 + 4 * n + 2]; c3 = up ? kv1[24 + 4 * n + 3] : kv1[16 + 4 * n + 3];
              }
              float* p = kvp + b * 1024 + n * 8;
              asm volatile("red.relaxed.gpu.global.add.v2.f32 [%0], {%1,%2};" ::"l"(p), "f"(c0), "f"(c1) : "memory");
              asm volatile("red.relaxed.gpu.global.add.v2.f32 [%0], {%1,%2};" ::"l"(p + 128), "f"(c2), "f"(c3) : "memory");
            }
            if (t == 0) {
              asm volatile("red.relaxed.gpu.global.add.f32 [%0], %1;" ::"l"(zp + b * 64), "f"(b ? kv1[32] : kv0[32]) : "memory");
              asm volatile("red.relaxed.gpu.global.add.f32 [%0], %1;" ::"l"(zp + b * 64 + 8), "f"(b ? kv1[34] : kv0[34]) : "memory");
            }
          }
          bar_arrive(6 + wg, 160);
        }
        TSTAMP(3 + 2 * ps);
      }
#pragma unroll
      for (int i = 0; i < 32; i++) E[i >> 3][i & 7] = A[i >> 2][i & 3];
    }
    const int rh = 2 * rb + wg;
    mbar_wait(sb + SM_KVB);
    {
      const int r = tid & 127;
      const float4* src = reinterpret_cast<const float4*>(smem + SM_KV32) + r;
#pragma unroll
      for (int i = 0; i < 4; i++) {
        const float4 a = src[i * 128];
        *reinterpret_cast<uint2*>(smem + SM_KVS + (i * 32 + (r >> 2)) * 48 + (r & 3) * 8) = make_uint2(pack2(a.x, a.y), pack2(a.z, a.w));
      }
      const uint32_t zz = pack2(reinterpret_cast<const float*>(smem + SM_ONES)[r], 1.0f);
      *reinterpret_cast<uint4*>(smem + SM_KVS + r * 48 + 32) = make_uint4(zz, zz, zz, zz);
      bar_sync(1 + wg, 128);
    }
    TSTAMP(8);
    {
      uint4* op = &g_o[rh][hg][wq][0][lane];
#pragma unroll
      for (int h = 0; h < 4; h++) {
        uint32_t b0[4], b1[4], b2[4];
        const uint32_t kb = sb + SM_KVS + (h * 32 + lane) * 48;
        ldsm4t(b0, kb); ldsm4t(b1, kb + 16); ldsm4t(b2, kb + 32);
        const uint32_t ep[4] = {E[h][0], E[h][1], E[h][2], E[h][3]}, en[4] = {E[h][4], E[h][5], E[h][6], E[h][7]};
        float np0[4] = {0, 0, 0, 0}, np1[4] = {0, 0, 0, 0}, nn0[4] = {0, 0, 0, 0}, nn1[4] = {0, 0, 0, 0}, dp[4] = {0, 0, 0, 0}, dn[4] = {0, 0, 0, 0};
        mma16816(dp, ep, b2[0], b2[1]);  mma16816(dn, en, b2[2], b2[3]);
        mma16816(np0, ep, b0[0], b0[1]); mma16816(nn0, en, b0[2], b0[3]);
        mma16816(np1, ep, b1[0], b1[1]); mma16816(nn1, en, b1[2], b1[3]);
        const float i0 = rcp(fmaf(dp[0], dn[1], fmaf(dn[0], dp[1], 1e-6f * dp[1] * dn[1])));
        const float i1 = rcp(fmaf(dp[2], dn[3], fmaf(dn[2], dp[3], 1e-6f * dp[3] * dn[3])));
        const float cp0 = dn[1] * i0, cn0 = dp[1] * i0, cp1 = dn[3] * i1, cn1 = dp[3] * i1;
        st_rlx4(op + h * 32,
                tg(pack2(fmaf(np0[0], cp0, nn0[0] * cn0), fmaf(np0[1], cp0, nn0[1] * cn0)), T),
                pack2(fmaf(np0[2], cp1, nn0[2] * cn1), fmaf(np0[3], cp1, nn0[3] * cn1)),
                pack2(fmaf(np1[0], cp0, nn1[0] * cn0), fmaf(np1[1], cp0, nn1[1] * cn0)),
                pack2(fmaf(np1[2], cp1, nn1[2] * cn1), fmaf(np1[3], cp1, nn1[3] * cn1)));
      }
    }
    TSTAMP(9);

    {
      uint32_t xr[16];
      {
        const uint32_t* xp = reinterpret_cast<const uint32_t*>(x + (size_t)(rh * 64 + wq * 16 + g) * 512 + hg * 64 + 2 * t);
#pragma unroll
        for (int i = 0; i < 8; i++) { xr[2 * i] = __ldg(xp + 4 * i); xr[2 * i + 1] = __ldg(xp + 8 * 256 + 4 * i); }
      }
      uint32_t A[8][4][4];
      const uint4* op = &g_o[rh][0][wq][0][lane];
      const uint32_t ob = sb + 2 * SLOT + wq * 2048 + lane * 16;
      float acc[32];
#pragma unroll
      for (int p = 0; p < 3; p++) {
        mbar_wait(sb + SM_FULL + (ST_O0 + 3 * wg + p) * 8);
#pragma unroll
        for (int c = 3 * p; c < (p < 2 ? 3 * p + 3 : 8); c++)
#pragma unroll
          for (int s = 0; s < 4; s++)
            asm volatile("ld.shared.v4.b32 {%0,%1,%2,%3}, [%4];" : "=r"(A[c][s][0]), "=r"(A[c][s][1]), "=r"(A[c][s][2]), "=r"(A[c][s][3])
                         : "r"(ob + c * 8192 + s * 512) : "memory");
        __syncwarp();
        if (lane == 0) release(ST_O0 + 3 * wg + p);
        mbar_wait(sb + SM_FULL + (ST_WO + p) * 8);
#pragma unroll
        for (int c = 3 * p; c < (p < 2 ? 3 * p + 3 : 8); c++) {
          chk_chunk(A[c], op + c * 512, T);
          wg_fence();
#pragma unroll
          for (int s = 0; s < 4; s++)
            wgmma_rs_n64(acc, A[c][s], DESC(((ST_WO + p) % NSLOT) * SLOT + ((c % 3) * 4 + s) * 2048), (c | s) != 0);
          wg_commit();
        }
      }
      wg_wait<0>();
      if ((tid & 127) < 3) release(ST_WO + (tid & 127));
      TSTAMP(10);
      uint32_t hw[16];
      float s0 = 0.f, s1 = 0.f, q0 = 0.f, q1 = 0.f;
#pragma unroll
      for (int i = 0; i < 8; i++) {
        hw[2 * i]     = pack2(blo(xr[2 * i]) + acc[4 * i], bhi(xr[2 * i]) + acc[4 * i + 1]);
        hw[2 * i + 1] = pack2(blo(xr[2 * i + 1]) + acc[4 * i + 2], bhi(xr[2 * i + 1]) + acc[4 * i + 3]);
      }
      uint4* hp_ = &g_h[rh][hg][wq][0][lane];
#pragma unroll
      for (int s = 0; s < 4; s++) st_rlx4(hp_ + s * 32, tg(hw[4 * s], T), hw[4 * s + 1], hw[4 * s + 2], hw[4 * s + 3]);
#pragma unroll
      for (int i = 0; i < 8; i++) {
        float a = blo(hw[2 * i]), b = bhi(hw[2 * i]);
        s0 += a + b; q0 = fmaf(a, a, q0); q0 = fmaf(b, b, q0);
        a = blo(hw[2 * i + 1]); b = bhi(hw[2 * i + 1]);
        s1 += a + b; q1 = fmaf(a, a, q1); q1 = fmaf(b, b, q1);
      }
      s0 += __shfl_xor_sync(0xffffffffu, s0, 1); s1 += __shfl_xor_sync(0xffffffffu, s1, 1);
      q0 += __shfl_xor_sync(0xffffffffu, q0, 1); q1 += __shfl_xor_sync(0xffffffffu, q1, 1);
      s0 += __shfl_xor_sync(0xffffffffu, s0, 2); s1 += __shfl_xor_sync(0xffffffffu, s1, 2);
      q0 += __shfl_xor_sync(0xffffffffu, q0, 2); q1 += __shfl_xor_sync(0xffffffffu, q1, 2);
      if (t < 2) st_rlx2(&g_st[rh][hg][wq * 16 + g + t * 8], tg(__float_as_uint(t ? s1 : s0), T), __float_as_uint(t ? q1 : q0));
      uint32_t hx = T;
#pragma unroll
      for (int i = 0; i < 4; i++) hx |= (hw[4 * i] & 1u) << (i + 1);
      st_rlx1(&g_hx[rh][hg][wq][lane], hx);
    }
    TSTAMP(11);

    const int rh3 = 2 * rb3 + wg;
    uint32_t HH[11][4];
    {
      uint32_t A[2][4][4];
      const uint4* hp_ = &g_h[rh3][0][wq][0][lane];
      uint32_t m0, m1;
      {
        const uint2* sp = &g_st[rh3][2 * t][wq * 16 + g];
        uint32_t a[4], b[4];
        int it = 0;
#pragma unroll 1
        do {
          ld_rlx2(a[0], a[1], sp); ld_rlx2(a[2], a[3], sp + 64); ld_rlx2(b[0], b[1], sp + 8); ld_rlx2(b[2], b[3], sp + 72);
          if (++it > (1 << 18)) break;
        } while (__any_sync(0xffffffffu, bad4(a[0], a[2], b[0], b[2], T) & 1));
        ld_chunk(A[0], hp_);
        float s0 = __uint_as_float(a[0]) + __uint_as_float(a[2]), q0 = __uint_as_float(a[1]) + __uint_as_float(a[3]);
        float s1 = __uint_as_float(b[0]) + __uint_as_float(b[2]), q1 = __uint_as_float(b[1]) + __uint_as_float(b[3]);
        s0 += __shfl_xor_sync(0xffffffffu, s0, 1); s1 += __shfl_xor_sync(0xffffffffu, s1, 1);
        q0 += __shfl_xor_sync(0xffffffffu, q0, 1); q1 += __shfl_xor_sync(0xffffffffu, q1, 1);
        s0 += __shfl_xor_sync(0xffffffffu, s0, 2); s1 += __shfl_xor_sync(0xffffffffu, s1, 2);
        q0 += __shfl_xor_sync(0xffffffffu, q0, 2); q1 += __shfl_xor_sync(0xffffffffu, q1, 2);
        s0 *= (1.f / 512.f); s1 *= (1.f / 512.f);
        r0 = rcp(fmaxf(q0 * (1.f / 512.f) - s0 * s0, 0.f) + 1e-5f);
        r1 = rcp(fmaxf(q1 * (1.f / 512.f) - s1 * s1, 0.f) + 1e-5f);
        m0 = pack2(s0, s0); m1 = pack2(s1, s1);
      }
      TSTAMP(12);
      float ag[88], au[88];
      int slot = 5;
#pragma unroll 1
      for (int c2 = 0; c2 < 8; c2 += 2) {
#pragma unroll
        for (int b = 0; b < 2; b++) {
          const int c = c2 + b, sG = ST_GU + 2 * c;
          chk_chunk(A[b], hp_ + c * 512, T);
#pragma unroll
          for (int s = 0; s < 4; s++) {
            A[b][s][0] = hsub2(A[b][s][0], m0); A[b][s][1] = hsub2(A[b][s][1], m1);
            A[b][s][2] = hsub2(A[b][s][2], m0); A[b][s][3] = hsub2(A[b][s][3], m1);
          }
          mbar_wait(sb + SM_FULL + sG * 8);
          wg_fence();
#pragma unroll
          for (int s = 0; s < 4; s++)
            wgmma_rs_n176(ag, A[b][s], db + slot * (SLOT >> 4) + s * 128, (c | s) != 0);
          wg_commit();
          if (++slot == NSLOT) slot = 0;
          wg_wait<1>();
          if (lead && c > 0) release(sG - 1);
          if (c < 7) ld_chunk(A[b ^ 1], hp_ + (c + 1) * 512);
          mbar_wait(sb + SM_FULL + (sG + 1) * 8);
          wg_fence();
#pragma unroll
          for (int s = 0; s < 4; s++)
            wgmma_rs_n176(au, A[b][s], db + slot * (SLOT >> 4) + s * 128, (c | s) != 0);
          wg_commit();
          if (++slot == NSLOT) slot = 0;
          wg_wait<1>();
          if (lead) release(sG);
        }
      }
      wg_wait<0>();
      TSTAMP(13);
#pragma unroll
      for (int s = 0; s < 11; s++) {
        HH[s][0] = pack2(ag[8 * s + 0] * au[8 * s + 0] * r0, ag[8 * s + 1] * au[8 * s + 1] * r0);
        HH[s][1] = pack2(ag[8 * s + 2] * au[8 * s + 2] * r1, ag[8 * s + 3] * au[8 * s + 3] * r1);
        HH[s][2] = pack2(ag[8 * s + 4] * au[8 * s + 4] * r0, ag[8 * s + 5] * au[8 * s + 5] * r0);
        HH[s][3] = pack2(ag[8 * s + 6] * au[8 * s + 6] * r1, ag[8 * s + 7] * au[8 * s + 7] * r1);
      }
    }
    TSTAMP(14);

    {
      float acc[32];
      uint32_t in[8][4][4];
      const uint4* inb = &g_part[rh3][jf][0][wq][0][lane];
      uint4* outb = &g_part[rh3][0][jf][wq][0][lane];
      const uint32_t* hint = reinterpret_cast<const uint32_t*>(&g_part[rh3][jf][(jf - 1 - lane) & 7][wq][3][31]);
      int slot = (5 + 16) % NSLOT;
      auto step = [&](int st) {
        uint32_t pk[16];
        if (st > 0) {
#pragma unroll
          for (int i = 0; i < 16; i++) pk[i] = pack2(acc[2 * i], acc[2 * i + 1]);
        }
        mbar_wait(sb + SM_FULL + (ST_D + st) * 8);
        wg_fence();
#pragma unroll
        for (int s = 0; s < 4; s++) wgmma_rs_n64(acc, HH[s], db + slot * (SLOT >> 4) + s * 128, s != 0);
        if (st > 0) {
          uint4* p = outb + ((jf + st) & 7) * 4096;
#pragma unroll
          for (int s = 0; s < 4; s++) st_rlx4(p + s * 32, tg(pk[4 * s], T), pk[4 * s + 1], pk[4 * s + 2], pk[4 * s + 3]);
        }
#pragma unroll
        for (int s = 4; s < 11; s++) wgmma_rs_n64(acc, HH[s], db + slot * (SLOT >> 4) + s * 128, 1);
        wg_commit();
        if (++slot == NSLOT) slot = 0;
      };
      auto fetch = [&](int q) { ld_chunk(in[q], inb + ((jf - 1 - q) & 7) * 512); };
#pragma unroll 1
      for (int st = 0; st < 5; st++) { step(st); wg_wait<0>(); }
      step(5); fetch(0); wg_wait<0>();
      step(6); fetch(1); fetch(2); wg_wait<0>();
      step(7); fetch(3);
      ld_chunk(in[7], &g_h[rh3][jf][wq][0][lane]);
      uint32_t hx = ld_rlx1(&g_hx[rh3][jf][wq][lane]);
      wg_wait<0>();
      TSTAMP(15);
      {
        uint32_t ready = 0; int it = 0;
#pragma unroll
        for (int q = 4; q < 7; q++) {
#pragma unroll 1
          while (!((ready >> q) & 1)) {
            ready = __ballot_sync(0xffffffffu, ((ld_rlx1(hint) ^ T) & 1) == 0);
            if (++it > (1 << 18)) break;
          }
          fetch(q);
        }
#pragma unroll 1
        while (__any_sync(0xffffffffu, (hx ^ T) & 1)) {
          hx = ld_rlx1(&g_hx[rh3][jf][wq][lane]);
          if (++it > (1 << 18)) break;
        }
      }
#pragma unroll
      for (int s = 0; s < 4; s++) in[7][s][0] = (in[7][s][0] & 0xFFFFFFFEu) | ((hx >> (s + 1)) & 1u);
#pragma unroll
      for (int k = 0; k < 8; k++) {
        const int q = k == 0 ? 7 : k - 1;
        if (q < 7) chk_chunk(in[q], inb + ((jf - 1 - q) & 7) * 512, T);
#pragma unroll
        for (int i = 0; i < 16; i++) { acc[2 * i] += blo(in[q][i >> 2][i & 3]); acc[2 * i + 1] += bhi(in[q][i >> 2][i & 3]); }
      }
      uint32_t* op = reinterpret_cast<uint32_t*>(out + (size_t)(rh3 * 64 + wq * 16 + g) * 512 + jf * 64 + 2 * t);
#pragma unroll
      for (int i = 0; i < 8; i++) {
        op[4 * i]           = pack2(acc[4 * i], acc[4 * i + 1]);
        op[8 * 256 + 4 * i] = pack2(acc[4 * i + 2], acc[4 * i + 3]);
      }
    }
    TSTAMP(16);
    asm volatile("barrier.cluster.arrive.relaxed.aligned;" ::: "memory");
    asm volatile("barrier.cluster.wait.aligned;" ::: "memory");
  }
}

typedef CUresult (*EncodeFn)(CUtensorMap*, CUtensorMapDataType, cuuint32_t, void*, const cuuint64_t*, const cuuint64_t*,
                             const cuuint32_t*, const cuuint32_t*, CUtensorMapInterleave, CUtensorMapSwizzle,
                             CUtensorMapL2promotion, CUtensorMapFloatOOBfill);

void encode(EncodeFn fn, CUtensorMap* m, const void* base, int rank, const cuuint64_t* dims, const cuuint64_t* strides,
            const cuuint32_t* box) {
  cuuint32_t es[3] = {1, 1, 1};
  fn(m, CU_TENSOR_MAP_DATA_TYPE_BFLOAT16, (cuuint32_t)rank, const_cast<void*>(base), dims, strides, box, es,
     CU_TENSOR_MAP_INTERLEAVE_NONE, CU_TENSOR_MAP_SWIZZLE_128B, CU_TENSOR_MAP_L2_PROMOTION_L2_256B,
     CU_TENSOR_MAP_FLOAT_OOB_FILL_NONE);
}

}

extern "C" void kernel_launch(void* const* d_in, const int* in_sizes, int n_in, void* d_out, int out_size) {
  (void)in_sizes; (void)n_in; (void)out_size;
  const __nv_bfloat16* x    = (const __nv_bfloat16*)d_in[0];
  const __nv_bfloat16* wqkv = (const __nv_bfloat16*)d_in[1];
  const __nv_bfloat16* wphi = (const __nv_bfloat16*)d_in[2];
  const __nv_bfloat16* wo   = (const __nv_bfloat16*)d_in[3];
  const __nv_bfloat16* wg   = (const __nv_bfloat16*)d_in[5];
  const __nv_bfloat16* wu   = (const __nv_bfloat16*)d_in[6];
  const __nv_bfloat16* wd   = (const __nv_bfloat16*)d_in[7];

  static EncodeFn fn = nullptr;
  if (!fn) {
    void* p = nullptr;
    cudaDriverEntryPointQueryResult qr;
    cudaGetDriverEntryPoint("cuTensorMapEncodeTiled", &p, cudaEnableDefault, &qr);
    fn = (EncodeFn)p;
    cudaFuncSetAttribute(fused_kernel, cudaFuncAttributeMaxDynamicSharedMemorySize, SM_TOTAL);
  }
  Maps maps;
  {
    cuuint64_t d[3] = {64, 2048, 8}, s[2] = {1024, 128}; cuuint32_t b[3] = {64, 64, 3};
    encode(fn, &maps.x, x, 3, d, s, b);
  }
  {
    cuuint64_t d[2] = {1536, 512}, s[1] = {3072}; cuuint32_t b[2] = {64, 192};
    encode(fn, &maps.w, wqkv, 2, d, s, b);
  }
  {
    cuuint64_t d[2] = {512, 512}, s[1] = {1024}; cuuint32_t b[2] = {64, 192};
    encode(fn, &maps.wo, wo, 2, d, s, b);
  }
  {
    cuuint64_t d[3] = {176, 7, 512}, d7[3] = {144, 1, 512}, s[2] = {352, 2752}; cuuint32_t b[3] = {64, 1, 64};
    encode(fn, &maps.g, wg, 3, d, s, b);
    encode(fn, &maps.u, wu, 3, d, s, b);
    encode(fn, &maps.g7, wg + 1232, 3, d7, s, b);
    encode(fn, &maps.u7, wu + 1232, 3, d7, s, b);
  }
  {
    cuuint64_t d[2] = {512, 1376}, s[1] = {1024}; cuuint32_t b[2] = {64, 176};
    encode(fn, &maps.d, wd, 2, d, s, b);
  }
  fused_kernel<<<NCTA, 384, SM_TOTAL>>>(maps, x, wphi, wo, wg, wu, wd, (__nv_bfloat16*)d_out);
}
```

```cpp
#include <cuda_runtime.h>
#include <cuda_bf16.h>
#include <cuda.h>
#include <stdint.h>

#define PROF 0

#define THR 3

namespace {

constexpr int NCTA   = 128;
constexpr int SLOT   = 24576;
constexpr int NSLOT  = 9;
constexpr int NSTAGE = 50;

constexpr int ST_X0   = 0;
constexpr int ST_WK   = 3;
constexpr int ST_X1   = 6;
constexpr int ST_SCR0 = 9;
constexpr int ST_WV   = 10;
constexpr int ST_SCR1 = 13;
constexpr int ST_WQ   = 14;
constexpr int ST_WO   = 17;
constexpr int ST_O0   = 20;
constexpr int ST_O1   = 23;
constexpr int ST_GU   = 26;
constexpr int ST_D    = 42;

__host__ __device__ constexpr int st_next(int d) { return d < ST_WQ ? d + 9 : d < ST_O0 ? d + 12 : d < ST_O1 ? d + 3 : d + 9; }
__host__ __device__ constexpr int st_bytes(int s) { return s >= ST_D ? 22528 : (s == ST_O0 + 2 || s == ST_O1 + 2) ? 16384 : 24576; }
__host__ __device__ constexpr int st_empty_cnt(int d) {
  return ((d < 3 || (d >= 6 && d < 9) || (d >= ST_O0 && d < ST_GU)) ? 4 : 0 ? 1 : 2) *
         (st_next(d) >= ST_GU ? 2 : 1);
}

constexpr int SM_ONES = NSLOT * SLOT;
constexpr int SM_WPHI = SM_ONES + 2048;
constexpr int SM_KVS  = SM_WPHI + 2048;
constexpr int SM_KV32 = 4 * SLOT + 16384;
constexpr int SM_BAR  = SM_KVS + 6144;
constexpr int SM_FULL  = SM_BAR;
constexpr int SM_EMPTY = SM_BAR + NSTAGE * 8;
constexpr int SM_MISCB = SM_BAR + 2 * NSTAGE * 8;
constexpr int SM_KVB   = SM_MISCB + 8;
constexpr int SM_EPOCH = SM_KVB + 8;
constexpr int SM_TOTAL = SM_BAR + 1024;

static_assert(SM_TOTAL == 232448, "smem budget");

struct Maps { CUtensorMap x, w, wo, g, u, g7, u7, d; };

__device__ uint4    g_o[32][8][4][4][32];
__device__ uint4    g_h[32][8][4][4][32];
__device__ uint32_t g_hx[32][8][4][32];
__device__ uint2    g_st[32][8][64];
__device__ uint4    g_part[32][8][8][4][4][32];
__device__ float    g_kv[2][32 * 32 * 16];
__device__ float    g_z[2][32 * 32];
__device__ unsigned g_kvcnt[8 * 32];
__device__ unsigned g_start;

__device__ __forceinline__ uint32_t smem_u32(const void* p) { return (uint32_t)__cvta_generic_to_shared(p); }
__device__ __forceinline__ void mbar_init(uint32_t bar, int cnt) {
  asm volatile("mbarrier.init.shared::cta.b64 [%0], %1;" ::"r"(bar), "r"(cnt) : "memory");
}
__device__ __forceinline__ void mbar_expect_tx(uint32_t bar, uint32_t bytes) {
  asm volatile("mbarrier.arrive.expect_tx.shared::cta.b64 _, [%0], %1;" ::"r"(bar), "r"(bytes) : "memory");
}
__device__ __forceinline__ void mbar_arrive(uint32_t bar) {
  asm volatile("mbarrier.arrive.shared::cta.b64 _, [%0];" ::"r"(bar) : "memory");
}
__device__ __forceinline__ void mbar_arrive_cluster(uint32_t bar, uint32_t rank) {
  asm volatile("{\n.reg .b32 ra;\nmapa.shared::cluster.u32 ra, %0, %1;\n"
               "mbarrier.arrive.shared::cluster.b64 _, [ra];\n}" ::"r"(bar), "r"(rank) : "memory");
}
__device__ __forceinline__ bool mbar_try(uint32_t bar) {
  uint32_t ok;
  asm volatile("{\n.reg .pred p;\nmbarrier.try_wait.parity.shared::cta.b64 p, [%1], 0;\nselp.u32 %0, 1, 0, p;\n}"
               : "=r"(ok) : "r"(bar) : "memory");
  return ok != 0;
}
__device__ __forceinline__ void mbar_wait(uint32_t bar) {
  int it = 0;
#pragma unroll 1
  while (!mbar_try(bar)) {
    if (++it > (1 << 20)) __trap();
  }
}
__device__ __forceinline__ void bar_sync(int id, int n)   { asm volatile("bar.sync %0, %1;" ::"r"(id), "r"(n) : "memory"); }
__device__ __forceinline__ void bar_arrive(int id, int n) { asm volatile("bar.arrive %0, %1;" ::"r"(id), "r"(n) : "memory"); }
__device__ __forceinline__ void fence_async_smem() { asm volatile("fence.proxy.async.shared::cta;" ::: "memory"); }
__device__ __forceinline__ void wg_fence()  { asm volatile("wgmma.fence.sync.aligned;" ::: "memory"); }
__device__ __forceinline__ void wg_commit() { asm volatile("wgmma.commit_group.sync.aligned;" ::: "memory"); }
template <int N> __device__ __forceinline__ void wg_wait() { asm volatile("wgmma.wait_group.sync.aligned %0;" ::"n"(N) : "memory"); }
#define DESC(off) (db + ((uint32_t)(off) >> 4))
__device__ __forceinline__ void tma2d(uint32_t dst, const CUtensorMap* m, int c0, int c1, uint32_t bar) {
  asm volatile("cp.async.bulk.tensor.2d.shared::cluster.global.mbarrier::complete_tx::bytes [%0], [%1, {%3, %4}], [%2];"
               ::"r"(dst), "l"(m), "r"(bar), "r"(c0), "r"(c1) : "memory");
}
__device__ __forceinline__ void tma2d_mc(uint32_t dst, const CUtensorMap* m, int c0, int c1, uint32_t bar) {
  asm volatile("cp.async.bulk.tensor.2d.shared::cluster.global.mbarrier::complete_tx::bytes.multicast::cluster [%0], [%1, {%3, %4}], [%2], %5;"
               ::"r"(dst), "l"(m), "r"(bar), "r"(c0), "r"(c1), "h"((uint16_t)3) : "memory");
}
__device__ __forceinline__ void tma3d(uint32_t dst, const CUtensorMap* m, int c0, int c1, int c2, uint32_t bar) {
  asm volatile("cp.async.bulk.tensor.3d.shared::cluster.global.mbarrier::complete_tx::bytes [%0], [%1, {%3, %4, %5}], [%2];"
               ::"r"(dst), "l"(m), "r"(bar), "r"(c0), "r"(c1), "r"(c2) : "memory");
}
__device__ __forceinline__ void tma3d_mc(uint32_t dst, const CUtensorMap* m, int c0, int c1, int c2, uint32_t bar) {
  asm volatile("cp.async.bulk.tensor.3d.shared::cluster.global.mbarrier::complete_tx::bytes.multicast::cluster [%0], [%1, {%3, %4, %5}], [%2], %6;"
               ::"r"(dst), "l"(m), "r"(bar), "r"(c0), "r"(c1), "r"(c2), "h"((uint16_t)3) : "memory");
}
__device__ __forceinline__ void ldsm4(uint32_t (&r)[4], uint32_t addr) {
  asm volatile("ldmatrix.sync.aligned.m8n8.x4.shared.b16 {%0,%1,%2,%3}, [%4];"
               : "=r"(r[0]), "=r"(r[1]), "=r"(r[2]), "=r"(r[3]) : "r"(addr) : "memory");
}
__device__ __forceinline__ void ldsm4t(uint32_t (&r)[4], uint32_t addr) {
  asm volatile("ldmatrix.sync.aligned.m8n8.x4.trans.shared.b16 {%0,%1,%2,%3}, [%4];"
               : "=r"(r[0]), "=r"(r[1]), "=r"(r[2]), "=r"(r[3]) : "r"(addr) : "memory");
}
__device__ __forceinline__ void stsm4(uint32_t addr, uint32_t r0, uint32_t r1, uint32_t r2, uint32_t r3) {
  asm volatile("stmatrix.sync.aligned.m8n8.x4.shared.b16 [%0], {%1,%2,%3,%4};"
               ::"r"(addr), "r"(r0), "r"(r1), "r"(r2), "r"(r3) : "memory");
}
__device__ __forceinline__ void mma16816(float (&c)[4], const uint32_t (&a)[4], uint32_t b0, uint32_t b1) {
  asm volatile("mma.sync.aligned.m16n8k16.row.col.f32.bf16.bf16.f32 {%0,%1,%2,%3},{%4,%5,%6,%7},{%8,%9},{%0,%1,%2,%3};"
               : "+f"(c[0]), "+f"(c[1]), "+f"(c[2]), "+f"(c[3])
               : "r"(a[0]), "r"(a[1]), "r"(a[2]), "r"(a[3]), "r"(b0), "r"(b1));
}
__device__ __forceinline__ uint32_t pack2(float lo, float hi) {
  uint32_t r; asm("cvt.rn.bf16x2.f32 %0, %1, %2;" : "=r"(r) : "f"(hi), "f"(lo)); return r;
}
__device__ __forceinline__ float blo(uint32_t w) { return __uint_as_float(w << 16); }
__device__ __forceinline__ float bhi(uint32_t w) { return __uint_as_float(w & 0xFFFF0000u); }
__device__ __forceinline__ uint32_t hsub2(uint32_t a, uint32_t b) { uint32_t r; asm("sub.rn.bf16x2 %0, %1, %2;" : "=r"(r) : "r"(a), "r"(b)); return r; }
__device__ __forceinline__ uint32_t hadd2(uint32_t a, uint32_t b) { uint32_t r; asm("add.rn.bf16x2 %0, %1, %2;" : "=r"(r) : "r"(a), "r"(b)); return r; }
__device__ __forceinline__ uint32_t hmul2(uint32_t a, uint32_t b) { uint32_t r; asm("mul.rn.bf16x2 %0, %1, %2;" : "=r"(r) : "r"(a), "r"(b)); return r; }
__device__ __forceinline__ uint32_t hfma2(uint32_t a, uint32_t b, uint32_t c) { uint32_t r; asm("fma.rn.bf16x2 %0, %1, %2, %3;" : "=r"(r) : "r"(a), "r"(b), "r"(c)); return r; }
__device__ __forceinline__ uint32_t hmax2(uint32_t a, uint32_t b) { uint32_t r; asm("max.bf16x2 %0, %1, %2;" : "=r"(r) : "r"(a), "r"(b)); return r; }
__device__ __forceinline__ uint32_t hmin2(uint32_t a, uint32_t b) { uint32_t r; asm("min.bf16x2 %0, %1, %2;" : "=r"(r) : "r"(a), "r"(b)); return r; }
__device__ __forceinline__ float ex2(float x) { float r; asm("ex2.approx.ftz.f32 %0, %1;" : "=f"(r) : "f"(x)); return r; }
__device__ __forceinline__ float rcp(float x) { float r; asm("rcp.approx.ftz.f32 %0, %1;" : "=f"(r) : "f"(x)); return r; }
__device__ __forceinline__ void ld_rlx4(uint32_t (&r)[4], const uint4* p) {
  asm volatile("{\n.reg .b128 v;\nld.relaxed.gpu.global.b128 v, [%4];\nmov.b128 {%0,%1,%2,%3}, v;\n}"
               : "=r"(r[0]), "=r"(r[1]), "=r"(r[2]), "=r"(r[3]) : "l"(p) : "memory");
}
__device__ __forceinline__ void st_rlx4(uint4* p, uint32_t a, uint32_t b, uint32_t c, uint32_t d) {
  asm volatile("{\n.reg .b128 v;\nmov.b128 v, {%1,%2,%3,%4};\nst.relaxed.gpu.global.b128 [%0], v;\n}"
               ::"l"(p), "r"(a), "r"(b), "r"(c), "r"(d) : "memory");
}
__device__ __forceinline__ void st_rlx2(uint2* p, uint32_t a, uint32_t b) {
  asm volatile("{\n.reg .b64 v;\nmov.b64 v, {%1,%2};\nst.relaxed.gpu.global.b64 [%0], v;\n}" ::"l"(p), "r"(a), "r"(b) : "memory");
}
__device__ __forceinline__ uint32_t ld_rlx1(const uint32_t* p) {
  uint32_t r; asm volatile("ld.relaxed.gpu.global.b32 %0, [%1];" : "=r"(r) : "l"(p) : "memory"); return r;
}
__device__ __forceinline__ void st_rlx1(uint32_t* p, uint32_t a) {
  asm volatile("st.relaxed.gpu.global.b32 [%0], %1;" ::"l"(p), "r"(a) : "memory");
}
__device__ __forceinline__ void ld_rlx2(uint32_t& a, uint32_t& b, const uint2* p) {
  asm volatile("{\n.reg .b64 v;\nld.relaxed.gpu.global.b64 v, [%2];\nmov.b64 {%0,%1}, v;\n}" : "=r"(a), "=r"(b) : "l"(p) : "memory");
}
__device__ __forceinline__ void bulk_g2s(uint32_t dst, const void* src, uint32_t bytes, uint32_t bar) {
  asm volatile("cp.async.bulk.shared::cluster.global.mbarrier::complete_tx::bytes [%0], [%1], %2, [%3];"
               ::"r"(dst), "l"(src), "r"(bytes), "r"(bar) : "memory");
}
__device__ __forceinline__ uint32_t tg(uint32_t w, uint32_t T) { return (w & 0xFFFFFFFEu) | T; }
__device__ __forceinline__ uint32_t bad4(uint32_t a, uint32_t b, uint32_t c, uint32_t d, uint32_t T) {
  uint32_t u, v;
  asm("lop3.b32 %0, %1, %2, %3, 0x7E;" : "=r"(u) : "r"(a), "r"(b), "r"(T));
  asm("lop3.b32 %0, %1, %2, %3, 0x7E;" : "=r"(v) : "r"(c), "r"(d), "r"(T));
  return u | v;
}

__device__ __forceinline__ void ld_chunk(uint32_t (&a)[4][4], const uint4* p) {
#pragma unroll
  for (int s = 0; s < 4; s++) ld_rlx4(a[s], p + s * 32);
}
__device__ __forceinline__ void chk_chunk(uint32_t (&a)[4][4], const uint4* p, uint32_t T) {
  int it = 0;
#pragma unroll 1
  while (__any_sync(0xffffffffu, bad4(a[0][0], a[1][0], a[2][0], a[3][0], T) & 1)) {
    ld_chunk(a, p);
    if (++it > (1 << 18)) break;
  }
}

__device__ __forceinline__ void wgmma_rs_n64(float (&d)[32], const uint32_t (&a)[4], uint32_t descB, int scaleD) {
  asm volatile("{\n.reg .pred p;\n.reg .b64 db;\nsetp.ne.b32 p, %37, 0;\nmov.b64 db, {%36, 0x40000040};\n"
    "wgmma.mma_async.sync.aligned.m64n64k16.f32.bf16.bf16 {%0,%1,%2,%3,%4,%5,%6,%7,%8,%9,%10,%11,%12,%13,%14,%15,%16,%17,%18,%19,%20,%21,%22,%23,%24,%25,%26,%27,%28,%29,%30,%31}, {%32,%33,%34,%35}, db, p, 1, 1, 1;\n}\n"
    : "+f"(d[0]),"+f"(d[1]),"+f"(d[2]),"+f"(d[3]),"+f"(d[4]),"+f"(d[5]),"+f"(d[6]),"+f"(d[7]),"+f"(d[8]),"+f"(d[9]),"+f"(d[10]),"+f"(d[11]),"+f"(d[12]),"+f"(d[13]),"+f"(d[14]),"+f"(d[15]),"+f"(d[16]),"+f"(d[17]),"+f"(d[18]),"+f"(d[19]),"+f"(d[20]),"+f"(d[21]),"+f"(d[22]),"+f"(d[23]),"+f"(d[24]),"+f"(d[25]),"+f"(d[26]),"+f"(d[27]),"+f"(d[28]),"+f"(d[29]),"+f"(d[30]),"+f"(d[31])
    : "r"(a[0]), "r"(a[1]), "r"(a[2]), "r"(a[3]), "r"(descB), "r"(scaleD));
}
__device__ __forceinline__ void wgmma_rs_n176(float (&d)[88], const uint32_t (&a)[4], uint32_t descB, int scaleD) {
  asm volatile("{\n.reg .pred p;\n.reg .b64 db;\nsetp.ne.b32 p, %93, 0;\nmov.b64 db, {%92, 0x40000040};\n"
    "wgmma.mma_async.sync.aligned.m64n176k16.f32.bf16.bf16 {%0,%1,%2,%3,%4,%5,%6,%7,%8,%9,%10,%11,%12,%13,%14,%15,%16,%17,%18,%19,%20,%21,%22,%23,%24,%25,%26,%27,%28,%29,%30,%31,%32,%33,%34,%35,%36,%37,%38,%39,%40,%41,%42,%43,%44,%45,%46,%47,%48,%49,%50,%51,%52,%53,%54,%55,%56,%57,%58,%59,%60,%61,%62,%63,%64,%65,%66,%67,%68,%69,%70,%71,%72,%73,%74,%75,%76,%77,%78,%79,%80,%81,%82,%83,%84,%85,%86,%87}, {%88,%89,%90,%91}, db, p, 1, 1, 1;\n}\n"
    : "+f"(d[0]),"+f"(d[1]),"+f"(d[2]),"+f"(d[3]),"+f"(d[4]),"+f"(d[5]),"+f"(d[6]),"+f"(d[7]),"+f"(d[8]),"+f"(d[9]),"+f"(d[10]),"+f"(d[11]),"+f"(d[12]),"+f"(d[13]),"+f"(d[14]),"+f"(d[15]),"+f"(d[16]),"+f"(d[17]),"+f"(d[18]),"+f"(d[19]),"+f"(d[20]),"+f"(d[21]),"+f"(d[22]),"+f"(d[23]),"+f"(d[24]),"+f"(d[25]),"+f"(d[26]),"+f"(d[27]),"+f"(d[28]),"+f"(d[29]),"+f"(d[30]),"+f"(d[31]),"+f"(d[32]),"+f"(d[33]),"+f"(d[34]),"+f"(d[35]),"+f"(d[36]),"+f"(d[37]),"+f"(d[38]),"+f"(d[39]),"+f"(d[40]),"+f"(d[41]),"+f"(d[42]),"+f"(d[43]),"+f"(d[44]),"+f"(d[45]),"+f"(d[46]),"+f"(d[47]),"+f"(d[48]),"+f"(d[49]),"+f"(d[50]),"+f"(d[51]),"+f"(d[52]),"+f"(d[53]),"+f"(d[54]),"+f"(d[55]),"+f"(d[56]),"+f"(d[57]),"+f"(d[58]),"+f"(d[59]),"+f"(d[60]),"+f"(d[61]),"+f"(d[62]),"+f"(d[63]),"+f"(d[64]),"+f"(d[65]),"+f"(d[66]),"+f"(d[67]),"+f"(d[68]),"+f"(d[69]),"+f"(d[70]),"+f"(d[71]),"+f"(d[72]),"+f"(d[73]),"+f"(d[74]),"+f"(d[75]),"+f"(d[76]),"+f"(d[77]),"+f"(d[78]),"+f"(d[79]),"+f"(d[80]),"+f"(d[81]),"+f"(d[82]),"+f"(d[83]),"+f"(d[84]),"+f"(d[85]),"+f"(d[86]),"+f"(d[87])
    : "r"(a[0]), "r"(a[1]), "r"(a[2]), "r"(a[3]), "r"(descB), "r"(scaleD));
}
__device__ __forceinline__ void wgmma_ss_n72_t11(float (&d)[36], uint32_t descA, uint32_t descB, int scaleD) {
  asm volatile("{\n.reg .pred p;\n.reg .b64 da, db;\nsetp.ne.b32 p, %38, 0;\nmov.b64 da, {%36, 0x40000040};\nmov.b64 db, {%37, 0x40000040};\n"
    "wgmma.mma_async.sync.aligned.m64n72k16.f32.bf16.bf16 {%0,%1,%2,%3,%4,%5,%6,%7,%8,%9,%10,%11,%12,%13,%14,%15,%16,%17,%18,%19,%20,%21,%22,%23,%24,%25,%26,%27,%28,%29,%30,%31,%32,%33,%34,%35}, da, db, p, 1, 1, 1, 1;\n}\n"
    : "+f"(d[0]),"+f"(d[1]),"+f"(d[2]),"+f"(d[3]),"+f"(d[4]),"+f"(d[5]),"+f"(d[6]),"+f"(d[7]),"+f"(d[8]),"+f"(d[9]),"+f"(d[10]),"+f"(d[11]),"+f"(d[12]),"+f"(d[13]),"+f"(d[14]),"+f"(d[15]),"+f"(d[16]),"+f"(d[17]),"+f"(d[18]),"+f"(d[19]),"+f"(d[20]),"+f"(d[21]),"+f"(d[22]),"+f"(d[23]),"+f"(d[24]),"+f"(d[25]),"+f"(d[26]),"+f"(d[27]),"+f"(d[28]),"+f"(d[29]),"+f"(d[30]),"+f"(d[31]),"+f"(d[32]),"+f"(d[33]),"+f"(d[34]),"+f"(d[35])
    : "r"(descA), "r"(descB), "r"(scaleD));
}

#define TSTAMP(i) do {} while (0)
#define TS2(w, i) do {} while (0)

constexpr float LOG2E = 1.4426950408889634f;

__device__ __forceinline__ void feat_exp(const float (&p0)[4], const float (&p1)[4], float (&e)[16]) {
  uint32_t P0 = pack2(p0[0], p0[1]), P1 = pack2(p0[2], p0[3]), P2 = pack2(p1[0], p1[1]), P3 = pack2(p1[2], p1[3]);
  uint32_t a = hmax2(P0, P2), b = hmax2(P1, P3);
  uint32_t mx = hmax2(__byte_perm(a, b, 0x5410), __byte_perm(a, b, 0x7632));
  a = hmin2(P0, P2); b = hmin2(P1, P3);
  uint32_t mn = hmin2(__byte_perm(a, b, 0x5410), __byte_perm(a, b, 0x7632));
  mx = hmax2(mx, __shfl_xor_sync(0xffffffffu, mx, 1));
  mn = hmin2(mn, __shfl_xor_sync(0xffffffffu, mn, 1));
  mx = hmax2(mx, __shfl_xor_sync(0xffffffffu, mx, 2));
  mn = hmin2(mn, __shfl_xor_sync(0xffffffffu, mn, 2));
  float mx0 = -blo(mx) * LOG2E, mx1 = -bhi(mx) * LOG2E, mn0 = blo(mn) * LOG2E, mn1 = bhi(mn) * LOG2E;
  float v[8] = {blo(P0), bhi(P0), blo(P1), bhi(P1), blo(P2), bhi(P2), blo(P3), bhi(P3)};
#pragma unroll
  for (int i = 0; i < 8; i++) {
    bool r1 = (i >> 1) & 1;
    e[i]     = ex2(fmaf(v[i],  LOG2E, r1 ? mx1 : mx0));
    e[8 + i] = ex2(fmaf(v[i], -LOG2E, r1 ? mn1 : mn0));
  }
}

__global__ void __cluster_dims__(2, 1, 1) __launch_bounds__(384, 1)
fused_kernel(const __grid_constant__ Maps maps, const __nv_bfloat16* __restrict__ x, const __nv_bfloat16* __restrict__ wphi,
             const __nv_bfloat16* __restrict__ wo, const __nv_bfloat16* __restrict__ wg_, const __nv_bfloat16* __restrict__ wu_,
             const __nv_bfloat16* __restrict__ wd_, __nv_bfloat16* __restrict__ out) {
  extern __shared__ __align__(1024) unsigned char smem[];
  const uint32_t sb = smem_u32(smem);
  const int tid = threadIdx.x, lane = tid & 31;
  const int warp = __shfl_sync(0xffffffffu, tid >> 5, 0);
  const uint32_t rank = blockIdx.x & 1;
  const int cl = blockIdx.x >> 1;
  int quad, qi;
  if (cl < 4) { quad = 15; qi = cl; }
  else if (cl < 36) { quad = (cl - 4) & 7; qi = (cl - 4) >> 3; }
  else { qi = (cl - 36) / 7; quad = 8 + (cl - 36) - 7 * qi; }
  const int rb = quad, hg = 2 * qi + rank;
  const int rb3 = (quad & ~1) + rank, jf = 4 * (quad & 1) + qi;

  if (warp >= 8) {
    asm volatile("setmaxnreg.dec.sync.aligned.u32 24;");
    if (lane == 0) {
      if (warp == 8) {
#pragma unroll
        for (int k = 0; k < 9; k++) {
          const int s = k < 3 ? k : (k < 6 ? k + 3 : k - 3);
          const uint32_t bar = sb + SM_FULL + s * 8;
          mbar_init(bar, 1);
          mbar_expect_tx(bar, SLOT);
          if (s >= 3 && s < 6) tma2d(sb + s * SLOT, &maps.w, 512 + hg * 64, (s - 3) * 192, bar);
          else tma3d(sb + s * SLOT, &maps.x, 0, rb * 128 + (s >= 6 ? 64 : 0), 3 * (s % 3), bar);
        }
      } else if (warp == 9) {
        mbar_init(sb + SM_MISCB, 2);
        mbar_init(sb + SM_KVB, 32);
        mbar_expect_tx(sb + SM_MISCB, 2048);
        bulk_g2s(sb + SM_WPHI, wphi + hg * 1024, 2048, sb + SM_MISCB);
      } else if (warp == 11) {
        *reinterpret_cast<volatile unsigned*>(smem + SM_EPOCH) = atomicAdd(&g_start, 1u) / NCTA;
      }
      asm volatile("fence.mbarrier_init.release.cluster;" ::: "memory");
    }
    if (tid == 256) TS2(0, 18);
    __syncwarp();
    if (warp != 11) bar_sync(0, 352);
    asm volatile("barrier.cluster.arrive.relaxed.aligned;" ::: "memory");
    if (warp == 8) {
      asm volatile("barrier.cluster.wait.aligned;" ::: "memory");
      if (lane == 0) {
        const CUtensorMap* mgu = rank ? (jf == 7 ? &maps.u7 : &maps.u) : (jf == 7 ? &maps.g7 : &maps.g);
        asm volatile("prefetch.tensormap [%0];" ::"l"(&maps.wo) : "memory");
        asm volatile("prefetch.tensormap [%0];" ::"l"(mgu) : "memory");
        asm volatile("prefetch.tensormap [%0];" ::"l"(&maps.d) : "memory");
#pragma unroll 1
        for (int s = ST_WV; s < ST_O0; s++) {
          if (s == ST_SCR1) continue;
          mbar_wait(sb + SM_EMPTY + (s - 9) * 8);
          const uint32_t dst = sb + (s >= 18 ? s - 18 : s - 9) * SLOT, bar = sb + SM_FULL + s * 8;
          if (s < ST_WO) tma2d(dst, &maps.w, (s < ST_WQ ? 1024 : 0) + hg * 64, (s < ST_WQ ? s - ST_WV : s - ST_WQ) * 192, bar);
          else { mbar_wait(bar - 8); tma2d(dst, &maps.wo, hg * 64, (s - ST_WO) * 192, bar); }
        }
        const int jc = jf == 7 ? 0 : jf;
        int slot = 5 + rank;
#pragma unroll 1
        for (int s = ST_GU + rank; s < NSTAGE; s += 2) {
          mbar_wait(sb + SM_EMPTY + (s < ST_GU + 6 ? s - 12 : s - 9) * 8);
          if (s > ST_GU && s < ST_GU + THR) mbar_wait(sb + SM_FULL + (s - 1) * 8);
          const uint32_t dst = sb + slot * SLOT, bar = sb + SM_FULL + s * 8;
          if (s < ST_D) {
            const int c = (s - ST_GU) >> 1;
#pragma unroll
            for (int b = 0; b < 3; b++) tma3d_mc(dst + b * 8192, mgu, b * 64, jc, c * 64, bar);
          } else {
            tma2d_mc(dst, &maps.d, ((jf + 1 + (s - ST_D)) & 7) * 64, jf * 176, bar);
          }
          slot += 2; if (slot >= NSLOT) slot -= NSLOT;
        }
      }
      __syncwarp();
    } else {
      asm volatile("barrier.cluster.wait.aligned;" ::: "memory");
      if (warp == 11) {
#pragma unroll
        for (int i = 0; i < 4; i++)
          reinterpret_cast<uint4*>(smem + SM_ONES)[lane + 32 * i] = make_uint4(0x3F803F80u, 0x3F803F80u, 0x3F803F80u, 0x3F803F80u);
        fence_async_smem();
        __syncwarp();
        if (lane == 0) { mbar_arrive(sb + SM_MISCB); TS2(0, 19); }
      }
      mbar_wait(sb + SM_MISCB);
      const unsigned epoch = *reinterpret_cast<volatile unsigned*>(smem + SM_EPOCH);
      const uint32_t T = (epoch & 1) ^ 1;
      if (warp == 11) {
        reinterpret_cast<float4*>(&g_kv[T][blockIdx.x * 128])[lane] = make_float4(0.f, 0.f, 0.f, 0.f);
        if (lane < 8) g_z[T][blockIdx.x * 8 + lane] = 0.f;
        mbar_wait(sb + SM_FULL + (ST_WK + 2) * 8);
        if (lane == 0) {
          asm volatile("cp.async.bulk.prefetch.L2.global [%0], 4096;" ::"l"((const char*)wo + blockIdx.x * 4096) : "memory");
          asm volatile("cp.async.bulk.prefetch.L2.global [%0], 11008;" ::"l"((const char*)wg_ + blockIdx.x * 11008) : "memory");
          asm volatile("cp.async.bulk.prefetch.L2.global [%0], 11008;" ::"l"((const char*)wu_ + blockIdx.x * 11008) : "memory");
          asm volatile("cp.async.bulk.prefetch.L2.global [%0], 11008;" ::"l"((const char*)wd_ + blockIdx.x * 11008) : "memory");
          const unsigned target = (epoch + 1) * 32;
          unsigned v; int it = 0;
#pragma unroll 1
          do {
            asm volatile("ld.acquire.gpu.global.u32 %0, [%1];" : "=r"(v) : "l"(&g_kvcnt[hg * 32]) : "memory");
            if (++it > (1 << 18)) break;
          } while ((int)(v - target) < 0);
          TS2(0, 26);
        }
        __syncwarp();
        {
          const char* src = reinterpret_cast<const char*>(&g_kv[T ^ 1][hg * 2048]) + lane * 16;
#pragma unroll
          for (int i = 0; i < 16; i++)
            asm volatile("cp.async.cg.shared.global [%0], [%1], 16;" ::"r"(sb + SM_KV32 + lane * 16 + i * 512), "l"(src + i * 512) : "memory");
          asm volatile("cp.async.cg.shared.global [%0], [%1], 16;" ::"r"(sb + SM_ONES + lane * 16), "l"(&g_z[T ^ 1][hg * 128 + lane * 4]) : "memory");
          asm volatile("cp.async.mbarrier.arrive.noinc.shared::cta.b64 [%0];" ::"r"(sb + SM_KVB) : "memory");
        }
      } else {
        const int w = warp - 9;
        st_rlx4(reinterpret_cast<uint4*>(&g_st[2 * rb + w][hg][0]) + lane, T ^ 1, T ^ 1, T ^ 1, T ^ 1);
        if (lane < 8) st_rlx4(&g_o[2 * rb + w][hg][lane >> 1][3][30 + (lane & 1)], T ^ 1, T ^ 1, T ^ 1, T ^ 1);
        st_rlx4(&g_part[2 * rb3 + w][lane >> 2][jf][lane & 3][3][30], T ^ 1, T ^ 1, T ^ 1, T ^ 1);
        st_rlx4(&g_part[2 * rb3 + w][lane >> 2][jf][lane & 3][3][31], T ^ 1, T ^ 1, T ^ 1, T ^ 1);
        bar_sync(6 + w, 160);
        if (lane == 0) {
          asm volatile("fence.acq_rel.gpu;" ::: "memory");
          TS2(w, 25);
          asm volatile("red.relaxed.gpu.global.add.u32 [%0], 1;" ::"l"(&g_kvcnt[hg * 32]) : "memory");
        }
        mbar_wait(sb + SM_KVB);
        const uint32_t* pw = reinterpret_cast<const uint32_t*>(&g_o[2 * rb + w][lane >> 2][lane & 3][3][31]);
        int it = 0;
#pragma unroll 1
        while (__any_sync(0xffffffffu, (ld_rlx1(pw) ^ T) & 1)) { if (++it > (1 << 18)) break; }
        if (lane == 0) {
          TS2(w, 27);
#pragma unroll 1
          for (int i = 0; i < 3; i++) {
            mbar_wait(sb + SM_EMPTY + (w ? ST_O0 + i : ST_O0 - 9 + i) * 8);
            bulk_g2s(sb + (2 + i) * SLOT, &g_o[2 * rb + w][3 * i][0][0][0], i < 2 ? 24576 : 16384, sb + SM_FULL + (ST_O0 + 3 * w + i) * 8);
          }
        }
        __syncwarp();
      }
    }
    asm volatile("barrier.cluster.arrive.relaxed.aligned;" ::: "memory");
    asm volatile("barrier.cluster.wait.aligned;" ::: "memory");
  } else {
    asm volatile("setmaxnreg.inc.sync.aligned.u32 240;");
    if (lane == 0) {
#pragma unroll 1
      for (int d = warp; d + 9 < NSTAGE; d += 8) {
        mbar_init(sb + SM_EMPTY + d * 8, st_empty_cnt(d));
        mbar_init(sb + SM_FULL + (d + 9) * 8, 1);
        mbar_expect_tx(sb + SM_FULL + (d + 9) * 8, st_bytes(d + 9));
      }
      asm volatile("fence.mbarrier_init.release.cluster;" ::: "memory");
    }
    __syncwarp();
    bar_sync(0, 352);
    asm volatile("barrier.cluster.arrive.relaxed.aligned;" ::: "memory");
    const int wg = warp >> 2, wq = warp & 3, g = lane >> 2, t = lane & 3;
    const bool lead = (tid & 127) == 0;
    const uint32_t db = ((sb & 0x3FFFF) >> 4) | (512u << 16);
    auto release = [&](int d) {
      const int s = st_next(d);
      if (s < NSTAGE) mbar_arrive_cluster(sb + SM_EMPTY + d * 8, s >= ST_GU ? (uint32_t)(s & 1) : rank);
    };
    const uint32_t lrow = (uint32_t)(wq * 16 + (lane & 7) + ((lane >> 3) & 1) * 8) * 128;
    const uint32_t lx = lane & 7, lhi = lane >> 4;
    if (wg == 1) bar_arrive(4, 256);
    TSTAMP(0);

    float r0, r1;
    uint32_t E[4][8];
    uint32_t T = 0;
    {
      uint32_t A[32][4];
      const int sx = wg ? ST_X1 : ST_X0;
      {
        const uint32_t base = sb + sx * SLOT + lrow;
        float s0 = 0.f, s1 = 0.f;
#pragma unroll
        for (int c = 0; c < 8; c++) {
          if (c % 3 == 0) mbar_wait(sb + SM_FULL + (sx + c / 3) * 8);
#pragma unroll
          for (int k = 0; k < 4; k++) ldsm4(A[4 * c + k], base + c * 8192 + (((2 * k + lhi) ^ lx) << 4));
          const uint32_t u0 = hadd2(hadd2(hadd2(A[4 * c][0], A[4 * c][2]), hadd2(A[4 * c + 1][0], A[4 * c + 1][2])),
                                    hadd2(hadd2(A[4 * c + 2][0], A[4 * c + 2][2]), hadd2(A[4 * c + 3][0], A[4 * c + 3][2])));
          const uint32_t u1 = hadd2(hadd2(hadd2(A[4 * c][1], A[4 * c][3]), hadd2(A[4 * c + 1][1], A[4 * c + 1][3])),
                                    hadd2(hadd2(A[4 * c + 2][1], A[4 * c + 2][3]), hadd2(A[4 * c + 3][1], A[4 * c + 3][3])));
          s0 += blo(u0) + bhi(u0); s1 += blo(u1) + bhi(u1);
        }
        s0 += __shfl_xor_sync(0xffffffffu, s0, 1); s1 += __shfl_xor_sync(0xffffffffu, s1, 1);
        s0 += __shfl_xor_sync(0xffffffffu, s0, 2); s1 += __shfl_xor_sync(0xffffffffu, s1, 2);
        TSTAMP(17);
        asm volatile("barrier.cluster.wait.aligned;" ::: "memory");
        if (lane < 3) release(sx + lane);
        s0 *= (1.f / 512.f); s1 *= (1.f / 512.f);
        const uint32_t m0 = pack2(s0, s0), m1 = pack2(s1, s1);
        float q0 = 0.f, q1 = 0.f;
#pragma unroll
        for (int ks = 0; ks < 32; ks += 2) {
          uint32_t v0, v1;
          A[ks][0] = hsub2(A[ks][0], m0); A[ks][1] = hsub2(A[ks][1], m1);
          A[ks][2] = hsub2(A[ks][2], m0); A[ks][3] = hsub2(A[ks][3], m1);
          A[ks + 1][0] = hsub2(A[ks + 1][0], m0); A[ks + 1][1] = hsub2(A[ks + 1][1], m1);
          A[ks + 1][2] = hsub2(A[ks + 1][2], m0); A[ks + 1][3] = hsub2(A[ks + 1][3], m1);
          v0 = hfma2(A[ks][2], A[ks][2], hmul2(A[ks][0], A[ks][0]));
          v1 = hfma2(A[ks][3], A[ks][3], hmul2(A[ks][1], A[ks][1]));
          v0 = hfma2(A[ks + 1][2], A[ks + 1][2], hfma2(A[ks + 1][0], A[ks + 1][0], v0));
          v1 = hfma2(A[ks + 1][3], A[ks + 1][3], hfma2(A[ks + 1][1], A[ks + 1][1], v1));
          q0 += blo(v0) + bhi(v0); q1 += blo(v1) + bhi(v1);
        }
        q0 += __shfl_xor_sync(0xffffffffu, q0, 1); q1 += __shfl_xor_sync(0xffffffffu, q1, 1);
        q0 += __shfl_xor_sync(0xffffffffu, q0, 2); q1 += __shfl_xor_sync(0xffffffffu, q1, 2);
        s0 -= blo(m0); s1 -= blo(m1);
        r0 = rsqrtf(fmaxf(q0 * (1.f / 512.f) - s0 * s0, 0.f) + 1e-5f);
        r1 = rsqrtf(fmaxf(q1 * (1.f / 512.f) - s1 * s1, 0.f) + 1e-5f);
      }
      TSTAMP(1);

      const uint32_t scr = sb + (wg ? (ST_SCR1 % NSLOT) : (ST_SCR0 % NSLOT)) * SLOT;
#pragma unroll 1
      for (int ps = 0; ps < 3; ps++) {
        const int st0 = ps == 0 ? ST_WK : (ps == 1 ? ST_WV : ST_WQ);
        const uint32_t wdesc = DESC((ps == 0 ? ST_WK % NSLOT : (ps == 1 ? ST_WV % NSLOT : ST_WQ % NSLOT)) * SLOT);
        float acc[32];
        bar_sync(4 + wg, 256);
#pragma unroll
        for (int i = 0; i < 3; i++) {
          mbar_wait(sb + SM_FULL + (st0 + i) * 8);
          wg_fence();
#pragma unroll
          for (int kk = 0; kk < (i < 2 ? 12 : 8); kk++)
            wgmma_rs_n64(acc, A[12 * i + kk], wdesc + ((i * SLOT + kk * 2048) >> 4), (i | kk) != 0);
          wg_commit();
          if (i > 0) { wg_wait<1>(); if (lead) release(st0 + i - 1); }
        }
        if (ps == 0 || wg == 0) bar_arrive(4 + (wg ^ 1), 256);
        wg_wait<0>();
        if (lead) release(st0 + 2);
        TSTAMP(2 + 2 * ps);
        uint32_t a[4][4];
#pragma unroll
        for (int h = 0; h < 4; h++) {
          a[h][0] = pack2(acc[8 * h + 0] * r0, acc[8 * h + 1] * r0); a[h][1] = pack2(acc[8 * h + 2] * r1, acc[8 * h + 3] * r1);
          a[h][2] = pack2(acc[8 * h + 4] * r0, acc[8 * h + 5] * r0); a[h][3] = pack2(acc[8 * h + 6] * r1, acc[8 * h + 7] * r1);
        }
        if (ps != 1) {
          if (ps == 0) {
            mbar_wait(sb + SM_MISCB);
            T = (*reinterpret_cast<volatile unsigned*>(smem + SM_EPOCH) & 1) ^ 1;
            mbar_wait(sb + SM_EMPTY + (wg ? ST_SCR1 - NSLOT : ST_SCR0 - NSLOT) * 8);
          }
          float pp[4][2][4];
#pragma unroll
          for (int h = 0; h < 4; h++) {
            uint32_t b[4];
            ldsm4t(b, sb + SM_WPHI + h * 512 + ((lane & 7) + ((lane >> 3) & 1) * 8) * 32 + lhi * 16);
#pragma unroll
            for (int i = 0; i < 4; i++) { pp[h][0][i] = 0.f; pp[h][1][i] = 0.f; }
            mma16816(pp[h][0], a[h], b[0], b[1]);
            mma16816(pp[h][1], a[h], b[2], b[3]);
          }
          float e[4][16];
#pragma unroll
          for (int h = 0; h < 4; h++) feat_exp(pp[h][0], pp[h][1], e[h]);
          if (ps == 0) {
#pragma unroll
            for (int h = 0; h < 4; h++) {
              const float (&f)[16] = e[h];
              float sp0 = (f[0] + f[1]) + (f[4] + f[5]), sp1 = (f[2] + f[3]) + (f[6] + f[7]);
              float sn0 = (f[8] + f[9]) + (f[12] + f[13]), sn1 = (f[10] + f[11]) + (f[14] + f[15]);
              sp0 += __shfl_xor_sync(0xffffffffu, sp0, 1); sp1 += __shfl_xor_sync(0xffffffffu, sp1, 1);
              sn0 += __shfl_xor_sync(0xffffffffu, sn0, 1); sn1 += __shfl_xor_sync(0xffffffffu, sn1, 1);
              sp0 += __shfl_xor_sync(0xffffffffu, sp0, 2); sp1 += __shfl_xor_sync(0xffffffffu, sp1, 2);
              sn0 += __shfl_xor_sync(0xffffffffu, sn0, 2); sn1 += __shfl_xor_sync(0xffffffffu, sn1, 2);
              sp0 = rcp(sp0); sp1 = rcp(sp1); sn0 = rcp(sn0); sn1 = rcp(sn1);
              const uint32_t dst = scr + (h >> 1) * 8192 + lrow;
              stsm4(dst + ((((h & 1) * 4 + lhi) ^ lx) << 4), pack2(f[0] * sp0, f[1] * sp0), pack2(f[2] * sp1, f[3] * sp1),
                    pack2(f[4] * sp0, f[5] * sp0), pack2(f[6] * sp1, f[7] * sp1));
              stsm4(dst + ((((h & 1) * 4 + 2 + lhi) ^ lx) << 4), pack2(f[8] * sn0, f[9] * sn0), pack2(f[10] * sn1, f[11] * sn1),
                    pack2(f[12] * sn0, f[13] * sn0), pack2(f[14] * sn1, f[15] * sn1));
            }
          } else {
#pragma unroll
            for (int h = 0; h < 4; h++)
#pragma unroll
              for (int i = 0; i < 8; i++) A[2 * h + (i >> 2)][i & 3] = pack2(e[h][2 * i], e[h][2 * i + 1]);
          }
        } else {
#pragma unroll
          for (int h = 0; h < 4; h++) stsm4(scr + 16384 + lrow + (((2 * h + lhi) ^ lx) << 4), a[h][0], a[h][1], a[h][2], a[h][3]);
          fence_async_smem();
          bar_sync(3, 256);
          float kv[36];
          wg_fence();
#pragma unroll
          for (int ks = 0; ks < 8; ks++) {
            const uint32_t sk = (ks < 4 ? (ST_SCR0 % NSLOT) : (ST_SCR1 % NSLOT)) * SLOT + (ks & 3) * 2048;
            const uint32_t dv = (DESC(sk + 16384) & 0xFFFFu) | (((SM_ONES - sk - 16384) >> 4) << 16);
            wgmma_ss_n72_t11(kv, DESC(sk) + wg * 512, dv, ks != 0);
          }
          wg_commit();
          if (wg == 1) bar_arrive(4, 256);
          wg_wait<0>();
          if (lead) { release(ST_SCR0); release(ST_SCR1); }
          const int hl = 2 * wg + (wq >> 1), f = (wq & 1) * 16 + g;
          float* kvp = &g_kv[T ^ 1][((hg * 4 + hl) * 32 + f) * 16 + 2 * t];
          float* zp = &g_z[T ^ 1][(hg * 4 + hl) * 32 + f];
          float c[8];
#pragma unroll
          for (int i = 0; i < 8; i++) c[i] = hl >= 2 ? (hl == 3 ? kv[24 + i] : kv[16 + i]) : (hl == 1 ? kv[8 + i] : kv[i]);
#pragma unroll
          for (int n = 0; n < 2; n++) {
            asm volatile("red.relaxed.gpu.global.add.v2.f32 [%0], {%1,%2};" ::"l"(kvp + n * 8), "f"(c[4 * n]), "f"(c[4 * n + 1]) : "memory");
            asm volatile("red.relaxed.gpu.global.add.v2.f32 [%0], {%1,%2};" ::"l"(kvp + n * 8 + 128), "f"(c[4 * n + 2]), "f"(c[4 * n + 3]) : "memory");
          }
          if (t < 2) asm volatile("red.relaxed.gpu.global.add.f32 [%0], %1;" ::"l"(zp + t * 8), "f"(t ? kv[34] : kv[32]) : "memory");
          bar_arrive(6 + wg, 160);
        }
        TSTAMP(3 + 2 * ps);
      }
#pragma unroll
      for (int i = 0; i < 32; i++) E[i >> 3][i & 7] = A[i >> 2][i & 3];
    }
    const int rh = 2 * rb + wg;
    mbar_wait(sb + SM_KVB);
    {
      const int r = tid & 127;
      const float4* src = reinterpret_cast<const float4*>(smem + SM_KV32) + r;
#pragma unroll
      for (int i = 0; i < 4; i++) {
        const float4 a = src[i * 128];
        *reinterpret_cast<uint2*>(smem + SM_KVS + (i * 32 + (r >> 2)) * 48 + (r & 3) * 8) = make_uint2(pack2(a.x, a.y), pack2(a.z, a.w));
      }
      const uint32_t zz = pack2(reinterpret_cast<const float*>(smem + SM_ONES)[r], 1.0f);
      *reinterpret_cast<uint4*>(smem + SM_KVS + r * 48 + 32) = make_uint4(zz, zz, zz, zz);
      bar_sync(1 + wg, 128);
    }
    TSTAMP(8);
    {
      uint4* op = &g_o[rh][hg][wq][0][lane];
#pragma unroll
      for (int h = 0; h < 4; h++) {
        uint32_t b0[4], b1[4], b2[4];
        const uint32_t kb = sb + SM_KVS + (h * 32 + lane) * 48;
        ldsm4t(b0, kb); ldsm4t(b1, kb + 16); ldsm4t(b2, kb + 32);
        const uint32_t ep[4] = {E[h][0], E[h][1], E[h][2], E[h][3]}, en[4] = {E[h][4], E[h][5], E[h][6], E[h][7]};
        float np0[4] = {0, 0, 0, 0}, np1[4] = {0, 0, 0, 0}, nn0[4] = {0, 0, 0, 0}, nn1[4] = {0, 0, 0, 0}, dp[4] = {0, 0, 0, 0}, dn[4] = {0, 0, 0, 0};
        mma16816(dp, ep, b2[0], b2[1]);  mma16816(dn, en, b2[2], b2[3]);
        mma16816(np0, ep, b0[0], b0[1]); mma16816(nn0, en, b0[2], b0[3]);
        mma16816(np1, ep, b1[0], b1[1]); mma16816(nn1, en, b1[2], b1[3]);
        const float i0 = rcp(fmaf(dp[0], dn[1], fmaf(dn[0], dp[1], 1e-6f * dp[1] * dn[1])));
        const float i1 = rcp(fmaf(dp[2], dn[3], fmaf(dn[2], dp[3], 1e-6f * dp[3] * dn[3])));
        const float cp0 = dn[1] * i0, cn0 = dp[1] * i0, cp1 = dn[3] * i1, cn1 = dp[3] * i1;
        st_rlx4(op + h * 32,
                tg(pack2(fmaf(np0[0], cp0, nn0[0] * cn0), fmaf(np0[1], cp0, nn0[1] * cn0)), T),
                pack2(fmaf(np0[2], cp1, nn0[2] * cn1), fmaf(np0[3], cp1, nn0[3] * cn1)),
                pack2(fmaf(np1[0], cp0, nn1[0] * cn0), fmaf(np1[1], cp0, nn1[1] * cn0)),
                pack2(fmaf(np1[2], cp1, nn1[2] * cn1), fmaf(np1[3], cp1, nn1[3] * cn1)));
      }
    }
    TSTAMP(9);

    {
      uint32_t xr[16];
      {
        const uint32_t* xp = reinterpret_cast<const uint32_t*>(x + (size_t)(rh * 64 + wq * 16 + g) * 512 + hg * 64 + 2 * t);
#pragma unroll
        for (int i = 0; i < 8; i++) { xr[2 * i] = __ldg(xp + 4 * i); xr[2 * i + 1] = __ldg(xp + 8 * 256 + 4 * i); }
      }
      uint32_t A[8][4][4];
      const uint4* op = &g_o[rh][0][wq][0][lane];
      const uint32_t ob = sb + 2 * SLOT + wq * 2048 + lane * 16;
      float acc[32];
#pragma unroll
      for (int p = 0; p < 3; p++) {
        mbar_wait(sb + SM_FULL + (ST_O0 + 3 * wg + p) * 8);
#pragma unroll
        for (int c = 3 * p; c < (p < 2 ? 3 * p + 3 : 8); c++)
#pragma unroll
          for (int s = 0; s < 4; s++)
            asm volatile("ld.shared.v4.b32 {%0,%1,%2,%3}, [%4];" : "=r"(A[c][s][0]), "=r"(A[c][s][1]), "=r"(A[c][s][2]), "=r"(A[c][s][3])
                         : "r"(ob + c * 8192 + s * 512) : "memory");
        __syncwarp();
        if (lane == 0) release(ST_O0 + 3 * wg + p);
        mbar_wait(sb + SM_FULL + (ST_WO + p) * 8);
#pragma unroll
        for (int c = 3 * p; c < (p < 2 ? 3 * p + 3 : 8); c++) {
          chk_chunk(A[c], op + c * 512, T);
          wg_fence();
#pragma unroll
          for (int s = 0; s < 4; s++)
            wgmma_rs_n64(acc, A[c][s], DESC(((ST_WO + p) % NSLOT) * SLOT + ((c % 3) * 4 + s) * 2048), (c | s) != 0);
          wg_commit();
        }
      }
      wg_wait<0>();
      if ((tid & 127) < 3) release(ST_WO + (tid & 127));
      TSTAMP(10);
      uint32_t hw[16];
      float s0 = 0.f, s1 = 0.f, q0 = 0.f, q1 = 0.f;
#pragma unroll
      for (int i = 0; i < 8; i++) {
        hw[2 * i]     = pack2(blo(xr[2 * i]) + acc[4 * i], bhi(xr[2 * i]) + acc[4 * i + 1]);
        hw[2 * i + 1] = pack2(blo(xr[2 * i + 1]) + acc[4 * i + 2], bhi(xr[2 * i + 1]) + acc[4 * i + 3]);
      }
      uint4* hp_ = &g_h[rh][hg][wq][0][lane];
#pragma unroll
      for (int s = 0; s < 4; s++) st_rlx4(hp_ + s * 32, tg(hw[4 * s], T), hw[4 * s + 1], hw[4 * s + 2], hw[4 * s + 3]);
#pragma unroll
      for (int i = 0; i < 8; i++) {
        float a = blo(hw[2 * i]), b = bhi(hw[2 * i]);
        s0 += a + b; q0 = fmaf(a, a, q0); q0 = fmaf(b, b, q0);
        a = blo(hw[2 * i + 1]); b = bhi(hw[2 * i + 1]);
        s1 += a + b; q1 = fmaf(a, a, q1); q1 = fmaf(b, b, q1);
      }
      s0 += __shfl_xor_sync(0xffffffffu, s0, 1); s1 += __shfl_xor_sync(0xffffffffu, s1, 1);
      q0 += __shfl_xor_sync(0xffffffffu, q0, 1); q1 += __shfl_xor_sync(0xffffffffu, q1, 1);
      s0 += __shfl_xor_sync(0xffffffffu, s0, 2); s1 += __shfl_xor_sync(0xffffffffu, s1, 2);
      q0 += __shfl_xor_sync(0xffffffffu, q0, 2); q1 += __shfl_xor_sync(0xffffffffu, q1, 2);
      if (t < 2) st_rlx2(&g_st[rh][hg][wq * 16 + g + t * 8], tg(__float_as_uint(t ? s1 : s0), T), __float_as_uint(t ? q1 : q0));
      uint32_t hx = T;
#pragma unroll
      for (int i = 0; i < 4; i++) hx |= (hw[4 * i] & 1u) << (i + 1);
      st_rlx1(&g_hx[rh][hg][wq][lane], hx);
    }
    TSTAMP(11);

    const int rh3 = 2 * rb3 + wg;
    uint32_t HH[11][4];
    {
      uint32_t A[2][4][4];
      const uint4* hp_ = &g_h[rh3][0][wq][0][lane];
      uint32_t m0, m1;
      {
        const uint2* sp = &g_st[rh3][2 * t][wq * 16 + g];
        uint32_t a[4], b[4];
        int it = 0;
#pragma unroll 1
        do {
          ld_rlx2(a[0], a[1], sp); ld_rlx2(a[2], a[3], sp + 64); ld_rlx2(b[0], b[1], sp + 8); ld_rlx2(b[2], b[3], sp + 72);
          if (++it > (1 << 18)) break;
        } while (__any_sync(0xffffffffu, bad4(a[0], a[2], b[0], b[2], T) & 1));
        ld_chunk(A[0], hp_);
        float s0 = __uint_as_float(a[0]) + __uint_as_float(a[2]), q0 = __uint_as_float(a[1]) + __uint_as_float(a[3]);
        float s1 = __uint_as_float(b[0]) + __uint_as_float(b[2]), q1 = __uint_as_float(b[1]) + __uint_as_float(b[3]);
        s0 += __shfl_xor_sync(0xffffffffu, s0, 1); s1 += __shfl_xor_sync(0xffffffffu, s1, 1);
        q0 += __shfl_xor_sync(0xffffffffu, q0, 1); q1 += __shfl_xor_sync(0xffffffffu, q1, 1);
        s0 += __shfl_xor_sync(0xffffffffu, s0, 2); s1 += __shfl_xor_sync(0xffffffffu, s1, 2);
        q0 += __shfl_xor_sync(0xffffffffu, q0, 2); q1 += __shfl_xor_sync(0xffffffffu, q1, 2);
        s0 *= (1.f / 512.f); s1 *= (1.f / 512.f);
        r0 = rcp(fmaxf(q0 * (1.f / 512.f) - s0 * s0, 0.f) + 1e-5f);
        r1 = rcp(fmaxf(q1 * (1.f / 512.f) - s1 * s1, 0.f) + 1e-5f);
        m0 = pack2(s0, s0); m1 = pack2(s1, s1);
      }
      TSTAMP(12);
      float ag[88], au[88];
      int slot = 5;
#pragma unroll 1
      for (int c2 = 0; c2 < 8; c2 += 2) {
#pragma unroll
        for (int b = 0; b < 2; b++) {
          const int c = c2 + b, sG = ST_GU + 2 * c;
          chk_chunk(A[b], hp_ + c * 512, T);
#pragma unroll
          for (int s = 0; s < 4; s++) {
            A[b][s][0] = hsub2(A[b][s][0], m0); A[b][s][1] = hsub2(A[b][s][1], m1);
            A[b][s][2] = hsub2(A[b][s][2], m0); A[b][s][3] = hsub2(A[b][s][3], m1);
          }
          mbar_wait(sb + SM_FULL + sG * 8);
          wg_fence();
#pragma unroll
          for (int s = 0; s < 4; s++)
            wgmma_rs_n176(ag, A[b][s], db + slot * (SLOT >> 4) + s * 128, (c | s) != 0);
          wg_commit();
          if (++slot == NSLOT) slot = 0;
          wg_wait<1>();
          if (lead && c > 0) release(sG - 1);
          if (c < 7) ld_chunk(A[b ^ 1], hp_ + (c + 1) * 512);
          mbar_wait(sb + SM_FULL + (sG + 1) * 8);
          wg_fence();
#pragma unroll
          for (int s = 0; s < 4; s++)
            wgmma_rs_n176(au, A[b][s], db + slot * (SLOT >> 4) + s * 128, (c | s) != 0);
          wg_commit();
          if (++slot == NSLOT) slot = 0;
          wg_wait<1>();
          if (lead) release(sG);
        }
      }
      wg_wait<0>();
      TSTAMP(13);
#pragma unroll
      for (int s = 0; s < 11; s++) {
        HH[s][0] = pack2(ag[8 * s + 0] * au[8 * s + 0] * r0, ag[8 * s + 1] * au[8 * s + 1] * r0);
        HH[s][1] = pack2(ag[8 * s + 2] * au[8 * s + 2] * r1, ag[8 * s + 3] * au[8 * s + 3] * r1);
        HH[s][2] = pack2(ag[8 * s + 4] * au[8 * s + 4] * r0, ag[8 * s + 5] * au[8 * s + 5] * r0);
        HH[s][3] = pack2(ag[8 * s + 6] * au[8 * s + 6] * r1, ag[8 * s + 7] * au[8 * s + 7] * r1);
      }
    }
    TSTAMP(14);

    {
      float acc[32], sum[32];
      uint32_t in[4][4][4];
      const uint4* inb = &g_part[rh3][jf][0][wq][0][lane];
      uint4* outb = &g_part[rh3][0][jf][wq][0][lane];
      const uint32_t* hint = reinterpret_cast<const uint32_t*>(&g_part[rh3][jf][(jf - 1 - lane) & 7][wq][3][31]);
      int slot = (5 + 16) % NSLOT;
      auto step = [&](int st) {
        uint32_t pk[16];
        if (st > 0) {
#pragma unroll
          for (int i = 0; i < 16; i++) pk[i] = pack2(acc[2 * i], acc[2 * i + 1]);
        }
        mbar_wait(sb + SM_FULL + (ST_D + st) * 8);
        wg_fence();
#pragma unroll
        for (int s = 0; s < 4; s++) wgmma_rs_n64(acc, HH[s], db + slot * (SLOT >> 4) + s * 128, s != 0);
        if (st > 0) {
          uint4* p = outb + ((jf + st) & 7) * 4096;
#pragma unroll
          for (int s = 0; s < 4; s++) st_rlx4(p + s * 32, tg(pk[4 * s], T), pk[4 * s + 1], pk[4 * s + 2], pk[4 * s + 3]);
        }
#pragma unroll
        for (int s = 4; s < 11; s++) wgmma_rs_n64(acc, HH[s], db + slot * (SLOT >> 4) + s * 128, 1);
        wg_commit();
        if (++slot == NSLOT) slot = 0;
      };
      auto fetch = [&](int q) { ld_chunk(in[q & 3], inb + ((jf - 1 - q) & 7) * 512); };
      auto add = [&](int q) {
        chk_chunk(in[q & 3], inb + ((jf - 1 - q) & 7) * 512, T);
#pragma unroll
        for (int i = 0; i < 16; i++) { sum[2 * i] += blo(in[q & 3][i >> 2][i & 3]); sum[2 * i + 1] += bhi(in[q & 3][i >> 2][i & 3]); }
      };
      uint32_t ready = 0; int it = 0;
      auto await = [&](int q) {
#pragma unroll 1
        while (!((ready >> q) & 1)) {
          ready = __ballot_sync(0xffffffffu, ((ld_rlx1(hint) ^ T) & 1) == 0);
          if (++it > (1 << 18)) break;
        }
      };
      ld_chunk(in[3], &g_h[rh3][jf][wq][0][lane]);
      uint32_t hx = ld_rlx1(&g_hx[rh3][jf][wq][lane]);
#pragma unroll 1
      for (int st = 0; st < 4; st++) { step(st); wg_wait<0>(); }
      step(4);
#pragma unroll 1
      while (__any_sync(0xffffffffu, (hx ^ T) & 1)) {
        hx = ld_rlx1(&g_hx[rh3][jf][wq][lane]);
        if (++it > (1 << 18)) break;
      }
#pragma unroll
      for (int s = 0; s < 4; s++) in[3][s][0] = (in[3][s][0] & 0xFFFFFFFEu) | ((hx >> (s + 1)) & 1u);
#pragma unroll
      for (int i = 0; i < 16; i++) { sum[2 * i] = blo(in[3][i >> 2][i & 3]); sum[2 * i + 1] = bhi(in[3][i >> 2][i & 3]); }
      fetch(0); wg_wait<0>();
      step(5); fetch(1); wg_wait<0>();
      step(6); fetch(2); add(0); wg_wait<0>();
      step(7); fetch(3); add(1);
      await(4); fetch(4); add(2);
      await(5); fetch(5); add(3);
      wg_wait<0>();
      TSTAMP(15);
#pragma unroll
      for (int i = 0; i < 32; i++) sum[i] += acc[i];
      await(6); fetch(6); add(4); add(5); add(6);
      uint32_t* op = reinterpret_cast<uint32_t*>(out + (size_t)(rh3 * 64 + wq * 16 + g) * 512 + jf * 64 + 2 * t);
#pragma unroll
      for (int i = 0; i < 8; i++) {
        op[4 * i]           = pack2(sum[4 * i], sum[4 * i + 1]);
        op[8 * 256 + 4 * i] = pack2(sum[4 * i + 2], sum[4 * i + 3]);
      }
    }
    TSTAMP(16);
    asm volatile("barrier.cluster.arrive.relaxed.aligned;" ::: "memory");
    asm volatile("barrier.cluster.wait.aligned;" ::: "memory");
  }
}

typedef CUresult (*EncodeFn)(CUtensorMap*, CUtensorMapDataType, cuuint32_t, void*, const cuuint64_t*, const cuuint64_t*,
                             const cuuint32_t*, const cuuint32_t*, CUtensorMapInterleave, CUtensorMapSwizzle,
                             CUtensorMapL2promotion, CUtensorMapFloatOOBfill);

void encode(EncodeFn fn, CUtensorMap* m, const void* base, int rank, const cuuint64_t* dims, const cuuint64_t* strides,
            const cuuint32_t* box) {
  cuuint32_t es[3] = {1, 1, 1};
  fn(m, CU_TENSOR_MAP_DATA_TYPE_BFLOAT16, (cuuint32_t)rank, const_cast<void*>(base), dims, strides, box, es,
     CU_TENSOR_MAP_INTERLEAVE_NONE, CU_TENSOR_MAP_SWIZZLE_128B, CU_TENSOR_MAP_L2_PROMOTION_L2_256B,
     CU_TENSOR_MAP_FLOAT_OOB_FILL_NONE);
}

}

extern "C" void kernel_launch(void* const* d_in, const int* in_sizes, int n_in, void* d_out, int out_size) {
  (void)in_sizes; (void)n_in; (void)out_size;
  const __nv_bfloat16* x    = (const __nv_bfloat16*)d_in[0];
  const __nv_bfloat16* wqkv = (const __nv_bfloat16*)d_in[1];
  const __nv_bfloat16* wphi = (const __nv_bfloat16*)d_in[2];
  const __nv_bfloat16* wo   = (const __nv_bfloat16*)d_in[3];
  const __nv_bfloat16* wg   = (const __nv_bfloat16*)d_in[5];
  const __nv_bfloat16* wu   = (const __nv_bfloat16*)d_in[6];
  const __nv_bfloat16* wd   = (const __nv_bfloat16*)d_in[7];

  static EncodeFn fn = nullptr;
  if (!fn) {
    void* p = nullptr;
    cudaDriverEntryPointQueryResult qr;
    cudaGetDriverEntryPoint("cuTensorMapEncodeTiled", &p, cudaEnableDefault, &qr);
    fn = (EncodeFn)p;
    cudaFuncSetAttribute(fused_kernel, cudaFuncAttributeMaxDynamicSharedMemorySize, SM_TOTAL);
  }
  Maps maps;
  {
    cuuint64_t d[3] = {64, 2048, 8}, s[2] = {1024, 128}; cuuint32_t b[3] = {64, 64, 3};
    encode(fn, &maps.x, x, 3, d, s, b);
  }
  {
    cuuint64_t d[2] = {1536, 512}, s[1] = {3072}; cuuint32_t b[2] = {64, 192};
    encode(fn, &maps.w, wqkv, 2, d, s, b);
  }
  {
    cuuint64_t d[2] = {512, 512}, s[1] = {1024}; cuuint32_t b[2] = {64, 192};
    encode(fn, &maps.wo, wo, 2, d, s, b);
  }
  {
    cuuint64_t d[3] = {176, 7, 512}, d7[3] = {144, 1, 512}, s[2] = {352, 2752}; cuuint32_t b[3] = {64, 1, 64};
    encode(fn, &maps.g, wg, 3, d, s, b);
    encode(fn, &maps.u, wu, 3, d, s, b);
    encode(fn, &maps.g7, wg + 1232, 3, d7, s, b);
    encode(fn, &maps.u7, wu + 1232, 3, d7, s, b);
  }
  {
    cuuint64_t d[2] = {512, 1376}, s[1] = {1024}; cuuint32_t b[2] = {64, 176};
    encode(fn, &maps.d, wd, 2, d, s, b);
  }
  fused_kernel<<<NCTA, 384, SM_TOTAL>>>(maps, x, wphi, wo, wg, wu, wd, (__nv_bfloat16*)d_out);
}
```

```cpp
#include <cuda_runtime.h>
#include <cuda_bf16.h>
#include <cuda.h>
#include <stdint.h>

#define PROF 0

#define THR 3

namespace {

constexpr int NCTA   = 128;
constexpr int SLOT   = 24576;
constexpr int NSLOT  = 9;
constexpr int NSTAGE = 50;

constexpr int ST_X0   = 0;
constexpr int ST_WK   = 3;
constexpr int ST_X1   = 6;
constexpr int ST_SCR0 = 9;
constexpr int ST_WV   = 10;
constexpr int ST_SCR1 = 13;
constexpr int ST_WQ   = 14;
constexpr int ST_WO   = 17;
constexpr int ST_O0   = 20;
constexpr int ST_O1   = 23;
constexpr int ST_GU   = 26;
constexpr int ST_D    = 42;

__host__ __device__ constexpr int st_next(int d) { return d < ST_WQ ? d + 9 : d < ST_O0 ? d + 12 : d < ST_O1 ? d + 3 : d + 9; }
__host__ __device__ constexpr int st_bytes(int s) { return s >= ST_D ? 22528 : (s == ST_O0 + 2 || s == ST_O1 + 2) ? 16384 : 24576; }
__host__ __device__ constexpr int st_empty_cnt(int d) {
  return ((d < 3 || (d >= 6 && d < 9) || (d >= ST_O0 && d < ST_GU)) ? 4 : 0 ? 1 : 2) *
         (st_next(d) >= ST_GU ? 2 : 1);
}

constexpr int SM_ONES = NSLOT * SLOT;
constexpr int SM_WPHI = SM_ONES + 2048;
constexpr int SM_KVS  = SM_WPHI + 2048;
constexpr int SM_KV32 = 4 * SLOT + 16384;
constexpr int SM_BAR  = SM_KVS + 6144;
constexpr int SM_FULL  = SM_BAR;
constexpr int SM_EMPTY = SM_BAR + NSTAGE * 8;
constexpr int SM_MISCB = SM_BAR + 2 * NSTAGE * 8;
constexpr int SM_KVB   = SM_MISCB + 8;
constexpr int SM_EPOCH = SM_KVB + 8;
constexpr int SM_TOTAL = SM_BAR + 1024;

static_assert(SM_TOTAL == 232448, "smem budget");

struct Maps { CUtensorMap x, w, wo, g, u, g7, u7, d; };

__device__ uint4    g_o[32][8][4][4][32];
__device__ uint4    g_h[32][8][4][4][32];
__device__ uint32_t g_hx[32][8][4][32];
__device__ uint2    g_st[32][8][64];
__device__ uint4    g_part[32][8][8][4][4][32];
__device__ float    g_kv[2][32 * 32 * 16];
__device__ float    g_z[2][32 * 32];
__device__ unsigned g_kvcnt[8 * 32];
__device__ unsigned g_start;

__device__ __forceinline__ uint32_t smem_u32(const void* p) { return (uint32_t)__cvta_generic_to_shared(p); }
__device__ __forceinline__ void mbar_init(uint32_t bar, int cnt) {
  asm volatile("mbarrier.init.shared::cta.b64 [%0], %1;" ::"r"(bar), "r"(cnt) : "memory");
}
__device__ __forceinline__ void mbar_expect_tx(uint32_t bar, uint32_t bytes) {
  asm volatile("mbarrier.arrive.expect_tx.shared::cta.b64 _, [%0], %1;" ::"r"(bar), "r"(bytes) : "memory");
}
__device__ __forceinline__ void mbar_arrive(uint32_t bar) {
  asm volatile("mbarrier.arrive.shared::cta.b64 _, [%0];" ::"r"(bar) : "memory");
}
__device__ __forceinline__ void mbar_arrive_cluster(uint32_t bar, uint32_t rank) {
  asm volatile("{\n.reg .b32 ra;\nmapa.shared::cluster.u32 ra, %0, %1;\n"
               "mbarrier.arrive.shared::cluster.b64 _, [ra];\n}" ::"r"(bar), "r"(rank) : "memory");
}
__device__ __forceinline__ bool mbar_try(uint32_t bar) {
  uint32_t ok;
  asm volatile("{\n.reg .pred p;\nmbarrier.try_wait.parity.shared::cta.b64 p, [%1], 0;\nselp.u32 %0, 1, 0, p;\n}"
               : "=r"(ok) : "r"(bar) : "memory");
  return ok != 0;
}
__device__ __forceinline__ void mbar_wait(uint32_t bar) {
  int it = 0;
#pragma unroll 1
  while (!mbar_try(bar)) {
    if (++it > (1 << 20)) __trap();
  }
}
__device__ __forceinline__ void bar_sync(int id, int n)   { asm volatile("bar.sync %0, %1;" ::"r"(id), "r"(n) : "memory"); }
__device__ __forceinline__ void bar_arrive(int id, int n) { asm volatile("bar.arrive %0, %1;" ::"r"(id), "r"(n) : "memory"); }
__device__ __forceinline__ void fence_async_smem() { asm volatile("fence.proxy.async.shared::cta;" ::: "memory"); }
__device__ __forceinline__ void wg_fence()  { asm volatile("wgmma.fence.sync.aligned;" ::: "memory"); }
__device__ __forceinline__ void wg_commit() { asm volatile("wgmma.commit_group.sync.aligned;" ::: "memory"); }
template <int N> __device__ __forceinline__ void wg_wait() { asm volatile("wgmma.wait_group.sync.aligned %0;" ::"n"(N) : "memory"); }
#define DESC(off) (db + ((uint32_t)(off) >> 4))
__device__ __forceinline__ void tma2d(uint32_t dst, const CUtensorMap* m, int c0, int c1, uint32_t bar) {
  asm volatile("cp.async.bulk.tensor.2d.shared::cluster.global.mbarrier::complete_tx::bytes [%0], [%1, {%3, %4}], [%2];"
               ::"r"(dst), "l"(m), "r"(bar), "r"(c0), "r"(c1) : "memory");
}
__device__ __forceinline__ void tma2d_mc(uint32_t dst, const CUtensorMap* m, int c0, int c1, uint32_t bar) {
  asm volatile("cp.async.bulk.tensor.2d.shared::cluster.global.mbarrier::complete_tx::bytes.multicast::cluster [%0], [%1, {%3, %4}], [%2], %5;"
               ::"r"(dst), "l"(m), "r"(bar), "r"(c0), "r"(c1), "h"((uint16_t)3) : "memory");
}
__device__ __forceinline__ void tma3d(uint32_t dst, const CUtensorMap* m, int c0, int c1, int c2, uint32_t bar) {
  asm volatile("cp.async.bulk.tensor.3d.shared::cluster.global.mbarrier::complete_tx::bytes [%0], [%1, {%3, %4, %5}], [%2];"
               ::"r"(dst), "l"(m), "r"(bar), "r"(c0), "r"(c1), "r"(c2) : "memory");
}
__device__ __forceinline__ void tma3d_mc(uint32_t dst, const CUtensorMap* m, int c0, int c1, int c2, uint32_t bar) {
  asm volatile("cp.async.bulk.tensor.3d.shared::cluster.global.mbarrier::complete_tx::bytes.multicast::cluster [%0], [%1, {%3, %4, %5}], [%2], %6;"
               ::"r"(dst), "l"(m), "r"(bar), "r"(c0), "r"(c1), "r"(c2), "h"((uint16_t)3) : "memory");
}
__device__ __forceinline__ void ldsm4(uint32_t (&r)[4], uint32_t addr) {
  asm volatile("ldmatrix.sync.aligned.m8n8.x4.shared.b16 {%0,%1,%2,%3}, [%4];"
               : "=r"(r[0]), "=r"(r[1]), "=r"(r[2]), "=r"(r[3]) : "r"(addr) : "memory");
}
__device__ __forceinline__ void ldsm4t(uint32_t (&r)[4], uint32_t addr) {
  asm volatile("ldmatrix.sync.aligned.m8n8.x4.trans.shared.b16 {%0,%1,%2,%3}, [%4];"
               : "=r"(r[0]), "=r"(r[1]), "=r"(r[2]), "=r"(r[3]) : "r"(addr) : "memory");
}
__device__ __forceinline__ void stsm4(uint32_t addr, uint32_t r0, uint32_t r1, uint32_t r2, uint32_t r3) {
  asm volatile("stmatrix.sync.aligned.m8n8.x4.shared.b16 [%0], {%1,%2,%3,%4};"
               ::"r"(addr), "r"(r0), "r"(r1), "r"(r2), "r"(r3) : "memory");
}
__device__ __forceinline__ void mma16816(float (&c)[4], const uint32_t (&a)[4], uint32_t b0, uint32_t b1) {
  asm volatile("mma.sync.aligned.m16n8k16.row.col.f32.bf16.bf16.f32 {%0,%1,%2,%3},{%4,%5,%6,%7},{%8,%9},{%0,%1,%2,%3};"
               : "+f"(c[0]), "+f"(c[1]), "+f"(c[2]), "+f"(c[3])
               : "r"(a[0]), "r"(a[1]), "r"(a[2]), "r"(a[3]), "r"(b0), "r"(b1));
}
__device__ __forceinline__ uint32_t pack2(float lo, float hi) {
  uint32_t r; asm("cvt.rn.bf16x2.f32 %0, %1, %2;" : "=r"(r) : "f"(hi), "f"(lo)); return r;
}
__device__ __forceinline__ float blo(uint32_t w) { return __uint_as_float(w << 16); }
__device__ __forceinline__ float bhi(uint32_t w) { return __uint_as_float(w & 0xFFFF0000u); }
__device__ __forceinline__ uint32_t hsub2(uint32_t a, uint32_t b) { uint32_t r; asm("sub.rn.bf16x2 %0, %1, %2;" : "=r"(r) : "r"(a), "r"(b)); return r; }
__device__ __forceinline__ uint32_t hadd2(uint32_t a, uint32_t b) { uint32_t r; asm("add.rn.bf16x2 %0, %1, %2;" : "=r"(r) : "r"(a), "r"(b)); return r; }
__device__ __forceinline__ uint32_t hmul2(uint32_t a, uint32_t b) { uint32_t r; asm("mul.rn.bf16x2 %0, %1, %2;" : "=r"(r) : "r"(a), "r"(b)); return r; }
__device__ __forceinline__ uint32_t hfma2(uint32_t a, uint32_t b, uint32_t c) { uint32_t r; asm("fma.rn.bf16x2 %0, %1, %2, %3;" : "=r"(r) : "r"(a), "r"(b), "r"(c)); return r; }
__device__ __forceinline__ uint32_t hmax2(uint32_t a, uint32_t b) { uint32_t r; asm("max.bf16x2 %0, %1, %2;" : "=r"(r) : "r"(a), "r"(b)); return r; }
__device__ __forceinline__ uint32_t hmin2(uint32_t a, uint32_t b) { uint32_t r; asm("min.bf16x2 %0, %1, %2;" : "=r"(r) : "r"(a), "r"(b)); return r; }
__device__ __forceinline__ float ex2(float x) { float r; asm("ex2.approx.ftz.f32 %0, %1;" : "=f"(r) : "f"(x)); return r; }
__device__ __forceinline__ float rcp(float x) { float r; asm("rcp.approx.ftz.f32 %0, %1;" : "=f"(r) : "f"(x)); return r; }
__device__ __forceinline__ void ld_rlx4(uint32_t (&r)[4], const uint4* p) {
  asm volatile("{\n.reg .b128 v;\nld.relaxed.gpu.global.b128 v, [%4];\nmov.b128 {%0,%1,%2,%3}, v;\n}"
               : "=r"(r[0]), "=r"(r[1]), "=r"(r[2]), "=r"(r[3]) : "l"(p) : "memory");
}
__device__ __forceinline__ void st_rlx4(uint4* p, uint32_t a, uint32_t b, uint32_t c, uint32_t d) {
  asm volatile("{\n.reg .b128 v;\nmov.b128 v, {%1,%2,%3,%4};\nst.relaxed.gpu.global.b128 [%0], v;\n}"
               ::"l"(p), "r"(a), "r"(b), "r"(c), "r"(d) : "memory");
}
__device__ __forceinline__ void st_rlx2(uint2* p, uint32_t a, uint32_t b) {
  asm volatile("{\n.reg .b64 v;\nmov.b64 v, {%1,%2};\nst.relaxed.gpu.global.b64 [%0], v;\n}" ::"l"(p), "r"(a), "r"(b) : "memory");
}
__device__ __forceinline__ uint32_t ld_rlx1(const uint32_t* p) {
  uint32_t r; asm volatile("ld.relaxed.gpu.global.b32 %0, [%1];" : "=r"(r) : "l"(p) : "memory"); return r;
}
__device__ __forceinline__ void st_rlx1(uint32_t* p, uint32_t a) {
  asm volatile("st.relaxed.gpu.global.b32 [%0], %1;" ::"l"(p), "r"(a) : "memory");
}
__device__ __forceinline__ void ld_rlx2(uint32_t& a, uint32_t& b, const uint2* p) {
  asm volatile("{\n.reg .b64 v;\nld.relaxed.gpu.global.b64 v, [%2];\nmov.b64 {%0,%1}, v;\n}" : "=r"(a), "=r"(b) : "l"(p) : "memory");
}
__device__ __forceinline__ void bulk_g2s(uint32_t dst, const void* src, uint32_t bytes, uint32_t bar) {
  asm volatile("cp.async.bulk.shared::cluster.global.mbarrier::complete_tx::bytes [%0], [%1], %2, [%3];"
               ::"r"(dst), "l"(src), "r"(bytes), "r"(bar) : "memory");
}
__device__ __forceinline__ uint32_t tg(uint32_t w, uint32_t T) { return (w & 0xFFFFFFFEu) | T; }
__device__ __forceinline__ uint32_t bad4(uint32_t a, uint32_t b, uint32_t c, uint32_t d, uint32_t T) {
  uint32_t u, v;
  asm("lop3.b32 %0, %1, %2, %3, 0x7E;" : "=r"(u) : "r"(a), "r"(b), "r"(T));
  asm("lop3.b32 %0, %1, %2, %3, 0x7E;" : "=r"(v) : "r"(c), "r"(d), "r"(T));
  return u | v;
}

__device__ __forceinline__ void ld_chunk(uint32_t (&a)[4][4], const uint4* p) {
#pragma unroll
  for (int s = 0; s < 4; s++) ld_rlx4(a[s], p + s * 32);
}
__device__ __forceinline__ void chk_chunk(uint32_t (&a)[4][4], const uint4* p, uint32_t T) {
  int it = 0;
#pragma unroll 1
  while (__any_sync(0xffffffffu, bad4(a[0][0], a[1][0], a[2][0], a[3][0], T) & 1)) {
    ld_chunk(a, p);
    if (++it > (1 << 18)) break;
  }
}

__device__ __forceinline__ void wgmma_rs_n64(float (&d)[32], const uint32_t (&a)[4], uint32_t descB, int scaleD) {
  asm volatile("{\n.reg .pred p;\n.reg .b64 db;\nsetp.ne.b32 p, %37, 0;\nmov.b64 db, {%36, 0x40000040};\n"
    "wgmma.mma_async.sync.aligned.m64n64k16.f32.bf16.bf16 {%0,%1,%2,%3,%4,%5,%6,%7,%8,%9,%10,%11,%12,%13,%14,%15,%16,%17,%18,%19,%20,%21,%22,%23,%24,%25,%26,%27,%28,%29,%30,%31}, {%32,%33,%34,%35}, db, p, 1, 1, 1;\n}\n"
    : "+f"(d[0]),"+f"(d[1]),"+f"(d[2]),"+f"(d[3]),"+f"(d[4]),"+f"(d[5]),"+f"(d[6]),"+f"(d[7]),"+f"(d[8]),"+f"(d[9]),"+f"(d[10]),"+f"(d[11]),"+f"(d[12]),"+f"(d[13]),"+f"(d[14]),"+f"(d[15]),"+f"(d[16]),"+f"(d[17]),"+f"(d[18]),"+f"(d[19]),"+f"(d[20]),"+f"(d[21]),"+f"(d[22]),"+f"(d[23]),"+f"(d[24]),"+f"(d[25]),"+f"(d[26]),"+f"(d[27]),"+f"(d[28]),"+f"(d[29]),"+f"(d[30]),"+f"(d[31])
    : "r"(a[0]), "r"(a[1]), "r"(a[2]), "r"(a[3]), "r"(descB), "r"(scaleD));
}
__device__ __forceinline__ void wgmma_rs_n176(float (&d)[88], const uint32_t (&a)[4], uint32_t descB, int scaleD) {
  asm volatile("{\n.reg .pred p;\n.reg .b64 db;\nsetp.ne.b32 p, %93, 0;\nmov.b64 db, {%92, 0x40000040};\n"
    "wgmma.mma_async.sync.aligned.m64n176k16.f32.bf16.bf16 {%0,%1,%2,%3,%4,%5,%6,%7,%8,%9,%10,%11,%12,%13,%14,%15,%16,%17,%18,%19,%20,%21,%22,%23,%24,%25,%26,%27,%28,%29,%30,%31,%32,%33,%34,%35,%36,%37,%38,%39,%40,%41,%42,%43,%44,%45,%46,%47,%48,%49,%50,%51,%52,%53,%54,%55,%56,%57,%58,%59,%60,%61,%62,%63,%64,%65,%66,%67,%68,%69,%70,%71,%72,%73,%74,%75,%76,%77,%78,%79,%80,%81,%82,%83,%84,%85,%86,%87}, {%88,%89,%90,%91}, db, p, 1, 1, 1;\n}\n"
    : "+f"(d[0]),"+f"(d[1]),"+f"(d[2]),"+f"(d[3]),"+f"(d[4]),"+f"(d[5]),"+f"(d[6]),"+f"(d[7]),"+f"(d[8]),"+f"(d[9]),"+f"(d[10]),"+f"(d[11]),"+f"(d[12]),"+f"(d[13]),"+f"(d[14]),"+f"(d[15]),"+f"(d[16]),"+f"(d[17]),"+f"(d[18]),"+f"(d[19]),"+f"(d[20]),"+f"(d[21]),"+f"(d[22]),"+f"(d[23]),"+f"(d[24]),"+f"(d[25]),"+f"(d[26]),"+f"(d[27]),"+f"(d[28]),"+f"(d[29]),"+f"(d[30]),"+f"(d[31]),"+f"(d[32]),"+f"(d[33]),"+f"(d[34]),"+f"(d[35]),"+f"(d[36]),"+f"(d[37]),"+f"(d[38]),"+f"(d[39]),"+f"(d[40]),"+f"(d[41]),"+f"(d[42]),"+f"(d[43]),"+f"(d[44]),"+f"(d[45]),"+f"(d[46]),"+f"(d[47]),"+f"(d[48]),"+f"(d[49]),"+f"(d[50]),"+f"(d[51]),"+f"(d[52]),"+f"(d[53]),"+f"(d[54]),"+f"(d[55]),"+f"(d[56]),"+f"(d[57]),"+f"(d[58]),"+f"(d[59]),"+f"(d[60]),"+f"(d[61]),"+f"(d[62]),"+f"(d[63]),"+f"(d[64]),"+f"(d[65]),"+f"(d[66]),"+f"(d[67]),"+f"(d[68]),"+f"(d[69]),"+f"(d[70]),"+f"(d[71]),"+f"(d[72]),"+f"(d[73]),"+f"(d[74]),"+f"(d[75]),"+f"(d[76]),"+f"(d[77]),"+f"(d[78]),"+f"(d[79]),"+f"(d[80]),"+f"(d[81]),"+f"(d[82]),"+f"(d[83]),"+f"(d[84]),"+f"(d[85]),"+f"(d[86]),"+f"(d[87])
    : "r"(a[0]), "r"(a[1]), "r"(a[2]), "r"(a[3]), "r"(descB), "r"(scaleD));
}
__device__ __forceinline__ void wgmma_ss_n72_t11(float (&d)[36], uint32_t descA, uint32_t descB, int scaleD) {
  asm volatile("{\n.reg .pred p;\n.reg .b64 da, db;\nsetp.ne.b32 p, %38, 0;\nmov.b64 da, {%36, 0x40000040};\nmov.b64 db, {%37, 0x40000040};\n"
    "wgmma.mma_async.sync.aligned.m64n72k16.f32.bf16.bf16 {%0,%1,%2,%3,%4,%5,%6,%7,%8,%9,%10,%11,%12,%13,%14,%15,%16,%17,%18,%19,%20,%21,%22,%23,%24,%25,%26,%27,%28,%29,%30,%31,%32,%33,%34,%35}, da, db, p, 1, 1, 1, 1;\n}\n"
    : "+f"(d[0]),"+f"(d[1]),"+f"(d[2]),"+f"(d[3]),"+f"(d[4]),"+f"(d[5]),"+f"(d[6]),"+f"(d[7]),"+f"(d[8]),"+f"(d[9]),"+f"(d[10]),"+f"(d[11]),"+f"(d[12]),"+f"(d[13]),"+f"(d[14]),"+f"(d[15]),"+f"(d[16]),"+f"(d[17]),"+f"(d[18]),"+f"(d[19]),"+f"(d[20]),"+f"(d[21]),"+f"(d[22]),"+f"(d[23]),"+f"(d[24]),"+f"(d[25]),"+f"(d[26]),"+f"(d[27]),"+f"(d[28]),"+f"(d[29]),"+f"(d[30]),"+f"(d[31]),"+f"(d[32]),"+f"(d[33]),"+f"(d[34]),"+f"(d[35])
    : "r"(descA), "r"(descB), "r"(scaleD));
}

#define TSTAMP(i) do {} while (0)
#define TS2(w, i) do {} while (0)

constexpr float LOG2E = 1.4426950408889634f;

__device__ __forceinline__ void feat_exp(const uint32_t (&P)[4], float (&e)[16]) {
  uint32_t a = hmax2(P[0], P[2]), b = hmax2(P[1], P[3]);
  uint32_t mx = hmax2(__byte_perm(a, b, 0x5410), __byte_perm(a, b, 0x7632));
  a = hmin2(P[0], P[2]); b = hmin2(P[1], P[3]);
  uint32_t mn = hmin2(__byte_perm(a, b, 0x5410), __byte_perm(a, b, 0x7632));
  mx = hmax2(mx, __shfl_xor_sync(0xffffffffu, mx, 1));
  mn = hmin2(mn, __shfl_xor_sync(0xffffffffu, mn, 1));
  mx = hmax2(mx, __shfl_xor_sync(0xffffffffu, mx, 2));
  mn = hmin2(mn, __shfl_xor_sync(0xffffffffu, mn, 2));
  float mx0 = -blo(mx) * LOG2E, mx1 = -bhi(mx) * LOG2E, mn0 = blo(mn) * LOG2E, mn1 = bhi(mn) * LOG2E;
  float v[8] = {blo(P[0]), bhi(P[0]), blo(P[1]), bhi(P[1]), blo(P[2]), bhi(P[2]), blo(P[3]), bhi(P[3])};
#pragma unroll
  for (int i = 0; i < 8; i++) {
    bool r1 = (i >> 1) & 1;
    e[i]     = ex2(fmaf(v[i],  LOG2E, r1 ? mx1 : mx0));
    e[8 + i] = ex2(fmaf(v[i], -LOG2E, r1 ? mn1 : mn0));
  }
}

__global__ void __cluster_dims__(2, 1, 1) __launch_bounds__(384, 1)
fused_kernel(const __grid_constant__ Maps maps, const __nv_bfloat16* __restrict__ x, const __nv_bfloat16* __restrict__ wphi,
             const __nv_bfloat16* __restrict__ wo, const __nv_bfloat16* __restrict__ wg_, const __nv_bfloat16* __restrict__ wu_,
             const __nv_bfloat16* __restrict__ wd_, __nv_bfloat16* __restrict__ out) {
  extern __shared__ __align__(1024) unsigned char smem[];
  const uint32_t sb = smem_u32(smem);
  const int tid = threadIdx.x, lane = tid & 31;
  const int warp = __shfl_sync(0xffffffffu, tid >> 5, 0);
  const uint32_t rank = blockIdx.x & 1;
  const int cl = blockIdx.x >> 1;
  int quad, qi;
  if (cl < 4) { quad = 15; qi = cl; }
  else if (cl < 36) { quad = (cl - 4) & 7; qi = (cl - 4) >> 3; }
  else { qi = (cl - 36) / 7; quad = 8 + (cl - 36) - 7 * qi; }
  const int rb = quad, hg = 2 * qi + rank;
  const int rb3 = (quad & ~1) + rank, jf = 4 * (quad & 1) + qi;

  if (warp >= 8) {
    asm volatile("setmaxnreg.dec.sync.aligned.u32 24;");
    if (lane == 0) {
      if (warp == 8) {
#pragma unroll
        for (int k = 0; k < 9; k++) {
          const int s = k < 3 ? k : (k < 6 ? k + 3 : k - 3);
          const uint32_t bar = sb + SM_FULL + s * 8;
          mbar_init(bar, 1);
          mbar_expect_tx(bar, SLOT);
          if (s >= 3 && s < 6) tma2d(sb + s * SLOT, &maps.w, 512 + hg * 64, (s - 3) * 192, bar);
          else tma3d(sb + s * SLOT, &maps.x, 0, rb * 128 + (s >= 6 ? 64 : 0), 3 * (s % 3), bar);
        }
      } else if (warp == 9) {
        mbar_init(sb + SM_MISCB, 2);
        mbar_init(sb + SM_KVB, 32);
        mbar_expect_tx(sb + SM_MISCB, 2048);
        bulk_g2s(sb + SM_WPHI, wphi + hg * 1024, 2048, sb + SM_MISCB);
      } else if (warp == 11) {
        *reinterpret_cast<volatile unsigned*>(smem + SM_EPOCH) = atomicAdd(&g_start, 1u) / NCTA;
      }
      asm volatile("fence.mbarrier_init.release.cluster;" ::: "memory");
    }
    if (tid == 256) TS2(0, 18);
    __syncwarp();
    if (warp != 11) bar_sync(0, 352);
    asm volatile("barrier.cluster.arrive.relaxed.aligned;" ::: "memory");
    if (warp == 8) {
      asm volatile("barrier.cluster.wait.aligned;" ::: "memory");
      if (lane == 0) {
        const CUtensorMap* mgu = rank ? (jf == 7 ? &maps.u7 : &maps.u) : (jf == 7 ? &maps.g7 : &maps.g);
        asm volatile("prefetch.tensormap [%0];" ::"l"(&maps.wo) : "memory");
        asm volatile("prefetch.tensormap [%0];" ::"l"(mgu) : "memory");
        asm volatile("prefetch.tensormap [%0];" ::"l"(&maps.d) : "memory");
#pragma unroll 1
        for (int s = ST_WV; s < ST_O0; s++) {
          if (s == ST_SCR1) continue;
          mbar_wait(sb + SM_EMPTY + (s - 9) * 8);
          const uint32_t dst = sb + (s >= 18 ? s - 18 : s - 9) * SLOT, bar = sb + SM_FULL + s * 8;
          if (s < ST_WO) tma2d(dst, &maps.w, (s < ST_WQ ? 1024 : 0) + hg * 64, (s < ST_WQ ? s - ST_WV : s - ST_WQ) * 192, bar);
          else { mbar_wait(bar - 8); tma2d(dst, &maps.wo, hg * 64, (s - ST_WO) * 192, bar); }
        }
        const int jc = jf == 7 ? 0 : jf;
        int slot = 5 + rank;
#pragma unroll 1
        for (int s = ST_GU + rank; s < NSTAGE; s += 2) {
          mbar_wait(sb + SM_EMPTY + (s < ST_GU + 6 ? s - 12 : s - 9) * 8);
          if (s > ST_GU && s < ST_GU + THR) mbar_wait(sb + SM_FULL + (s - 1) * 8);
          const uint32_t dst = sb + slot * SLOT, bar = sb + SM_FULL + s * 8;
          if (s < ST_D) {
            const int c = (s - ST_GU) >> 1;
#pragma unroll
            for (int b = 0; b < 3; b++) tma3d_mc(dst + b * 8192, mgu, b * 64, jc, c * 64, bar);
          } else {
            tma2d_mc(dst, &maps.d, ((jf + 1 + (s - ST_D)) & 7) * 64, jf * 176, bar);
          }
          slot += 2; if (slot >= NSLOT) slot -= NSLOT;
        }
      }
      __syncwarp();
    } else {
      asm volatile("barrier.cluster.wait.aligned;" ::: "memory");
      if (warp == 11) {
#pragma unroll
        for (int i = 0; i < 4; i++)
          reinterpret_cast<uint4*>(smem + SM_ONES)[lane + 32 * i] = make_uint4(0x3F803F80u, 0x3F803F80u, 0x3F803F80u, 0x3F803F80u);
        fence_async_smem();
        __syncwarp();
        if (lane == 0) { mbar_arrive(sb + SM_MISCB); TS2(0, 19); }
      }
      mbar_wait(sb + SM_MISCB);
      const unsigned epoch = *reinterpret_cast<volatile unsigned*>(smem + SM_EPOCH);
      const uint32_t T = (epoch & 1) ^ 1;
      if (warp == 11) {
        reinterpret_cast<float4*>(&g_kv[T][blockIdx.x * 128])[lane] = make_float4(0.f, 0.f, 0.f, 0.f);
        if (lane < 8) g_z[T][blockIdx.x * 8 + lane] = 0.f;
        mbar_wait(sb + SM_FULL + (ST_WK + 2) * 8);
        if (lane == 0) {
          asm volatile("cp.async.bulk.prefetch.L2.global [%0], 4096;" ::"l"((const char*)wo + blockIdx.x * 4096) : "memory");
          asm volatile("cp.async.bulk.prefetch.L2.global [%0], 11008;" ::"l"((const char*)wg_ + blockIdx.x * 11008) : "memory");
          asm volatile("cp.async.bulk.prefetch.L2.global [%0], 11008;" ::"l"((const char*)wu_ + blockIdx.x * 11008) : "memory");
          asm volatile("cp.async.bulk.prefetch.L2.global [%0], 11008;" ::"l"((const char*)wd_ + blockIdx.x * 11008) : "memory");
          const unsigned target = (epoch + 1) * 32;
          unsigned v; int it = 0;
#pragma unroll 1
          do {
            asm volatile("ld.acquire.gpu.global.u32 %0, [%1];" : "=r"(v) : "l"(&g_kvcnt[hg * 32]) : "memory");
            if (++it > (1 << 18)) break;
          } while ((int)(v - target) < 0);
          TS2(0, 26);
        }
        __syncwarp();
        {
          const char* src = reinterpret_cast<const char*>(&g_kv[T ^ 1][hg * 2048]) + lane * 16;
#pragma unroll
          for (int i = 0; i < 16; i++)
            asm volatile("cp.async.cg.shared.global [%0], [%1], 16;" ::"r"(sb + SM_KV32 + lane * 16 + i * 512), "l"(src + i * 512) : "memory");
          asm volatile("cp.async.cg.shared.global [%0], [%1], 16;" ::"r"(sb + SM_ONES + lane * 16), "l"(&g_z[T ^ 1][hg * 128 + lane * 4]) : "memory");
          asm volatile("cp.async.mbarrier.arrive.noinc.shared::cta.b64 [%0];" ::"r"(sb + SM_KVB) : "memory");
        }
      } else {
        const int w = warp - 9;
        st_rlx4(reinterpret_cast<uint4*>(&g_st[2 * rb + w][hg][0]) + lane, T ^ 1, T ^ 1, T ^ 1, T ^ 1);
        if (lane < 8) st_rlx4(&g_o[2 * rb + w][hg][lane >> 1][3][30 + (lane & 1)], T ^ 1, T ^ 1, T ^ 1, T ^ 1);
        st_rlx4(&g_part[2 * rb3 + w][lane >> 2][jf][lane & 3][3][30], T ^ 1, T ^ 1, T ^ 1, T ^ 1);
        st_rlx4(&g_part[2 * rb3 + w][lane >> 2][jf][lane & 3][3][31], T ^ 1, T ^ 1, T ^ 1, T ^ 1);
        bar_sync(6 + w, 160);
        if (lane == 0) {
          asm volatile("fence.acq_rel.gpu;" ::: "memory");
          TS2(w, 25);
          asm volatile("red.relaxed.gpu.global.add.u32 [%0], 1;" ::"l"(&g_kvcnt[hg * 32]) : "memory");
        }
        mbar_wait(sb + SM_KVB);
        const uint32_t* pw = reinterpret_cast<const uint32_t*>(&g_o[2 * rb + w][lane >> 2][lane & 3][3][31]);
        int it = 0;
#pragma unroll 1
        while (__any_sync(0xffffffffu, (ld_rlx1(pw) ^ T) & 1)) { if (++it > (1 << 18)) break; }
        if (lane == 0) {
          TS2(w, 27);
#pragma unroll 1
          for (int i = 0; i < 3; i++) {
            mbar_wait(sb + SM_EMPTY + (w ? ST_O0 + i : ST_O0 - 9 + i) * 8);
            bulk_g2s(sb + (2 + i) * SLOT, &g_o[2 * rb + w][3 * i][0][0][0], i < 2 ? 24576 : 16384, sb + SM_FULL + (ST_O0 + 3 * w + i) * 8);
          }
        }
        __syncwarp();
      }
    }
    asm volatile("barrier.cluster.arrive.relaxed.aligned;" ::: "memory");
    asm volatile("barrier.cluster.wait.aligned;" ::: "memory");
  } else {
    asm volatile("setmaxnreg.inc.sync.aligned.u32 240;");
    if (lane == 0) {
#pragma unroll 1
      for (int d = warp; d + 9 < NSTAGE; d += 8) {
        mbar_init(sb + SM_EMPTY + d * 8, st_empty_cnt(d));
        mbar_init(sb + SM_FULL + (d + 9) * 8, 1);
        mbar_expect_tx(sb + SM_FULL + (d + 9) * 8, st_bytes(d + 9));
      }
      asm volatile("fence.mbarrier_init.release.cluster;" ::: "memory");
    }
    __syncwarp();
    bar_sync(0, 352);
    asm volatile("barrier.cluster.arrive.relaxed.aligned;" ::: "memory");
    const int wg = warp >> 2, wq = warp & 3, g = lane >> 2, t = lane & 3;
    const bool lead = (tid & 127) == 0;
    const uint32_t db = ((sb & 0x3FFFF) >> 4) | (512u << 16);
    auto release = [&](int d) {
      const int s = st_next(d);
      if (s < NSTAGE) mbar_arrive_cluster(sb + SM_EMPTY + d * 8, s >= ST_GU ? (uint32_t)(s & 1) : rank);
    };
    const uint32_t lrow = (uint32_t)(wq * 16 + (lane & 7) + ((lane >> 3) & 1) * 8) * 128;
    const uint32_t lx = lane & 7, lhi = lane >> 4;
    TSTAMP(0);

    float r0, r1;
    uint32_t E[4][8];
    uint32_t T = 0;
    {
      uint32_t A[32][4];
      float acc[32];
      const int sx = wg ? ST_X1 : ST_X0;
      {
        const uint32_t base = sb + sx * SLOT + lrow;
        float s0 = 0.f, s1 = 0.f;
#pragma unroll
        for (int c = 0; c < 8; c++) {
          if (c % 3 == 0) mbar_wait(sb + SM_FULL + (sx + c / 3) * 8);
#pragma unroll
          for (int k = 0; k < 4; k++) ldsm4(A[4 * c + k], base + c * 8192 + (((2 * k + lhi) ^ lx) << 4));
          const uint32_t u0 = hadd2(hadd2(hadd2(A[4 * c][0], A[4 * c][2]), hadd2(A[4 * c + 1][0], A[4 * c + 1][2])),
                                    hadd2(hadd2(A[4 * c + 2][0], A[4 * c + 2][2]), hadd2(A[4 * c + 3][0], A[4 * c + 3][2])));
          const uint32_t u1 = hadd2(hadd2(hadd2(A[4 * c][1], A[4 * c][3]), hadd2(A[4 * c + 1][1], A[4 * c + 1][3])),
                                    hadd2(hadd2(A[4 * c + 2][1], A[4 * c + 2][3]), hadd2(A[4 * c + 3][1], A[4 * c + 3][3])));
          s0 += blo(u0) + bhi(u0); s1 += blo(u1) + bhi(u1);
        }
        s0 += __shfl_xor_sync(0xffffffffu, s0, 1); s1 += __shfl_xor_sync(0xffffffffu, s1, 1);
        s0 += __shfl_xor_sync(0xffffffffu, s0, 2); s1 += __shfl_xor_sync(0xffffffffu, s1, 2);
        TSTAMP(17);
        asm volatile("barrier.cluster.wait.aligned;" ::: "memory");
        if (lane < 3) release(sx + lane);
        s0 *= (1.f / 512.f); s1 *= (1.f / 512.f);
        const uint32_t m0 = pack2(s0, s0), m1 = pack2(s1, s1);
        float q0 = 0.f, q1 = 0.f;
#pragma unroll
        for (int c = 0; c < 8; c++) {
#pragma unroll
          for (int ks = 4 * c; ks < 4 * c + 4; ks += 2) {
            uint32_t v0, v1;
            A[ks][0] = hsub2(A[ks][0], m0); A[ks][1] = hsub2(A[ks][1], m1);
            A[ks][2] = hsub2(A[ks][2], m0); A[ks][3] = hsub2(A[ks][3], m1);
            A[ks + 1][0] = hsub2(A[ks + 1][0], m0); A[ks + 1][1] = hsub2(A[ks + 1][1], m1);
            A[ks + 1][2] = hsub2(A[ks + 1][2], m0); A[ks + 1][3] = hsub2(A[ks + 1][3], m1);
            v0 = hfma2(A[ks][2], A[ks][2], hmul2(A[ks][0], A[ks][0]));
            v1 = hfma2(A[ks][3], A[ks][3], hmul2(A[ks][1], A[ks][1]));
            v0 = hfma2(A[ks + 1][2], A[ks + 1][2], hfma2(A[ks + 1][0], A[ks + 1][0], v0));
            v1 = hfma2(A[ks + 1][3], A[ks + 1][3], hfma2(A[ks + 1][1], A[ks + 1][1], v1));
            q0 += blo(v0) + bhi(v0); q1 += blo(v1) + bhi(v1);
          }
          if (c % 3 == 0) mbar_wait(sb + SM_FULL + (ST_WK + c / 3) * 8);
          wg_fence();
#pragma unroll
          for (int ks = 4 * c; ks < 4 * c + 4; ks++) wgmma_rs_n64(acc, A[ks], DESC((ST_WK % NSLOT) * SLOT + ks * 2048), ks != 0);
          wg_commit();
          if (c == 4) { wg_wait<2>(); if (lead) release(ST_WK); }
        }
        q0 += __shfl_xor_sync(0xffffffffu, q0, 1); q1 += __shfl_xor_sync(0xffffffffu, q1, 1);
        q0 += __shfl_xor_sync(0xffffffffu, q0, 2); q1 += __shfl_xor_sync(0xffffffffu, q1, 2);
        s0 -= blo(m0); s1 -= blo(m1);
        r0 = rsqrtf(fmaxf(q0 * (1.f / 512.f) - s0 * s0, 0.f) + 1e-5f);
        r1 = rsqrtf(fmaxf(q1 * (1.f / 512.f) - s1 * s1, 0.f) + 1e-5f);
      }
      TSTAMP(1);
      uint32_t a[4][4];
      auto scale_pack = [&]() {
#pragma unroll
        for (int h = 0; h < 4; h++) {
          a[h][0] = pack2(acc[8 * h + 0] * r0, acc[8 * h + 1] * r0); a[h][1] = pack2(acc[8 * h + 2] * r1, acc[8 * h + 3] * r1);
          a[h][2] = pack2(acc[8 * h + 4] * r0, acc[8 * h + 5] * r0); a[h][3] = pack2(acc[8 * h + 6] * r1, acc[8 * h + 7] * r1);
        }
      };
      auto project = [&](const uint32_t (&b)[4][4]) {
        float pp[4][2][4];
#pragma unroll
        for (int h = 0; h < 4; h++) {
#pragma unroll
          for (int i = 0; i < 4; i++) { pp[h][0][i] = 0.f; pp[h][1][i] = 0.f; }
          mma16816(pp[h][0], a[h], b[h][0], b[h][1]);
          mma16816(pp[h][1], a[h], b[h][2], b[h][3]);
        }
#pragma unroll
        for (int h = 0; h < 4; h++) {
          a[h][0] = pack2(pp[h][0][0], pp[h][0][1]); a[h][1] = pack2(pp[h][0][2], pp[h][0][3]);
          a[h][2] = pack2(pp[h][1][0], pp[h][1][1]); a[h][3] = pack2(pp[h][1][2], pp[h][1][3]);
        }
      };
      const uint32_t wpa = sb + SM_WPHI + ((lane & 7) + ((lane >> 3) & 1) * 8) * 32 + lhi * 16;
      const uint32_t scr = sb + (wg ? (ST_SCR1 % NSLOT) : (ST_SCR0 % NSLOT)) * SLOT;
      {
        uint32_t b[4][4];
        mbar_wait(sb + SM_MISCB);
        T = (*reinterpret_cast<volatile unsigned*>(smem + SM_EPOCH) & 1) ^ 1;
#pragma unroll
        for (int h = 0; h < 4; h++) ldsm4t(b[h], wpa + h * 512);
        wg_wait<0>();
        if (lead) { release(ST_WK + 1); release(ST_WK + 2); }
        TSTAMP(2);
        scale_pack();
        project(b);
      }
      mbar_wait(sb + SM_EMPTY + (wg ? ST_SCR1 - NSLOT : ST_SCR0 - NSLOT) * 8);
      auto vgroup = [&](int c) {
        if (c % 3 == 0) mbar_wait(sb + SM_FULL + (ST_WV + c / 3) * 8);
        if (c == 0) wg_fence();
#pragma unroll
        for (int ks = 4 * c; ks < 4 * c + 4; ks++) wgmma_rs_n64(acc, A[ks], DESC((ST_WV % NSLOT) * SLOT + ks * 2048), ks != 0);
      };
#pragma unroll
      for (int h = 0; h < 4; h++) {
        vgroup(2 * h);
        float f[16];
        feat_exp(a[h], f);
        float sp0 = (f[0] + f[1]) + (f[4] + f[5]), sp1 = (f[2] + f[3]) + (f[6] + f[7]);
        float sn0 = (f[8] + f[9]) + (f[12] + f[13]), sn1 = (f[10] + f[11]) + (f[14] + f[15]);
        sp0 += __shfl_xor_sync(0xffffffffu, sp0, 1); sp1 += __shfl_xor_sync(0xffffffffu, sp1, 1);
        sn0 += __shfl_xor_sync(0xffffffffu, sn0, 1); sn1 += __shfl_xor_sync(0xffffffffu, sn1, 1);
        vgroup(2 * h + 1);
        sp0 += __shfl_xor_sync(0xffffffffu, sp0, 2); sp1 += __shfl_xor_sync(0xffffffffu, sp1, 2);
        sn0 += __shfl_xor_sync(0xffffffffu, sn0, 2); sn1 += __shfl_xor_sync(0xffffffffu, sn1, 2);
        sp0 = rcp(sp0); sp1 = rcp(sp1); sn0 = rcp(sn0); sn1 = rcp(sn1);
        const uint32_t dst = scr + (h >> 1) * 8192 + lrow;
        stsm4(dst + ((((h & 1) * 4 + lhi) ^ lx) << 4), pack2(f[0] * sp0, f[1] * sp0), pack2(f[2] * sp1, f[3] * sp1),
              pack2(f[4] * sp0, f[5] * sp0), pack2(f[6] * sp1, f[7] * sp1));
        stsm4(dst + ((((h & 1) * 4 + 2 + lhi) ^ lx) << 4), pack2(f[8] * sn0, f[9] * sn0), pack2(f[10] * sn1, f[11] * sn1),
              pack2(f[12] * sn0, f[13] * sn0), pack2(f[14] * sn1, f[15] * sn1));
      }
      wg_commit();
      TSTAMP(3);
      wg_wait<0>();
      if ((tid & 127) < 3) release(ST_WV + (tid & 127));
      TSTAMP(4);
      {
        scale_pack();
#pragma unroll
        for (int h = 0; h < 4; h++) stsm4(scr + 16384 + lrow + (((2 * h + lhi) ^ lx) << 4), a[h][0], a[h][1], a[h][2], a[h][3]);
        fence_async_smem();
        bar_sync(3, 256);
        float kv[36];
        wg_fence();
#pragma unroll
        for (int ks = 0; ks < 8; ks++) {
          const uint32_t sk = (ks < 4 ? (ST_SCR0 % NSLOT) : (ST_SCR1 % NSLOT)) * SLOT + (ks & 3) * 2048;
          const uint32_t dv = (DESC(sk + 16384) & 0xFFFFu) | (((SM_ONES - sk - 16384) >> 4) << 16);
          wgmma_ss_n72_t11(kv, DESC(sk) + wg * 512, dv, ks != 0);
        }
        wg_commit();
        wg_wait<0>();
        if (lead) { release(ST_SCR0); release(ST_SCR1); }
        const int hl = 2 * wg + (wq >> 1), f = (wq & 1) * 16 + g;
        float* kvp = &g_kv[T ^ 1][((hg * 4 + hl) * 32 + f) * 16 + 2 * t];
        float* zp = &g_z[T ^ 1][(hg * 4 + hl) * 32 + f];
        float c[8];
#pragma unroll
        for (int i = 0; i < 8; i++) c[i] = hl >= 2 ? (hl == 3 ? kv[24 + i] : kv[16 + i]) : (hl == 1 ? kv[8 + i] : kv[i]);
#pragma unroll
        for (int n = 0; n < 2; n++) {
          asm volatile("red.relaxed.gpu.global.add.v2.f32 [%0], {%1,%2};" ::"l"(kvp + n * 8), "f"(c[4 * n]), "f"(c[4 * n + 1]) : "memory");
          asm volatile("red.relaxed.gpu.global.add.v2.f32 [%0], {%1,%2};" ::"l"(kvp + n * 8 + 128), "f"(c[4 * n + 2]), "f"(c[4 * n + 3]) : "memory");
        }
        if (t < 2) asm volatile("red.relaxed.gpu.global.add.f32 [%0], %1;" ::"l"(zp + t * 8), "f"(t ? kv[34] : kv[32]) : "memory");
        bar_arrive(6 + wg, 160);
      }
      TSTAMP(5);
      {
        if (wg == 1) bar_sync(4, 256);
#pragma unroll
        for (int i = 0; i < 3; i++) {
          mbar_wait(sb + SM_FULL + (ST_WQ + i) * 8);
          wg_fence();
#pragma unroll
          for (int kk = 0; kk < 12; kk++)
            if (12 * i + kk < 32) wgmma_rs_n64(acc, A[(12 * i + kk) & 31], DESC((ST_WQ % NSLOT) * SLOT + (12 * i + kk) * 2048), (i | kk) != 0);
          wg_commit();
          if (i > 0) { wg_wait<1>(); if (lead) release(ST_WQ + i - 1); }
        }
        if (wg == 0) bar_arrive(4, 256);
        uint32_t b[4][4];
#pragma unroll
        for (int h = 0; h < 4; h++) ldsm4t(b[h], wpa + h * 512);
        wg_wait<0>();
        if (lead) release(ST_WQ + 2);
        TSTAMP(6);
        scale_pack();
        project(b);
#pragma unroll
        for (int h = 0; h < 4; h++) {
          float e[16];
          feat_exp(a[h], e);
#pragma unroll
          for (int i = 0; i < 8; i++) E[h][i] = pack2(e[2 * i], e[2 * i + 1]);
        }
      }
      TSTAMP(7);
    }
    const int rh = 2 * rb + wg;
    mbar_wait(sb + SM_KVB);
    {
      const int r = tid & 127;
      const float4* src = reinterpret_cast<const float4*>(smem + SM_KV32) + r;
#pragma unroll
      for (int i = 0; i < 4; i++) {
        const float4 a = src[i * 128];
        *reinterpret_cast<uint2*>(smem + SM_KVS + (i * 32 + (r >> 2)) * 48 + (r & 3) * 8) = make_uint2(pack2(a.x, a.y), pack2(a.z, a.w));
      }
      const uint32_t zz = pack2(reinterpret_cast<const float*>(smem + SM_ONES)[r], 1.0f);
      *reinterpret_cast<uint4*>(smem + SM_KVS + r * 48 + 32) = make_uint4(zz, zz, zz, zz);
      bar_sync(1 + wg, 128);
    }
    TSTAMP(8);
    {
      uint4* op = &g_o[rh][hg][wq][0][lane];
#pragma unroll
      for (int h = 0; h < 4; h++) {
        uint32_t b0[4], b1[4], b2[4];
        const uint32_t kb = sb + SM_KVS + (h * 32 + lane) * 48;
        ldsm4t(b0, kb); ldsm4t(b1, kb + 16); ldsm4t(b2, kb + 32);
        const uint32_t ep[4] = {E[h][0], E[h][1], E[h][2], E[h][3]}, en[4] = {E[h][4], E[h][5], E[h][6], E[h][7]};
        float np0[4] = {0, 0, 0, 0}, np1[4] = {0, 0, 0, 0}, nn0[4] = {0, 0, 0, 0}, nn1[4] = {0, 0, 0, 0}, dp[4] = {0, 0, 0, 0}, dn[4] = {0, 0, 0, 0};
        mma16816(dp, ep, b2[0], b2[1]);  mma16816(dn, en, b2[2], b2[3]);
        mma16816(np0, ep, b0[0], b0[1]); mma16816(nn0, en, b0[2], b0[3]);
        mma16816(np1, ep, b1[0], b1[1]); mma16816(nn1, en, b1[2], b1[3]);
        const float i0 = rcp(fmaf(dp[0], dn[1], fmaf(dn[0], dp[1], 1e-6f * dp[1] * dn[1])));
        const float i1 = rcp(fmaf(dp[2], dn[3], fmaf(dn[2], dp[3], 1e-6f * dp[3] * dn[3])));
        const float cp0 = dn[1] * i0, cn0 = dp[1] * i0, cp1 = dn[3] * i1, cn1 = dp[3] * i1;
        st_rlx4(op + h * 32,
                tg(pack2(fmaf(np0[0], cp0, nn0[0] * cn0), fmaf(np0[1], cp0, nn0[1] * cn0)), T),
                pack2(fmaf(np0[2], cp1, nn0[2] * cn1), fmaf(np0[3], cp1, nn0[3] * cn1)),
                pack2(fmaf(np1[0], cp0, nn1[0] * cn0), fmaf(np1[1], cp0, nn1[1] * cn0)),
                pack2(fmaf(np1[2], cp1, nn1[2] * cn1), fmaf(np1[3], cp1, nn1[3] * cn1)));
      }
    }
    TSTAMP(9);

    {
      uint32_t xr[16];
      {
        const uint32_t* xp = reinterpret_cast<const uint32_t*>(x + (size_t)(rh * 64 + wq * 16 + g) * 512 + hg * 64 + 2 * t);
#pragma unroll
        for (int i = 0; i < 8; i++) { xr[2 * i] = __ldg(xp + 4 * i); xr[2 * i + 1] = __ldg(xp + 8 * 256 + 4 * i); }
      }
      uint32_t A[8][4][4];
      const uint4* op = &g_o[rh][0][wq][0][lane];
      const uint32_t ob = sb + 2 * SLOT + wq * 2048 + lane * 16;
      float acc[32];
#pragma unroll
      for (int p = 0; p < 3; p++) {
        mbar_wait(sb + SM_FULL + (ST_O0 + 3 * wg + p) * 8);
#pragma unroll
        for (int c = 3 * p; c < (p < 2 ? 3 * p + 3 : 8); c++)
#pragma unroll
          for (int s = 0; s < 4; s++)
            asm volatile("ld.shared.v4.b32 {%0,%1,%2,%3}, [%4];" : "=r"(A[c][s][0]), "=r"(A[c][s][1]), "=r"(A[c][s][2]), "=r"(A[c][s][3])
                         : "r"(ob + c * 8192 + s * 512) : "memory");
        __syncwarp();
        if (lane == 0) release(ST_O0 + 3 * wg + p);
        mbar_wait(sb + SM_FULL + (ST_WO + p) * 8);
#pragma unroll
        for (int c = 3 * p; c < (p < 2 ? 3 * p + 3 : 8); c++) {
          chk_chunk(A[c], op + c * 512, T);
          wg_fence();
#pragma unroll
          for (int s = 0; s < 4; s++)
            wgmma_rs_n64(acc, A[c][s], DESC(((ST_WO + p) % NSLOT) * SLOT + ((c % 3) * 4 + s) * 2048), (c | s) != 0);
          wg_commit();
        }
      }
      wg_wait<0>();
      if ((tid & 127) < 3) release(ST_WO + (tid & 127));
      TSTAMP(10);
      uint32_t hw[16];
      float s0 = 0.f, s1 = 0.f, q0 = 0.f, q1 = 0.f;
#pragma unroll
      for (int i = 0; i < 8; i++) {
        hw[2 * i]     = pack2(blo(xr[2 * i]) + acc[4 * i], bhi(xr[2 * i]) + acc[4 * i + 1]);
        hw[2 * i + 1] = pack2(blo(xr[2 * i + 1]) + acc[4 * i + 2], bhi(xr[2 * i + 1]) + acc[4 * i + 3]);
      }
      uint4* hp_ = &g_h[rh][hg][wq][0][lane];
#pragma unroll
      for (int s = 0; s < 4; s++) st_rlx4(hp_ + s * 32, tg(hw[4 * s], T), hw[4 * s + 1], hw[4 * s + 2], hw[4 * s + 3]);
#pragma unroll
      for (int i = 0; i < 8; i++) {
        float a = blo(hw[2 * i]), b = bhi(hw[2 * i]);
        s0 += a + b; q0 = fmaf(a, a, q0); q0 = fmaf(b, b, q0);
        a = blo(hw[2 * i + 1]); b = bhi(hw[2 * i + 1]);
        s1 += a + b; q1 = fmaf(a, a, q1); q1 = fmaf(b, b, q1);
      }
      s0 += __shfl_xor_sync(0xffffffffu, s0, 1); s1 += __shfl_xor_sync(0xffffffffu, s1, 1);
      q0 += __shfl_xor_sync(0xffffffffu, q0, 1); q1 += __shfl_xor_sync(0xffffffffu, q1, 1);
      s0 += __shfl_xor_sync(0xffffffffu, s0, 2); s1 += __shfl_xor_sync(0xffffffffu, s1, 2);
      q0 += __shfl_xor_sync(0xffffffffu, q0, 2); q1 += __shfl_xor_sync(0xffffffffu, q1, 2);
      if (t < 2) st_rlx2(&g_st[rh][hg][wq * 16 + g + t * 8], tg(__float_as_uint(t ? s1 : s0), T), __float_as_uint(t ? q1 : q0));
      uint32_t hx = T;
#pragma unroll
      for (int i = 0; i < 4; i++) hx |= (hw[4 * i] & 1u) << (i + 1);
      st_rlx1(&g_hx[rh][hg][wq][lane], hx);
    }
    TSTAMP(11);

    const int rh3 = 2 * rb3 + wg;
    uint32_t HH[11][4];
    {
      uint32_t A[2][4][4];
      const uint4* hp_ = &g_h[rh3][0][wq][0][lane];
      uint32_t m0, m1;
      {
        const uint2* sp = &g_st[rh3][2 * t][wq * 16 + g];
        uint32_t a[4], b[4];
        int it = 0;
#pragma unroll 1
        do {
          ld_rlx2(a[0], a[1], sp); ld_rlx2(a[2], a[3], sp + 64); ld_rlx2(b[0], b[1], sp + 8); ld_rlx2(b[2], b[3], sp + 72);
          if (++it > (1 << 18)) break;
        } while (__any_sync(0xffffffffu, bad4(a[0], a[2], b[0], b[2], T) & 1));
        ld_chunk(A[0], hp_);
        float s0 = __uint_as_float(a[0]) + __uint_as_float(a[2]), q0 = __uint_as_float(a[1]) + __uint_as_float(a[3]);
        float s1 = __uint_as_float(b[0]) + __uint_as_float(b[2]), q1 = __uint_as_float(b[1]) + __uint_as_float(b[3]);
        s0 += __shfl_xor_sync(0xffffffffu, s0, 1); s1 += __shfl_xor_sync(0xffffffffu, s1, 1);
        q0 += __shfl_xor_sync(0xffffffffu, q0, 1); q1 += __shfl_xor_sync(0xffffffffu, q1, 1);
        s0 += __shfl_xor_sync(0xffffffffu, s0, 2); s1 += __shfl_xor_sync(0xffffffffu, s1, 2);
        q0 += __shfl_xor_sync(0xffffffffu, q0, 2); q1 += __shfl_xor_sync(0xffffffffu, q1, 2);
        s0 *= (1.f / 512.f); s1 *= (1.f / 512.f);
        r0 = rcp(fmaxf(q0 * (1.f / 512.f) - s0 * s0, 0.f) + 1e-5f);
        r1 = rcp(fmaxf(q1 * (1.f / 512.f) - s1 * s1, 0.f) + 1e-5f);
        m0 = pack2(s0, s0); m1 = pack2(s1, s1);
      }
      TSTAMP(12);
      float ag[88], au[88];
      int slot = 5;
#pragma unroll 1
      for (int c2 = 0; c2 < 8; c2 += 2) {
#pragma unroll
        for (int b = 0; b < 2; b++) {
          const int c = c2 + b, sG = ST_GU + 2 * c;
          chk_chunk(A[b], hp_ + c * 512, T);
#pragma unroll
          for (int s = 0; s < 4; s++) {
            A[b][s][0] = hsub2(A[b][s][0], m0); A[b][s][1] = hsub2(A[b][s][1], m1);
            A[b][s][2] = hsub2(A[b][s][2], m0); A[b][s][3] = hsub2(A[b][s][3], m1);
          }
          mbar_wait(sb + SM_FULL + sG * 8);
          wg_fence();
#pragma unroll
          for (int s = 0; s < 4; s++)
            wgmma_rs_n176(ag, A[b][s], db + slot * (SLOT >> 4) + s * 128, (c | s) != 0);
          wg_commit();
          if (++slot == NSLOT) slot = 0;
          wg_wait<1>();
          if (lead && c > 0) release(sG - 1);
          if (c < 7) ld_chunk(A[b ^ 1], hp_ + (c + 1) * 512);
          mbar_wait(sb + SM_FULL + (sG + 1) * 8);
          wg_fence();
#pragma unroll
          for (int s = 0; s < 4; s++)
            wgmma_rs_n176(au, A[b][s], db + slot * (SLOT >> 4) + s * 128, (c | s) != 0);
          wg_commit();
          if (++slot == NSLOT) slot = 0;
          wg_wait<1>();
          if (lead) release(sG);
        }
      }
      wg_wait<0>();
      TSTAMP(13);
#pragma unroll
      for (int s = 0; s < 11; s++) {
        HH[s][0] = pack2(ag[8 * s + 0] * au[8 * s + 0] * r0, ag[8 * s + 1] * au[8 * s + 1] * r0);
        HH[s][1] = pack2(ag[8 * s + 2] * au[8 * s + 2] * r1, ag[8 * s + 3] * au[8 * s + 3] * r1);
        HH[s][2] = pack2(ag[8 * s + 4] * au[8 * s + 4] * r0, ag[8 * s + 5] * au[8 * s + 5] * r0);
        HH[s][3] = pack2(ag[8 * s + 6] * au[8 * s + 6] * r1, ag[8 * s + 7] * au[8 * s + 7] * r1);
      }
    }
    TSTAMP(14);

    {
      float acc[32], sum[32];
      uint32_t in[4][4][4];
      const uint4* inb = &g_part[rh3][jf][0][wq][0][lane];
      uint4* outb = &g_part[rh3][0][jf][wq][0][lane];
      const uint32_t* hint = reinterpret_cast<const uint32_t*>(&g_part[rh3][jf][(jf - 1 - lane) & 7][wq][3][31]);
      int slot = (5 + 16) % NSLOT;
      auto step = [&](int st) {
        uint32_t pk[16];
        if (st > 0) {
#pragma unroll
          for (int i = 0; i < 16; i++) pk[i] = pack2(acc[2 * i], acc[2 * i + 1]);
        }
        mbar_wait(sb + SM_FULL + (ST_D + st) * 8);
        wg_fence();
#pragma unroll
        for (int s = 0; s < 4; s++) wgmma_rs_n64(acc, HH[s], db + slot * (SLOT >> 4) + s * 128, s != 0);
        if (st > 0) {
          uint4* p = outb + ((jf + st) & 7) * 4096;
#pragma unroll
          for (int s = 0; s < 4; s++) st_rlx4(p + s * 32, tg(pk[4 * s], T), pk[4 * s + 1], pk[4 * s + 2], pk[4 * s + 3]);
        }
#pragma unroll
        for (int s = 4; s < 11; s++) wgmma_rs_n64(acc, HH[s], db + slot * (SLOT >> 4) + s * 128, 1);
        wg_commit();
        if (++slot == NSLOT) slot = 0;
      };
      auto fetch = [&](int q) { ld_chunk(in[q & 3], inb + ((jf - 1 - q) & 7) * 512); };
      auto add = [&](int q) {
        chk_chunk(in[q & 3], inb + ((jf - 1 - q) & 7) * 512, T);
#pragma unroll
        for (int i = 0; i < 16; i++) { sum[2 * i] += blo(in[q & 3][i >> 2][i & 3]); sum[2 * i + 1] += bhi(in[q & 3][i >> 2][i & 3]); }
      };
      uint32_t ready = 0; int it = 0;
      auto await = [&](int q) {
#pragma unroll 1
        while (!((ready >> q) & 1)) {
          ready = __ballot_sync(0xffffffffu, ((ld_rlx1(hint) ^ T) & 1) == 0);
          if (++it > (1 << 18)) break;
        }
      };
      ld_chunk(in[3], &g_h[rh3][jf][wq][0][lane]);
      uint32_t hx = ld_rlx1(&g_hx[rh3][jf][wq][lane]);
#pragma unroll 1
      for (int st = 0; st < 4; st++) { step(st); wg_wait<0>(); }
      step(4);
#pragma unroll 1
      while (__any_sync(0xffffffffu, (hx ^ T) & 1)) {
        hx = ld_rlx1(&g_hx[rh3][jf][wq][lane]);
        if (++it > (1 << 18)) break;
      }
#pragma unroll
      for (int s = 0; s < 4; s++) in[3][s][0] = (in[3][s][0] & 0xFFFFFFFEu) | ((hx >> (s + 1)) & 1u);
#pragma unroll
      for (int i = 0; i < 16; i++) { sum[2 * i] = blo(in[3][i >> 2][i & 3]); sum[2 * i + 1] = bhi(in[3][i >> 2][i & 3]); }
      fetch(0); wg_wait<0>();
      step(5); fetch(1); wg_wait<0>();
      step(6); fetch(2); add(0); wg_wait<0>();
      step(7); fetch(3); add(1);
      await(4); fetch(4); add(2);
      await(5); fetch(5); add(3);
      wg_wait<0>();
      TSTAMP(15);
#pragma unroll
      for (int i = 0; i < 32; i++) sum[i] += acc[i];
      await(6); fetch(6); add(4); add(5); add(6);
      uint32_t* op = reinterpret_cast<uint32_t*>(out + (size_t)(rh3 * 64 + wq * 16 + g) * 512 + jf * 64 + 2 * t);
#pragma unroll
      for (int i = 0; i < 8; i++) {
        op[4 * i]           = pack2(sum[4 * i], sum[4 * i + 1]);
        op[8 * 256 + 4 * i] = pack2(sum[4 * i + 2], sum[4 * i + 3]);
      }
    }
    TSTAMP(16);
    asm volatile("barrier.cluster.arrive.relaxed.aligned;" ::: "memory");
    asm volatile("barrier.cluster.wait.aligned;" ::: "memory");
  }
}

typedef CUresult (*EncodeFn)(CUtensorMap*, CUtensorMapDataType, cuuint32_t, void*, const cuuint64_t*, const cuuint64_t*,
                             const cuuint32_t*, const cuuint32_t*, CUtensorMapInterleave, CUtensorMapSwizzle,
                             CUtensorMapL2promotion, CUtensorMapFloatOOBfill);

void encode(EncodeFn fn, CUtensorMap* m, const void* base, int rank, const cuuint64_t* dims, const cuuint64_t* strides,
            const cuuint32_t* box) {
  cuuint32_t es[3] = {1, 1, 1};
  fn(m, CU_TENSOR_MAP_DATA_TYPE_BFLOAT16, (cuuint32_t)rank, const_cast<void*>(base), dims, strides, box, es,
     CU_TENSOR_MAP_INTERLEAVE_NONE, CU_TENSOR_MAP_SWIZZLE_128B, CU_TENSOR_MAP_L2_PROMOTION_L2_256B,
     CU_TENSOR_MAP_FLOAT_OOB_FILL_NONE);
}

}

extern "C" void kernel_launch(void* const* d_in, const int* in_sizes, int n_in, void* d_out, int out_size) {
  (void)in_sizes; (void)n_in; (void)out_size;
  const __nv_bfloat16* x    = (const __nv_bfloat16*)d_in[0];
  const __nv_bfloat16* wqkv = (const __nv_bfloat16*)d_in[1];
  const __nv_bfloat16* wphi = (const __nv_bfloat16*)d_in[2];
  const __nv_bfloat16* wo   = (const __nv_bfloat16*)d_in[3];
  const __nv_bfloat16* wg   = (const __nv_bfloat16*)d_in[5];
  const __nv_bfloat16* wu   = (const __nv_bfloat16*)d_in[6];
  const __nv_bfloat16* wd   = (const __nv_bfloat16*)d_in[7];

  static EncodeFn fn = nullptr;
  if (!fn) {
    void* p = nullptr;
    cudaDriverEntryPointQueryResult qr;
    cudaGetDriverEntryPoint("cuTensorMapEncodeTiled", &p, cudaEnableDefault, &qr);
    fn = (EncodeFn)p;
    cudaFuncSetAttribute(fused_kernel, cudaFuncAttributeMaxDynamicSharedMemorySize, SM_TOTAL);
  }
  Maps maps;
  {
    cuuint64_t d[3] = {64, 2048, 8}, s[2] = {1024, 128}; cuuint32_t b[3] = {64, 64, 3};
    encode(fn, &maps.x, x, 3, d, s, b);
  }
  {
    cuuint64_t d[2] = {1536, 512}, s[1] = {3072}; cuuint32_t b[2] = {64, 192};
    encode(fn, &maps.w, wqkv, 2, d, s, b);
  }
  {
    cuuint64_t d[2] = {512, 512}, s[1] = {1024}; cuuint32_t b[2] = {64, 192};
    encode(fn, &maps.wo, wo, 2, d, s, b);
  }
  {
    cuuint64_t d[3] = {176, 7, 512}, d7[3] = {144, 1, 512}, s[2] = {352, 2752}; cuuint32_t b[3] = {64, 1, 64};
    encode(fn, &maps.g, wg, 3, d, s, b);
    encode(fn, &maps.u, wu, 3, d, s, b);
    encode(fn, &maps.g7, wg + 1232, 3, d7, s, b);
    encode(fn, &maps.u7, wu + 1232, 3, d7, s, b);
  }
  {
    cuuint64_t d[2] = {512, 1376}, s[1] = {1024}; cuuint32_t b[2] = {64, 176};
    encode(fn, &maps.d, wd, 2, d, s, b);
  }
  fused_kernel<<<NCTA, 384, SM_TOTAL>>>(maps, x, wphi, wo, wg, wu, wd, (__nv_bfloat16*)d_out);
}
```

```cpp
#include <cuda_runtime.h>
#include <cuda_bf16.h>
#include <cuda.h>
#include <stdint.h>

#define PROF 0

#define THR 6

namespace {

constexpr int NCTA   = 128;
constexpr int SLOT   = 24576;
constexpr int NSLOT  = 9;
constexpr int NSTAGE = 47;

constexpr int ST_X0   = 0;
constexpr int ST_WK   = 3;
constexpr int ST_X1   = 6;
constexpr int ST_SCR0 = 9;
constexpr int ST_WV   = 10;
constexpr int ST_SCR1 = 13;
constexpr int ST_WQ   = 14;
constexpr int ST_WO   = 17;
constexpr int ST_XC   = 20;
constexpr int ST_GU   = 23;
constexpr int ST_D    = 39;

__host__ __device__ constexpr int st_bytes(int s) { return s >= ST_D ? 22528 : 24576; }
__host__ __device__ constexpr int st_empty_cnt(int d) {
  return ((d < 3 || (d >= 6 && d < 9) || (d >= ST_XC && d < ST_GU)) ? 4 : 2) * (d + 9 >= ST_GU ? 2 : 1);
}

constexpr int SM_ONES = NSLOT * SLOT;
constexpr int SM_WPHI = SM_ONES + 2048;
constexpr int SM_KVS  = SM_WPHI + 2048;
constexpr int SM_KV32 = 4 * SLOT + 16384;
constexpr int SM_BAR  = SM_KVS + 6144;
constexpr int SM_FULL  = SM_BAR;
constexpr int SM_EMPTY = SM_BAR + NSTAGE * 8;
constexpr int SM_MISCB = SM_BAR + 2 * NSTAGE * 8;
constexpr int SM_KVB   = SM_MISCB + 8;
constexpr int SM_EPOCH = SM_KVB + 8;
constexpr int SM_XF    = SM_EPOCH + 8;
constexpr int SM_XE    = SM_XF + 16 * 8;
constexpr int SM_TOTAL = SM_BAR + 1024;

static_assert(SM_TOTAL == 232448 && SM_XE + 12 * 8 <= SM_TOTAL, "smem budget");

struct Maps { CUtensorMap x, w, wo, g, u, g7, u7, d; };

__device__ uint4    g_o[32][8][4][4][32];
__device__ uint4    g_h[32][8][4][4][32];
__device__ uint32_t g_hx[32][8][4][32];
__device__ uint2    g_st[32][8][64];
__device__ uint4    g_part[32][8][8][4][4][32];
__device__ float    g_kv[2][32 * 32 * 16];
__device__ float    g_z[2][32 * 32];
__device__ unsigned g_kvcnt[8 * 32];
__device__ unsigned g_start;

__device__ __forceinline__ uint32_t smem_u32(const void* p) { return (uint32_t)__cvta_generic_to_shared(p); }
__device__ __forceinline__ void mbar_init(uint32_t bar, int cnt) {
  asm volatile("mbarrier.init.shared::cta.b64 [%0], %1;" ::"r"(bar), "r"(cnt) : "memory");
}
__device__ __forceinline__ void mbar_expect_tx(uint32_t bar, uint32_t bytes) {
  asm volatile("mbarrier.arrive.expect_tx.shared::cta.b64 _, [%0], %1;" ::"r"(bar), "r"(bytes) : "memory");
}
__device__ __forceinline__ void mbar_arrive(uint32_t bar) {
  asm volatile("mbarrier.arrive.shared::cta.b64 _, [%0];" ::"r"(bar) : "memory");
}
__device__ __forceinline__ void mbar_arrive_cluster(uint32_t bar, uint32_t rank) {
  asm volatile("{\n.reg .b32 ra;\nmapa.shared::cluster.u32 ra, %0, %1;\n"
               "mbarrier.arrive.shared::cluster.b64 _, [ra];\n}" ::"r"(bar), "r"(rank) : "memory");
}
__device__ __forceinline__ bool mbar_try(uint32_t bar) {
  uint32_t ok;
  asm volatile("{\n.reg .pred p;\nmbarrier.try_wait.parity.shared::cta.b64 p, [%1], 0;\nselp.u32 %0, 1, 0, p;\n}"
               : "=r"(ok) : "r"(bar) : "memory");
  return ok != 0;
}
__device__ __forceinline__ void mbar_wait(uint32_t bar) {
  int it = 0;
#pragma unroll 1
  while (!mbar_try(bar)) {
    if (++it > (1 << 20)) __trap();
  }
}
__device__ __forceinline__ void bar_sync(int id, int n)   { asm volatile("bar.sync %0, %1;" ::"r"(id), "r"(n) : "memory"); }
__device__ __forceinline__ void bar_arrive(int id, int n) { asm volatile("bar.arrive %0, %1;" ::"r"(id), "r"(n) : "memory"); }
__device__ __forceinline__ void fence_async_smem() { asm volatile("fence.proxy.async.shared::cta;" ::: "memory"); }
__device__ __forceinline__ void wg_fence()  { asm volatile("wgmma.fence.sync.aligned;" ::: "memory"); }
__device__ __forceinline__ void wg_commit() { asm volatile("wgmma.commit_group.sync.aligned;" ::: "memory"); }
template <int N> __device__ __forceinline__ void wg_wait() { asm volatile("wgmma.wait_group.sync.aligned %0;" ::"n"(N) : "memory"); }
#define DESC(off) (db + ((uint32_t)(off) >> 4))
__device__ __forceinline__ void tma2d(uint32_t dst, const CUtensorMap* m, int c0, int c1, uint32_t bar) {
  asm volatile("cp.async.bulk.tensor.2d.shared::cluster.global.mbarrier::complete_tx::bytes [%0], [%1, {%3, %4}], [%2];"
               ::"r"(dst), "l"(m), "r"(bar), "r"(c0), "r"(c1) : "memory");
}
__device__ __forceinline__ void tma2d_mc(uint32_t dst, const CUtensorMap* m, int c0, int c1, uint32_t bar) {
  asm volatile("cp.async.bulk.tensor.2d.shared::cluster.global.mbarrier::complete_tx::bytes.multicast::cluster [%0], [%1, {%3, %4}], [%2], %5;"
               ::"r"(dst), "l"(m), "r"(bar), "r"(c0), "r"(c1), "h"((uint16_t)3) : "memory");
}
__device__ __forceinline__ void tma3d(uint32_t dst, const CUtensorMap* m, int c0, int c1, int c2, uint32_t bar) {
  asm volatile("cp.async.bulk.tensor.3d.shared::cluster.global.mbarrier::complete_tx::bytes [%0], [%1, {%3, %4, %5}], [%2];"
               ::"r"(dst), "l"(m), "r"(bar), "r"(c0), "r"(c1), "r"(c2) : "memory");
}
__device__ __forceinline__ void tma3d_mc(uint32_t dst, const CUtensorMap* m, int c0, int c1, int c2, uint32_t bar) {
  asm volatile("cp.async.bulk.tensor.3d.shared::cluster.global.mbarrier::complete_tx::bytes.multicast::cluster [%0], [%1, {%3, %4, %5}], [%2], %6;"
               ::"r"(dst), "l"(m), "r"(bar), "r"(c0), "r"(c1), "r"(c2), "h"((uint16_t)3) : "memory");
}
__device__ __forceinline__ void ldsm4(uint32_t (&r)[4], uint32_t addr) {
  asm volatile("ldmatrix.sync.aligned.m8n8.x4.shared.b16 {%0,%1,%2,%3}, [%4];"
               : "=r"(r[0]), "=r"(r[1]), "=r"(r[2]), "=r"(r[3]) : "r"(addr) : "memory");
}
__device__ __forceinline__ void ldsm4t(uint32_t (&r)[4], uint32_t addr) {
  asm volatile("ldmatrix.sync.aligned.m8n8.x4.trans.shared.b16 {%0,%1,%2,%3}, [%4];"
               : "=r"(r[0]), "=r"(r[1]), "=r"(r[2]), "=r"(r[3]) : "r"(addr) : "memory");
}
__device__ __forceinline__ void stsm4(uint32_t addr, uint32_t r0, uint32_t r1, uint32_t r2, uint32_t r3) {
  asm volatile("stmatrix.sync.aligned.m8n8.x4.shared.b16 [%0], {%1,%2,%3,%4};"
               ::"r"(addr), "r"(r0), "r"(r1), "r"(r2), "r"(r3) : "memory");
}
__device__ __forceinline__ void mma16816(float (&c)[4], const uint32_t (&a)[4], uint32_t b0, uint32_t b1) {
  asm volatile("mma.sync.aligned.m16n8k16.row.col.f32.bf16.bf16.f32 {%0,%1,%2,%3},{%4,%5,%6,%7},{%8,%9},{%0,%1,%2,%3};"
               : "+f"(c[0]), "+f"(c[1]), "+f"(c[2]), "+f"(c[3])
               : "r"(a[0]), "r"(a[1]), "r"(a[2]), "r"(a[3]), "r"(b0), "r"(b1));
}
__device__ __forceinline__ uint32_t pack2(float lo, float hi) {
  uint32_t r; asm("cvt.rn.bf16x2.f32 %0, %1, %2;" : "=r"(r) : "f"(hi), "f"(lo)); return r;
}
__device__ __forceinline__ float blo(uint32_t w) { return __uint_as_float(w << 16); }
__device__ __forceinline__ float bhi(uint32_t w) { return __uint_as_float(w & 0xFFFF0000u); }
__device__ __forceinline__ uint32_t hsub2(uint32_t a, uint32_t b) { uint32_t r; asm("sub.rn.bf16x2 %0, %1, %2;" : "=r"(r) : "r"(a), "r"(b)); return r; }
__device__ __forceinline__ uint32_t hadd2(uint32_t a, uint32_t b) { uint32_t r; asm("add.rn.bf16x2 %0, %1, %2;" : "=r"(r) : "r"(a), "r"(b)); return r; }
__device__ __forceinline__ uint32_t hmul2(uint32_t a, uint32_t b) { uint32_t r; asm("mul.rn.bf16x2 %0, %1, %2;" : "=r"(r) : "r"(a), "r"(b)); return r; }
__device__ __forceinline__ uint32_t hfma2(uint32_t a, uint32_t b, uint32_t c) { uint32_t r; asm("fma.rn.bf16x2 %0, %1, %2, %3;" : "=r"(r) : "r"(a), "r"(b), "r"(c)); return r; }
__device__ __forceinline__ uint32_t hmax2(uint32_t a, uint32_t b) { uint32_t r; asm("max.bf16x2 %0, %1, %2;" : "=r"(r) : "r"(a), "r"(b)); return r; }
__device__ __forceinline__ uint32_t hmin2(uint32_t a, uint32_t b) { uint32_t r; asm("min.bf16x2 %0, %1, %2;" : "=r"(r) : "r"(a), "r"(b)); return r; }
__device__ __forceinline__ float ex2(float x) { float r; asm("ex2.approx.ftz.f32 %0, %1;" : "=f"(r) : "f"(x)); return r; }
__device__ __forceinline__ float rcp(float x) { float r; asm("rcp.approx.ftz.f32 %0, %1;" : "=f"(r) : "f"(x)); return r; }
__device__ __forceinline__ void ld_rlx4(uint32_t (&r)[4], const uint4* p) {
  asm volatile("{\n.reg .b128 v;\nld.relaxed.gpu.global.b128 v, [%4];\nmov.b128 {%0,%1,%2,%3}, v;\n}"
               : "=r"(r[0]), "=r"(r[1]), "=r"(r[2]), "=r"(r[3]) : "l"(p) : "memory");
}
__device__ __forceinline__ void st_rlx4(uint4* p, uint32_t a, uint32_t b, uint32_t c, uint32_t d) {
  asm volatile("{\n.reg .b128 v;\nmov.b128 v, {%1,%2,%3,%4};\nst.relaxed.gpu.global.b128 [%0], v;\n}"
               ::"l"(p), "r"(a), "r"(b), "r"(c), "r"(d) : "memory");
}
__device__ __forceinline__ void st_rlx2(uint2* p, uint32_t a, uint32_t b) {
  asm volatile("{\n.reg .b64 v;\nmov.b64 v, {%1,%2};\nst.relaxed.gpu.global.b64 [%0], v;\n}" ::"l"(p), "r"(a), "r"(b) : "memory");
}
__device__ __forceinline__ uint32_t ld_rlx1(const uint32_t* p) {
  uint32_t r; asm volatile("ld.relaxed.gpu.global.b32 %0, [%1];" : "=r"(r) : "l"(p) : "memory"); return r;
}
__device__ __forceinline__ void st_rlx1(uint32_t* p, uint32_t a) {
  asm volatile("st.relaxed.gpu.global.b32 [%0], %1;" ::"l"(p), "r"(a) : "memory");
}
__device__ __forceinline__ void ld_rlx2(uint32_t& a, uint32_t& b, const uint2* p) {
  asm volatile("{\n.reg .b64 v;\nld.relaxed.gpu.global.b64 v, [%2];\nmov.b64 {%0,%1}, v;\n}" : "=r"(a), "=r"(b) : "l"(p) : "memory");
}
__device__ __forceinline__ void bulk_g2s(uint32_t dst, const void* src, uint32_t bytes, uint32_t bar) {
  asm volatile("cp.async.bulk.shared::cluster.global.mbarrier::complete_tx::bytes [%0], [%1], %2, [%3];"
               ::"r"(dst), "l"(src), "r"(bytes), "r"(bar) : "memory");
}
__device__ __forceinline__ uint32_t tg(uint32_t w, uint32_t T) { return (w & 0xFFFFFFFEu) | T; }
__device__ __forceinline__ uint32_t bad4(uint32_t a, uint32_t b, uint32_t c, uint32_t d, uint32_t T) {
  uint32_t u, v;
  asm("lop3.b32 %0, %1, %2, %3, 0x7E;" : "=r"(u) : "r"(a), "r"(b), "r"(T));
  asm("lop3.b32 %0, %1, %2, %3, 0x7E;" : "=r"(v) : "r"(c), "r"(d), "r"(T));
  return u | v;
}

__device__ __forceinline__ void ld_chunk(uint32_t (&a)[4][4], const uint4* p) {
#pragma unroll
  for (int s = 0; s < 4; s++) ld_rlx4(a[s], p + s * 32);
}
__device__ __forceinline__ void lds_chunk(uint32_t (&a)[4][4], uint32_t addr) {
#pragma unroll
  for (int s = 0; s < 4; s++)
    asm volatile("ld.shared.v4.b32 {%0,%1,%2,%3}, [%4];" : "=r"(a[s][0]), "=r"(a[s][1]), "=r"(a[s][2]), "=r"(a[s][3])
                 : "r"(addr + s * 512) : "memory");
}
__device__ __forceinline__ void chk_chunk(uint32_t (&a)[4][4], const uint4* p, uint32_t T) {
  int it = 0;
#pragma unroll 1
  while (__any_sync(0xffffffffu, bad4(a[0][0], a[1][0], a[2][0], a[3][0], T) & 1)) {
    ld_chunk(a, p);
    if (++it > (1 << 18)) break;
  }
}

__device__ __forceinline__ void wgmma_rs_n48(float (&d)[24], const uint32_t (&a)[4], uint32_t descB, int scaleD) {
  asm volatile("{\n.reg .pred p;\n.reg .b64 db;\nsetp.ne.b32 p, %29, 0;\nmov.b64 db, {%28, 0x40000040};\n"
    "wgmma.mma_async.sync.aligned.m64n48k16.f32.bf16.bf16 {%0,%1,%2,%3,%4,%5,%6,%7,%8,%9,%10,%11,%12,%13,%14,%15,%16,%17,%18,%19,%20,%21,%22,%23}, {%24,%25,%26,%27}, db, p, 1, 1, 1;\n}\n"
    : "+f"(d[0]),"+f"(d[1]),"+f"(d[2]),"+f"(d[3]),"+f"(d[4]),"+f"(d[5]),"+f"(d[6]),"+f"(d[7]),"+f"(d[8]),"+f"(d[9]),"+f"(d[10]),"+f"(d[11]),"+f"(d[12]),"+f"(d[13]),"+f"(d[14]),"+f"(d[15]),"+f"(d[16]),"+f"(d[17]),"+f"(d[18]),"+f"(d[19]),"+f"(d[20]),"+f"(d[21]),"+f"(d[22]),"+f"(d[23])
    : "r"(a[0]), "r"(a[1]), "r"(a[2]), "r"(a[3]), "r"(descB), "r"(scaleD));
}
__device__ __forceinline__ void wgmma_rs_n64(float (&d)[32], const uint32_t (&a)[4], uint32_t descB, int scaleD) {
  asm volatile("{\n.reg .pred p;\n.reg .b64 db;\nsetp.ne.b32 p, %37, 0;\nmov.b64 db, {%36, 0x40000040};\n"
    "wgmma.mma_async.sync.aligned.m64n64k16.f32.bf16.bf16 {%0,%1,%2,%3,%4,%5,%6,%7,%8,%9,%10,%11,%12,%13,%14,%15,%16,%17,%18,%19,%20,%21,%22,%23,%24,%25,%26,%27,%28,%29,%30,%31}, {%32,%33,%34,%35}, db, p, 1, 1, 1;\n}\n"
    : "+f"(d[0]),"+f"(d[1]),"+f"(d[2]),"+f"(d[3]),"+f"(d[4]),"+f"(d[5]),"+f"(d[6]),"+f"(d[7]),"+f"(d[8]),"+f"(d[9]),"+f"(d[10]),"+f"(d[11]),"+f"(d[12]),"+f"(d[13]),"+f"(d[14]),"+f"(d[15]),"+f"(d[16]),"+f"(d[17]),"+f"(d[18]),"+f"(d[19]),"+f"(d[20]),"+f"(d[21]),"+f"(d[22]),"+f"(d[23]),"+f"(d[24]),"+f"(d[25]),"+f"(d[26]),"+f"(d[27]),"+f"(d[28]),"+f"(d[29]),"+f"(d[30]),"+f"(d[31])
    : "r"(a[0]), "r"(a[1]), "r"(a[2]), "r"(a[3]), "r"(descB), "r"(scaleD));
}
__device__ __forceinline__ void wgmma_rs_n128(float (&d)[64], const uint32_t (&a)[4], uint32_t descB, int scaleD) {
  asm volatile("{\n.reg .pred p;\n.reg .b64 db;\nsetp.ne.b32 p, %69, 0;\nmov.b64 db, {%68, 0x40000040};\n"
    "wgmma.mma_async.sync.aligned.m64n128k16.f32.bf16.bf16 {%0,%1,%2,%3,%4,%5,%6,%7,%8,%9,%10,%11,%12,%13,%14,%15,%16,%17,%18,%19,%20,%21,%22,%23,%24,%25,%26,%27,%28,%29,%30,%31,%32,%33,%34,%35,%36,%37,%38,%39,%40,%41,%42,%43,%44,%45,%46,%47,%48,%49,%50,%51,%52,%53,%54,%55,%56,%57,%58,%59,%60,%61,%62,%63}, {%64,%65,%66,%67}, db, p, 1, 1, 1;\n}\n"
    : "+f"(d[0]),"+f"(d[1]),"+f"(d[2]),"+f"(d[3]),"+f"(d[4]),"+f"(d[5]),"+f"(d[6]),"+f"(d[7]),"+f"(d[8]),"+f"(d[9]),"+f"(d[10]),"+f"(d[11]),"+f"(d[12]),"+f"(d[13]),"+f"(d[14]),"+f"(d[15]),"+f"(d[16]),"+f"(d[17]),"+f"(d[18]),"+f"(d[19]),"+f"(d[20]),"+f"(d[21]),"+f"(d[22]),"+f"(d[23]),"+f"(d[24]),"+f"(d[25]),"+f"(d[26]),"+f"(d[27]),"+f"(d[28]),"+f"(d[29]),"+f"(d[30]),"+f"(d[31]),"+f"(d[32]),"+f"(d[33]),"+f"(d[34]),"+f"(d[35]),"+f"(d[36]),"+f"(d[37]),"+f"(d[38]),"+f"(d[39]),"+f"(d[40]),"+f"(d[41]),"+f"(d[42]),"+f"(d[43]),"+f"(d[44]),"+f"(d[45]),"+f"(d[46]),"+f"(d[47]),"+f"(d[48]),"+f"(d[49]),"+f"(d[50]),"+f"(d[51]),"+f"(d[52]),"+f"(d[53]),"+f"(d[54]),"+f"(d[55]),"+f"(d[56]),"+f"(d[57]),"+f"(d[58]),"+f"(d[59]),"+f"(d[60]),"+f"(d[61]),"+f"(d[62]),"+f"(d[63])
    : "r"(a[0]), "r"(a[1]), "r"(a[2]), "r"(a[3]), "r"(descB), "r"(scaleD));
}
__device__ __forceinline__ void wgmma_ss_n72_t11(float (&d)[36], uint32_t descA, uint32_t descB, int scaleD) {
  asm volatile("{\n.reg .pred p;\n.reg .b64 da, db;\nsetp.ne.b32 p, %38, 0;\nmov.b64 da, {%36, 0x40000040};\nmov.b64 db, {%37, 0x40000040};\n"
    "wgmma.mma_async.sync.aligned.m64n72k16.f32.bf16.bf16 {%0,%1,%2,%3,%4,%5,%6,%7,%8,%9,%10,%11,%12,%13,%14,%15,%16,%17,%18,%19,%20,%21,%22,%23,%24,%25,%26,%27,%28,%29,%30,%31,%32,%33,%34,%35}, da, db, p, 1, 1, 1, 1;\n}\n"
    : "+f"(d[0]),"+f"(d[1]),"+f"(d[2]),"+f"(d[3]),"+f"(d[4]),"+f"(d[5]),"+f"(d[6]),"+f"(d[7]),"+f"(d[8]),"+f"(d[9]),"+f"(d[10]),"+f"(d[11]),"+f"(d[12]),"+f"(d[13]),"+f"(d[14]),"+f"(d[15]),"+f"(d[16]),"+f"(d[17]),"+f"(d[18]),"+f"(d[19]),"+f"(d[20]),"+f"(d[21]),"+f"(d[22]),"+f"(d[23]),"+f"(d[24]),"+f"(d[25]),"+f"(d[26]),"+f"(d[27]),"+f"(d[28]),"+f"(d[29]),"+f"(d[30]),"+f"(d[31]),"+f"(d[32]),"+f"(d[33]),"+f"(d[34]),"+f"(d[35])
    : "r"(descA), "r"(descB), "r"(scaleD));
}

#define TSTAMP(i) do {} while (0)
#define TS2(w, i) do {} while (0)

constexpr float LOG2E = 1.4426950408889634f;

__device__ __forceinline__ void feat_exp(const uint32_t (&P)[4], float (&e)[16]) {
  uint32_t a = hmax2(P[0], P[2]), b = hmax2(P[1], P[3]);
  uint32_t mx = hmax2(__byte_perm(a, b, 0x5410), __byte_perm(a, b, 0x7632));
  a = hmin2(P[0], P[2]); b = hmin2(P[1], P[3]);
  uint32_t mn = hmin2(__byte_perm(a, b, 0x5410), __byte_perm(a, b, 0x7632));
  mx = hmax2(mx, __shfl_xor_sync(0xffffffffu, mx, 1));
  mn = hmin2(mn, __shfl_xor_sync(0xffffffffu, mn, 1));
  mx = hmax2(mx, __shfl_xor_sync(0xffffffffu, mx, 2));
  mn = hmin2(mn, __shfl_xor_sync(0xffffffffu, mn, 2));
  float mx0 = -blo(mx) * LOG2E, mx1 = -bhi(mx) * LOG2E, mn0 = blo(mn) * LOG2E, mn1 = bhi(mn) * LOG2E;
  float v[8] = {blo(P[0]), bhi(P[0]), blo(P[1]), bhi(P[1]), blo(P[2]), bhi(P[2]), blo(P[3]), bhi(P[3])};
#pragma unroll
  for (int i = 0; i < 8; i++) {
    bool r1 = (i >> 1) & 1;
    e[i]     = ex2(fmaf(v[i],  LOG2E, r1 ? mx1 : mx0));
    e[8 + i] = ex2(fmaf(v[i], -LOG2E, r1 ? mn1 : mn0));
  }
}

__global__ void __cluster_dims__(2, 1, 1) __launch_bounds__(384, 1)
fused_kernel(const __grid_constant__ Maps maps, const __nv_bfloat16* __restrict__ x, const __nv_bfloat16* __restrict__ wphi,
             const __nv_bfloat16* __restrict__ wo, const __nv_bfloat16* __restrict__ wg_, const __nv_bfloat16* __restrict__ wu_,
             const __nv_bfloat16* __restrict__ wd_, __nv_bfloat16* __restrict__ out) {
  extern __shared__ __align__(1024) unsigned char smem[];
  const uint32_t sb = smem_u32(smem);
  const int tid = threadIdx.x, lane = tid & 31;
  const int warp = __shfl_sync(0xffffffffu, tid >> 5, 0);
  const uint32_t rank = blockIdx.x & 1;
  const int cl = blockIdx.x >> 1;
  int quad, qi;
  if (cl < 4) { quad = 15; qi = cl; }
  else if (cl < 36) { quad = (cl - 4) & 7; qi = (cl - 4) >> 3; }
  else { qi = (cl - 36) / 7; quad = 8 + (cl - 36) - 7 * qi; }
  const int rb = quad, hg = 2 * qi + rank;
  const int rb3 = (quad & ~1) + rank, jf = 4 * (quad & 1) + qi;

  if (warp >= 8) {
    asm volatile("setmaxnreg.dec.sync.aligned.u32 24;");
    if (lane == 0) {
      if (warp == 8) {
#pragma unroll
        for (int k = 0; k < 9; k++) {
          const int s = k < 3 ? k : (k < 6 ? k + 3 : k - 3);
          const uint32_t bar = sb + SM_FULL + s * 8;
          mbar_init(bar, 1);
          mbar_expect_tx(bar, SLOT);
          if (s >= 3 && s < 6) tma2d(sb + s * SLOT, &maps.w, 512 + hg * 64, (s - 3) * 192, bar);
          else tma3d(sb + s * SLOT, &maps.x, 0, rb * 128 + (s >= 6 ? 64 : 0), 3 * (s % 3), bar);
        }
      } else if (warp == 9) {
        mbar_init(sb + SM_MISCB, 2);
        mbar_init(sb + SM_KVB, 32);
        mbar_expect_tx(sb + SM_MISCB, 2048);
        bulk_g2s(sb + SM_WPHI, wphi + hg * 1024, 2048, sb + SM_MISCB);
      } else if (warp == 10) {
#pragma unroll 1
        for (int i = 0; i < 16; i++) {
          mbar_init(sb + SM_XF + i * 8, 1);
          mbar_expect_tx(sb + SM_XF + i * 8, (i == 8 || i == 12) ? 20480 : 16384);
          if (i < 12) mbar_init(sb + SM_XE + i * 8, 4);
        }
      } else {
        *reinterpret_cast<volatile unsigned*>(smem + SM_EPOCH) = atomicAdd(&g_start, 1u) / NCTA;
      }
      asm volatile("fence.mbarrier_init.release.cluster;" ::: "memory");
    }
    if (tid == 256) TS2(0, 18);
    __syncwarp();
    if (warp != 11) bar_sync(0, 352);
    asm volatile("barrier.cluster.arrive.relaxed.aligned;" ::: "memory");
    if (warp == 8) {
      asm volatile("barrier.cluster.wait.aligned;" ::: "memory");
      if (lane == 0) {
        const CUtensorMap* mg = jf == 7 ? &maps.g7 : &maps.g;
        const CUtensorMap* mu = jf == 7 ? &maps.u7 : &maps.u;
        asm volatile("prefetch.tensormap [%0];" ::"l"(&maps.wo) : "memory");
        asm volatile("prefetch.tensormap [%0];" ::"l"(mg) : "memory");
        asm volatile("prefetch.tensormap [%0];" ::"l"(mu) : "memory");
        asm volatile("prefetch.tensormap [%0];" ::"l"(&maps.d) : "memory");
#pragma unroll 1
        for (int s = ST_WV; s < ST_XC; s++) {
          if (s == ST_SCR1) continue;
          mbar_wait(sb + SM_EMPTY + (s - 9) * 8);
          const uint32_t dst = sb + (s >= 18 ? s - 18 : s - 9) * SLOT, bar = sb + SM_FULL + s * 8;
          if (s < ST_WO) tma2d(dst, &maps.w, (s < ST_WQ ? 1024 : 0) + hg * 64, (s < ST_WQ ? s - ST_WV : s - ST_WQ) * 192, bar);
          else { mbar_wait(bar - 8); tma2d(dst, &maps.wo, hg * 64, (s - ST_WO) * 192, bar); }
        }
        const int jc = jf == 7 ? 0 : jf;
        int slot = (ST_GU + 1 - rank) % NSLOT;
#pragma unroll 1
        for (int s = ST_GU + 1 - rank; s < NSTAGE; s += 2) {
          mbar_wait(sb + SM_EMPTY + (s - 9) * 8);
          if (s > ST_GU && s < ST_GU + THR) mbar_wait(sb + SM_FULL + (s - 1) * 8);
          const uint32_t dst = sb + slot * SLOT, bar = sb + SM_FULL + s * 8;
          if (s < ST_D) {
#pragma unroll 1
            for (int i = 0; i < 3; i++) {
              const int u = (s - ST_GU) * 3 + i;
              tma3d_mc(dst + i * 8192, mg, (u >> 4) * 64, jc, (u & 15) * 32, bar);
              tma3d_mc(dst + i * 8192 + 4096, mu, (u >> 4) * 64, jc, (u & 15) * 32, bar);
            }
          } else {
            tma2d_mc(dst, &maps.d, ((jf + 1 + (s - ST_D)) & 7) * 64, jf * 176, bar);
          }
          slot += 2; if (slot >= NSLOT) slot -= NSLOT;
        }
      }
      __syncwarp();
    } else {
      asm volatile("barrier.cluster.wait.aligned;" ::: "memory");
      if (warp == 11) {
#pragma unroll
        for (int i = 0; i < 4; i++)
          reinterpret_cast<uint4*>(smem + SM_ONES)[lane + 32 * i] = make_uint4(0x3F803F80u, 0x3F803F80u, 0x3F803F80u, 0x3F803F80u);
        fence_async_smem();
        __syncwarp();
        if (lane == 0) { mbar_arrive(sb + SM_MISCB); TS2(0, 19); }
      }
      mbar_wait(sb + SM_MISCB);
      const unsigned epoch = *reinterpret_cast<volatile unsigned*>(smem + SM_EPOCH);
      const uint32_t T = (epoch & 1) ^ 1;
      if (warp == 11) {
        reinterpret_cast<float4*>(&g_kv[T][blockIdx.x * 128])[lane] = make_float4(0.f, 0.f, 0.f, 0.f);
        if (lane < 8) g_z[T][blockIdx.x * 8 + lane] = 0.f;
        mbar_wait(sb + SM_FULL + (ST_WK + 2) * 8);
        if (lane == 0) {
          asm volatile("cp.async.bulk.prefetch.L2.global [%0], 4096;" ::"l"((const char*)wo + blockIdx.x * 4096) : "memory");
          asm volatile("cp.async.bulk.prefetch.L2.global [%0], 11008;" ::"l"((const char*)wg_ + blockIdx.x * 11008) : "memory");
          asm volatile("cp.async.bulk.prefetch.L2.global [%0], 11008;" ::"l"((const char*)wu_ + blockIdx.x * 11008) : "memory");
          asm volatile("cp.async.bulk.prefetch.L2.global [%0], 11008;" ::"l"((const char*)wd_ + blockIdx.x * 11008) : "memory");
          const unsigned target = (epoch + 1) * 32;
          unsigned v; int it = 0;
#pragma unroll 1
          do {
            asm volatile("ld.acquire.gpu.global.u32 %0, [%1];" : "=r"(v) : "l"(&g_kvcnt[hg * 32]) : "memory");
            if (++it > (1 << 18)) break;
          } while ((int)(v - target) < 0);
          TS2(0, 26);
        }
        __syncwarp();
        {
          const char* src = reinterpret_cast<const char*>(&g_kv[T ^ 1][hg * 2048]) + lane * 16;
#pragma unroll
          for (int i = 0; i < 16; i++)
            asm volatile("cp.async.cg.shared.global [%0], [%1], 16;" ::"r"(sb + SM_KV32 + lane * 16 + i * 512), "l"(src + i * 512) : "memory");
          asm volatile("cp.async.cg.shared.global [%0], [%1], 16;" ::"r"(sb + SM_ONES + lane * 16), "l"(&g_z[T ^ 1][hg * 128 + lane * 4]) : "memory");
          asm volatile("cp.async.mbarrier.arrive.noinc.shared::cta.b64 [%0];" ::"r"(sb + SM_KVB) : "memory");
        }
      } else {
        const int w = warp - 9;
        st_rlx4(reinterpret_cast<uint4*>(&g_st[2 * rb + w][hg][0]) + lane, T ^ 1, T ^ 1, T ^ 1, T ^ 1);
        if (lane < 8) st_rlx4(&g_o[2 * rb + w][hg][lane >> 1][3][30 + (lane & 1)], T ^ 1, T ^ 1, T ^ 1, T ^ 1);
        st_rlx4(&g_part[2 * rb3 + w][lane >> 2][jf][lane & 3][3][30], T ^ 1, T ^ 1, T ^ 1, T ^ 1);
        st_rlx4(&g_part[2 * rb3 + w][lane >> 2][jf][lane & 3][3][31], T ^ 1, T ^ 1, T ^ 1, T ^ 1);
        bar_sync(6 + w, 160);
        if (lane == 0) {
          asm volatile("fence.acq_rel.gpu;" ::: "memory");
          TS2(w, 25);
          asm volatile("red.relaxed.gpu.global.add.u32 [%0], 1;" ::"l"(&g_kvcnt[hg * 32]) : "memory");
        }
        mbar_wait(sb + SM_KVB);
        if (w == 0) { mbar_wait(sb + SM_EMPTY + 11 * 8); mbar_wait(sb + SM_EMPTY + 12 * 8); mbar_wait(sb + SM_EMPTY + 13 * 8); }
#pragma unroll 1
        for (int ph = 0; ph < 2; ph++) {
          const int use = 2 * ph + w, r = ph ? 2 * rb3 + w : 2 * rb + w;
          const uint32_t* pw = ph ? reinterpret_cast<const uint32_t*>(&g_st[r][lane >> 2][(lane & 3) * 16 + 15])
                                  : reinterpret_cast<const uint32_t*>(&g_o[r][lane >> 2][lane & 3][3][31]);
          const char* src = reinterpret_cast<const char*>(ph ? &g_h[r][0][0][0][0] : &g_o[r][0][0][0][0]);
          uint32_t ready = 0; int it = 0;
#pragma unroll 1
          for (int p = 0; p < 4; p++) {
            const uint32_t need = ph ? 0xFFFFFFFFu : 0xFFu << (8 * p);
#pragma unroll 1
            while ((ready & need) != need) {
              ready = __ballot_sync(0xffffffffu, ((ld_rlx1(pw) ^ T) & 1) == 0);
              if (++it > (1 << 18)) break;
            }
            if (lane == 0) {
              if (p == 0) TS2(w, 27 + ph);
              if (use > 0) mbar_wait(sb + SM_XE + ((use - 1) * 4 + p) * 8);
              const uint32_t bar = sb + SM_XF + (use * 4 + p) * 8;
              if (ph && p == 0) bulk_g2s(sb + SM_KV32 + w * 4096, &g_st[r][0][0], 4096, bar);
              bulk_g2s(sb + 2 * SLOT + p * 16384, src + p * 16384, 16384, bar);
            }
            __syncwarp();
          }
        }
      }
    }
    asm volatile("barrier.cluster.arrive.relaxed.aligned;" ::: "memory");
    asm volatile("barrier.cluster.wait.aligned;" ::: "memory");
  } else {
    asm volatile("setmaxnreg.inc.sync.aligned.u32 240;");
    if (lane == 0) {
#pragma unroll 1
      for (int d = warp; d + 9 < NSTAGE; d += 8) {
        mbar_init(sb + SM_EMPTY + d * 8, st_empty_cnt(d));
        mbar_init(sb + SM_FULL + (d + 9) * 8, 1);
        mbar_expect_tx(sb + SM_FULL + (d + 9) * 8, st_bytes(d + 9));
      }
      asm volatile("fence.mbarrier_init.release.cluster;" ::: "memory");
    }
    __syncwarp();
    bar_sync(0, 352);
    asm volatile("barrier.cluster.arrive.relaxed.aligned;" ::: "memory");
    const int wg = warp >> 2, wq = warp & 3, g = lane >> 2, t = lane & 3;
    const bool lead = (tid & 127) == 0;
    const uint32_t db = ((sb & 0x3FFFF) >> 4) | (512u << 16);
    auto release = [&](int d) {
      const int s = d + NSLOT;
      if (s < NSTAGE) mbar_arrive_cluster(sb + SM_EMPTY + d * 8, s >= ST_GU ? (uint32_t)(s & 1) : rank);
    };
    const uint32_t lrow = (uint32_t)(wq * 16 + (lane & 7) + ((lane >> 3) & 1) * 8) * 128;
    const uint32_t lx = lane & 7, lhi = lane >> 4;
    TSTAMP(0);

    float r0, r1;
    uint32_t E[4][8];
    uint32_t T = 0;
    {
      uint32_t A[32][4];
      float acc[32];
      const int sx = wg ? ST_X1 : ST_X0;
      {
        const uint32_t base = sb + sx * SLOT + lrow;
        float s0 = 0.f, s1 = 0.f;
#pragma unroll
        for (int c = 0; c < 8; c++) {
          if (c % 3 == 0) mbar_wait(sb + SM_FULL + (sx + c / 3) * 8);
#pragma unroll
          for (int k = 0; k < 4; k++) ldsm4(A[4 * c + k], base + c * 8192 + (((2 * k + lhi) ^ lx) << 4));
          const uint32_t u0 = hadd2(hadd2(hadd2(A[4 * c][0], A[4 * c][2]), hadd2(A[4 * c + 1][0], A[4 * c + 1][2])),
                                    hadd2(hadd2(A[4 * c + 2][0], A[4 * c + 2][2]), hadd2(A[4 * c + 3][0], A[4 * c + 3][2])));
          const uint32_t u1 = hadd2(hadd2(hadd2(A[4 * c][1], A[4 * c][3]), hadd2(A[4 * c + 1][1], A[4 * c + 1][3])),
                                    hadd2(hadd2(A[4 * c + 2][1], A[4 * c + 2][3]), hadd2(A[4 * c + 3][1], A[4 * c + 3][3])));
          s0 += blo(u0) + bhi(u0); s1 += blo(u1) + bhi(u1);
        }
        s0 += __shfl_xor_sync(0xffffffffu, s0, 1); s1 += __shfl_xor_sync(0xffffffffu, s1, 1);
        s0 += __shfl_xor_sync(0xffffffffu, s0, 2); s1 += __shfl_xor_sync(0xffffffffu, s1, 2);
        TSTAMP(17);
        asm volatile("barrier.cluster.wait.aligned;" ::: "memory");
        if (lane < 3) release(sx + lane);
        s0 *= (1.f / 512.f); s1 *= (1.f / 512.f);
        const uint32_t m0 = pack2(s0, s0), m1 = pack2(s1, s1);
        float q0 = 0.f, q1 = 0.f;
#pragma unroll
        for (int c = 0; c < 8; c++) {
#pragma unroll
          for (int ks = 4 * c; ks < 4 * c + 4; ks += 2) {
            uint32_t v0, v1;
            A[ks][0] = hsub2(A[ks][0], m0); A[ks][1] = hsub2(A[ks][1], m1);
            A[ks][2] = hsub2(A[ks][2], m0); A[ks][3] = hsub2(A[ks][3], m1);
            A[ks + 1][0] = hsub2(A[ks + 1][0], m0); A[ks + 1][1] = hsub2(A[ks + 1][1], m1);
            A[ks + 1][2] = hsub2(A[ks + 1][2], m0); A[ks + 1][3] = hsub2(A[ks + 1][3], m1);
            v0 = hfma2(A[ks][2], A[ks][2], hmul2(A[ks][0], A[ks][0]));
            v1 = hfma2(A[ks][3], A[ks][3], hmul2(A[ks][1], A[ks][1]));
            v0 = hfma2(A[ks + 1][2], A[ks + 1][2], hfma2(A[ks + 1][0], A[ks + 1][0], v0));
            v1 = hfma2(A[ks + 1][3], A[ks + 1][3], hfma2(A[ks + 1][1], A[ks + 1][1], v1));
            q0 += blo(v0) + bhi(v0); q1 += blo(v1) + bhi(v1);
          }
          if (c % 3 == 0) mbar_wait(sb + SM_FULL + (ST_WK + c / 3) * 8);
          wg_fence();
#pragma unroll
          for (int ks = 4 * c; ks < 4 * c + 4; ks++) wgmma_rs_n64(acc, A[ks], DESC((ST_WK % NSLOT) * SLOT + ks * 2048), ks != 0);
          wg_commit();
          if (c == 4) { wg_wait<2>(); if (lead) release(ST_WK); }
        }
        q0 += __shfl_xor_sync(0xffffffffu, q0, 1); q1 += __shfl_xor_sync(0xffffffffu, q1, 1);
        q0 += __shfl_xor_sync(0xffffffffu, q0, 2); q1 += __shfl_xor_sync(0xffffffffu, q1, 2);
        s0 -= blo(m0); s1 -= blo(m1);
        r0 = rsqrtf(fmaxf(q0 * (1.f / 512.f) - s0 * s0, 0.f) + 1e-5f);
        r1 = rsqrtf(fmaxf(q1 * (1.f / 512.f) - s1 * s1, 0.f) + 1e-5f);
      }
      TSTAMP(1);
      uint32_t a[4][4];
      auto scale_pack = [&]() {
#pragma unroll
        for (int h = 0; h < 4; h++) {
          a[h][0] = pack2(acc[8 * h + 0] * r0, acc[8 * h + 1] * r0); a[h][1] = pack2(acc[8 * h + 2] * r1, acc[8 * h + 3] * r1);
          a[h][2] = pack2(acc[8 * h + 4] * r0, acc[8 * h + 5] * r0); a[h][3] = pack2(acc[8 * h + 6] * r1, acc[8 * h + 7] * r1);
        }
      };
      auto project = [&](const uint32_t (&b)[4][4]) {
        float pp[4][2][4];
#pragma unroll
        for (int h = 0; h < 4; h++) {
#pragma unroll
          for (int i = 0; i < 4; i++) { pp[h][0][i] = 0.f; pp[h][1][i] = 0.f; }
          mma16816(pp[h][0], a[h], b[h][0], b[h][1]);
          mma16816(pp[h][1], a[h], b[h][2], b[h][3]);
        }
#pragma unroll
        for (int h = 0; h < 4; h++) {
          a[h][0] = pack2(pp[h][0][0], pp[h][0][1]); a[h][1] = pack2(pp[h][0][2], pp[h][0][3]);
          a[h][2] = pack2(pp[h][1][0], pp[h][1][1]); a[h][3] = pack2(pp[h][1][2], pp[h][1][3]);
        }
      };
      const uint32_t wpa = sb + SM_WPHI + ((lane & 7) + ((lane >> 3) & 1) * 8) * 32 + lhi * 16;
      const uint32_t scr = sb + (wg ? (ST_SCR1 % NSLOT) : (ST_SCR0 % NSLOT)) * SLOT;
      {
        uint32_t b[4][4];
        mbar_wait(sb + SM_MISCB);
        T = (*reinterpret_cast<volatile unsigned*>(smem + SM_EPOCH) & 1) ^ 1;
#pragma unroll
        for (int h = 0; h < 4; h++) ldsm4t(b[h], wpa + h * 512);
        wg_wait<0>();
        if (lead) { release(ST_WK + 1); release(ST_WK + 2); }
        TSTAMP(2);
        scale_pack();
        project(b);
      }
      mbar_wait(sb + SM_EMPTY + (wg ? ST_SCR1 - NSLOT : ST_SCR0 - NSLOT) * 8);
      auto vgroup = [&](int c) {
        if (c % 3 == 0) mbar_wait(sb + SM_FULL + (ST_WV + c / 3) * 8);
        if (c == 0) wg_fence();
#pragma unroll
        for (int ks = 4 * c; ks < 4 * c + 4; ks++) wgmma_rs_n64(acc, A[ks], DESC((ST_WV % NSLOT) * SLOT + ks * 2048), ks != 0);
      };
#pragma unroll
      for (int h = 0; h < 4; h++) {
        vgroup(2 * h);
        float f[16];
        feat_exp(a[h], f);
        float sp0 = (f[0] + f[1]) + (f[4] + f[5]), sp1 = (f[2] + f[3]) + (f[6] + f[7]);
        float sn0 = (f[8] + f[9]) + (f[12] + f[13]), sn1 = (f[10] + f[11]) + (f[14] + f[15]);
        sp0 += __shfl_xor_sync(0xffffffffu, sp0, 1); sp1 += __shfl_xor_sync(0xffffffffu, sp1, 1);
        sn0 += __shfl_xor_sync(0xffffffffu, sn0, 1); sn1 += __shfl_xor_sync(0xffffffffu, sn1, 1);
        vgroup(2 * h + 1);
        sp0 += __shfl_xor_sync(0xffffffffu, sp0, 2); sp1 += __shfl_xor_sync(0xffffffffu, sp1, 2);
        sn0 += __shfl_xor_sync(0xffffffffu, sn0, 2); sn1 += __shfl_xor_sync(0xffffffffu, sn1, 2);
        sp0 = rcp(sp0); sp1 = rcp(sp1); sn0 = rcp(sn0); sn1 = rcp(sn1);
        const uint32_t dst = scr + (h >> 1) * 8192 + lrow;
        stsm4(dst + ((((h & 1) * 4 + lhi) ^ lx) << 4), pack2(f[0] * sp0, f[1] * sp0), pack2(f[2] * sp1, f[3] * sp1),
              pack2(f[4] * sp0, f[5] * sp0), pack2(f[6] * sp1, f[7] * sp1));
        stsm4(dst + ((((h & 1) * 4 + 2 + lhi) ^ lx) << 4), pack2(f[8] * sn0, f[9] * sn0), pack2(f[10] * sn1, f[11] * sn1),
              pack2(f[12] * sn0, f[13] * sn0), pack2(f[14] * sn1, f[15] * sn1));
      }
      wg_commit();
      TSTAMP(3);
      wg_wait<0>();
      if ((tid & 127) < 3) release(ST_WV + (tid & 127));
      TSTAMP(4);
      {
        scale_pack();
#pragma unroll
        for (int h = 0; h < 4; h++) stsm4(scr + 16384 + lrow + (((2 * h + lhi) ^ lx) << 4), a[h][0], a[h][1], a[h][2], a[h][3]);
        fence_async_smem();
        bar_sync(3, 256);
        float kv[36];
        wg_fence();
#pragma unroll
        for (int ks = 0; ks < 8; ks++) {
          const uint32_t sk = (ks < 4 ? (ST_SCR0 % NSLOT) : (ST_SCR1 % NSLOT)) * SLOT + (ks & 3) * 2048;
          const uint32_t dv = (DESC(sk + 16384) & 0xFFFFu) | (((SM_ONES - sk - 16384) >> 4) << 16);
          wgmma_ss_n72_t11(kv, DESC(sk) + wg * 512, dv, ks != 0);
        }
        wg_commit();
        wg_wait<0>();
        if (lead) { release(ST_SCR0); release(ST_SCR1); }
        const int hl = 2 * wg + (wq >> 1), f = (wq & 1) * 16 + g;
        float* kvp = &g_kv[T ^ 1][((hg * 4 + hl) * 32 + f) * 16 + 2 * t];
        float* zp = &g_z[T ^ 1][(hg * 4 + hl) * 32 + f];
        float c[8];
#pragma unroll
        for (int i = 0; i < 8; i++) c[i] = hl >= 2 ? (hl == 3 ? kv[24 + i] : kv[16 + i]) : (hl == 1 ? kv[8 + i] : kv[i]);
#pragma unroll
        for (int n = 0; n < 2; n++) {
          asm volatile("red.relaxed.gpu.global.add.v2.f32 [%0], {%1,%2};" ::"l"(kvp + n * 8), "f"(c[4 * n]), "f"(c[4 * n + 1]) : "memory");
          asm volatile("red.relaxed.gpu.global.add.v2.f32 [%0], {%1,%2};" ::"l"(kvp + n * 8 + 128), "f"(c[4 * n + 2]), "f"(c[4 * n + 3]) : "memory");
        }
        if (t < 2) asm volatile("red.relaxed.gpu.global.add.f32 [%0], %1;" ::"l"(zp + t * 8), "f"(t ? kv[34] : kv[32]) : "memory");
        bar_arrive(6 + wg, 160);
      }
      TSTAMP(5);
      {
        if (wg == 1) bar_sync(4, 256);
#pragma unroll
        for (int i = 0; i < 3; i++) {
          mbar_wait(sb + SM_FULL + (ST_WQ + i) * 8);
          wg_fence();
#pragma unroll
          for (int kk = 0; kk < 12; kk++)
            if (12 * i + kk < 32) wgmma_rs_n64(acc, A[(12 * i + kk) & 31], DESC((ST_WQ % NSLOT) * SLOT + (12 * i + kk) * 2048), (i | kk) != 0);
          wg_commit();
          if (i > 0) { wg_wait<1>(); if (lead) release(ST_WQ + i - 1); }
        }
        if (wg == 0) bar_arrive(4, 256);
        uint32_t b[4][4];
#pragma unroll
        for (int h = 0; h < 4; h++) ldsm4t(b[h], wpa + h * 512);
        wg_wait<0>();
        if (lead) release(ST_WQ + 2);
        TSTAMP(6);
        scale_pack();
        project(b);
#pragma unroll
        for (int h = 0; h < 4; h++) {
          float e[16];
          feat_exp(a[h], e);
#pragma unroll
          for (int i = 0; i < 8; i++) E[h][i] = pack2(e[2 * i], e[2 * i + 1]);
        }
      }
      TSTAMP(7);
    }
    const int rh = 2 * rb + wg;
    const uint32_t xb = sb + 2 * SLOT + wq * 2048 + lane * 16;
    mbar_wait(sb + SM_KVB);
    {
      const int r = tid & 127;
      const float4* src = reinterpret_cast<const float4*>(smem + SM_KV32) + r;
#pragma unroll
      for (int i = 0; i < 4; i++) {
        const float4 a = src[i * 128];
        *reinterpret_cast<uint2*>(smem + SM_KVS + (i * 32 + (r >> 2)) * 48 + (r & 3) * 8) = make_uint2(pack2(a.x, a.y), pack2(a.z, a.w));
      }
      const uint32_t zz = pack2(reinterpret_cast<const float*>(smem + SM_ONES)[r], 1.0f);
      *reinterpret_cast<uint4*>(smem + SM_KVS + r * 48 + 32) = make_uint4(zz, zz, zz, zz);
      bar_sync(1 + wg, 128);
    }
    TSTAMP(8);
    {
      uint4* op = &g_o[rh][hg][wq][0][lane];
#pragma unroll
      for (int h = 0; h < 4; h++) {
        uint32_t b0[4], b1[4], b2[4];
        const uint32_t kb = sb + SM_KVS + (h * 32 + lane) * 48;
        ldsm4t(b0, kb); ldsm4t(b1, kb + 16); ldsm4t(b2, kb + 32);
        const uint32_t ep[4] = {E[h][0], E[h][1], E[h][2], E[h][3]}, en[4] = {E[h][4], E[h][5], E[h][6], E[h][7]};
        float np0[4] = {0, 0, 0, 0}, np1[4] = {0, 0, 0, 0}, nn0[4] = {0, 0, 0, 0}, nn1[4] = {0, 0, 0, 0}, dp[4] = {0, 0, 0, 0}, dn[4] = {0, 0, 0, 0};
        mma16816(dp, ep, b2[0], b2[1]);  mma16816(dn, en, b2[2], b2[3]);
        mma16816(np0, ep, b0[0], b0[1]); mma16816(nn0, en, b0[2], b0[3]);
        mma16816(np1, ep, b1[0], b1[1]); mma16816(nn1, en, b1[2], b1[3]);
        const float i0 = rcp(fmaf(dp[0], dn[1], fmaf(dn[0], dp[1], 1e-6f * dp[1] * dn[1])));
        const float i1 = rcp(fmaf(dp[2], dn[3], fmaf(dn[2], dp[3], 1e-6f * dp[3] * dn[3])));
        const float cp0 = dn[1] * i0, cn0 = dp[1] * i0, cp1 = dn[3] * i1, cn1 = dp[3] * i1;
        st_rlx4(op + h * 32,
                tg(pack2(fmaf(np0[0], cp0, nn0[0] * cn0), fmaf(np0[1], cp0, nn0[1] * cn0)), T),
                pack2(fmaf(np0[2], cp1, nn0[2] * cn1), fmaf(np0[3], cp1, nn0[3] * cn1)),
                pack2(fmaf(np1[0], cp0, nn1[0] * cn0), fmaf(np1[1], cp0, nn1[1] * cn0)),
                pack2(fmaf(np1[2], cp1, nn1[2] * cn1), fmaf(np1[3], cp1, nn1[3] * cn1)));
      }
    }
    TSTAMP(9);

    {
      uint32_t xr[16];
      {
        const uint32_t* xp = reinterpret_cast<const uint32_t*>(x + (size_t)(rh * 64 + wq * 16 + g) * 512 + hg * 64 + 2 * t);
#pragma unroll
        for (int i = 0; i < 8; i++) { xr[2 * i] = __ldg(xp + 4 * i); xr[2 * i + 1] = __ldg(xp + 8 * 256 + 4 * i); }
      }
      uint32_t A[8][4][4];
      const uint4* op = &g_o[rh][0][wq][0][lane];
      float acc[32];
#pragma unroll
      for (int p = 0; p < 4; p++) {
        mbar_wait(sb + SM_XF + (wg * 4 + p) * 8);
        lds_chunk(A[2 * p], xb + p * 16384);
        lds_chunk(A[2 * p + 1], xb + p * 16384 + 8192);
        chk_chunk(A[2 * p], op + 2 * p * 512, T);
        chk_chunk(A[2 * p + 1], op + (2 * p + 1) * 512, T);
        if (lane == 0) mbar_arrive(sb + SM_XE + (wg * 4 + p) * 8);
#pragma unroll
        for (int c = 2 * p; c < 2 * p + 2; c++) {
          if (c % 3 == 0) mbar_wait(sb + SM_FULL + (ST_WO + c / 3) * 8);
          wg_fence();
#pragma unroll
          for (int s = 0; s < 4; s++)
            wgmma_rs_n64(acc, A[c][s], DESC(((ST_WO + c / 3) % NSLOT) * SLOT + ((c % 3) * 4 + s) * 2048), (c | s) != 0);
          wg_commit();
        }
      }
      wg_wait<0>();
      if ((tid & 127) < 3) release(ST_WO + (tid & 127));
      TSTAMP(10);
      uint32_t hw[16];
      float s0 = 0.f, s1 = 0.f, q0 = 0.f, q1 = 0.f;
#pragma unroll
      for (int i = 0; i < 8; i++) {
        hw[2 * i]     = pack2(blo(xr[2 * i]) + acc[4 * i], bhi(xr[2 * i]) + acc[4 * i + 1]);
        hw[2 * i + 1] = pack2(blo(xr[2 * i + 1]) + acc[4 * i + 2], bhi(xr[2 * i + 1]) + acc[4 * i + 3]);
      }
      uint4* hp_ = &g_h[rh][hg][wq][0][lane];
#pragma unroll
      for (int s = 0; s < 4; s++) st_rlx4(hp_ + s * 32, tg(hw[4 * s], T), hw[4 * s + 1], hw[4 * s + 2], hw[4 * s + 3]);
#pragma unroll
      for (int i = 0; i < 8; i++) {
        float a = blo(hw[2 * i]), b = bhi(hw[2 * i]);
        s0 += a + b; q0 = fmaf(a, a, q0); q0 = fmaf(b, b, q0);
        a = blo(hw[2 * i + 1]); b = bhi(hw[2 * i + 1]);
        s1 += a + b; q1 = fmaf(a, a, q1); q1 = fmaf(b, b, q1);
      }
      s0 += __shfl_xor_sync(0xffffffffu, s0, 1); s1 += __shfl_xor_sync(0xffffffffu, s1, 1);
      q0 += __shfl_xor_sync(0xffffffffu, q0, 1); q1 += __shfl_xor_sync(0xffffffffu, q1, 1);
      s0 += __shfl_xor_sync(0xffffffffu, s0, 2); s1 += __shfl_xor_sync(0xffffffffu, s1, 2);
      q0 += __shfl_xor_sync(0xffffffffu, q0, 2); q1 += __shfl_xor_sync(0xffffffffu, q1, 2);
      if (t < 2) st_rlx2(&g_st[rh][hg][wq * 16 + g + t * 8], tg(__float_as_uint(t ? s1 : s0), T), __float_as_uint(t ? q1 : q0));
      uint32_t hx = T;
#pragma unroll
      for (int i = 0; i < 4; i++) hx |= (hw[4 * i] & 1u) << (i + 1);
      st_rlx1(&g_hx[rh][hg][wq][lane], hx);
    }
    TSTAMP(11);

    const int rh3 = 2 * rb3 + wg;
    uint32_t HH[11][4];
    {
      uint32_t A[8][4][4];
      const uint4* hp_ = &g_h[rh3][0][wq][0][lane];
      const uint32_t dg = (db & 0xFFFFu) | (256u << 16);
      uint32_t m0, m1;
      mbar_wait(sb + SM_XF + ((2 + wg) * 4) * 8);
      {
        const uint2* sp = &g_st[rh3][2 * t][wq * 16 + g];
        const uint2* ss = reinterpret_cast<const uint2*>(smem + SM_KV32 + wg * 4096) + 2 * t * 64 + wq * 16 + g;
        uint2 a0 = ss[0], a1 = ss[64], b0 = ss[8], b1 = ss[72];
        int it = 0;
#pragma unroll 1
        while (__any_sync(0xffffffffu, bad4(a0.x, a1.x, b0.x, b1.x, T) & 1)) {
          ld_rlx2(a0.x, a0.y, sp); ld_rlx2(a1.x, a1.y, sp + 64); ld_rlx2(b0.x, b0.y, sp + 8); ld_rlx2(b1.x, b1.y, sp + 72);
          if (++it > (1 << 18)) break;
        }
        float s0 = __uint_as_float(a0.x) + __uint_as_float(a1.x), q0 = __uint_as_float(a0.y) + __uint_as_float(a1.y);
        float s1 = __uint_as_float(b0.x) + __uint_as_float(b1.x), q1 = __uint_as_float(b0.y) + __uint_as_float(b1.y);
        s0 += __shfl_xor_sync(0xffffffffu, s0, 1); s1 += __shfl_xor_sync(0xffffffffu, s1, 1);
        q0 += __shfl_xor_sync(0xffffffffu, q0, 1); q1 += __shfl_xor_sync(0xffffffffu, q1, 1);
        s0 += __shfl_xor_sync(0xffffffffu, s0, 2); s1 += __shfl_xor_sync(0xffffffffu, s1, 2);
        q0 += __shfl_xor_sync(0xffffffffu, q0, 2); q1 += __shfl_xor_sync(0xffffffffu, q1, 2);
        s0 *= (1.f / 512.f); s1 *= (1.f / 512.f);
        r0 = rcp(fmaxf(q0 * (1.f / 512.f) - s0 * s0, 0.f) + 1e-5f);
        r1 = rcp(fmaxf(q1 * (1.f / 512.f) - s1 * s1, 0.f) + 1e-5f);
        m0 = pack2(s0, s0); m1 = pack2(s1, s1);
      }
      TSTAMP(12);
#define UOFF(u) ((((ST_GU + (u) / 3) % NSLOT) * SLOT + ((u) % 3) * 8192) >> 4)
#define UNIT_PRE(u)  do { if ((u) % 3 == 0) mbar_wait(sb + SM_FULL + (ST_GU + (u) / 3) * 8); wg_fence(); } while (0)
#define UNIT_POST(u) do { wg_commit(); if ((u) % 3 == 1 && (u) > 3) { wg_wait<2>(); if (lead) release(ST_GU + (u) / 3 - 1); } } while (0)
#pragma unroll
      for (int ps = 0; ps < 2; ps++) {
        float acc[64];
#pragma unroll
        for (int k = 0; k < 16; k++) {
          const int u = 16 * ps + k, c = k >> 1;
          if (ps == 0 && (k & 3) == 0) {
            const int p = k >> 2;
            if (p > 0) mbar_wait(sb + SM_XF + ((2 + wg) * 4 + p) * 8);
            lds_chunk(A[2 * p], xb + p * 16384);
            lds_chunk(A[2 * p + 1], xb + p * 16384 + 8192);
            chk_chunk(A[2 * p], hp_ + 2 * p * 512, T);
            chk_chunk(A[2 * p + 1], hp_ + (2 * p + 1) * 512, T);
            if (lane == 0) {
              if (wg == 0) mbar_arrive(sb + SM_XE + (8 + p) * 8);
              else if (p > 0) release(ST_XC + p - 1);
            }
          }
          if (ps == 0 && (k & 1) == 0) {
#pragma unroll
            for (int s = 0; s < 4; s++) {
              A[c][s][0] = hsub2(A[c][s][0], m0); A[c][s][1] = hsub2(A[c][s][1], m1);
              A[c][s][2] = hsub2(A[c][s][2], m0); A[c][s][3] = hsub2(A[c][s][3], m1);
            }
          }
          UNIT_PRE(u);
          wgmma_rs_n128(acc, A[c][(k & 1) * 2], dg + UOFF(u), k != 0);
          wgmma_rs_n128(acc, A[c][(k & 1) * 2 + 1], dg + UOFF(u) + 128, 1);
          UNIT_POST(u);
        }
        wg_wait<0>();
#pragma unroll
        for (int s = 0; s < 4; s++) {
          HH[4 * ps + s][0] = pack2(acc[8 * s + 0] * acc[32 + 8 * s + 0] * r0, acc[8 * s + 1] * acc[32 + 8 * s + 1] * r0);
          HH[4 * ps + s][1] = pack2(acc[8 * s + 2] * acc[32 + 8 * s + 2] * r1, acc[8 * s + 3] * acc[32 + 8 * s + 3] * r1);
          HH[4 * ps + s][2] = pack2(acc[8 * s + 4] * acc[32 + 8 * s + 4] * r0, acc[8 * s + 5] * acc[32 + 8 * s + 5] * r0);
          HH[4 * ps + s][3] = pack2(acc[8 * s + 6] * acc[32 + 8 * s + 6] * r1, acc[8 * s + 7] * acc[32 + 8 * s + 7] * r1);
        }
      }
      {
        float ag[24], au[24];
#pragma unroll
        for (int k = 0; k < 16; k++) {
          const int u = 32 + k, c = k >> 1;
          UNIT_PRE(u);
          wgmma_rs_n48(ag, A[c][(k & 1) * 2], dg + UOFF(u), k != 0);
          wgmma_rs_n48(au, A[c][(k & 1) * 2], dg + UOFF(u) + 256, k != 0);
          wgmma_rs_n48(ag, A[c][(k & 1) * 2 + 1], dg + UOFF(u) + 128, 1);
          wgmma_rs_n48(au, A[c][(k & 1) * 2 + 1], dg + UOFF(u) + 256 + 128, 1);
          UNIT_POST(u);
        }
        wg_wait<0>();
        TSTAMP(13);
#pragma unroll
        for (int s = 0; s < 3; s++) {
          HH[8 + s][0] = pack2(ag[8 * s + 0] * au[8 * s + 0] * r0, ag[8 * s + 1] * au[8 * s + 1] * r0);
          HH[8 + s][1] = pack2(ag[8 * s + 2] * au[8 * s + 2] * r1, ag[8 * s + 3] * au[8 * s + 3] * r1);
          HH[8 + s][2] = pack2(ag[8 * s + 4] * au[8 * s + 4] * r0, ag[8 * s + 5] * au[8 * s + 5] * r0);
          HH[8 + s][3] = pack2(ag[8 * s + 6] * au[8 * s + 6] * r1, ag[8 * s + 7] * au[8 * s + 7] * r1);
        }
      }
    }
    TSTAMP(14);

    {
      float acc[32], sum[32];
      uint32_t in[4][4][4];
      const uint4* inb = &g_part[rh3][jf][0][wq][0][lane];
      uint4* outb = &g_part[rh3][0][jf][wq][0][lane];
      const uint32_t* hint = reinterpret_cast<const uint32_t*>(&g_part[rh3][jf][(jf - 1 - lane) & 7][wq][3][31]);
      int slot = ST_D % NSLOT;
      auto step = [&](int st) {
        uint32_t pk[16];
        if (st > 0) {
#pragma unroll
          for (int i = 0; i < 16; i++) pk[i] = pack2(acc[2 * i], acc[2 * i + 1]);
        }
        mbar_wait(sb + SM_FULL + (ST_D + st) * 8);
        wg_fence();
#pragma unroll
        for (int s = 0; s < 4; s++) wgmma_rs_n64(acc, HH[s], db + slot * (SLOT >> 4) + s * 128, s != 0);
        if (st > 0) {
          uint4* p = outb + ((jf + st) & 7) * 4096;
#pragma unroll
          for (int s = 0; s < 4; s++) st_rlx4(p + s * 32, tg(pk[4 * s], T), pk[4 * s + 1], pk[4 * s + 2], pk[4 * s + 3]);
        }
#pragma unroll
        for (int s = 4; s < 11; s++) wgmma_rs_n64(acc, HH[s], db + slot * (SLOT >> 4) + s * 128, 1);
        wg_commit();
        if (++slot == NSLOT) slot = 0;
      };
      auto fetch = [&](int q) { ld_chunk(in[q & 3], inb + ((jf - 1 - q) & 7) * 512); };
      auto add = [&](int q) {
        chk_chunk(in[q & 3], inb + ((jf - 1 - q) & 7) * 512, T);
#pragma unroll
        for (int i = 0; i < 16; i++) { sum[2 * i] += blo(in[q & 3][i >> 2][i & 3]); sum[2 * i + 1] += bhi(in[q & 3][i >> 2][i & 3]); }
      };
      uint32_t ready = 0; int it = 0;
      auto await = [&](int q) {
#pragma unroll 1
        while (!((ready >> q) & 1)) {
          ready = __ballot_sync(0xffffffffu, ((ld_rlx1(hint) ^ T) & 1) == 0);
          if (++it > (1 << 18)) break;
        }
      };
      ld_chunk(in[3], &g_h[rh3][jf][wq][0][lane]);
      uint32_t hx = ld_rlx1(&g_hx[rh3][jf][wq][lane]);
#pragma unroll 1
      for (int st = 0; st < 4; st++) { step(st); wg_wait<0>(); }
      step(4);
#pragma unroll 1
      while (__any_sync(0xffffffffu, (hx ^ T) & 1)) {
        hx = ld_rlx1(&g_hx[rh3][jf][wq][lane]);
        if (++it > (1 << 18)) break;
      }
#pragma unroll
      for (int s = 0; s < 4; s++) in[3][s][0] = (in[3][s][0] & 0xFFFFFFFEu) | ((hx >> (s + 1)) & 1u);
#pragma unroll
      for (int i = 0; i < 16; i++) { sum[2 * i] = blo(in[3][i >> 2][i & 3]); sum[2 * i + 1] = bhi(in[3][i >> 2][i & 3]); }
      fetch(0); wg_wait<0>();
      step(5); fetch(1); wg_wait<0>();
      step(6); fetch(2); add(0); wg_wait<0>();
      step(7); fetch(3); add(1);
      await(4); fetch(4); add(2);
      await(5); fetch(5); add(3);
      wg_wait<0>();
      TSTAMP(15);
#pragma unroll
      for (int i = 0; i < 32; i++) sum[i] += acc[i];
      await(6); fetch(6); add(4); add(5); add(6);
      uint32_t* op = reinterpret_cast<uint32_t*>(out + (size_t)(rh3 * 64 + wq * 16 + g) * 512 + jf * 64 + 2 * t);
#pragma unroll
      for (int i = 0; i < 8; i++) {
        op[4 * i]           = pack2(sum[4 * i], sum[4 * i + 1]);
        op[8 * 256 + 4 * i] = pack2(sum[4 * i + 2], sum[4 * i + 3]);
      }
    }
    TSTAMP(16);
    asm volatile("barrier.cluster.arrive.relaxed.aligned;" ::: "memory");
    asm volatile("barrier.cluster.wait.aligned;" ::: "memory");
  }
}

typedef CUresult (*EncodeFn)(CUtensorMap*, CUtensorMapDataType, cuuint32_t, void*, const cuuint64_t*, const cuuint64_t*,
                             const cuuint32_t*, const cuuint32_t*, CUtensorMapInterleave, CUtensorMapSwizzle,
                             CUtensorMapL2promotion, CUtensorMapFloatOOBfill);

void encode(EncodeFn fn, CUtensorMap* m, const void* base, int rank, const cuuint64_t* dims, const cuuint64_t* strides,
            const cuuint32_t* box) {
  cuuint32_t es[3] = {1, 1, 1};
  fn(m, CU_TENSOR_MAP_DATA_TYPE_BFLOAT16, (cuuint32_t)rank, const_cast<void*>(base), dims, strides, box, es,
     CU_TENSOR_MAP_INTERLEAVE_NONE, CU_TENSOR_MAP_SWIZZLE_128B, CU_TENSOR_MAP_L2_PROMOTION_L2_256B,
     CU_TENSOR_MAP_FLOAT_OOB_FILL_NONE);
}

}

extern "C" void kernel_launch(void* const* d_in, const int* in_sizes, int n_in, void* d_out, int out_size) {
  (void)in_sizes; (void)n_in; (void)out_size;
  const __nv_bfloat16* x    = (const __nv_bfloat16*)d_in[0];
  const __nv_bfloat16* wqkv = (const __nv_bfloat16*)d_in[1];
  const __nv_bfloat16* wphi = (const __nv_bfloat16*)d_in[2];
  const __nv_bfloat16* wo   = (const __nv_bfloat16*)d_in[3];
  const __nv_bfloat16* wg   = (const __nv_bfloat16*)d_in[5];
  const __nv_bfloat16* wu   = (const __nv_bfloat16*)d_in[6];
  const __nv_bfloat16* wd   = (const __nv_bfloat16*)d_in[7];

  static EncodeFn fn = nullptr;
  if (!fn) {
    void* p = nullptr;
    cudaDriverEntryPointQueryResult qr;
    cudaGetDriverEntryPoint("cuTensorMapEncodeTiled", &p, cudaEnableDefault, &qr);
    fn = (EncodeFn)p;
    cudaFuncSetAttribute(fused_kernel, cudaFuncAttributeMaxDynamicSharedMemorySize, SM_TOTAL);
  }
  Maps maps;
  {
    cuuint64_t d[3] = {64, 2048, 8}, s[2] = {1024, 128}; cuuint32_t b[3] = {64, 64, 3};
    encode(fn, &maps.x, x, 3, d, s, b);
  }
  {
    cuuint64_t d[2] = {1536, 512}, s[1] = {3072}; cuuint32_t b[2] = {64, 192};
    encode(fn, &maps.w, wqkv, 2, d, s, b);
  }
  {
    cuuint64_t d[2] = {512, 512}, s[1] = {1024}; cuuint32_t b[2] = {64, 192};
    encode(fn, &maps.wo, wo, 2, d, s, b);
  }
  {
    cuuint64_t d[3] = {176, 7, 512}, d7[3] = {144, 1, 512}, s[2] = {352, 2752}; cuuint32_t b[3] = {64, 1, 32};
    encode(fn, &maps.g, wg, 3, d, s, b);
    encode(fn, &maps.u, wu, 3, d, s, b);
    encode(fn, &maps.g7, wg + 1232, 3, d7, s, b);
    encode(fn, &maps.u7, wu + 1232, 3, d7, s, b);
  }
  {
    cuuint64_t d[2] = {512, 1376}, s[1] = {1024}; cuuint32_t b[2] = {64, 176};
    encode(fn, &maps.d, wd, 2, d, s, b);
  }
  fused_kernel<<<NCTA, 384, SM_TOTAL>>>(maps, x, wphi, wo, wg, wu, wd, (__nv_bfloat16*)d_out);
}
```

```cpp
#include <cuda_runtime.h>
#include <cuda_bf16.h>
#include <cuda.h>
#include <stdint.h>

#define PROF 0

#define THR 6

namespace {

constexpr int NCTA   = 128;
constexpr int SLOT   = 24576;
constexpr int NSLOT  = 9;
constexpr int NSTAGE = 47;

constexpr int ST_X0   = 0;
constexpr int ST_WK   = 3;
constexpr int ST_X1   = 6;
constexpr int ST_SCR0 = 9;
constexpr int ST_WV   = 10;
constexpr int ST_SCR1 = 13;
constexpr int ST_WQ   = 14;
constexpr int ST_WO   = 17;
constexpr int ST_XC   = 20;
constexpr int ST_GU   = 23;
constexpr int ST_D    = 39;

__host__ __device__ constexpr int st_bytes(int s) { return s >= ST_D ? 22528 : 24576; }
__host__ __device__ constexpr int st_empty_cnt(int d) {
  return ((d < 3 || (d >= 6 && d < 9) || (d >= ST_XC && d < ST_GU)) ? 4 : 2) * (d + 9 >= ST_GU && d + 9 < NSTAGE ? 2 : 1);
}

constexpr int SM_ONES = NSLOT * SLOT;
constexpr int SM_WPHI = SM_ONES + 2048;
constexpr int SM_KVS  = SM_WPHI + 2048;
constexpr int SM_KV32 = 4 * SLOT + 16384;
constexpr int SM_BAR  = SM_KVS + 6144;
constexpr int SM_FULL  = SM_BAR;
constexpr int SM_EMPTY = SM_BAR + NSTAGE * 8;
constexpr int SM_MISCB = SM_BAR + 2 * NSTAGE * 8;
constexpr int SM_KVB   = SM_MISCB + 8;
constexpr int SM_EPOCH = SM_KVB + 8;
constexpr int SM_XF    = SM_EPOCH + 8;
constexpr int SM_XE    = SM_XF + 16 * 8;
constexpr int SM_TOTAL = SM_BAR + 1024;

static_assert(SM_TOTAL == 232448 && SM_XE + 12 * 8 <= SM_TOTAL, "smem budget");

struct Maps { CUtensorMap x, w, wo, g, u, g7, u7, d; };

__device__ uint4    g_o[32][8][4][4][32];
__device__ uint4    g_h[32][8][4][4][32];
__device__ uint32_t g_hx[32][8][4][32];
__device__ uint2    g_st[32][8][64];
__device__ uint4    g_part[32][8][8][4][4][32];
__device__ float    g_kv[2][32 * 32 * 16];
__device__ float    g_z[2][32 * 32];
__device__ unsigned g_kvcnt[8 * 32];
__device__ unsigned g_start;

__device__ __forceinline__ uint32_t smem_u32(const void* p) { return (uint32_t)__cvta_generic_to_shared(p); }
__device__ __forceinline__ void mbar_init(uint32_t bar, int cnt) {
  asm volatile("mbarrier.init.shared::cta.b64 [%0], %1;" ::"r"(bar), "r"(cnt) : "memory");
}
__device__ __forceinline__ void mbar_expect_tx(uint32_t bar, uint32_t bytes) {
  asm volatile("mbarrier.arrive.expect_tx.shared::cta.b64 _, [%0], %1;" ::"r"(bar), "r"(bytes) : "memory");
}
__device__ __forceinline__ void mbar_arrive(uint32_t bar) {
  asm volatile("mbarrier.arrive.shared::cta.b64 _, [%0];" ::"r"(bar) : "memory");
}
__device__ __forceinline__ void mbar_arrive_cluster(uint32_t bar, uint32_t rank) {
  asm volatile("{\n.reg .b32 ra;\nmapa.shared::cluster.u32 ra, %0, %1;\n"
               "mbarrier.arrive.shared::cluster.b64 _, [ra];\n}" ::"r"(bar), "r"(rank) : "memory");
}
__device__ __forceinline__ bool mbar_try(uint32_t bar) {
  uint32_t ok;
  asm volatile("{\n.reg .pred p;\nmbarrier.try_wait.parity.shared::cta.b64 p, [%1], 0;\nselp.u32 %0, 1, 0, p;\n}"
               : "=r"(ok) : "r"(bar) : "memory");
  return ok != 0;
}
__device__ __forceinline__ bool mbar_test1(uint32_t bar) {
  uint32_t ok;
  asm volatile("{\n.reg .pred p;\nmbarrier.test_wait.parity.shared::cta.b64 p, [%1], 1;\nselp.u32 %0, 1, 0, p;\n}"
               : "=r"(ok) : "r"(bar) : "memory");
  return ok != 0;
}
__device__ __forceinline__ void mbar_wait(uint32_t bar) {
  int it = 0;
#pragma unroll 1
  while (!mbar_try(bar)) {
    if (++it > (1 << 20)) __trap();
  }
}
__device__ __forceinline__ void bar_sync(int id, int n)   { asm volatile("bar.sync %0, %1;" ::"r"(id), "r"(n) : "memory"); }
__device__ __forceinline__ void bar_arrive(int id, int n) { asm volatile("bar.arrive %0, %1;" ::"r"(id), "r"(n) : "memory"); }
__device__ __forceinline__ void fence_async_smem() { asm volatile("fence.proxy.async.shared::cta;" ::: "memory"); }
__device__ __forceinline__ void wg_fence()  { asm volatile("wgmma.fence.sync.aligned;" ::: "memory"); }
__device__ __forceinline__ void wg_commit() { asm volatile("wgmma.commit_group.sync.aligned;" ::: "memory"); }
template <int N> __device__ __forceinline__ void wg_wait() { asm volatile("wgmma.wait_group.sync.aligned %0;" ::"n"(N) : "memory"); }
#define DESC(off) (db + ((uint32_t)(off) >> 4))
__device__ __forceinline__ void tma2d(uint32_t dst, const CUtensorMap* m, int c0, int c1, uint32_t bar) {
  asm volatile("cp.async.bulk.tensor.2d.shared::cluster.global.mbarrier::complete_tx::bytes [%0], [%1, {%3, %4}], [%2];"
               ::"r"(dst), "l"(m), "r"(bar), "r"(c0), "r"(c1) : "memory");
}
__device__ __forceinline__ void tma2d_mc(uint32_t dst, const CUtensorMap* m, int c0, int c1, uint32_t bar) {
  asm volatile("cp.async.bulk.tensor.2d.shared::cluster.global.mbarrier::complete_tx::bytes.multicast::cluster [%0], [%1, {%3, %4}], [%2], %5;"
               ::"r"(dst), "l"(m), "r"(bar), "r"(c0), "r"(c1), "h"((uint16_t)3) : "memory");
}
__device__ __forceinline__ void tma3d(uint32_t dst, const CUtensorMap* m, int c0, int c1, int c2, uint32_t bar) {
  asm volatile("cp.async.bulk.tensor.3d.shared::cluster.global.mbarrier::complete_tx::bytes [%0], [%1, {%3, %4, %5}], [%2];"
               ::"r"(dst), "l"(m), "r"(bar), "r"(c0), "r"(c1), "r"(c2) : "memory");
}
__device__ __forceinline__ void tma3d_mc(uint32_t dst, const CUtensorMap* m, int c0, int c1, int c2, uint32_t bar) {
  asm volatile("cp.async.bulk.tensor.3d.shared::cluster.global.mbarrier::complete_tx::bytes.multicast::cluster [%0], [%1, {%3, %4, %5}], [%2], %6;"
               ::"r"(dst), "l"(m), "r"(bar), "r"(c0), "r"(c1), "r"(c2), "h"((uint16_t)3) : "memory");
}
__device__ __forceinline__ void ldsm4(uint32_t (&r)[4], uint32_t addr) {
  asm volatile("ldmatrix.sync.aligned.m8n8.x4.shared.b16 {%0,%1,%2,%3}, [%4];"
               : "=r"(r[0]), "=r"(r[1]), "=r"(r[2]), "=r"(r[3]) : "r"(addr) : "memory");
}
__device__ __forceinline__ void ldsm4t(uint32_t (&r)[4], uint32_t addr) {
  asm volatile("ldmatrix.sync.aligned.m8n8.x4.trans.shared.b16 {%0,%1,%2,%3}, [%4];"
               : "=r"(r[0]), "=r"(r[1]), "=r"(r[2]), "=r"(r[3]) : "r"(addr) : "memory");
}
__device__ __forceinline__ void stsm4(uint32_t addr, uint32_t r0, uint32_t r1, uint32_t r2, uint32_t r3) {
  asm volatile("stmatrix.sync.aligned.m8n8.x4.shared.b16 [%0], {%1,%2,%3,%4};"
               ::"r"(addr), "r"(r0), "r"(r1), "r"(r2), "r"(r3) : "memory");
}
__device__ __forceinline__ void mma16816(float (&c)[4], const uint32_t (&a)[4], uint32_t b0, uint32_t b1) {
  asm volatile("mma.sync.aligned.m16n8k16.row.col.f32.bf16.bf16.f32 {%0,%1,%2,%3},{%4,%5,%6,%7},{%8,%9},{%0,%1,%2,%3};"
               : "+f"(c[0]), "+f"(c[1]), "+f"(c[2]), "+f"(c[3])
               : "r"(a[0]), "r"(a[1]), "r"(a[2]), "r"(a[3]), "r"(b0), "r"(b1));
}
__device__ __forceinline__ uint32_t pack2(float lo, float hi) {
  uint32_t r; asm("cvt.rn.bf16x2.f32 %0, %1, %2;" : "=r"(r) : "f"(hi), "f"(lo)); return r;
}
__device__ __forceinline__ float blo(uint32_t w) { return __uint_as_float(w << 16); }
__device__ __forceinline__ float bhi(uint32_t w) { return __uint_as_float(w & 0xFFFF0000u); }
__device__ __forceinline__ uint32_t hsub2(uint32_t a, uint32_t b) { uint32_t r; asm("sub.rn.bf16x2 %0, %1, %2;" : "=r"(r) : "r"(a), "r"(b)); return r; }
__device__ __forceinline__ uint32_t hmax2(uint32_t a, uint32_t b) { uint32_t r; asm("max.bf16x2 %0, %1, %2;" : "=r"(r) : "r"(a), "r"(b)); return r; }
__device__ __forceinline__ uint32_t hmin2(uint32_t a, uint32_t b) { uint32_t r; asm("min.bf16x2 %0, %1, %2;" : "=r"(r) : "r"(a), "r"(b)); return r; }
__device__ __forceinline__ float ex2(float x) { float r; asm("ex2.approx.ftz.f32 %0, %1;" : "=f"(r) : "f"(x)); return r; }
__device__ __forceinline__ float rcp(float x) { float r; asm("rcp.approx.ftz.f32 %0, %1;" : "=f"(r) : "f"(x)); return r; }
__device__ __forceinline__ void ld_rlx4(uint32_t (&r)[4], const uint4* p) {
  asm volatile("{\n.reg .b128 v;\nld.relaxed.gpu.global.b128 v, [%4];\nmov.b128 {%0,%1,%2,%3}, v;\n}"
               : "=r"(r[0]), "=r"(r[1]), "=r"(r[2]), "=r"(r[3]) : "l"(p) : "memory");
}
__device__ __forceinline__ void st_rlx4(uint4* p, uint32_t a, uint32_t b, uint32_t c, uint32_t d) {
  asm volatile("{\n.reg .b128 v;\nmov.b128 v, {%1,%2,%3,%4};\nst.relaxed.gpu.global.b128 [%0], v;\n}"
               ::"l"(p), "r"(a), "r"(b), "r"(c), "r"(d) : "memory");
}
__device__ __forceinline__ void st_rlx2(uint2* p, uint32_t a, uint32_t b) {
  asm volatile("{\n.reg .b64 v;\nmov.b64 v, {%1,%2};\nst.relaxed.gpu.global.b64 [%0], v;\n}" ::"l"(p), "r"(a), "r"(b) : "memory");
}
__device__ __forceinline__ uint32_t ld_rlx1(const uint32_t* p) {
  uint32_t r; asm volatile("ld.relaxed.gpu.global.b32 %0, [%1];" : "=r"(r) : "l"(p) : "memory"); return r;
}
__device__ __forceinline__ void st_rlx1(uint32_t* p, uint32_t a) {
  asm volatile("st.relaxed.gpu.global.b32 [%0], %1;" ::"l"(p), "r"(a) : "memory");
}
__device__ __forceinline__ void ld_rlx2(uint32_t& a, uint32_t& b, const uint2* p) {
  asm volatile("{\n.reg .b64 v;\nld.relaxed.gpu.global.b64 v, [%2];\nmov.b64 {%0,%1}, v;\n}" : "=r"(a), "=r"(b) : "l"(p) : "memory");
}
__device__ __forceinline__ void bulk_g2s(uint32_t dst, const void* src, uint32_t bytes, uint32_t bar) {
  asm volatile("cp.async.bulk.shared::cluster.global.mbarrier::complete_tx::bytes [%0], [%1], %2, [%3];"
               ::"r"(dst), "l"(src), "r"(bytes), "r"(bar) : "memory");
}
__device__ __forceinline__ uint32_t tg(uint32_t w, uint32_t T) { return (w & 0xFFFFFFFEu) | T; }
__device__ __forceinline__ uint32_t bad4(uint32_t a, uint32_t b, uint32_t c, uint32_t d, uint32_t T) {
  uint32_t u, v;
  asm("lop3.b32 %0, %1, %2, %3, 0x7E;" : "=r"(u) : "r"(a), "r"(b), "r"(T));
  asm("lop3.b32 %0, %1, %2, %3, 0x7E;" : "=r"(v) : "r"(c), "r"(d), "r"(T));
  return u | v;
}

__device__ __forceinline__ void ld_chunk(uint32_t (&a)[4][4], const uint4* p) {
#pragma unroll
  for (int s = 0; s < 4; s++) ld_rlx4(a[s], p + s * 32);
}
__device__ __forceinline__ void lds_chunk(uint32_t (&a)[4][4], uint32_t addr) {
#pragma unroll
  for (int s = 0; s < 4; s++)
    asm volatile("ld.shared.v4.b32 {%0,%1,%2,%3}, [%4];" : "=r"(a[s][0]), "=r"(a[s][1]), "=r"(a[s][2]), "=r"(a[s][3])
                 : "r"(addr + s * 512) : "memory");
}
__device__ __forceinline__ void chk_chunk(uint32_t (&a)[4][4], const uint4* p, uint32_t T) {
  int it = 0;
#pragma unroll 1
  while (__any_sync(0xffffffffu, bad4(a[0][0], a[1][0], a[2][0], a[3][0], T) & 1)) {
    ld_chunk(a, p);
    if (++it > (1 << 18)) break;
  }
}

__device__ __forceinline__ void wgmma_rs_n48(float (&d)[24], const uint32_t (&a)[4], uint32_t descB, int scaleD) {
  asm volatile("{\n.reg .pred p;\n.reg .b64 db;\nsetp.ne.b32 p, %29, 0;\nmov.b64 db, {%28, 0x40000040};\n"
    "wgmma.mma_async.sync.aligned.m64n48k16.f32.bf16.bf16 {%0,%1,%2,%3,%4,%5,%6,%7,%8,%9,%10,%11,%12,%13,%14,%15,%16,%17,%18,%19,%20,%21,%22,%23}, {%24,%25,%26,%27}, db, p, 1, 1, 1;\n}\n"
    : "+f"(d[0]),"+f"(d[1]),"+f"(d[2]),"+f"(d[3]),"+f"(d[4]),"+f"(d[5]),"+f"(d[6]),"+f"(d[7]),"+f"(d[8]),"+f"(d[9]),"+f"(d[10]),"+f"(d[11]),"+f"(d[12]),"+f"(d[13]),"+f"(d[14]),"+f"(d[15]),"+f"(d[16]),"+f"(d[17]),"+f"(d[18]),"+f"(d[19]),"+f"(d[20]),"+f"(d[21]),"+f"(d[22]),"+f"(d[23])
    : "r"(a[0]), "r"(a[1]), "r"(a[2]), "r"(a[3]), "r"(descB), "r"(scaleD));
}
__device__ __forceinline__ void wgmma_rs_n64(float (&d)[32], const uint32_t (&a)[4], uint32_t descB, int scaleD) {
  asm volatile("{\n.reg .pred p;\n.reg .b64 db;\nsetp.ne.b32 p, %37, 0;\nmov.b64 db, {%36, 0x40000040};\n"
    "wgmma.mma_async.sync.aligned.m64n64k16.f32.bf16.bf16 {%0,%1,%2,%3,%4,%5,%6,%7,%8,%9,%10,%11,%12,%13,%14,%15,%16,%17,%18,%19,%20,%21,%22,%23,%24,%25,%26,%27,%28,%29,%30,%31}, {%32,%33,%34,%35}, db, p, 1, 1, 1;\n}\n"
    : "+f"(d[0]),"+f"(d[1]),"+f"(d[2]),"+f"(d[3]),"+f"(d[4]),"+f"(d[5]),"+f"(d[6]),"+f"(d[7]),"+f"(d[8]),"+f"(d[9]),"+f"(d[10]),"+f"(d[11]),"+f"(d[12]),"+f"(d[13]),"+f"(d[14]),"+f"(d[15]),"+f"(d[16]),"+f"(d[17]),"+f"(d[18]),"+f"(d[19]),"+f"(d[20]),"+f"(d[21]),"+f"(d[22]),"+f"(d[23]),"+f"(d[24]),"+f"(d[25]),"+f"(d[26]),"+f"(d[27]),"+f"(d[28]),"+f"(d[29]),"+f"(d[30]),"+f"(d[31])
    : "r"(a[0]), "r"(a[1]), "r"(a[2]), "r"(a[3]), "r"(descB), "r"(scaleD));
}
__device__ __forceinline__ void wgmma_rs_n128(float (&d)[64], const uint32_t (&a)[4], uint32_t descB, int scaleD) {
  asm volatile("{\n.reg .pred p;\n.reg .b64 db;\nsetp.ne.b32 p, %69, 0;\nmov.b64 db, {%68, 0x40000040};\n"
    "wgmma.mma_async.sync.aligned.m64n128k16.f32.bf16.bf16 {%0,%1,%2,%3,%4,%5,%6,%7,%8,%9,%10,%11,%12,%13,%14,%15,%16,%17,%18,%19,%20,%21,%22,%23,%24,%25,%26,%27,%28,%29,%30,%31,%32,%33,%34,%35,%36,%37,%38,%39,%40,%41,%42,%43,%44,%45,%46,%47,%48,%49,%50,%51,%52,%53,%54,%55,%56,%57,%58,%59,%60,%61,%62,%63}, {%64,%65,%66,%67}, db, p, 1, 1, 1;\n}\n"
    : "+f"(d[0]),"+f"(d[1]),"+f"(d[2]),"+f"(d[3]),"+f"(d[4]),"+f"(d[5]),"+f"(d[6]),"+f"(d[7]),"+f"(d[8]),"+f"(d[9]),"+f"(d[10]),"+f"(d[11]),"+f"(d[12]),"+f"(d[13]),"+f"(d[14]),"+f"(d[15]),"+f"(d[16]),"+f"(d[17]),"+f"(d[18]),"+f"(d[19]),"+f"(d[20]),"+f"(d[21]),"+f"(d[22]),"+f"(d[23]),"+f"(d[24]),"+f"(d[25]),"+f"(d[26]),"+f"(d[27]),"+f"(d[28]),"+f"(d[29]),"+f"(d[30]),"+f"(d[31]),"+f"(d[32]),"+f"(d[33]),"+f"(d[34]),"+f"(d[35]),"+f"(d[36]),"+f"(d[37]),"+f"(d[38]),"+f"(d[39]),"+f"(d[40]),"+f"(d[41]),"+f"(d[42]),"+f"(d[43]),"+f"(d[44]),"+f"(d[45]),"+f"(d[46]),"+f"(d[47]),"+f"(d[48]),"+f"(d[49]),"+f"(d[50]),"+f"(d[51]),"+f"(d[52]),"+f"(d[53]),"+f"(d[54]),"+f"(d[55]),"+f"(d[56]),"+f"(d[57]),"+f"(d[58]),"+f"(d[59]),"+f"(d[60]),"+f"(d[61]),"+f"(d[62]),"+f"(d[63])
    : "r"(a[0]), "r"(a[1]), "r"(a[2]), "r"(a[3]), "r"(descB), "r"(scaleD));
}
__device__ __forceinline__ void wgmma_ss_n72_t11(float (&d)[36], uint32_t descA, uint32_t descB, int scaleD) {
  asm volatile("{\n.reg .pred p;\n.reg .b64 da, db;\nsetp.ne.b32 p, %38, 0;\nmov.b64 da, {%36, 0x40000040};\nmov.b64 db, {%37, 0x40000040};\n"
    "wgmma.mma_async.sync.aligned.m64n72k16.f32.bf16.bf16 {%0,%1,%2,%3,%4,%5,%6,%7,%8,%9,%10,%11,%12,%13,%14,%15,%16,%17,%18,%19,%20,%21,%22,%23,%24,%25,%26,%27,%28,%29,%30,%31,%32,%33,%34,%35}, da, db, p, 1, 1, 1, 1;\n}\n"
    : "+f"(d[0]),"+f"(d[1]),"+f"(d[2]),"+f"(d[3]),"+f"(d[4]),"+f"(d[5]),"+f"(d[6]),"+f"(d[7]),"+f"(d[8]),"+f"(d[9]),"+f"(d[10]),"+f"(d[11]),"+f"(d[12]),"+f"(d[13]),"+f"(d[14]),"+f"(d[15]),"+f"(d[16]),"+f"(d[17]),"+f"(d[18]),"+f"(d[19]),"+f"(d[20]),"+f"(d[21]),"+f"(d[22]),"+f"(d[23]),"+f"(d[24]),"+f"(d[25]),"+f"(d[26]),"+f"(d[27]),"+f"(d[28]),"+f"(d[29]),"+f"(d[30]),"+f"(d[31]),"+f"(d[32]),"+f"(d[33]),"+f"(d[34]),"+f"(d[35])
    : "r"(descA), "r"(descB), "r"(scaleD));
}

#define TSTAMP(i) do {} while (0)
#define TS2(w, i) do {} while (0)

constexpr float LOG2E = 1.4426950408889634f;

__device__ __forceinline__ void feat_exp(const uint32_t (&P)[4], float (&e)[16]) {
  uint32_t a = hmax2(P[0], P[2]), b = hmax2(P[1], P[3]);
  uint32_t mx = hmax2(__byte_perm(a, b, 0x5410), __byte_perm(a, b, 0x7632));
  a = hmin2(P[0], P[2]); b = hmin2(P[1], P[3]);
  uint32_t mn = hmin2(__byte_perm(a, b, 0x5410), __byte_perm(a, b, 0x7632));
  mx = hmax2(mx, __shfl_xor_sync(0xffffffffu, mx, 1));
  mn = hmin2(mn, __shfl_xor_sync(0xffffffffu, mn, 1));
  mx = hmax2(mx, __shfl_xor_sync(0xffffffffu, mx, 2));
  mn = hmin2(mn, __shfl_xor_sync(0xffffffffu, mn, 2));
  float mx0 = -blo(mx) * LOG2E, mx1 = -bhi(mx) * LOG2E, mn0 = blo(mn) * LOG2E, mn1 = bhi(mn) * LOG2E;
  float v[8] = {blo(P[0]), bhi(P[0]), blo(P[1]), bhi(P[1]), blo(P[2]), bhi(P[2]), blo(P[3]), bhi(P[3])};
#pragma unroll
  for (int i = 0; i < 8; i++) {
    bool r1 = (i >> 1) & 1;
    e[i]     = ex2(fmaf(v[i],  LOG2E, r1 ? mx1 : mx0));
    e[8 + i] = ex2(fmaf(v[i], -LOG2E, r1 ? mn1 : mn0));
  }
}

__global__ void __cluster_dims__(2, 1, 1) __launch_bounds__(384, 1)
fused_kernel(const __grid_constant__ Maps maps, const __nv_bfloat16* __restrict__ x, const __nv_bfloat16* __restrict__ wphi,
             const __nv_bfloat16* __restrict__ wo, const __nv_bfloat16* __restrict__ wg_, const __nv_bfloat16* __restrict__ wu_,
             const __nv_bfloat16* __restrict__ wd_, __nv_bfloat16* __restrict__ out) {
  extern __shared__ __align__(1024) unsigned char smem[];
  const uint32_t sb = smem_u32(smem);
  const int tid = threadIdx.x, lane = tid & 31;
  const int warp = __shfl_sync(0xffffffffu, tid >> 5, 0);
  const uint32_t rank = blockIdx.x & 1;
  const int cl = blockIdx.x >> 1;
  int quad, qi;
  if (cl < 4) { quad = 15; qi = cl; }
  else if (cl < 36) { quad = (cl - 4) & 7; qi = (cl - 4) >> 3; }
  else { qi = (cl - 36) / 7; quad = 8 + (cl - 36) - 7 * qi; }
  const int rb = quad, hg = 2 * qi + rank;
  const int rb3 = (quad & ~1) + rank, jf = 4 * (quad & 1) + qi;

  if (warp >= 8) {
    asm volatile("setmaxnreg.dec.sync.aligned.u32 24;");
    if (lane == 0) {
      if (warp == 8) {
#pragma unroll
        for (int k = 0; k < 9; k++) {
          const int s = k < 3 ? k : (k < 6 ? k + 3 : k - 3);
          const uint32_t bar = sb + SM_FULL + s * 8;
          mbar_init(bar, 1);
          mbar_expect_tx(bar, SLOT);
          if (s >= 3 && s < 6) tma2d(sb + s * SLOT, &maps.w, 512 + hg * 64, (s - 3) * 192, bar);
          else tma3d(sb + s * SLOT, &maps.x, 0, rb * 128 + (s >= 6 ? 64 : 0), 3 * (s % 3), bar);
        }
      } else if (warp == 9) {
        mbar_init(sb + SM_MISCB, 2);
        mbar_init(sb + SM_KVB, 32);
        mbar_expect_tx(sb + SM_MISCB, 2048);
        bulk_g2s(sb + SM_WPHI, wphi + hg * 1024, 2048, sb + SM_MISCB);
      } else if (warp == 10) {
#pragma unroll 1
        for (int i = 0; i < 16; i++) {
          mbar_init(sb + SM_XF + i * 8, 1);
          mbar_expect_tx(sb + SM_XF + i * 8, (i == 8 || i == 12) ? 20480 : 16384);
          if (i < 12) mbar_init(sb + SM_XE + i * 8, 4);
        }
      } else {
        *reinterpret_cast<volatile unsigned*>(smem + SM_EPOCH) = atomicAdd(&g_start, 1u) / NCTA;
      }
      asm volatile("fence.mbarrier_init.release.cluster;" ::: "memory");
    }
    if (tid == 256) TS2(0, 18);
    __syncwarp();
    if (warp != 11) bar_sync(0, 352);
    asm volatile("barrier.cluster.arrive.relaxed.aligned;" ::: "memory");
    if (warp == 8) {
      asm volatile("barrier.cluster.wait.aligned;" ::: "memory");
      if (lane == 0) {
        const CUtensorMap* mg = jf == 7 ? &maps.g7 : &maps.g;
        const CUtensorMap* mu = jf == 7 ? &maps.u7 : &maps.u;
        asm volatile("prefetch.tensormap [%0];" ::"l"(&maps.wo) : "memory");
        asm volatile("prefetch.tensormap [%0];" ::"l"(mg) : "memory");
        asm volatile("prefetch.tensormap [%0];" ::"l"(mu) : "memory");
        asm volatile("prefetch.tensormap [%0];" ::"l"(&maps.d) : "memory");
#pragma unroll 1
        for (int s = ST_WV; s < ST_XC; s++) {
          if (s == ST_SCR1) continue;
          mbar_wait(sb + SM_EMPTY + (s - 9) * 8);
          const uint32_t dst = sb + (s >= 18 ? s - 18 : s - 9) * SLOT, bar = sb + SM_FULL + s * 8;
          if (s < ST_WO) tma2d(dst, &maps.w, (s < ST_WQ ? 1024 : 0) + hg * 64, (s < ST_WQ ? s - ST_WV : s - ST_WQ) * 192, bar);
          else { mbar_wait(bar - 8); tma2d(dst, &maps.wo, hg * 64, (s - ST_WO) * 192, bar); }
        }
        const int jc = jf == 7 ? 0 : jf;
        int slot = (ST_GU + 1 - rank) % NSLOT;
#pragma unroll 1
        for (int s = ST_GU + 1 - rank; s < NSTAGE; s += 2) {
          mbar_wait(sb + SM_EMPTY + (s - 9) * 8);
          if (s > ST_GU && s < ST_GU + THR) mbar_wait(sb + SM_FULL + (s - 1) * 8);
          const uint32_t dst = sb + slot * SLOT, bar = sb + SM_FULL + s * 8;
          if (s < ST_D) {
#pragma unroll 1
            for (int i = 0; i < 3; i++) {
              const int u = (s - ST_GU) * 3 + i;
              tma3d_mc(dst + i * 8192, mg, (u >> 4) * 64, jc, (u & 15) * 32, bar);
              tma3d_mc(dst + i * 8192 + 4096, mu, (u >> 4) * 64, jc, (u & 15) * 32, bar);
            }
          } else {
            tma2d_mc(dst, &maps.d, ((jf + 1 + (s - ST_D)) & 7) * 64, jf * 176, bar);
          }
          slot += 2; if (slot >= NSLOT) slot -= NSLOT;
        }
      }
      __syncwarp();
    } else {
      asm volatile("barrier.cluster.wait.aligned;" ::: "memory");
      if (warp == 11) {
#pragma unroll
        for (int i = 0; i < 4; i++)
          reinterpret_cast<uint4*>(smem + SM_ONES)[lane + 32 * i] = make_uint4(0x3F803F80u, 0x3F803F80u, 0x3F803F80u, 0x3F803F80u);
        fence_async_smem();
        __syncwarp();
        if (lane == 0) { mbar_arrive(sb + SM_MISCB); TS2(0, 19); }
      }
      mbar_wait(sb + SM_MISCB);
      const unsigned epoch = *reinterpret_cast<volatile unsigned*>(smem + SM_EPOCH);
      const uint32_t T = (epoch & 1) ^ 1;
      if (warp == 11) {
        reinterpret_cast<float4*>(&g_kv[T][blockIdx.x * 128])[lane] = make_float4(0.f, 0.f, 0.f, 0.f);
        if (lane < 8) g_z[T][blockIdx.x * 8 + lane] = 0.f;
        mbar_wait(sb + SM_FULL + (ST_WK + 2) * 8);
        if (lane == 0) {
          asm volatile("cp.async.bulk.prefetch.L2.global [%0], 4096;" ::"l"((const char*)wo + blockIdx.x * 4096) : "memory");
          asm volatile("cp.async.bulk.prefetch.L2.global [%0], 11008;" ::"l"((const char*)wg_ + blockIdx.x * 11008) : "memory");
          asm volatile("cp.async.bulk.prefetch.L2.global [%0], 11008;" ::"l"((const char*)wu_ + blockIdx.x * 11008) : "memory");
          asm volatile("cp.async.bulk.prefetch.L2.global [%0], 11008;" ::"l"((const char*)wd_ + blockIdx.x * 11008) : "memory");
          const unsigned target = (epoch + 1) * 32;
          unsigned v; int it = 0;
#pragma unroll 1
          do {
            asm volatile("ld.acquire.gpu.global.u32 %0, [%1];" : "=r"(v) : "l"(&g_kvcnt[hg * 32]) : "memory");
            if (++it > (1 << 18)) break;
          } while ((int)(v - target) < 0);
          TS2(0, 26);
        }
        __syncwarp();
        {
          const char* src = reinterpret_cast<const char*>(&g_kv[T ^ 1][hg * 2048]) + lane * 16;
#pragma unroll
          for (int i = 0; i < 16; i++)
            asm volatile("cp.async.cg.shared.global [%0], [%1], 16;" ::"r"(sb + SM_KV32 + lane * 16 + i * 512), "l"(src + i * 512) : "memory");
          asm volatile("cp.async.cg.shared.global [%0], [%1], 16;" ::"r"(sb + SM_ONES + lane * 16), "l"(&g_z[T ^ 1][hg * 128 + lane * 4]) : "memory");
          asm volatile("cp.async.mbarrier.arrive.noinc.shared::cta.b64 [%0];" ::"r"(sb + SM_KVB) : "memory");
        }
      } else {
        const int w = warp - 9;
        st_rlx4(reinterpret_cast<uint4*>(&g_st[2 * rb + w][hg][0]) + lane, T ^ 1, T ^ 1, T ^ 1, T ^ 1);
        if (lane < 8) st_rlx4(&g_o[2 * rb + w][hg][lane >> 1][3][30 + (lane & 1)], T ^ 1, T ^ 1, T ^ 1, T ^ 1);
        st_rlx4(&g_part[2 * rb3 + w][lane >> 2][jf][lane & 3][3][30], T ^ 1, T ^ 1, T ^ 1, T ^ 1);
        st_rlx4(&g_part[2 * rb3 + w][lane >> 2][jf][lane & 3][3][31], T ^ 1, T ^ 1, T ^ 1, T ^ 1);
        bar_sync(6 + w, 160);
        if (lane == 0) {
          asm volatile("fence.acq_rel.gpu;" ::: "memory");
          TS2(w, 25);
          asm volatile("red.relaxed.gpu.global.add.u32 [%0], 1;" ::"l"(&g_kvcnt[hg * 32]) : "memory");
        }
        mbar_wait(sb + SM_KVB);
        if (w == 0) { mbar_wait(sb + SM_EMPTY + 11 * 8); mbar_wait(sb + SM_EMPTY + 12 * 8); mbar_wait(sb + SM_EMPTY + 13 * 8); }
#pragma unroll 1
        for (int ph = 0; ph < 2; ph++) {
          const int use = 2 * ph + w, r = ph ? 2 * rb3 + w : 2 * rb + w;
          const uint32_t* pw = ph ? reinterpret_cast<const uint32_t*>(&g_st[r][lane >> 2][(lane & 3) * 16 + 15])
                                  : reinterpret_cast<const uint32_t*>(&g_o[r][lane >> 2][lane & 3][3][31]);
          const char* src = reinterpret_cast<const char*>(ph ? &g_h[r][0][0][0][0] : &g_o[r][0][0][0][0]);
          uint32_t ready = 0; int it = 0;
#pragma unroll 1
          for (int p = 0; p < 4; p++) {
            const uint32_t need = ph ? 0xFFFFFFFFu : 0xFFu << (8 * p);
#pragma unroll 1
            while ((ready & need) != need) {
              ready = __ballot_sync(0xffffffffu, ((ld_rlx1(pw) ^ T) & 1) == 0);
              if (++it > (1 << 18)) break;
            }
            if (lane == 0) {
              if (p == 0) TS2(w, 27 + ph);
              if (use > 0) mbar_wait(sb + SM_XE + ((use - 1) * 4 + p) * 8);
              const uint32_t bar = sb + SM_XF + (use * 4 + p) * 8;
              if (ph && p == 0) bulk_g2s(sb + SM_KV32 + w * 4096, &g_st[r][0][0], 4096, bar);
              bulk_g2s(sb + 2 * SLOT + p * 16384, src + p * 16384, 16384, bar);
            }
            __syncwarp();
          }
        }
        {
          const uint32_t* pw = reinterpret_cast<const uint32_t*>(&g_part[2 * rb3 + w][jf][(jf - 1 - (lane >> 2)) & 7][lane & 3][3][31]);
          uint32_t ready = 0; int it = 0, slot = (ST_D - 1) % NSLOT;
#pragma unroll 1
          for (int q = 0; q < 7; q++) {
            mbar_wait(sb + SM_EMPTY + (ST_D - 1 + q) * 8);
#pragma unroll 1
            while (((ready >> (4 * q)) & 15) != 15) {
              ready = __ballot_sync(0xffffffffu, ((ld_rlx1(pw) ^ T) & 1) == 0);
              if (++it > (1 << 18)) break;
            }
            if (lane == 0) {
              const uint32_t bar = sb + SM_XF + (w * 4 + (q & 3) + (q >> 2) * 8) * 8;
              mbar_expect_tx(bar, 8192);
              bulk_g2s(sb + slot * SLOT + w * 8192, &g_part[2 * rb3 + w][jf][(jf - 1 - q) & 7][0][0][0], 8192, bar);
            }
            __syncwarp();
            if (++slot == NSLOT) slot = 0;
          }
        }
      }
    }
    asm volatile("barrier.cluster.arrive.relaxed.aligned;" ::: "memory");
    asm volatile("barrier.cluster.wait.aligned;" ::: "memory");
  } else {
    asm volatile("setmaxnreg.inc.sync.aligned.u32 240;");
    if (lane == 0) {
#pragma unroll 1
      for (int d = warp; d < NSTAGE; d += 8) {
        mbar_init(sb + SM_EMPTY + d * 8, st_empty_cnt(d));
        if (d + 9 < NSTAGE) {
          mbar_init(sb + SM_FULL + (d + 9) * 8, 1);
          mbar_expect_tx(sb + SM_FULL + (d + 9) * 8, st_bytes(d + 9));
        }
      }
      asm volatile("fence.mbarrier_init.release.cluster;" ::: "memory");
    }
    __syncwarp();
    bar_sync(0, 352);
    asm volatile("barrier.cluster.arrive.relaxed.aligned;" ::: "memory");
    const int wg = warp >> 2, wq = warp & 3, g = lane >> 2, t = lane & 3;
    const bool lead = (tid & 127) == 0;
    const uint32_t db = ((sb & 0x3FFFF) >> 4) | (512u << 16);
    auto release = [&](int d) {
      const int s = d + NSLOT;
      if (s < NSTAGE) mbar_arrive_cluster(sb + SM_EMPTY + d * 8, s >= ST_GU ? (uint32_t)(s & 1) : rank);
    };
    const uint32_t lrow = (uint32_t)(wq * 16 + (lane & 7) + ((lane >> 3) & 1) * 8) * 128;
    const uint32_t lx = lane & 7, lhi = lane >> 4;
    TSTAMP(0);

    float r0, r1;
    uint32_t E[4][8];
    uint32_t T = 0;
    {
      uint32_t A[32][4];
      float acc[32];
      const int sx = wg ? ST_X1 : ST_X0;
      {
        const uint32_t base = sb + sx * SLOT + lrow;
        float cs[2][4], c0[2][4], c1[2][4];
#pragma unroll
        for (int i = 0; i < 4; i++) { cs[0][i] = cs[1][i] = c0[0][i] = c0[1][i] = c1[0][i] = c1[1][i] = 0.f; }
#pragma unroll
        for (int c = 0; c < 8; c++) {
          if (c % 3 == 0) mbar_wait(sb + SM_FULL + (sx + c / 3) * 8);
#pragma unroll
          for (int k = 0; k < 4; k++) ldsm4(A[4 * c + k], base + c * 8192 + (((2 * k + lhi) ^ lx) << 4));
#pragma unroll
          for (int k = 0; k < 4; k++) {
            const uint32_t (&f)[4] = A[4 * c + k];
            mma16816(cs[k & 1], f, 0x3F803F80u, 0x3F803F80u);
            mma16816(c0[k & 1], f, f[0], f[2]);
            mma16816(c1[k & 1], f, f[1], f[3]);
          }
        }
        const float s0 = (cs[0][0] + cs[1][0]) * (1.f / 512.f), s1 = (cs[0][2] + cs[1][2]) * (1.f / 512.f);
        TSTAMP(17);
        asm volatile("barrier.cluster.wait.aligned;" ::: "memory");
        if (lane < 3) release(sx + lane);
        const uint32_t m0 = pack2(s0, s0), m1 = pack2(s1, s1);
        float q0 = (g & 1) ? c0[0][1] + c0[1][1] : c0[0][0] + c0[1][0];
        float q1 = (g & 1) ? c1[0][3] + c1[1][3] : c1[0][2] + c1[1][2];
        q0 = __shfl_sync(0xffffffffu, q0, (lane & ~3) | (g >> 1));
        q1 = __shfl_sync(0xffffffffu, q1, (lane & ~3) | (g >> 1));
        r0 = rsqrtf(fmaxf(q0 * (1.f / 512.f) - s0 * s0, 0.f) + 1e-5f);
        r1 = rsqrtf(fmaxf(q1 * (1.f / 512.f) - s1 * s1, 0.f) + 1e-5f);
#pragma unroll
        for (int c = 0; c < 8; c++) {
#pragma unroll
          for (int ks = 4 * c; ks < 4 * c + 4; ks++) {
            A[ks][0] = hsub2(A[ks][0], m0); A[ks][1] = hsub2(A[ks][1], m1);
            A[ks][2] = hsub2(A[ks][2], m0); A[ks][3] = hsub2(A[ks][3], m1);
          }
          if (c % 3 == 0) mbar_wait(sb + SM_FULL + (ST_WK + c / 3) * 8);
          wg_fence();
#pragma unroll
          for (int ks = 4 * c; ks < 4 * c + 4; ks++) wgmma_rs_n64(acc, A[ks], DESC((ST_WK % NSLOT) * SLOT + ks * 2048), ks != 0);
          wg_commit();
          if (c == 4) { wg_wait<2>(); if (lead) release(ST_WK); }
        }
      }
      TSTAMP(1);
      uint32_t a[4][4];
      auto scale_pack = [&]() {
#pragma unroll
        for (int h = 0; h < 4; h++) {
          a[h][0] = pack2(acc[8 * h + 0] * r0, acc[8 * h + 1] * r0); a[h][1] = pack2(acc[8 * h + 2] * r1, acc[8 * h + 3] * r1);
          a[h][2] = pack2(acc[8 * h + 4] * r0, acc[8 * h + 5] * r0); a[h][3] = pack2(acc[8 * h + 6] * r1, acc[8 * h + 7] * r1);
        }
      };
      auto project = [&](const uint32_t (&b)[4][4]) {
        float pp[4][2][4];
#pragma unroll
        for (int h = 0; h < 4; h++) {
#pragma unroll
          for (int i = 0; i < 4; i++) { pp[h][0][i] = 0.f; pp[h][1][i] = 0.f; }
          mma16816(pp[h][0], a[h], b[h][0], b[h][1]);
          mma16816(pp[h][1], a[h], b[h][2], b[h][3]);
        }
#pragma unroll
        for (int h = 0; h < 4; h++) {
          a[h][0] = pack2(pp[h][0][0], pp[h][0][1]); a[h][1] = pack2(pp[h][0][2], pp[h][0][3]);
          a[h][2] = pack2(pp[h][1][0], pp[h][1][1]); a[h][3] = pack2(pp[h][1][2], pp[h][1][3]);
        }
      };
      const uint32_t wpa = sb + SM_WPHI + ((lane & 7) + ((lane >> 3) & 1) * 8) * 32 + lhi * 16;
      const uint32_t scr = sb + (wg ? (ST_SCR1 % NSLOT) : (ST_SCR0 % NSLOT)) * SLOT;
      {
        uint32_t b[4][4];
        mbar_wait(sb + SM_MISCB);
        T = (*reinterpret_cast<volatile unsigned*>(smem + SM_EPOCH) & 1) ^ 1;
#pragma unroll
        for (int h = 0; h < 4; h++) ldsm4t(b[h], wpa + h * 512);
        wg_wait<0>();
        if (lead) { release(ST_WK + 1); release(ST_WK + 2); }
        TSTAMP(2);
        scale_pack();
        project(b);
      }
      mbar_wait(sb + SM_EMPTY + (wg ? ST_SCR1 - NSLOT : ST_SCR0 - NSLOT) * 8);
      auto vgroup = [&](int c) {
        if (c % 3 == 0) mbar_wait(sb + SM_FULL + (ST_WV + c / 3) * 8);
        if (c == 0) wg_fence();
#pragma unroll
        for (int ks = 4 * c; ks < 4 * c + 4; ks++) wgmma_rs_n64(acc, A[ks], DESC((ST_WV % NSLOT) * SLOT + ks * 2048), ks != 0);
      };
#pragma unroll
      for (int h = 0; h < 4; h++) {
        vgroup(2 * h);
        float f[16];
        feat_exp(a[h], f);
        float sp0 = (f[0] + f[1]) + (f[4] + f[5]), sp1 = (f[2] + f[3]) + (f[6] + f[7]);
        float sn0 = (f[8] + f[9]) + (f[12] + f[13]), sn1 = (f[10] + f[11]) + (f[14] + f[15]);
        sp0 += __shfl_xor_sync(0xffffffffu, sp0, 1); sp1 += __shfl_xor_sync(0xffffffffu, sp1, 1);
        sn0 += __shfl_xor_sync(0xffffffffu, sn0, 1); sn1 += __shfl_xor_sync(0xffffffffu, sn1, 1);
        vgroup(2 * h + 1);
        sp0 += __shfl_xor_sync(0xffffffffu, sp0, 2); sp1 += __shfl_xor_sync(0xffffffffu, sp1, 2);
        sn0 += __shfl_xor_sync(0xffffffffu, sn0, 2); sn1 += __shfl_xor_sync(0xffffffffu, sn1, 2);
        sp0 = rcp(sp0); sp1 = rcp(sp1); sn0 = rcp(sn0); sn1 = rcp(sn1);
        const uint32_t dst = scr + (h >> 1) * 8192 + lrow;
        stsm4(dst + ((((h & 1) * 4 + lhi) ^ lx) << 4), pack2(f[0] * sp0, f[1] * sp0), pack2(f[2] * sp1, f[3] * sp1),
              pack2(f[4] * sp0, f[5] * sp0), pack2(f[6] * sp1, f[7] * sp1));
        stsm4(dst + ((((h & 1) * 4 + 2 + lhi) ^ lx) << 4), pack2(f[8] * sn0, f[9] * sn0), pack2(f[10] * sn1, f[11] * sn1),
              pack2(f[12] * sn0, f[13] * sn0), pack2(f[14] * sn1, f[15] * sn1));
      }
      wg_commit();
      TSTAMP(3);
      wg_wait<0>();
      if ((tid & 127) < 3) release(ST_WV + (tid & 127));
      TSTAMP(4);
      {
        scale_pack();
#pragma unroll
        for (int h = 0; h < 4; h++) stsm4(scr + 16384 + lrow + (((2 * h + lhi) ^ lx) << 4), a[h][0], a[h][1], a[h][2], a[h][3]);
        fence_async_smem();
        bar_sync(3, 256);
        float kv[36];
        wg_fence();
#pragma unroll
        for (int ks = 0; ks < 8; ks++) {
          const uint32_t sk = (ks < 4 ? (ST_SCR0 % NSLOT) : (ST_SCR1 % NSLOT)) * SLOT + (ks & 3) * 2048;
          const uint32_t dv = (DESC(sk + 16384) & 0xFFFFu) | (((SM_ONES - sk - 16384) >> 4) << 16);
          wgmma_ss_n72_t11(kv, DESC(sk) + wg * 512, dv, ks != 0);
        }
        wg_commit();
        wg_wait<0>();
        if (lead) { release(ST_SCR0); release(ST_SCR1); }
        const int hl = 2 * wg + (wq >> 1), f = (wq & 1) * 16 + g;
        float* kvp = &g_kv[T ^ 1][((hg * 4 + hl) * 32 + f) * 16 + 2 * t];
        float* zp = &g_z[T ^ 1][(hg * 4 + hl) * 32 + f];
        float c[8];
#pragma unroll
        for (int i = 0; i < 8; i++) c[i] = hl >= 2 ? (hl == 3 ? kv[24 + i] : kv[16 + i]) : (hl == 1 ? kv[8 + i] : kv[i]);
#pragma unroll
        for (int n = 0; n < 2; n++) {
          asm volatile("red.relaxed.gpu.global.add.v2.f32 [%0], {%1,%2};" ::"l"(kvp + n * 8), "f"(c[4 * n]), "f"(c[4 * n + 1]) : "memory");
          asm volatile("red.relaxed.gpu.global.add.v2.f32 [%0], {%1,%2};" ::"l"(kvp + n * 8 + 128), "f"(c[4 * n + 2]), "f"(c[4 * n + 3]) : "memory");
        }
        if (t < 2) asm volatile("red.relaxed.gpu.global.add.f32 [%0], %1;" ::"l"(zp + t * 8), "f"(t ? kv[34] : kv[32]) : "memory");
        bar_arrive(6 + wg, 160);
      }
      TSTAMP(5);
      {
        if (wg == 1) bar_sync(4, 256);
#pragma unroll
        for (int i = 0; i < 3; i++) {
          mbar_wait(sb + SM_FULL + (ST_WQ + i) * 8);
          wg_fence();
#pragma unroll
          for (int kk = 0; kk < 12; kk++)
            if (12 * i + kk < 32) wgmma_rs_n64(acc, A[(12 * i + kk) & 31], DESC((ST_WQ % NSLOT) * SLOT + (12 * i + kk) * 2048), (i | kk) != 0);
          wg_commit();
          if (i > 0) { wg_wait<1>(); if (lead) release(ST_WQ + i - 1); }
        }
        if (wg == 0) bar_arrive(4, 256);
        uint32_t b[4][4];
#pragma unroll
        for (int h = 0; h < 4; h++) ldsm4t(b[h], wpa + h * 512);
        wg_wait<0>();
        if (lead) release(ST_WQ + 2);
        TSTAMP(6);
        scale_pack();
        project(b);
#pragma unroll
        for (int h = 0; h < 4; h++) {
          float e[16];
          feat_exp(a[h], e);
#pragma unroll
          for (int i = 0; i < 8; i++) E[h][i] = pack2(e[2 * i], e[2 * i + 1]);
        }
      }
      TSTAMP(7);
    }
    const int rh = 2 * rb + wg;
    const uint32_t xb = sb + 2 * SLOT + wq * 2048 + lane * 16;
    mbar_wait(sb + SM_KVB);
    {
      const int r = tid & 127;
      const float4* src = reinterpret_cast<const float4*>(smem + SM_KV32) + r;
#pragma unroll
      for (int i = 0; i < 4; i++) {
        const float4 a = src[i * 128];
        *reinterpret_cast<uint2*>(smem + SM_KVS + (i * 32 + (r >> 2)) * 48 + (r & 3) * 8) = make_uint2(pack2(a.x, a.y), pack2(a.z, a.w));
      }
      const uint32_t zz = pack2(reinterpret_cast<const float*>(smem + SM_ONES)[r], 1.0f);
      *reinterpret_cast<uint4*>(smem + SM_KVS + r * 48 + 32) = make_uint4(zz, zz, zz, zz);
      bar_sync(1 + wg, 128);
    }
    TSTAMP(8);
    {
      uint4* op = &g_o[rh][hg][wq][0][lane];
#pragma unroll
      for (int h = 0; h < 4; h++) {
        uint32_t b0[4], b1[4], b2[4];
        const uint32_t kb = sb + SM_KVS + (h * 32 + lane) * 48;
        ldsm4t(b0, kb); ldsm4t(b1, kb + 16); ldsm4t(b2, kb + 32);
        const uint32_t ep[4] = {E[h][0], E[h][1], E[h][2], E[h][3]}, en[4] = {E[h][4], E[h][5], E[h][6], E[h][7]};
        float np0[4] = {0, 0, 0, 0}, np1[4] = {0, 0, 0, 0}, nn0[4] = {0, 0, 0, 0}, nn1[4] = {0, 0, 0, 0}, dp[4] = {0, 0, 0, 0}, dn[4] = {0, 0, 0, 0};
        mma16816(dp, ep, b2[0], b2[1]);  mma16816(dn, en, b2[2], b2[3]);
        mma16816(np0, ep, b0[0], b0[1]); mma16816(nn0, en, b0[2], b0[3]);
        mma16816(np1, ep, b1[0], b1[1]); mma16816(nn1, en, b1[2], b1[3]);
        const float i0 = rcp(fmaf(dp[0], dn[1], fmaf(dn[0], dp[1], 1e-6f * dp[1] * dn[1])));
        const float i1 = rcp(fmaf(dp[2], dn[3], fmaf(dn[2], dp[3], 1e-6f * dp[3] * dn[3])));
        const float cp0 = dn[1] * i0, cn0 = dp[1] * i0, cp1 = dn[3] * i1, cn1 = dp[3] * i1;
        st_rlx4(op + h * 32,
                tg(pack2(fmaf(np0[0], cp0, nn0[0] * cn0), fmaf(np0[1], cp0, nn0[1] * cn0)), T),
                pack2(fmaf(np0[2], cp1, nn0[2] * cn1), fmaf(np0[3], cp1, nn0[3] * cn1)),
                pack2(fmaf(np1[0], cp0, nn1[0] * cn0), fmaf(np1[1], cp0, nn1[1] * cn0)),
                pack2(fmaf(np1[2], cp1, nn1[2] * cn1), fmaf(np1[3], cp1, nn1[3] * cn1)));
      }
    }
    TSTAMP(9);

    {
      uint32_t xr[16];
      {
        const uint32_t* xp = reinterpret_cast<const uint32_t*>(x + (size_t)(rh * 64 + wq * 16 + g) * 512 + hg * 64 + 2 * t);
#pragma unroll
        for (int i = 0; i < 8; i++) { xr[2 * i] = __ldg(xp + 4 * i); xr[2 * i + 1] = __ldg(xp + 8 * 256 + 4 * i); }
      }
      uint32_t A[8][4][4];
      const uint4* op = &g_o[rh][0][wq][0][lane];
      float acc[32];
      mbar_wait(sb + SM_XF + (wg * 4) * 8);
      lds_chunk(A[0], xb); lds_chunk(A[1], xb + 8192);
#pragma unroll
      for (int p = 0; p < 4; p++) {
        chk_chunk(A[2 * p], op + 2 * p * 512, T);
        chk_chunk(A[2 * p + 1], op + (2 * p + 1) * 512, T);
        if (lane == 0) mbar_arrive(sb + SM_XE + (wg * 4 + p) * 8);
#pragma unroll
        for (int c = 2 * p; c < 2 * p + 2; c++) {
          if (c % 3 == 0) mbar_wait(sb + SM_FULL + (ST_WO + c / 3) * 8);
          if ((c & 1) && p < 3) {
            mbar_wait(sb + SM_XF + (wg * 4 + p + 1) * 8);
            lds_chunk(A[2 * p + 2], xb + (p + 1) * 16384); lds_chunk(A[2 * p + 3], xb + (p + 1) * 16384 + 8192);
          }
          wg_fence();
#pragma unroll
          for (int s = 0; s < 4; s++)
            wgmma_rs_n64(acc, A[c][s], DESC(((ST_WO + c / 3) % NSLOT) * SLOT + ((c % 3) * 4 + s) * 2048), (c | s) != 0);
          wg_commit();
        }
      }
      wg_wait<0>();
      if ((tid & 127) < 3) release(ST_WO + (tid & 127));
      TSTAMP(10);
      uint32_t hw[16];
      float s0 = 0.f, s1 = 0.f, q0 = 0.f, q1 = 0.f;
#pragma unroll
      for (int i = 0; i < 8; i++) {
        hw[2 * i]     = pack2(blo(xr[2 * i]) + acc[4 * i], bhi(xr[2 * i]) + acc[4 * i + 1]);
        hw[2 * i + 1] = pack2(blo(xr[2 * i + 1]) + acc[4 * i + 2], bhi(xr[2 * i + 1]) + acc[4 * i + 3]);
      }
      uint4* hp_ = &g_h[rh][hg][wq][0][lane];
#pragma unroll
      for (int s = 0; s < 4; s++) st_rlx4(hp_ + s * 32, tg(hw[4 * s], T), hw[4 * s + 1], hw[4 * s + 2], hw[4 * s + 3]);
#pragma unroll
      for (int i = 0; i < 8; i++) {
        float a = blo(hw[2 * i]), b = bhi(hw[2 * i]);
        s0 += a + b; q0 = fmaf(a, a, q0); q0 = fmaf(b, b, q0);
        a = blo(hw[2 * i + 1]); b = bhi(hw[2 * i + 1]);
        s1 += a + b; q1 = fmaf(a, a, q1); q1 = fmaf(b, b, q1);
      }
      s0 += __shfl_xor_sync(0xffffffffu, s0, 1); s1 += __shfl_xor_sync(0xffffffffu, s1, 1);
      q0 += __shfl_xor_sync(0xffffffffu, q0, 1); q1 += __shfl_xor_sync(0xffffffffu, q1, 1);
      s0 += __shfl_xor_sync(0xffffffffu, s0, 2); s1 += __shfl_xor_sync(0xffffffffu, s1, 2);
      q0 += __shfl_xor_sync(0xffffffffu, q0, 2); q1 += __shfl_xor_sync(0xffffffffu, q1, 2);
      if (t < 2) st_rlx2(&g_st[rh][hg][wq * 16 + g + t * 8], tg(__float_as_uint(t ? s1 : s0), T), __float_as_uint(t ? q1 : q0));
      uint32_t hx = T;
#pragma unroll
      for (int i = 0; i < 4; i++) hx |= (hw[4 * i] & 1u) << (i + 1);
      st_rlx1(&g_hx[rh][hg][wq][lane], hx);
    }
    TSTAMP(11);

    const int rh3 = 2 * rb3 + wg;
    uint32_t HH[11][4];
    {
      uint32_t A[8][4][4];
      const uint4* hp_ = &g_h[rh3][0][wq][0][lane];
      const uint32_t dg = (db & 0xFFFFu) | (256u << 16);
      uint32_t m0, m1;
      mbar_wait(sb + SM_XF + ((2 + wg) * 4) * 8);
      lds_chunk(A[0], xb); lds_chunk(A[1], xb + 8192);
      {
        const uint2* sp = &g_st[rh3][2 * t][wq * 16 + g];
        const uint2* ss = reinterpret_cast<const uint2*>(smem + SM_KV32 + wg * 4096) + 2 * t * 64 + wq * 16 + g;
        uint2 a0 = ss[0], a1 = ss[64], b0 = ss[8], b1 = ss[72];
        int it = 0;
#pragma unroll 1
        while (__any_sync(0xffffffffu, bad4(a0.x, a1.x, b0.x, b1.x, T) & 1)) {
          ld_rlx2(a0.x, a0.y, sp); ld_rlx2(a1.x, a1.y, sp + 64); ld_rlx2(b0.x, b0.y, sp + 8); ld_rlx2(b1.x, b1.y, sp + 72);
          if (++it > (1 << 18)) break;
        }
        float s0 = __uint_as_float(a0.x) + __uint_as_float(a1.x), q0 = __uint_as_float(a0.y) + __uint_as_float(a1.y);
        float s1 = __uint_as_float(b0.x) + __uint_as_float(b1.x), q1 = __uint_as_float(b0.y) + __uint_as_float(b1.y);
        s0 += __shfl_xor_sync(0xffffffffu, s0, 1); s1 += __shfl_xor_sync(0xffffffffu, s1, 1);
        q0 += __shfl_xor_sync(0xffffffffu, q0, 1); q1 += __shfl_xor_sync(0xffffffffu, q1, 1);
        s0 += __shfl_xor_sync(0xffffffffu, s0, 2); s1 += __shfl_xor_sync(0xffffffffu, s1, 2);
        q0 += __shfl_xor_sync(0xffffffffu, q0, 2); q1 += __shfl_xor_sync(0xffffffffu, q1, 2);
        s0 *= (1.f / 512.f); s1 *= (1.f / 512.f);
        r0 = rcp(fmaxf(q0 * (1.f / 512.f) - s0 * s0, 0.f) + 1e-5f);
        r1 = rcp(fmaxf(q1 * (1.f / 512.f) - s1 * s1, 0.f) + 1e-5f);
        m0 = pack2(s0, s0); m1 = pack2(s1, s1);
      }
      TSTAMP(12);
#define UOFF(u) ((((ST_GU + (u) / 3) % NSLOT) * SLOT + ((u) % 3) * 8192) >> 4)
#define UNIT_PRE(u)  do { if ((u) % 3 == 0) mbar_wait(sb + SM_FULL + (ST_GU + (u) / 3) * 8); wg_fence(); } while (0)
#define UNIT_POST(u) do { wg_commit(); if ((u) % 3 == 1 && (u) > 3) { wg_wait<2>(); if (lead) release(ST_GU + (u) / 3 - 1); } } while (0)
#pragma unroll
      for (int ps = 0; ps < 2; ps++) {
        float acc[64];
#pragma unroll
        for (int k = 0; k < 16; k++) {
          const int u = 16 * ps + k, c = k >> 1;
          if (ps == 0 && (k & 3) == 0) {
            const int p = k >> 2;
            chk_chunk(A[2 * p], hp_ + 2 * p * 512, T);
            chk_chunk(A[2 * p + 1], hp_ + (2 * p + 1) * 512, T);
            if (lane == 0) {
              if (wg == 0) mbar_arrive(sb + SM_XE + (8 + p) * 8);
              else if (p > 0) release(ST_XC + p - 1);
            }
          }
          if (ps == 0 && (k & 3) == 1 && k < 12) {
            const int p = (k >> 2) + 1;
            mbar_wait(sb + SM_XF + ((2 + wg) * 4 + p) * 8);
            lds_chunk(A[2 * p], xb + p * 16384);
            lds_chunk(A[2 * p + 1], xb + p * 16384 + 8192);
          }
          if (ps == 0 && (k & 1) == 0) {
#pragma unroll
            for (int s = 0; s < 4; s++) {
              A[c][s][0] = hsub2(A[c][s][0], m0); A[c][s][1] = hsub2(A[c][s][1], m1);
              A[c][s][2] = hsub2(A[c][s][2], m0); A[c][s][3] = hsub2(A[c][s][3], m1);
            }
          }
          UNIT_PRE(u);
          wgmma_rs_n128(acc, A[c][(k & 1) * 2], dg + UOFF(u), k != 0);
          wgmma_rs_n128(acc, A[c][(k & 1) * 2 + 1], dg + UOFF(u) + 128, 1);
          UNIT_POST(u);
        }
        wg_wait<0>();
#pragma unroll
        for (int s = 0; s < 4; s++) {
          HH[4 * ps + s][0] = pack2(acc[8 * s + 0] * acc[32 + 8 * s + 0] * r0, acc[8 * s + 1] * acc[32 + 8 * s + 1] * r0);
          HH[4 * ps + s][1] = pack2(acc[8 * s + 2] * acc[32 + 8 * s + 2] * r1, acc[8 * s + 3] * acc[32 + 8 * s + 3] * r1);
          HH[4 * ps + s][2] = pack2(acc[8 * s + 4] * acc[32 + 8 * s + 4] * r0, acc[8 * s + 5] * acc[32 + 8 * s + 5] * r0);
          HH[4 * ps + s][3] = pack2(acc[8 * s + 6] * acc[32 + 8 * s + 6] * r1, acc[8 * s + 7] * acc[32 + 8 * s + 7] * r1);
        }
      }
      {
        float ag[24], au[24];
#pragma unroll
        for (int k = 0; k < 16; k++) {
          const int u = 32 + k, c = k >> 1;
          UNIT_PRE(u);
          wgmma_rs_n48(ag, A[c][(k & 1) * 2], dg + UOFF(u), k != 0);
          wgmma_rs_n48(au, A[c][(k & 1) * 2], dg + UOFF(u) + 256, k != 0);
          wgmma_rs_n48(ag, A[c][(k & 1) * 2 + 1], dg + UOFF(u) + 128, 1);
          wgmma_rs_n48(au, A[c][(k & 1) * 2 + 1], dg + UOFF(u) + 256 + 128, 1);
          UNIT_POST(u);
        }
        wg_wait<0>();
        if (lead) mbar_arrive(sb + SM_EMPTY + (ST_D - 1) * 8);
        TSTAMP(13);
#pragma unroll
        for (int s = 0; s < 3; s++) {
          HH[8 + s][0] = pack2(ag[8 * s + 0] * au[8 * s + 0] * r0, ag[8 * s + 1] * au[8 * s + 1] * r0);
          HH[8 + s][1] = pack2(ag[8 * s + 2] * au[8 * s + 2] * r1, ag[8 * s + 3] * au[8 * s + 3] * r1);
          HH[8 + s][2] = pack2(ag[8 * s + 4] * au[8 * s + 4] * r0, ag[8 * s + 5] * au[8 * s + 5] * r0);
          HH[8 + s][3] = pack2(ag[8 * s + 6] * au[8 * s + 6] * r1, ag[8 * s + 7] * au[8 * s + 7] * r1);
        }
      }
    }
    TSTAMP(14);

    {
      float acc[32], sum[32];
      uint32_t in[4][4];
      const uint4* inb = &g_part[rh3][jf][0][wq][0][lane];
      uint4* outb = &g_part[rh3][0][jf][wq][0][lane];
      ld_chunk(in, &g_h[rh3][jf][wq][0][lane]);
      uint32_t hx = ld_rlx1(&g_hx[rh3][jf][wq][lane]);
      int slot = ST_D % NSLOT, q = 0, qslot = (ST_D - 1) % NSLOT, it = 0;
#pragma unroll 1
      for (int st = 0; q < 7; st++) {
        if (st < 8) {
          uint32_t pk[16];
#pragma unroll
          for (int i = 0; i < 16; i++) pk[i] = pack2(acc[2 * i], acc[2 * i + 1]);
          mbar_wait(sb + SM_FULL + (ST_D + st) * 8);
          wg_fence();
#pragma unroll
          for (int s = 0; s < 4; s++) wgmma_rs_n64(acc, HH[s], db + slot * (SLOT >> 4) + s * 128, s != 0);
          if (st > 0) {
            uint4* p = outb + ((jf + st) & 7) * 4096;
#pragma unroll
            for (int s = 0; s < 4; s++) st_rlx4(p + s * 32, tg(pk[4 * s], T), pk[4 * s + 1], pk[4 * s + 2], pk[4 * s + 3]);
          }
#pragma unroll
          for (int s = 4; s < 11; s++) wgmma_rs_n64(acc, HH[s], db + slot * (SLOT >> 4) + s * 128, 1);
          wg_commit();
          if (++slot == NSLOT) slot = 0;
          wg_wait<0>();
          if (lead) mbar_arrive(sb + SM_EMPTY + (ST_D + st) * 8);
          if (st == 7) TSTAMP(15);
        }
        if (st == 1) {
#pragma unroll 1
          while (__any_sync(0xffffffffu, (hx ^ T) & 1)) {
            hx = ld_rlx1(&g_hx[rh3][jf][wq][lane]);
            if (++it > (1 << 18)) break;
          }
#pragma unroll
          for (int s = 0; s < 4; s++) in[s][0] = (in[s][0] & 0xFFFFFFFEu) | ((hx >> (s + 1)) & 1u);
#pragma unroll
          for (int i = 0; i < 16; i++) { sum[2 * i] = blo(in[i >> 2][i & 3]); sum[2 * i + 1] = bhi(in[i >> 2][i & 3]); }
        }
        if (st >= 2 && (__all_sync(0xffffffffu, mbar_test1(sb + SM_XF + (wg * 4 + (q & 3) + (q >> 2) * 8) * 8)) || ++it > (1 << 22))) {
          lds_chunk(in, sb + qslot * SLOT + wg * 8192 + wq * 2048 + lane * 16);
          chk_chunk(in, inb + ((jf - 1 - q) & 7) * 512, T);
#pragma unroll
          for (int i = 0; i < 16; i++) { sum[2 * i] += blo(in[i >> 2][i & 3]); sum[2 * i + 1] += bhi(in[i >> 2][i & 3]); }
          q++;
          if (++qslot == NSLOT) qslot = 0;
        }
      }
#pragma unroll
      for (int i = 0; i < 32; i++) sum[i] += acc[i];
      uint32_t* op = reinterpret_cast<uint32_t*>(out + (size_t)(rh3 * 64 + wq * 16 + g) * 512 + jf * 64 + 2 * t);
#pragma unroll
      for (int i = 0; i < 8; i++) {
        op[4 * i]           = pack2(sum[4 * i], sum[4 * i + 1]);
        op[8 * 256 + 4 * i] = pack2(sum[4 * i + 2], sum[4 * i + 3]);
      }
    }
    TSTAMP(16);
    asm volatile("barrier.cluster.arrive.relaxed.aligned;" ::: "memory");
    asm volatile("barrier.cluster.wait.aligned;" ::: "memory");
  }
}

typedef CUresult (*EncodeFn)(CUtensorMap*, CUtensorMapDataType, cuuint32_t, void*, const cuuint64_t*, const cuuint64_t*,
                             const cuuint32_t*, const cuuint32_t*, CUtensorMapInterleave, CUtensorMapSwizzle,
                             CUtensorMapL2promotion, CUtensorMapFloatOOBfill);

void encode(EncodeFn fn, CUtensorMap* m, const void* base, int rank, const cuuint64_t* dims, const cuuint64_t* strides,
            const cuuint32_t* box) {
  cuuint32_t es[3] = {1, 1, 1};
  fn(m, CU_TENSOR_MAP_DATA_TYPE_BFLOAT16, (cuuint32_t)rank, const_cast<void*>(base), dims, strides, box, es,
     CU_TENSOR_MAP_INTERLEAVE_NONE, CU_TENSOR_MAP_SWIZZLE_128B, CU_TENSOR_MAP_L2_PROMOTION_L2_256B,
     CU_TENSOR_MAP_FLOAT_OOB_FILL_NONE);
}

}

extern "C" void kernel_launch(void* const* d_in, const int* in_sizes, int n_in, void* d_out, int out_size) {
  (void)in_sizes; (void)n_in; (void)out_size;
  const __nv_bfloat16* x    = (const __nv_bfloat16*)d_in[0];
  const __nv_bfloat16* wqkv = (const __nv_bfloat16*)d_in[1];
  const __nv_bfloat16* wphi = (const __nv_bfloat16*)d_in[2];
  const __nv_bfloat16* wo   = (const __nv_bfloat16*)d_in[3];
  const __nv_bfloat16* wg   = (const __nv_bfloat16*)d_in[5];
  const __nv_bfloat16* wu   = (const __nv_bfloat16*)d_in[6];
  const __nv_bfloat16* wd   = (const __nv_bfloat16*)d_in[7];

  static EncodeFn fn = nullptr;
  if (!fn) {
    void* p = nullptr;
    cudaDriverEntryPointQueryResult qr;
    cudaGetDriverEntryPoint("cuTensorMapEncodeTiled", &p, cudaEnableDefault, &qr);
    fn = (EncodeFn)p;
    cudaFuncSetAttribute(fused_kernel, cudaFuncAttributeMaxDynamicSharedMemorySize, SM_TOTAL);
  }
  Maps maps;
  {
    cuuint64_t d[3] = {64, 2048, 8}, s[2] = {1024, 128}; cuuint32_t b[3] = {64, 64, 3};
    encode(fn, &maps.x, x, 3, d, s, b);
  }
  {
    cuuint64_t d[2] = {1536, 512}, s[1] = {3072}; cuuint32_t b[2] = {64, 192};
    encode(fn, &maps.w, wqkv, 2, d, s, b);
  }
  {
    cuuint64_t d[2] = {512, 512}, s[1] = {1024}; cuuint32_t b[2] = {64, 192};
    encode(fn, &maps.wo, wo, 2, d, s, b);
  }
  {
    cuuint64_t d[3] = {176, 7, 512}, d7[3] = {144, 1, 512}, s[2] = {352, 2752}; cuuint32_t b[3] = {64, 1, 32};
    encode(fn, &maps.g, wg, 3, d, s, b);
    encode(fn, &maps.u, wu, 3, d, s, b);
    encode(fn, &maps.g7, wg + 1232, 3, d7, s, b);
    encode(fn, &maps.u7, wu + 1232, 3, d7, s, b);
  }
  {
    cuuint64_t d[2] = {512, 1376}, s[1] = {1024}; cuuint32_t b[2] = {64, 176};
    encode(fn, &maps.d, wd, 2, d, s, b);
  }
  fused_kernel<<<NCTA, 384, SM_TOTAL>>>(maps, x, wphi, wo, wg, wu, wd, (__nv_bfloat16*)d_out);
}
```

```cpp
#include <cuda_runtime.h>
#include <cuda_bf16.h>
#include <cuda.h>
#include <stdint.h>

#define PROF 0

#define THR 6

namespace {

constexpr int NCTA   = 128;
constexpr int SLOT   = 24576;
constexpr int NSLOT  = 9;
constexpr int NSTAGE = 39;

constexpr int ST_X0   = 0;
constexpr int ST_WK   = 3;
constexpr int ST_X1   = 6;
constexpr int ST_SCR0 = 9;
constexpr int ST_WV   = 10;
constexpr int ST_SCR1 = 13;
constexpr int ST_WQ   = 14;
constexpr int ST_WO   = 17;
constexpr int ST_XC   = 20;
constexpr int ST_GU   = 23;
constexpr int ST_D    = 39;

__host__ __device__ constexpr int st_empty_cnt(int d) {
  return ((d < 3 || (d >= 6 && d < 9) || (d >= ST_XC && d < ST_GU)) ? 4 : 2) * (d + 9 >= ST_GU && d + 9 < ST_D ? 2 : 1);
}

constexpr int SM_ONES = NSLOT * SLOT;
constexpr int SM_WPHI = SM_ONES + 2048;
constexpr int SM_KVS  = SM_WPHI + 2048;
constexpr int SM_KV32 = 4 * SLOT + 16384;
constexpr int SM_BAR  = SM_KVS + 6144;
constexpr int SM_FULL  = SM_BAR;
constexpr int SM_EMPTY = SM_BAR + NSTAGE * 8;
constexpr int SM_MISCB = SM_BAR + 2 * NSTAGE * 8;
constexpr int SM_KVB   = SM_MISCB + 8;
constexpr int SM_EPOCH = SM_KVB + 8;
constexpr int SM_XF    = SM_EPOCH + 8;
constexpr int SM_XE    = SM_XF + 16 * 8;
constexpr int SM_DF    = SM_XE + 12 * 8;
constexpr int SM_DE    = SM_DF + 9 * 8;
constexpr int SM_TOTAL = SM_BAR + 1024;

static_assert(SM_TOTAL == 232448 && SM_DE + 9 * 8 <= SM_TOTAL, "smem budget");

struct Maps { CUtensorMap x, w, wo, g, u, g7, u7, d, d48; };

__device__ uint4    g_o[32][8][4][4][32];
__device__ uint4    g_h[32][8][4][4][32];
__device__ uint32_t g_hx[32][8][4][32];
__device__ uint2    g_st[32][8][64];
__device__ uint4    g_hh[32][3][8][4][4][32];
__device__ float    g_kv[2][32 * 32 * 16];
__device__ float    g_z[2][32 * 32];
__device__ unsigned g_kvcnt[8 * 32];
__device__ unsigned g_start;

__device__ __forceinline__ uint32_t smem_u32(const void* p) { return (uint32_t)__cvta_generic_to_shared(p); }
__device__ __forceinline__ void mbar_init(uint32_t bar, int cnt) {
  asm volatile("mbarrier.init.shared::cta.b64 [%0], %1;" ::"r"(bar), "r"(cnt) : "memory");
}
__device__ __forceinline__ void mbar_expect_tx(uint32_t bar, uint32_t bytes) {
  asm volatile("mbarrier.arrive.expect_tx.shared::cta.b64 _, [%0], %1;" ::"r"(bar), "r"(bytes) : "memory");
}
__device__ __forceinline__ void mbar_arrive(uint32_t bar) {
  asm volatile("mbarrier.arrive.shared::cta.b64 _, [%0];" ::"r"(bar) : "memory");
}
__device__ __forceinline__ void mbar_arrive_cluster(uint32_t bar, uint32_t rank) {
  asm volatile("{\n.reg .b32 ra;\nmapa.shared::cluster.u32 ra, %0, %1;\n"
               "mbarrier.arrive.shared::cluster.b64 _, [ra];\n}" ::"r"(bar), "r"(rank) : "memory");
}
__device__ __forceinline__ bool mbar_try(uint32_t bar) {
  uint32_t ok;
  asm volatile("{\n.reg .pred p;\nmbarrier.try_wait.parity.shared::cta.b64 p, [%1], 0;\nselp.u32 %0, 1, 0, p;\n}"
               : "=r"(ok) : "r"(bar) : "memory");
  return ok != 0;
}
__device__ __forceinline__ void mbar_wait_p(uint32_t bar, uint32_t parity) {
  uint32_t ok; int it = 0;
#pragma unroll 1
  do {
    asm volatile("{\n.reg .pred p;\nmbarrier.try_wait.parity.shared::cta.b64 p, [%1], %2;\nselp.u32 %0, 1, 0, p;\n}"
                 : "=r"(ok) : "r"(bar), "r"(parity) : "memory");
  } while (!ok && ++it < (1 << 18));
}
__device__ __forceinline__ void mbar_wait(uint32_t bar) {
  int it = 0;
#pragma unroll 1
  while (!mbar_try(bar)) {
    if (++it > (1 << 20)) __trap();
  }
}
__device__ __forceinline__ void bar_sync(int id, int n)   { asm volatile("bar.sync %0, %1;" ::"r"(id), "r"(n) : "memory"); }
__device__ __forceinline__ void bar_arrive(int id, int n) { asm volatile("bar.arrive %0, %1;" ::"r"(id), "r"(n) : "memory"); }
__device__ __forceinline__ void fence_async_smem() { asm volatile("fence.proxy.async.shared::cta;" ::: "memory"); }
__device__ __forceinline__ void wg_fence()  { asm volatile("wgmma.fence.sync.aligned;" ::: "memory"); }
__device__ __forceinline__ void wg_commit() { asm volatile("wgmma.commit_group.sync.aligned;" ::: "memory"); }
template <int N> __device__ __forceinline__ void wg_wait() { asm volatile("wgmma.wait_group.sync.aligned %0;" ::"n"(N) : "memory"); }
#define DESC(off) (db + ((uint32_t)(off) >> 4))
__device__ __forceinline__ void tma2d(uint32_t dst, const CUtensorMap* m, int c0, int c1, uint32_t bar) {
  asm volatile("cp.async.bulk.tensor.2d.shared::cluster.global.mbarrier::complete_tx::bytes [%0], [%1, {%3, %4}], [%2];"
               ::"r"(dst), "l"(m), "r"(bar), "r"(c0), "r"(c1) : "memory");
}
__device__ __forceinline__ void tma3d(uint32_t dst, const CUtensorMap* m, int c0, int c1, int c2, uint32_t bar) {
  asm volatile("cp.async.bulk.tensor.3d.shared::cluster.global.mbarrier::complete_tx::bytes [%0], [%1, {%3, %4, %5}], [%2];"
               ::"r"(dst), "l"(m), "r"(bar), "r"(c0), "r"(c1), "r"(c2) : "memory");
}
__device__ __forceinline__ void tma3d_mc(uint32_t dst, const CUtensorMap* m, int c0, int c1, int c2, uint32_t bar) {
  asm volatile("cp.async.bulk.tensor.3d.shared::cluster.global.mbarrier::complete_tx::bytes.multicast::cluster [%0], [%1, {%3, %4, %5}], [%2], %6;"
               ::"r"(dst), "l"(m), "r"(bar), "r"(c0), "r"(c1), "r"(c2), "h"((uint16_t)3) : "memory");
}
__device__ __forceinline__ void ldsm4(uint32_t (&r)[4], uint32_t addr) {
  asm volatile("ldmatrix.sync.aligned.m8n8.x4.shared.b16 {%0,%1,%2,%3}, [%4];"
               : "=r"(r[0]), "=r"(r[1]), "=r"(r[2]), "=r"(r[3]) : "r"(addr) : "memory");
}
__device__ __forceinline__ void ldsm4t(uint32_t (&r)[4], uint32_t addr) {
  asm volatile("ldmatrix.sync.aligned.m8n8.x4.trans.shared.b16 {%0,%1,%2,%3}, [%4];"
               : "=r"(r[0]), "=r"(r[1]), "=r"(r[2]), "=r"(r[3]) : "r"(addr) : "memory");
}
__device__ __forceinline__ void stsm4(uint32_t addr, uint32_t r0, uint32_t r1, uint32_t r2, uint32_t r3) {
  asm volatile("stmatrix.sync.aligned.m8n8.x4.shared.b16 [%0], {%1,%2,%3,%4};"
               ::"r"(addr), "r"(r0), "r"(r1), "r"(r2), "r"(r3) : "memory");
}
__device__ __forceinline__ void mma16816(float (&c)[4], const uint32_t (&a)[4], uint32_t b0, uint32_t b1) {
  asm volatile("mma.sync.aligned.m16n8k16.row.col.f32.bf16.bf16.f32 {%0,%1,%2,%3},{%4,%5,%6,%7},{%8,%9},{%0,%1,%2,%3};"
               : "+f"(c[0]), "+f"(c[1]), "+f"(c[2]), "+f"(c[3])
               : "r"(a[0]), "r"(a[1]), "r"(a[2]), "r"(a[3]), "r"(b0), "r"(b1));
}
__device__ __forceinline__ uint32_t pack2(float lo, float hi) {
  uint32_t r; asm("cvt.rn.bf16x2.f32 %0, %1, %2;" : "=r"(r) : "f"(hi), "f"(lo)); return r;
}
__device__ __forceinline__ float blo(uint32_t w) { return __uint_as_float(w << 16); }
__device__ __forceinline__ float bhi(uint32_t w) { return __uint_as_float(w & 0xFFFF0000u); }
__device__ __forceinline__ uint32_t hsub2(uint32_t a, uint32_t b) { uint32_t r; asm("sub.rn.bf16x2 %0, %1, %2;" : "=r"(r) : "r"(a), "r"(b)); return r; }
__device__ __forceinline__ uint32_t hmax2(uint32_t a, uint32_t b) { uint32_t r; asm("max.bf16x2 %0, %1, %2;" : "=r"(r) : "r"(a), "r"(b)); return r; }
__device__ __forceinline__ uint32_t hmin2(uint32_t a, uint32_t b) { uint32_t r; asm("min.bf16x2 %0, %1, %2;" : "=r"(r) : "r"(a), "r"(b)); return r; }
__device__ __forceinline__ float ex2(float x) { float r; asm("ex2.approx.ftz.f32 %0, %1;" : "=f"(r) : "f"(x)); return r; }
__device__ __forceinline__ float rcp(float x) { float r; asm("rcp.approx.ftz.f32 %0, %1;" : "=f"(r) : "f"(x)); return r; }
__device__ __forceinline__ void ld_rlx4(uint32_t (&r)[4], const uint4* p) {
  asm volatile("{\n.reg .b128 v;\nld.relaxed.gpu.global.b128 v, [%4];\nmov.b128 {%0,%1,%2,%3}, v;\n}"
               : "=r"(r[0]), "=r"(r[1]), "=r"(r[2]), "=r"(r[3]) : "l"(p) : "memory");
}
__device__ __forceinline__ void st_rlx4(uint4* p, uint32_t a, uint32_t b, uint32_t c, uint32_t d) {
  asm volatile("{\n.reg .b128 v;\nmov.b128 v, {%1,%2,%3,%4};\nst.relaxed.gpu.global.b128 [%0], v;\n}"
               ::"l"(p), "r"(a), "r"(b), "r"(c), "r"(d) : "memory");
}
__device__ __forceinline__ void st_rlx2(uint2* p, uint32_t a, uint32_t b) {
  asm volatile("{\n.reg .b64 v;\nmov.b64 v, {%1,%2};\nst.relaxed.gpu.global.b64 [%0], v;\n}" ::"l"(p), "r"(a), "r"(b) : "memory");
}
__device__ __forceinline__ uint32_t ld_rlx1(const uint32_t* p) {
  uint32_t r; asm volatile("ld.relaxed.gpu.global.b32 %0, [%1];" : "=r"(r) : "l"(p) : "memory"); return r;
}
__device__ __forceinline__ void st_rlx1(uint32_t* p, uint32_t a) {
  asm volatile("st.relaxed.gpu.global.b32 [%0], %1;" ::"l"(p), "r"(a) : "memory");
}
__device__ __forceinline__ void ld_rlx2(uint32_t& a, uint32_t& b, const uint2* p) {
  asm volatile("{\n.reg .b64 v;\nld.relaxed.gpu.global.b64 v, [%2];\nmov.b64 {%0,%1}, v;\n}" : "=r"(a), "=r"(b) : "l"(p) : "memory");
}
__device__ __forceinline__ void bulk_g2s(uint32_t dst, const void* src, uint32_t bytes, uint32_t bar) {
  asm volatile("cp.async.bulk.shared::cluster.global.mbarrier::complete_tx::bytes [%0], [%1], %2, [%3];"
               ::"r"(dst), "l"(src), "r"(bytes), "r"(bar) : "memory");
}
__device__ __forceinline__ uint32_t tg(uint32_t w, uint32_t T) { return (w & 0xFFFFFFFEu) | T; }
__device__ __forceinline__ uint32_t bad4(uint32_t a, uint32_t b, uint32_t c, uint32_t d, uint32_t T) {
  uint32_t u, v;
  asm("lop3.b32 %0, %1, %2, %3, 0x7E;" : "=r"(u) : "r"(a), "r"(b), "r"(T));
  asm("lop3.b32 %0, %1, %2, %3, 0x7E;" : "=r"(v) : "r"(c), "r"(d), "r"(T));
  return u | v;
}

__device__ __forceinline__ void ld_chunk(uint32_t (&a)[4][4], const uint4* p) {
#pragma unroll
  for (int s = 0; s < 4; s++) ld_rlx4(a[s], p + s * 32);
}
__device__ __forceinline__ void lds_chunk(uint32_t (&a)[4][4], uint32_t addr) {
#pragma unroll
  for (int s = 0; s < 4; s++)
    asm volatile("ld.shared.v4.b32 {%0,%1,%2,%3}, [%4];" : "=r"(a[s][0]), "=r"(a[s][1]), "=r"(a[s][2]), "=r"(a[s][3])
                 : "r"(addr + s * 512) : "memory");
}
__device__ __forceinline__ void chk_chunk(uint32_t (&a)[4][4], const uint4* p, uint32_t T) {
  int it = 0;
#pragma unroll 1
  while (__any_sync(0xffffffffu, bad4(a[0][0], a[1][0], a[2][0], a[3][0], T) & 1)) {
    ld_chunk(a, p);
    if (++it > (1 << 18)) break;
  }
}

__device__ __forceinline__ void wgmma_rs_n48(float (&d)[24], const uint32_t (&a)[4], uint32_t descB, int scaleD) {
  asm volatile("{\n.reg .pred p;\n.reg .b64 db;\nsetp.ne.b32 p, %29, 0;\nmov.b64 db, {%28, 0x40000040};\n"
    "wgmma.mma_async.sync.aligned.m64n48k16.f32.bf16.bf16 {%0,%1,%2,%3,%4,%5,%6,%7,%8,%9,%10,%11,%12,%13,%14,%15,%16,%17,%18,%19,%20,%21,%22,%23}, {%24,%25,%26,%27}, db, p, 1, 1, 1;\n}\n"
    : "+f"(d[0]),"+f"(d[1]),"+f"(d[2]),"+f"(d[3]),"+f"(d[4]),"+f"(d[5]),"+f"(d[6]),"+f"(d[7]),"+f"(d[8]),"+f"(d[9]),"+f"(d[10]),"+f"(d[11]),"+f"(d[12]),"+f"(d[13]),"+f"(d[14]),"+f"(d[15]),"+f"(d[16]),"+f"(d[17]),"+f"(d[18]),"+f"(d[19]),"+f"(d[20]),"+f"(d[21]),"+f"(d[22]),"+f"(d[23])
    : "r"(a[0]), "r"(a[1]), "r"(a[2]), "r"(a[3]), "r"(descB), "r"(scaleD));
}
__device__ __forceinline__ void wgmma_rs_n64(float (&d)[32], const uint32_t (&a)[4], uint32_t descB, int scaleD) {
  asm volatile("{\n.reg .pred p;\n.reg .b64 db;\nsetp.ne.b32 p, %37, 0;\nmov.b64 db, {%36, 0x40000040};\n"
    "wgmma.mma_async.sync.aligned.m64n64k16.f32.bf16.bf16 {%0,%1,%2,%3,%4,%5,%6,%7,%8,%9,%10,%11,%12,%13,%14,%15,%16,%17,%18,%19,%20,%21,%22,%23,%24,%25,%26,%27,%28,%29,%30,%31}, {%32,%33,%34,%35}, db, p, 1, 1, 1;\n}\n"
    : "+f"(d[0]),"+f"(d[1]),"+f"(d[2]),"+f"(d[3]),"+f"(d[4]),"+f"(d[5]),"+f"(d[6]),"+f"(d[7]),"+f"(d[8]),"+f"(d[9]),"+f"(d[10]),"+f"(d[11]),"+f"(d[12]),"+f"(d[13]),"+f"(d[14]),"+f"(d[15]),"+f"(d[16]),"+f"(d[17]),"+f"(d[18]),"+f"(d[19]),"+f"(d[20]),"+f"(d[21]),"+f"(d[22]),"+f"(d[23]),"+f"(d[24]),"+f"(d[25]),"+f"(d[26]),"+f"(d[27]),"+f"(d[28]),"+f"(d[29]),"+f"(d[30]),"+f"(d[31])
    : "r"(a[0]), "r"(a[1]), "r"(a[2]), "r"(a[3]), "r"(descB), "r"(scaleD));
}
__device__ __forceinline__ void wgmma_rs_n128(float (&d)[64], const uint32_t (&a)[4], uint32_t descB, int scaleD) {
  asm volatile("{\n.reg .pred p;\n.reg .b64 db;\nsetp.ne.b32 p, %69, 0;\nmov.b64 db, {%68, 0x40000040};\n"
    "wgmma.mma_async.sync.aligned.m64n128k16.f32.bf16.bf16 {%0,%1,%2,%3,%4,%5,%6,%7,%8,%9,%10,%11,%12,%13,%14,%15,%16,%17,%18,%19,%20,%21,%22,%23,%24,%25,%26,%27,%28,%29,%30,%31,%32,%33,%34,%35,%36,%37,%38,%39,%40,%41,%42,%43,%44,%45,%46,%47,%48,%49,%50,%51,%52,%53,%54,%55,%56,%57,%58,%59,%60,%61,%62,%63}, {%64,%65,%66,%67}, db, p, 1, 1, 1;\n}\n"
    : "+f"(d[0]),"+f"(d[1]),"+f"(d[2]),"+f"(d[3]),"+f"(d[4]),"+f"(d[5]),"+f"(d[6]),"+f"(d[7]),"+f"(d[8]),"+f"(d[9]),"+f"(d[10]),"+f"(d[11]),"+f"(d[12]),"+f"(d[13]),"+f"(d[14]),"+f"(d[15]),"+f"(d[16]),"+f"(d[17]),"+f"(d[18]),"+f"(d[19]),"+f"(d[20]),"+f"(d[21]),"+f"(d[22]),"+f"(d[23]),"+f"(d[24]),"+f"(d[25]),"+f"(d[26]),"+f"(d[27]),"+f"(d[28]),"+f"(d[29]),"+f"(d[30]),"+f"(d[31]),"+f"(d[32]),"+f"(d[33]),"+f"(d[34]),"+f"(d[35]),"+f"(d[36]),"+f"(d[37]),"+f"(d[38]),"+f"(d[39]),"+f"(d[40]),"+f"(d[41]),"+f"(d[42]),"+f"(d[43]),"+f"(d[44]),"+f"(d[45]),"+f"(d[46]),"+f"(d[47]),"+f"(d[48]),"+f"(d[49]),"+f"(d[50]),"+f"(d[51]),"+f"(d[52]),"+f"(d[53]),"+f"(d[54]),"+f"(d[55]),"+f"(d[56]),"+f"(d[57]),"+f"(d[58]),"+f"(d[59]),"+f"(d[60]),"+f"(d[61]),"+f"(d[62]),"+f"(d[63])
    : "r"(a[0]), "r"(a[1]), "r"(a[2]), "r"(a[3]), "r"(descB), "r"(scaleD));
}
__device__ __forceinline__ void wgmma_ss_n72_t11(float (&d)[36], uint32_t descA, uint32_t descB, int scaleD) {
  asm volatile("{\n.reg .pred p;\n.reg .b64 da, db;\nsetp.ne.b32 p, %38, 0;\nmov.b64 da, {%36, 0x40000040};\nmov.b64 db, {%37, 0x40000040};\n"
    "wgmma.mma_async.sync.aligned.m64n72k16.f32.bf16.bf16 {%0,%1,%2,%3,%4,%5,%6,%7,%8,%9,%10,%11,%12,%13,%14,%15,%16,%17,%18,%19,%20,%21,%22,%23,%24,%25,%26,%27,%28,%29,%30,%31,%32,%33,%34,%35}, da, db, p, 1, 1, 1, 1;\n}\n"
    : "+f"(d[0]),"+f"(d[1]),"+f"(d[2]),"+f"(d[3]),"+f"(d[4]),"+f"(d[5]),"+f"(d[6]),"+f"(d[7]),"+f"(d[8]),"+f"(d[9]),"+f"(d[10]),"+f"(d[11]),"+f"(d[12]),"+f"(d[13]),"+f"(d[14]),"+f"(d[15]),"+f"(d[16]),"+f"(d[17]),"+f"(d[18]),"+f"(d[19]),"+f"(d[20]),"+f"(d[21]),"+f"(d[22]),"+f"(d[23]),"+f"(d[24]),"+f"(d[25]),"+f"(d[26]),"+f"(d[27]),"+f"(d[28]),"+f"(d[29]),"+f"(d[30]),"+f"(d[31]),"+f"(d[32]),"+f"(d[33]),"+f"(d[34]),"+f"(d[35])
    : "r"(descA), "r"(descB), "r"(scaleD));
}

#define TSTAMP(i) do {} while (0)
#define TS2(w, i) do {} while (0)

constexpr float LOG2E = 1.4426950408889634f;

__device__ __forceinline__ void feat_exp(const uint32_t (&P)[4], float (&e)[16]) {
  uint32_t a = hmax2(P[0], P[2]), b = hmax2(P[1], P[3]);
  uint32_t mx = hmax2(__byte_perm(a, b, 0x5410), __byte_perm(a, b, 0x7632));
  a = hmin2(P[0], P[2]); b = hmin2(P[1], P[3]);
  uint32_t mn = hmin2(__byte_perm(a, b, 0x5410), __byte_perm(a, b, 0x7632));
  mx = hmax2(mx, __shfl_xor_sync(0xffffffffu, mx, 1));
  mn = hmin2(mn, __shfl_xor_sync(0xffffffffu, mn, 1));
  mx = hmax2(mx, __shfl_xor_sync(0xffffffffu, mx, 2));
  mn = hmin2(mn, __shfl_xor_sync(0xffffffffu, mn, 2));
  float mx0 = -blo(mx) * LOG2E, mx1 = -bhi(mx) * LOG2E, mn0 = blo(mn) * LOG2E, mn1 = bhi(mn) * LOG2E;
  float v[8] = {blo(P[0]), bhi(P[0]), blo(P[1]), bhi(P[1]), blo(P[2]), bhi(P[2]), blo(P[3]), bhi(P[3])};
#pragma unroll
  for (int i = 0; i < 8; i++) {
    bool r1 = (i >> 1) & 1;
    e[i]     = ex2(fmaf(v[i],  LOG2E, r1 ? mx1 : mx0));
    e[8 + i] = ex2(fmaf(v[i], -LOG2E, r1 ? mn1 : mn0));
  }
}

__global__ void __cluster_dims__(2, 1, 1) __launch_bounds__(384, 1)
fused_kernel(const __grid_constant__ Maps maps, const __nv_bfloat16* __restrict__ x, const __nv_bfloat16* __restrict__ wphi,
             const __nv_bfloat16* __restrict__ wo, const __nv_bfloat16* __restrict__ wg_, const __nv_bfloat16* __restrict__ wu_,
             const __nv_bfloat16* __restrict__ wd_, __nv_bfloat16* __restrict__ out) {
  extern __shared__ __align__(1024) unsigned char smem[];
  const uint32_t sb = smem_u32(smem);
  const int tid = threadIdx.x, lane = tid & 31;
  const int warp = __shfl_sync(0xffffffffu, tid >> 5, 0);
  const uint32_t rank = blockIdx.x & 1;
  const int cl = blockIdx.x >> 1;
  int quad, qi;
  if (cl < 4) { quad = 15; qi = cl; }
  else if (cl < 36) { quad = (cl - 4) & 7; qi = (cl - 4) >> 3; }
  else { qi = (cl - 36) / 7; quad = 8 + (cl - 36) - 7 * qi; }
  const int rb = quad, hg = 2 * qi + rank;
  const int rb3 = (quad & ~1) + rank, jf = 4 * (quad & 1) + qi;

  if (warp >= 8) {
    asm volatile("setmaxnreg.dec.sync.aligned.u32 24;");
    if (lane == 0) {
      if (warp == 8) {
#pragma unroll
        for (int k = 0; k < 9; k++) {
          const int s = k < 3 ? k : (k < 6 ? k + 3 : k - 3);
          const uint32_t bar = sb + SM_FULL + s * 8;
          mbar_init(bar, 1);
          mbar_expect_tx(bar, SLOT);
          if (s >= 3 && s < 6) tma2d(sb + s * SLOT, &maps.w, 512 + hg * 64, (s - 3) * 192, bar);
          else tma3d(sb + s * SLOT, &maps.x, 0, rb * 128 + (s >= 6 ? 64 : 0), 3 * (s % 3), bar);
        }
      } else if (warp == 9) {
        mbar_init(sb + SM_MISCB, 2);
        mbar_init(sb + SM_KVB, 32);
        mbar_expect_tx(sb + SM_MISCB, 2048);
        bulk_g2s(sb + SM_WPHI, wphi + hg * 1024, 2048, sb + SM_MISCB);
      } else if (warp == 10) {
#pragma unroll 1
        for (int i = 0; i < 16; i++) {
          mbar_init(sb + SM_XF + i * 8, 1);
          mbar_expect_tx(sb + SM_XF + i * 8, (i == 8 || i == 12) ? 20480 : 16384);
          if (i < 12) mbar_init(sb + SM_XE + i * 8, 4);
          if (i < 9) { mbar_init(sb + SM_DF + i * 8, 3); mbar_init(sb + SM_DE + i * 8, 2); }
        }
      } else {
        *reinterpret_cast<volatile unsigned*>(smem + SM_EPOCH) = atomicAdd(&g_start, 1u) / NCTA;
      }
      asm volatile("fence.mbarrier_init.release.cluster;" ::: "memory");
    }
    if (tid == 256) TS2(0, 18);
    __syncwarp();
    if (warp != 11) bar_sync(0, 352);
    asm volatile("barrier.cluster.arrive.relaxed.aligned;" ::: "memory");
    if (warp == 8) {
      asm volatile("barrier.cluster.wait.aligned;" ::: "memory");
      if (lane == 0) {
        const CUtensorMap* mg = jf == 7 ? &maps.g7 : &maps.g;
        const CUtensorMap* mu = jf == 7 ? &maps.u7 : &maps.u;
        asm volatile("prefetch.tensormap [%0];" ::"l"(&maps.wo) : "memory");
        asm volatile("prefetch.tensormap [%0];" ::"l"(mg) : "memory");
        asm volatile("prefetch.tensormap [%0];" ::"l"(mu) : "memory");
        asm volatile("prefetch.tensormap [%0];" ::"l"(&maps.d) : "memory");
        asm volatile("prefetch.tensormap [%0];" ::"l"(&maps.d48) : "memory");
#pragma unroll 1
        for (int s = ST_WV; s < ST_XC; s++) {
          if (s == ST_SCR1) continue;
          mbar_wait(sb + SM_EMPTY + (s - 9) * 8);
          const uint32_t dst = sb + (s >= 18 ? s - 18 : s - 9) * SLOT, bar = sb + SM_FULL + s * 8;
          if (s < ST_WO) tma2d(dst, &maps.w, (s < ST_WQ ? 1024 : 0) + hg * 64, (s < ST_WQ ? s - ST_WV : s - ST_WQ) * 192, bar);
          else { mbar_wait(bar - 8); tma2d(dst, &maps.wo, hg * 64, (s - ST_WO) * 192, bar); }
        }
        const int jc = jf == 7 ? 0 : jf;
        int slot = (ST_GU + 1 - rank) % NSLOT;
#pragma unroll 1
        for (int s = ST_GU + 1 - rank; s < NSTAGE; s += 2) {
          mbar_wait(sb + SM_EMPTY + (s - 9) * 8);
          if (s > ST_GU && s < ST_GU + THR) mbar_wait(sb + SM_FULL + (s - 1) * 8);
          const uint32_t dst = sb + slot * SLOT, bar = sb + SM_FULL + s * 8;
#pragma unroll 1
          for (int i = 0; i < 3; i++) {
            const int u = (s - ST_GU) * 3 + i;
            tma3d_mc(dst + i * 8192, mg, (u >> 4) * 64, jc, (u & 15) * 32, bar);
            tma3d_mc(dst + i * 8192 + 4096, mu, (u >> 4) * 64, jc, (u & 15) * 32, bar);
          }
          slot += 2; if (slot >= NSLOT) slot -= NSLOT;
        }
        slot = ST_D % NSLOT;
#pragma unroll 1
        for (int i = 0; i < 24; i++) {
          if (i < 9) mbar_wait(sb + SM_EMPTY + (ST_D - 9 + i) * 8);
          else mbar_wait_p(sb + SM_DE + slot * 8, i >= 18);
          const uint32_t bar = sb + SM_DF + slot * 8;
          mbar_expect_tx(bar, i < 16 ? 8192 : 6144);
          tma2d(sb + slot * SLOT + 16384, i < 16 ? &maps.d : &maps.d48, hg * 64, (i & 7) * 176 + (i >> 3) * 64, bar);
          if (++slot == NSLOT) slot = 0;
        }
      }
      __syncwarp();
    } else {
      asm volatile("barrier.cluster.wait.aligned;" ::: "memory");
      if (warp == 11) {
#pragma unroll
        for (int i = 0; i < 4; i++)
          reinterpret_cast<uint4*>(smem + SM_ONES)[lane + 32 * i] = make_uint4(0x3F803F80u, 0x3F803F80u, 0x3F803F80u, 0x3F803F80u);
        fence_async_smem();
        __syncwarp();
        if (lane == 0) { mbar_arrive(sb + SM_MISCB); TS2(0, 19); }
      }
      mbar_wait(sb + SM_MISCB);
      const unsigned epoch = *reinterpret_cast<volatile unsigned*>(smem + SM_EPOCH);
      const uint32_t T = (epoch & 1) ^ 1;
      if (warp == 11) {
        reinterpret_cast<float4*>(&g_kv[T][blockIdx.x * 128])[lane] = make_float4(0.f, 0.f, 0.f, 0.f);
        if (lane < 8) g_z[T][blockIdx.x * 8 + lane] = 0.f;
        mbar_wait(sb + SM_FULL + (ST_WK + 2) * 8);
        if (lane == 0) {
          asm volatile("cp.async.bulk.prefetch.L2.global [%0], 4096;" ::"l"((const char*)wo + blockIdx.x * 4096) : "memory");
          asm volatile("cp.async.bulk.prefetch.L2.global [%0], 11008;" ::"l"((const char*)wg_ + blockIdx.x * 11008) : "memory");
          asm volatile("cp.async.bulk.prefetch.L2.global [%0], 11008;" ::"l"((const char*)wu_ + blockIdx.x * 11008) : "memory");
          asm volatile("cp.async.bulk.prefetch.L2.global [%0], 11008;" ::"l"((const char*)wd_ + blockIdx.x * 11008) : "memory");
          const unsigned target = (epoch + 1) * 32;
          unsigned v; int it = 0;
#pragma unroll 1
          do {
            asm volatile("ld.acquire.gpu.global.u32 %0, [%1];" : "=r"(v) : "l"(&g_kvcnt[hg * 32]) : "memory");
            if (++it > (1 << 18)) break;
          } while ((int)(v - target) < 0);
          TS2(0, 26);
        }
        __syncwarp();
        {
          const char* src = reinterpret_cast<const char*>(&g_kv[T ^ 1][hg * 2048]) + lane * 16;
#pragma unroll
          for (int i = 0; i < 16; i++)
            asm volatile("cp.async.cg.shared.global [%0], [%1], 16;" ::"r"(sb + SM_KV32 + lane * 16 + i * 512), "l"(src + i * 512) : "memory");
          asm volatile("cp.async.cg.shared.global [%0], [%1], 16;" ::"r"(sb + SM_ONES + lane * 16), "l"(&g_z[T ^ 1][hg * 128 + lane * 4]) : "memory");
          asm volatile("cp.async.mbarrier.arrive.noinc.shared::cta.b64 [%0];" ::"r"(sb + SM_KVB) : "memory");
        }
      } else {
        const int w = warp - 9;
        st_rlx4(reinterpret_cast<uint4*>(&g_st[2 * rb + w][hg][0]) + lane, T ^ 1, T ^ 1, T ^ 1, T ^ 1);
        if (lane < 8) st_rlx4(&g_o[2 * rb + w][hg][lane >> 1][3][30 + (lane & 1)], T ^ 1, T ^ 1, T ^ 1, T ^ 1);
        if (lane < 24) st_rlx4(&g_hh[2 * rb3 + w][lane >> 3][jf][2][(lane >> 1) & 3][30 + (lane & 1)], T ^ 1, T ^ 1, T ^ 1, T ^ 1);
        bar_sync(6 + w, 160);
        if (lane == 0) {
          asm volatile("fence.acq_rel.gpu;" ::: "memory");
          TS2(w, 25);
          asm volatile("red.relaxed.gpu.global.add.u32 [%0], 1;" ::"l"(&g_kvcnt[hg * 32]) : "memory");
        }
        mbar_wait(sb + SM_KVB);
        if (w == 0) { mbar_wait(sb + SM_EMPTY + 11 * 8); mbar_wait(sb + SM_EMPTY + 12 * 8); mbar_wait(sb + SM_EMPTY + 13 * 8); }
#pragma unroll 1
        for (int ph = 0; ph < 2; ph++) {
          const int use = 2 * ph + w, r = ph ? 2 * rb3 + w : 2 * rb + w;
          const uint32_t* pw = ph ? reinterpret_cast<const uint32_t*>(&g_st[r][lane >> 2][(lane & 3) * 16 + 15])
                                  : reinterpret_cast<const uint32_t*>(&g_o[r][lane >> 2][lane & 3][3][31]);
          const char* src = reinterpret_cast<const char*>(ph ? &g_h[r][0][0][0][0] : &g_o[r][0][0][0][0]);
          uint32_t ready = 0; int it = 0;
#pragma unroll 1
          for (int p = 0; p < 4; p++) {
            const uint32_t need = ph ? 0xFFFFFFFFu : 0xFFu << (8 * p);
#pragma unroll 1
            while ((ready & need) != need) {
              ready = __ballot_sync(0xffffffffu, ((ld_rlx1(pw) ^ T) & 1) == 0);
              if (++it > (1 << 18)) break;
            }
            if (lane == 0) {
              if (p == 0) TS2(w, 27 + ph);
              if (use > 0) mbar_wait(sb + SM_XE + ((use - 1) * 4 + p) * 8);
              const uint32_t bar = sb + SM_XF + (use * 4 + p) * 8;
              if (ph && p == 0) bulk_g2s(sb + SM_KV32 + w * 4096, &g_st[r][0][0], 4096, bar);
              bulk_g2s(sb + 2 * SLOT + p * 16384, src + p * 16384, 16384, bar);
            }
            __syncwarp();
          }
        }
        {
          uint32_t ready = 0; int it = 0, slot = ST_D % NSLOT;
#pragma unroll 1
          for (int i = 0; i < 24; i++) {
            if (i < 9) mbar_wait(sb + SM_EMPTY + (ST_D - 9 + i) * 8);
            else mbar_wait_p(sb + SM_DE + slot * 8, i >= 18);
            if ((i & 7) == 0) ready = 0;
            const uint32_t* pw = reinterpret_cast<const uint32_t*>(&g_hh[2 * rb + w][i >> 3][lane >> 2][2][lane & 3][31]);
#pragma unroll 1
            while (((ready >> (4 * (i & 7))) & 15) != 15) {
              ready = __ballot_sync(0xffffffffu, ((ld_rlx1(pw) ^ T) & 1) == 0);
              if (++it > (1 << 18)) break;
            }
            if (lane == 0) {
              const uint32_t bar = sb + SM_DF + slot * 8, n = i < 16 ? 8192 : 6144;
              mbar_expect_tx(bar, n);
              bulk_g2s(sb + slot * SLOT + w * 8192, &g_hh[2 * rb + w][i >> 3][i & 7][0][0][0], n, bar);
            }
            __syncwarp();
            if (++slot == NSLOT) slot = 0;
          }
        }
      }
    }
    asm volatile("barrier.cluster.arrive.relaxed.aligned;" ::: "memory");
    asm volatile("barrier.cluster.wait.aligned;" ::: "memory");
  } else {
    asm volatile("setmaxnreg.inc.sync.aligned.u32 240;");
    if (lane == 0) {
#pragma unroll 1
      for (int d = warp; d < NSTAGE; d += 8) {
        mbar_init(sb + SM_EMPTY + d * 8, st_empty_cnt(d));
        if (d + 9 < NSTAGE) {
          mbar_init(sb + SM_FULL + (d + 9) * 8, 1);
          mbar_expect_tx(sb + SM_FULL + (d + 9) * 8, SLOT);
        }
      }
      asm volatile("fence.mbarrier_init.release.cluster;" ::: "memory");
    }
    __syncwarp();
    bar_sync(0, 352);
    asm volatile("barrier.cluster.arrive.relaxed.aligned;" ::: "memory");
    const int wg = warp >> 2, wq = warp & 3, g = lane >> 2, t = lane & 3;
    const bool lead = (tid & 127) == 0;
    const uint32_t db = ((sb & 0x3FFFF) >> 4) | (512u << 16);
    auto release = [&](int d) {
      const int s = d + NSLOT;
      mbar_arrive_cluster(sb + SM_EMPTY + d * 8, (s >= ST_GU && s < ST_D) ? (uint32_t)(s & 1) : rank);
    };
    const uint32_t lrow = (uint32_t)(wq * 16 + (lane & 7) + ((lane >> 3) & 1) * 8) * 128;
    const uint32_t lx = lane & 7, lhi = lane >> 4;
    TSTAMP(0);

    float r0, r1;
    uint32_t E[4][8];
    uint32_t T = 0;
    {
      uint32_t A[32][4];
      float acc[32];
      const int sx = wg ? ST_X1 : ST_X0;
      {
        const uint32_t base = sb + sx * SLOT + lrow;
        float cs[2][4], c0[2][4], c1[2][4];
#pragma unroll
        for (int i = 0; i < 4; i++) { cs[0][i] = cs[1][i] = c0[0][i] = c0[1][i] = c1[0][i] = c1[1][i] = 0.f; }
#pragma unroll
        for (int c = 0; c < 8; c++) {
          if (c % 3 == 0) mbar_wait(sb + SM_FULL + (sx + c / 3) * 8);
#pragma unroll
          for (int k = 0; k < 4; k++) ldsm4(A[4 * c + k], base + c * 8192 + (((2 * k + lhi) ^ lx) << 4));
#pragma unroll
          for (int k = 0; k < 4; k++) {
            const uint32_t (&f)[4] = A[4 * c + k];
            mma16816(cs[k & 1], f, 0x3F803F80u, 0x3F803F80u);
            mma16816(c0[k & 1], f, f[0], f[2]);
            mma16816(c1[k & 1], f, f[1], f[3]);
          }
        }
        const float s0 = (cs[0][0] + cs[1][0]) * (1.f / 512.f), s1 = (cs[0][2] + cs[1][2]) * (1.f / 512.f);
        TSTAMP(17);
        asm volatile("barrier.cluster.wait.aligned;" ::: "memory");
        if (lane < 3) release(sx + lane);
        const uint32_t m0 = pack2(s0, s0), m1 = pack2(s1, s1);
        float q0 = (g & 1) ? c0[0][1] + c0[1][1] : c0[0][0] + c0[1][0];
        float q1 = (g & 1) ? c1[0][3] + c1[1][3] : c1[0][2] + c1[1][2];
        q0 = __shfl_sync(0xffffffffu, q0, (lane & ~3) | (g >> 1));
        q1 = __shfl_sync(0xffffffffu, q1, (lane & ~3) | (g >> 1));
        r0 = rsqrtf(fmaxf(q0 * (1.f / 512.f) - s0 * s0, 0.f) + 1e-5f);
        r1 = rsqrtf(fmaxf(q1 * (1.f / 512.f) - s1 * s1, 0.f) + 1e-5f);
#pragma unroll
        for (int c = 0; c < 8; c++) {
#pragma unroll
          for (int ks = 4 * c; ks < 4 * c + 4; ks++) {
            A[ks][0] = hsub2(A[ks][0], m0); A[ks][1] = hsub2(A[ks][1], m1);
            A[ks][2] = hsub2(A[ks][2], m0); A[ks][3] = hsub2(A[ks][3], m1);
          }
          if (c % 3 == 0) mbar_wait(sb + SM_FULL + (ST_WK + c / 3) * 8);
          wg_fence();
#pragma unroll
          for (int ks = 4 * c; ks < 4 * c + 4; ks++) wgmma_rs_n64(acc, A[ks], DESC((ST_WK % NSLOT) * SLOT + ks * 2048), ks != 0);
          wg_commit();
          if (c == 4) { wg_wait<2>(); if (lead) release(ST_WK); }
        }
      }
      TSTAMP(1);
      uint32_t a[4][4];
      auto scale_pack = [&]() {
#pragma unroll
        for (int h = 0; h < 4; h++) {
          a[h][0] = pack2(acc[8 * h + 0] * r0, acc[8 * h + 1] * r0); a[h][1] = pack2(acc[8 * h + 2] * r1, acc[8 * h + 3] * r1);
          a[h][2] = pack2(acc[8 * h + 4] * r0, acc[8 * h + 5] * r0); a[h][3] = pack2(acc[8 * h + 6] * r1, acc[8 * h + 7] * r1);
        }
      };
      auto project = [&](const uint32_t (&b)[4][4]) {
        float pp[4][2][4];
#pragma unroll
        for (int h = 0; h < 4; h++) {
#pragma unroll
          for (int i = 0; i < 4; i++) { pp[h][0][i] = 0.f; pp[h][1][i] = 0.f; }
          mma16816(pp[h][0], a[h], b[h][0], b[h][1]);
          mma16816(pp[h][1], a[h], b[h][2], b[h][3]);
        }
#pragma unroll
        for (int h = 0; h < 4; h++) {
          a[h][0] = pack2(pp[h][0][0], pp[h][0][1]); a[h][1] = pack2(pp[h][0][2], pp[h][0][3]);
          a[h][2] = pack2(pp[h][1][0], pp[h][1][1]); a[h][3] = pack2(pp[h][1][2], pp[h][1][3]);
        }
      };
      const uint32_t wpa = sb + SM_WPHI + ((lane & 7) + ((lane >> 3) & 1) * 8) * 32 + lhi * 16;
      const uint32_t scr = sb + (wg ? (ST_SCR1 % NSLOT) : (ST_SCR0 % NSLOT)) * SLOT;
      {
        uint32_t b[4][4];
        mbar_wait(sb + SM_MISCB);
        T = (*reinterpret_cast<volatile unsigned*>(smem + SM_EPOCH) & 1) ^ 1;
#pragma unroll
        for (int h = 0; h < 4; h++) ldsm4t(b[h], wpa + h * 512);
        wg_wait<0>();
        if (lead) { release(ST_WK + 1); release(ST_WK + 2); }
        TSTAMP(2);
        scale_pack();
        project(b);
      }
      mbar_wait(sb + SM_EMPTY + (wg ? ST_SCR1 - NSLOT : ST_SCR0 - NSLOT) * 8);
      auto vgroup = [&](int c) {
        if (c % 3 == 0) mbar_wait(sb + SM_FULL + (ST_WV + c / 3) * 8);
        if (c == 0) wg_fence();
#pragma unroll
        for (int ks = 4 * c; ks < 4 * c + 4; ks++) wgmma_rs_n64(acc, A[ks], DESC((ST_WV % NSLOT) * SLOT + ks * 2048), ks != 0);
      };
#pragma unroll
      for (int h = 0; h < 4; h++) {
        vgroup(2 * h);
        float f[16];
        feat_exp(a[h], f);
        float sp0 = (f[0] + f[1]) + (f[4] + f[5]), sp1 = (f[2] + f[3]) + (f[6] + f[7]);
        float sn0 = (f[8] + f[9]) + (f[12] + f[13]), sn1 = (f[10] + f[11]) + (f[14] + f[15]);
        sp0 += __shfl_xor_sync(0xffffffffu, sp0, 1); sp1 += __shfl_xor_sync(0xffffffffu, sp1, 1);
        sn0 += __shfl_xor_sync(0xffffffffu, sn0, 1); sn1 += __shfl_xor_sync(0xffffffffu, sn1, 1);
        vgroup(2 * h + 1);
        sp0 += __shfl_xor_sync(0xffffffffu, sp0, 2); sp1 += __shfl_xor_sync(0xffffffffu, sp1, 2);
        sn0 += __shfl_xor_sync(0xffffffffu, sn0, 2); sn1 += __shfl_xor_sync(0xffffffffu, sn1, 2);
        sp0 = rcp(sp0); sp1 = rcp(sp1); sn0 = rcp(sn0); sn1 = rcp(sn1);
        const uint32_t dst = scr + (h >> 1) * 8192 + lrow;
        stsm4(dst + ((((h & 1) * 4 + lhi) ^ lx) << 4), pack2(f[0] * sp0, f[1] * sp0), pack2(f[2] * sp1, f[3] * sp1),
              pack2(f[4] * sp0, f[5] * sp0), pack2(f[6] * sp1, f[7] * sp1));
        stsm4(dst + ((((h & 1) * 4 + 2 + lhi) ^ lx) << 4), pack2(f[8] * sn0, f[9] * sn0), pack2(f[10] * sn1, f[11] * sn1),
              pack2(f[12] * sn0, f[13] * sn0), pack2(f[14] * sn1, f[15] * sn1));
      }
      wg_commit();
      TSTAMP(3);
      wg_wait<0>();
      if ((tid & 127) < 3) release(ST_WV + (tid & 127));
      TSTAMP(4);
      {
        scale_pack();
#pragma unroll
        for (int h = 0; h < 4; h++) stsm4(scr + 16384 + lrow + (((2 * h + lhi) ^ lx) << 4), a[h][0], a[h][1], a[h][2], a[h][3]);
        fence_async_smem();
        bar_sync(3, 256);
        float kv[36];
        wg_fence();
#pragma unroll
        for (int ks = 0; ks < 8; ks++) {
          const uint32_t sk = (ks < 4 ? (ST_SCR0 % NSLOT) : (ST_SCR1 % NSLOT)) * SLOT + (ks & 3) * 2048;
          const uint32_t dv = (DESC(sk + 16384) & 0xFFFFu) | (((SM_ONES - sk - 16384) >> 4) << 16);
          wgmma_ss_n72_t11(kv, DESC(sk) + wg * 512, dv, ks != 0);
        }
        wg_commit();
        wg_wait<0>();
        if (lead) { release(ST_SCR0); release(ST_SCR1); }
        const int hl = 2 * wg + (wq >> 1), f = (wq & 1) * 16 + g;
        float* kvp = &g_kv[T ^ 1][((hg * 4 + hl) * 32 + f) * 16 + 2 * t];
        float* zp = &g_z[T ^ 1][(hg * 4 + hl) * 32 + f];
        float c[8];
#pragma unroll
        for (int i = 0; i < 8; i++) c[i] = hl >= 2 ? (hl == 3 ? kv[24 + i] : kv[16 + i]) : (hl == 1 ? kv[8 + i] : kv[i]);
#pragma unroll
        for (int n = 0; n < 2; n++) {
          asm volatile("red.relaxed.gpu.global.add.v2.f32 [%0], {%1,%2};" ::"l"(kvp + n * 8), "f"(c[4 * n]), "f"(c[4 * n + 1]) : "memory");
          asm volatile("red.relaxed.gpu.global.add.v2.f32 [%0], {%1,%2};" ::"l"(kvp + n * 8 + 128), "f"(c[4 * n + 2]), "f"(c[4 * n + 3]) : "memory");
        }
        if (t < 2) asm volatile("red.relaxed.gpu.global.add.f32 [%0], %1;" ::"l"(zp + t * 8), "f"(t ? kv[34] : kv[32]) : "memory");
        bar_arrive(6 + wg, 160);
      }
      TSTAMP(5);
      {
        if (wg == 1) bar_sync(4, 256);
#pragma unroll
        for (int i = 0; i < 3; i++) {
          mbar_wait(sb + SM_FULL + (ST_WQ + i) * 8);
          wg_fence();
#pragma unroll
          for (int kk = 0; kk < 12; kk++)
            if (12 * i + kk < 32) wgmma_rs_n64(acc, A[(12 * i + kk) & 31], DESC((ST_WQ % NSLOT) * SLOT + (12 * i + kk) * 2048), (i | kk) != 0);
          wg_commit();
          if (i > 0) { wg_wait<1>(); if (lead) release(ST_WQ + i - 1); }
        }
        if (wg == 0) bar_arrive(4, 256);
        uint32_t b[4][4];
#pragma unroll
        for (int h = 0; h < 4; h++) ldsm4t(b[h], wpa + h * 512);
        wg_wait<0>();
        if (lead) release(ST_WQ + 2);
        TSTAMP(6);
        scale_pack();
        project(b);
#pragma unroll
        for (int h = 0; h < 4; h++) {
          float e[16];
          feat_exp(a[h], e);
#pragma unroll
          for (int i = 0; i < 8; i++) E[h][i] = pack2(e[2 * i], e[2 * i + 1]);
        }
      }
      TSTAMP(7);
    }
    const int rh = 2 * rb + wg;
    const uint32_t xb = sb + 2 * SLOT + wq * 2048 + lane * 16;
    mbar_wait(sb + SM_KVB);
    {
      const int r = tid & 127;
      const float4* src = reinterpret_cast<const float4*>(smem + SM_KV32) + r;
#pragma unroll
      for (int i = 0; i < 4; i++) {
        const float4 a = src[i * 128];
        *reinterpret_cast<uint2*>(smem + SM_KVS + (i * 32 + (r >> 2)) * 48 + (r & 3) * 8) = make_uint2(pack2(a.x, a.y), pack2(a.z, a.w));
      }
      const uint32_t zz = pack2(reinterpret_cast<const float*>(smem + SM_ONES)[r], 1.0f);
      *reinterpret_cast<uint4*>(smem + SM_KVS + r * 48 + 32) = make_uint4(zz, zz, zz, zz);
      bar_sync(1 + wg, 128);
    }
    TSTAMP(8);
    {
      uint4* op = &g_o[rh][hg][wq][0][lane];
#pragma unroll
      for (int h = 0; h < 4; h++) {
        uint32_t b0[4], b1[4], b2[4];
        const uint32_t kb = sb + SM_KVS + (h * 32 + lane) * 48;
        ldsm4t(b0, kb); ldsm4t(b1, kb + 16); ldsm4t(b2, kb + 32);
        const uint32_t ep[4] = {E[h][0], E[h][1], E[h][2], E[h][3]}, en[4] = {E[h][4], E[h][5], E[h][6], E[h][7]};
        float np0[4] = {0, 0, 0, 0}, np1[4] = {0, 0, 0, 0}, nn0[4] = {0, 0, 0, 0}, nn1[4] = {0, 0, 0, 0}, dp[4] = {0, 0, 0, 0}, dn[4] = {0, 0, 0, 0};
        mma16816(dp, ep, b2[0], b2[1]);  mma16816(dn, en, b2[2], b2[3]);
        mma16816(np0, ep, b0[0], b0[1]); mma16816(nn0, en, b0[2], b0[3]);
        mma16816(np1, ep, b1[0], b1[1]); mma16816(nn1, en, b1[2], b1[3]);
        const float i0 = rcp(fmaf(dp[0], dn[1], fmaf(dn[0], dp[1], 1e-6f * dp[1] * dn[1])));
        const float i1 = rcp(fmaf(dp[2], dn[3], fmaf(dn[2], dp[3], 1e-6f * dp[3] * dn[3])));
        const float cp0 = dn[1] * i0, cn0 = dp[1] * i0, cp1 = dn[3] * i1, cn1 = dp[3] * i1;
        st_rlx4(op + h * 32,
                tg(pack2(fmaf(np0[0], cp0, nn0[0] * cn0), fmaf(np0[1], cp0, nn0[1] * cn0)), T),
                pack2(fmaf(np0[2], cp1, nn0[2] * cn1), fmaf(np0[3], cp1, nn0[3] * cn1)),
                pack2(fmaf(np1[0], cp0, nn1[0] * cn0), fmaf(np1[1], cp0, nn1[1] * cn0)),
                pack2(fmaf(np1[2], cp1, nn1[2] * cn1), fmaf(np1[3], cp1, nn1[3] * cn1)));
      }
    }
    TSTAMP(9);

    {
      uint32_t xr[16];
      {
        const uint32_t* xp = reinterpret_cast<const uint32_t*>(x + (size_t)(rh * 64 + wq * 16 + g) * 512 + hg * 64 + 2 * t);
#pragma unroll
        for (int i = 0; i < 8; i++) { xr[2 * i] = __ldg(xp + 4 * i); xr[2 * i + 1] = __ldg(xp + 8 * 256 + 4 * i); }
      }
      uint32_t A[8][4][4];
      const uint4* op = &g_o[rh][0][wq][0][lane];
      float acc[32];
      mbar_wait(sb + SM_XF + (wg * 4) * 8);
      lds_chunk(A[0], xb); lds_chunk(A[1], xb + 8192);
#pragma unroll
      for (int p = 0; p < 4; p++) {
        chk_chunk(A[2 * p], op + 2 * p * 512, T);
        chk_chunk(A[2 * p + 1], op + (2 * p + 1) * 512, T);
        if (lane == 0) mbar_arrive(sb + SM_XE + (wg * 4 + p) * 8);
#pragma unroll
        for (int c = 2 * p; c < 2 * p + 2; c++) {
          if (c % 3 == 0) mbar_wait(sb + SM_FULL + (ST_WO + c / 3) * 8);
          if ((c & 1) && p < 3) {
            mbar_wait(sb + SM_XF + (wg * 4 + p + 1) * 8);
            lds_chunk(A[2 * p + 2], xb + (p + 1) * 16384); lds_chunk(A[2 * p + 3], xb + (p + 1) * 16384 + 8192);
          }
          wg_fence();
#pragma unroll
          for (int s = 0; s < 4; s++)
            wgmma_rs_n64(acc, A[c][s], DESC(((ST_WO + c / 3) % NSLOT) * SLOT + ((c % 3) * 4 + s) * 2048), (c | s) != 0);
          wg_commit();
        }
      }
      wg_wait<0>();
      if ((tid & 127) < 3) release(ST_WO + (tid & 127));
      TSTAMP(10);
      uint32_t hw[16];
      float s0 = 0.f, s1 = 0.f, q0 = 0.f, q1 = 0.f;
#pragma unroll
      for (int i = 0; i < 8; i++) {
        hw[2 * i]     = pack2(blo(xr[2 * i]) + acc[4 * i], bhi(xr[2 * i]) + acc[4 * i + 1]);
        hw[2 * i + 1] = pack2(blo(xr[2 * i + 1]) + acc[4 * i + 2], bhi(xr[2 * i + 1]) + acc[4 * i + 3]);
      }
      uint4* hp_ = &g_h[rh][hg][wq][0][lane];
#pragma unroll
      for (int s = 0; s < 4; s++) st_rlx4(hp_ + s * 32, tg(hw[4 * s], T), hw[4 * s + 1], hw[4 * s + 2], hw[4 * s + 3]);
#pragma unroll
      for (int i = 0; i < 8; i++) {
        float a = blo(hw[2 * i]), b = bhi(hw[2 * i]);
        s0 += a + b; q0 = fmaf(a, a, q0); q0 = fmaf(b, b, q0);
        a = blo(hw[2 * i + 1]); b = bhi(hw[2 * i + 1]);
        s1 += a + b; q1 = fmaf(a, a, q1); q1 = fmaf(b, b, q1);
      }
      s0 += __shfl_xor_sync(0xffffffffu, s0, 1); s1 += __shfl_xor_sync(0xffffffffu, s1, 1);
      q0 += __shfl_xor_sync(0xffffffffu, q0, 1); q1 += __shfl_xor_sync(0xffffffffu, q1, 1);
      s0 += __shfl_xor_sync(0xffffffffu, s0, 2); s1 += __shfl_xor_sync(0xffffffffu, s1, 2);
      q0 += __shfl_xor_sync(0xffffffffu, q0, 2); q1 += __shfl_xor_sync(0xffffffffu, q1, 2);
      if (t < 2) st_rlx2(&g_st[rh][hg][wq * 16 + g + t * 8], tg(__float_as_uint(t ? s1 : s0), T), __float_as_uint(t ? q1 : q0));
      uint32_t hx = T;
#pragma unroll
      for (int i = 0; i < 4; i++) hx |= (hw[4 * i] & 1u) << (i + 1);
      st_rlx1(&g_hx[rh][hg][wq][lane], hx);
    }
    TSTAMP(11);

    const int rh3 = 2 * rb3 + wg;
    {
      uint32_t A[8][4][4];
      const uint4* hp_ = &g_h[rh3][0][wq][0][lane];
      uint4* hhp = &g_hh[rh3][0][jf][0][wq][lane];
      const uint32_t dg = (db & 0xFFFFu) | (256u << 16);
      uint32_t m0, m1;
      mbar_wait(sb + SM_XF + ((2 + wg) * 4) * 8);
      lds_chunk(A[0], xb); lds_chunk(A[1], xb + 8192);
      {
        const uint2* sp = &g_st[rh3][2 * t][wq * 16 + g];
        const uint2* ss = reinterpret_cast<const uint2*>(smem + SM_KV32 + wg * 4096) + 2 * t * 64 + wq * 16 + g;
        uint2 a0 = ss[0], a1 = ss[64], b0 = ss[8], b1 = ss[72];
        int it = 0;
#pragma unroll 1
        while (__any_sync(0xffffffffu, bad4(a0.x, a1.x, b0.x, b1.x, T) & 1)) {
          ld_rlx2(a0.x, a0.y, sp); ld_rlx2(a1.x, a1.y, sp + 64); ld_rlx2(b0.x, b0.y, sp + 8); ld_rlx2(b1.x, b1.y, sp + 72);
          if (++it > (1 << 18)) break;
        }
        float s0 = __uint_as_float(a0.x) + __uint_as_float(a1.x), q0 = __uint_as_float(a0.y) + __uint_as_float(a1.y);
        float s1 = __uint_as_float(b0.x) + __uint_as_float(b1.x), q1 = __uint_as_float(b0.y) + __uint_as_float(b1.y);
        s0 += __shfl_xor_sync(0xffffffffu, s0, 1); s1 += __shfl_xor_sync(0xffffffffu, s1, 1);
        q0 += __shfl_xor_sync(0xffffffffu, q0, 1); q1 += __shfl_xor_sync(0xffffffffu, q1, 1);
        s0 += __shfl_xor_sync(0xffffffffu, s0, 2); s1 += __shfl_xor_sync(0xffffffffu, s1, 2);
        q0 += __shfl_xor_sync(0xffffffffu, q0, 2); q1 += __shfl_xor_sync(0xffffffffu, q1, 2);
        s0 *= (1.f / 512.f); s1 *= (1.f / 512.f);
        r0 = rcp(fmaxf(q0 * (1.f / 512.f) - s0 * s0, 0.f) + 1e-5f);
        r1 = rcp(fmaxf(q1 * (1.f / 512.f) - s1 * s1, 0.f) + 1e-5f);
        m0 = pack2(s0, s0); m1 = pack2(s1, s1);
      }
      TSTAMP(12);
#define UOFF(u) ((((ST_GU + (u) / 3) % NSLOT) * SLOT + ((u) % 3) * 8192) >> 4)
#define UNIT_PRE(u)  do { if ((u) % 3 == 0) mbar_wait(sb + SM_FULL + (ST_GU + (u) / 3) * 8); wg_fence(); } while (0)
#define UNIT_POST(u) do { wg_commit(); if ((u) % 3 == 1 && (u) > 3) { wg_wait<2>(); if (lead) release(ST_GU + (u) / 3 - 1); } } while (0)
      float acc[64];
      const int rz = blockIdx.y;
#pragma unroll
      for (int ps = 0; ps < 2; ps++) {
#pragma unroll
        for (int k = 0; k < 16; k++) {
          const int u = 16 * ps + k, c = k >> 1;
          if (ps == 0 && (k & 3) == 0) {
            const int p = k >> 2;
            chk_chunk(A[2 * p], hp_ + 2 * p * 512, T);
            chk_chunk(A[2 * p + 1], hp_ + (2 * p + 1) * 512, T);
            if (lane == 0) {
              if (wg == 0) mbar_arrive(sb + SM_XE + (8 + p) * 8);
              else if (p > 0) release(ST_XC + p - 1);
            }
          }
          if (ps == 0 && (k & 3) == 1 && k < 12) {
            const int p = (k >> 2) + 1;
            mbar_wait(sb + SM_XF + ((2 + wg) * 4 + p) * 8);
            lds_chunk(A[2 * p], xb + p * 16384);
            lds_chunk(A[2 * p + 1], xb + p * 16384 + 8192);
          }
          if (ps == 0 && (k & 1) == 0) {
#pragma unroll
            for (int s = 0; s < 4; s++) {
              A[c][s][0] = hsub2(A[c][s][0], m0); A[c][s][1] = hsub2(A[c][s][1], m1);
              A[c][s][2] = hsub2(A[c][s][2], m0); A[c][s][3] = hsub2(A[c][s][3], m1);
            }
          }
          UNIT_PRE(u);
          wgmma_rs_n128(acc, A[c][(k & 1) * 2], dg + UOFF(u), k != 0 ? 1 : (ps ? rz : 0));
          wgmma_rs_n128(acc, A[c][(k & 1) * 2 + 1], dg + UOFF(u) + 128, 1);
          UNIT_POST(u);
        }
        wg_wait<0>();
#pragma unroll
        for (int k = 0; k < 4; k++) {
          const int s = k == 2 ? 3 : (k == 3 ? 2 : k);
          st_rlx4(hhp + ps * 4096 + s * 128,
                  tg(pack2(acc[8 * s + 0] * acc[32 + 8 * s + 0] * r0, acc[8 * s + 1] * acc[32 + 8 * s + 1] * r0), T),
                  pack2(acc[8 * s + 2] * acc[32 + 8 * s + 2] * r1, acc[8 * s + 3] * acc[32 + 8 * s + 3] * r1),
                  pack2(acc[8 * s + 4] * acc[32 + 8 * s + 4] * r0, acc[8 * s + 5] * acc[32 + 8 * s + 5] * r0),
                  pack2(acc[8 * s + 6] * acc[32 + 8 * s + 6] * r1, acc[8 * s + 7] * acc[32 + 8 * s + 7] * r1));
        }
      }
      {
        float ag[24], au[24];
        bar_sync(1 + wg, 128);
#pragma unroll
        for (int k = 0; k < 16; k++) {
          const int u = 32 + k, c = k >> 1;
          UNIT_PRE(u);
          wgmma_rs_n48(ag, A[c][(k & 1) * 2], dg + UOFF(u), k != 0);
          wgmma_rs_n48(au, A[c][(k & 1) * 2], dg + UOFF(u) + 256, k != 0);
          wgmma_rs_n48(ag, A[c][(k & 1) * 2 + 1], dg + UOFF(u) + 128, 1);
          wgmma_rs_n48(au, A[c][(k & 1) * 2 + 1], dg + UOFF(u) + 256 + 128, 1);
          UNIT_POST(u);
        }
        wg_wait<0>();
        if (lead) release(ST_D - 1);
        TSTAMP(13);
#pragma unroll
        for (int s = 0; s < 3; s++)
          st_rlx4(hhp + 2 * 4096 + s * 128,
                  tg(pack2(ag[8 * s + 0] * au[8 * s + 0] * r0, ag[8 * s + 1] * au[8 * s + 1] * r0), T),
                  pack2(ag[8 * s + 2] * au[8 * s + 2] * r1, ag[8 * s + 3] * au[8 * s + 3] * r1),
                  pack2(ag[8 * s + 4] * au[8 * s + 4] * r0, ag[8 * s + 5] * au[8 * s + 5] * r0),
                  pack2(ag[8 * s + 6] * au[8 * s + 6] * r1, ag[8 * s + 7] * au[8 * s + 7] * r1));
      }
    }
    TSTAMP(14);

    {
      float acc[32];
      uint32_t F[2][4][4], hr[4][4];
      ld_chunk(hr, &g_h[rh][hg][wq][0][lane]);
      const uint32_t hx = ld_rlx1(&g_hx[rh][hg][wq][lane]);
      const uint4* gp = &g_hh[rh][0][0][0][wq][lane];
      const uint32_t fb = sb + wg * 8192 + wq * 512 + lane * 16;
      auto load = [&](uint32_t (&f)[4][4], int i, int slot, int nk) {
        mbar_wait_p(sb + SM_DF + slot * 8, i >= 9 && i < 18);
#pragma unroll
        for (int s = 0; s < 4; s++)
          if (s < nk) asm volatile("ld.shared.v4.b32 {%0,%1,%2,%3}, [%4];" : "=r"(f[s][0]), "=r"(f[s][1]), "=r"(f[s][2]), "=r"(f[s][3])
                                   : "r"(fb + slot * SLOT + s * 2048) : "memory");
        int it = 0;
#pragma unroll 1
        while (__any_sync(0xffffffffu, bad4(f[0][0], f[1][0], f[2][0], f[nk - 1][0], T) & 1)) {
#pragma unroll
          for (int s = 0; s < 4; s++) if (s < nk) ld_rlx4(f[s], gp + i * 512 + s * 128);
          if (++it > (1 << 18)) break;
        }
      };
      int slot = ST_D % NSLOT, pslot = 0;
      load(F[0], 0, slot, 4);
      auto stage = [&](int i, int b, int nk, int nk_next, bool last) {
        wg_fence();
#pragma unroll
        for (int s = 0; s < 4; s++) if (s < nk) wgmma_rs_n64(acc, F[b][s], db + slot * (SLOT >> 4) + 1024 + s * 128, (i | s) != 0);
        wg_commit();
        wg_wait<1>();
        if (lead && i > 0) mbar_arrive(sb + SM_DE + pslot * 8);
        pslot = slot;
        if (++slot == NSLOT) slot = 0;
        if (!last) load(F[b ^ 1], i + 1, slot, nk_next);
      };
#pragma unroll 1
      for (int i = 0; i < 14; i += 2) { stage(i, 0, 4, 4, false); stage(i + 1, 1, 4, 4, false); }
      stage(14, 0, 4, 4, false); stage(15, 1, 4, 3, false);
#pragma unroll 1
      for (int i = 16; i < 24; i += 2) { stage(i, 0, 3, 3, false); stage(i + 1, 1, 3, 3, i == 22); }
      wg_wait<0>();
      TSTAMP(15);
#pragma unroll
      for (int s = 0; s < 4; s++) hr[s][0] = (hr[s][0] & 0xFFFFFFFEu) | ((hx >> (s + 1)) & 1u);
      uint32_t* op = reinterpret_cast<uint32_t*>(out + (size_t)(rh * 64 + wq * 16 + g) * 512 + hg * 64 + 2 * t);
#pragma unroll
      for (int i = 0; i < 8; i++) {
        const uint32_t h0 = hr[i >> 1][(i & 1) * 2], h1 = hr[i >> 1][(i & 1) * 2 + 1];
        op[4 * i]           = pack2(blo(h0) + acc[4 * i], bhi(h0) + acc[4 * i + 1]);
        op[8 * 256 + 4 * i] = pack2(blo(h1) + acc[4 * i + 2], bhi(h1) + acc[4 * i + 3]);
      }
    }
    TSTAMP(16);
    asm volatile("barrier.cluster.arrive.relaxed.aligned;" ::: "memory");
    asm volatile("barrier.cluster.wait.aligned;" ::: "memory");
  }
}

typedef CUresult (*EncodeFn)(CUtensorMap*, CUtensorMapDataType, cuuint32_t, void*, const cuuint64_t*, const cuuint64_t*,
                             const cuuint32_t*, const cuuint32_t*, CUtensorMapInterleave, CUtensorMapSwizzle,
                             CUtensorMapL2promotion, CUtensorMapFloatOOBfill);

void encode(EncodeFn fn, CUtensorMap* m, const void* base, int rank, const cuuint64_t* dims, const cuuint64_t* strides,
            const cuuint32_t* box) {
  cuuint32_t es[3] = {1, 1, 1};
  fn(m, CU_TENSOR_MAP_DATA_TYPE_BFLOAT16, (cuuint32_t)rank, const_cast<void*>(base), dims, strides, box, es,
     CU_TENSOR_MAP_INTERLEAVE_NONE, CU_TENSOR_MAP_SWIZZLE_128B, CU_TENSOR_MAP_L2_PROMOTION_L2_256B,
     CU_TENSOR_MAP_FLOAT_OOB_FILL_NONE);
}

}

extern "C" void kernel_launch(void* const* d_in, const int* in_sizes, int n_in, void* d_out, int out_size) {
  (void)in_sizes; (void)n_in; (void)out_size;
  const __nv_bfloat16* x    = (const __nv_bfloat16*)d_in[0];
  const __nv_bfloat16* wqkv = (const __nv_bfloat16*)d_in[1];
  const __nv_bfloat16* wphi = (const __nv_bfloat16*)d_in[2];
  const __nv_bfloat16* wo   = (const __nv_bfloat16*)d_in[3];
  const __nv_bfloat16* wg   = (const __nv_bfloat16*)d_in[5];
  const __nv_bfloat16* wu   = (const __nv_bfloat16*)d_in[6];
  const __nv_bfloat16* wd   = (const __nv_bfloat16*)d_in[7];

  static EncodeFn fn = nullptr;
  if (!fn) {
    void* p = nullptr;
    cudaDriverEntryPointQueryResult qr;
    cudaGetDriverEntryPoint("cuTensorMapEncodeTiled", &p, cudaEnableDefault, &qr);
    fn = (EncodeFn)p;
    cudaFuncSetAttribute(fused_kernel, cudaFuncAttributeMaxDynamicSharedMemorySize, SM_TOTAL);
  }
  Maps maps;
  {
    cuuint64_t d[3] = {64, 2048, 8}, s[2] = {1024, 128}; cuuint32_t b[3] = {64, 64, 3};
    encode(fn, &maps.x, x, 3, d, s, b);
  }
  {
    cuuint64_t d[2] = {1536, 512}, s[1] = {3072}; cuuint32_t b[2] = {64, 192};
    encode(fn, &maps.w, wqkv, 2, d, s, b);
  }
  {
    cuuint64_t d[2] = {512, 512}, s[1] = {1024}; cuuint32_t b[2] = {64, 192};
    encode(fn, &maps.wo, wo, 2, d, s, b);
  }
  {
    cuuint64_t d[3] = {176, 7, 512}, d7[3] = {144, 1, 512}, s[2] = {352, 2752}; cuuint32_t b[3] = {64, 1, 32};
    encode(fn, &maps.g, wg, 3, d, s, b);
    encode(fn, &maps.u, wu, 3, d, s, b);
    encode(fn, &maps.g7, wg + 1232, 3, d7, s, b);
    encode(fn, &maps.u7, wu + 1232, 3, d7, s, b);
  }
  {
    cuuint64_t d[2] = {512, 1376}, s[1] = {1024}; cuuint32_t b[2] = {64, 64}, b2[2] = {64, 48};
    encode(fn, &maps.d, wd, 2, d, s, b);
    encode(fn, &maps.d48, wd, 2, d, s, b2);
  }
  fused_kernel<<<NCTA, 384, SM_TOTAL>>>(maps, x, wphi, wo, wg, wu, wd, (__nv_bfloat16*)d_out);
}
```

```cpp
#include <cuda_runtime.h>
#include <cuda_bf16.h>
#include <cuda.h>
#include <stdint.h>

#define PROF 0

#define THR 6

namespace {

constexpr int NCTA   = 128;
constexpr int SLOT   = 24576;
constexpr int NSLOT  = 9;
constexpr int NSTAGE = 39;

constexpr int ST_X0   = 0;
constexpr int ST_WK   = 3;
constexpr int ST_X1   = 6;
constexpr int ST_SCR0 = 9;
constexpr int ST_WV   = 10;
constexpr int ST_SCR1 = 13;
constexpr int ST_WQ   = 14;
constexpr int ST_WO   = 17;
constexpr int ST_XC   = 20;
constexpr int ST_GU   = 23;
constexpr int ST_D    = 39;

__host__ __device__ constexpr int st_empty_cnt(int d) {
  return ((d < 3 || (d >= 6 && d < 9) || (d >= ST_XC && d < ST_GU)) ? 4 : 2) * (d + 9 >= ST_GU ? 2 : 1);
}

constexpr int SM_ONES = NSLOT * SLOT;
constexpr int SM_WPHI = SM_ONES + 2048;
constexpr int SM_KVS  = SM_WPHI + 2048;
constexpr int SM_KV32 = 4 * SLOT + 16384;
constexpr int SM_BAR  = SM_KVS + 6144;
constexpr int SM_FULL  = SM_BAR;
constexpr int SM_EMPTY = SM_BAR + NSTAGE * 8;
constexpr int SM_MISCB = SM_BAR + 2 * NSTAGE * 8;
constexpr int SM_KVB   = SM_MISCB + 8;
constexpr int SM_EPOCH = SM_KVB + 8;
constexpr int SM_XF    = SM_EPOCH + 8;
constexpr int SM_XE    = SM_XF + 16 * 8;
constexpr int SM_DF    = SM_XE + 12 * 8;
constexpr int SM_DE    = SM_DF + 9 * 8;
constexpr int SM_TOTAL = SM_BAR + 1024;

static_assert(SM_TOTAL == 232448 && SM_DE + 9 * 8 <= SM_TOTAL, "smem budget");

struct Maps { CUtensorMap x, w, wo, g, u, g7, u7, d, d48; };

__device__ uint4    g_o[32][8][4][4][32];
__device__ uint4    g_h[32][8][4][4][32];
__device__ uint32_t g_hx[32][8][4][32];
__device__ uint2    g_st[32][8][64];
__device__ uint4    g_hh[32][3][8][4][4][32];
__device__ float    g_kv[2][32 * 32 * 16];
__device__ float    g_z[2][32 * 32];
__device__ unsigned g_kvcnt[8 * 32];
__device__ unsigned g_start;

__device__ __forceinline__ uint32_t smem_u32(const void* p) { return (uint32_t)__cvta_generic_to_shared(p); }
__device__ __forceinline__ void mbar_init(uint32_t bar, int cnt) {
  asm volatile("mbarrier.init.shared::cta.b64 [%0], %1;" ::"r"(bar), "r"(cnt) : "memory");
}
__device__ __forceinline__ void mbar_expect_tx(uint32_t bar, uint32_t bytes) {
  asm volatile("mbarrier.arrive.expect_tx.shared::cta.b64 _, [%0], %1;" ::"r"(bar), "r"(bytes) : "memory");
}
__device__ __forceinline__ void mbar_arrive(uint32_t bar) {
  asm volatile("mbarrier.arrive.shared::cta.b64 _, [%0];" ::"r"(bar) : "memory");
}
__device__ __forceinline__ void mbar_arrive_cluster(uint32_t bar, uint32_t rank) {
  asm volatile("{\n.reg .b32 ra;\nmapa.shared::cluster.u32 ra, %0, %1;\n"
               "mbarrier.arrive.shared::cluster.b64 _, [ra];\n}" ::"r"(bar), "r"(rank) : "memory");
}
__device__ __forceinline__ bool mbar_try(uint32_t bar) {
  uint32_t ok;
  asm volatile("{\n.reg .pred p;\nmbarrier.try_wait.parity.shared::cta.b64 p, [%1], 0;\nselp.u32 %0, 1, 0, p;\n}"
               : "=r"(ok) : "r"(bar) : "memory");
  return ok != 0;
}
__device__ __forceinline__ void mbar_wait_p(uint32_t bar, uint32_t parity) {
  uint32_t ok; int it = 0;
#pragma unroll 1
  do {
    asm volatile("{\n.reg .pred p;\nmbarrier.try_wait.parity.shared::cta.b64 p, [%1], %2;\nselp.u32 %0, 1, 0, p;\n}"
                 : "=r"(ok) : "r"(bar), "r"(parity) : "memory");
  } while (!ok && ++it < (1 << 18));
}
__device__ __forceinline__ void mbar_wait(uint32_t bar) {
  int it = 0;
#pragma unroll 1
  while (!mbar_try(bar)) {
    if (++it > (1 << 20)) __trap();
  }
}
__device__ __forceinline__ void bar_sync(int id, int n)   { asm volatile("bar.sync %0, %1;" ::"r"(id), "r"(n) : "memory"); }
__device__ __forceinline__ void bar_arrive(int id, int n) { asm volatile("bar.arrive %0, %1;" ::"r"(id), "r"(n) : "memory"); }
__device__ __forceinline__ void fence_async_smem() { asm volatile("fence.proxy.async.shared::cta;" ::: "memory"); }
__device__ __forceinline__ void wg_fence()  { asm volatile("wgmma.fence.sync.aligned;" ::: "memory"); }
__device__ __forceinline__ void wg_commit() { asm volatile("wgmma.commit_group.sync.aligned;" ::: "memory"); }
template <int N> __device__ __forceinline__ void wg_wait() { asm volatile("wgmma.wait_group.sync.aligned %0;" ::"n"(N) : "memory"); }
#define DESC(off) (db + ((uint32_t)(off) >> 4))
__device__ __forceinline__ void tma2d(uint32_t dst, const CUtensorMap* m, int c0, int c1, uint32_t bar) {
  asm volatile("cp.async.bulk.tensor.2d.shared::cluster.global.mbarrier::complete_tx::bytes [%0], [%1, {%3, %4}], [%2];"
               ::"r"(dst), "l"(m), "r"(bar), "r"(c0), "r"(c1) : "memory");
}
__device__ __forceinline__ void tma3d(uint32_t dst, const CUtensorMap* m, int c0, int c1, int c2, uint32_t bar) {
  asm volatile("cp.async.bulk.tensor.3d.shared::cluster.global.mbarrier::complete_tx::bytes [%0], [%1, {%3, %4, %5}], [%2];"
               ::"r"(dst), "l"(m), "r"(bar), "r"(c0), "r"(c1), "r"(c2) : "memory");
}
__device__ __forceinline__ void tma3d_mc(uint32_t dst, const CUtensorMap* m, int c0, int c1, int c2, uint32_t bar) {
  asm volatile("cp.async.bulk.tensor.3d.shared::cluster.global.mbarrier::complete_tx::bytes.multicast::cluster [%0], [%1, {%3, %4, %5}], [%2], %6;"
               ::"r"(dst), "l"(m), "r"(bar), "r"(c0), "r"(c1), "r"(c2), "h"((uint16_t)3) : "memory");
}
__device__ __forceinline__ void ldsm4(uint32_t (&r)[4], uint32_t addr) {
  asm volatile("ldmatrix.sync.aligned.m8n8.x4.shared.b16 {%0,%1,%2,%3}, [%4];"
               : "=r"(r[0]), "=r"(r[1]), "=r"(r[2]), "=r"(r[3]) : "r"(addr) : "memory");
}
__device__ __forceinline__ void ldsm4t(uint32_t (&r)[4], uint32_t addr) {
  asm volatile("ldmatrix.sync.aligned.m8n8.x4.trans.shared.b16 {%0,%1,%2,%3}, [%4];"
               : "=r"(r[0]), "=r"(r[1]), "=r"(r[2]), "=r"(r[3]) : "r"(addr) : "memory");
}
__device__ __forceinline__ void stsm4(uint32_t addr, uint32_t r0, uint32_t r1, uint32_t r2, uint32_t r3) {
  asm volatile("stmatrix.sync.aligned.m8n8.x4.shared.b16 [%0], {%1,%2,%3,%4};"
               ::"r"(addr), "r"(r0), "r"(r1), "r"(r2), "r"(r3) : "memory");
}
__device__ __forceinline__ void mma16816(float (&c)[4], const uint32_t (&a)[4], uint32_t b0, uint32_t b1) {
  asm volatile("mma.sync.aligned.m16n8k16.row.col.f32.bf16.bf16.f32 {%0,%1,%2,%3},{%4,%5,%6,%7},{%8,%9},{%0,%1,%2,%3};"
               : "+f"(c[0]), "+f"(c[1]), "+f"(c[2]), "+f"(c[3])
               : "r"(a[0]), "r"(a[1]), "r"(a[2]), "r"(a[3]), "r"(b0), "r"(b1));
}
__device__ __forceinline__ uint32_t pack2(float lo, float hi) {
  uint32_t r; asm("cvt.rn.bf16x2.f32 %0, %1, %2;" : "=r"(r) : "f"(hi), "f"(lo)); return r;
}
__device__ __forceinline__ float blo(uint32_t w) { return __uint_as_float(w << 16); }
__device__ __forceinline__ float bhi(uint32_t w) { return __uint_as_float(w & 0xFFFF0000u); }
__device__ __forceinline__ uint32_t hsub2(uint32_t a, uint32_t b) { uint32_t r; asm("sub.rn.bf16x2 %0, %1, %2;" : "=r"(r) : "r"(a), "r"(b)); return r; }
__device__ __forceinline__ uint32_t hmax2(uint32_t a, uint32_t b) { uint32_t r; asm("max.bf16x2 %0, %1, %2;" : "=r"(r) : "r"(a), "r"(b)); return r; }
__device__ __forceinline__ uint32_t hmin2(uint32_t a, uint32_t b) { uint32_t r; asm("min.bf16x2 %0, %1, %2;" : "=r"(r) : "r"(a), "r"(b)); return r; }
__device__ __forceinline__ float ex2(float x) { float r; asm("ex2.approx.ftz.f32 %0, %1;" : "=f"(r) : "f"(x)); return r; }
__device__ __forceinline__ float rcp(float x) { float r; asm("rcp.approx.ftz.f32 %0, %1;" : "=f"(r) : "f"(x)); return r; }
__device__ __forceinline__ void ld_rlx4(uint32_t (&r)[4], const uint4* p) {
  asm volatile("{\n.reg .b128 v;\nld.relaxed.gpu.global.b128 v, [%4];\nmov.b128 {%0,%1,%2,%3}, v;\n}"
               : "=r"(r[0]), "=r"(r[1]), "=r"(r[2]), "=r"(r[3]) : "l"(p) : "memory");
}
__device__ __forceinline__ void st_rlx4(uint4* p, uint32_t a, uint32_t b, uint32_t c, uint32_t d) {
  asm volatile("{\n.reg .b128 v;\nmov.b128 v, {%1,%2,%3,%4};\nst.relaxed.gpu.global.b128 [%0], v;\n}"
               ::"l"(p), "r"(a), "r"(b), "r"(c), "r"(d) : "memory");
}
__device__ __forceinline__ void st_rlx2(uint2* p, uint32_t a, uint32_t b) {
  asm volatile("{\n.reg .b64 v;\nmov.b64 v, {%1,%2};\nst.relaxed.gpu.global.b64 [%0], v;\n}" ::"l"(p), "r"(a), "r"(b) : "memory");
}
__device__ __forceinline__ uint32_t ld_rlx1(const uint32_t* p) {
  uint32_t r; asm volatile("ld.relaxed.gpu.global.b32 %0, [%1];" : "=r"(r) : "l"(p) : "memory"); return r;
}
__device__ __forceinline__ void st_rlx1(uint32_t* p, uint32_t a) {
  asm volatile("st.relaxed.gpu.global.b32 [%0], %1;" ::"l"(p), "r"(a) : "memory");
}
__device__ __forceinline__ void ld_rlx2(uint32_t& a, uint32_t& b, const uint2* p) {
  asm volatile("{\n.reg .b64 v;\nld.relaxed.gpu.global.b64 v, [%2];\nmov.b64 {%0,%1}, v;\n}" : "=r"(a), "=r"(b) : "l"(p) : "memory");
}
__device__ __forceinline__ void bulk_g2s(uint32_t dst, const void* src, uint32_t bytes, uint32_t bar) {
  asm volatile("cp.async.bulk.shared::cluster.global.mbarrier::complete_tx::bytes [%0], [%1], %2, [%3];"
               ::"r"(dst), "l"(src), "r"(bytes), "r"(bar) : "memory");
}
__device__ __forceinline__ uint32_t tg(uint32_t w, uint32_t T) { return (w & 0xFFFFFFFEu) | T; }
__device__ __forceinline__ uint32_t bad4(uint32_t a, uint32_t b, uint32_t c, uint32_t d, uint32_t T) {
  uint32_t u, v;
  asm("lop3.b32 %0, %1, %2, %3, 0x7E;" : "=r"(u) : "r"(a), "r"(b), "r"(T));
  asm("lop3.b32 %0, %1, %2, %3, 0x7E;" : "=r"(v) : "r"(c), "r"(d), "r"(T));
  return u | v;
}

__device__ __forceinline__ void ld_chunk(uint32_t (&a)[4][4], const uint4* p) {
#pragma unroll
  for (int s = 0; s < 4; s++) ld_rlx4(a[s], p + s * 32);
}
__device__ __forceinline__ void lds_chunk(uint32_t (&a)[4][4], uint32_t addr) {
#pragma unroll
  for (int s = 0; s < 4; s++)
    asm volatile("ld.shared.v4.b32 {%0,%1,%2,%3}, [%4];" : "=r"(a[s][0]), "=r"(a[s][1]), "=r"(a[s][2]), "=r"(a[s][3])
                 : "r"(addr + s * 512) : "memory");
}
__device__ __forceinline__ void chk_chunk(uint32_t (&a)[4][4], const uint4* p, uint32_t T) {
  int it = 0;
#pragma unroll 1
  while (__any_sync(0xffffffffu, bad4(a[0][0], a[1][0], a[2][0], a[3][0], T) & 1)) {
    ld_chunk(a, p);
    if (++it > (1 << 18)) break;
  }
}

__device__ __forceinline__ void wgmma_rs_n48(float (&d)[24], const uint32_t (&a)[4], uint32_t descB, int scaleD) {
  asm volatile("{\n.reg .pred p;\n.reg .b64 db;\nsetp.ne.b32 p, %29, 0;\nmov.b64 db, {%28, 0x40000040};\n"
    "wgmma.mma_async.sync.aligned.m64n48k16.f32.bf16.bf16 {%0,%1,%2,%3,%4,%5,%6,%7,%8,%9,%10,%11,%12,%13,%14,%15,%16,%17,%18,%19,%20,%21,%22,%23}, {%24,%25,%26,%27}, db, p, 1, 1, 1;\n}\n"
    : "+f"(d[0]),"+f"(d[1]),"+f"(d[2]),"+f"(d[3]),"+f"(d[4]),"+f"(d[5]),"+f"(d[6]),"+f"(d[7]),"+f"(d[8]),"+f"(d[9]),"+f"(d[10]),"+f"(d[11]),"+f"(d[12]),"+f"(d[13]),"+f"(d[14]),"+f"(d[15]),"+f"(d[16]),"+f"(d[17]),"+f"(d[18]),"+f"(d[19]),"+f"(d[20]),"+f"(d[21]),"+f"(d[22]),"+f"(d[23])
    : "r"(a[0]), "r"(a[1]), "r"(a[2]), "r"(a[3]), "r"(descB), "r"(scaleD));
}
__device__ __forceinline__ void wgmma_rs_n64(float (&d)[32], const uint32_t (&a)[4], uint32_t descB, int scaleD) {
  asm volatile("{\n.reg .pred p;\n.reg .b64 db;\nsetp.ne.b32 p, %37, 0;\nmov.b64 db, {%36, 0x40000040};\n"
    "wgmma.mma_async.sync.aligned.m64n64k16.f32.bf16.bf16 {%0,%1,%2,%3,%4,%5,%6,%7,%8,%9,%10,%11,%12,%13,%14,%15,%16,%17,%18,%19,%20,%21,%22,%23,%24,%25,%26,%27,%28,%29,%30,%31}, {%32,%33,%34,%35}, db, p, 1, 1, 1;\n}\n"
    : "+f"(d[0]),"+f"(d[1]),"+f"(d[2]),"+f"(d[3]),"+f"(d[4]),"+f"(d[5]),"+f"(d[6]),"+f"(d[7]),"+f"(d[8]),"+f"(d[9]),"+f"(d[10]),"+f"(d[11]),"+f"(d[12]),"+f"(d[13]),"+f"(d[14]),"+f"(d[15]),"+f"(d[16]),"+f"(d[17]),"+f"(d[18]),"+f"(d[19]),"+f"(d[20]),"+f"(d[21]),"+f"(d[22]),"+f"(d[23]),"+f"(d[24]),"+f"(d[25]),"+f"(d[26]),"+f"(d[27]),"+f"(d[28]),"+f"(d[29]),"+f"(d[30]),"+f"(d[31])
    : "r"(a[0]), "r"(a[1]), "r"(a[2]), "r"(a[3]), "r"(descB), "r"(scaleD));
}
__device__ __forceinline__ void wgmma_rs_n128(float (&d)[64], const uint32_t (&a)[4], uint32_t descB, int scaleD) {
  asm volatile("{\n.reg .pred p;\n.reg .b64 db;\nsetp.ne.b32 p, %69, 0;\nmov.b64 db, {%68, 0x40000040};\n"
    "wgmma.mma_async.sync.aligned.m64n128k16.f32.bf16.bf16 {%0,%1,%2,%3,%4,%5,%6,%7,%8,%9,%10,%11,%12,%13,%14,%15,%16,%17,%18,%19,%20,%21,%22,%23,%24,%25,%26,%27,%28,%29,%30,%31,%32,%33,%34,%35,%36,%37,%38,%39,%40,%41,%42,%43,%44,%45,%46,%47,%48,%49,%50,%51,%52,%53,%54,%55,%56,%57,%58,%59,%60,%61,%62,%63}, {%64,%65,%66,%67}, db, p, 1, 1, 1;\n}\n"
    : "+f"(d[0]),"+f"(d[1]),"+f"(d[2]),"+f"(d[3]),"+f"(d[4]),"+f"(d[5]),"+f"(d[6]),"+f"(d[7]),"+f"(d[8]),"+f"(d[9]),"+f"(d[10]),"+f"(d[11]),"+f"(d[12]),"+f"(d[13]),"+f"(d[14]),"+f"(d[15]),"+f"(d[16]),"+f"(d[17]),"+f"(d[18]),"+f"(d[19]),"+f"(d[20]),"+f"(d[21]),"+f"(d[22]),"+f"(d[23]),"+f"(d[24]),"+f"(d[25]),"+f"(d[26]),"+f"(d[27]),"+f"(d[28]),"+f"(d[29]),"+f"(d[30]),"+f"(d[31]),"+f"(d[32]),"+f"(d[33]),"+f"(d[34]),"+f"(d[35]),"+f"(d[36]),"+f"(d[37]),"+f"(d[38]),"+f"(d[39]),"+f"(d[40]),"+f"(d[41]),"+f"(d[42]),"+f"(d[43]),"+f"(d[44]),"+f"(d[45]),"+f"(d[46]),"+f"(d[47]),"+f"(d[48]),"+f"(d[49]),"+f"(d[50]),"+f"(d[51]),"+f"(d[52]),"+f"(d[53]),"+f"(d[54]),"+f"(d[55]),"+f"(d[56]),"+f"(d[57]),"+f"(d[58]),"+f"(d[59]),"+f"(d[60]),"+f"(d[61]),"+f"(d[62]),"+f"(d[63])
    : "r"(a[0]), "r"(a[1]), "r"(a[2]), "r"(a[3]), "r"(descB), "r"(scaleD));
}
__device__ __forceinline__ void wgmma_ss_n72_t11(float (&d)[36], uint32_t descA, uint32_t descB, int scaleD) {
  asm volatile("{\n.reg .pred p;\n.reg .b64 da, db;\nsetp.ne.b32 p, %38, 0;\nmov.b64 da, {%36, 0x40000040};\nmov.b64 db, {%37, 0x40000040};\n"
    "wgmma.mma_async.sync.aligned.m64n72k16.f32.bf16.bf16 {%0,%1,%2,%3,%4,%5,%6,%7,%8,%9,%10,%11,%12,%13,%14,%15,%16,%17,%18,%19,%20,%21,%22,%23,%24,%25,%26,%27,%28,%29,%30,%31,%32,%33,%34,%35}, da, db, p, 1, 1, 1, 1;\n}\n"
    : "+f"(d[0]),"+f"(d[1]),"+f"(d[2]),"+f"(d[3]),"+f"(d[4]),"+f"(d[5]),"+f"(d[6]),"+f"(d[7]),"+f"(d[8]),"+f"(d[9]),"+f"(d[10]),"+f"(d[11]),"+f"(d[12]),"+f"(d[13]),"+f"(d[14]),"+f"(d[15]),"+f"(d[16]),"+f"(d[17]),"+f"(d[18]),"+f"(d[19]),"+f"(d[20]),"+f"(d[21]),"+f"(d[22]),"+f"(d[23]),"+f"(d[24]),"+f"(d[25]),"+f"(d[26]),"+f"(d[27]),"+f"(d[28]),"+f"(d[29]),"+f"(d[30]),"+f"(d[31]),"+f"(d[32]),"+f"(d[33]),"+f"(d[34]),"+f"(d[35])
    : "r"(descA), "r"(descB), "r"(scaleD));
}

#define TSTAMP(i) do {} while (0)
#define TS2(w, i) do {} while (0)

constexpr float LOG2E = 1.4426950408889634f;

__device__ __forceinline__ void feat_exp(const uint32_t (&P)[4], float (&e)[16]) {
  uint32_t a = hmax2(P[0], P[2]), b = hmax2(P[1], P[3]);
  uint32_t mx = hmax2(__byte_perm(a, b, 0x5410), __byte_perm(a, b, 0x7632));
  a = hmin2(P[0], P[2]); b = hmin2(P[1], P[3]);
  uint32_t mn = hmin2(__byte_perm(a, b, 0x5410), __byte_perm(a, b, 0x7632));
  mx = hmax2(mx, __shfl_xor_sync(0xffffffffu, mx, 1));
  mn = hmin2(mn, __shfl_xor_sync(0xffffffffu, mn, 1));
  mx = hmax2(mx, __shfl_xor_sync(0xffffffffu, mx, 2));
  mn = hmin2(mn, __shfl_xor_sync(0xffffffffu, mn, 2));
  float mx0 = -blo(mx) * LOG2E, mx1 = -bhi(mx) * LOG2E, mn0 = blo(mn) * LOG2E, mn1 = bhi(mn) * LOG2E;
  float v[8] = {blo(P[0]), bhi(P[0]), blo(P[1]), bhi(P[1]), blo(P[2]), bhi(P[2]), blo(P[3]), bhi(P[3])};
#pragma unroll
  for (int i = 0; i < 8; i++) {
    bool r1 = (i >> 1) & 1;
    e[i]     = ex2(fmaf(v[i],  LOG2E, r1 ? mx1 : mx0));
    e[8 + i] = ex2(fmaf(v[i], -LOG2E, r1 ? mn1 : mn0));
  }
}

__global__ void __cluster_dims__(2, 1, 1) __launch_bounds__(384, 1)
fused_kernel(const __grid_constant__ Maps maps, const __nv_bfloat16* __restrict__ x, const __nv_bfloat16* __restrict__ wphi,
             const __nv_bfloat16* __restrict__ wo, const __nv_bfloat16* __restrict__ wg_, const __nv_bfloat16* __restrict__ wu_,
             const __nv_bfloat16* __restrict__ wd_, __nv_bfloat16* __restrict__ out) {
  extern __shared__ __align__(1024) unsigned char smem[];
  const uint32_t sb = smem_u32(smem);
  const int tid = threadIdx.x, lane = tid & 31;
  const int warp = __shfl_sync(0xffffffffu, tid >> 5, 0);
  const uint32_t rank = blockIdx.x & 1;
  const int cl = blockIdx.x >> 1;
  int quad, qi;
  if (cl < 4) { quad = 15; qi = cl; }
  else if (cl < 36) { quad = (cl - 4) & 7; qi = (cl - 4) >> 3; }
  else { qi = (cl - 36) / 7; quad = 8 + (cl - 36) - 7 * qi; }
  const int rb = quad, hg = 2 * qi + rank;
  const int rb3 = (quad & ~1) + rank, jf = 4 * (quad & 1) + qi;

  if (warp >= 8) {
    asm volatile("setmaxnreg.dec.sync.aligned.u32 24;");
    if (lane == 0) {
      if (warp == 8) {
#pragma unroll
        for (int k = 0; k < 9; k++) {
          const int s = k < 3 ? k : (k < 6 ? k + 3 : k - 3);
          const uint32_t bar = sb + SM_FULL + s * 8;
          mbar_init(bar, 1);
          mbar_expect_tx(bar, SLOT);
          if (s >= 3 && s < 6) tma2d(sb + s * SLOT, &maps.w, 512 + hg * 64, (s - 3) * 192, bar);
          else tma3d(sb + s * SLOT, &maps.x, 0, rb * 128 + (s >= 6 ? 64 : 0), 3 * (s % 3), bar);
        }
      } else if (warp == 9) {
        mbar_init(sb + SM_MISCB, 2);
        mbar_init(sb + SM_KVB, 32);
        mbar_expect_tx(sb + SM_MISCB, 2048);
        bulk_g2s(sb + SM_WPHI, wphi + hg * 1024, 2048, sb + SM_MISCB);
      } else if (warp == 10) {
#pragma unroll 1
        for (int i = 0; i < 16; i++) {
          mbar_init(sb + SM_XF + i * 8, 1);
          mbar_expect_tx(sb + SM_XF + i * 8, (i == 8 || i == 12) ? 20480 : 16384);
          if (i < 12) mbar_init(sb + SM_XE + i * 8, 4);
          if (i < 9) { mbar_init(sb + SM_DF + i * 8, 1); mbar_init(sb + SM_DE + i * 8, 4); }
        }
      } else {
        *reinterpret_cast<volatile unsigned*>(smem + SM_EPOCH) = atomicAdd(&g_start, 1u) / NCTA;
      }
      asm volatile("fence.mbarrier_init.release.cluster;" ::: "memory");
    }
    if (tid == 256) TS2(0, 18);
    __syncwarp();
    if (warp != 11) bar_sync(0, 352);
    asm volatile("barrier.cluster.arrive.relaxed.aligned;" ::: "memory");
    if (warp == 8) {
      asm volatile("barrier.cluster.wait.aligned;" ::: "memory");
      if (lane == 0) {
        const CUtensorMap* mg = jf == 7 ? &maps.g7 : &maps.g;
        const CUtensorMap* mu = jf == 7 ? &maps.u7 : &maps.u;
        asm volatile("prefetch.tensormap [%0];" ::"l"(&maps.wo) : "memory");
        asm volatile("prefetch.tensormap [%0];" ::"l"(mg) : "memory");
        asm volatile("prefetch.tensormap [%0];" ::"l"(mu) : "memory");
        asm volatile("prefetch.tensormap [%0];" ::"l"(&maps.d) : "memory");
        asm volatile("prefetch.tensormap [%0];" ::"l"(&maps.d48) : "memory");
#pragma unroll 1
        for (int s = ST_WV; s < ST_XC; s++) {
          if (s == ST_SCR1) continue;
          mbar_wait(sb + SM_EMPTY + (s - 9) * 8);
          const uint32_t dst = sb + (s >= 18 ? s - 18 : s - 9) * SLOT, bar = sb + SM_FULL + s * 8;
          if (s < ST_WO) tma2d(dst, &maps.w, (s < ST_WQ ? 1024 : 0) + hg * 64, (s < ST_WQ ? s - ST_WV : s - ST_WQ) * 192, bar);
          else { mbar_wait(bar - 8); tma2d(dst, &maps.wo, hg * 64, (s - ST_WO) * 192, bar); }
        }
        const int jc = jf == 7 ? 0 : jf;
        int slot = (ST_GU + 1 - rank) % NSLOT;
#pragma unroll 1
        for (int s = ST_GU + 1 - rank; s < NSTAGE; s += 2) {
          mbar_wait(sb + SM_EMPTY + (s - 9) * 8);
          if (s > ST_GU && s < ST_GU + THR) mbar_wait(sb + SM_FULL + (s - 1) * 8);
          const uint32_t dst = sb + slot * SLOT, bar = sb + SM_FULL + s * 8;
#pragma unroll 1
          for (int i = 0; i < 3; i++) {
            const int u = (s - ST_GU) * 3 + i;
            tma3d_mc(dst + i * 8192, mg, (u >> 4) * 64, jc, (u & 15) * 32, bar);
            tma3d_mc(dst + i * 8192 + 4096, mu, (u >> 4) * 64, jc, (u & 15) * 32, bar);
          }
          slot += 2; if (slot >= NSLOT) slot -= NSLOT;
        }
        slot = ST_D % NSLOT;
#pragma unroll 1
        for (int i = 0; i < 24; i++) {
          if (i < 9) mbar_wait(sb + SM_EMPTY + (ST_D - 9 + i) * 8);
          else mbar_wait_p(sb + SM_DE + slot * 8, i >= 18);
          const uint32_t bar = sb + SM_DF + slot * 8;
          mbar_expect_tx(bar, i < 16 ? 3 * 8192 : 3 * 6144);
          tma2d(sb + slot * SLOT + 16384, i < 16 ? &maps.d : &maps.d48, hg * 64, (i & 7) * 176 + (i >> 3) * 64, bar);
          if (++slot == NSLOT) slot = 0;
        }
      }
      __syncwarp();
    } else {
      asm volatile("barrier.cluster.wait.aligned;" ::: "memory");
      if (warp == 11) {
#pragma unroll
        for (int i = 0; i < 4; i++)
          reinterpret_cast<uint4*>(smem + SM_ONES)[lane + 32 * i] = make_uint4(0x3F803F80u, 0x3F803F80u, 0x3F803F80u, 0x3F803F80u);
        fence_async_smem();
        __syncwarp();
        if (lane == 0) { mbar_arrive(sb + SM_MISCB); TS2(0, 19); }
      }
      mbar_wait(sb + SM_MISCB);
      const unsigned epoch = *reinterpret_cast<volatile unsigned*>(smem + SM_EPOCH);
      const uint32_t T = (epoch & 1) ^ 1;
      if (warp == 11) {
        reinterpret_cast<float4*>(&g_kv[T][blockIdx.x * 128])[lane] = make_float4(0.f, 0.f, 0.f, 0.f);
        if (lane < 8) g_z[T][blockIdx.x * 8 + lane] = 0.f;
        mbar_wait(sb + SM_FULL + (ST_WK + 2) * 8);
        if (lane == 0) {
          asm volatile("cp.async.bulk.prefetch.L2.global [%0], 4096;" ::"l"((const char*)wo + blockIdx.x * 4096) : "memory");
          asm volatile("cp.async.bulk.prefetch.L2.global [%0], 11008;" ::"l"((const char*)wg_ + blockIdx.x * 11008) : "memory");
          asm volatile("cp.async.bulk.prefetch.L2.global [%0], 11008;" ::"l"((const char*)wu_ + blockIdx.x * 11008) : "memory");
          asm volatile("cp.async.bulk.prefetch.L2.global [%0], 11008;" ::"l"((const char*)wd_ + blockIdx.x * 11008) : "memory");
          const unsigned target = (epoch + 1) * 32;
          unsigned v; int it = 0;
#pragma unroll 1
          do {
            asm volatile("ld.acquire.gpu.global.u32 %0, [%1];" : "=r"(v) : "l"(&g_kvcnt[hg * 32]) : "memory");
            if (++it > (1 << 18)) break;
          } while ((int)(v - target) < 0);
          TS2(0, 26);
        }
        __syncwarp();
        {
          const char* src = reinterpret_cast<const char*>(&g_kv[T ^ 1][hg * 2048]) + lane * 16;
#pragma unroll
          for (int i = 0; i < 16; i++)
            asm volatile("cp.async.cg.shared.global [%0], [%1], 16;" ::"r"(sb + SM_KV32 + lane * 16 + i * 512), "l"(src + i * 512) : "memory");
          asm volatile("cp.async.cg.shared.global [%0], [%1], 16;" ::"r"(sb + SM_ONES + lane * 16), "l"(&g_z[T ^ 1][hg * 128 + lane * 4]) : "memory");
          asm volatile("cp.async.mbarrier.arrive.noinc.shared::cta.b64 [%0];" ::"r"(sb + SM_KVB) : "memory");
        }
      } else {
        const int w = warp - 9;
        st_rlx4(reinterpret_cast<uint4*>(&g_st[2 * rb + w][hg][0]) + lane, T ^ 1, T ^ 1, T ^ 1, T ^ 1);
        if (lane < 8) st_rlx4(&g_o[2 * rb + w][hg][lane >> 1][3][30 + (lane & 1)], T ^ 1, T ^ 1, T ^ 1, T ^ 1);
        if (lane < 24) st_rlx4(&g_hh[2 * rb3 + w][lane >> 3][jf][2][(lane >> 1) & 3][30 + (lane & 1)], T ^ 1, T ^ 1, T ^ 1, T ^ 1);
        bar_sync(6 + w, 160);
        if (lane == 0) {
          asm volatile("fence.acq_rel.gpu;" ::: "memory");
          TS2(w, 25);
          asm volatile("red.relaxed.gpu.global.add.u32 [%0], 1;" ::"l"(&g_kvcnt[hg * 32]) : "memory");
        }
        mbar_wait(sb + SM_KVB);
        if (w == 0) { mbar_wait(sb + SM_EMPTY + 11 * 8); mbar_wait(sb + SM_EMPTY + 12 * 8); mbar_wait(sb + SM_EMPTY + 13 * 8); }
#pragma unroll 1
        for (int ph = 0; ph < 2; ph++) {
          const int use = 2 * ph + w, r = ph ? 2 * rb3 + w : 2 * rb + w;
          const uint32_t* pw = ph ? reinterpret_cast<const uint32_t*>(&g_st[r][lane >> 2][(lane & 3) * 16 + 15])
                                  : reinterpret_cast<const uint32_t*>(&g_o[r][lane >> 2][lane & 3][3][31]);
          const char* src = reinterpret_cast<const char*>(ph ? &g_h[r][0][0][0][0] : &g_o[r][0][0][0][0]);
          uint32_t ready = 0; int it = 0;
#pragma unroll 1
          for (int p = 0; p < 4; p++) {
            const uint32_t need = ph ? 0xFFFFFFFFu : 0xFFu << (8 * p);
#pragma unroll 1
            while ((ready & need) != need) {
              ready = __ballot_sync(0xffffffffu, ((ld_rlx1(pw) ^ T) & 1) == 0);
              if (++it > (1 << 18)) break;
            }
            if (lane == 0) {
              if (p == 0) TS2(w, 27 + ph);
              if (use > 0) mbar_wait(sb + SM_XE + ((use - 1) * 4 + p) * 8);
              const uint32_t bar = sb + SM_XF + (use * 4 + p) * 8;
              if (ph && p == 0) bulk_g2s(sb + SM_KV32 + w * 4096, &g_st[r][0][0], 4096, bar);
              bulk_g2s(sb + 2 * SLOT + p * 16384, src + p * 16384, 16384, bar);
            }
            __syncwarp();
          }
        }
        if (w == (int)rank) {
          uint32_t ready = 0; int it = 0, slot = ST_D % NSLOT;
#pragma unroll 1
          for (int i = 0; i < 24; i++) {
            if (i < 9) mbar_wait(sb + SM_EMPTY + (ST_D - 9 + i) * 8);
            else mbar_wait_p(sb + SM_DE + slot * 8, i >= 18);
            if ((i & 7) == 0) ready = 0;
            const uint32_t* pw = reinterpret_cast<const uint32_t*>(&g_hh[2 * rb + w][i >> 3][lane >> 2][2][lane & 3][31]);
#pragma unroll 1
            while (((ready >> (4 * (i & 7))) & 15) != 15) {
              ready = __ballot_sync(0xffffffffu, ((ld_rlx1(pw) ^ T) & 1) == 0);
              if (++it > (1 << 18)) break;
            }
            if (lane == 0) {
              asm volatile("cp.async.bulk.shared::cluster.global.mbarrier::complete_tx::bytes.multicast::cluster [%0], [%1], %2, [%3], %4;"
                           ::"r"(sb + slot * SLOT + w * 8192), "l"(&g_hh[2 * rb + w][i >> 3][i & 7][0][0][0]), "r"(i < 16 ? 8192 : 6144),
                             "r"(sb + SM_DF + slot * 8), "h"((uint16_t)3) : "memory");
            }
            __syncwarp();
            if (++slot == NSLOT) slot = 0;
          }
        }
      }
    }
    asm volatile("barrier.cluster.arrive.relaxed.aligned;" ::: "memory");
    asm volatile("barrier.cluster.wait.aligned;" ::: "memory");
  } else {
    asm volatile("setmaxnreg.inc.sync.aligned.u32 240;");
    if (lane == 0) {
#pragma unroll 1
      for (int d = warp; d < NSTAGE; d += 8) {
        mbar_init(sb + SM_EMPTY + d * 8, st_empty_cnt(d));
        if (d + 9 < NSTAGE) {
          mbar_init(sb + SM_FULL + (d + 9) * 8, 1);
          mbar_expect_tx(sb + SM_FULL + (d + 9) * 8, SLOT);
        }
      }
      asm volatile("fence.mbarrier_init.release.cluster;" ::: "memory");
    }
    __syncwarp();
    bar_sync(0, 352);
    asm volatile("barrier.cluster.arrive.relaxed.aligned;" ::: "memory");
    const int wg = warp >> 2, wq = warp & 3, g = lane >> 2, t = lane & 3;
    const bool lead = (tid & 127) == 0;
    const uint32_t db = ((sb & 0x3FFFF) >> 4) | (512u << 16);
    auto release = [&](int d) {
      const int s = d + NSLOT;
      mbar_arrive_cluster(sb + SM_EMPTY + d * 8, (s >= ST_GU && s < ST_D) ? (uint32_t)(s & 1) : rank);
      if (s >= ST_D) mbar_arrive_cluster(sb + SM_EMPTY + d * 8, rank ^ 1);
    };
    const uint32_t lrow = (uint32_t)(wq * 16 + (lane & 7) + ((lane >> 3) & 1) * 8) * 128;
    const uint32_t lx = lane & 7, lhi = lane >> 4;
    TSTAMP(0);

    float r0, r1;
    uint32_t E[4][8];
    uint32_t T = 0;
    {
      uint32_t A[32][4];
      float acc[32];
      const int sx = wg ? ST_X1 : ST_X0;
      {
        const uint32_t base = sb + sx * SLOT + lrow;
        float cs[2][4], c0[2][4], c1[2][4];
#pragma unroll
        for (int i = 0; i < 4; i++) { cs[0][i] = cs[1][i] = c0[0][i] = c0[1][i] = c1[0][i] = c1[1][i] = 0.f; }
#pragma unroll
        for (int c = 0; c < 8; c++) {
          if (c % 3 == 0) mbar_wait(sb + SM_FULL + (sx + c / 3) * 8);
#pragma unroll
          for (int k = 0; k < 4; k++) ldsm4(A[4 * c + k], base + c * 8192 + (((2 * k + lhi) ^ lx) << 4));
#pragma unroll
          for (int k = 0; k < 4; k++) {
            const uint32_t (&f)[4] = A[4 * c + k];
            mma16816(cs[k & 1], f, 0x3F803F80u, 0x3F803F80u);
            mma16816(c0[k & 1], f, f[0], f[2]);
            mma16816(c1[k & 1], f, f[1], f[3]);
          }
        }
        const float s0 = (cs[0][0] + cs[1][0]) * (1.f / 512.f), s1 = (cs[0][2] + cs[1][2]) * (1.f / 512.f);
        TSTAMP(17);
        asm volatile("barrier.cluster.wait.aligned;" ::: "memory");
        if (lane < 3) release(sx + lane);
        const uint32_t m0 = pack2(s0, s0), m1 = pack2(s1, s1);
        float q0 = (g & 1) ? c0[0][1] + c0[1][1] : c0[0][0] + c0[1][0];
        float q1 = (g & 1) ? c1[0][3] + c1[1][3] : c1[0][2] + c1[1][2];
        q0 = __shfl_sync(0xffffffffu, q0, (lane & ~3) | (g >> 1));
        q1 = __shfl_sync(0xffffffffu, q1, (lane & ~3) | (g >> 1));
        r0 = rsqrtf(fmaxf(q0 * (1.f / 512.f) - s0 * s0, 0.f) + 1e-5f);
        r1 = rsqrtf(fmaxf(q1 * (1.f / 512.f) - s1 * s1, 0.f) + 1e-5f);
#pragma unroll
        for (int c = 0; c < 8; c++) {
#pragma unroll
          for (int ks = 4 * c; ks < 4 * c + 4; ks++) {
            A[ks][0] = hsub2(A[ks][0], m0); A[ks][1] = hsub2(A[ks][1], m1);
            A[ks][2] = hsub2(A[ks][2], m0); A[ks][3] = hsub2(A[ks][3], m1);
          }
          if (c % 3 == 0) mbar_wait(sb + SM_FULL + (ST_WK + c / 3) * 8);
          wg_fence();
#pragma unroll
          for (int ks = 4 * c; ks < 4 * c + 4; ks++) wgmma_rs_n64(acc, A[ks], DESC((ST_WK % NSLOT) * SLOT + ks * 2048), ks != 0);
          wg_commit();
          if (c == 4) { wg_wait<2>(); if (lead) release(ST_WK); }
        }
      }
      TSTAMP(1);
      uint32_t a[4][4];
      auto scale_pack = [&]() {
#pragma unroll
        for (int h = 0; h < 4; h++) {
          a[h][0] = pack2(acc[8 * h + 0] * r0, acc[8 * h + 1] * r0); a[h][1] = pack2(acc[8 * h + 2] * r1, acc[8 * h + 3] * r1);
          a[h][2] = pack2(acc[8 * h + 4] * r0, acc[8 * h + 5] * r0); a[h][3] = pack2(acc[8 * h + 6] * r1, acc[8 * h + 7] * r1);
        }
      };
      auto project = [&](const uint32_t (&b)[4][4]) {
        float pp[4][2][4];
#pragma unroll
        for (int h = 0; h < 4; h++) {
#pragma unroll
          for (int i = 0; i < 4; i++) { pp[h][0][i] = 0.f; pp[h][1][i] = 0.f; }
          mma16816(pp[h][0], a[h], b[h][0], b[h][1]);
          mma16816(pp[h][1], a[h], b[h][2], b[h][3]);
        }
#pragma unroll
        for (int h = 0; h < 4; h++) {
          a[h][0] = pack2(pp[h][0][0], pp[h][0][1]); a[h][1] = pack2(pp[h][0][2], pp[h][0][3]);
          a[h][2] = pack2(pp[h][1][0], pp[h][1][1]); a[h][3] = pack2(pp[h][1][2], pp[h][1][3]);
        }
      };
      const uint32_t wpa = sb + SM_WPHI + ((lane & 7) + ((lane >> 3) & 1) * 8) * 32 + lhi * 16;
      const uint32_t scr = sb + (wg ? (ST_SCR1 % NSLOT) : (ST_SCR0 % NSLOT)) * SLOT;
      {
        uint32_t b[4][4];
        mbar_wait(sb + SM_MISCB);
        T = (*reinterpret_cast<volatile unsigned*>(smem + SM_EPOCH) & 1) ^ 1;
#pragma unroll
        for (int h = 0; h < 4; h++) ldsm4t(b[h], wpa + h * 512);
        wg_wait<0>();
        if (lead) { release(ST_WK + 1); release(ST_WK + 2); }
        TSTAMP(2);
        scale_pack();
        project(b);
      }
      mbar_wait(sb + SM_EMPTY + (wg ? ST_SCR1 - NSLOT : ST_SCR0 - NSLOT) * 8);
      auto vgroup = [&](int c) {
        if (c % 3 == 0) mbar_wait(sb + SM_FULL + (ST_WV + c / 3) * 8);
        if (c == 0) wg_fence();
#pragma unroll
        for (int ks = 4 * c; ks < 4 * c + 4; ks++) wgmma_rs_n64(acc, A[ks], DESC((ST_WV % NSLOT) * SLOT + ks * 2048), ks != 0);
      };
#pragma unroll
      for (int h = 0; h < 4; h++) {
        vgroup(2 * h);
        float f[16];
        feat_exp(a[h], f);
        float sp0 = (f[0] + f[1]) + (f[4] + f[5]), sp1 = (f[2] + f[3]) + (f[6] + f[7]);
        float sn0 = (f[8] + f[9]) + (f[12] + f[13]), sn1 = (f[10] + f[11]) + (f[14] + f[15]);
        sp0 += __shfl_xor_sync(0xffffffffu, sp0, 1); sp1 += __shfl_xor_sync(0xffffffffu, sp1, 1);
        sn0 += __shfl_xor_sync(0xffffffffu, sn0, 1); sn1 += __shfl_xor_sync(0xffffffffu, sn1, 1);
        vgroup(2 * h + 1);
        sp0 += __shfl_xor_sync(0xffffffffu, sp0, 2); sp1 += __shfl_xor_sync(0xffffffffu, sp1, 2);
        sn0 += __shfl_xor_sync(0xffffffffu, sn0, 2); sn1 += __shfl_xor_sync(0xffffffffu, sn1, 2);
        sp0 = rcp(sp0); sp1 = rcp(sp1); sn0 = rcp(sn0); sn1 = rcp(sn1);
        const uint32_t dst = scr + (h >> 1) * 8192 + lrow;
        stsm4(dst + ((((h & 1) * 4 + lhi) ^ lx) << 4), pack2(f[0] * sp0, f[1] * sp0), pack2(f[2] * sp1, f[3] * sp1),
              pack2(f[4] * sp0, f[5] * sp0), pack2(f[6] * sp1, f[7] * sp1));
        stsm4(dst + ((((h & 1) * 4 + 2 + lhi) ^ lx) << 4), pack2(f[8] * sn0, f[9] * sn0), pack2(f[10] * sn1, f[11] * sn1),
              pack2(f[12] * sn0, f[13] * sn0), pack2(f[14] * sn1, f[15] * sn1));
      }
      wg_commit();
      TSTAMP(3);
      wg_wait<0>();
      if ((tid & 127) < 3) release(ST_WV + (tid & 127));
      TSTAMP(4);
      {
        scale_pack();
#pragma unroll
        for (int h = 0; h < 4; h++) stsm4(scr + 16384 + lrow + (((2 * h + lhi) ^ lx) << 4), a[h][0], a[h][1], a[h][2], a[h][3]);
        fence_async_smem();
        bar_sync(3, 256);
        float kv[36];
        wg_fence();
#pragma unroll
        for (int ks = 0; ks < 8; ks++) {
          const uint32_t sk = (ks < 4 ? (ST_SCR0 % NSLOT) : (ST_SCR1 % NSLOT)) * SLOT + (ks & 3) * 2048;
          const uint32_t dv = (DESC(sk + 16384) & 0xFFFFu) | (((SM_ONES - sk - 16384) >> 4) << 16);
          wgmma_ss_n72_t11(kv, DESC(sk) + wg * 512, dv, ks != 0);
        }
        wg_commit();
        wg_wait<0>();
        if (lead) { release(ST_SCR0); release(ST_SCR1); }
        const int hl = 2 * wg + (wq >> 1), f = (wq & 1) * 16 + g;
        float* kvp = &g_kv[T ^ 1][((hg * 4 + hl) * 32 + f) * 16 + 2 * t];
        float* zp = &g_z[T ^ 1][(hg * 4 + hl) * 32 + f];
        float c[8];
#pragma unroll
        for (int i = 0; i < 8; i++) c[i] = hl >= 2 ? (hl == 3 ? kv[24 + i] : kv[16 + i]) : (hl == 1 ? kv[8 + i] : kv[i]);
#pragma unroll
        for (int n = 0; n < 2; n++) {
          asm volatile("red.relaxed.gpu.global.add.v2.f32 [%0], {%1,%2};" ::"l"(kvp + n * 8), "f"(c[4 * n]), "f"(c[4 * n + 1]) : "memory");
          asm volatile("red.relaxed.gpu.global.add.v2.f32 [%0], {%1,%2};" ::"l"(kvp + n * 8 + 128), "f"(c[4 * n + 2]), "f"(c[4 * n + 3]) : "memory");
        }
        if (t < 2) asm volatile("red.relaxed.gpu.global.add.f32 [%0], %1;" ::"l"(zp + t * 8), "f"(t ? kv[34] : kv[32]) : "memory");
        bar_arrive(6 + wg, 160);
      }
      TSTAMP(5);
      {
        if (wg == 1) bar_sync(4, 256);
#pragma unroll
        for (int i = 0; i < 3; i++) {
          mbar_wait(sb + SM_FULL + (ST_WQ + i) * 8);
          wg_fence();
#pragma unroll
          for (int kk = 0; kk < 12; kk++)
            if (12 * i + kk < 32) wgmma_rs_n64(acc, A[(12 * i + kk) & 31], DESC((ST_WQ % NSLOT) * SLOT + (12 * i + kk) * 2048), (i | kk) != 0);
          wg_commit();
          if (i > 0) { wg_wait<1>(); if (lead) release(ST_WQ + i - 1); }
        }
        if (wg == 0) bar_arrive(4, 256);
        uint32_t b[4][4];
#pragma unroll
        for (int h = 0; h < 4; h++) ldsm4t(b[h], wpa + h * 512);
        wg_wait<0>();
        if (lead) release(ST_WQ + 2);
        TSTAMP(6);
        scale_pack();
        project(b);
#pragma unroll
        for (int h = 0; h < 4; h++) {
          float e[16];
          feat_exp(a[h], e);
#pragma unroll
          for (int i = 0; i < 8; i++) E[h][i] = pack2(e[2 * i], e[2 * i + 1]);
        }
      }
      TSTAMP(7);
    }
    const int rh = 2 * rb + wg;
    const uint32_t xb = sb + 2 * SLOT + wq * 2048 + lane * 16;
    mbar_wait(sb + SM_KVB);
    {
      const int r = tid & 127;
      const float4* src = reinterpret_cast<const float4*>(smem + SM_KV32) + r;
#pragma unroll
      for (int i = 0; i < 4; i++) {
        const float4 a = src[i * 128];
        *reinterpret_cast<uint2*>(smem + SM_KVS + (i * 32 + (r >> 2)) * 48 + (r & 3) * 8) = make_uint2(pack2(a.x, a.y), pack2(a.z, a.w));
      }
      const uint32_t zz = pack2(reinterpret_cast<const float*>(smem + SM_ONES)[r], 1.0f);
      *reinterpret_cast<uint4*>(smem + SM_KVS + r * 48 + 32) = make_uint4(zz, zz, zz, zz);
      bar_sync(1 + wg, 128);
    }
    TSTAMP(8);
    {
      uint4* op = &g_o[rh][hg][wq][0][lane];
#pragma unroll
      for (int h = 0; h < 4; h++) {
        uint32_t b0[4], b1[4], b2[4];
        const uint32_t kb = sb + SM_KVS + (h * 32 + lane) * 48;
        ldsm4t(b0, kb); ldsm4t(b1, kb + 16); ldsm4t(b2, kb + 32);
        const uint32_t ep[4] = {E[h][0], E[h][1], E[h][2], E[h][3]}, en[4] = {E[h][4], E[h][5], E[h][6], E[h][7]};
        float np0[4] = {0, 0, 0, 0}, np1[4] = {0, 0, 0, 0}, nn0[4] = {0, 0, 0, 0}, nn1[4] = {0, 0, 0, 0}, dp[4] = {0, 0, 0, 0}, dn[4] = {0, 0, 0, 0};
        mma16816(dp, ep, b2[0], b2[1]);  mma16816(dn, en, b2[2], b2[3]);
        mma16816(np0, ep, b0[0], b0[1]); mma16816(nn0, en, b0[2], b0[3]);
        mma16816(np1, ep, b1[0], b1[1]); mma16816(nn1, en, b1[2], b1[3]);
        const float i0 = rcp(fmaf(dp[0], dn[1], fmaf(dn[0], dp[1], 1e-6f * dp[1] * dn[1])));
        const float i1 = rcp(fmaf(dp[2], dn[3], fmaf(dn[2], dp[3], 1e-6f * dp[3] * dn[3])));
        const float cp0 = dn[1] * i0, cn0 = dp[1] * i0, cp1 = dn[3] * i1, cn1 = dp[3] * i1;
        st_rlx4(op + h * 32,
                tg(pack2(fmaf(np0[0], cp0, nn0[0] * cn0), fmaf(np0[1], cp0, nn0[1] * cn0)), T),
                pack2(fmaf(np0[2], cp1, nn0[2] * cn1), fmaf(np0[3], cp1, nn0[3] * cn1)),
                pack2(fmaf(np1[0], cp0, nn1[0] * cn0), fmaf(np1[1], cp0, nn1[1] * cn0)),
                pack2(fmaf(np1[2], cp1, nn1[2] * cn1), fmaf(np1[3], cp1, nn1[3] * cn1)));
      }
    }
    TSTAMP(9);

    {
      uint32_t xr[16];
      {
        const uint32_t* xp = reinterpret_cast<const uint32_t*>(x + (size_t)(rh * 64 + wq * 16 + g) * 512 + hg * 64 + 2 * t);
#pragma unroll
        for (int i = 0; i < 8; i++) { xr[2 * i] = __ldg(xp + 4 * i); xr[2 * i + 1] = __ldg(xp + 8 * 256 + 4 * i); }
      }
      uint32_t A[8][4][4];
      const uint4* op = &g_o[rh][0][wq][0][lane];
      float acc[32];
      mbar_wait(sb + SM_XF + (wg * 4) * 8);
      lds_chunk(A[0], xb); lds_chunk(A[1], xb + 8192);
#pragma unroll
      for (int p = 0; p < 4; p++) {
        chk_chunk(A[2 * p], op + 2 * p * 512, T);
        chk_chunk(A[2 * p + 1], op + (2 * p + 1) * 512, T);
        if (lane == 0) mbar_arrive(sb + SM_XE + (wg * 4 + p) * 8);
#pragma unroll
        for (int c = 2 * p; c < 2 * p + 2; c++) {
          if (c % 3 == 0) mbar_wait(sb + SM_FULL + (ST_WO + c / 3) * 8);
          if ((c & 1) && p < 3) {
            mbar_wait(sb + SM_XF + (wg * 4 + p + 1) * 8);
            lds_chunk(A[2 * p + 2], xb + (p + 1) * 16384); lds_chunk(A[2 * p + 3], xb + (p + 1) * 16384 + 8192);
          }
          wg_fence();
#pragma unroll
          for (int s = 0; s < 4; s++)
            wgmma_rs_n64(acc, A[c][s], DESC(((ST_WO + c / 3) % NSLOT) * SLOT + ((c % 3) * 4 + s) * 2048), (c | s) != 0);
          wg_commit();
        }
      }
      wg_wait<0>();
      if ((tid & 127) < 3) release(ST_WO + (tid & 127));
      TSTAMP(10);
      uint32_t hw[16];
      float s0 = 0.f, s1 = 0.f, q0 = 0.f, q1 = 0.f;
#pragma unroll
      for (int i = 0; i < 8; i++) {
        hw[2 * i]     = pack2(blo(xr[2 * i]) + acc[4 * i], bhi(xr[2 * i]) + acc[4 * i + 1]);
        hw[2 * i + 1] = pack2(blo(xr[2 * i + 1]) + acc[4 * i + 2], bhi(xr[2 * i + 1]) + acc[4 * i + 3]);
      }
      uint4* hp_ = &g_h[rh][hg][wq][0][lane];
#pragma unroll
      for (int s = 0; s < 4; s++) st_rlx4(hp_ + s * 32, tg(hw[4 * s], T), hw[4 * s + 1], hw[4 * s + 2], hw[4 * s + 3]);
#pragma unroll
      for (int i = 0; i < 8; i++) {
        float a = blo(hw[2 * i]), b = bhi(hw[2 * i]);
        s0 += a + b; q0 = fmaf(a, a, q0); q0 = fmaf(b, b, q0);
        a = blo(hw[2 * i + 1]); b = bhi(hw[2 * i + 1]);
        s1 += a + b; q1 = fmaf(a, a, q1); q1 = fmaf(b, b, q1);
      }
      s0 += __shfl_xor_sync(0xffffffffu, s0, 1); s1 += __shfl_xor_sync(0xffffffffu, s1, 1);
      q0 += __shfl_xor_sync(0xffffffffu, q0, 1); q1 += __shfl_xor_sync(0xffffffffu, q1, 1);
      s0 += __shfl_xor_sync(0xffffffffu, s0, 2); s1 += __shfl_xor_sync(0xffffffffu, s1, 2);
      q0 += __shfl_xor_sync(0xffffffffu, q0, 2); q1 += __shfl_xor_sync(0xffffffffu, q1, 2);
      if (t < 2) st_rlx2(&g_st[rh][hg][wq * 16 + g + t * 8], tg(__float_as_uint(t ? s1 : s0), T), __float_as_uint(t ? q1 : q0));
      uint32_t hx = T;
#pragma unroll
      for (int i = 0; i < 4; i++) hx |= (hw[4 * i] & 1u) << (i + 1);
      st_rlx1(&g_hx[rh][hg][wq][lane], hx);
    }
    TSTAMP(11);

    const int rh3 = 2 * rb3 + wg;
    {
      uint32_t A[8][4][4];
      const uint4* hp_ = &g_h[rh3][0][wq][0][lane];
      uint4* hhp = &g_hh[rh3][0][jf][0][wq][lane];
      const uint32_t dg = (db & 0xFFFFu) | (256u << 16);
      uint32_t m0, m1;
      mbar_wait(sb + SM_XF + ((2 + wg) * 4) * 8);
      lds_chunk(A[0], xb); lds_chunk(A[1], xb + 8192);
      {
        const uint2* sp = &g_st[rh3][2 * t][wq * 16 + g];
        const uint2* ss = reinterpret_cast<const uint2*>(smem + SM_KV32 + wg * 4096) + 2 * t * 64 + wq * 16 + g;
        uint2 a0 = ss[0], a1 = ss[64], b0 = ss[8], b1 = ss[72];
        int it = 0;
#pragma unroll 1
        while (__any_sync(0xffffffffu, bad4(a0.x, a1.x, b0.x, b1.x, T) & 1)) {
          ld_rlx2(a0.x, a0.y, sp); ld_rlx2(a1.x, a1.y, sp + 64); ld_rlx2(b0.x, b0.y, sp + 8); ld_rlx2(b1.x, b1.y, sp + 72);
          if (++it > (1 << 18)) break;
        }
        float s0 = __uint_as_float(a0.x) + __uint_as_float(a1.x), q0 = __uint_as_float(a0.y) + __uint_as_float(a1.y);
        float s1 = __uint_as_float(b0.x) + __uint_as_float(b1.x), q1 = __uint_as_float(b0.y) + __uint_as_float(b1.y);
        s0 += __shfl_xor_sync(0xffffffffu, s0, 1); s1 += __shfl_xor_sync(0xffffffffu, s1, 1);
        q0 += __shfl_xor_sync(0xffffffffu, q0, 1); q1 += __shfl_xor_sync(0xffffffffu, q1, 1);
        s0 += __shfl_xor_sync(0xffffffffu, s0, 2); s1 += __shfl_xor_sync(0xffffffffu, s1, 2);
        q0 += __shfl_xor_sync(0xffffffffu, q0, 2); q1 += __shfl_xor_sync(0xffffffffu, q1, 2);
        s0 *= (1.f / 512.f); s1 *= (1.f / 512.f);
        r0 = rcp(fmaxf(q0 * (1.f / 512.f) - s0 * s0, 0.f) + 1e-5f);
        r1 = rcp(fmaxf(q1 * (1.f / 512.f) - s1 * s1, 0.f) + 1e-5f);
        m0 = pack2(s0, s0); m1 = pack2(s1, s1);
      }
      TSTAMP(12);
#define UOFF(u) ((((ST_GU + (u) / 3) % NSLOT) * SLOT + ((u) % 3) * 8192) >> 4)
#define UNIT_PRE(u)  do { if ((u) % 3 == 0) mbar_wait(sb + SM_FULL + (ST_GU + (u) / 3) * 8); wg_fence(); } while (0)
#define UNIT_POST(u) do { wg_commit(); if ((u) % 3 == 1 && (u) > 3) { wg_wait<2>(); if (lead) release(ST_GU + (u) / 3 - 1); } } while (0)
      float acc[64];
      const int rz = blockIdx.y;
#pragma unroll
      for (int ps = 0; ps < 2; ps++) {
#pragma unroll
        for (int k = 0; k < 16; k++) {
          const int u = 16 * ps + k, c = k >> 1;
          if (ps == 0 && (k & 3) == 0) {
            const int p = k >> 2;
            chk_chunk(A[2 * p], hp_ + 2 * p * 512, T);
            chk_chunk(A[2 * p + 1], hp_ + (2 * p + 1) * 512, T);
            if (lane == 0) {
              if (wg == 0) mbar_arrive(sb + SM_XE + (8 + p) * 8);
              else if (p > 0) release(ST_XC + p - 1);
            }
          }
          if (ps == 0 && (k & 3) == 1 && k < 12) {
            const int p = (k >> 2) + 1;
            mbar_wait(sb + SM_XF + ((2 + wg) * 4 + p) * 8);
            lds_chunk(A[2 * p], xb + p * 16384);
            lds_chunk(A[2 * p + 1], xb + p * 16384 + 8192);
          }
          if (ps == 0 && (k & 1) == 0) {
#pragma unroll
            for (int s = 0; s < 4; s++) {
              A[c][s][0] = hsub2(A[c][s][0], m0); A[c][s][1] = hsub2(A[c][s][1], m1);
              A[c][s][2] = hsub2(A[c][s][2], m0); A[c][s][3] = hsub2(A[c][s][3], m1);
            }
          }
          UNIT_PRE(u);
          wgmma_rs_n128(acc, A[c][(k & 1) * 2], dg + UOFF(u), k != 0 ? 1 : (ps ? rz : 0));
          wgmma_rs_n128(acc, A[c][(k & 1) * 2 + 1], dg + UOFF(u) + 128, 1);
          UNIT_POST(u);
        }
        wg_wait<0>();
#pragma unroll
        for (int k = 0; k < 4; k++) {
          const int s = k == 2 ? 3 : (k == 3 ? 2 : k);
          st_rlx4(hhp + ps * 4096 + s * 128,
                  tg(pack2(acc[8 * s + 0] * acc[32 + 8 * s + 0] * r0, acc[8 * s + 1] * acc[32 + 8 * s + 1] * r0), T),
                  pack2(acc[8 * s + 2] * acc[32 + 8 * s + 2] * r1, acc[8 * s + 3] * acc[32 + 8 * s + 3] * r1),
                  pack2(acc[8 * s + 4] * acc[32 + 8 * s + 4] * r0, acc[8 * s + 5] * acc[32 + 8 * s + 5] * r0),
                  pack2(acc[8 * s + 6] * acc[32 + 8 * s + 6] * r1, acc[8 * s + 7] * acc[32 + 8 * s + 7] * r1));
        }
      }
      {
        float ag[24], au[24];
        bar_sync(1 + wg, 128);
#pragma unroll
        for (int k = 0; k < 16; k++) {
          const int u = 32 + k, c = k >> 1;
          UNIT_PRE(u);
          wgmma_rs_n48(ag, A[c][(k & 1) * 2], dg + UOFF(u), k != 0);
          wgmma_rs_n48(au, A[c][(k & 1) * 2], dg + UOFF(u) + 256, k != 0);
          wgmma_rs_n48(ag, A[c][(k & 1) * 2 + 1], dg + UOFF(u) + 128, 1);
          wgmma_rs_n48(au, A[c][(k & 1) * 2 + 1], dg + UOFF(u) + 256 + 128, 1);
          UNIT_POST(u);
        }
        wg_wait<0>();
        if (lead) release(ST_D - 1);
        TSTAMP(13);
#pragma unroll
        for (int s = 0; s < 3; s++)
          st_rlx4(hhp + 2 * 4096 + s * 128,
                  tg(pack2(ag[8 * s + 0] * au[8 * s + 0] * r0, ag[8 * s + 1] * au[8 * s + 1] * r0), T),
                  pack2(ag[8 * s + 2] * au[8 * s + 2] * r1, ag[8 * s + 3] * au[8 * s + 3] * r1),
                  pack2(ag[8 * s + 4] * au[8 * s + 4] * r0, ag[8 * s + 5] * au[8 * s + 5] * r0),
                  pack2(ag[8 * s + 6] * au[8 * s + 6] * r1, ag[8 * s + 7] * au[8 * s + 7] * r1));
      }
    }
    TSTAMP(14);

    {
      float acc[32];
      uint32_t F[2][4][4], hr[4][4];
      ld_chunk(hr, &g_h[rh][hg][wq][0][lane]);
      const uint32_t hx = ld_rlx1(&g_hx[rh][hg][wq][lane]);
      const uint4* gp = &g_hh[rh][0][0][0][wq][lane];
      const uint32_t fb = sb + wg * 8192 + wq * 512 + lane * 16;
      auto load = [&](uint32_t (&f)[4][4], int i, int slot, int nk) {
        mbar_wait_p(sb + SM_DF + slot * 8, i >= 9 && i < 18);
#pragma unroll
        for (int s = 0; s < 4; s++)
          if (s < nk) asm volatile("ld.shared.v4.b32 {%0,%1,%2,%3}, [%4];" : "=r"(f[s][0]), "=r"(f[s][1]), "=r"(f[s][2]), "=r"(f[s][3])
                                   : "r"(fb + slot * SLOT + s * 2048) : "memory");
        int it = 0;
#pragma unroll 1
        while (__any_sync(0xffffffffu, bad4(f[0][0], f[1][0], f[2][0], f[nk - 1][0], T) & 1)) {
#pragma unroll
          for (int s = 0; s < 4; s++) if (s < nk) ld_rlx4(f[s], gp + i * 512 + s * 128);
          if (++it > (1 << 18)) break;
        }
      };
      int slot = ST_D % NSLOT, pslot = 0;
      load(F[0], 0, slot, 4);
      auto stage = [&](int i, int b, int nk, int nk_next, bool last) {
        wg_fence();
#pragma unroll
        for (int s = 0; s < 4; s++) if (s < nk) wgmma_rs_n64(acc, F[b][s], db + slot * (SLOT >> 4) + 1024 + s * 128, (i | s) != 0);
        wg_commit();
        wg_wait<1>();
        if ((tid & 127) < 2 && i > 0 && i < 16) mbar_arrive_cluster(sb + SM_DE + pslot * 8, tid & 1);
        pslot = slot;
        if (++slot == NSLOT) slot = 0;
        if (!last) load(F[b ^ 1], i + 1, slot, nk_next);
      };
#pragma unroll 1
      for (int i = 0; i < 14; i += 2) { stage(i, 0, 4, 4, false); stage(i + 1, 1, 4, 4, false); }
      stage(14, 0, 4, 4, false); stage(15, 1, 4, 3, false);
#pragma unroll 1
      for (int i = 16; i < 24; i += 2) { stage(i, 0, 3, 3, false); stage(i + 1, 1, 3, 3, i == 22); }
      wg_wait<0>();
      TSTAMP(15);
#pragma unroll
      for (int s = 0; s < 4; s++) hr[s][0] = (hr[s][0] & 0xFFFFFFFEu) | ((hx >> (s + 1)) & 1u);
      const uint32_t ob = sb + wg * 8192;
#pragma unroll
      for (int s = 0; s < 4; s++)
        stsm4(ob + lrow + (((2 * s + lhi) ^ lx) << 4),
              pack2(blo(hr[s][0]) + acc[8 * s + 0], bhi(hr[s][0]) + acc[8 * s + 1]), pack2(blo(hr[s][1]) + acc[8 * s + 2], bhi(hr[s][1]) + acc[8 * s + 3]),
              pack2(blo(hr[s][2]) + acc[8 * s + 4], bhi(hr[s][2]) + acc[8 * s + 5]), pack2(blo(hr[s][3]) + acc[8 * s + 6], bhi(hr[s][3]) + acc[8 * s + 7]));
      __syncwarp();
#pragma unroll
      for (int i = 0; i < 4; i++) {
        const int row = wq * 16 + i * 4 + (lane >> 3);
        uint4 v;
        asm volatile("ld.shared.v4.b32 {%0,%1,%2,%3}, [%4];" : "=r"(v.x), "=r"(v.y), "=r"(v.z), "=r"(v.w)
                     : "r"(ob + row * 128 + ((lx ^ (row & 7)) << 4)) : "memory");
        *reinterpret_cast<uint4*>(out + (size_t)(rh * 64 + row) * 512 + hg * 64 + lx * 8) = v;
      }
    }
    TSTAMP(16);
    asm volatile("barrier.cluster.arrive.relaxed.aligned;" ::: "memory");
    asm volatile("barrier.cluster.wait.aligned;" ::: "memory");
  }
}

typedef CUresult (*EncodeFn)(CUtensorMap*, CUtensorMapDataType, cuuint32_t, void*, const cuuint64_t*, const cuuint64_t*,
                             const cuuint32_t*, const cuuint32_t*, CUtensorMapInterleave, CUtensorMapSwizzle,
                             CUtensorMapL2promotion, CUtensorMapFloatOOBfill);

void encode(EncodeFn fn, CUtensorMap* m, const void* base, int rank, const cuuint64_t* dims, const cuuint64_t* strides,
            const cuuint32_t* box) {
  cuuint32_t es[3] = {1, 1, 1};
  fn(m, CU_TENSOR_MAP_DATA_TYPE_BFLOAT16, (cuuint32_t)rank, const_cast<void*>(base), dims, strides, box, es,
     CU_TENSOR_MAP_INTERLEAVE_NONE, CU_TENSOR_MAP_SWIZZLE_128B, CU_TENSOR_MAP_L2_PROMOTION_L2_256B,
     CU_TENSOR_MAP_FLOAT_OOB_FILL_NONE);
}

}

extern "C" void kernel_launch(void* const* d_in, const int* in_sizes, int n_in, void* d_out, int out_size) {
  (void)in_sizes; (void)n_in; (void)out_size;
  const __nv_bfloat16* x    = (const __nv_bfloat16*)d_in[0];
  const __nv_bfloat16* wqkv = (const __nv_bfloat16*)d_in[1];
  const __nv_bfloat16* wphi = (const __nv_bfloat16*)d_in[2];
  const __nv_bfloat16* wo   = (const __nv_bfloat16*)d_in[3];
  const __nv_bfloat16* wg   = (const __nv_bfloat16*)d_in[5];
  const __nv_bfloat16* wu   = (const __nv_bfloat16*)d_in[6];
  const __nv_bfloat16* wd   = (const __nv_bfloat16*)d_in[7];

  static EncodeFn fn = nullptr;
  if (!fn) {
    void* p = nullptr;
    cudaDriverEntryPointQueryResult qr;
    cudaGetDriverEntryPoint("cuTensorMapEncodeTiled", &p, cudaEnableDefault, &qr);
    fn = (EncodeFn)p;
    cudaFuncSetAttribute(fused_kernel, cudaFuncAttributeMaxDynamicSharedMemorySize, SM_TOTAL);
  }
  Maps maps;
  {
    cuuint64_t d[3] = {64, 2048, 8}, s[2] = {1024, 128}; cuuint32_t b[3] = {64, 64, 3};
    encode(fn, &maps.x, x, 3, d, s, b);
  }
  {
    cuuint64_t d[2] = {1536, 512}, s[1] = {3072}; cuuint32_t b[2] = {64, 192};
    encode(fn, &maps.w, wqkv, 2, d, s, b);
  }
  {
    cuuint64_t d[2] = {512, 512}, s[1] = {1024}; cuuint32_t b[2] = {64, 192};
    encode(fn, &maps.wo, wo, 2, d, s, b);
  }
  {
    cuuint64_t d[3] = {176, 7, 512}, d7[3] = {144, 1, 512}, s[2] = {352, 2752}; cuuint32_t b[3] = {64, 1, 32};
    encode(fn, &maps.g, wg, 3, d, s, b);
    encode(fn, &maps.u, wu, 3, d, s, b);
    encode(fn, &maps.g7, wg + 1232, 3, d7, s, b);
    encode(fn, &maps.u7, wu + 1232, 3, d7, s, b);
  }
  {
    cuuint64_t d[2] = {512, 1376}, s[1] = {1024}; cuuint32_t b[2] = {64, 64}, b2[2] = {64, 48};
    encode(fn, &maps.d, wd, 2, d, s, b);
    encode(fn, &maps.d48, wd, 2, d, s, b2);
  }
  fused_kernel<<<NCTA, 384, SM_TOTAL>>>(maps, x, wphi, wo, wg, wu, wd, (__nv_bfloat16*)d_out);
}
```

```cpp
#include <cuda_runtime.h>
#include <cuda_bf16.h>
#include <cuda.h>
#include <stdint.h>

#define PROF 0

#define SAFE_WAIT 0
#define THR 6

namespace {

constexpr int NCTA   = 128;
constexpr int SLOT   = 24576;
constexpr int NSLOT  = 9;
constexpr int NSTAGE = 39;

constexpr int ST_X0   = 0;
constexpr int ST_WK   = 3;
constexpr int ST_X1   = 6;
constexpr int ST_SCR0 = 9;
constexpr int ST_WV   = 10;
constexpr int ST_SCR1 = 13;
constexpr int ST_WQ   = 14;
constexpr int ST_WO   = 17;
constexpr int ST_XC   = 20;
constexpr int ST_GU   = 23;
constexpr int ST_D    = 39;

__host__ __device__ constexpr int st_empty_cnt(int d) {
  return ((d < 3 || (d >= 6 && d < 9) || (d >= ST_XC && d < ST_GU)) ? 4 : 2) * (d + 9 >= ST_GU ? 2 : 1);
}

constexpr int SM_ONES = NSLOT * SLOT;
constexpr int SM_WPHI = SM_ONES + 2048;
constexpr int SM_KVS  = SM_WPHI + 2048;
constexpr int SM_KV32 = 4 * SLOT + 16384;
constexpr int SM_BAR  = SM_KVS + 6144;
constexpr int SM_FULL  = SM_BAR;
constexpr int SM_EMPTY = SM_BAR + NSTAGE * 8;
constexpr int SM_MISCB = SM_BAR + 2 * NSTAGE * 8;
constexpr int SM_KVB   = SM_MISCB + 8;
constexpr int SM_EPOCH = SM_KVB + 8;
constexpr int SM_XF    = SM_EPOCH + 8;
constexpr int SM_XE    = SM_XF + 16 * 8;
constexpr int SM_DF    = SM_XE + 12 * 8;
constexpr int SM_DE    = SM_DF + 9 * 8;
constexpr int SM_TOTAL = SM_BAR + 1024;

static_assert(SM_TOTAL == 232448 && SM_DE + 9 * 8 <= SM_TOTAL, "smem budget");

struct Maps { CUtensorMap x, w, wo, g, u, g7, u7, d, d48; };

__device__ uint4    g_o[32][8][4][4][32];
__device__ uint4    g_h[32][8][4][4][32];
__device__ uint32_t g_hx[32][8][4][32];
__device__ uint2    g_st[32][8][64];
__device__ uint4    g_hh[32][3][8][4][4][32];
__device__ float    g_kv[2][32 * 32 * 16];
__device__ float    g_z[2][32 * 32];
__device__ unsigned g_kvcnt[8 * 32];
__device__ unsigned g_start;

__device__ __forceinline__ uint32_t smem_u32(const void* p) { return (uint32_t)__cvta_generic_to_shared(p); }
__device__ __forceinline__ void mbar_init(uint32_t bar, int cnt) {
  asm volatile("mbarrier.init.shared::cta.b64 [%0], %1;" ::"r"(bar), "r"(cnt) : "memory");
}
__device__ __forceinline__ void mbar_expect_tx(uint32_t bar, uint32_t bytes) {
  asm volatile("mbarrier.arrive.expect_tx.shared::cta.b64 _, [%0], %1;" ::"r"(bar), "r"(bytes) : "memory");
}
__device__ __forceinline__ void mbar_arrive(uint32_t bar) {
  asm volatile("mbarrier.arrive.shared::cta.b64 _, [%0];" ::"r"(bar) : "memory");
}
__device__ __forceinline__ void mbar_arrive_cluster(uint32_t bar, uint32_t rank) {
  asm volatile("{\n.reg .b32 ra;\nmapa.shared::cluster.u32 ra, %0, %1;\n"
               "mbarrier.arrive.shared::cluster.b64 _, [ra];\n}" ::"r"(bar), "r"(rank) : "memory");
}
__device__ __forceinline__ void mbar_wait_p(uint32_t bar, uint32_t parity) {
  asm volatile("{\n.reg .pred p;\nW: mbarrier.try_wait.parity.shared::cta.b64 p, [%0], %1;\n@!p bra W;\n}" ::"r"(bar), "r"(parity) : "memory");
}
__device__ __forceinline__ void mbar_wait(uint32_t bar) { mbar_wait_p(bar, 0); }
__device__ __forceinline__ void bar_sync(int id, int n)   { asm volatile("bar.sync %0, %1;" ::"r"(id), "r"(n) : "memory"); }
__device__ __forceinline__ void bar_arrive(int id, int n) { asm volatile("bar.arrive %0, %1;" ::"r"(id), "r"(n) : "memory"); }
__device__ __forceinline__ void fence_async_smem() { asm volatile("fence.proxy.async.shared::cta;" ::: "memory"); }
__device__ __forceinline__ void wg_fence()  { asm volatile("wgmma.fence.sync.aligned;" ::: "memory"); }
__device__ __forceinline__ void wg_commit() { asm volatile("wgmma.commit_group.sync.aligned;" ::: "memory"); }
template <int N> __device__ __forceinline__ void wg_wait() { asm volatile("wgmma.wait_group.sync.aligned %0;" ::"n"(N) : "memory"); }
#define DESC(off) (db + ((uint32_t)(off) >> 4))
__device__ __forceinline__ void tma2d(uint32_t dst, const CUtensorMap* m, int c0, int c1, uint32_t bar) {
  asm volatile("cp.async.bulk.tensor.2d.shared::cluster.global.mbarrier::complete_tx::bytes [%0], [%1, {%3, %4}], [%2];"
               ::"r"(dst), "l"(m), "r"(bar), "r"(c0), "r"(c1) : "memory");
}
__device__ __forceinline__ void tma3d(uint32_t dst, const CUtensorMap* m, int c0, int c1, int c2, uint32_t bar) {
  asm volatile("cp.async.bulk.tensor.3d.shared::cluster.global.mbarrier::complete_tx::bytes [%0], [%1, {%3, %4, %5}], [%2];"
               ::"r"(dst), "l"(m), "r"(bar), "r"(c0), "r"(c1), "r"(c2) : "memory");
}
__device__ __forceinline__ void tma3d_mc(uint32_t dst, const CUtensorMap* m, int c0, int c1, int c2, uint32_t bar) {
  asm volatile("cp.async.bulk.tensor.3d.shared::cluster.global.mbarrier::complete_tx::bytes.multicast::cluster [%0], [%1, {%3, %4, %5}], [%2], %6;"
               ::"r"(dst), "l"(m), "r"(bar), "r"(c0), "r"(c1), "r"(c2), "h"((uint16_t)3) : "memory");
}
__device__ __forceinline__ void ldsm4(uint32_t (&r)[4], uint32_t addr) {
  asm volatile("ldmatrix.sync.aligned.m8n8.x4.shared.b16 {%0,%1,%2,%3}, [%4];"
               : "=r"(r[0]), "=r"(r[1]), "=r"(r[2]), "=r"(r[3]) : "r"(addr) : "memory");
}
__device__ __forceinline__ void ldsm4t(uint32_t (&r)[4], uint32_t addr) {
  asm volatile("ldmatrix.sync.aligned.m8n8.x4.trans.shared.b16 {%0,%1,%2,%3}, [%4];"
               : "=r"(r[0]), "=r"(r[1]), "=r"(r[2]), "=r"(r[3]) : "r"(addr) : "memory");
}
__device__ __forceinline__ void stsm4(uint32_t addr, uint32_t r0, uint32_t r1, uint32_t r2, uint32_t r3) {
  asm volatile("stmatrix.sync.aligned.m8n8.x4.shared.b16 [%0], {%1,%2,%3,%4};"
               ::"r"(addr), "r"(r0), "r"(r1), "r"(r2), "r"(r3) : "memory");
}
__device__ __forceinline__ void mma16816(float (&c)[4], const uint32_t (&a)[4], uint32_t b0, uint32_t b1) {
  asm volatile("mma.sync.aligned.m16n8k16.row.col.f32.bf16.bf16.f32 {%0,%1,%2,%3},{%4,%5,%6,%7},{%8,%9},{%0,%1,%2,%3};"
               : "+f"(c[0]), "+f"(c[1]), "+f"(c[2]), "+f"(c[3])
               : "r"(a[0]), "r"(a[1]), "r"(a[2]), "r"(a[3]), "r"(b0), "r"(b1));
}
__device__ __forceinline__ uint32_t pack2(float lo, float hi) {
  uint32_t r; asm("cvt.rn.bf16x2.f32 %0, %1, %2;" : "=r"(r) : "f"(hi), "f"(lo)); return r;
}
__device__ __forceinline__ float blo(uint32_t w) { return __uint_as_float(w << 16); }
__device__ __forceinline__ float bhi(uint32_t w) { return __uint_as_float(w & 0xFFFF0000u); }
__device__ __forceinline__ uint32_t hsub2(uint32_t a, uint32_t b) { uint32_t r; asm("sub.rn.bf16x2 %0, %1, %2;" : "=r"(r) : "r"(a), "r"(b)); return r; }
__device__ __forceinline__ uint32_t hmax2(uint32_t a, uint32_t b) { uint32_t r; asm("max.bf16x2 %0, %1, %2;" : "=r"(r) : "r"(a), "r"(b)); return r; }
__device__ __forceinline__ uint32_t hmin2(uint32_t a, uint32_t b) { uint32_t r; asm("min.bf16x2 %0, %1, %2;" : "=r"(r) : "r"(a), "r"(b)); return r; }
__device__ __forceinline__ float ex2(float x) { float r; asm("ex2.approx.ftz.f32 %0, %1;" : "=f"(r) : "f"(x)); return r; }
__device__ __forceinline__ float rcp(float x) { float r; asm("rcp.approx.ftz.f32 %0, %1;" : "=f"(r) : "f"(x)); return r; }
__device__ __forceinline__ void ld_rlx4(uint32_t (&r)[4], const uint4* p) {
  asm volatile("{\n.reg .b128 v;\nld.relaxed.gpu.global.b128 v, [%4];\nmov.b128 {%0,%1,%2,%3}, v;\n}"
               : "=r"(r[0]), "=r"(r[1]), "=r"(r[2]), "=r"(r[3]) : "l"(p) : "memory");
}
__device__ __forceinline__ void st_rlx4(uint4* p, uint32_t a, uint32_t b, uint32_t c, uint32_t d) {
  asm volatile("{\n.reg .b128 v;\nmov.b128 v, {%1,%2,%3,%4};\nst.relaxed.gpu.global.b128 [%0], v;\n}"
               ::"l"(p), "r"(a), "r"(b), "r"(c), "r"(d) : "memory");
}
__device__ __forceinline__ void st_rlx2(uint2* p, uint32_t a, uint32_t b) {
  asm volatile("{\n.reg .b64 v;\nmov.b64 v, {%1,%2};\nst.relaxed.gpu.global.b64 [%0], v;\n}" ::"l"(p), "r"(a), "r"(b) : "memory");
}
__device__ __forceinline__ uint32_t ld_rlx1(const uint32_t* p) {
  uint32_t r; asm volatile("ld.relaxed.gpu.global.b32 %0, [%1];" : "=r"(r) : "l"(p) : "memory"); return r;
}
__device__ __forceinline__ void st_rlx1(uint32_t* p, uint32_t a) {
  asm volatile("st.relaxed.gpu.global.b32 [%0], %1;" ::"l"(p), "r"(a) : "memory");
}
__device__ __forceinline__ void ld_rlx2(uint32_t& a, uint32_t& b, const uint2* p) {
  asm volatile("{\n.reg .b64 v;\nld.relaxed.gpu.global.b64 v, [%2];\nmov.b64 {%0,%1}, v;\n}" : "=r"(a), "=r"(b) : "l"(p) : "memory");
}
__device__ __forceinline__ void bulk_g2s(uint32_t dst, const void* src, uint32_t bytes, uint32_t bar) {
  asm volatile("cp.async.bulk.shared::cluster.global.mbarrier::complete_tx::bytes [%0], [%1], %2, [%3];"
               ::"r"(dst), "l"(src), "r"(bytes), "r"(bar) : "memory");
}
__device__ __forceinline__ uint32_t tg(uint32_t w, uint32_t T) { return (w & 0xFFFFFFFEu) | T; }
__device__ __forceinline__ uint32_t bad4(uint32_t a, uint32_t b, uint32_t c, uint32_t d, uint32_t T) {
  uint32_t u, v;
  asm("lop3.b32 %0, %1, %2, %3, 0x7E;" : "=r"(u) : "r"(a), "r"(b), "r"(T));
  asm("lop3.b32 %0, %1, %2, %3, 0x7E;" : "=r"(v) : "r"(c), "r"(d), "r"(T));
  asm("lop3.b32 %0, %1, %2, 1, 0xA8;" : "=r"(u) : "r"(u), "r"(v));
  return u;
}

__device__ __forceinline__ void ld_chunk(uint32_t (&a)[4][4], const uint4* p) {
#pragma unroll
  for (int s = 0; s < 4; s++) ld_rlx4(a[s], p + s * 32);
}
__device__ __forceinline__ void lds_chunk(uint32_t (&a)[4][4], uint32_t addr) {
#pragma unroll
  for (int s = 0; s < 4; s++)
    asm volatile("ld.shared.v4.b32 {%0,%1,%2,%3}, [%4];" : "=r"(a[s][0]), "=r"(a[s][1]), "=r"(a[s][2]), "=r"(a[s][3])
                 : "r"(addr + s * 512) : "memory");
}
__device__ __forceinline__ void chk_pair(uint32_t (&a)[4][4], uint32_t (&b)[4][4], const uint4* p, uint32_t T) {
  int it = 0;
#pragma unroll 1
  while (__any_sync(0xffffffffu, bad4(a[0][0], a[1][0], a[2][0], a[3][0], T) | bad4(b[0][0], b[1][0], b[2][0], b[3][0], T))) {
    ld_chunk(a, p); ld_chunk(b, p + 512);
    if (++it > (1 << 18)) break;
  }
}

__device__ __forceinline__ void wgmma_rs_n48(float (&d)[24], const uint32_t (&a)[4], uint32_t descB, int scaleD) {
  asm volatile("{\n.reg .pred p;\n.reg .b64 db;\nsetp.ne.b32 p, %29, 0;\nmov.b64 db, {%28, 0x40000040};\n"
    "wgmma.mma_async.sync.aligned.m64n48k16.f32.bf16.bf16 {%0,%1,%2,%3,%4,%5,%6,%7,%8,%9,%10,%11,%12,%13,%14,%15,%16,%17,%18,%19,%20,%21,%22,%23}, {%24,%25,%26,%27}, db, p, 1, 1, 1;\n}\n"
    : "+f"(d[0]),"+f"(d[1]),"+f"(d[2]),"+f"(d[3]),"+f"(d[4]),"+f"(d[5]),"+f"(d[6]),"+f"(d[7]),"+f"(d[8]),"+f"(d[9]),"+f"(d[10]),"+f"(d[11]),"+f"(d[12]),"+f"(d[13]),"+f"(d[14]),"+f"(d[15]),"+f"(d[16]),"+f"(d[17]),"+f"(d[18]),"+f"(d[19]),"+f"(d[20]),"+f"(d[21]),"+f"(d[22]),"+f"(d[23])
    : "r"(a[0]), "r"(a[1]), "r"(a[2]), "r"(a[3]), "r"(descB), "r"(scaleD));
}
__device__ __forceinline__ void wgmma_rs_n64(float (&d)[32], const uint32_t (&a)[4], uint32_t descB, int scaleD) {
  asm volatile("{\n.reg .pred p;\n.reg .b64 db;\nsetp.ne.b32 p, %37, 0;\nmov.b64 db, {%36, 0x40000040};\n"
    "wgmma.mma_async.sync.aligned.m64n64k16.f32.bf16.bf16 {%0,%1,%2,%3,%4,%5,%6,%7,%8,%9,%10,%11,%12,%13,%14,%15,%16,%17,%18,%19,%20,%21,%22,%23,%24,%25,%26,%27,%28,%29,%30,%31}, {%32,%33,%34,%35}, db, p, 1, 1, 1;\n}\n"
    : "+f"(d[0]),"+f"(d[1]),"+f"(d[2]),"+f"(d[3]),"+f"(d[4]),"+f"(d[5]),"+f"(d[6]),"+f"(d[7]),"+f"(d[8]),"+f"(d[9]),"+f"(d[10]),"+f"(d[11]),"+f"(d[12]),"+f"(d[13]),"+f"(d[14]),"+f"(d[15]),"+f"(d[16]),"+f"(d[17]),"+f"(d[18]),"+f"(d[19]),"+f"(d[20]),"+f"(d[21]),"+f"(d[22]),"+f"(d[23]),"+f"(d[24]),"+f"(d[25]),"+f"(d[26]),"+f"(d[27]),"+f"(d[28]),"+f"(d[29]),"+f"(d[30]),"+f"(d[31])
    : "r"(a[0]), "r"(a[1]), "r"(a[2]), "r"(a[3]), "r"(descB), "r"(scaleD));
}
__device__ __forceinline__ void wgmma_rs_n128(float (&d)[64], const uint32_t (&a)[4], uint32_t descB, int scaleD) {
  asm volatile("{\n.reg .pred p;\n.reg .b64 db;\nsetp.ne.b32 p, %69, 0;\nmov.b64 db, {%68, 0x40000040};\n"
    "wgmma.mma_async.sync.aligned.m64n128k16.f32.bf16.bf16 {%0,%1,%2,%3,%4,%5,%6,%7,%8,%9,%10,%11,%12,%13,%14,%15,%16,%17,%18,%19,%20,%21,%22,%23,%24,%25,%26,%27,%28,%29,%30,%31,%32,%33,%34,%35,%36,%37,%38,%39,%40,%41,%42,%43,%44,%45,%46,%47,%48,%49,%50,%51,%52,%53,%54,%55,%56,%57,%58,%59,%60,%61,%62,%63}, {%64,%65,%66,%67}, db, p, 1, 1, 1;\n}\n"
    : "+f"(d[0]),"+f"(d[1]),"+f"(d[2]),"+f"(d[3]),"+f"(d[4]),"+f"(d[5]),"+f"(d[6]),"+f"(d[7]),"+f"(d[8]),"+f"(d[9]),"+f"(d[10]),"+f"(d[11]),"+f"(d[12]),"+f"(d[13]),"+f"(d[14]),"+f"(d[15]),"+f"(d[16]),"+f"(d[17]),"+f"(d[18]),"+f"(d[19]),"+f"(d[20]),"+f"(d[21]),"+f"(d[22]),"+f"(d[23]),"+f"(d[24]),"+f"(d[25]),"+f"(d[26]),"+f"(d[27]),"+f"(d[28]),"+f"(d[29]),"+f"(d[30]),"+f"(d[31]),"+f"(d[32]),"+f"(d[33]),"+f"(d[34]),"+f"(d[35]),"+f"(d[36]),"+f"(d[37]),"+f"(d[38]),"+f"(d[39]),"+f"(d[40]),"+f"(d[41]),"+f"(d[42]),"+f"(d[43]),"+f"(d[44]),"+f"(d[45]),"+f"(d[46]),"+f"(d[47]),"+f"(d[48]),"+f"(d[49]),"+f"(d[50]),"+f"(d[51]),"+f"(d[52]),"+f"(d[53]),"+f"(d[54]),"+f"(d[55]),"+f"(d[56]),"+f"(d[57]),"+f"(d[58]),"+f"(d[59]),"+f"(d[60]),"+f"(d[61]),"+f"(d[62]),"+f"(d[63])
    : "r"(a[0]), "r"(a[1]), "r"(a[2]), "r"(a[3]), "r"(descB), "r"(scaleD));
}
__device__ __forceinline__ void wgmma_ss_n72_t11(float (&d)[36], uint32_t descA, uint32_t descB, int scaleD) {
  asm volatile("{\n.reg .pred p;\n.reg .b64 da, db;\nsetp.ne.b32 p, %38, 0;\nmov.b64 da, {%36, 0x40000040};\nmov.b64 db, {%37, 0x40000040};\n"
    "wgmma.mma_async.sync.aligned.m64n72k16.f32.bf16.bf16 {%0,%1,%2,%3,%4,%5,%6,%7,%8,%9,%10,%11,%12,%13,%14,%15,%16,%17,%18,%19,%20,%21,%22,%23,%24,%25,%26,%27,%28,%29,%30,%31,%32,%33,%34,%35}, da, db, p, 1, 1, 1, 1;\n}\n"
    : "+f"(d[0]),"+f"(d[1]),"+f"(d[2]),"+f"(d[3]),"+f"(d[4]),"+f"(d[5]),"+f"(d[6]),"+f"(d[7]),"+f"(d[8]),"+f"(d[9]),"+f"(d[10]),"+f"(d[11]),"+f"(d[12]),"+f"(d[13]),"+f"(d[14]),"+f"(d[15]),"+f"(d[16]),"+f"(d[17]),"+f"(d[18]),"+f"(d[19]),"+f"(d[20]),"+f"(d[21]),"+f"(d[22]),"+f"(d[23]),"+f"(d[24]),"+f"(d[25]),"+f"(d[26]),"+f"(d[27]),"+f"(d[28]),"+f"(d[29]),"+f"(d[30]),"+f"(d[31]),"+f"(d[32]),"+f"(d[33]),"+f"(d[34]),"+f"(d[35])
    : "r"(descA), "r"(descB), "r"(scaleD));
}

#define TSTAMP(i) do {} while (0)
#define TS2(w, i) do {} while (0)

constexpr float LOG2E = 1.4426950408889634f;

__device__ __forceinline__ void feat_exp(const uint32_t (&P)[4], float (&e)[16]) {
  uint32_t a = hmax2(P[0], P[2]), b = hmax2(P[1], P[3]);
  uint32_t mx = hmax2(__byte_perm(a, b, 0x5410), __byte_perm(a, b, 0x7632));
  a = hmin2(P[0], P[2]); b = hmin2(P[1], P[3]);
  uint32_t mn = hmin2(__byte_perm(a, b, 0x5410), __byte_perm(a, b, 0x7632));
  mx = hmax2(mx, __shfl_xor_sync(0xffffffffu, mx, 1));
  mn = hmin2(mn, __shfl_xor_sync(0xffffffffu, mn, 1));
  mx = hmax2(mx, __shfl_xor_sync(0xffffffffu, mx, 2));
  mn = hmin2(mn, __shfl_xor_sync(0xffffffffu, mn, 2));
  float mx0 = -blo(mx) * LOG2E, mx1 = -bhi(mx) * LOG2E, mn0 = blo(mn) * LOG2E, mn1 = bhi(mn) * LOG2E;
  float v[8] = {blo(P[0]), bhi(P[0]), blo(P[1]), bhi(P[1]), blo(P[2]), bhi(P[2]), blo(P[3]), bhi(P[3])};
#pragma unroll
  for (int i = 0; i < 8; i++) {
    bool r1 = (i >> 1) & 1;
    e[i]     = ex2(fmaf(v[i],  LOG2E, r1 ? mx1 : mx0));
    e[8 + i] = ex2(fmaf(v[i], -LOG2E, r1 ? mn1 : mn0));
  }
}

template <int SBASE>
__global__ void __cluster_dims__(2, 1, 1) __launch_bounds__(384, 1)
fused_kernel(const __grid_constant__ Maps maps, const __nv_bfloat16* __restrict__ x, const __nv_bfloat16* __restrict__ wphi,
             const __nv_bfloat16* __restrict__ wo, const __nv_bfloat16* __restrict__ wg_, const __nv_bfloat16* __restrict__ wu_,
             const __nv_bfloat16* __restrict__ wd_, __nv_bfloat16* __restrict__ out) {
  extern __shared__ __align__(1024) unsigned char smem[];
  const uint32_t sb = smem_u32(smem);
  const int tid = threadIdx.x, lane = tid & 31;
  const int warp = __shfl_sync(0xffffffffu, tid >> 5, 0);
  const uint32_t rank = blockIdx.x & 1;
  const int cl = blockIdx.x >> 1;
  int quad, qi;
  if (cl < 4) { quad = 15; qi = cl; }
  else if (cl < 36) { quad = (cl - 4) & 7; qi = (cl - 4) >> 3; }
  else { qi = (cl - 36) / 7; quad = 8 + (cl - 36) - 7 * qi; }
  const int rb = quad, hg = 2 * qi + rank;
  const int rb3 = (quad & ~1) + rank, jf = 4 * (quad & 1) + qi;

  if (warp < 8) {
    asm volatile("setmaxnreg.inc.sync.aligned.u32 240;");
    if (lane == 0) {
#pragma unroll 1
      for (int d = warp; d < NSTAGE; d += 8) {
        mbar_init(sb + SM_EMPTY + d * 8, st_empty_cnt(d));
        if (d + 9 < NSTAGE) {
          mbar_init(sb + SM_FULL + (d + 9) * 8, 1);
          mbar_expect_tx(sb + SM_FULL + (d + 9) * 8, SLOT);
        }
      }
      asm volatile("fence.mbarrier_init.release.cluster;" ::: "memory");
    }
    __syncwarp();
    bar_sync(0, 352);
    asm volatile("barrier.cluster.arrive.relaxed.aligned;" ::: "memory");
    const int wg = warp >> 2, wq = warp & 3, g = lane >> 2, t = lane & 3;
    const bool lead = (tid & 127) == 0;
    const uint32_t db = ((SBASE ? (uint32_t)SBASE : (sb & 0x3FFFF)) >> 4) | (512u << 16);
    auto release = [&](int d) {
      const int s = d + NSLOT;
      mbar_arrive_cluster(sb + SM_EMPTY + d * 8, (s >= ST_GU && s < ST_D) ? (uint32_t)(s & 1) : rank);
      if (s >= ST_D) mbar_arrive_cluster(sb + SM_EMPTY + d * 8, rank ^ 1);
    };
    const uint32_t lrow = (uint32_t)(wq * 16 + (lane & 7) + ((lane >> 3) & 1) * 8) * 128;
    const uint32_t lx = lane & 7, lhi = lane >> 4;
    if (wg == 1) bar_arrive(4, 256);
    TSTAMP(0);

    float r0, r1;
    uint32_t E[4][8];
    uint32_t T = 0;
    {
      uint32_t A[32][4];
      const int sx = wg ? ST_X1 : ST_X0;
      {
        const uint32_t base = sb + sx * SLOT + lrow;
        float cs[2][4], c0[2][4], c1[2][4];
#pragma unroll
        for (int i = 0; i < 4; i++) { cs[0][i] = cs[1][i] = c0[0][i] = c0[1][i] = c1[0][i] = c1[1][i] = 0.f; }
#pragma unroll
        for (int c = 0; c < 8; c++) {
          if (c % 3 == 0) mbar_wait(sb + SM_FULL + (sx + c / 3) * 8);
#pragma unroll
          for (int k = 0; k < 4; k++) ldsm4(A[4 * c + k], base + c * 8192 + (((2 * k + lhi) ^ lx) << 4));
#pragma unroll
          for (int k = 0; k < 4; k++) {
            const uint32_t (&f)[4] = A[4 * c + k];
            mma16816(cs[k & 1], f, 0x3F803F80u, 0x3F803F80u);
            mma16816(c0[k & 1], f, f[0], f[2]);
            mma16816(c1[k & 1], f, f[1], f[3]);
          }
        }
        const float s0 = (cs[0][0] + cs[1][0]) * (1.f / 512.f), s1 = (cs[0][2] + cs[1][2]) * (1.f / 512.f);
        TSTAMP(17);
        asm volatile("barrier.cluster.wait.aligned;" ::: "memory");
        if (lane < 3) release(sx + lane);
        const uint32_t m0 = pack2(s0, s0), m1 = pack2(s1, s1);
        float q0 = (g & 1) ? c0[0][1] + c0[1][1] : c0[0][0] + c0[1][0];
        float q1 = (g & 1) ? c1[0][3] + c1[1][3] : c1[0][2] + c1[1][2];
        q0 = __shfl_sync(0xffffffffu, q0, (lane & ~3) | (g >> 1));
        q1 = __shfl_sync(0xffffffffu, q1, (lane & ~3) | (g >> 1));
        r0 = rsqrtf(fmaxf(q0 * (1.f / 512.f) - s0 * s0, 0.f) + 1e-5f);
        r1 = rsqrtf(fmaxf(q1 * (1.f / 512.f) - s1 * s1, 0.f) + 1e-5f);
#pragma unroll
        for (int ks = 0; ks < 32; ks++) {
          A[ks][0] = hsub2(A[ks][0], m0); A[ks][1] = hsub2(A[ks][1], m1);
          A[ks][2] = hsub2(A[ks][2], m0); A[ks][3] = hsub2(A[ks][3], m1);
        }
      }
      TSTAMP(1);
      const uint32_t wpa = sb + SM_WPHI + ((lane & 7) + ((lane >> 3) & 1) * 8) * 32 + lhi * 16;
      const uint32_t scr = sb + (wg ? (ST_SCR1 % NSLOT) : (ST_SCR0 % NSLOT)) * SLOT;
      mbar_wait(sb + SM_MISCB);
      T = (*reinterpret_cast<volatile unsigned*>(smem + SM_EPOCH) & 1) ^ 1;
#pragma unroll 1
      for (int ps = 0; ps < 3; ps++) {
        const int st0 = ps == 0 ? ST_WK : (ps == 1 ? ST_WV : ST_WQ);
        const uint32_t wdesc = DESC((ps == 0 ? ST_WK % NSLOT : (ps == 1 ? ST_WV % NSLOT : ST_WQ % NSLOT)) * SLOT);
        float acc[32];
        bar_sync(4 + wg, 256);
#pragma unroll
        for (int i = 0; i < 3; i++) {
          mbar_wait(sb + SM_FULL + (st0 + i) * 8);
          wg_fence();
#pragma unroll
          for (int kk = 0; kk < (i < 2 ? 12 : 8); kk++)
            wgmma_rs_n64(acc, A[12 * i + kk], wdesc + ((i * SLOT + kk * 2048) >> 4), (i | kk) != 0);
          wg_commit();
          if (i == 1) { wg_wait<1>(); if (lead) release(st0); }
        }
        if (ps == 0 || wg == 0) bar_arrive(4 + (wg ^ 1), 256);
        uint32_t a[4][4], b[4][4];
#pragma unroll
        for (int h = 0; h < 4; h++) ldsm4t(b[h], wpa + h * 512);
        wg_wait<0>();
        if ((tid & 127) < 2) release(st0 + 1 + (tid & 1));
        TSTAMP(2 + 2 * ps);
#pragma unroll
        for (int h = 0; h < 4; h++) {
          a[h][0] = pack2(acc[8 * h + 0] * r0, acc[8 * h + 1] * r0); a[h][1] = pack2(acc[8 * h + 2] * r1, acc[8 * h + 3] * r1);
          a[h][2] = pack2(acc[8 * h + 4] * r0, acc[8 * h + 5] * r0); a[h][3] = pack2(acc[8 * h + 6] * r1, acc[8 * h + 7] * r1);
        }
        if (ps != 1) {
          {
            float pp[4][2][4];
#pragma unroll
            for (int h = 0; h < 4; h++) {
#pragma unroll
              for (int i = 0; i < 4; i++) { pp[h][0][i] = 0.f; pp[h][1][i] = 0.f; }
              mma16816(pp[h][0], a[h], b[h][0], b[h][1]);
              mma16816(pp[h][1], a[h], b[h][2], b[h][3]);
            }
#pragma unroll
            for (int h = 0; h < 4; h++) {
              a[h][0] = pack2(pp[h][0][0], pp[h][0][1]); a[h][1] = pack2(pp[h][0][2], pp[h][0][3]);
              a[h][2] = pack2(pp[h][1][0], pp[h][1][1]); a[h][3] = pack2(pp[h][1][2], pp[h][1][3]);
            }
          }
          if (ps == 0) mbar_wait(sb + SM_EMPTY + (wg ? ST_SCR1 - NSLOT : ST_SCR0 - NSLOT) * 8);
#pragma unroll 1
          for (int hp = 0; hp < 2; hp++) {
            float e[2][16];
            feat_exp(a[0], e[0]);
            feat_exp(a[1], e[1]);
            if (ps == 0) {
#pragma unroll
              for (int h = 0; h < 2; h++) {
                const float (&f)[16] = e[h];
                float sp0 = (f[0] + f[1]) + (f[4] + f[5]), sp1 = (f[2] + f[3]) + (f[6] + f[7]);
                float sn0 = (f[8] + f[9]) + (f[12] + f[13]), sn1 = (f[10] + f[11]) + (f[14] + f[15]);
                sp0 += __shfl_xor_sync(0xffffffffu, sp0, 1); sp1 += __shfl_xor_sync(0xffffffffu, sp1, 1);
                sn0 += __shfl_xor_sync(0xffffffffu, sn0, 1); sn1 += __shfl_xor_sync(0xffffffffu, sn1, 1);
                sp0 += __shfl_xor_sync(0xffffffffu, sp0, 2); sp1 += __shfl_xor_sync(0xffffffffu, sp1, 2);
                sn0 += __shfl_xor_sync(0xffffffffu, sn0, 2); sn1 += __shfl_xor_sync(0xffffffffu, sn1, 2);
                sp0 = rcp(sp0); sp1 = rcp(sp1); sn0 = rcp(sn0); sn1 = rcp(sn1);
                const uint32_t dst = scr + hp * 8192 + lrow;
                stsm4(dst + (((h * 4 + lhi) ^ lx) << 4), pack2(f[0] * sp0, f[1] * sp0), pack2(f[2] * sp1, f[3] * sp1),
                      pack2(f[4] * sp0, f[5] * sp0), pack2(f[6] * sp1, f[7] * sp1));
                stsm4(dst + (((h * 4 + 2 + lhi) ^ lx) << 4), pack2(f[8] * sn0, f[9] * sn0), pack2(f[10] * sn1, f[11] * sn1),
                      pack2(f[12] * sn0, f[13] * sn0), pack2(f[14] * sn1, f[15] * sn1));
              }
            } else {
#pragma unroll
              for (int i = 0; i < 16; i++) {
                A[i >> 2][i & 3] = A[4 + (i >> 2)][i & 3];
                A[4 + (i >> 2)][i & 3] = pack2(e[i >> 3][2 * (i & 7)], e[i >> 3][2 * (i & 7) + 1]);
              }
            }
#pragma unroll
            for (int i = 0; i < 4; i++) { a[0][i] = a[2][i]; a[1][i] = a[3][i]; }
          }
        } else {
#pragma unroll
          for (int h = 0; h < 4; h++) stsm4(scr + 16384 + lrow + (((2 * h + lhi) ^ lx) << 4), a[h][0], a[h][1], a[h][2], a[h][3]);
          fence_async_smem();
          bar_sync(3, 256);
          float kv[36];
          wg_fence();
#pragma unroll
          for (int ks = 0; ks < 8; ks++) {
            const uint32_t sk = (ks < 4 ? (ST_SCR0 % NSLOT) : (ST_SCR1 % NSLOT)) * SLOT + (ks & 3) * 2048;
            const uint32_t dv = (DESC(sk + 16384) & 0xFFFFu) | (((SM_ONES - sk - 16384) >> 4) << 16);
            wgmma_ss_n72_t11(kv, DESC(sk) + wg * 512, dv, ks != 0);
          }
          wg_commit();
          if (wg == 1) bar_arrive(4, 256);
          wg_wait<0>();
          if (lead) { mbar_arrive(sb + SM_EMPTY + ST_SCR0 * 8); mbar_arrive(sb + SM_EMPTY + ST_SCR1 * 8); }
          const int hl = 2 * wg + (wq >> 1), f = (wq & 1) * 16 + g;
          float* kvp = &g_kv[T ^ 1][((hg * 4 + hl) * 32 + f) * 16 + 2 * t];
          float* zp = &g_z[T ^ 1][(hg * 4 + hl) * 32 + f];
          float c[8];
#pragma unroll
          for (int i = 0; i < 8; i++) c[i] = hl >= 2 ? (hl == 3 ? kv[24 + i] : kv[16 + i]) : (hl == 1 ? kv[8 + i] : kv[i]);
#pragma unroll
          for (int n = 0; n < 2; n++) {
            asm volatile("red.relaxed.gpu.global.add.v2.f32 [%0], {%1,%2};" ::"l"(kvp + n * 8), "f"(c[4 * n]), "f"(c[4 * n + 1]) : "memory");
            asm volatile("red.relaxed.gpu.global.add.v2.f32 [%0], {%1,%2};" ::"l"(kvp + n * 8 + 128), "f"(c[4 * n + 2]), "f"(c[4 * n + 3]) : "memory");
          }
          if (t < 2) asm volatile("red.relaxed.gpu.global.add.f32 [%0], %1;" ::"l"(zp + t * 8), "f"(t ? kv[34] : kv[32]) : "memory");
          bar_arrive(6 + wg, 160);
        }
        TSTAMP(3 + 2 * ps);
      }
#pragma unroll
      for (int i = 0; i < 32; i++) E[i >> 3][i & 7] = A[i >> 2][i & 3];
    }
    const int rh = 2 * rb + wg;
    const uint32_t xb = sb + 2 * SLOT + wq * 2048 + lane * 16;
    mbar_wait(sb + SM_KVB);
    {
      const int r = tid & 127;
      const float4* src = reinterpret_cast<const float4*>(smem + SM_KV32) + r;
#pragma unroll
      for (int i = 0; i < 4; i++) {
        const float4 a = src[i * 128];
        *reinterpret_cast<uint2*>(smem + SM_KVS + (i * 32 + (r >> 2)) * 48 + (r & 3) * 8) = make_uint2(pack2(a.x, a.y), pack2(a.z, a.w));
      }
      const uint32_t zz = pack2(reinterpret_cast<const float*>(smem + SM_ONES)[r], 1.0f);
      *reinterpret_cast<uint4*>(smem + SM_KVS + r * 48 + 32) = make_uint4(zz, zz, zz, zz);
      bar_sync(1 + wg, 128);
    }
    TSTAMP(8);
    {
      uint4* op = &g_o[rh][hg][wq][0][lane];
#pragma unroll
      for (int h = 0; h < 4; h++) {
        uint32_t b0[4], b1[4], b2[4];
        const uint32_t kb = sb + SM_KVS + (h * 32 + lane) * 48;
        ldsm4t(b0, kb); ldsm4t(b1, kb + 16); ldsm4t(b2, kb + 32);
        const uint32_t ep[4] = {E[h][0], E[h][1], E[h][2], E[h][3]}, en[4] = {E[h][4], E[h][5], E[h][6], E[h][7]};
        float np0[4] = {0, 0, 0, 0}, np1[4] = {0, 0, 0, 0}, nn0[4] = {0, 0, 0, 0}, nn1[4] = {0, 0, 0, 0}, dp[4] = {0, 0, 0, 0}, dn[4] = {0, 0, 0, 0};
        mma16816(dp, ep, b2[0], b2[1]);  mma16816(dn, en, b2[2], b2[3]);
        mma16816(np0, ep, b0[0], b0[1]); mma16816(nn0, en, b0[2], b0[3]);
        mma16816(np1, ep, b1[0], b1[1]); mma16816(nn1, en, b1[2], b1[3]);
        const float i0 = rcp(fmaf(dp[0], dn[1], fmaf(dn[0], dp[1], 1e-6f * dp[1] * dn[1])));
        const float i1 = rcp(fmaf(dp[2], dn[3], fmaf(dn[2], dp[3], 1e-6f * dp[3] * dn[3])));
        const float cp0 = dn[1] * i0, cn0 = dp[1] * i0, cp1 = dn[3] * i1, cn1 = dp[3] * i1;
        st_rlx4(op + h * 32,
                tg(pack2(fmaf(np0[0], cp0, nn0[0] * cn0), fmaf(np0[1], cp0, nn0[1] * cn0)), T),
                pack2(fmaf(np0[2], cp1, nn0[2] * cn1), fmaf(np0[3], cp1, nn0[3] * cn1)),
                pack2(fmaf(np1[0], cp0, nn1[0] * cn0), fmaf(np1[1], cp0, nn1[1] * cn0)),
                pack2(fmaf(np1[2], cp1, nn1[2] * cn1), fmaf(np1[3], cp1, nn1[3] * cn1)));
      }
    }
    TSTAMP(9);

    {
      uint32_t xr[16];
      {
        const uint32_t* xp = reinterpret_cast<const uint32_t*>(x + (size_t)(rh * 64 + wq * 16 + g) * 512 + hg * 64 + 2 * t);
#pragma unroll
        for (int i = 0; i < 8; i++) { xr[2 * i] = __ldg(xp + 4 * i); xr[2 * i + 1] = __ldg(xp + 8 * 256 + 4 * i); }
      }
      uint32_t A[8][4][4];
      const uint4* op = &g_o[rh][0][wq][0][lane];
      float acc[32];
      mbar_wait(sb + SM_XF + (wg * 4) * 8);
      lds_chunk(A[0], xb); lds_chunk(A[1], xb + 8192);
#pragma unroll
      for (int p = 0; p < 4; p++) {
        chk_pair(A[2 * p], A[2 * p + 1], op + p * 1024, T);
        if (lane == 0) mbar_arrive(sb + SM_XE + (wg * 4 + p) * 8);
#pragma unroll
        for (int c = 2 * p; c < 2 * p + 2; c++) {
          if (c % 3 == 0) mbar_wait(sb + SM_FULL + (ST_WO + c / 3) * 8);
          if ((c & 1) && p < 3) {
            mbar_wait(sb + SM_XF + (wg * 4 + p + 1) * 8);
            lds_chunk(A[2 * p + 2], xb + (p + 1) * 16384); lds_chunk(A[2 * p + 3], xb + (p + 1) * 16384 + 8192);
          }
          wg_fence();
#pragma unroll
          for (int s = 0; s < 4; s++)
            wgmma_rs_n64(acc, A[c][s], DESC(((ST_WO + c / 3) % NSLOT) * SLOT + ((c % 3) * 4 + s) * 2048), (c | s) != 0);
          wg_commit();
        }
      }
      wg_wait<0>();
      if ((tid & 127) < 3) release(ST_WO + (tid & 127));
      TSTAMP(10);
      uint32_t hw[16];
      float s0 = 0.f, s1 = 0.f, q0 = 0.f, q1 = 0.f;
#pragma unroll
      for (int i = 0; i < 8; i++) {
        hw[2 * i]     = pack2(blo(xr[2 * i]) + acc[4 * i], bhi(xr[2 * i]) + acc[4 * i + 1]);
        hw[2 * i + 1] = pack2(blo(xr[2 * i + 1]) + acc[4 * i + 2], bhi(xr[2 * i + 1]) + acc[4 * i + 3]);
      }
      uint4* hp_ = &g_h[rh][hg][wq][0][lane];
#pragma unroll
      for (int s = 0; s < 4; s++) st_rlx4(hp_ + s * 32, tg(hw[4 * s], T), hw[4 * s + 1], hw[4 * s + 2], hw[4 * s + 3]);
#pragma unroll
      for (int i = 0; i < 8; i++) {
        float a = blo(hw[2 * i]), b = bhi(hw[2 * i]);
        s0 += a + b; q0 = fmaf(a, a, q0); q0 = fmaf(b, b, q0);
        a = blo(hw[2 * i + 1]); b = bhi(hw[2 * i + 1]);
        s1 += a + b; q1 = fmaf(a, a, q1); q1 = fmaf(b, b, q1);
      }
      s0 += __shfl_xor_sync(0xffffffffu, s0, 1); s1 += __shfl_xor_sync(0xffffffffu, s1, 1);
      q0 += __shfl_xor_sync(0xffffffffu, q0, 1); q1 += __shfl_xor_sync(0xffffffffu, q1, 1);
      s0 += __shfl_xor_sync(0xffffffffu, s0, 2); s1 += __shfl_xor_sync(0xffffffffu, s1, 2);
      q0 += __shfl_xor_sync(0xffffffffu, q0, 2); q1 += __shfl_xor_sync(0xffffffffu, q1, 2);
      if (t < 2) st_rlx2(&g_st[rh][hg][wq * 16 + g + t * 8], tg(__float_as_uint(t ? s1 : s0), T), __float_as_uint(t ? q1 : q0));
      uint32_t hx = T;
#pragma unroll
      for (int i = 0; i < 4; i++) hx |= (hw[4 * i] & 1u) << (i + 1);
      st_rlx1(&g_hx[rh][hg][wq][lane], hx);
    }
    TSTAMP(11);

    const int rh3 = 2 * rb3 + wg;
    {
      uint32_t A[8][4][4];
      const uint4* hp_ = &g_h[rh3][0][wq][0][lane];
      uint4* hhp = &g_hh[rh3][0][jf][0][wq][lane];
      const uint32_t dg = (db & 0xFFFFu) | (256u << 16);
      uint32_t m0, m1;
      mbar_wait(sb + SM_XF + ((2 + wg) * 4) * 8);
      lds_chunk(A[0], xb); lds_chunk(A[1], xb + 8192);
      {
        const uint2* sp = &g_st[rh3][2 * t][wq * 16 + g];
        const uint2* ss = reinterpret_cast<const uint2*>(smem + SM_KV32 + wg * 4096) + 2 * t * 64 + wq * 16 + g;
        uint2 a0 = ss[0], a1 = ss[64], b0 = ss[8], b1 = ss[72];
        int it = 0;
#pragma unroll 1
        while (__any_sync(0xffffffffu, bad4(a0.x, a1.x, b0.x, b1.x, T))) {
          ld_rlx2(a0.x, a0.y, sp); ld_rlx2(a1.x, a1.y, sp + 64); ld_rlx2(b0.x, b0.y, sp + 8); ld_rlx2(b1.x, b1.y, sp + 72);
          if (++it > (1 << 18)) break;
        }
        float s0 = __uint_as_float(a0.x) + __uint_as_float(a1.x), q0 = __uint_as_float(a0.y) + __uint_as_float(a1.y);
        float s1 = __uint_as_float(b0.x) + __uint_as_float(b1.x), q1 = __uint_as_float(b0.y) + __uint_as_float(b1.y);
        s0 += __shfl_xor_sync(0xffffffffu, s0, 1); s1 += __shfl_xor_sync(0xffffffffu, s1, 1);
        q0 += __shfl_xor_sync(0xffffffffu, q0, 1); q1 += __shfl_xor_sync(0xffffffffu, q1, 1);
        s0 += __shfl_xor_sync(0xffffffffu, s0, 2); s1 += __shfl_xor_sync(0xffffffffu, s1, 2);
        q0 += __shfl_xor_sync(0xffffffffu, q0, 2); q1 += __shfl_xor_sync(0xffffffffu, q1, 2);
        s0 *= (1.f / 512.f); s1 *= (1.f / 512.f);
        r0 = rcp(fmaxf(q0 * (1.f / 512.f) - s0 * s0, 0.f) + 1e-5f);
        r1 = rcp(fmaxf(q1 * (1.f / 512.f) - s1 * s1, 0.f) + 1e-5f);
        m0 = pack2(s0, s0); m1 = pack2(s1, s1);
      }
      TSTAMP(12);
#pragma unroll
      for (int p = 0; p < 4; p++) {
        if (p < 3) {
          mbar_wait(sb + SM_XF + ((2 + wg) * 4 + p + 1) * 8);
          lds_chunk(A[2 * p + 2], xb + (p + 1) * 16384); lds_chunk(A[2 * p + 3], xb + (p + 1) * 16384 + 8192);
        }
        chk_pair(A[2 * p], A[2 * p + 1], hp_ + p * 1024, T);
        if (lane == 0) {
          if (wg == 0) mbar_arrive(sb + SM_XE + (8 + p) * 8);
          else if (p > 0) release(ST_XC + p - 1);
        }
#pragma unroll
        for (int c = 2 * p; c < 2 * p + 2; c++)
#pragma unroll
          for (int s = 0; s < 4; s++) {
            A[c][s][0] = hsub2(A[c][s][0], m0); A[c][s][1] = hsub2(A[c][s][1], m1);
            A[c][s][2] = hsub2(A[c][s][2], m0); A[c][s][3] = hsub2(A[c][s][3], m1);
          }
      }
      TSTAMP(19);
#define UOFF(u) ((((ST_GU + (u) / 3) % NSLOT) * SLOT + ((u) % 3) * 8192) >> 4)
#define UNIT_PRE(u)  do { if ((u) % 3 == 0) mbar_wait(sb + SM_FULL + (ST_GU + (u) / 3) * 8); } while (0)
#define UNIT_POST(u) do { wg_commit(); if ((u) % 3 == 1 && (u) > 3) { wg_wait<2>(); if (lead) release(ST_GU + (u) / 3 - 1); } } while (0)
      float acc[64];
      const int rz = blockIdx.y;
#pragma unroll
      for (int ps = 0; ps < 2; ps++) {
        wg_fence();
#pragma unroll
        for (int k = 0; k < 16; k++) {
          const int u = 16 * ps + k, c = k >> 1;
          UNIT_PRE(u);
          wgmma_rs_n128(acc, A[c][(k & 1) * 2], dg + UOFF(u), k != 0 ? 1 : (ps ? rz : 0));
          wgmma_rs_n128(acc, A[c][(k & 1) * 2 + 1], dg + UOFF(u) + 128, 1);
          UNIT_POST(u);
        }
        wg_wait<0>();
#pragma unroll
        for (int k = 0; k < 4; k++) {
          const int s = k == 2 ? 3 : (k == 3 ? 2 : k);
          st_rlx4(hhp + ps * 4096 + s * 128,
                  tg(pack2(acc[8 * s + 0] * acc[32 + 8 * s + 0] * r0, acc[8 * s + 1] * acc[32 + 8 * s + 1] * r0), T),
                  pack2(acc[8 * s + 2] * acc[32 + 8 * s + 2] * r1, acc[8 * s + 3] * acc[32 + 8 * s + 3] * r1),
                  pack2(acc[8 * s + 4] * acc[32 + 8 * s + 4] * r0, acc[8 * s + 5] * acc[32 + 8 * s + 5] * r0),
                  pack2(acc[8 * s + 6] * acc[32 + 8 * s + 6] * r1, acc[8 * s + 7] * acc[32 + 8 * s + 7] * r1));
        }
      }
      {
        float ag[24], au[24];
        bar_sync(1 + wg, 128);
        wg_fence();
#pragma unroll
        for (int k = 0; k < 16; k++) {
          const int u = 32 + k, c = k >> 1;
          UNIT_PRE(u);
          wgmma_rs_n48(ag, A[c][(k & 1) * 2], dg + UOFF(u), k != 0);
          wgmma_rs_n48(au, A[c][(k & 1) * 2], dg + UOFF(u) + 256, k != 0);
          wgmma_rs_n48(ag, A[c][(k & 1) * 2 + 1], dg + UOFF(u) + 128, 1);
          wgmma_rs_n48(au, A[c][(k & 1) * 2 + 1], dg + UOFF(u) + 256 + 128, 1);
          UNIT_POST(u);
        }
        wg_wait<0>();
        if (lead) release(ST_D - 1);
        TSTAMP(13);
#pragma unroll
        for (int s = 0; s < 3; s++)
          st_rlx4(hhp + 2 * 4096 + s * 128,
                  tg(pack2(ag[8 * s + 0] * au[8 * s + 0] * r0, ag[8 * s + 1] * au[8 * s + 1] * r0), T),
                  pack2(ag[8 * s + 2] * au[8 * s + 2] * r1, ag[8 * s + 3] * au[8 * s + 3] * r1),
                  pack2(ag[8 * s + 4] * au[8 * s + 4] * r0, ag[8 * s + 5] * au[8 * s + 5] * r0),
                  pack2(ag[8 * s + 6] * au[8 * s + 6] * r1, ag[8 * s + 7] * au[8 * s + 7] * r1));
      }
    }
    TSTAMP(14);

    {
      float acc[32];
      uint32_t F[2][8][4], hr[4][4];
      ld_chunk(hr, &g_h[rh][hg][wq][0][lane]);
      const uint32_t hx = ld_rlx1(&g_hx[rh][hg][wq][lane]);
      const uint4* gp = &g_hh[rh][0][0][0][wq][lane];
      const uint32_t fb = sb + wg * 8192 + wq * 512 + lane * 16;
      auto load = [&](uint32_t (&f)[8][4], int i, int s0, int s1) {
        mbar_wait_p(sb + SM_DF + s0 * 8, i >= 9 && i < 18);
        mbar_wait_p(sb + SM_DF + s1 * 8, i >= 8 && i < 17);
        const uint32_t o3 = i < 16 ? 3 * 2048 : 0;
#pragma unroll
        for (int s = 0; s < 8; s++)
          asm volatile("ld.shared.v4.b32 {%0,%1,%2,%3}, [%4];" : "=r"(f[s][0]), "=r"(f[s][1]), "=r"(f[s][2]), "=r"(f[s][3])
                       : "r"(fb + (s < 4 ? s0 : s1) * SLOT + ((s & 3) == 3 ? o3 : (s & 3) * 2048)) : "memory");
        int it = 0;
#pragma unroll 1
        while (__any_sync(0xffffffffu, bad4(f[0][0], f[1][0], f[2][0], f[3][0], T) | bad4(f[4][0], f[5][0], f[6][0], f[7][0], T))) {
#pragma unroll
          for (int s = 0; s < 8; s++) ld_rlx4(f[s], gp + (i + (s >> 2)) * 512 + ((s & 3) == 3 ? (o3 >> 4) : (s & 3) * 128));
          if (++it > (1 << 18)) break;
        }
      };
      int s0 = ST_D % NSLOT, s1 = s0 + 1, p0 = 0, p1 = 0;
      load(F[0], 0, s0, s1);
#pragma unroll 1
      for (int i2 = 0; i2 < 24; i2 += 4) {
#pragma unroll
        for (int b = 0; b < 2; b++) {
          const int i = i2 + 2 * b;
          const uint32_t d0 = db + s0 * (SLOT >> 4) + 1024, d1 = db + s1 * (SLOT >> 4) + 1024;
          wg_fence();
#pragma unroll
          for (int s = 0; s < 3; s++) wgmma_rs_n64(acc, F[b][s], d0 + s * 128, (i | s) != 0);
#pragma unroll
          for (int s = 0; s < 3; s++) wgmma_rs_n64(acc, F[b][4 + s], d1 + s * 128, 1);
          if (i < 16) { wgmma_rs_n64(acc, F[b][3], d0 + 384, 1); wgmma_rs_n64(acc, F[b][7], d1 + 384, 1); }
          wg_commit();
          wg_wait<1>();
          if ((tid & 127) < 4 && i > 0 && i + ((tid >> 1) & 1) < 17) mbar_arrive_cluster(sb + SM_DE + ((tid & 2) ? p1 : p0) * 8, tid & 1);
          p0 = s0; p1 = s1;
          s0 = s1 + 1 == NSLOT ? 0 : s1 + 1;
          s1 = s0 + 1 == NSLOT ? 0 : s0 + 1;
          if (i < 22) load(F[b ^ 1], i + 2, s0, s1);
        }
      }
      wg_wait<0>();
      TSTAMP(15);
#pragma unroll
      for (int s = 0; s < 4; s++) hr[s][0] = (hr[s][0] & 0xFFFFFFFEu) | ((hx >> (s + 1)) & 1u);
      const uint32_t ob = sb + wg * 8192;
#pragma unroll
      for (int s = 0; s < 4; s++)
        stsm4(ob + lrow + (((2 * s + lhi) ^ lx) << 4),
              pack2(blo(hr[s][0]) + acc[8 * s + 0], bhi(hr[s][0]) + acc[8 * s + 1]), pack2(blo(hr[s][1]) + acc[8 * s + 2], bhi(hr[s][1]) + acc[8 * s + 3]),
              pack2(blo(hr[s][2]) + acc[8 * s + 4], bhi(hr[s][2]) + acc[8 * s + 5]), pack2(blo(hr[s][3]) + acc[8 * s + 6], bhi(hr[s][3]) + acc[8 * s + 7]));
      __syncwarp();
#pragma unroll
      for (int i = 0; i < 4; i++) {
        const int row = wq * 16 + i * 4 + (lane >> 3);
        uint4 v;
        asm volatile("ld.shared.v4.b32 {%0,%1,%2,%3}, [%4];" : "=r"(v.x), "=r"(v.y), "=r"(v.z), "=r"(v.w)
                     : "r"(ob + row * 128 + ((lx ^ (row & 7)) << 4)) : "memory");
        asm volatile("st.global.v4.b32 [%0], {%1,%2,%3,%4};" ::"l"(out + (size_t)(rh * 64 + row) * 512 + hg * 64 + lx * 8),
                     "r"(v.x), "r"(v.y), "r"(v.z), "r"(v.w) : "memory");
      }
    }
    TSTAMP(16);
    asm volatile("barrier.cluster.arrive.relaxed.aligned;" ::: "memory");
    asm volatile("barrier.cluster.wait.aligned;" ::: "memory");
  } else {
    asm volatile("setmaxnreg.dec.sync.aligned.u32 24;");
    if (lane == 0) {
      if (warp == 8) {
#pragma unroll
        for (int k = 0; k < 9; k++) {
          const int s = k < 3 ? k : (k < 6 ? k + 3 : k - 3);
          const uint32_t bar = sb + SM_FULL + s * 8;
          mbar_init(bar, 1);
          mbar_expect_tx(bar, SLOT);
          if (s >= 3 && s < 6) tma2d(sb + s * SLOT, &maps.w, 512 + hg * 64, (s - 3) * 192, bar);
          else tma3d(sb + s * SLOT, &maps.x, 0, rb * 128 + (s >= 6 ? 64 : 0), 3 * (s % 3), bar);
        }
      } else if (warp == 9) {
        mbar_init(sb + SM_MISCB, 2);
        mbar_init(sb + SM_KVB, 32);
        mbar_expect_tx(sb + SM_MISCB, 2048);
        bulk_g2s(sb + SM_WPHI, wphi + hg * 1024, 2048, sb + SM_MISCB);
      } else if (warp == 10) {
#pragma unroll 1
        for (int i = 0; i < 16; i++) {
          mbar_init(sb + SM_XF + i * 8, 1);
          mbar_expect_tx(sb + SM_XF + i * 8, (i == 8 || i == 12) ? 20480 : 16384);
          if (i < 12) mbar_init(sb + SM_XE + i * 8, 4);
          if (i < 9) { mbar_init(sb + SM_DF + i * 8, 1); mbar_init(sb + SM_DE + i * 8, 4); }
        }
      } else {
        *reinterpret_cast<volatile unsigned*>(smem + SM_EPOCH) = atomicAdd(&g_start, 1u) / NCTA;
      }
      asm volatile("fence.mbarrier_init.release.cluster;" ::: "memory");
    }
    if (tid == 256) TS2(0, 18);
    __syncwarp();
    if (warp != 11) bar_sync(0, 352);
    asm volatile("barrier.cluster.arrive.relaxed.aligned;" ::: "memory");
    if (warp == 8) {
      asm volatile("barrier.cluster.wait.aligned;" ::: "memory");
      if (lane == 0) {
        const CUtensorMap* mg = jf == 7 ? &maps.g7 : &maps.g;
        const CUtensorMap* mu = jf == 7 ? &maps.u7 : &maps.u;
        asm volatile("prefetch.tensormap [%0];" ::"l"(&maps.wo) : "memory");
        asm volatile("prefetch.tensormap [%0];" ::"l"(mg) : "memory");
        asm volatile("prefetch.tensormap [%0];" ::"l"(mu) : "memory");
        asm volatile("prefetch.tensormap [%0];" ::"l"(&maps.d) : "memory");
        asm volatile("prefetch.tensormap [%0];" ::"l"(&maps.d48) : "memory");
#pragma unroll 1
        for (int s = ST_WV; s < ST_XC; s++) {
          if (s == ST_SCR1) continue;
          mbar_wait(sb + SM_EMPTY + (s - 9) * 8);
          const uint32_t dst = sb + (s >= 18 ? s - 18 : s - 9) * SLOT, bar = sb + SM_FULL + s * 8;
          if (s < ST_WO) tma2d(dst, &maps.w, (s < ST_WQ ? 1024 : 0) + hg * 64, (s < ST_WQ ? s - ST_WV : s - ST_WQ) * 192, bar);
          else { mbar_wait(bar - 8); tma2d(dst, &maps.wo, hg * 64, (s - ST_WO) * 192, bar); }
        }
        const int jc = jf == 7 ? 0 : jf;
        int slot = (ST_GU + 1 - rank) % NSLOT;
#pragma unroll 1
        for (int s = ST_GU + 1 - rank; s < NSTAGE; s += 2) {
          mbar_wait(sb + SM_EMPTY + (s - 9) * 8);
          if (s > ST_GU && s < ST_GU + THR) mbar_wait(sb + SM_FULL + (s - 1) * 8);
          const uint32_t dst = sb + slot * SLOT, bar = sb + SM_FULL + s * 8;
#pragma unroll 1
          for (int i = 0; i < 3; i++) {
            const int u = (s - ST_GU) * 3 + i;
            tma3d_mc(dst + i * 8192, mg, (u >> 4) * 64, jc, (u & 15) * 32, bar);
            tma3d_mc(dst + i * 8192 + 4096, mu, (u >> 4) * 64, jc, (u & 15) * 32, bar);
          }
          slot += 2; if (slot >= NSLOT) slot -= NSLOT;
        }
        slot = ST_D % NSLOT;
#pragma unroll 1
        for (int i = 0; i < 24; i++) {
          if (i < 9) mbar_wait(sb + SM_EMPTY + (ST_D - 9 + i) * 8);
          else mbar_wait_p(sb + SM_DE + slot * 8, i >= 18);
          const uint32_t bar = sb + SM_DF + slot * 8;
          mbar_expect_tx(bar, i < 16 ? 3 * 8192 : 3 * 6144);
          tma2d(sb + slot * SLOT + 16384, i < 16 ? &maps.d : &maps.d48, hg * 64, (i & 7) * 176 + (i >> 3) * 64, bar);
          if (++slot == NSLOT) slot = 0;
        }
      }
      __syncwarp();
    } else {
      asm volatile("barrier.cluster.wait.aligned;" ::: "memory");
      if (warp == 11) {
#pragma unroll
        for (int i = 0; i < 4; i++)
          reinterpret_cast<uint4*>(smem + SM_ONES)[lane + 32 * i] = make_uint4(0x3F803F80u, 0x3F803F80u, 0x3F803F80u, 0x3F803F80u);
        fence_async_smem();
        __syncwarp();
        if (lane == 0) mbar_arrive(sb + SM_MISCB);
      }
      mbar_wait(sb + SM_MISCB);
      const unsigned epoch = *reinterpret_cast<volatile unsigned*>(smem + SM_EPOCH);
      const uint32_t T = (epoch & 1) ^ 1;
      if (warp == 11) {
        reinterpret_cast<float4*>(&g_kv[T][blockIdx.x * 128])[lane] = make_float4(0.f, 0.f, 0.f, 0.f);
        if (lane < 8) g_z[T][blockIdx.x * 8 + lane] = 0.f;
        mbar_wait(sb + SM_FULL + (ST_WK + 2) * 8);
        if (lane == 0) {
          asm volatile("cp.async.bulk.prefetch.L2.global [%0], 4096;" ::"l"((const char*)wo + blockIdx.x * 4096) : "memory");
          asm volatile("cp.async.bulk.prefetch.L2.global [%0], 11008;" ::"l"((const char*)wg_ + blockIdx.x * 11008) : "memory");
          asm volatile("cp.async.bulk.prefetch.L2.global [%0], 11008;" ::"l"((const char*)wu_ + blockIdx.x * 11008) : "memory");
          asm volatile("cp.async.bulk.prefetch.L2.global [%0], 11008;" ::"l"((const char*)wd_ + blockIdx.x * 11008) : "memory");
          const unsigned target = (epoch + 1) * 32;
          unsigned v; int it = 0;
#pragma unroll 1
          do {
            asm volatile("ld.acquire.gpu.global.u32 %0, [%1];" : "=r"(v) : "l"(&g_kvcnt[hg * 32]) : "memory");
            if (++it > (1 << 18)) break;
          } while ((int)(v - target) < 0);
          TS2(0, 26);
        }
        __syncwarp();
        {
          const char* src = reinterpret_cast<const char*>(&g_kv[T ^ 1][hg * 2048]) + lane * 16;
#pragma unroll 4
          for (int i = 0; i < 16; i++)
            asm volatile("cp.async.cg.shared.global [%0], [%1], 16;" ::"r"(sb + SM_KV32 + lane * 16 + i * 512), "l"(src + i * 512) : "memory");
          asm volatile("cp.async.cg.shared.global [%0], [%1], 16;" ::"r"(sb + SM_ONES + lane * 16), "l"(&g_z[T ^ 1][hg * 128 + lane * 4]) : "memory");
          asm volatile("cp.async.mbarrier.arrive.noinc.shared::cta.b64 [%0];" ::"r"(sb + SM_KVB) : "memory");
        }
      } else {
        const int w = warp - 9;
        st_rlx4(reinterpret_cast<uint4*>(&g_st[2 * rb + w][hg][0]) + lane, T ^ 1, T ^ 1, T ^ 1, T ^ 1);
        if (lane < 8) st_rlx4(&g_o[2 * rb + w][hg][lane >> 1][3][30 + (lane & 1)], T ^ 1, T ^ 1, T ^ 1, T ^ 1);
        if (lane < 24) st_rlx4(&g_hh[2 * rb3 + w][lane >> 3][jf][2][(lane >> 1) & 3][30 + (lane & 1)], T ^ 1, T ^ 1, T ^ 1, T ^ 1);
        bar_sync(6 + w, 160);
        if (lane == 0) {
          asm volatile("fence.acq_rel.gpu;" ::: "memory");
          TS2(w, 25);
          asm volatile("red.relaxed.gpu.global.add.u32 [%0], 1;" ::"l"(&g_kvcnt[hg * 32]) : "memory");
        }
        mbar_wait(sb + SM_KVB);
        if (w == 0) { mbar_wait(sb + SM_EMPTY + 11 * 8); mbar_wait(sb + SM_EMPTY + 12 * 8); mbar_wait(sb + SM_EMPTY + 13 * 8); }
#pragma unroll 1
        for (int ph = 0; ph < 2; ph++) {
          const int use = 2 * ph + w, r = ph ? 2 * rb3 + w : 2 * rb + w;
          const uint32_t* pw = ph ? reinterpret_cast<const uint32_t*>(&g_st[r][lane >> 2][(lane & 3) * 16 + 15])
                                  : reinterpret_cast<const uint32_t*>(&g_o[r][lane >> 2][lane & 3][3][31]);
          const char* src = reinterpret_cast<const char*>(ph ? &g_h[r][0][0][0][0] : &g_o[r][0][0][0][0]);
          uint32_t ready = 0; int it = 0;
#pragma unroll 1
          for (int p = 0; p < 4; p++) {
            const uint32_t need = ph ? 0xFFFFFFFFu : 0xFFu << (8 * p);
#pragma unroll 1
            while ((ready & need) != need) {
              ready = __ballot_sync(0xffffffffu, ((ld_rlx1(pw) ^ T) & 1) == 0);
              if (++it > (1 << 18)) break;
            }
            if (lane == 0) {
              if (p == 0) TS2(w, 27 + ph);
              if (use > 0) mbar_wait(sb + SM_XE + ((use - 1) * 4 + p) * 8);
              const uint32_t bar = sb + SM_XF + (use * 4 + p) * 8;
              if (ph && p == 0) bulk_g2s(sb + SM_KV32 + w * 4096, &g_st[r][0][0], 4096, bar);
              bulk_g2s(sb + 2 * SLOT + p * 16384, src + p * 16384, 16384, bar);
            }
            __syncwarp();
          }
        }
        if (w == (int)rank) {
          uint32_t ready = 0; int it = 0, slot = ST_D % NSLOT;
#pragma unroll 1
          for (int i = 0; i < 24; i++) {
            if (i < 9) mbar_wait(sb + SM_EMPTY + (ST_D - 9 + i) * 8);
            else mbar_wait_p(sb + SM_DE + slot * 8, i >= 18);
            if ((i & 7) == 0) ready = 0;
            const uint32_t* pw = reinterpret_cast<const uint32_t*>(&g_hh[2 * rb + w][i >> 3][lane >> 2][2][lane & 3][31]);
#pragma unroll 1
            while (((ready >> (4 * (i & 7))) & 15) != 15) {
              ready = __ballot_sync(0xffffffffu, ((ld_rlx1(pw) ^ T) & 1) == 0);
              if (++it > (1 << 18)) break;
            }
            if (lane == 0) {
              asm volatile("cp.async.bulk.shared::cluster.global.mbarrier::complete_tx::bytes.multicast::cluster [%0], [%1], %2, [%3], %4;"
                           ::"r"(sb + slot * SLOT + w * 8192), "l"(&g_hh[2 * rb + w][i >> 3][i & 7][0][0][0]), "r"(i < 16 ? 8192 : 6144),
                             "r"(sb + SM_DF + slot * 8), "h"((uint16_t)3) : "memory");
            }
            __syncwarp();
            if (++slot == NSLOT) slot = 0;
          }
        }
      }
    }
    asm volatile("barrier.cluster.arrive.relaxed.aligned;" ::: "memory");
    asm volatile("barrier.cluster.wait.aligned;" ::: "memory");
  }
}

typedef CUresult (*EncodeFn)(CUtensorMap*, CUtensorMapDataType, cuuint32_t, void*, const cuuint64_t*, const cuuint64_t*,
                             const cuuint32_t*, const cuuint32_t*, CUtensorMapInterleave, CUtensorMapSwizzle,
                             CUtensorMapL2promotion, CUtensorMapFloatOOBfill);

void encode(EncodeFn fn, CUtensorMap* m, const void* base, int rank, const cuuint64_t* dims, const cuuint64_t* strides,
            const cuuint32_t* box) {
  cuuint32_t es[3] = {1, 1, 1};
  fn(m, CU_TENSOR_MAP_DATA_TYPE_BFLOAT16, (cuuint32_t)rank, const_cast<void*>(base), dims, strides, box, es,
     CU_TENSOR_MAP_INTERLEAVE_NONE, CU_TENSOR_MAP_SWIZZLE_128B, CU_TENSOR_MAP_L2_PROMOTION_L2_256B,
     CU_TENSOR_MAP_FLOAT_OOB_FILL_NONE);
}

}

extern "C" void kernel_launch(void* const* d_in, const int* in_sizes, int n_in, void* d_out, int out_size) {
  (void)in_sizes; (void)n_in; (void)out_size;
  const __nv_bfloat16* x    = (const __nv_bfloat16*)d_in[0];
  const __nv_bfloat16* wqkv = (const __nv_bfloat16*)d_in[1];
  const __nv_bfloat16* wphi = (const __nv_bfloat16*)d_in[2];
  const __nv_bfloat16* wo   = (const __nv_bfloat16*)d_in[3];
  const __nv_bfloat16* wg   = (const __nv_bfloat16*)d_in[5];
  const __nv_bfloat16* wu   = (const __nv_bfloat16*)d_in[6];
  const __nv_bfloat16* wd   = (const __nv_bfloat16*)d_in[7];

  static EncodeFn fn = nullptr;
  static int reserved = 0;
  if (!fn) {
    void* p = nullptr;
    cudaDriverEntryPointQueryResult qr;
    cudaGetDriverEntryPoint("cuTensorMapEncodeTiled", &p, cudaEnableDefault, &qr);
    fn = (EncodeFn)p;
    cudaFuncSetAttribute(fused_kernel<1024>, cudaFuncAttributeMaxDynamicSharedMemorySize, SM_TOTAL);
    cudaFuncSetAttribute(fused_kernel<0>, cudaFuncAttributeMaxDynamicSharedMemorySize, SM_TOTAL);
    int dev = 0;
    cudaGetDevice(&dev);
    cudaDeviceGetAttribute(&reserved, cudaDevAttrReservedSharedMemoryPerBlock, dev);
  }
  Maps maps;
  {
    cuuint64_t d[3] = {64, 2048, 8}, s[2] = {1024, 128}; cuuint32_t b[3] = {64, 64, 3};
    encode(fn, &maps.x, x, 3, d, s, b);
  }
  {
    cuuint64_t d[2] = {1536, 512}, s[1] = {3072}; cuuint32_t b[2] = {64, 192};
    encode(fn, &maps.w, wqkv, 2, d, s, b);
  }
  {
    cuuint64_t d[2] = {512, 512}, s[1] = {1024}; cuuint32_t b[2] = {64, 192};
    encode(fn, &maps.wo, wo, 2, d, s, b);
  }
  {
    cuuint64_t d[3] = {176, 7, 512}, d7[3] = {144, 1, 512}, s[2] = {352, 2752}; cuuint32_t b[3] = {64, 1, 32};
    encode(fn, &maps.g, wg, 3, d, s, b);
    encode(fn, &maps.u, wu, 3, d, s, b);
    encode(fn, &maps.g7, wg + 1232, 3, d7, s, b);
    encode(fn, &maps.u7, wu + 1232, 3, d7, s, b);
  }
  {
    cuuint64_t d[2] = {512, 1376}, s[1] = {1024}; cuuint32_t b[2] = {64, 64}, b2[2] = {64, 48};
    encode(fn, &maps.d, wd, 2, d, s, b);
    encode(fn, &maps.d48, wd, 2, d, s, b2);
  }
  if (reserved == 1024) fused_kernel<1024><<<NCTA, 384, SM_TOTAL>>>(maps, x, wphi, wo, wg, wu, wd, (__nv_bfloat16*)d_out);
  else fused_kernel<0><<<NCTA, 384, SM_TOTAL>>>(maps, x, wphi, wo, wg, wu, wd, (__nv_bfloat16*)d_out);
}
```

```cpp
#include <cuda_runtime.h>
#include <cuda_bf16.h>
#include <cuda.h>
#include <stdint.h>

#define PROF 0

#define SAFE_WAIT 0
#define THR 6

namespace {

constexpr int NCTA   = 128;
constexpr int SLOT   = 24576;
constexpr int NSLOT  = 9;
constexpr int NSTAGE = 39;

constexpr int ST_X0   = 0;
constexpr int ST_WK   = 3;
constexpr int ST_X1   = 6;
constexpr int ST_SCR0 = 9;
constexpr int ST_WV   = 10;
constexpr int ST_SCR1 = 13;
constexpr int ST_WQ   = 14;
constexpr int ST_WO   = 17;
constexpr int ST_XC   = 20;
constexpr int ST_GU   = 23;
constexpr int ST_D    = 39;

__host__ __device__ constexpr int st_empty_cnt(int d) {
  return ((d < 3 || (d >= 6 && d < 9) || (d >= ST_XC && d < ST_GU)) ? 4 : 2) * (d + 9 >= ST_GU ? 2 : 1);
}

constexpr int SM_ONES = NSLOT * SLOT;
constexpr int SM_WPHI = SM_ONES + 2048;
constexpr int SM_KVS  = SM_WPHI + 2048;
constexpr int SM_KV32 = 4 * SLOT + 16384;
constexpr int SM_BAR  = SM_KVS + 6144;
constexpr int SM_FULL  = SM_BAR;
constexpr int SM_EMPTY = SM_BAR + NSTAGE * 8;
constexpr int SM_MISCB = SM_BAR + 2 * NSTAGE * 8;
constexpr int SM_KVB   = SM_MISCB + 8;
constexpr int SM_EPOCH = SM_KVB + 8;
constexpr int SM_XF    = SM_EPOCH + 8;
constexpr int SM_XE    = SM_XF + 16 * 8;
constexpr int SM_DF    = SM_XE + 12 * 8;
constexpr int SM_DE    = SM_DF + 9 * 8;
constexpr int SM_TOTAL = SM_BAR + 1024;

static_assert(SM_TOTAL == 232448 && SM_DE + 9 * 8 <= SM_TOTAL, "smem budget");

struct Maps { CUtensorMap x, w, wo, g, u, g7, u7, d, d48; };

__device__ uint4    g_o[32][8][4][4][32];
__device__ uint4    g_h[32][8][4][4][32];
__device__ uint32_t g_hx[32][8][4][32];
__device__ uint2    g_st[32][8][64];
__device__ uint4    g_hh[32][2 * 4096 + 3072];
__device__ float    g_kv[2][32 * 32 * 16];
__device__ float    g_z[2][32 * 32];
__device__ unsigned g_kvcnt[8 * 32];
__device__ unsigned g_start;

__device__ __forceinline__ uint32_t smem_u32(const void* p) { return (uint32_t)__cvta_generic_to_shared(p); }
__device__ __forceinline__ void mbar_init(uint32_t bar, int cnt) {
  asm volatile("mbarrier.init.shared::cta.b64 [%0], %1;" ::"r"(bar), "r"(cnt) : "memory");
}
__device__ __forceinline__ void mbar_expect_tx(uint32_t bar, uint32_t bytes) {
  asm volatile("mbarrier.arrive.expect_tx.shared::cta.b64 _, [%0], %1;" ::"r"(bar), "r"(bytes) : "memory");
}
__device__ __forceinline__ void mbar_arrive(uint32_t bar) {
  asm volatile("mbarrier.arrive.shared::cta.b64 _, [%0];" ::"r"(bar) : "memory");
}
__device__ __forceinline__ void mbar_arrive_cluster(uint32_t bar, uint32_t rank) {
  asm volatile("{\n.reg .b32 ra;\nmapa.shared::cluster.u32 ra, %0, %1;\n"
               "mbarrier.arrive.shared::cluster.b64 _, [ra];\n}" ::"r"(bar), "r"(rank) : "memory");
}
__device__ __forceinline__ void mbar_wait_p(uint32_t bar, uint32_t parity) {
  asm volatile("{\n.reg .pred p;\nW: mbarrier.try_wait.parity.shared::cta.b64 p, [%0], %1;\n@!p bra W;\n}" ::"r"(bar), "r"(parity) : "memory");
}
__device__ __forceinline__ void mbar_wait(uint32_t bar) { mbar_wait_p(bar, 0); }
__device__ __forceinline__ void bar_sync(int id, int n)   { asm volatile("bar.sync %0, %1;" ::"r"(id), "r"(n) : "memory"); }
__device__ __forceinline__ void bar_arrive(int id, int n) { asm volatile("bar.arrive %0, %1;" ::"r"(id), "r"(n) : "memory"); }
__device__ __forceinline__ void fence_async_smem() { asm volatile("fence.proxy.async.shared::cta;" ::: "memory"); }
__device__ __forceinline__ void wg_fence()  { asm volatile("wgmma.fence.sync.aligned;" ::: "memory"); }
__device__ __forceinline__ void wg_commit() { asm volatile("wgmma.commit_group.sync.aligned;" ::: "memory"); }
template <int N> __device__ __forceinline__ void wg_wait() { asm volatile("wgmma.wait_group.sync.aligned %0;" ::"n"(N) : "memory"); }
#define DESC(off) (db + ((uint32_t)(off) >> 4))
__device__ __forceinline__ void tma2d(uint32_t dst, const CUtensorMap* m, int c0, int c1, uint32_t bar) {
  asm volatile("cp.async.bulk.tensor.2d.shared::cluster.global.mbarrier::complete_tx::bytes [%0], [%1, {%3, %4}], [%2];"
               ::"r"(dst), "l"(m), "r"(bar), "r"(c0), "r"(c1) : "memory");
}
__device__ __forceinline__ void tma3d(uint32_t dst, const CUtensorMap* m, int c0, int c1, int c2, uint32_t bar) {
  asm volatile("cp.async.bulk.tensor.3d.shared::cluster.global.mbarrier::complete_tx::bytes [%0], [%1, {%3, %4, %5}], [%2];"
               ::"r"(dst), "l"(m), "r"(bar), "r"(c0), "r"(c1), "r"(c2) : "memory");
}
__device__ __forceinline__ void tma3d_mc(uint32_t dst, const CUtensorMap* m, int c0, int c1, int c2, uint32_t bar) {
  asm volatile("cp.async.bulk.tensor.3d.shared::cluster.global.mbarrier::complete_tx::bytes.multicast::cluster [%0], [%1, {%3, %4, %5}], [%2], %6;"
               ::"r"(dst), "l"(m), "r"(bar), "r"(c0), "r"(c1), "r"(c2), "h"((uint16_t)3) : "memory");
}
__device__ __forceinline__ void ldsm4(uint32_t (&r)[4], uint32_t addr) {
  asm volatile("ldmatrix.sync.aligned.m8n8.x4.shared.b16 {%0,%1,%2,%3}, [%4];"
               : "=r"(r[0]), "=r"(r[1]), "=r"(r[2]), "=r"(r[3]) : "r"(addr) : "memory");
}
__device__ __forceinline__ void ldsm4t(uint32_t (&r)[4], uint32_t addr) {
  asm volatile("ldmatrix.sync.aligned.m8n8.x4.trans.shared.b16 {%0,%1,%2,%3}, [%4];"
               : "=r"(r[0]), "=r"(r[1]), "=r"(r[2]), "=r"(r[3]) : "r"(addr) : "memory");
}
__device__ __forceinline__ void stsm4(uint32_t addr, uint32_t r0, uint32_t r1, uint32_t r2, uint32_t r3) {
  asm volatile("stmatrix.sync.aligned.m8n8.x4.shared.b16 [%0], {%1,%2,%3,%4};"
               ::"r"(addr), "r"(r0), "r"(r1), "r"(r2), "r"(r3) : "memory");
}
__device__ __forceinline__ void mma16816(float (&c)[4], const uint32_t (&a)[4], uint32_t b0, uint32_t b1) {
  asm volatile("mma.sync.aligned.m16n8k16.row.col.f32.bf16.bf16.f32 {%0,%1,%2,%3},{%4,%5,%6,%7},{%8,%9},{%0,%1,%2,%3};"
               : "+f"(c[0]), "+f"(c[1]), "+f"(c[2]), "+f"(c[3])
               : "r"(a[0]), "r"(a[1]), "r"(a[2]), "r"(a[3]), "r"(b0), "r"(b1));
}
__device__ __forceinline__ uint32_t pack2(float lo, float hi) {
  uint32_t r; asm("cvt.rn.bf16x2.f32 %0, %1, %2;" : "=r"(r) : "f"(hi), "f"(lo)); return r;
}
__device__ __forceinline__ float blo(uint32_t w) { return __uint_as_float(w << 16); }
__device__ __forceinline__ float bhi(uint32_t w) { return __uint_as_float(w & 0xFFFF0000u); }
__device__ __forceinline__ uint32_t hsub2(uint32_t a, uint32_t b) { uint32_t r; asm("sub.rn.bf16x2 %0, %1, %2;" : "=r"(r) : "r"(a), "r"(b)); return r; }
__device__ __forceinline__ uint32_t hmax2(uint32_t a, uint32_t b) { uint32_t r; asm("max.bf16x2 %0, %1, %2;" : "=r"(r) : "r"(a), "r"(b)); return r; }
__device__ __forceinline__ uint32_t hmin2(uint32_t a, uint32_t b) { uint32_t r; asm("min.bf16x2 %0, %1, %2;" : "=r"(r) : "r"(a), "r"(b)); return r; }
__device__ __forceinline__ float ex2(float x) { float r; asm("ex2.approx.ftz.f32 %0, %1;" : "=f"(r) : "f"(x)); return r; }
__device__ __forceinline__ float rcp(float x) { float r; asm("rcp.approx.ftz.f32 %0, %1;" : "=f"(r) : "f"(x)); return r; }
__device__ __forceinline__ void ld_rlx4(uint32_t (&r)[4], const uint4* p) {
  asm volatile("{\n.reg .b128 v;\nld.relaxed.gpu.global.b128 v, [%4];\nmov.b128 {%0,%1,%2,%3}, v;\n}"
               : "=r"(r[0]), "=r"(r[1]), "=r"(r[2]), "=r"(r[3]) : "l"(p) : "memory");
}
__device__ __forceinline__ void st_rlx4(uint4* p, uint32_t a, uint32_t b, uint32_t c, uint32_t d) {
  asm volatile("{\n.reg .b128 v;\nmov.b128 v, {%1,%2,%3,%4};\nst.relaxed.gpu.global.b128 [%0], v;\n}"
               ::"l"(p), "r"(a), "r"(b), "r"(c), "r"(d) : "memory");
}
__device__ __forceinline__ void st_rlx2(uint2* p, uint32_t a, uint32_t b) {
  asm volatile("{\n.reg .b64 v;\nmov.b64 v, {%1,%2};\nst.relaxed.gpu.global.b64 [%0], v;\n}" ::"l"(p), "r"(a), "r"(b) : "memory");
}
__device__ __forceinline__ uint32_t ld_rlx1(const uint32_t* p) {
  uint32_t r; asm volatile("ld.relaxed.gpu.global.b32 %0, [%1];" : "=r"(r) : "l"(p) : "memory"); return r;
}
__device__ __forceinline__ void st_rlx1(uint32_t* p, uint32_t a) {
  asm volatile("st.relaxed.gpu.global.b32 [%0], %1;" ::"l"(p), "r"(a) : "memory");
}
__device__ __forceinline__ void ld_rlx2(uint32_t& a, uint32_t& b, const uint2* p) {
  asm volatile("{\n.reg .b64 v;\nld.relaxed.gpu.global.b64 v, [%2];\nmov.b64 {%0,%1}, v;\n}" : "=r"(a), "=r"(b) : "l"(p) : "memory");
}
__device__ __forceinline__ void bulk_g2s(uint32_t dst, const void* src, uint32_t bytes, uint32_t bar) {
  asm volatile("cp.async.bulk.shared::cluster.global.mbarrier::complete_tx::bytes [%0], [%1], %2, [%3];"
               ::"r"(dst), "l"(src), "r"(bytes), "r"(bar) : "memory");
}
__device__ __forceinline__ uint32_t tg(uint32_t w, uint32_t T) { return (w & 0xFFFFFFFEu) | T; }
__device__ __forceinline__ uint32_t bad4(uint32_t a, uint32_t b, uint32_t c, uint32_t d, uint32_t T) {
  uint32_t u, v;
  asm("lop3.b32 %0, %1, %2, %3, 0x7E;" : "=r"(u) : "r"(a), "r"(b), "r"(T));
  asm("lop3.b32 %0, %1, %2, %3, 0x7E;" : "=r"(v) : "r"(c), "r"(d), "r"(T));
  asm("lop3.b32 %0, %1, %2, 1, 0xA8;" : "=r"(u) : "r"(u), "r"(v));
  return u;
}

__device__ __forceinline__ void ld_chunk(uint32_t (&a)[4][4], const uint4* p) {
#pragma unroll
  for (int s = 0; s < 4; s++) ld_rlx4(a[s], p + s * 32);
}
__device__ __forceinline__ void lds_chunk(uint32_t (&a)[4][4], uint32_t addr) {
#pragma unroll
  for (int s = 0; s < 4; s++)
    asm volatile("ld.shared.v4.b32 {%0,%1,%2,%3}, [%4];" : "=r"(a[s][0]), "=r"(a[s][1]), "=r"(a[s][2]), "=r"(a[s][3])
                 : "r"(addr + s * 512) : "memory");
}
__device__ __forceinline__ void chk_pair(uint32_t (&a)[4][4], uint32_t (&b)[4][4], const uint4* p, uint32_t T) {
  int it = 0;
#pragma unroll 1
  while (__any_sync(0xffffffffu, bad4(a[0][0], a[1][0], a[2][0], a[3][0], T) | bad4(b[0][0], b[1][0], b[2][0], b[3][0], T))) {
    ld_chunk(a, p); ld_chunk(b, p + 512);
    if (++it > (1 << 18)) break;
  }
}

__device__ __forceinline__ void wgmma_rs_n48(float (&d)[24], const uint32_t (&a)[4], uint32_t descB, int scaleD) {
  asm volatile("{\n.reg .pred p;\n.reg .b64 db;\nsetp.ne.b32 p, %29, 0;\nmov.b64 db, {%28, 0x40000040};\n"
    "wgmma.mma_async.sync.aligned.m64n48k16.f32.bf16.bf16 {%0,%1,%2,%3,%4,%5,%6,%7,%8,%9,%10,%11,%12,%13,%14,%15,%16,%17,%18,%19,%20,%21,%22,%23}, {%24,%25,%26,%27}, db, p, 1, 1, 1;\n}\n"
    : "+f"(d[0]),"+f"(d[1]),"+f"(d[2]),"+f"(d[3]),"+f"(d[4]),"+f"(d[5]),"+f"(d[6]),"+f"(d[7]),"+f"(d[8]),"+f"(d[9]),"+f"(d[10]),"+f"(d[11]),"+f"(d[12]),"+f"(d[13]),"+f"(d[14]),"+f"(d[15]),"+f"(d[16]),"+f"(d[17]),"+f"(d[18]),"+f"(d[19]),"+f"(d[20]),"+f"(d[21]),"+f"(d[22]),"+f"(d[23])
    : "r"(a[0]), "r"(a[1]), "r"(a[2]), "r"(a[3]), "r"(descB), "r"(scaleD));
}
__device__ __forceinline__ void wgmma_rs_n64(float (&d)[32], const uint32_t (&a)[4], uint32_t descB, int scaleD) {
  asm volatile("{\n.reg .pred p;\n.reg .b64 db;\nsetp.ne.b32 p, %37, 0;\nmov.b64 db, {%36, 0x40000040};\n"
    "wgmma.mma_async.sync.aligned.m64n64k16.f32.bf16.bf16 {%0,%1,%2,%3,%4,%5,%6,%7,%8,%9,%10,%11,%12,%13,%14,%15,%16,%17,%18,%19,%20,%21,%22,%23,%24,%25,%26,%27,%28,%29,%30,%31}, {%32,%33,%34,%35}, db, p, 1, 1, 1;\n}\n"
    : "+f"(d[0]),"+f"(d[1]),"+f"(d[2]),"+f"(d[3]),"+f"(d[4]),"+f"(d[5]),"+f"(d[6]),"+f"(d[7]),"+f"(d[8]),"+f"(d[9]),"+f"(d[10]),"+f"(d[11]),"+f"(d[12]),"+f"(d[13]),"+f"(d[14]),"+f"(d[15]),"+f"(d[16]),"+f"(d[17]),"+f"(d[18]),"+f"(d[19]),"+f"(d[20]),"+f"(d[21]),"+f"(d[22]),"+f"(d[23]),"+f"(d[24]),"+f"(d[25]),"+f"(d[26]),"+f"(d[27]),"+f"(d[28]),"+f"(d[29]),"+f"(d[30]),"+f"(d[31])
    : "r"(a[0]), "r"(a[1]), "r"(a[2]), "r"(a[3]), "r"(descB), "r"(scaleD));
}
__device__ __forceinline__ void wgmma_rs_n128(float (&d)[64], const uint32_t (&a)[4], uint32_t descB, int scaleD) {
  asm volatile("{\n.reg .pred p;\n.reg .b64 db;\nsetp.ne.b32 p, %69, 0;\nmov.b64 db, {%68, 0x40000040};\n"
    "wgmma.mma_async.sync.aligned.m64n128k16.f32.bf16.bf16 {%0,%1,%2,%3,%4,%5,%6,%7,%8,%9,%10,%11,%12,%13,%14,%15,%16,%17,%18,%19,%20,%21,%22,%23,%24,%25,%26,%27,%28,%29,%30,%31,%32,%33,%34,%35,%36,%37,%38,%39,%40,%41,%42,%43,%44,%45,%46,%47,%48,%49,%50,%51,%52,%53,%54,%55,%56,%57,%58,%59,%60,%61,%62,%63}, {%64,%65,%66,%67}, db, p, 1, 1, 1;\n}\n"
    : "+f"(d[0]),"+f"(d[1]),"+f"(d[2]),"+f"(d[3]),"+f"(d[4]),"+f"(d[5]),"+f"(d[6]),"+f"(d[7]),"+f"(d[8]),"+f"(d[9]),"+f"(d[10]),"+f"(d[11]),"+f"(d[12]),"+f"(d[13]),"+f"(d[14]),"+f"(d[15]),"+f"(d[16]),"+f"(d[17]),"+f"(d[18]),"+f"(d[19]),"+f"(d[20]),"+f"(d[21]),"+f"(d[22]),"+f"(d[23]),"+f"(d[24]),"+f"(d[25]),"+f"(d[26]),"+f"(d[27]),"+f"(d[28]),"+f"(d[29]),"+f"(d[30]),"+f"(d[31]),"+f"(d[32]),"+f"(d[33]),"+f"(d[34]),"+f"(d[35]),"+f"(d[36]),"+f"(d[37]),"+f"(d[38]),"+f"(d[39]),"+f"(d[40]),"+f"(d[41]),"+f"(d[42]),"+f"(d[43]),"+f"(d[44]),"+f"(d[45]),"+f"(d[46]),"+f"(d[47]),"+f"(d[48]),"+f"(d[49]),"+f"(d[50]),"+f"(d[51]),"+f"(d[52]),"+f"(d[53]),"+f"(d[54]),"+f"(d[55]),"+f"(d[56]),"+f"(d[57]),"+f"(d[58]),"+f"(d[59]),"+f"(d[60]),"+f"(d[61]),"+f"(d[62]),"+f"(d[63])
    : "r"(a[0]), "r"(a[1]), "r"(a[2]), "r"(a[3]), "r"(descB), "r"(scaleD));
}
__device__ __forceinline__ void wgmma_ss_n72_t11(float (&d)[36], uint32_t descA, uint32_t descB, int scaleD) {
  asm volatile("{\n.reg .pred p;\n.reg .b64 da, db;\nsetp.ne.b32 p, %38, 0;\nmov.b64 da, {%36, 0x40000040};\nmov.b64 db, {%37, 0x40000040};\n"
    "wgmma.mma_async.sync.aligned.m64n72k16.f32.bf16.bf16 {%0,%1,%2,%3,%4,%5,%6,%7,%8,%9,%10,%11,%12,%13,%14,%15,%16,%17,%18,%19,%20,%21,%22,%23,%24,%25,%26,%27,%28,%29,%30,%31,%32,%33,%34,%35}, da, db, p, 1, 1, 1, 1;\n}\n"
    : "+f"(d[0]),"+f"(d[1]),"+f"(d[2]),"+f"(d[3]),"+f"(d[4]),"+f"(d[5]),"+f"(d[6]),"+f"(d[7]),"+f"(d[8]),"+f"(d[9]),"+f"(d[10]),"+f"(d[11]),"+f"(d[12]),"+f"(d[13]),"+f"(d[14]),"+f"(d[15]),"+f"(d[16]),"+f"(d[17]),"+f"(d[18]),"+f"(d[19]),"+f"(d[20]),"+f"(d[21]),"+f"(d[22]),"+f"(d[23]),"+f"(d[24]),"+f"(d[25]),"+f"(d[26]),"+f"(d[27]),"+f"(d[28]),"+f"(d[29]),"+f"(d[30]),"+f"(d[31]),"+f"(d[32]),"+f"(d[33]),"+f"(d[34]),"+f"(d[35])
    : "r"(descA), "r"(descB), "r"(scaleD));
}

#define TSTAMP(i) do {} while (0)
#define TS2(w, i) do {} while (0)

constexpr float LOG2E = 1.4426950408889634f;

__device__ __forceinline__ void feat_exp(const uint32_t (&P)[4], float (&e)[16]) {
  uint32_t a = hmax2(P[0], P[2]), b = hmax2(P[1], P[3]);
  uint32_t mx = hmax2(__byte_perm(a, b, 0x5410), __byte_perm(a, b, 0x7632));
  a = hmin2(P[0], P[2]); b = hmin2(P[1], P[3]);
  uint32_t mn = hmin2(__byte_perm(a, b, 0x5410), __byte_perm(a, b, 0x7632));
  mx = hmax2(mx, __shfl_xor_sync(0xffffffffu, mx, 1));
  mn = hmin2(mn, __shfl_xor_sync(0xffffffffu, mn, 1));
  mx = hmax2(mx, __shfl_xor_sync(0xffffffffu, mx, 2));
  mn = hmin2(mn, __shfl_xor_sync(0xffffffffu, mn, 2));
  float mx0 = -blo(mx) * LOG2E, mx1 = -bhi(mx) * LOG2E, mn0 = blo(mn) * LOG2E, mn1 = bhi(mn) * LOG2E;
  float v[8] = {blo(P[0]), bhi(P[0]), blo(P[1]), bhi(P[1]), blo(P[2]), bhi(P[2]), blo(P[3]), bhi(P[3])};
#pragma unroll
  for (int i = 0; i < 8; i++) {
    bool r1 = (i >> 1) & 1;
    e[i]     = ex2(fmaf(v[i],  LOG2E, r1 ? mx1 : mx0));
    e[8 + i] = ex2(fmaf(v[i], -LOG2E, r1 ? mn1 : mn0));
  }
}

template <int SBASE>
__global__ void __cluster_dims__(2, 1, 1) __launch_bounds__(384, 1)
fused_kernel(const __grid_constant__ Maps maps, const __nv_bfloat16* __restrict__ x, const __nv_bfloat16* __restrict__ wphi,
             const __nv_bfloat16* __restrict__ wo, const __nv_bfloat16* __restrict__ wg_, const __nv_bfloat16* __restrict__ wu_,
             const __nv_bfloat16* __restrict__ wd_, __nv_bfloat16* __restrict__ out) {
  extern __shared__ __align__(1024) unsigned char smem[];
  const uint32_t sb = smem_u32(smem);
  const int tid = threadIdx.x, lane = tid & 31;
  const int warp = __shfl_sync(0xffffffffu, tid >> 5, 0);
  const uint32_t rank = blockIdx.x & 1;
  const int cl = blockIdx.x >> 1;
  int quad, qi;
  if (cl < 4) { quad = 15; qi = cl; }
  else if (cl < 36) { quad = (cl - 4) & 7; qi = (cl - 4) >> 3; }
  else { qi = (cl - 36) / 7; quad = 8 + (cl - 36) - 7 * qi; }
  const int rb = quad, hg = 2 * qi + rank;
  const int rb3 = (quad & ~1) + rank, jf = 4 * (quad & 1) + qi;

  if (warp < 8) {
    asm volatile("setmaxnreg.inc.sync.aligned.u32 240;");
    if (lane == 0) {
#pragma unroll 1
      for (int d = warp; d < NSTAGE; d += 8) {
        mbar_init(sb + SM_EMPTY + d * 8, st_empty_cnt(d));
        if (d + 9 < NSTAGE) {
          mbar_init(sb + SM_FULL + (d + 9) * 8, 1);
          mbar_expect_tx(sb + SM_FULL + (d + 9) * 8, SLOT);
        }
      }
      asm volatile("fence.mbarrier_init.release.cluster;" ::: "memory");
    }
    __syncwarp();
    bar_sync(0, 352);
    asm volatile("barrier.cluster.arrive.relaxed.aligned;" ::: "memory");
    const int wg = warp >> 2, wq = warp & 3, g = lane >> 2, t = lane & 3;
    const bool lead = (tid & 127) == 0;
    const uint32_t db = ((SBASE ? (uint32_t)SBASE : (sb & 0x3FFFF)) >> 4) | (512u << 16);
    auto release = [&](int d) {
      const int s = d + NSLOT;
      mbar_arrive_cluster(sb + SM_EMPTY + d * 8, (s >= ST_GU && s < ST_D) ? (uint32_t)(s & 1) : rank);
      if (s >= ST_D) mbar_arrive_cluster(sb + SM_EMPTY + d * 8, rank ^ 1);
    };
    const uint32_t lrow = (uint32_t)(wq * 16 + (lane & 7) + ((lane >> 3) & 1) * 8) * 128;
    const uint32_t lx = lane & 7, lhi = lane >> 4;
    if (wg == 1) bar_arrive(4, 256);

    float r0, r1;
    uint32_t E[4][8];
    uint32_t T = 0;
    {
      uint32_t A[32][4];
      const int sx = wg ? ST_X1 : ST_X0;
      {
        const uint32_t base = sb + sx * SLOT + lrow;
        float cs[2][4], c0[2][4], c1[2][4];
#pragma unroll
        for (int i = 0; i < 4; i++) { cs[0][i] = cs[1][i] = c0[0][i] = c0[1][i] = c1[0][i] = c1[1][i] = 0.f; }
#pragma unroll
        for (int c = 0; c < 8; c++) {
          if (c % 3 == 0) mbar_wait(sb + SM_FULL + (sx + c / 3) * 8);
#pragma unroll
          for (int k = 0; k < 4; k++) ldsm4(A[4 * c + k], base + c * 8192 + (((2 * k + lhi) ^ lx) << 4));
#pragma unroll
          for (int k = 0; k < 4; k++) {
            const uint32_t (&f)[4] = A[4 * c + k];
            mma16816(cs[k & 1], f, 0x3F803F80u, 0x3F803F80u);
            mma16816(c0[k & 1], f, f[0], f[2]);
            mma16816(c1[k & 1], f, f[1], f[3]);
          }
        }
        const float s0 = (cs[0][0] + cs[1][0]) * (1.f / 512.f), s1 = (cs[0][2] + cs[1][2]) * (1.f / 512.f);
        asm volatile("barrier.cluster.wait.aligned;" ::: "memory");
        if (lane < 3) release(sx + lane);
        const uint32_t m0 = pack2(s0, s0), m1 = pack2(s1, s1);
        float q0 = (g & 1) ? c0[0][1] + c0[1][1] : c0[0][0] + c0[1][0];
        float q1 = (g & 1) ? c1[0][3] + c1[1][3] : c1[0][2] + c1[1][2];
        q0 = __shfl_sync(0xffffffffu, q0, (lane & ~3) | (g >> 1));
        q1 = __shfl_sync(0xffffffffu, q1, (lane & ~3) | (g >> 1));
        r0 = rsqrtf(fmaxf(q0 * (1.f / 512.f) - s0 * s0, 0.f) + 1e-5f);
        r1 = rsqrtf(fmaxf(q1 * (1.f / 512.f) - s1 * s1, 0.f) + 1e-5f);
#pragma unroll
        for (int ks = 0; ks < 32; ks++) {
          A[ks][0] = hsub2(A[ks][0], m0); A[ks][1] = hsub2(A[ks][1], m1);
          A[ks][2] = hsub2(A[ks][2], m0); A[ks][3] = hsub2(A[ks][3], m1);
        }
      }
      TSTAMP(1);
      const uint32_t wpa = sb + SM_WPHI + ((lane & 7) + ((lane >> 3) & 1) * 8) * 32 + lhi * 16;
      const uint32_t scr = sb + (wg ? (ST_SCR1 % NSLOT) : (ST_SCR0 % NSLOT)) * SLOT;
      mbar_wait(sb + SM_MISCB);
      T = (*reinterpret_cast<volatile unsigned*>(smem + SM_EPOCH) & 1) ^ 1;
#pragma unroll 1
      for (int ps = 0; ps < 3; ps++) {
        const int st0 = ps == 0 ? ST_WK : (ps == 1 ? ST_WV : ST_WQ);
        const uint32_t wdesc = DESC((ps == 0 ? ST_WK % NSLOT : (ps == 1 ? ST_WV % NSLOT : ST_WQ % NSLOT)) * SLOT);
        float acc[32];
        bar_sync(4 + wg, 256);
#pragma unroll
        for (int i = 0; i < 3; i++) {
          mbar_wait(sb + SM_FULL + (st0 + i) * 8);
          wg_fence();
#pragma unroll
          for (int kk = 0; kk < (i < 2 ? 12 : 8); kk++)
            wgmma_rs_n64(acc, A[12 * i + kk], wdesc + ((i * SLOT + kk * 2048) >> 4), (i | kk) != 0);
          wg_commit();
          if (i == 1) { wg_wait<1>(); if (lead) release(st0); }
        }
        if (ps == 0 || wg == 0) bar_arrive(4 + (wg ^ 1), 256);
        uint32_t a[4][4], b[4][4];
#pragma unroll
        for (int h = 0; h < 4; h++) ldsm4t(b[h], wpa + h * 512);
        wg_wait<0>();
        if ((tid & 127) < 2) release(st0 + 1 + (tid & 1));
        TSTAMP(2 + 2 * ps);
#pragma unroll
        for (int h = 0; h < 4; h++) {
          a[h][0] = pack2(acc[8 * h + 0] * r0, acc[8 * h + 1] * r0); a[h][1] = pack2(acc[8 * h + 2] * r1, acc[8 * h + 3] * r1);
          a[h][2] = pack2(acc[8 * h + 4] * r0, acc[8 * h + 5] * r0); a[h][3] = pack2(acc[8 * h + 6] * r1, acc[8 * h + 7] * r1);
        }
        if (ps != 1) {
          {
            float pp[4][2][4];
#pragma unroll
            for (int h = 0; h < 4; h++) {
#pragma unroll
              for (int i = 0; i < 4; i++) { pp[h][0][i] = 0.f; pp[h][1][i] = 0.f; }
              mma16816(pp[h][0], a[h], b[h][0], b[h][1]);
              mma16816(pp[h][1], a[h], b[h][2], b[h][3]);
            }
#pragma unroll
            for (int h = 0; h < 4; h++) {
              a[h][0] = pack2(pp[h][0][0], pp[h][0][1]); a[h][1] = pack2(pp[h][0][2], pp[h][0][3]);
              a[h][2] = pack2(pp[h][1][0], pp[h][1][1]); a[h][3] = pack2(pp[h][1][2], pp[h][1][3]);
            }
          }
          if (ps == 0) mbar_wait(sb + SM_EMPTY + (wg ? ST_SCR1 - NSLOT : ST_SCR0 - NSLOT) * 8);
#pragma unroll 1
          for (int hp = 0; hp < 2; hp++) {
            float e[2][16];
            feat_exp(a[0], e[0]);
            feat_exp(a[1], e[1]);
            if (ps == 0) {
#pragma unroll
              for (int h = 0; h < 2; h++) {
                const float (&f)[16] = e[h];
                float sp0 = (f[0] + f[1]) + (f[4] + f[5]), sp1 = (f[2] + f[3]) + (f[6] + f[7]);
                float sn0 = (f[8] + f[9]) + (f[12] + f[13]), sn1 = (f[10] + f[11]) + (f[14] + f[15]);
                sp0 += __shfl_xor_sync(0xffffffffu, sp0, 1); sp1 += __shfl_xor_sync(0xffffffffu, sp1, 1);
                sn0 += __shfl_xor_sync(0xffffffffu, sn0, 1); sn1 += __shfl_xor_sync(0xffffffffu, sn1, 1);
                sp0 += __shfl_xor_sync(0xffffffffu, sp0, 2); sp1 += __shfl_xor_sync(0xffffffffu, sp1, 2);
                sn0 += __shfl_xor_sync(0xffffffffu, sn0, 2); sn1 += __shfl_xor_sync(0xffffffffu, sn1, 2);
                sp0 = rcp(sp0); sp1 = rcp(sp1); sn0 = rcp(sn0); sn1 = rcp(sn1);
                const uint32_t dst = scr + hp * 8192 + lrow;
                stsm4(dst + (((h * 4 + lhi) ^ lx) << 4), pack2(f[0] * sp0, f[1] * sp0), pack2(f[2] * sp1, f[3] * sp1),
                      pack2(f[4] * sp0, f[5] * sp0), pack2(f[6] * sp1, f[7] * sp1));
                stsm4(dst + (((h * 4 + 2 + lhi) ^ lx) << 4), pack2(f[8] * sn0, f[9] * sn0), pack2(f[10] * sn1, f[11] * sn1),
                      pack2(f[12] * sn0, f[13] * sn0), pack2(f[14] * sn1, f[15] * sn1));
              }
            } else {
#pragma unroll
              for (int i = 0; i < 16; i++) {
                A[i >> 2][i & 3] = A[4 + (i >> 2)][i & 3];
                A[4 + (i >> 2)][i & 3] = pack2(e[i >> 3][2 * (i & 7)], e[i >> 3][2 * (i & 7) + 1]);
              }
            }
#pragma unroll
            for (int i = 0; i < 4; i++) { a[0][i] = a[2][i]; a[1][i] = a[3][i]; }
          }
        } else {
#pragma unroll
          for (int h = 0; h < 4; h++) stsm4(scr + 16384 + lrow + (((2 * h + lhi) ^ lx) << 4), a[h][0], a[h][1], a[h][2], a[h][3]);
          fence_async_smem();
          bar_sync(3, 256);
          float kv[36];
          wg_fence();
#pragma unroll
          for (int ks = 0; ks < 8; ks++) {
            const uint32_t sk = (ks < 4 ? (ST_SCR0 % NSLOT) : (ST_SCR1 % NSLOT)) * SLOT + (ks & 3) * 2048;
            const uint32_t dv = (DESC(sk + 16384) & 0xFFFFu) | (((SM_ONES - sk - 16384) >> 4) << 16);
            wgmma_ss_n72_t11(kv, DESC(sk) + wg * 512, dv, ks != 0);
          }
          wg_commit();
          if (wg == 1) bar_arrive(4, 256);
          wg_wait<0>();
          if (lead) { mbar_arrive(sb + SM_EMPTY + ST_SCR0 * 8); mbar_arrive(sb + SM_EMPTY + ST_SCR1 * 8); }
          const int hl = 2 * wg + (wq >> 1), f = (wq & 1) * 16 + g;
          float* kvp = &g_kv[T ^ 1][((hg * 4 + hl) * 32 + f) * 16 + 2 * t];
          float* zp = &g_z[T ^ 1][(hg * 4 + hl) * 32 + f];
          float c[8];
#pragma unroll
          for (int i = 0; i < 8; i++) c[i] = hl >= 2 ? (hl == 3 ? kv[24 + i] : kv[16 + i]) : (hl == 1 ? kv[8 + i] : kv[i]);
#pragma unroll
          for (int n = 0; n < 2; n++) {
            asm volatile("red.relaxed.gpu.global.add.v2.f32 [%0], {%1,%2};" ::"l"(kvp + n * 8), "f"(c[4 * n]), "f"(c[4 * n + 1]) : "memory");
            asm volatile("red.relaxed.gpu.global.add.v2.f32 [%0], {%1,%2};" ::"l"(kvp + n * 8 + 128), "f"(c[4 * n + 2]), "f"(c[4 * n + 3]) : "memory");
          }
          if (t < 2) asm volatile("red.relaxed.gpu.global.add.f32 [%0], %1;" ::"l"(zp + t * 8), "f"(t ? kv[34] : kv[32]) : "memory");
          bar_arrive(6 + wg, 160);
        }
        TSTAMP(3 + 2 * ps);
      }
#pragma unroll
      for (int i = 0; i < 32; i++) E[i >> 3][i & 7] = A[i >> 2][i & 3];
    }
    const int rh = 2 * rb + wg;
    const uint32_t xb = sb + 2 * SLOT + wq * 2048 + lane * 16;
    mbar_wait(sb + SM_KVB);
    {
      const int r = tid & 127;
      const float4* src = reinterpret_cast<const float4*>(smem + SM_KV32) + r;
#pragma unroll
      for (int i = 0; i < 4; i++) {
        const float4 a = src[i * 128];
        *reinterpret_cast<uint2*>(smem + SM_KVS + (i * 32 + (r >> 2)) * 48 + (r & 3) * 8) = make_uint2(pack2(a.x, a.y), pack2(a.z, a.w));
      }
      const uint32_t zz = pack2(reinterpret_cast<const float*>(smem + SM_ONES)[r], 1.0f);
      *reinterpret_cast<uint4*>(smem + SM_KVS + r * 48 + 32) = make_uint4(zz, zz, zz, zz);
      bar_sync(1 + wg, 128);
    }
    TSTAMP(8);
    {
      uint4* op = &g_o[rh][hg][wq][0][lane];
#pragma unroll
      for (int h = 0; h < 4; h++) {
        uint32_t b0[4], b1[4], b2[4];
        const uint32_t kb = sb + SM_KVS + (h * 32 + lane) * 48;
        ldsm4t(b0, kb); ldsm4t(b1, kb + 16); ldsm4t(b2, kb + 32);
        const uint32_t ep[4] = {E[h][0], E[h][1], E[h][2], E[h][3]}, en[4] = {E[h][4], E[h][5], E[h][6], E[h][7]};
        float np0[4] = {0, 0, 0, 0}, np1[4] = {0, 0, 0, 0}, nn0[4] = {0, 0, 0, 0}, nn1[4] = {0, 0, 0, 0}, dp[4] = {0, 0, 0, 0}, dn[4] = {0, 0, 0, 0};
        mma16816(dp, ep, b2[0], b2[1]);  mma16816(dn, en, b2[2], b2[3]);
        mma16816(np0, ep, b0[0], b0[1]); mma16816(nn0, en, b0[2], b0[3]);
        mma16816(np1, ep, b1[0], b1[1]); mma16816(nn1, en, b1[2], b1[3]);
        const float i0 = rcp(fmaf(dp[0], dn[1], fmaf(dn[0], dp[1], 1e-6f * dp[1] * dn[1])));
        const float i1 = rcp(fmaf(dp[2], dn[3], fmaf(dn[2], dp[3], 1e-6f * dp[3] * dn[3])));
        const float cp0 = dn[1] * i0, cn0 = dp[1] * i0, cp1 = dn[3] * i1, cn1 = dp[3] * i1;
        st_rlx4(op + h * 32,
                tg(pack2(fmaf(np0[0], cp0, nn0[0] * cn0), fmaf(np0[1], cp0, nn0[1] * cn0)), T),
                pack2(fmaf(np0[2], cp1, nn0[2] * cn1), fmaf(np0[3], cp1, nn0[3] * cn1)),
                pack2(fmaf(np1[0], cp0, nn1[0] * cn0), fmaf(np1[1], cp0, nn1[1] * cn0)),
                pack2(fmaf(np1[2], cp1, nn1[2] * cn1), fmaf(np1[3], cp1, nn1[3] * cn1)));
      }
    }
    TSTAMP(9);

    {
      uint32_t xr[16];
      {
        const uint32_t* xp = reinterpret_cast<const uint32_t*>(x + (size_t)(rh * 64 + wq * 16 + g) * 512 + hg * 64 + 2 * t);
#pragma unroll
        for (int i = 0; i < 8; i++) { xr[2 * i] = __ldg(xp + 4 * i); xr[2 * i + 1] = __ldg(xp + 8 * 256 + 4 * i); }
      }
      uint32_t A[8][4][4];
      const uint4* op = &g_o[rh][0][wq][0][lane];
      float acc[32];
      mbar_wait(sb + SM_XF + (wg * 4) * 8);
      lds_chunk(A[0], xb); lds_chunk(A[1], xb + 8192);
#pragma unroll
      for (int p = 0; p < 4; p++) {
        chk_pair(A[2 * p], A[2 * p + 1], op + p * 1024, T);
        if (lane == 0) mbar_arrive(sb + SM_XE + (wg * 4 + p) * 8);
#pragma unroll
        for (int c = 2 * p; c < 2 * p + 2; c++) {
          if (c % 3 == 0) mbar_wait(sb + SM_FULL + (ST_WO + c / 3) * 8);
          if ((c & 1) && p < 3) {
            mbar_wait(sb + SM_XF + (wg * 4 + p + 1) * 8);
            lds_chunk(A[2 * p + 2], xb + (p + 1) * 16384); lds_chunk(A[2 * p + 3], xb + (p + 1) * 16384 + 8192);
          }
          wg_fence();
#pragma unroll
          for (int s = 0; s < 4; s++)
            wgmma_rs_n64(acc, A[c][s], DESC(((ST_WO + c / 3) % NSLOT) * SLOT + ((c % 3) * 4 + s) * 2048), (c | s) != 0);
          wg_commit();
        }
      }
      wg_wait<0>();
      if ((tid & 127) < 3) release(ST_WO + (tid & 127));
      TSTAMP(10);
      uint32_t hw[16];
      float s0 = 0.f, s1 = 0.f, q0 = 0.f, q1 = 0.f;
#pragma unroll
      for (int i = 0; i < 8; i++) {
        hw[2 * i]     = pack2(blo(xr[2 * i]) + acc[4 * i], bhi(xr[2 * i]) + acc[4 * i + 1]);
        hw[2 * i + 1] = pack2(blo(xr[2 * i + 1]) + acc[4 * i + 2], bhi(xr[2 * i + 1]) + acc[4 * i + 3]);
      }
      uint4* hp_ = &g_h[rh][hg][wq][0][lane];
#pragma unroll
      for (int s = 0; s < 4; s++) st_rlx4(hp_ + s * 32, tg(hw[4 * s], T), hw[4 * s + 1], hw[4 * s + 2], hw[4 * s + 3]);
#pragma unroll
      for (int i = 0; i < 8; i++) {
        float a = blo(hw[2 * i]), b = bhi(hw[2 * i]);
        s0 += a + b; q0 = fmaf(a, a, q0); q0 = fmaf(b, b, q0);
        a = blo(hw[2 * i + 1]); b = bhi(hw[2 * i + 1]);
        s1 += a + b; q1 = fmaf(a, a, q1); q1 = fmaf(b, b, q1);
      }
      s0 += __shfl_xor_sync(0xffffffffu, s0, 1); s1 += __shfl_xor_sync(0xffffffffu, s1, 1);
      q0 += __shfl_xor_sync(0xffffffffu, q0, 1); q1 += __shfl_xor_sync(0xffffffffu, q1, 1);
      s0 += __shfl_xor_sync(0xffffffffu, s0, 2); s1 += __shfl_xor_sync(0xffffffffu, s1, 2);
      q0 += __shfl_xor_sync(0xffffffffu, q0, 2); q1 += __shfl_xor_sync(0xffffffffu, q1, 2);
      if (t < 2) st_rlx2(&g_st[rh][hg][wq * 16 + g + t * 8], tg(__float_as_uint(t ? s1 : s0), T), __float_as_uint(t ? q1 : q0));
      uint32_t hx = T;
#pragma unroll
      for (int i = 0; i < 4; i++) hx |= (hw[4 * i] & 1u) << (i + 1);
      st_rlx1(&g_hx[rh][hg][wq][lane], hx);
    }
    TSTAMP(11);

    const int rh3 = 2 * rb3 + wg;
    {
      uint32_t A[8][4][4];
      const uint4* hp_ = &g_h[rh3][0][wq][0][lane];
      uint4* hhp = &g_hh[rh3][jf * 512 + wq * 32 + lane];
      const uint32_t dg = (db & 0xFFFFu) | (256u << 16);
      uint32_t m0, m1;
      mbar_wait(sb + SM_XF + ((2 + wg) * 4) * 8);
      lds_chunk(A[0], xb); lds_chunk(A[1], xb + 8192);
      {
        const uint2* sp = &g_st[rh3][2 * t][wq * 16 + g];
        const uint2* ss = reinterpret_cast<const uint2*>(smem + SM_KV32 + wg * 4096) + 2 * t * 64 + wq * 16 + g;
        uint2 a0 = ss[0], a1 = ss[64], b0 = ss[8], b1 = ss[72];
        int it = 0;
#pragma unroll 1
        while (__any_sync(0xffffffffu, bad4(a0.x, a1.x, b0.x, b1.x, T))) {
          ld_rlx2(a0.x, a0.y, sp); ld_rlx2(a1.x, a1.y, sp + 64); ld_rlx2(b0.x, b0.y, sp + 8); ld_rlx2(b1.x, b1.y, sp + 72);
          if (++it > (1 << 18)) break;
        }
        float s0 = __uint_as_float(a0.x) + __uint_as_float(a1.x), q0 = __uint_as_float(a0.y) + __uint_as_float(a1.y);
        float s1 = __uint_as_float(b0.x) + __uint_as_float(b1.x), q1 = __uint_as_float(b0.y) + __uint_as_float(b1.y);
        s0 += __shfl_xor_sync(0xffffffffu, s0, 1); s1 += __shfl_xor_sync(0xffffffffu, s1, 1);
        q0 += __shfl_xor_sync(0xffffffffu, q0, 1); q1 += __shfl_xor_sync(0xffffffffu, q1, 1);
        s0 += __shfl_xor_sync(0xffffffffu, s0, 2); s1 += __shfl_xor_sync(0xffffffffu, s1, 2);
        q0 += __shfl_xor_sync(0xffffffffu, q0, 2); q1 += __shfl_xor_sync(0xffffffffu, q1, 2);
        s0 *= (1.f / 512.f); s1 *= (1.f / 512.f);
        r0 = rcp(fmaxf(q0 * (1.f / 512.f) - s0 * s0, 0.f) + 1e-5f);
        r1 = rcp(fmaxf(q1 * (1.f / 512.f) - s1 * s1, 0.f) + 1e-5f);
        m0 = pack2(s0, s0); m1 = pack2(s1, s1);
      }
      TSTAMP(12);
#pragma unroll
      for (int p = 0; p < 4; p++) {
        if (p < 3) {
          mbar_wait(sb + SM_XF + ((2 + wg) * 4 + p + 1) * 8);
          lds_chunk(A[2 * p + 2], xb + (p + 1) * 16384); lds_chunk(A[2 * p + 3], xb + (p + 1) * 16384 + 8192);
        }
        chk_pair(A[2 * p], A[2 * p + 1], hp_ + p * 1024, T);
        if (lane == 0) {
          if (wg == 0) mbar_arrive(sb + SM_XE + (8 + p) * 8);
          else if (p > 0) release(ST_XC + p - 1);
        }
#pragma unroll
        for (int c = 2 * p; c < 2 * p + 2; c++)
#pragma unroll
          for (int s = 0; s < 4; s++) {
            A[c][s][0] = hsub2(A[c][s][0], m0); A[c][s][1] = hsub2(A[c][s][1], m1);
            A[c][s][2] = hsub2(A[c][s][2], m0); A[c][s][3] = hsub2(A[c][s][3], m1);
          }
      }
      TSTAMP(19);
#define UOFF(u) ((((ST_GU + (u) / 3) % NSLOT) * SLOT + ((u) % 3) * 8192) >> 4)
#define UNIT_PRE(u)  do { if ((u) % 3 == 0) mbar_wait(sb + SM_FULL + (ST_GU + (u) / 3) * 8); } while (0)
#define UNIT_POST(u) do { wg_commit(); if ((u) % 3 == 1 && (u) > 3) { wg_wait<2>(); if (lead) release(ST_GU + (u) / 3 - 1); } } while (0)
      float acc[64];
      const int rz = blockIdx.y;
#pragma unroll
      for (int ps = 0; ps < 2; ps++) {
        wg_fence();
#pragma unroll
        for (int k = 0; k < 16; k++) {
          const int u = 16 * ps + k, c = k >> 1;
          UNIT_PRE(u);
          wgmma_rs_n128(acc, A[c][(k & 1) * 2], dg + UOFF(u), k != 0 ? 1 : (ps ? rz : 0));
          wgmma_rs_n128(acc, A[c][(k & 1) * 2 + 1], dg + UOFF(u) + 128, 1);
          UNIT_POST(u);
        }
        wg_wait<0>();
#pragma unroll
        for (int k = 0; k < 4; k++) {
          const int s = k == 2 ? 3 : (k == 3 ? 2 : k);
          st_rlx4(hhp + ps * 4096 + s * 128,
                  tg(pack2(acc[8 * s + 0] * acc[32 + 8 * s + 0] * r0, acc[8 * s + 1] * acc[32 + 8 * s + 1] * r0), T),
                  pack2(acc[8 * s + 2] * acc[32 + 8 * s + 2] * r1, acc[8 * s + 3] * acc[32 + 8 * s + 3] * r1),
                  pack2(acc[8 * s + 4] * acc[32 + 8 * s + 4] * r0, acc[8 * s + 5] * acc[32 + 8 * s + 5] * r0),
                  pack2(acc[8 * s + 6] * acc[32 + 8 * s + 6] * r1, acc[8 * s + 7] * acc[32 + 8 * s + 7] * r1));
        }
      }
      {
        float ag[24], au[24];
        bar_sync(1 + wg, 128);
        wg_fence();
#pragma unroll
        for (int k = 0; k < 16; k++) {
          const int u = 32 + k, c = k >> 1;
          UNIT_PRE(u);
          wgmma_rs_n48(ag, A[c][(k & 1) * 2], dg + UOFF(u), k != 0);
          wgmma_rs_n48(au, A[c][(k & 1) * 2], dg + UOFF(u) + 256, k != 0);
          wgmma_rs_n48(ag, A[c][(k & 1) * 2 + 1], dg + UOFF(u) + 128, 1);
          wgmma_rs_n48(au, A[c][(k & 1) * 2 + 1], dg + UOFF(u) + 256 + 128, 1);
          UNIT_POST(u);
        }
        wg_wait<0>();
        if (lead) release(ST_D - 1);
        TSTAMP(13);
#pragma unroll
        for (int s = 0; s < 3; s++)
          st_rlx4(hhp + 2 * 4096 - jf * 128 + s * 128,
                  tg(pack2(ag[8 * s + 0] * au[8 * s + 0] * r0, ag[8 * s + 1] * au[8 * s + 1] * r0), T),
                  pack2(ag[8 * s + 2] * au[8 * s + 2] * r1, ag[8 * s + 3] * au[8 * s + 3] * r1),
                  pack2(ag[8 * s + 4] * au[8 * s + 4] * r0, ag[8 * s + 5] * au[8 * s + 5] * r0),
                  pack2(ag[8 * s + 6] * au[8 * s + 6] * r1, ag[8 * s + 7] * au[8 * s + 7] * r1));
      }
    }
    TSTAMP(14);

    {
      float acc[32];
      uint32_t F[2][8][4], hr[4][4];
      ld_chunk(hr, &g_h[rh][hg][wq][0][lane]);
      const uint32_t hx = ld_rlx1(&g_hx[rh][hg][wq][lane]);
      const uint4* gp = &g_hh[rh][wq * 32 + lane];
      const uint32_t fb = sb + wq * 512 + lane * 16;
      auto load = [&](uint32_t (&f)[8][4], int i, int s0, int s1) {
        mbar_wait_p(sb + SM_DF + s0 * 8, i >= 9 && i < 18);
        mbar_wait_p(sb + SM_DF + s1 * 8, i >= 8 && i < 17);
        const uint32_t fa = fb + (wg ? s1 : s0) * SLOT;
        const int o6 = i < 16 ? 6 : 0;
#pragma unroll
        for (int s = 0; s < 8; s++)
          asm volatile("ld.shared.v4.b32 {%0,%1,%2,%3}, [%4];" : "=r"(f[s][0]), "=r"(f[s][1]), "=r"(f[s][2]), "=r"(f[s][3])
                       : "r"(fa + (s < 6 ? s : o6 + s - 6) * 2048) : "memory");
        int it = 0;
#pragma unroll 1
        while (__any_sync(0xffffffffu, bad4(f[0][0], f[1][0], f[2][0], f[3][0], T) | bad4(f[4][0], f[5][0], f[6][0], f[7][0], T))) {
#pragma unroll
          for (int s = 0; s < 8; s++) ld_rlx4(f[s], gp + (i < 16 ? i * 512 : 2048 + i * 384) + (s < 6 ? s : o6 + s - 6) * 128);
          if (++it > (1 << 18)) break;
        }
      };
      int s0 = ST_D % NSLOT, s1 = s0 + 1, p0 = 0, p1 = 0;
      load(F[0], 0, s0, s1);
#pragma unroll 1
      for (int i2 = 0; i2 < 24; i2 += 4) {
#pragma unroll
        for (int b = 0; b < 2; b++) {
          const int i = i2 + 2 * b;
          const uint32_t d0 = db + s0 * (SLOT >> 4) + 1024, d1 = db + s1 * (SLOT >> 4) + 1024;
          wg_fence();
          const uint32_t d3 = i < 16 ? d0 + 384 : d1, d4 = i < 16 ? d1 : d1 + 128;
#pragma unroll
          for (int s = 0; s < 3; s++) wgmma_rs_n64(acc, F[b][s], d0 + s * 128, (i | s) != 0);
          wgmma_rs_n64(acc, F[b][3], d3, 1);
          wgmma_rs_n64(acc, F[b][4], d4, 1);
          wgmma_rs_n64(acc, F[b][5], d4 + 128, 1);
          if (i < 16) { wgmma_rs_n64(acc, F[b][6], d1 + 256, 1); wgmma_rs_n64(acc, F[b][7], d1 + 384, 1); }
          wg_commit();
          wg_wait<1>();
          if ((tid & 127) < 4 && i > 0 && i + ((tid >> 1) & 1) < 17) mbar_arrive_cluster(sb + SM_DE + ((tid & 2) ? p1 : p0) * 8, tid & 1);
          p0 = s0; p1 = s1;
          s0 = s1 + 1 == NSLOT ? 0 : s1 + 1;
          s1 = s0 + 1 == NSLOT ? 0 : s0 + 1;
          if (i < 22) load(F[b ^ 1], i + 2, s0, s1);
        }
      }
      wg_wait<0>();
      TSTAMP(15);
#pragma unroll
      for (int s = 0; s < 4; s++) hr[s][0] = (hr[s][0] & 0xFFFFFFFEu) | ((hx >> (s + 1)) & 1u);
      const uint32_t ob = sb + (wg ? (ST_D + 15) % NSLOT : (ST_D + 16) % NSLOT) * SLOT;
#pragma unroll
      for (int s = 0; s < 4; s++)
        stsm4(ob + lrow + (((2 * s + lhi) ^ lx) << 4),
              pack2(blo(hr[s][0]) + acc[8 * s + 0], bhi(hr[s][0]) + acc[8 * s + 1]), pack2(blo(hr[s][1]) + acc[8 * s + 2], bhi(hr[s][1]) + acc[8 * s + 3]),
              pack2(blo(hr[s][2]) + acc[8 * s + 4], bhi(hr[s][2]) + acc[8 * s + 5]), pack2(blo(hr[s][3]) + acc[8 * s + 6], bhi(hr[s][3]) + acc[8 * s + 7]));
      __syncwarp();
#pragma unroll
      for (int i = 0; i < 4; i++) {
        const int row = wq * 16 + i * 4 + (lane >> 3);
        uint4 v;
        asm volatile("ld.shared.v4.b32 {%0,%1,%2,%3}, [%4];" : "=r"(v.x), "=r"(v.y), "=r"(v.z), "=r"(v.w)
                     : "r"(ob + row * 128 + ((lx ^ (row & 7)) << 4)) : "memory");
        asm volatile("st.global.v4.b32 [%0], {%1,%2,%3,%4};" ::"l"(out + (size_t)(rh * 64 + row) * 512 + hg * 64 + lx * 8),
                     "r"(v.x), "r"(v.y), "r"(v.z), "r"(v.w) : "memory");
      }
    }
    TSTAMP(16);
    asm volatile("barrier.cluster.arrive.relaxed.aligned;" ::: "memory");
    asm volatile("barrier.cluster.wait.aligned;" ::: "memory");
  } else {
    asm volatile("setmaxnreg.dec.sync.aligned.u32 24;");
    if (lane == 0) {
      if (warp == 8) {
#pragma unroll
        for (int k = 0; k < 9; k++) {
          const int s = k < 3 ? k : (k < 6 ? k + 3 : k - 3);
          const uint32_t bar = sb + SM_FULL + s * 8;
          mbar_init(bar, 1);
          mbar_expect_tx(bar, SLOT);
          if (s >= 3 && s < 6) tma2d(sb + s * SLOT, &maps.w, 512 + hg * 64, (s - 3) * 192, bar);
          else tma3d(sb + s * SLOT, &maps.x, 0, rb * 128 + (s >= 6 ? 64 : 0), 3 * (s % 3), bar);
        }
      } else if (warp == 9) {
        mbar_init(sb + SM_MISCB, 2);
        mbar_init(sb + SM_KVB, 32);
        mbar_expect_tx(sb + SM_MISCB, 2048);
        bulk_g2s(sb + SM_WPHI, wphi + hg * 1024, 2048, sb + SM_MISCB);
      } else if (warp == 10) {
#pragma unroll 1
        for (int i = 0; i < 16; i++) {
          mbar_init(sb + SM_XF + i * 8, 1);
          mbar_expect_tx(sb + SM_XF + i * 8, (i == 8 || i == 12) ? 20480 : 16384);
          if (i < 12) mbar_init(sb + SM_XE + i * 8, 4);
          if (i < 9) { mbar_init(sb + SM_DF + i * 8, 1); mbar_init(sb + SM_DE + i * 8, 4); }
        }
      } else {
        *reinterpret_cast<volatile unsigned*>(smem + SM_EPOCH) = atomicAdd(&g_start, 1u) / NCTA;
      }
      asm volatile("fence.mbarrier_init.release.cluster;" ::: "memory");
    }
    __syncwarp();
    if (warp != 11) bar_sync(0, 352);
    asm volatile("barrier.cluster.arrive.relaxed.aligned;" ::: "memory");
    auto down_rows = [&](int i0) {
      int slot = (ST_D + i0) % NSLOT, row = i0 * 176;
#pragma unroll 1
      for (int i = i0; i < 24; i += 2) {
        if (i < 9) mbar_wait(sb + SM_EMPTY + (ST_D - 9 + i) * 8);
        else mbar_wait_p(sb + SM_DE + slot * 8, i >= 18);
        const uint32_t bar = sb + SM_DF + slot * 8;
        mbar_expect_tx(bar, i < 16 ? 3 * 8192 : 3 * 6144);
        tma2d(sb + slot * SLOT + 16384, i < 16 ? &maps.d : &maps.d48, hg * 64, row, bar);
        if (i == 0) TS2(0, 18); if (i == 4) TS2(0, 23); if (i == 8) TS2(0, 17); if (i == 12) TS2(0, 0);
        slot += 2; if (slot >= NSLOT) slot -= NSLOT;
        row += 352; if (row >= 1408) row -= 1408 - 64;
      }
    };
    if (warp == 8) {
      asm volatile("barrier.cluster.wait.aligned;" ::: "memory");
      if (lane == 0) {
        const CUtensorMap* mg = jf == 7 ? &maps.g7 : &maps.g;
        const CUtensorMap* mu = jf == 7 ? &maps.u7 : &maps.u;
        asm volatile("prefetch.tensormap [%0];" ::"l"(&maps.wo) : "memory");
        asm volatile("prefetch.tensormap [%0];" ::"l"(mg) : "memory");
        asm volatile("prefetch.tensormap [%0];" ::"l"(mu) : "memory");
        asm volatile("prefetch.tensormap [%0];" ::"l"(&maps.d) : "memory");
        asm volatile("prefetch.tensormap [%0];" ::"l"(&maps.d48) : "memory");
#pragma unroll 1
        for (int s = ST_WV; s < ST_XC; s++) {
          if (s == ST_SCR1) continue;
          mbar_wait(sb + SM_EMPTY + (s - 9) * 8);
          const uint32_t dst = sb + (s >= 18 ? s - 18 : s - 9) * SLOT, bar = sb + SM_FULL + s * 8;
          if (s < ST_WO) tma2d(dst, &maps.w, (s < ST_WQ ? 1024 : 0) + hg * 64, (s < ST_WQ ? s - ST_WV : s - ST_WQ) * 192, bar);
          else { mbar_wait(bar - 8); tma2d(dst, &maps.wo, hg * 64, (s - ST_WO) * 192, bar); }
        }
        const int jc = jf == 7 ? 0 : jf;
        int slot = (ST_GU + 1 - rank) % NSLOT;
#pragma unroll 1
        for (int s = ST_GU + 1 - rank; s < NSTAGE; s += 2) {
          mbar_wait(sb + SM_EMPTY + (s - 9) * 8);
          if (s > ST_GU && s < ST_GU + THR) mbar_wait(sb + SM_FULL + (s - 1) * 8);
          const uint32_t dst = sb + slot * SLOT, bar = sb + SM_FULL + s * 8;
#pragma unroll 1
          for (int i = 0; i < 3; i++) {
            const int u = (s - ST_GU) * 3 + i;
            tma3d_mc(dst + i * 8192, mg, (u >> 4) * 64, jc, (u & 15) * 32, bar);
            tma3d_mc(dst + i * 8192 + 4096, mu, (u >> 4) * 64, jc, (u & 15) * 32, bar);
          }
          slot += 2; if (slot >= NSLOT) slot -= NSLOT;
        }
        down_rows(0);
      }
      __syncwarp();
    } else {
      asm volatile("barrier.cluster.wait.aligned;" ::: "memory");
      if (warp == 11) {
#pragma unroll
        for (int i = 0; i < 4; i++)
          reinterpret_cast<uint4*>(smem + SM_ONES)[lane + 32 * i] = make_uint4(0x3F803F80u, 0x3F803F80u, 0x3F803F80u, 0x3F803F80u);
        fence_async_smem();
        __syncwarp();
        if (lane == 0) mbar_arrive(sb + SM_MISCB);
      }
      mbar_wait(sb + SM_MISCB);
      const unsigned epoch = *reinterpret_cast<volatile unsigned*>(smem + SM_EPOCH);
      const uint32_t T = (epoch & 1) ^ 1;
      if (warp == 11) {
        reinterpret_cast<float4*>(&g_kv[T][blockIdx.x * 128])[lane] = make_float4(0.f, 0.f, 0.f, 0.f);
        if (lane < 8) g_z[T][blockIdx.x * 8 + lane] = 0.f;
        mbar_wait(sb + SM_FULL + (ST_WK + 2) * 8);
        if (lane == 0) {
          asm volatile("cp.async.bulk.prefetch.L2.global [%0], 4096;" ::"l"((const char*)wo + blockIdx.x * 4096) : "memory");
          asm volatile("cp.async.bulk.prefetch.L2.global [%0], 11008;" ::"l"((const char*)wg_ + blockIdx.x * 11008) : "memory");
          asm volatile("cp.async.bulk.prefetch.L2.global [%0], 11008;" ::"l"((const char*)wu_ + blockIdx.x * 11008) : "memory");
          asm volatile("cp.async.bulk.prefetch.L2.global [%0], 11008;" ::"l"((const char*)wd_ + blockIdx.x * 11008) : "memory");
          const unsigned target = (epoch + 1) * 32;
          unsigned v; int it = 0;
#pragma unroll 1
          do {
            asm volatile("ld.acquire.gpu.global.u32 %0, [%1];" : "=r"(v) : "l"(&g_kvcnt[hg * 32]) : "memory");
            if (++it > (1 << 18)) break;
          } while ((int)(v - target) < 0);
          TS2(0, 26);
        }
        __syncwarp();
        {
          const char* src = reinterpret_cast<const char*>(&g_kv[T ^ 1][hg * 2048]) + lane * 16;
#pragma unroll 4
          for (int i = 0; i < 16; i++)
            asm volatile("cp.async.cg.shared.global [%0], [%1], 16;" ::"r"(sb + SM_KV32 + lane * 16 + i * 512), "l"(src + i * 512) : "memory");
          asm volatile("cp.async.cg.shared.global [%0], [%1], 16;" ::"r"(sb + SM_ONES + lane * 16), "l"(&g_z[T ^ 1][hg * 128 + lane * 4]) : "memory");
          asm volatile("cp.async.mbarrier.arrive.noinc.shared::cta.b64 [%0];" ::"r"(sb + SM_KVB) : "memory");
        }
        if (lane == 0) down_rows(1);
        __syncwarp();
      } else {
        const int w = warp - 9;
        st_rlx4(reinterpret_cast<uint4*>(&g_st[2 * rb + w][hg][0]) + lane, T ^ 1, T ^ 1, T ^ 1, T ^ 1);
        if (lane < 8) st_rlx4(&g_o[2 * rb + w][hg][lane >> 1][3][30 + (lane & 1)], T ^ 1, T ^ 1, T ^ 1, T ^ 1);
        if (lane < 24) st_rlx4(&g_hh[2 * rb3 + w][(lane >> 3) * 4096 + jf * (lane < 16 ? 512 : 384) + 256 + ((lane >> 1) & 3) * 32 + 30 + (lane & 1)], T ^ 1, T ^ 1, T ^ 1, T ^ 1);
        bar_sync(6 + w, 160);
        if (lane == 0) {
          asm volatile("fence.acq_rel.gpu;" ::: "memory");
          TS2(w, 25);
          asm volatile("red.relaxed.gpu.global.add.u32 [%0], 1;" ::"l"(&g_kvcnt[hg * 32]) : "memory");
        }
        mbar_wait(sb + SM_KVB);
        if (w == 0) { mbar_wait(sb + SM_EMPTY + 11 * 8); mbar_wait(sb + SM_EMPTY + 12 * 8); mbar_wait(sb + SM_EMPTY + 13 * 8); }
#pragma unroll 1
        for (int ph = 0; ph < 2; ph++) {
          const int use = 2 * ph + w, r = ph ? 2 * rb3 + w : 2 * rb + w;
          const uint32_t* pw = ph ? reinterpret_cast<const uint32_t*>(&g_st[r][lane >> 2][(lane & 3) * 16 + 15])
                                  : reinterpret_cast<const uint32_t*>(&g_o[r][lane >> 2][lane & 3][3][31]);
          const char* src = reinterpret_cast<const char*>(ph ? &g_h[r][0][0][0][0] : &g_o[r][0][0][0][0]);
          uint32_t ready = 0; int it = 0;
#pragma unroll 1
          for (int p = 0; p < 4; p++) {
            const uint32_t need = ph ? 0xFFFFFFFFu : 0xFFu << (8 * p);
#pragma unroll 1
            while ((ready & need) != need) {
              ready = __ballot_sync(0xffffffffu, ((ld_rlx1(pw) ^ T) & 1) == 0);
              if (++it > (1 << 18)) break;
            }
            if (lane == 0) {
              if (p == 0) TS2(w, 27 + ph);
              if (use > 0) mbar_wait(sb + SM_XE + ((use - 1) * 4 + p) * 8);
              const uint32_t bar = sb + SM_XF + (use * 4 + p) * 8;
              if (ph && p == 0) bulk_g2s(sb + SM_KV32 + w * 4096, &g_st[r][0][0], 4096, bar);
              bulk_g2s(sb + 2 * SLOT + p * 16384, src + p * 16384, 16384, bar);
            }
            __syncwarp();
          }
        }
        {
          const uint4* src = &g_hh[2 * rb + rank][0];
          uint32_t ready = 0; int it = 0, slot = (ST_D + 2 * w + rank) % NSLOT;
#pragma unroll 1
          for (int i = 2 * w + rank; i < 24; i += 4) {
            const int ps = i >> 3, cs = ps == 2 ? 384 : 512;
            if ((i & 4) == 0) ready = 0;
            if (i < 9) mbar_wait(sb + SM_EMPTY + (ST_D - 9 + i) * 8);
            else mbar_wait_p(sb + SM_DE + slot * 8, i >= 18);
            const uint32_t* pw = reinterpret_cast<const uint32_t*>(src + ps * 4096 + (lane >> 2) * cs + 256 + (lane & 3) * 32 + 31);
#pragma unroll 1
            while (((ready >> (4 * (i & 6))) & 255) != 255) {
              ready = __ballot_sync(0xffffffffu, ((ld_rlx1(pw) ^ T) & 1) == 0);
              if (++it > (1 << 18)) break;
            }
            if (lane == 0) {
              asm volatile("cp.async.bulk.shared::cluster.global.mbarrier::complete_tx::bytes.multicast::cluster [%0], [%1], %2, [%3], %4;"
                           ::"r"(sb + slot * SLOT), "l"(src + ps * 4096 + (i & 6) * cs), "r"(cs * 32),
                             "r"(sb + SM_DF + slot * 8), "h"((uint16_t)3) : "memory");
              if (i < 2) TS2(1, 18); if ((i & ~1) == 4) TS2(1, 23); if ((i & ~1) == 8) TS2(1, 17); if ((i & ~1) == 12) TS2(1, 0);
            }
            __syncwarp();
            slot += 4; if (slot >= NSLOT) slot -= NSLOT;
          }
        }
      }
    }
    asm volatile("barrier.cluster.arrive.relaxed.aligned;" ::: "memory");
    asm volatile("barrier.cluster.wait.aligned;" ::: "memory");
  }
}

typedef CUresult (*EncodeFn)(CUtensorMap*, CUtensorMapDataType, cuuint32_t, void*, const cuuint64_t*, const cuuint64_t*,
                             const cuuint32_t*, const cuuint32_t*, CUtensorMapInterleave, CUtensorMapSwizzle,
                             CUtensorMapL2promotion, CUtensorMapFloatOOBfill);

void encode(EncodeFn fn, CUtensorMap* m, const void* base, int rank, const cuuint64_t* dims, const cuuint64_t* strides,
            const cuuint32_t* box) {
  cuuint32_t es[3] = {1, 1, 1};
  fn(m, CU_TENSOR_MAP_DATA_TYPE_BFLOAT16, (cuuint32_t)rank, const_cast<void*>(base), dims, strides, box, es,
     CU_TENSOR_MAP_INTERLEAVE_NONE, CU_TENSOR_MAP_SWIZZLE_128B, CU_TENSOR_MAP_L2_PROMOTION_L2_256B,
     CU_TENSOR_MAP_FLOAT_OOB_FILL_NONE);
}

}

extern "C" void kernel_launch(void* const* d_in, const int* in_sizes, int n_in, void* d_out, int out_size) {
  (void)in_sizes; (void)n_in; (void)out_size;
  const __nv_bfloat16* x    = (const __nv_bfloat16*)d_in[0];
  const __nv_bfloat16* wqkv = (const __nv_bfloat16*)d_in[1];
  const __nv_bfloat16* wphi = (const __nv_bfloat16*)d_in[2];
  const __nv_bfloat16* wo   = (const __nv_bfloat16*)d_in[3];
  const __nv_bfloat16* wg   = (const __nv_bfloat16*)d_in[5];
  const __nv_bfloat16* wu   = (const __nv_bfloat16*)d_in[6];
  const __nv_bfloat16* wd   = (const __nv_bfloat16*)d_in[7];

  static EncodeFn fn = nullptr;
  static int reserved = 0;
  if (!fn) {
    void* p = nullptr;
    cudaDriverEntryPointQueryResult qr;
    cudaGetDriverEntryPoint("cuTensorMapEncodeTiled", &p, cudaEnableDefault, &qr);
    fn = (EncodeFn)p;
    cudaFuncSetAttribute(fused_kernel<1024>, cudaFuncAttributeMaxDynamicSharedMemorySize, SM_TOTAL);
    cudaFuncSetAttribute(fused_kernel<0>, cudaFuncAttributeMaxDynamicSharedMemorySize, SM_TOTAL);
    int dev = 0;
    cudaGetDevice(&dev);
    cudaDeviceGetAttribute(&reserved, cudaDevAttrReservedSharedMemoryPerBlock, dev);
  }
  Maps maps;
  {
    cuuint64_t d[3] = {64, 2048, 8}, s[2] = {1024, 128}; cuuint32_t b[3] = {64, 64, 3};
    encode(fn, &maps.x, x, 3, d, s, b);
  }
  {
    cuuint64_t d[2] = {1536, 512}, s[1] = {3072}; cuuint32_t b[2] = {64, 192};
    encode(fn, &maps.w, wqkv, 2, d, s, b);
  }
  {
    cuuint64_t d[2] = {512, 512}, s[1] = {1024}; cuuint32_t b[2] = {64, 192};
    encode(fn, &maps.wo, wo, 2, d, s, b);
  }
  {
    cuuint64_t d[3] = {176, 7, 512}, d7[3] = {144, 1, 512}, s[2] = {352, 2752}; cuuint32_t b[3] = {64, 1, 32};
    encode(fn, &maps.g, wg, 3, d, s, b);
    encode(fn, &maps.u, wu, 3, d, s, b);
    encode(fn, &maps.g7, wg + 1232, 3, d7, s, b);
    encode(fn, &maps.u7, wu + 1232, 3, d7, s, b);
  }
  {
    cuuint64_t d[2] = {512, 1376}, s[1] = {1024}; cuuint32_t b[2] = {64, 64}, b2[2] = {64, 48};
    encode(fn, &maps.d, wd, 2, d, s, b);
    encode(fn, &maps.d48, wd, 2, d, s, b2);
  }
  if (reserved == 1024) fused_kernel<1024><<<NCTA, 384, SM_TOTAL>>>(maps, x, wphi, wo, wg, wu, wd, (__nv_bfloat16*)d_out);
  else fused_kernel<0><<<NCTA, 384, SM_TOTAL>>>(maps, x, wphi, wo, wg, wu, wd, (__nv_bfloat16*)d_out);
}
```

```cpp
#include <cuda_runtime.h>
#include <cuda_bf16.h>
#include <cuda.h>
#include <stdint.h>

#define PROF 0

#define SAFE_WAIT 0
#define THR 6

namespace {

constexpr int NCTA   = 128;
constexpr int SLOT   = 24576;
constexpr int NSLOT  = 9;
constexpr int NSTAGE = 47;

constexpr int ST_X0   = 0;
constexpr int ST_WK   = 3;
constexpr int ST_X1   = 6;
constexpr int ST_SCR0 = 9;
constexpr int ST_WV   = 10;
constexpr int ST_SCR1 = 13;
constexpr int ST_WQ   = 14;
constexpr int ST_WO   = 17;
constexpr int ST_XC   = 20;
constexpr int ST_GU   = 23;
constexpr int ST_D    = 39;

__host__ __device__ constexpr int st_empty_cnt(int d) {
  return ((d < 3 || (d >= 6 && d < 9) || (d >= ST_XC && d < ST_GU)) ? 4 : 2) * (d + 9 >= ST_GU ? 2 : 1);
}

constexpr int SM_ONES = NSLOT * SLOT;
constexpr int SM_WPHI = SM_ONES + 2048;
constexpr int SM_KVS  = SM_WPHI + 2048;
constexpr int SM_KV32 = 4 * SLOT + 16384;
constexpr int SM_BAR  = SM_KVS + 6144;
constexpr int SM_FULL  = SM_BAR;
constexpr int SM_EMPTY = SM_BAR + NSTAGE * 8;
constexpr int SM_MISCB = SM_BAR + 2 * NSTAGE * 8;
constexpr int SM_KVB   = SM_MISCB + 8;
constexpr int SM_EPOCH = SM_KVB + 8;
constexpr int SM_XF    = SM_EPOCH + 8;
constexpr int SM_XE    = SM_XF + 16 * 8;
constexpr int SM_TOTAL = SM_BAR + 1024;

static_assert(SM_TOTAL == 232448 && SM_XE + 12 * 8 <= SM_TOTAL, "smem budget");

struct Maps { CUtensorMap x, w, wo, g, u, g7, u7, d; };

__device__ uint4    g_o[32][8][4][4][32];
__device__ uint4    g_h[32][8][4][4][32];
__device__ uint32_t g_hx[32][8][4][32];
__device__ uint2    g_st[32][8][64];
__device__ uint4    g_hh[32][8][11][4][32];
__device__ uint4    g_part[32][8][4][4][4][32];
__device__ float    g_kv[2][32 * 32 * 16];
__device__ float    g_z[2][32 * 32];
__device__ unsigned g_kvcnt[8 * 32];
__device__ unsigned g_start;

__device__ __forceinline__ uint32_t smem_u32(const void* p) { return (uint32_t)__cvta_generic_to_shared(p); }
__device__ __forceinline__ void mbar_init(uint32_t bar, int cnt) {
  asm volatile("mbarrier.init.shared::cta.b64 [%0], %1;" ::"r"(bar), "r"(cnt) : "memory");
}
__device__ __forceinline__ void mbar_expect_tx(uint32_t bar, uint32_t bytes) {
  asm volatile("mbarrier.arrive.expect_tx.shared::cta.b64 _, [%0], %1;" ::"r"(bar), "r"(bytes) : "memory");
}
__device__ __forceinline__ void mbar_arrive(uint32_t bar) {
  asm volatile("mbarrier.arrive.shared::cta.b64 _, [%0];" ::"r"(bar) : "memory");
}
__device__ __forceinline__ void mbar_arrive_cluster(uint32_t bar, uint32_t rank) {
  asm volatile("{\n.reg .b32 ra;\nmapa.shared::cluster.u32 ra, %0, %1;\n"
               "mbarrier.arrive.shared::cluster.b64 _, [ra];\n}" ::"r"(bar), "r"(rank) : "memory");
}
__device__ __forceinline__ void mbar_wait_p(uint32_t bar, uint32_t parity) {
  asm volatile("{\n.reg .pred p;\nW: mbarrier.try_wait.parity.shared::cta.b64 p, [%0], %1;\n@!p bra W;\n}" ::"r"(bar), "r"(parity) : "memory");
}
__device__ __forceinline__ void mbar_wait(uint32_t bar) { mbar_wait_p(bar, 0); }
__device__ __forceinline__ void bar_sync(int id, int n)   { asm volatile("bar.sync %0, %1;" ::"r"(id), "r"(n) : "memory"); }
__device__ __forceinline__ void bar_arrive(int id, int n) { asm volatile("bar.arrive %0, %1;" ::"r"(id), "r"(n) : "memory"); }
__device__ __forceinline__ void fence_async_smem() { asm volatile("fence.proxy.async.shared::cta;" ::: "memory"); }
__device__ __forceinline__ void wg_fence()  { asm volatile("wgmma.fence.sync.aligned;" ::: "memory"); }
__device__ __forceinline__ void wg_commit() { asm volatile("wgmma.commit_group.sync.aligned;" ::: "memory"); }
template <int N> __device__ __forceinline__ void wg_wait() { asm volatile("wgmma.wait_group.sync.aligned %0;" ::"n"(N) : "memory"); }
#define DESC(off) (db + ((uint32_t)(off) >> 4))
__device__ __forceinline__ void tma2d(uint32_t dst, const CUtensorMap* m, int c0, int c1, uint32_t bar) {
  asm volatile("cp.async.bulk.tensor.2d.shared::cluster.global.mbarrier::complete_tx::bytes [%0], [%1, {%3, %4}], [%2];"
               ::"r"(dst), "l"(m), "r"(bar), "r"(c0), "r"(c1) : "memory");
}
__device__ __forceinline__ void tma2d_mc(uint32_t dst, const CUtensorMap* m, int c0, int c1, uint32_t bar) {
  asm volatile("cp.async.bulk.tensor.2d.shared::cluster.global.mbarrier::complete_tx::bytes.multicast::cluster [%0], [%1, {%3, %4}], [%2], %5;"
               ::"r"(dst), "l"(m), "r"(bar), "r"(c0), "r"(c1), "h"((uint16_t)3) : "memory");
}
__device__ __forceinline__ void tma3d(uint32_t dst, const CUtensorMap* m, int c0, int c1, int c2, uint32_t bar) {
  asm volatile("cp.async.bulk.tensor.3d.shared::cluster.global.mbarrier::complete_tx::bytes [%0], [%1, {%3, %4, %5}], [%2];"
               ::"r"(dst), "l"(m), "r"(bar), "r"(c0), "r"(c1), "r"(c2) : "memory");
}
__device__ __forceinline__ void tma3d_mc(uint32_t dst, const CUtensorMap* m, int c0, int c1, int c2, uint32_t bar) {
  asm volatile("cp.async.bulk.tensor.3d.shared::cluster.global.mbarrier::complete_tx::bytes.multicast::cluster [%0], [%1, {%3, %4, %5}], [%2], %6;"
               ::"r"(dst), "l"(m), "r"(bar), "r"(c0), "r"(c1), "r"(c2), "h"((uint16_t)3) : "memory");
}
__device__ __forceinline__ void ldsm4(uint32_t (&r)[4], uint32_t addr) {
  asm volatile("ldmatrix.sync.aligned.m8n8.x4.shared.b16 {%0,%1,%2,%3}, [%4];"
               : "=r"(r[0]), "=r"(r[1]), "=r"(r[2]), "=r"(r[3]) : "r"(addr) : "memory");
}
__device__ __forceinline__ void ldsm4t(uint32_t (&r)[4], uint32_t addr) {
  asm volatile("ldmatrix.sync.aligned.m8n8.x4.trans.shared.b16 {%0,%1,%2,%3}, [%4];"
               : "=r"(r[0]), "=r"(r[1]), "=r"(r[2]), "=r"(r[3]) : "r"(addr) : "memory");
}
__device__ __forceinline__ void stsm4(uint32_t addr, uint32_t r0, uint32_t r1, uint32_t r2, uint32_t r3) {
  asm volatile("stmatrix.sync.aligned.m8n8.x4.shared.b16 [%0], {%1,%2,%3,%4};"
               ::"r"(addr), "r"(r0), "r"(r1), "r"(r2), "r"(r3) : "memory");
}
__device__ __forceinline__ void mma16816(float (&c)[4], const uint32_t (&a)[4], uint32_t b0, uint32_t b1) {
  asm volatile("mma.sync.aligned.m16n8k16.row.col.f32.bf16.bf16.f32 {%0,%1,%2,%3},{%4,%5,%6,%7},{%8,%9},{%0,%1,%2,%3};"
               : "+f"(c[0]), "+f"(c[1]), "+f"(c[2]), "+f"(c[3])
               : "r"(a[0]), "r"(a[1]), "r"(a[2]), "r"(a[3]), "r"(b0), "r"(b1));
}
__device__ __forceinline__ uint32_t pack2(float lo, float hi) {
  uint32_t r; asm("cvt.rn.bf16x2.f32 %0, %1, %2;" : "=r"(r) : "f"(hi), "f"(lo)); return r;
}
__device__ __forceinline__ float blo(uint32_t w) { return __uint_as_float(w << 16); }
__device__ __forceinline__ float bhi(uint32_t w) { return __uint_as_float(w & 0xFFFF0000u); }
__device__ __forceinline__ uint32_t hsub2(uint32_t a, uint32_t b) { uint32_t r; asm("sub.rn.bf16x2 %0, %1, %2;" : "=r"(r) : "r"(a), "r"(b)); return r; }
__device__ __forceinline__ uint32_t hmax2(uint32_t a, uint32_t b) { uint32_t r; asm("max.bf16x2 %0, %1, %2;" : "=r"(r) : "r"(a), "r"(b)); return r; }
__device__ __forceinline__ uint32_t hmin2(uint32_t a, uint32_t b) { uint32_t r; asm("min.bf16x2 %0, %1, %2;" : "=r"(r) : "r"(a), "r"(b)); return r; }
__device__ __forceinline__ float ex2(float x) { float r; asm("ex2.approx.ftz.f32 %0, %1;" : "=f"(r) : "f"(x)); return r; }
__device__ __forceinline__ float rcp(float x) { float r; asm("rcp.approx.ftz.f32 %0, %1;" : "=f"(r) : "f"(x)); return r; }
__device__ __forceinline__ void ld_rlx4(uint32_t (&r)[4], const uint4* p) {
  asm volatile("{\n.reg .b128 v;\nld.relaxed.gpu.global.b128 v, [%4];\nmov.b128 {%0,%1,%2,%3}, v;\n}"
               : "=r"(r[0]), "=r"(r[1]), "=r"(r[2]), "=r"(r[3]) : "l"(p) : "memory");
}
__device__ __forceinline__ void st_rlx4(uint4* p, uint32_t a, uint32_t b, uint32_t c, uint32_t d) {
  asm volatile("{\n.reg .b128 v;\nmov.b128 v, {%1,%2,%3,%4};\nst.relaxed.gpu.global.b128 [%0], v;\n}"
               ::"l"(p), "r"(a), "r"(b), "r"(c), "r"(d) : "memory");
}
__device__ __forceinline__ void st_rlx2(uint2* p, uint32_t a, uint32_t b) {
  asm volatile("{\n.reg .b64 v;\nmov.b64 v, {%1,%2};\nst.relaxed.gpu.global.b64 [%0], v;\n}" ::"l"(p), "r"(a), "r"(b) : "memory");
}
__device__ __forceinline__ uint32_t ld_rlx1(const uint32_t* p) {
  uint32_t r; asm volatile("ld.relaxed.gpu.global.b32 %0, [%1];" : "=r"(r) : "l"(p) : "memory"); return r;
}
__device__ __forceinline__ void st_rlx1(uint32_t* p, uint32_t a) {
  asm volatile("st.relaxed.gpu.global.b32 [%0], %1;" ::"l"(p), "r"(a) : "memory");
}
__device__ __forceinline__ void ld_rlx2(uint32_t& a, uint32_t& b, const uint2* p) {
  asm volatile("{\n.reg .b64 v;\nld.relaxed.gpu.global.b64 v, [%2];\nmov.b64 {%0,%1}, v;\n}" : "=r"(a), "=r"(b) : "l"(p) : "memory");
}
__device__ __forceinline__ void bulk_g2s(uint32_t dst, const void* src, uint32_t bytes, uint32_t bar) {
  asm volatile("cp.async.bulk.shared::cluster.global.mbarrier::complete_tx::bytes [%0], [%1], %2, [%3];"
               ::"r"(dst), "l"(src), "r"(bytes), "r"(bar) : "memory");
}
__device__ __forceinline__ uint32_t tg(uint32_t w, uint32_t T) { return (w & 0xFFFFFFFEu) | T; }
__device__ __forceinline__ uint32_t bad4(uint32_t a, uint32_t b, uint32_t c, uint32_t d, uint32_t T) {
  uint32_t u, v;
  asm("lop3.b32 %0, %1, %2, %3, 0x7E;" : "=r"(u) : "r"(a), "r"(b), "r"(T));
  asm("lop3.b32 %0, %1, %2, %3, 0x7E;" : "=r"(v) : "r"(c), "r"(d), "r"(T));
  asm("lop3.b32 %0, %1, %2, 1, 0xA8;" : "=r"(u) : "r"(u), "r"(v));
  return u;
}

__device__ __forceinline__ void ld_chunk(uint32_t (&a)[4][4], const uint4* p) {
#pragma unroll
  for (int s = 0; s < 4; s++) ld_rlx4(a[s], p + s * 32);
}
__device__ __forceinline__ void lds_chunk(uint32_t (&a)[4][4], uint32_t addr) {
#pragma unroll
  for (int s = 0; s < 4; s++)
    asm volatile("ld.shared.v4.b32 {%0,%1,%2,%3}, [%4];" : "=r"(a[s][0]), "=r"(a[s][1]), "=r"(a[s][2]), "=r"(a[s][3])
                 : "r"(addr + s * 512) : "memory");
}
__device__ __forceinline__ void chk_pair(uint32_t (&a)[4][4], uint32_t (&b)[4][4], const uint4* p, uint32_t T) {
  int it = 0;
#pragma unroll 1
  while (__any_sync(0xffffffffu, bad4(a[0][0], a[1][0], a[2][0], a[3][0], T) | bad4(b[0][0], b[1][0], b[2][0], b[3][0], T))) {
    ld_chunk(a, p); ld_chunk(b, p + 512);
    if (++it > (1 << 18)) break;
  }
}

__device__ __forceinline__ void wgmma_rs_n48(float (&d)[24], const uint32_t (&a)[4], uint32_t descB, int scaleD) {
  asm volatile("{\n.reg .pred p;\n.reg .b64 db;\nsetp.ne.b32 p, %29, 0;\nmov.b64 db, {%28, 0x40000040};\n"
    "wgmma.mma_async.sync.aligned.m64n48k16.f32.bf16.bf16 {%0,%1,%2,%3,%4,%5,%6,%7,%8,%9,%10,%11,%12,%13,%14,%15,%16,%17,%18,%19,%20,%21,%22,%23}, {%24,%25,%26,%27}, db, p, 1, 1, 1;\n}\n"
    : "+f"(d[0]),"+f"(d[1]),"+f"(d[2]),"+f"(d[3]),"+f"(d[4]),"+f"(d[5]),"+f"(d[6]),"+f"(d[7]),"+f"(d[8]),"+f"(d[9]),"+f"(d[10]),"+f"(d[11]),"+f"(d[12]),"+f"(d[13]),"+f"(d[14]),"+f"(d[15]),"+f"(d[16]),"+f"(d[17]),"+f"(d[18]),"+f"(d[19]),"+f"(d[20]),"+f"(d[21]),"+f"(d[22]),"+f"(d[23])
    : "r"(a[0]), "r"(a[1]), "r"(a[2]), "r"(a[3]), "r"(descB), "r"(scaleD));
}
__device__ __forceinline__ void wgmma_rs_n64(float (&d)[32], const uint32_t (&a)[4], uint32_t descB, int scaleD) {
  asm volatile("{\n.reg .pred p;\n.reg .b64 db;\nsetp.ne.b32 p, %37, 0;\nmov.b64 db, {%36, 0x40000040};\n"
    "wgmma.mma_async.sync.aligned.m64n64k16.f32.bf16.bf16 {%0,%1,%2,%3,%4,%5,%6,%7,%8,%9,%10,%11,%12,%13,%14,%15,%16,%17,%18,%19,%20,%21,%22,%23,%24,%25,%26,%27,%28,%29,%30,%31}, {%32,%33,%34,%35}, db, p, 1, 1, 1;\n}\n"
    : "+f"(d[0]),"+f"(d[1]),"+f"(d[2]),"+f"(d[3]),"+f"(d[4]),"+f"(d[5]),"+f"(d[6]),"+f"(d[7]),"+f"(d[8]),"+f"(d[9]),"+f"(d[10]),"+f"(d[11]),"+f"(d[12]),"+f"(d[13]),"+f"(d[14]),"+f"(d[15]),"+f"(d[16]),"+f"(d[17]),"+f"(d[18]),"+f"(d[19]),"+f"(d[20]),"+f"(d[21]),"+f"(d[22]),"+f"(d[23]),"+f"(d[24]),"+f"(d[25]),"+f"(d[26]),"+f"(d[27]),"+f"(d[28]),"+f"(d[29]),"+f"(d[30]),"+f"(d[31])
    : "r"(a[0]), "r"(a[1]), "r"(a[2]), "r"(a[3]), "r"(descB), "r"(scaleD));
}
__device__ __forceinline__ void wgmma_rs_n128(float (&d)[64], const uint32_t (&a)[4], uint32_t descB, int scaleD) {
  asm volatile("{\n.reg .pred p;\n.reg .b64 db;\nsetp.ne.b32 p, %69, 0;\nmov.b64 db, {%68, 0x40000040};\n"
    "wgmma.mma_async.sync.aligned.m64n128k16.f32.bf16.bf16 {%0,%1,%2,%3,%4,%5,%6,%7,%8,%9,%10,%11,%12,%13,%14,%15,%16,%17,%18,%19,%20,%21,%22,%23,%24,%25,%26,%27,%28,%29,%30,%31,%32,%33,%34,%35,%36,%37,%38,%39,%40,%41,%42,%43,%44,%45,%46,%47,%48,%49,%50,%51,%52,%53,%54,%55,%56,%57,%58,%59,%60,%61,%62,%63}, {%64,%65,%66,%67}, db, p, 1, 1, 1;\n}\n"
    : "+f"(d[0]),"+f"(d[1]),"+f"(d[2]),"+f"(d[3]),"+f"(d[4]),"+f"(d[5]),"+f"(d[6]),"+f"(d[7]),"+f"(d[8]),"+f"(d[9]),"+f"(d[10]),"+f"(d[11]),"+f"(d[12]),"+f"(d[13]),"+f"(d[14]),"+f"(d[15]),"+f"(d[16]),"+f"(d[17]),"+f"(d[18]),"+f"(d[19]),"+f"(d[20]),"+f"(d[21]),"+f"(d[22]),"+f"(d[23]),"+f"(d[24]),"+f"(d[25]),"+f"(d[26]),"+f"(d[27]),"+f"(d[28]),"+f"(d[29]),"+f"(d[30]),"+f"(d[31]),"+f"(d[32]),"+f"(d[33]),"+f"(d[34]),"+f"(d[35]),"+f"(d[36]),"+f"(d[37]),"+f"(d[38]),"+f"(d[39]),"+f"(d[40]),"+f"(d[41]),"+f"(d[42]),"+f"(d[43]),"+f"(d[44]),"+f"(d[45]),"+f"(d[46]),"+f"(d[47]),"+f"(d[48]),"+f"(d[49]),"+f"(d[50]),"+f"(d[51]),"+f"(d[52]),"+f"(d[53]),"+f"(d[54]),"+f"(d[55]),"+f"(d[56]),"+f"(d[57]),"+f"(d[58]),"+f"(d[59]),"+f"(d[60]),"+f"(d[61]),"+f"(d[62]),"+f"(d[63])
    : "r"(a[0]), "r"(a[1]), "r"(a[2]), "r"(a[3]), "r"(descB), "r"(scaleD));
}
__device__ __forceinline__ void wgmma_ss_n72_t11(float (&d)[36], uint32_t descA, uint32_t descB, int scaleD) {
  asm volatile("{\n.reg .pred p;\n.reg .b64 da, db;\nsetp.ne.b32 p, %38, 0;\nmov.b64 da, {%36, 0x40000040};\nmov.b64 db, {%37, 0x40000040};\n"
    "wgmma.mma_async.sync.aligned.m64n72k16.f32.bf16.bf16 {%0,%1,%2,%3,%4,%5,%6,%7,%8,%9,%10,%11,%12,%13,%14,%15,%16,%17,%18,%19,%20,%21,%22,%23,%24,%25,%26,%27,%28,%29,%30,%31,%32,%33,%34,%35}, da, db, p, 1, 1, 1, 1;\n}\n"
    : "+f"(d[0]),"+f"(d[1]),"+f"(d[2]),"+f"(d[3]),"+f"(d[4]),"+f"(d[5]),"+f"(d[6]),"+f"(d[7]),"+f"(d[8]),"+f"(d[9]),"+f"(d[10]),"+f"(d[11]),"+f"(d[12]),"+f"(d[13]),"+f"(d[14]),"+f"(d[15]),"+f"(d[16]),"+f"(d[17]),"+f"(d[18]),"+f"(d[19]),"+f"(d[20]),"+f"(d[21]),"+f"(d[22]),"+f"(d[23]),"+f"(d[24]),"+f"(d[25]),"+f"(d[26]),"+f"(d[27]),"+f"(d[28]),"+f"(d[29]),"+f"(d[30]),"+f"(d[31]),"+f"(d[32]),"+f"(d[33]),"+f"(d[34]),"+f"(d[35])
    : "r"(descA), "r"(descB), "r"(scaleD));
}

#define TSTAMP(i) do {} while (0)
#define TS2(w, i) do {} while (0)

constexpr float LOG2E = 1.4426950408889634f;

__device__ __forceinline__ void feat_exp(const uint32_t (&P)[4], float (&e)[16]) {
  uint32_t a = hmax2(P[0], P[2]), b = hmax2(P[1], P[3]);
  uint32_t mx = hmax2(__byte_perm(a, b, 0x5410), __byte_perm(a, b, 0x7632));
  a = hmin2(P[0], P[2]); b = hmin2(P[1], P[3]);
  uint32_t mn = hmin2(__byte_perm(a, b, 0x5410), __byte_perm(a, b, 0x7632));
  mx = hmax2(mx, __shfl_xor_sync(0xffffffffu, mx, 1));
  mn = hmin2(mn, __shfl_xor_sync(0xffffffffu, mn, 1));
  mx = hmax2(mx, __shfl_xor_sync(0xffffffffu, mx, 2));
  mn = hmin2(mn, __shfl_xor_sync(0xffffffffu, mn, 2));
  float mx0 = -blo(mx) * LOG2E, mx1 = -bhi(mx) * LOG2E, mn0 = blo(mn) * LOG2E, mn1 = bhi(mn) * LOG2E;
  float v[8] = {blo(P[0]), bhi(P[0]), blo(P[1]), bhi(P[1]), blo(P[2]), bhi(P[2]), blo(P[3]), bhi(P[3])};
#pragma unroll
  for (int i = 0; i < 8; i++) {
    bool r1 = (i >> 1) & 1;
    e[i]     = ex2(fmaf(v[i],  LOG2E, r1 ? mx1 : mx0));
    e[8 + i] = ex2(fmaf(v[i], -LOG2E, r1 ? mn1 : mn0));
  }
}

template <int SBASE>
__global__ void __cluster_dims__(2, 1, 1) __launch_bounds__(384, 1)
fused_kernel(const __grid_constant__ Maps maps, const __nv_bfloat16* __restrict__ x, const __nv_bfloat16* __restrict__ wphi,
             const __nv_bfloat16* __restrict__ wo, const __nv_bfloat16* __restrict__ wg_, const __nv_bfloat16* __restrict__ wu_,
             const __nv_bfloat16* __restrict__ wd_, __nv_bfloat16* __restrict__ out) {
  extern __shared__ __align__(1024) unsigned char smem[];
  const uint32_t sb = smem_u32(smem);
  const int tid = threadIdx.x, lane = tid & 31;
  const int warp = __shfl_sync(0xffffffffu, tid >> 5, 0);
  const uint32_t rank = blockIdx.x & 1;
  const int cl = blockIdx.x >> 1;
  int quad, qi;
  if (cl < 4) { quad = 15; qi = cl; }
  else if (cl < 36) { quad = (cl - 4) & 7; qi = (cl - 4) >> 3; }
  else { qi = (cl - 36) / 7; quad = 8 + (cl - 36) - 7 * qi; }
  const int rb = quad, hg = 2 * qi + rank;
  const int rb3 = (quad & ~1) + rank, jf = 4 * (quad & 1) + qi;

  if (warp < 8) {
    asm volatile("setmaxnreg.inc.sync.aligned.u32 240;");
    if (lane == 0) {
#pragma unroll 1
      for (int d = warp; d + 9 < NSTAGE; d += 8) {
        mbar_init(sb + SM_EMPTY + d * 8, st_empty_cnt(d));
        {
          mbar_init(sb + SM_FULL + (d + 9) * 8, 1);
          mbar_expect_tx(sb + SM_FULL + (d + 9) * 8, d + 9 >= ST_D ? 22528 : SLOT);
        }
      }
      asm volatile("fence.mbarrier_init.release.cluster;" ::: "memory");
    }
    __syncwarp();
    bar_sync(0, 352);
    asm volatile("barrier.cluster.arrive.relaxed.aligned;" ::: "memory");
    const int wg = warp >> 2, wq = warp & 3, g = lane >> 2, t = lane & 3;
    const bool lead = (tid & 127) == 0;
    const uint32_t db = ((SBASE ? (uint32_t)SBASE : (sb & 0x3FFFF)) >> 4) | (512u << 16);
    auto release = [&](int d) {
      const int s = d + NSLOT;
      mbar_arrive_cluster(sb + SM_EMPTY + d * 8, s >= ST_GU ? (uint32_t)(s & 1) : rank);
    };
    const uint32_t lrow = (uint32_t)(wq * 16 + (lane & 7) + ((lane >> 3) & 1) * 8) * 128;
    const uint32_t lx = lane & 7, lhi = lane >> 4;
    if (wg == 1) bar_arrive(4, 256);

    float r0, r1;
    uint32_t E[4][8];
    uint32_t T = 0;
    {
      uint32_t A[32][4];
      const int sx = wg ? ST_X1 : ST_X0;
      {
        const uint32_t base = sb + sx * SLOT + lrow;
        float cs[2][4], c0[2][4], c1[2][4];
#pragma unroll
        for (int i = 0; i < 4; i++) { cs[0][i] = cs[1][i] = c0[0][i] = c0[1][i] = c1[0][i] = c1[1][i] = 0.f; }
#pragma unroll
        for (int c = 0; c < 8; c++) {
          if (c % 3 == 0) mbar_wait(sb + SM_FULL + (sx + c / 3) * 8);
#pragma unroll
          for (int k = 0; k < 4; k++) ldsm4(A[4 * c + k], base + c * 8192 + (((2 * k + lhi) ^ lx) << 4));
#pragma unroll
          for (int k = 0; k < 4; k++) {
            const uint32_t (&f)[4] = A[4 * c + k];
            mma16816(cs[k & 1], f, 0x3F803F80u, 0x3F803F80u);
            mma16816(c0[k & 1], f, f[0], f[2]);
            mma16816(c1[k & 1], f, f[1], f[3]);
          }
        }
        const float s0 = (cs[0][0] + cs[1][0]) * (1.f / 512.f), s1 = (cs[0][2] + cs[1][2]) * (1.f / 512.f);
        asm volatile("barrier.cluster.wait.aligned;" ::: "memory");
        if (lane < 3) release(sx + lane);
        const uint32_t m0 = pack2(s0, s0), m1 = pack2(s1, s1);
        float q0 = (g & 1) ? c0[0][1] + c0[1][1] : c0[0][0] + c0[1][0];
        float q1 = (g & 1) ? c1[0][3] + c1[1][3] : c1[0][2] + c1[1][2];
        q0 = __shfl_sync(0xffffffffu, q0, (lane & ~3) | (g >> 1));
        q1 = __shfl_sync(0xffffffffu, q1, (lane & ~3) | (g >> 1));
        r0 = rsqrtf(fmaxf(q0 * (1.f / 512.f) - s0 * s0, 0.f) + 1e-5f);
        r1 = rsqrtf(fmaxf(q1 * (1.f / 512.f) - s1 * s1, 0.f) + 1e-5f);
#pragma unroll
        for (int ks = 0; ks < 32; ks++) {
          A[ks][0] = hsub2(A[ks][0], m0); A[ks][1] = hsub2(A[ks][1], m1);
          A[ks][2] = hsub2(A[ks][2], m0); A[ks][3] = hsub2(A[ks][3], m1);
        }
      }
      TSTAMP(1);
      const uint32_t wpa = sb + SM_WPHI + ((lane & 7) + ((lane >> 3) & 1) * 8) * 32 + lhi * 16;
      const uint32_t scr = sb + (wg ? (ST_SCR1 % NSLOT) : (ST_SCR0 % NSLOT)) * SLOT;
      mbar_wait(sb + SM_MISCB);
      T = (*reinterpret_cast<volatile unsigned*>(smem + SM_EPOCH) & 1) ^ 1;
#pragma unroll 1
      for (int ps = 0; ps < 3; ps++) {
        const int st0 = ps == 0 ? ST_WK : (ps == 1 ? ST_WV : ST_WQ);
        const uint32_t wdesc = DESC((ps == 0 ? ST_WK % NSLOT : (ps == 1 ? ST_WV % NSLOT : ST_WQ % NSLOT)) * SLOT);
        float acc[32];
        bar_sync(4 + wg, 256);
#pragma unroll
        for (int i = 0; i < 3; i++) {
          mbar_wait(sb + SM_FULL + (st0 + i) * 8);
          wg_fence();
#pragma unroll
          for (int kk = 0; kk < (i < 2 ? 12 : 8); kk++)
            wgmma_rs_n64(acc, A[12 * i + kk], wdesc + ((i * SLOT + kk * 2048) >> 4), (i | kk) != 0);
          wg_commit();
          if (i == 1) { wg_wait<1>(); if (lead) release(st0); }
        }
        if (ps == 0 || wg == 0) bar_arrive(4 + (wg ^ 1), 256);
        uint32_t a[4][4], b[4][4];
#pragma unroll
        for (int h = 0; h < 4; h++) ldsm4t(b[h], wpa + h * 512);
        wg_wait<0>();
        if ((tid & 127) < 2) release(st0 + 1 + (tid & 1));
        TSTAMP(2 + 2 * ps);
#pragma unroll
        for (int h = 0; h < 4; h++) {
          a[h][0] = pack2(acc[8 * h + 0] * r0, acc[8 * h + 1] * r0); a[h][1] = pack2(acc[8 * h + 2] * r1, acc[8 * h + 3] * r1);
          a[h][2] = pack2(acc[8 * h + 4] * r0, acc[8 * h + 5] * r0); a[h][3] = pack2(acc[8 * h + 6] * r1, acc[8 * h + 7] * r1);
        }
        if (ps != 1) {
          {
            float pp[4][2][4];
#pragma unroll
            for (int h = 0; h < 4; h++) {
#pragma unroll
              for (int i = 0; i < 4; i++) { pp[h][0][i] = 0.f; pp[h][1][i] = 0.f; }
              mma16816(pp[h][0], a[h], b[h][0], b[h][1]);
              mma16816(pp[h][1], a[h], b[h][2], b[h][3]);
            }
#pragma unroll
            for (int h = 0; h < 4; h++) {
              a[h][0] = pack2(pp[h][0][0], pp[h][0][1]); a[h][1] = pack2(pp[h][0][2], pp[h][0][3]);
              a[h][2] = pack2(pp[h][1][0], pp[h][1][1]); a[h][3] = pack2(pp[h][1][2], pp[h][1][3]);
            }
          }
          if (ps == 0) mbar_wait(sb + SM_EMPTY + (wg ? ST_SCR1 - NSLOT : ST_SCR0 - NSLOT) * 8);
#pragma unroll 1
          for (int hp = 0; hp < 2; hp++) {
            float e[2][16];
            feat_exp(a[0], e[0]);
            feat_exp(a[1], e[1]);
            if (ps == 0) {
#pragma unroll
              for (int h = 0; h < 2; h++) {
                const float (&f)[16] = e[h];
                float sp0 = (f[0] + f[1]) + (f[4] + f[5]), sp1 = (f[2] + f[3]) + (f[6] + f[7]);
                float sn0 = (f[8] + f[9]) + (f[12] + f[13]), sn1 = (f[10] + f[11]) + (f[14] + f[15]);
                sp0 += __shfl_xor_sync(0xffffffffu, sp0, 1); sp1 += __shfl_xor_sync(0xffffffffu, sp1, 1);
                sn0 += __shfl_xor_sync(0xffffffffu, sn0, 1); sn1 += __shfl_xor_sync(0xffffffffu, sn1, 1);
                sp0 += __shfl_xor_sync(0xffffffffu, sp0, 2); sp1 += __shfl_xor_sync(0xffffffffu, sp1, 2);
                sn0 += __shfl_xor_sync(0xffffffffu, sn0, 2); sn1 += __shfl_xor_sync(0xffffffffu, sn1, 2);
                sp0 = rcp(sp0); sp1 = rcp(sp1); sn0 = rcp(sn0); sn1 = rcp(sn1);
                const uint32_t dst = scr + hp * 8192 + lrow;
                stsm4(dst + (((h * 4 + lhi) ^ lx) << 4), pack2(f[0] * sp0, f[1] * sp0), pack2(f[2] * sp1, f[3] * sp1),
                      pack2(f[4] * sp0, f[5] * sp0), pack2(f[6] * sp1, f[7] * sp1));
                stsm4(dst + (((h * 4 + 2 + lhi) ^ lx) << 4), pack2(f[8] * sn0, f[9] * sn0), pack2(f[10] * sn1, f[11] * sn1),
                      pack2(f[12] * sn0, f[13] * sn0), pack2(f[14] * sn1, f[15] * sn1));
              }
            } else {
#pragma unroll
              for (int i = 0; i < 16; i++) {
                A[i >> 2][i & 3] = A[4 + (i >> 2)][i & 3];
                A[4 + (i >> 2)][i & 3] = pack2(e[i >> 3][2 * (i & 7)], e[i >> 3][2 * (i & 7) + 1]);
              }
            }
#pragma unroll
            for (int i = 0; i < 4; i++) { a[0][i] = a[2][i]; a[1][i] = a[3][i]; }
          }
        } else {
#pragma unroll
          for (int h = 0; h < 4; h++) stsm4(scr + 16384 + lrow + (((2 * h + lhi) ^ lx) << 4), a[h][0], a[h][1], a[h][2], a[h][3]);
          fence_async_smem();
          bar_sync(3, 256);
          float kv[36];
          wg_fence();
#pragma unroll
          for (int ks = 0; ks < 8; ks++) {
            const uint32_t sk = (ks < 4 ? (ST_SCR0 % NSLOT) : (ST_SCR1 % NSLOT)) * SLOT + (ks & 3) * 2048;
            const uint32_t dv = (DESC(sk + 16384) & 0xFFFFu) | (((SM_ONES - sk - 16384) >> 4) << 16);
            wgmma_ss_n72_t11(kv, DESC(sk) + wg * 512, dv, ks != 0);
          }
          wg_commit();
          if (wg == 1) bar_arrive(4, 256);
          wg_wait<0>();
          if (lead) { mbar_arrive(sb + SM_EMPTY + ST_SCR0 * 8); mbar_arrive(sb + SM_EMPTY + ST_SCR1 * 8); }
          const int hl = 2 * wg + (wq >> 1), f = (wq & 1) * 16 + g;
          float* kvp = &g_kv[T ^ 1][((hg * 4 + hl) * 32 + f) * 16 + 2 * t];
          float* zp = &g_z[T ^ 1][(hg * 4 + hl) * 32 + f];
          float c[8];
#pragma unroll
          for (int i = 0; i < 8; i++) c[i] = hl >= 2 ? (hl == 3 ? kv[24 + i] : kv[16 + i]) : (hl == 1 ? kv[8 + i] : kv[i]);
#pragma unroll
          for (int n = 0; n < 2; n++) {
            asm volatile("red.relaxed.gpu.global.add.v2.f32 [%0], {%1,%2};" ::"l"(kvp + n * 8), "f"(c[4 * n]), "f"(c[4 * n + 1]) : "memory");
            asm volatile("red.relaxed.gpu.global.add.v2.f32 [%0], {%1,%2};" ::"l"(kvp + n * 8 + 128), "f"(c[4 * n + 2]), "f"(c[4 * n + 3]) : "memory");
          }
          if (t < 2) asm volatile("red.relaxed.gpu.global.add.f32 [%0], %1;" ::"l"(zp + t * 8), "f"(t ? kv[34] : kv[32]) : "memory");
          bar_arrive(6 + wg, 160);
        }
        TSTAMP(3 + 2 * ps);
      }
#pragma unroll
      for (int i = 0; i < 32; i++) E[i >> 3][i & 7] = A[i >> 2][i & 3];
    }
    const int rh = 2 * rb + wg;
    const uint32_t xb = sb + 2 * SLOT + wq * 2048 + lane * 16;
    mbar_wait(sb + SM_KVB);
    {
      const int r = tid & 127;
      const float4* src = reinterpret_cast<const float4*>(smem + SM_KV32) + r;
#pragma unroll
      for (int i = 0; i < 4; i++) {
        const float4 a = src[i * 128];
        *reinterpret_cast<uint2*>(smem + SM_KVS + (i * 32 + (r >> 2)) * 48 + (r & 3) * 8) = make_uint2(pack2(a.x, a.y), pack2(a.z, a.w));
      }
      const uint32_t zz = pack2(reinterpret_cast<const float*>(smem + SM_ONES)[r], 1.0f);
      *reinterpret_cast<uint4*>(smem + SM_KVS + r * 48 + 32) = make_uint4(zz, zz, zz, zz);
      bar_sync(1 + wg, 128);
    }
    TSTAMP(8);
    {
      uint4* op = &g_o[rh][hg][wq][0][lane];
#pragma unroll
      for (int h = 0; h < 4; h++) {
        uint32_t b0[4], b1[4], b2[4];
        const uint32_t kb = sb + SM_KVS + (h * 32 + lane) * 48;
        ldsm4t(b0, kb); ldsm4t(b1, kb + 16); ldsm4t(b2, kb + 32);
        const uint32_t ep[4] = {E[h][0], E[h][1], E[h][2], E[h][3]}, en[4] = {E[h][4], E[h][5], E[h][6], E[h][7]};
        float np0[4] = {0, 0, 0, 0}, np1[4] = {0, 0, 0, 0}, nn0[4] = {0, 0, 0, 0}, nn1[4] = {0, 0, 0, 0}, dp[4] = {0, 0, 0, 0}, dn[4] = {0, 0, 0, 0};
        mma16816(dp, ep, b2[0], b2[1]);  mma16816(dn, en, b2[2], b2[3]);
        mma16816(np0, ep, b0[0], b0[1]); mma16816(nn0, en, b0[2], b0[3]);
        mma16816(np1, ep, b1[0], b1[1]); mma16816(nn1, en, b1[2], b1[3]);
        const float i0 = rcp(fmaf(dp[0], dn[1], fmaf(dn[0], dp[1], 1e-6f * dp[1] * dn[1])));
        const float i1 = rcp(fmaf(dp[2], dn[3], fmaf(dn[2], dp[3], 1e-6f * dp[3] * dn[3])));
        const float cp0 = dn[1] * i0, cn0 = dp[1] * i0, cp1 = dn[3] * i1, cn1 = dp[3] * i1;
        st_rlx4(op + h * 32,
                tg(pack2(fmaf(np0[0], cp0, nn0[0] * cn0), fmaf(np0[1], cp0, nn0[1] * cn0)), T),
                pack2(fmaf(np0[2], cp1, nn0[2] * cn1), fmaf(np0[3], cp1, nn0[3] * cn1)),
                pack2(fmaf(np1[0], cp0, nn1[0] * cn0), fmaf(np1[1], cp0, nn1[1] * cn0)),
                pack2(fmaf(np1[2], cp1, nn1[2] * cn1), fmaf(np1[3], cp1, nn1[3] * cn1)));
      }
    }
    TSTAMP(9);

    {
      uint32_t xr[16];
      {
        const uint32_t* xp = reinterpret_cast<const uint32_t*>(x + (size_t)(rh * 64 + wq * 16 + g) * 512 + hg * 64 + 2 * t);
#pragma unroll
        for (int i = 0; i < 8; i++) { xr[2 * i] = __ldg(xp + 4 * i); xr[2 * i + 1] = __ldg(xp + 8 * 256 + 4 * i); }
      }
      uint32_t A[8][4][4];
      const uint4* op = &g_o[rh][0][wq][0][lane];
      float acc[32];
      mbar_wait(sb + SM_XF + (wg * 4) * 8);
      lds_chunk(A[0], xb); lds_chunk(A[1], xb + 8192);
#pragma unroll
      for (int p = 0; p < 4; p++) {
        chk_pair(A[2 * p], A[2 * p + 1], op + p * 1024, T);
        if (lane == 0) mbar_arrive(sb + SM_XE + (wg * 4 + p) * 8);
#pragma unroll
        for (int c = 2 * p; c < 2 * p + 2; c++) {
          if (c % 3 == 0) mbar_wait(sb + SM_FULL + (ST_WO + c / 3) * 8);
          if ((c & 1) && p < 3) {
            mbar_wait(sb + SM_XF + (wg * 4 + p + 1) * 8);
            lds_chunk(A[2 * p + 2], xb + (p + 1) * 16384); lds_chunk(A[2 * p + 3], xb + (p + 1) * 16384 + 8192);
          }
          wg_fence();
#pragma unroll
          for (int s = 0; s < 4; s++)
            wgmma_rs_n64(acc, A[c][s], DESC(((ST_WO + c / 3) % NSLOT) * SLOT + ((c % 3) * 4 + s) * 2048), (c | s) != 0);
          wg_commit();
        }
      }
      wg_wait<0>();
      if ((tid & 127) < 3) release(ST_WO + (tid & 127));
      TSTAMP(10);
      uint32_t hw[16];
      float s0 = 0.f, s1 = 0.f, q0 = 0.f, q1 = 0.f;
#pragma unroll
      for (int i = 0; i < 8; i++) {
        hw[2 * i]     = pack2(blo(xr[2 * i]) + acc[4 * i], bhi(xr[2 * i]) + acc[4 * i + 1]);
        hw[2 * i + 1] = pack2(blo(xr[2 * i + 1]) + acc[4 * i + 2], bhi(xr[2 * i + 1]) + acc[4 * i + 3]);
      }
      uint4* hp_ = &g_h[rh][hg][wq][0][lane];
#pragma unroll
      for (int s = 0; s < 4; s++) st_rlx4(hp_ + s * 32, tg(hw[4 * s], T), hw[4 * s + 1], hw[4 * s + 2], hw[4 * s + 3]);
#pragma unroll
      for (int i = 0; i < 8; i++) {
        float a = blo(hw[2 * i]), b = bhi(hw[2 * i]);
        s0 += a + b; q0 = fmaf(a, a, q0); q0 = fmaf(b, b, q0);
        a = blo(hw[2 * i + 1]); b = bhi(hw[2 * i + 1]);
        s1 += a + b; q1 = fmaf(a, a, q1); q1 = fmaf(b, b, q1);
      }
      s0 += __shfl_xor_sync(0xffffffffu, s0, 1); s1 += __shfl_xor_sync(0xffffffffu, s1, 1);
      q0 += __shfl_xor_sync(0xffffffffu, q0, 1); q1 += __shfl_xor_sync(0xffffffffu, q1, 1);
      s0 += __shfl_xor_sync(0xffffffffu, s0, 2); s1 += __shfl_xor_sync(0xffffffffu, s1, 2);
      q0 += __shfl_xor_sync(0xffffffffu, q0, 2); q1 += __shfl_xor_sync(0xffffffffu, q1, 2);
      if (t < 2) st_rlx2(&g_st[rh][hg][wq * 16 + g + t * 8], tg(__float_as_uint(t ? s1 : s0), T), __float_as_uint(t ? q1 : q0));
      uint32_t hx = T;
#pragma unroll
      for (int i = 0; i < 4; i++) hx |= (hw[4 * i] & 1u) << (i + 1);
      st_rlx1(&g_hx[rh][hg][wq][lane], hx);
    }
    TSTAMP(11);

    const int rh3 = 2 * rb3 + wg;
    uint32_t HH[11][4];
    {
      uint32_t A[8][4][4];
      const uint4* hp_ = &g_h[rh3][0][wq][0][lane];
      uint4* hhp = &g_hh[rh3][jf][0][wq][lane];
      const uint32_t dg = (db & 0xFFFFu) | (256u << 16);
      uint32_t m0, m1;
      mbar_wait(sb + SM_XF + ((2 + wg) * 4) * 8);
      lds_chunk(A[0], xb); lds_chunk(A[1], xb + 8192);
      {
        const uint2* sp = &g_st[rh3][2 * t][wq * 16 + g];
        const uint2* ss = reinterpret_cast<const uint2*>(smem + SM_KV32 + wg * 4096) + 2 * t * 64 + wq * 16 + g;
        uint2 a0 = ss[0], a1 = ss[64], b0 = ss[8], b1 = ss[72];
        int it = 0;
#pragma unroll 1
        while (__any_sync(0xffffffffu, bad4(a0.x, a1.x, b0.x, b1.x, T))) {
          ld_rlx2(a0.x, a0.y, sp); ld_rlx2(a1.x, a1.y, sp + 64); ld_rlx2(b0.x, b0.y, sp + 8); ld_rlx2(b1.x, b1.y, sp + 72);
          if (++it > (1 << 18)) break;
        }
        float s0 = __uint_as_float(a0.x) + __uint_as_float(a1.x), q0 = __uint_as_float(a0.y) + __uint_as_float(a1.y);
        float s1 = __uint_as_float(b0.x) + __uint_as_float(b1.x), q1 = __uint_as_float(b0.y) + __uint_as_float(b1.y);
        s0 += __shfl_xor_sync(0xffffffffu, s0, 1); s1 += __shfl_xor_sync(0xffffffffu, s1, 1);
        q0 += __shfl_xor_sync(0xffffffffu, q0, 1); q1 += __shfl_xor_sync(0xffffffffu, q1, 1);
        s0 += __shfl_xor_sync(0xffffffffu, s0, 2); s1 += __shfl_xor_sync(0xffffffffu, s1, 2);
        q0 += __shfl_xor_sync(0xffffffffu, q0, 2); q1 += __shfl_xor_sync(0xffffffffu, q1, 2);
        s0 *= (1.f / 512.f); s1 *= (1.f / 512.f);
        r0 = rcp(fmaxf(q0 * (1.f / 512.f) - s0 * s0, 0.f) + 1e-5f);
        r1 = rcp(fmaxf(q1 * (1.f / 512.f) - s1 * s1, 0.f) + 1e-5f);
        m0 = pack2(s0, s0); m1 = pack2(s1, s1);
      }
      TSTAMP(12);
#pragma unroll
      for (int p = 0; p < 4; p++) {
        if (p < 3) {
          mbar_wait(sb + SM_XF + ((2 + wg) * 4 + p + 1) * 8);
          lds_chunk(A[2 * p + 2], xb + (p + 1) * 16384); lds_chunk(A[2 * p + 3], xb + (p + 1) * 16384 + 8192);
        }
        chk_pair(A[2 * p], A[2 * p + 1], hp_ + p * 1024, T);
        if (lane == 0) {
          if (wg == 0) mbar_arrive(sb + SM_XE + (8 + p) * 8);
          else if (p > 0) release(ST_XC + p - 1);
        }
#pragma unroll
        for (int c = 2 * p; c < 2 * p + 2; c++)
#pragma unroll
          for (int s = 0; s < 4; s++) {
            A[c][s][0] = hsub2(A[c][s][0], m0); A[c][s][1] = hsub2(A[c][s][1], m1);
            A[c][s][2] = hsub2(A[c][s][2], m0); A[c][s][3] = hsub2(A[c][s][3], m1);
          }
      }
      TSTAMP(19);
#define UOFF(u) ((((ST_GU + (u) / 3) % NSLOT) * SLOT + ((u) % 3) * 8192) >> 4)
#define UNIT_PRE(u)  do { if ((u) % 3 == 0) mbar_wait(sb + SM_FULL + (ST_GU + (u) / 3) * 8); } while (0)
#define UNIT_POST(u) do { wg_commit(); if ((u) % 3 == 1 && (u) > 3) { wg_wait<2>(); if (lead) release(ST_GU + (u) / 3 - 1); } } while (0)
      float acc[64];
      const int rz = blockIdx.y;
#pragma unroll
      for (int ps = 0; ps < 2; ps++) {
        wg_fence();
#pragma unroll
        for (int k = 0; k < 16; k++) {
          const int u = 16 * ps + k, c = k >> 1;
          UNIT_PRE(u);
          wgmma_rs_n128(acc, A[c][(k & 1) * 2], dg + UOFF(u), k != 0 ? 1 : (ps ? rz : 0));
          wgmma_rs_n128(acc, A[c][(k & 1) * 2 + 1], dg + UOFF(u) + 128, 1);
          UNIT_POST(u);
        }
        wg_wait<0>();
#pragma unroll
        for (int s = 0; s < 4; s++) {
          uint32_t (&hh)[4] = HH[4 + s];
          hh[0] = tg(pack2(acc[8 * s + 0] * acc[32 + 8 * s + 0] * r0, acc[8 * s + 1] * acc[32 + 8 * s + 1] * r0), T);
          hh[1] = pack2(acc[8 * s + 2] * acc[32 + 8 * s + 2] * r1, acc[8 * s + 3] * acc[32 + 8 * s + 3] * r1);
          hh[2] = pack2(acc[8 * s + 4] * acc[32 + 8 * s + 4] * r0, acc[8 * s + 5] * acc[32 + 8 * s + 5] * r0);
          hh[3] = pack2(acc[8 * s + 6] * acc[32 + 8 * s + 6] * r1, acc[8 * s + 7] * acc[32 + 8 * s + 7] * r1);
          st_rlx4(hhp + (4 * ps + s) * 128, hh[0], hh[1], hh[2], hh[3]);
        }
      }
      {
        float ag[24], au[24];
        bar_sync(1 + wg, 128);
        wg_fence();
#pragma unroll
        for (int k = 0; k < 16; k++) {
          const int u = 32 + k, c = k >> 1;
          UNIT_PRE(u);
          wgmma_rs_n48(ag, A[c][(k & 1) * 2], dg + UOFF(u), k != 0);
          wgmma_rs_n48(au, A[c][(k & 1) * 2], dg + UOFF(u) + 256, k != 0);
          wgmma_rs_n48(ag, A[c][(k & 1) * 2 + 1], dg + UOFF(u) + 128, 1);
          wgmma_rs_n48(au, A[c][(k & 1) * 2 + 1], dg + UOFF(u) + 256 + 128, 1);
          UNIT_POST(u);
        }
        wg_wait<0>();
        TSTAMP(13);
#pragma unroll
        for (int s = 0; s < 4; s++) ld_rlx4(HH[s], hhp + s * 128);
#pragma unroll
        for (int s = 0; s < 3; s++) {
          uint32_t (&hh)[4] = HH[8 + s];
          hh[0] = tg(pack2(ag[8 * s + 0] * au[8 * s + 0] * r0, ag[8 * s + 1] * au[8 * s + 1] * r0), T);
          hh[1] = pack2(ag[8 * s + 2] * au[8 * s + 2] * r1, ag[8 * s + 3] * au[8 * s + 3] * r1);
          hh[2] = pack2(ag[8 * s + 4] * au[8 * s + 4] * r0, ag[8 * s + 5] * au[8 * s + 5] * r0);
          hh[3] = pack2(ag[8 * s + 6] * au[8 * s + 6] * r1, ag[8 * s + 7] * au[8 * s + 7] * r1);
          st_rlx4(hhp + (8 + s) * 128, hh[0], hh[1], hh[2], hh[3]);
        }
      }
    }
    TSTAMP(14);

    {
      float ac[3][32], acc[32];
      uint32_t PH[11][4], hr[4][4];
      const int m = jf >> 1, oc = (jf & 1) * 4 + m;
      const uint4* pp = &g_hh[rh3][jf ^ 1][0][wq][lane];
      bar_arrive(8 + wg, 256);
#pragma unroll
      for (int s = 0; s < 8; s++) ld_rlx4(PH[s], pp + s * 128);
      wg_fence();
#pragma unroll
      for (int k = 0; k < 3; k++) {
        mbar_wait(sb + SM_FULL + (ST_D + k) * 8);
        if (k == 2) {
#pragma unroll
          for (int s = 8; s < 11; s++) ld_rlx4(PH[s], pp + s * 128);
        }
#pragma unroll
        for (int s = 4; s < 11; s++) wgmma_rs_n64(ac[k], HH[s], DESC(((ST_D + k) % NSLOT) * SLOT + s * 2048), s != 4);
        if (k == 0) wg_fence();
#pragma unroll
        for (int s = 0; s < 4; s++) wgmma_rs_n64(ac[k], HH[s], DESC(((ST_D + k) % NSLOT) * SLOT + s * 2048), 1);
      }
      wg_commit();
      {
        int it = 0;
#pragma unroll 1
        while (__any_sync(0xffffffffu, bad4(PH[0][0], PH[1][0], PH[2][0], PH[3][0], T) | bad4(PH[4][0], PH[5][0], PH[6][0], PH[7][0], T) |
                                       bad4(PH[8][0], PH[9][0], PH[10][0], T, T))) {
#pragma unroll
          for (int s = 0; s < 11; s++) ld_rlx4(PH[s], pp + s * 128);
          if (++it > (1 << 18)) break;
        }
      }
      TSTAMP(20);
      uint4* outb = &g_part[rh3][(jf & 1) * 4][m][wq][0][lane];
#pragma unroll
      for (int k = 0; k < 4; k++) {
        mbar_wait(sb + SM_FULL + (ST_D + 3 + k) * 8);
        wg_fence();
#pragma unroll
        for (int s = 0; s < 11; s++) {
          if (k < 3) wgmma_rs_n64(ac[k], PH[s], DESC(((ST_D + 3 + k) % NSLOT) * SLOT + s * 2048), 1);
          else wgmma_rs_n64(acc, HH[s], DESC(((ST_D + 6) % NSLOT) * SLOT + s * 2048), s != 0);
        }
        wg_commit();
        if (k > 0) {
          wg_wait<1>();
          const float (&a)[32] = ac[k - 1];
          uint4* p = outb + ((m + k) & 3) * 2048;
#pragma unroll
          for (int s = 0; s < 4; s++)
            st_rlx4(p + s * 32, tg(pack2(a[8 * s + 0], a[8 * s + 1]), T), pack2(a[8 * s + 2], a[8 * s + 3]),
                    pack2(a[8 * s + 4], a[8 * s + 5]), pack2(a[8 * s + 6], a[8 * s + 7]));
        }
      }
      ld_chunk(hr, &g_h[rh3][oc][wq][0][lane]);
      mbar_wait(sb + SM_FULL + (ST_D + 7) * 8);
      wg_fence();
#pragma unroll
      for (int s = 0; s < 11; s++) wgmma_rs_n64(acc, PH[s], DESC(((ST_D + 7) % NSLOT) * SLOT + s * 2048), 1);
      wg_commit();
      uint32_t hx = ld_rlx1(&g_hx[rh3][oc][wq][lane]);
      uint32_t in[3][4][4];
      const uint4* inb = &g_part[rh3][oc][0][wq][0][lane];
      {
        const uint32_t* hint = reinterpret_cast<const uint32_t*>(&g_part[rh3][oc][(m - 1 - lane) & 3][wq][3][31]);
        uint32_t ready = 0; int it = 0;
#pragma unroll
        for (int q = 0; q < 3; q++) {
#pragma unroll 1
          while (!((ready >> q) & 1)) {
            ready = __ballot_sync(0xffffffffu, ((ld_rlx1(hint) ^ T) & 1) == 0);
            if (++it > (1 << 18)) break;
          }
          ld_chunk(in[q], inb + ((m - 1 - q) & 3) * 512);
        }
#pragma unroll 1
        while (__any_sync(0xffffffffu, bad4(in[0][0][0], in[0][1][0], in[0][2][0], in[0][3][0], T) | bad4(in[1][0][0], in[1][1][0], in[1][2][0], in[1][3][0], T) |
                                       bad4(in[2][0][0], in[2][1][0], in[2][2][0], in[2][3][0], T) | ((hx ^ T) & 1))) {
#pragma unroll
          for (int q = 0; q < 3; q++) ld_chunk(in[q], inb + ((m - 1 - q) & 3) * 512);
          hx = ld_rlx1(&g_hx[rh3][oc][wq][lane]);
          if (++it > (1 << 18)) break;
        }
      }
      wg_wait<0>();
      TSTAMP(15);
#pragma unroll
      for (int i = 0; i < 16; i++) {
        acc[2 * i]     += (blo(in[0][i >> 2][i & 3]) + blo(in[1][i >> 2][i & 3])) + blo(in[2][i >> 2][i & 3]);
        acc[2 * i + 1] += (bhi(in[0][i >> 2][i & 3]) + bhi(in[1][i >> 2][i & 3])) + bhi(in[2][i >> 2][i & 3]);
      }
#pragma unroll
      for (int s = 0; s < 4; s++) hr[s][0] = (hr[s][0] & 0xFFFFFFFEu) | ((hx >> (s + 1)) & 1u);
      bar_sync(9 - wg, 256);
      const uint32_t ob = sb + ((ST_D - 1) % NSLOT) * SLOT + wg * 8192;
#pragma unroll
      for (int s = 0; s < 4; s++)
        stsm4(ob + lrow + (((2 * s + lhi) ^ lx) << 4),
              pack2(blo(hr[s][0]) + acc[8 * s + 0], bhi(hr[s][0]) + acc[8 * s + 1]), pack2(blo(hr[s][1]) + acc[8 * s + 2], bhi(hr[s][1]) + acc[8 * s + 3]),
              pack2(blo(hr[s][2]) + acc[8 * s + 4], bhi(hr[s][2]) + acc[8 * s + 5]), pack2(blo(hr[s][3]) + acc[8 * s + 6], bhi(hr[s][3]) + acc[8 * s + 7]));
      __syncwarp();
#pragma unroll
      for (int i = 0; i < 4; i++) {
        const int row = wq * 16 + i * 4 + (lane >> 3);
        uint4 v;
        asm volatile("ld.shared.v4.b32 {%0,%1,%2,%3}, [%4];" : "=r"(v.x), "=r"(v.y), "=r"(v.z), "=r"(v.w)
                     : "r"(ob + row * 128 + ((lx ^ (row & 7)) << 4)) : "memory");
        asm volatile("st.global.v4.b32 [%0], {%1,%2,%3,%4};" ::"l"(out + (size_t)(rh3 * 64 + row) * 512 + oc * 64 + lx * 8),
                     "r"(v.x), "r"(v.y), "r"(v.z), "r"(v.w) : "memory");
      }
    }
    TSTAMP(16);
    asm volatile("barrier.cluster.arrive.relaxed.aligned;" ::: "memory");
    asm volatile("barrier.cluster.wait.aligned;" ::: "memory");
  } else {
    asm volatile("setmaxnreg.dec.sync.aligned.u32 24;");
    if (lane == 0) {
      if (warp == 8) {
#pragma unroll
        for (int k = 0; k < 9; k++) {
          const int s = k < 3 ? k : (k < 6 ? k + 3 : k - 3);
          const uint32_t bar = sb + SM_FULL + s * 8;
          mbar_init(bar, 1);
          mbar_expect_tx(bar, SLOT);
          if (s >= 3 && s < 6) tma2d(sb + s * SLOT, &maps.w, 512 + hg * 64, (s - 3) * 192, bar);
          else tma3d(sb + s * SLOT, &maps.x, 0, rb * 128 + (s >= 6 ? 64 : 0), 3 * (s % 3), bar);
        }
      } else if (warp == 9) {
        mbar_init(sb + SM_MISCB, 2);
        mbar_init(sb + SM_KVB, 32);
        mbar_expect_tx(sb + SM_MISCB, 2048);
        bulk_g2s(sb + SM_WPHI, wphi + hg * 1024, 2048, sb + SM_MISCB);
      } else if (warp == 10) {
#pragma unroll 1
        for (int i = 0; i < 16; i++) {
          mbar_init(sb + SM_XF + i * 8, 1);
          mbar_expect_tx(sb + SM_XF + i * 8, (i == 8 || i == 12) ? 20480 : 16384);
          if (i < 12) mbar_init(sb + SM_XE + i * 8, 4);
        }
      } else {
        *reinterpret_cast<volatile unsigned*>(smem + SM_EPOCH) = atomicAdd(&g_start, 1u) / NCTA;
      }
      asm volatile("fence.mbarrier_init.release.cluster;" ::: "memory");
    }
    __syncwarp();
    if (warp != 11) bar_sync(0, 352);
    asm volatile("barrier.cluster.arrive.relaxed.aligned;" ::: "memory");
    if (warp == 8) {
      asm volatile("barrier.cluster.wait.aligned;" ::: "memory");
      if (lane == 0) {
        const CUtensorMap* mg = jf == 7 ? &maps.g7 : &maps.g;
        const CUtensorMap* mu = jf == 7 ? &maps.u7 : &maps.u;
        asm volatile("prefetch.tensormap [%0];" ::"l"(&maps.wo) : "memory");
        asm volatile("prefetch.tensormap [%0];" ::"l"(mg) : "memory");
        asm volatile("prefetch.tensormap [%0];" ::"l"(mu) : "memory");
        asm volatile("prefetch.tensormap [%0];" ::"l"(&maps.d) : "memory");
#pragma unroll 1
        for (int s = ST_WV; s < ST_XC; s++) {
          if (s == ST_SCR1) continue;
          mbar_wait(sb + SM_EMPTY + (s - 9) * 8);
          const uint32_t dst = sb + (s >= 18 ? s - 18 : s - 9) * SLOT, bar = sb + SM_FULL + s * 8;
          if (s < ST_WO) tma2d(dst, &maps.w, (s < ST_WQ ? 1024 : 0) + hg * 64, (s < ST_WQ ? s - ST_WV : s - ST_WQ) * 192, bar);
          else { mbar_wait(bar - 8); tma2d(dst, &maps.wo, hg * 64, (s - ST_WO) * 192, bar); }
        }
        const int jc = jf == 7 ? 0 : jf;
        int slot = (ST_GU + 1 - rank) % NSLOT;
#pragma unroll 1
        for (int s = ST_GU + 1 - rank; s < NSTAGE; s += 2) {
          mbar_wait(sb + SM_EMPTY + (s - 9) * 8);
          if (s > ST_GU && s < ST_GU + THR) mbar_wait(sb + SM_FULL + (s - 1) * 8);
          const uint32_t dst = sb + slot * SLOT, bar = sb + SM_FULL + s * 8;
          if (s < ST_D) {
#pragma unroll 1
            for (int i = 0; i < 3; i++) {
              const int u = (s - ST_GU) * 3 + i;
              tma3d_mc(dst + i * 8192, mg, (u >> 4) * 64, jc, (u & 15) * 32, bar);
              tma3d_mc(dst + i * 8192 + 4096, mu, (u >> 4) * 64, jc, (u & 15) * 32, bar);
            }
          } else {
            const int i = s - ST_D, k = i < 3 ? i : (i < 6 ? i - 3 : 3), pt = (i >= 3 && i != 6) ? 1 : 0;
            tma2d_mc(dst, &maps.d, ((jf & 1) * 4 + (((jf >> 1) + 1 + k) & 3)) * 64, (jf ^ pt) * 176, bar);
          }
          slot += 2; if (slot >= NSLOT) slot -= NSLOT;
        }
      }
      __syncwarp();
    } else {
      asm volatile("barrier.cluster.wait.aligned;" ::: "memory");
      if (warp == 11) {
#pragma unroll
        for (int i = 0; i < 4; i++)
          reinterpret_cast<uint4*>(smem + SM_ONES)[lane + 32 * i] = make_uint4(0x3F803F80u, 0x3F803F80u, 0x3F803F80u, 0x3F803F80u);
        fence_async_smem();
        __syncwarp();
        if (lane == 0) mbar_arrive(sb + SM_MISCB);
      }
      mbar_wait(sb + SM_MISCB);
      const unsigned epoch = *reinterpret_cast<volatile unsigned*>(smem + SM_EPOCH);
      const uint32_t T = (epoch & 1) ^ 1;
      if (warp == 11) {
        reinterpret_cast<float4*>(&g_kv[T][blockIdx.x * 128])[lane] = make_float4(0.f, 0.f, 0.f, 0.f);
        if (lane < 8) g_z[T][blockIdx.x * 8 + lane] = 0.f;
        mbar_wait(sb + SM_FULL + (ST_WK + 2) * 8);
        if (lane == 0) {
          asm volatile("cp.async.bulk.prefetch.L2.global [%0], 4096;" ::"l"((const char*)wo + blockIdx.x * 4096) : "memory");
          asm volatile("cp.async.bulk.prefetch.L2.global [%0], 11008;" ::"l"((const char*)wg_ + blockIdx.x * 11008) : "memory");
          asm volatile("cp.async.bulk.prefetch.L2.global [%0], 11008;" ::"l"((const char*)wu_ + blockIdx.x * 11008) : "memory");
          asm volatile("cp.async.bulk.prefetch.L2.global [%0], 11008;" ::"l"((const char*)wd_ + blockIdx.x * 11008) : "memory");
          const unsigned target = (epoch + 1) * 32;
          unsigned v; int it = 0;
#pragma unroll 1
          do {
            asm volatile("ld.acquire.gpu.global.u32 %0, [%1];" : "=r"(v) : "l"(&g_kvcnt[hg * 32]) : "memory");
            if (++it > (1 << 18)) break;
          } while ((int)(v - target) < 0);
          TS2(0, 26);
        }
        __syncwarp();
        {
          const char* src = reinterpret_cast<const char*>(&g_kv[T ^ 1][hg * 2048]) + lane * 16;
#pragma unroll 4
          for (int i = 0; i < 16; i++)
            asm volatile("cp.async.cg.shared.global [%0], [%1], 16;" ::"r"(sb + SM_KV32 + lane * 16 + i * 512), "l"(src + i * 512) : "memory");
          asm volatile("cp.async.cg.shared.global [%0], [%1], 16;" ::"r"(sb + SM_ONES + lane * 16), "l"(&g_z[T ^ 1][hg * 128 + lane * 4]) : "memory");
          asm volatile("cp.async.mbarrier.arrive.noinc.shared::cta.b64 [%0];" ::"r"(sb + SM_KVB) : "memory");
        }
      } else {
        const int w = warp - 9;
        st_rlx4(reinterpret_cast<uint4*>(&g_st[2 * rb + w][hg][0]) + lane, T ^ 1, T ^ 1, T ^ 1, T ^ 1);
        if (lane < 8) st_rlx4(&g_o[2 * rb + w][hg][lane >> 1][3][30 + (lane & 1)], T ^ 1, T ^ 1, T ^ 1, T ^ 1);
        st_rlx4(&g_part[2 * rb3 + w][(jf & 1) * 4 + (lane >> 3)][jf >> 1][(lane >> 1) & 3][3][30 + (lane & 1)], T ^ 1, T ^ 1, T ^ 1, T ^ 1);
        bar_sync(6 + w, 160);
        if (lane == 0) {
          asm volatile("fence.acq_rel.gpu;" ::: "memory");
          TS2(w, 25);
          asm volatile("red.relaxed.gpu.global.add.u32 [%0], 1;" ::"l"(&g_kvcnt[hg * 32]) : "memory");
        }
        mbar_wait(sb + SM_KVB);
        if (w == 0) { mbar_wait(sb + SM_EMPTY + 11 * 8); mbar_wait(sb + SM_EMPTY + 12 * 8); mbar_wait(sb + SM_EMPTY + 13 * 8); }
#pragma unroll 1
        for (int ph = 0; ph < 2; ph++) {
          const int use = 2 * ph + w, r = ph ? 2 * rb3 + w : 2 * rb + w;
          const uint32_t* pw = ph ? reinterpret_cast<const uint32_t*>(&g_st[r][lane >> 2][(lane & 3) * 16 + 15])
                                  : reinterpret_cast<const uint32_t*>(&g_o[r][lane >> 2][lane & 3][3][31]);
          const char* src = reinterpret_cast<const char*>(ph ? &g_h[r][0][0][0][0] : &g_o[r][0][0][0][0]);
          const uint32_t bf = sb + SM_XF + use * 32, be = sb + SM_XE + (use - 1) * 32;
          if (use > 0) mbar_wait(be);
          int it = 0;
#pragma unroll 1
          while (__any_sync(0xffffffffu, (ld_rlx1(pw) ^ T) & 1)) { if (++it > (1 << 18)) break; }
          if (lane == 0) {
            TS2(w, 27 + ph);
            if (ph) bulk_g2s(sb + SM_KV32 + w * 4096, &g_st[r][0][0], 4096, bf);
#pragma unroll
            for (int p = 0; p < 4; p++) {
              if (p > 0 && use > 0) mbar_wait(be + p * 8);
              bulk_g2s(sb + 2 * SLOT + p * 16384, src + p * 16384, 16384, bf + p * 8);
            }
          }
          __syncwarp();
        }
      }
    }
    asm volatile("barrier.cluster.arrive.relaxed.aligned;" ::: "memory");
    asm volatile("barrier.cluster.wait.aligned;" ::: "memory");
  }
}

typedef CUresult (*EncodeFn)(CUtensorMap*, CUtensorMapDataType, cuuint32_t, void*, const cuuint64_t*, const cuuint64_t*,
                             const cuuint32_t*, const cuuint32_t*, CUtensorMapInterleave, CUtensorMapSwizzle,
                             CUtensorMapL2promotion, CUtensorMapFloatOOBfill);

void encode(EncodeFn fn, CUtensorMap* m, const void* base, int rank, const cuuint64_t* dims, const cuuint64_t* strides,
            const cuuint32_t* box) {
  cuuint32_t es[3] = {1, 1, 1};
  fn(m, CU_TENSOR_MAP_DATA_TYPE_BFLOAT16, (cuuint32_t)rank, const_cast<void*>(base), dims, strides, box, es,
     CU_TENSOR_MAP_INTERLEAVE_NONE, CU_TENSOR_MAP_SWIZZLE_128B, CU_TENSOR_MAP_L2_PROMOTION_L2_256B,
     CU_TENSOR_MAP_FLOAT_OOB_FILL_NONE);
}

}

extern "C" void kernel_launch(void* const* d_in, const int* in_sizes, int n_in, void* d_out, int out_size) {
  (void)in_sizes; (void)n_in; (void)out_size;
  const __nv_bfloat16* x    = (const __nv_bfloat16*)d_in[0];
  const __nv_bfloat16* wqkv = (const __nv_bfloat16*)d_in[1];
  const __nv_bfloat16* wphi = (const __nv_bfloat16*)d_in[2];
  const __nv_bfloat16* wo   = (const __nv_bfloat16*)d_in[3];
  const __nv_bfloat16* wg   = (const __nv_bfloat16*)d_in[5];
  const __nv_bfloat16* wu   = (const __nv_bfloat16*)d_in[6];
  const __nv_bfloat16* wd   = (const __nv_bfloat16*)d_in[7];

  static EncodeFn fn = nullptr;
  static int reserved = 0;
  if (!fn) {
    void* p = nullptr;
    cudaDriverEntryPointQueryResult qr;
    cudaGetDriverEntryPoint("cuTensorMapEncodeTiled", &p, cudaEnableDefault, &qr);
    fn = (EncodeFn)p;
    cudaFuncSetAttribute(fused_kernel<1024>, cudaFuncAttributeMaxDynamicSharedMemorySize, SM_TOTAL);
    cudaFuncSetAttribute(fused_kernel<0>, cudaFuncAttributeMaxDynamicSharedMemorySize, SM_TOTAL);
    int dev = 0;
    cudaGetDevice(&dev);
    cudaDeviceGetAttribute(&reserved, cudaDevAttrReservedSharedMemoryPerBlock, dev);
  }
  Maps maps;
  {
    cuuint64_t d[3] = {64, 2048, 8}, s[2] = {1024, 128}; cuuint32_t b[3] = {64, 64, 3};
    encode(fn, &maps.x, x, 3, d, s, b);
  }
  {
    cuuint64_t d[2] = {1536, 512}, s[1] = {3072}; cuuint32_t b[2] = {64, 192};
    encode(fn, &maps.w, wqkv, 2, d, s, b);
  }
  {
    cuuint64_t d[2] = {512, 512}, s[1] = {1024}; cuuint32_t b[2] = {64, 192};
    encode(fn, &maps.wo, wo, 2, d, s, b);
  }
  {
    cuuint64_t d[3] = {176, 7, 512}, d7[3] = {144, 1, 512}, s[2] = {352, 2752}; cuuint32_t b[3] = {64, 1, 32};
    encode(fn, &maps.g, wg, 3, d, s, b);
    encode(fn, &maps.u, wu, 3, d, s, b);
    encode(fn, &maps.g7, wg + 1232, 3, d7, s, b);
    encode(fn, &maps.u7, wu + 1232, 3, d7, s, b);
  }
  {
    cuuint64_t d[2] = {512, 1376}, s[1] = {1024}; cuuint32_t b[2] = {64, 176};
    encode(fn, &maps.d, wd, 2, d, s, b);
  }
  if (reserved == 1024) fused_kernel<1024><<<NCTA, 384, SM_TOTAL>>>(maps, x, wphi, wo, wg, wu, wd, (__nv_bfloat16*)d_out);
  else fused_kernel<0><<<NCTA, 384, SM_TOTAL>>>(maps, x, wphi, wo, wg, wu, wd, (__nv_bfloat16*)d_out);
}
```

```cpp
#include <cuda_runtime.h>
#include <cuda_bf16.h>
#include <cuda.h>
#include <stdint.h>

#define PROF 0

#define SAFE_WAIT 0
#define THR 6

namespace {

constexpr int NCTA   = 128;
constexpr int SLOT   = 24576;
constexpr int NSLOT  = 9;
constexpr int NSTAGE = 47;

constexpr int ST_X0   = 0;
constexpr int ST_WK   = 3;
constexpr int ST_X1   = 6;
constexpr int ST_SCR0 = 9;
constexpr int ST_WV   = 10;
constexpr int ST_SCR1 = 13;
constexpr int ST_WQ   = 14;
constexpr int ST_WO   = 17;
constexpr int ST_XC   = 20;
constexpr int ST_GU   = 23;
constexpr int ST_D    = 39;

__host__ __device__ constexpr int st_empty_cnt(int d) {
  return ((d < 3 || (d >= 6 && d < 9) || (d >= ST_XC && d < ST_GU)) ? 4 : 2) * (d + 9 >= ST_GU ? 2 : 1);
}

constexpr int SM_ONES = NSLOT * SLOT;
constexpr int SM_WPHI = SM_ONES + 2048;
constexpr int SM_KVS  = SM_WPHI + 2048;
constexpr int SM_KV32 = 4 * SLOT + 16384;
constexpr int SM_BAR  = SM_KVS + 6144;
constexpr int SM_FULL  = SM_BAR;
constexpr int SM_EMPTY = SM_BAR + NSTAGE * 8;
constexpr int SM_MISCB = SM_BAR + 2 * NSTAGE * 8;
constexpr int SM_KVB   = SM_MISCB + 8;
constexpr int SM_EPOCH = SM_KVB + 8;
constexpr int SM_XF    = SM_EPOCH + 8;
constexpr int SM_XE    = SM_XF + 16 * 8;
constexpr int SM_TOTAL = SM_BAR + 1024;

static_assert(SM_TOTAL == 232448 && SM_XE + 12 * 8 <= SM_TOTAL, "smem budget");

struct Maps { CUtensorMap x, w, wo, g, u, g7, u7, d; };

__device__ uint4    g_o[32][8][4][4][32];
__device__ uint4    g_h[32][8][4][4][32];
__device__ uint32_t g_hx[32][8][4][32];
__device__ uint2    g_st[32][8][64];
__device__ uint4    g_hh[32][8][11][4][32];
__device__ uint4    g_part[32][8][4][4][4][32];
__device__ float    g_kv[2][32 * 32 * 16];
__device__ float    g_z[2][32 * 32];
__device__ unsigned g_kvcnt[8 * 32];
__device__ unsigned g_start;

__device__ __forceinline__ uint32_t smem_u32(const void* p) { return (uint32_t)__cvta_generic_to_shared(p); }
__device__ __forceinline__ void mbar_init(uint32_t bar, int cnt) {
  asm volatile("mbarrier.init.shared::cta.b64 [%0], %1;" ::"r"(bar), "r"(cnt) : "memory");
}
__device__ __forceinline__ void mbar_expect_tx(uint32_t bar, uint32_t bytes) {
  asm volatile("mbarrier.arrive.expect_tx.shared::cta.b64 _, [%0], %1;" ::"r"(bar), "r"(bytes) : "memory");
}
__device__ __forceinline__ void mbar_arrive(uint32_t bar) {
  asm volatile("mbarrier.arrive.shared::cta.b64 _, [%0];" ::"r"(bar) : "memory");
}
__device__ __forceinline__ void mbar_arrive_cluster(uint32_t bar, uint32_t rank) {
  asm volatile("{\n.reg .b32 ra;\nmapa.shared::cluster.u32 ra, %0, %1;\n"
               "mbarrier.arrive.shared::cluster.b64 _, [ra];\n}" ::"r"(bar), "r"(rank) : "memory");
}
__device__ __forceinline__ void mbar_wait_p(uint32_t bar, uint32_t parity) {
  asm volatile("{\n.reg .pred p;\nW: mbarrier.try_wait.parity.shared::cta.b64 p, [%0], %1;\n@!p bra W;\n}" ::"r"(bar), "r"(parity) : "memory");
}
__device__ __forceinline__ void mbar_wait(uint32_t bar) { mbar_wait_p(bar, 0); }
__device__ __forceinline__ void bar_sync(int id, int n)   { asm volatile("bar.sync %0, %1;" ::"r"(id), "r"(n) : "memory"); }
__device__ __forceinline__ void bar_arrive(int id, int n) { asm volatile("bar.arrive %0, %1;" ::"r"(id), "r"(n) : "memory"); }
__device__ __forceinline__ void fence_async_smem() { asm volatile("fence.proxy.async.shared::cta;" ::: "memory"); }
__device__ __forceinline__ void wg_fence()  { asm volatile("wgmma.fence.sync.aligned;" ::: "memory"); }
__device__ __forceinline__ void wg_commit() { asm volatile("wgmma.commit_group.sync.aligned;" ::: "memory"); }
template <int N> __device__ __forceinline__ void wg_wait() { asm volatile("wgmma.wait_group.sync.aligned %0;" ::"n"(N) : "memory"); }
#define DESC(off) (db + ((uint32_t)(off) >> 4))
__device__ __forceinline__ void tma2d(uint32_t dst, const CUtensorMap* m, int c0, int c1, uint32_t bar) {
  asm volatile("cp.async.bulk.tensor.2d.shared::cluster.global.mbarrier::complete_tx::bytes [%0], [%1, {%3, %4}], [%2];"
               ::"r"(dst), "l"(m), "r"(bar), "r"(c0), "r"(c1) : "memory");
}
__device__ __forceinline__ void tma2d_mc(uint32_t dst, const CUtensorMap* m, int c0, int c1, uint32_t bar) {
  asm volatile("cp.async.bulk.tensor.2d.shared::cluster.global.mbarrier::complete_tx::bytes.multicast::cluster [%0], [%1, {%3, %4}], [%2], %5;"
               ::"r"(dst), "l"(m), "r"(bar), "r"(c0), "r"(c1), "h"((uint16_t)3) : "memory");
}
__device__ __forceinline__ void tma3d(uint32_t dst, const CUtensorMap* m, int c0, int c1, int c2, uint32_t bar) {
  asm volatile("cp.async.bulk.tensor.3d.shared::cluster.global.mbarrier::complete_tx::bytes [%0], [%1, {%3, %4, %5}], [%2];"
               ::"r"(dst), "l"(m), "r"(bar), "r"(c0), "r"(c1), "r"(c2) : "memory");
}
__device__ __forceinline__ void tma3d_mc(uint32_t dst, const CUtensorMap* m, int c0, int c1, int c2, uint32_t bar) {
  asm volatile("cp.async.bulk.tensor.3d.shared::cluster.global.mbarrier::complete_tx::bytes.multicast::cluster [%0], [%1, {%3, %4, %5}], [%2], %6;"
               ::"r"(dst), "l"(m), "r"(bar), "r"(c0), "r"(c1), "r"(c2), "h"((uint16_t)3) : "memory");
}
__device__ __forceinline__ void ldsm4(uint32_t (&r)[4], uint32_t addr) {
  asm volatile("ldmatrix.sync.aligned.m8n8.x4.shared.b16 {%0,%1,%2,%3}, [%4];"
               : "=r"(r[0]), "=r"(r[1]), "=r"(r[2]), "=r"(r[3]) : "r"(addr) : "memory");
}
__device__ __forceinline__ void ldsm4t(uint32_t (&r)[4], uint32_t addr) {
  asm volatile("ldmatrix.sync.aligned.m8n8.x4.trans.shared.b16 {%0,%1,%2,%3}, [%4];"
               : "=r"(r[0]), "=r"(r[1]), "=r"(r[2]), "=r"(r[3]) : "r"(addr) : "memory");
}
__device__ __forceinline__ void stsm4(uint32_t addr, uint32_t r0, uint32_t r1, uint32_t r2, uint32_t r3) {
  asm volatile("stmatrix.sync.aligned.m8n8.x4.shared.b16 [%0], {%1,%2,%3,%4};"
               ::"r"(addr), "r"(r0), "r"(r1), "r"(r2), "r"(r3) : "memory");
}
__device__ __forceinline__ void mma16816(float (&c)[4], const uint32_t (&a)[4], uint32_t b0, uint32_t b1) {
  asm volatile("mma.sync.aligned.m16n8k16.row.col.f32.bf16.bf16.f32 {%0,%1,%2,%3},{%4,%5,%6,%7},{%8,%9},{%0,%1,%2,%3};"
               : "+f"(c[0]), "+f"(c[1]), "+f"(c[2]), "+f"(c[3])
               : "r"(a[0]), "r"(a[1]), "r"(a[2]), "r"(a[3]), "r"(b0), "r"(b1));
}
__device__ __forceinline__ void add_frag(float (&c)[32], const uint32_t (&a)[4][4], uint32_t id) {
#pragma unroll
  for (int s = 0; s < 4; s++) {
    mma16816(*reinterpret_cast<float (*)[4]>(&c[8 * s]), a[s], id, 0u);
    mma16816(*reinterpret_cast<float (*)[4]>(&c[8 * s + 4]), a[s], 0u, id);
  }
}
__device__ __forceinline__ uint32_t pack2(float lo, float hi) {
  uint32_t r; asm("cvt.rn.bf16x2.f32 %0, %1, %2;" : "=r"(r) : "f"(hi), "f"(lo)); return r;
}
__device__ __forceinline__ float blo(uint32_t w) { return __uint_as_float(w << 16); }
__device__ __forceinline__ float bhi(uint32_t w) { return __uint_as_float(w & 0xFFFF0000u); }
__device__ __forceinline__ uint32_t hsub2(uint32_t a, uint32_t b) { uint32_t r; asm("sub.rn.bf16x2 %0, %1, %2;" : "=r"(r) : "r"(a), "r"(b)); return r; }
__device__ __forceinline__ uint32_t hmax2(uint32_t a, uint32_t b) { uint32_t r; asm("max.bf16x2 %0, %1, %2;" : "=r"(r) : "r"(a), "r"(b)); return r; }
__device__ __forceinline__ uint32_t hmin2(uint32_t a, uint32_t b) { uint32_t r; asm("min.bf16x2 %0, %1, %2;" : "=r"(r) : "r"(a), "r"(b)); return r; }
__device__ __forceinline__ float ex2(float x) { float r; asm("ex2.approx.ftz.f32 %0, %1;" : "=f"(r) : "f"(x)); return r; }
__device__ __forceinline__ float rcp(float x) { float r; asm("rcp.approx.ftz.f32 %0, %1;" : "=f"(r) : "f"(x)); return r; }
__device__ __forceinline__ void ld_rlx4(uint32_t (&r)[4], const uint4* p) {
  asm volatile("{\n.reg .b128 v;\nld.relaxed.gpu.global.b128 v, [%4];\nmov.b128 {%0,%1,%2,%3}, v;\n}"
               : "=r"(r[0]), "=r"(r[1]), "=r"(r[2]), "=r"(r[3]) : "l"(p) : "memory");
}
__device__ __forceinline__ void st_rlx4(uint4* p, uint32_t a, uint32_t b, uint32_t c, uint32_t d) {
  asm volatile("{\n.reg .b128 v;\nmov.b128 v, {%1,%2,%3,%4};\nst.relaxed.gpu.global.b128 [%0], v;\n}"
               ::"l"(p), "r"(a), "r"(b), "r"(c), "r"(d) : "memory");
}
__device__ __forceinline__ void st_rlx2(uint2* p, uint32_t a, uint32_t b) {
  asm volatile("{\n.reg .b64 v;\nmov.b64 v, {%1,%2};\nst.relaxed.gpu.global.b64 [%0], v;\n}" ::"l"(p), "r"(a), "r"(b) : "memory");
}
__device__ __forceinline__ uint32_t ld_rlx1(const uint32_t* p) {
  uint32_t r; asm volatile("ld.relaxed.gpu.global.b32 %0, [%1];" : "=r"(r) : "l"(p) : "memory"); return r;
}
__device__ __forceinline__ void st_rlx1(uint32_t* p, uint32_t a) {
  asm volatile("st.relaxed.gpu.global.b32 [%0], %1;" ::"l"(p), "r"(a) : "memory");
}
__device__ __forceinline__ void ld_rlx2(uint32_t& a, uint32_t& b, const uint2* p) {
  asm volatile("{\n.reg .b64 v;\nld.relaxed.gpu.global.b64 v, [%2];\nmov.b64 {%0,%1}, v;\n}" : "=r"(a), "=r"(b) : "l"(p) : "memory");
}
__device__ __forceinline__ void bulk_g2s(uint32_t dst, const void* src, uint32_t bytes, uint32_t bar) {
  asm volatile("cp.async.bulk.shared::cluster.global.mbarrier::complete_tx::bytes [%0], [%1], %2, [%3];"
               ::"r"(dst), "l"(src), "r"(bytes), "r"(bar) : "memory");
}
__device__ __forceinline__ uint32_t tg(uint32_t w, uint32_t T) { return (w & 0xFFFFFFFEu) | T; }
__device__ __forceinline__ uint32_t bad4(uint32_t a, uint32_t b, uint32_t c, uint32_t d, uint32_t T) {
  uint32_t u, v;
  asm("lop3.b32 %0, %1, %2, %3, 0x7E;" : "=r"(u) : "r"(a), "r"(b), "r"(T));
  asm("lop3.b32 %0, %1, %2, %3, 0x7E;" : "=r"(v) : "r"(c), "r"(d), "r"(T));
  asm("lop3.b32 %0, %1, %2, 1, 0xA8;" : "=r"(u) : "r"(u), "r"(v));
  return u;
}

__device__ __forceinline__ void ld_chunk(uint32_t (&a)[4][4], const uint4* p) {
#pragma unroll
  for (int s = 0; s < 4; s++) ld_rlx4(a[s], p + s * 32);
}
__device__ __forceinline__ void lds_chunk(uint32_t (&a)[4][4], uint32_t addr) {
#pragma unroll
  for (int s = 0; s < 4; s++)
    asm volatile("ld.shared.v4.b32 {%0,%1,%2,%3}, [%4];" : "=r"(a[s][0]), "=r"(a[s][1]), "=r"(a[s][2]), "=r"(a[s][3])
                 : "r"(addr + s * 512) : "memory");
}
__device__ __forceinline__ void chk_pair(uint32_t (&a)[4][4], uint32_t (&b)[4][4], const uint4* p, uint32_t T) {
  int it = 0;
#pragma unroll 1
  while (__any_sync(0xffffffffu, bad4(a[0][0], a[1][0], a[2][0], a[3][0], T) | bad4(b[0][0], b[1][0], b[2][0], b[3][0], T))) {
    ld_chunk(a, p); ld_chunk(b, p + 512);
    if (++it > (1 << 18)) break;
  }
}

__device__ __forceinline__ void wgmma_rs_n48(float (&d)[24], const uint32_t (&a)[4], uint32_t descB, int scaleD) {
  asm volatile("{\n.reg .pred p;\n.reg .b64 db;\nsetp.ne.b32 p, %29, 0;\nmov.b64 db, {%28, 0x40000040};\n"
    "wgmma.mma_async.sync.aligned.m64n48k16.f32.bf16.bf16 {%0,%1,%2,%3,%4,%5,%6,%7,%8,%9,%10,%11,%12,%13,%14,%15,%16,%17,%18,%19,%20,%21,%22,%23}, {%24,%25,%26,%27}, db, p, 1, 1, 1;\n}\n"
    : "+f"(d[0]),"+f"(d[1]),"+f"(d[2]),"+f"(d[3]),"+f"(d[4]),"+f"(d[5]),"+f"(d[6]),"+f"(d[7]),"+f"(d[8]),"+f"(d[9]),"+f"(d[10]),"+f"(d[11]),"+f"(d[12]),"+f"(d[13]),"+f"(d[14]),"+f"(d[15]),"+f"(d[16]),"+f"(d[17]),"+f"(d[18]),"+f"(d[19]),"+f"(d[20]),"+f"(d[21]),"+f"(d[22]),"+f"(d[23])
    : "r"(a[0]), "r"(a[1]), "r"(a[2]), "r"(a[3]), "r"(descB), "r"(scaleD));
}
__device__ __forceinline__ void wgmma_rs_n64(float (&d)[32], const uint32_t (&a)[4], uint32_t descB, int scaleD) {
  asm volatile("{\n.reg .pred p;\n.reg .b64 db;\nsetp.ne.b32 p, %37, 0;\nmov.b64 db, {%36, 0x40000040};\n"
    "wgmma.mma_async.sync.aligned.m64n64k16.f32.bf16.bf16 {%0,%1,%2,%3,%4,%5,%6,%7,%8,%9,%10,%11,%12,%13,%14,%15,%16,%17,%18,%19,%20,%21,%22,%23,%24,%25,%26,%27,%28,%29,%30,%31}, {%32,%33,%34,%35}, db, p, 1, 1, 1;\n}\n"
    : "+f"(d[0]),"+f"(d[1]),"+f"(d[2]),"+f"(d[3]),"+f"(d[4]),"+f"(d[5]),"+f"(d[6]),"+f"(d[7]),"+f"(d[8]),"+f"(d[9]),"+f"(d[10]),"+f"(d[11]),"+f"(d[12]),"+f"(d[13]),"+f"(d[14]),"+f"(d[15]),"+f"(d[16]),"+f"(d[17]),"+f"(d[18]),"+f"(d[19]),"+f"(d[20]),"+f"(d[21]),"+f"(d[22]),"+f"(d[23]),"+f"(d[24]),"+f"(d[25]),"+f"(d[26]),"+f"(d[27]),"+f"(d[28]),"+f"(d[29]),"+f"(d[30]),"+f"(d[31])
    : "r"(a[0]), "r"(a[1]), "r"(a[2]), "r"(a[3]), "r"(descB), "r"(scaleD));
}
__device__ __forceinline__ void wgmma_rs_n128(float (&d)[64], const uint32_t (&a)[4], uint32_t descB, int scaleD) {
  asm volatile("{\n.reg .pred p;\n.reg .b64 db;\nsetp.ne.b32 p, %69, 0;\nmov.b64 db, {%68, 0x40000040};\n"
    "wgmma.mma_async.sync.aligned.m64n128k16.f32.bf16.bf16 {%0,%1,%2,%3,%4,%5,%6,%7,%8,%9,%10,%11,%12,%13,%14,%15,%16,%17,%18,%19,%20,%21,%22,%23,%24,%25,%26,%27,%28,%29,%30,%31,%32,%33,%34,%35,%36,%37,%38,%39,%40,%41,%42,%43,%44,%45,%46,%47,%48,%49,%50,%51,%52,%53,%54,%55,%56,%57,%58,%59,%60,%61,%62,%63}, {%64,%65,%66,%67}, db, p, 1, 1, 1;\n}\n"
    : "+f"(d[0]),"+f"(d[1]),"+f"(d[2]),"+f"(d[3]),"+f"(d[4]),"+f"(d[5]),"+f"(d[6]),"+f"(d[7]),"+f"(d[8]),"+f"(d[9]),"+f"(d[10]),"+f"(d[11]),"+f"(d[12]),"+f"(d[13]),"+f"(d[14]),"+f"(d[15]),"+f"(d[16]),"+f"(d[17]),"+f"(d[18]),"+f"(d[19]),"+f"(d[20]),"+f"(d[21]),"+f"(d[22]),"+f"(d[23]),"+f"(d[24]),"+f"(d[25]),"+f"(d[26]),"+f"(d[27]),"+f"(d[28]),"+f"(d[29]),"+f"(d[30]),"+f"(d[31]),"+f"(d[32]),"+f"(d[33]),"+f"(d[34]),"+f"(d[35]),"+f"(d[36]),"+f"(d[37]),"+f"(d[38]),"+f"(d[39]),"+f"(d[40]),"+f"(d[41]),"+f"(d[42]),"+f"(d[43]),"+f"(d[44]),"+f"(d[45]),"+f"(d[46]),"+f"(d[47]),"+f"(d[48]),"+f"(d[49]),"+f"(d[50]),"+f"(d[51]),"+f"(d[52]),"+f"(d[53]),"+f"(d[54]),"+f"(d[55]),"+f"(d[56]),"+f"(d[57]),"+f"(d[58]),"+f"(d[59]),"+f"(d[60]),"+f"(d[61]),"+f"(d[62]),"+f"(d[63])
    : "r"(a[0]), "r"(a[1]), "r"(a[2]), "r"(a[3]), "r"(descB), "r"(scaleD));
}
__device__ __forceinline__ void wgmma_ss_n72_t11(float (&d)[36], uint32_t descA, uint32_t descB, int scaleD) {
  asm volatile("{\n.reg .pred p;\n.reg .b64 da, db;\nsetp.ne.b32 p, %38, 0;\nmov.b64 da, {%36, 0x40000040};\nmov.b64 db, {%37, 0x40000040};\n"
    "wgmma.mma_async.sync.aligned.m64n72k16.f32.bf16.bf16 {%0,%1,%2,%3,%4,%5,%6,%7,%8,%9,%10,%11,%12,%13,%14,%15,%16,%17,%18,%19,%20,%21,%22,%23,%24,%25,%26,%27,%28,%29,%30,%31,%32,%33,%34,%35}, da, db, p, 1, 1, 1, 1;\n}\n"
    : "+f"(d[0]),"+f"(d[1]),"+f"(d[2]),"+f"(d[3]),"+f"(d[4]),"+f"(d[5]),"+f"(d[6]),"+f"(d[7]),"+f"(d[8]),"+f"(d[9]),"+f"(d[10]),"+f"(d[11]),"+f"(d[12]),"+f"(d[13]),"+f"(d[14]),"+f"(d[15]),"+f"(d[16]),"+f"(d[17]),"+f"(d[18]),"+f"(d[19]),"+f"(d[20]),"+f"(d[21]),"+f"(d[22]),"+f"(d[23]),"+f"(d[24]),"+f"(d[25]),"+f"(d[26]),"+f"(d[27]),"+f"(d[28]),"+f"(d[29]),"+f"(d[30]),"+f"(d[31]),"+f"(d[32]),"+f"(d[33]),"+f"(d[34]),"+f"(d[35])
    : "r"(descA), "r"(descB), "r"(scaleD));
}

#define TSTAMP(i) do {} while (0)
#define TS2(w, i) do {} while (0)

constexpr float LOG2E = 1.4426950408889634f;

__device__ __forceinline__ void feat_exp(const uint32_t (&P)[4], float (&e)[16]) {
  uint32_t a = hmax2(P[0], P[2]), b = hmax2(P[1], P[3]);
  uint32_t mx = hmax2(__byte_perm(a, b, 0x5410), __byte_perm(a, b, 0x7632));
  a = hmin2(P[0], P[2]); b = hmin2(P[1], P[3]);
  uint32_t mn = hmin2(__byte_perm(a, b, 0x5410), __byte_perm(a, b, 0x7632));
  mx = hmax2(mx, __shfl_xor_sync(0xffffffffu, mx, 1));
  mn = hmin2(mn, __shfl_xor_sync(0xffffffffu, mn, 1));
  mx = hmax2(mx, __shfl_xor_sync(0xffffffffu, mx, 2));
  mn = hmin2(mn, __shfl_xor_sync(0xffffffffu, mn, 2));
  float mx0 = -blo(mx) * LOG2E, mx1 = -bhi(mx) * LOG2E, mn0 = blo(mn) * LOG2E, mn1 = bhi(mn) * LOG2E;
  float v[8] = {blo(P[0]), bhi(P[0]), blo(P[1]), bhi(P[1]), blo(P[2]), bhi(P[2]), blo(P[3]), bhi(P[3])};
#pragma unroll
  for (int i = 0; i < 8; i++) {
    bool r1 = (i >> 1) & 1;
    e[i]     = ex2(fmaf(v[i],  LOG2E, r1 ? mx1 : mx0));
    e[8 + i] = ex2(fmaf(v[i], -LOG2E, r1 ? mn1 : mn0));
  }
}

template <int SBASE>
__global__ void __cluster_dims__(2, 1, 1) __launch_bounds__(384, 1)
fused_kernel(const __grid_constant__ Maps maps, const __nv_bfloat16* __restrict__ x, const __nv_bfloat16* __restrict__ wphi,
             const __nv_bfloat16* __restrict__ wo, const __nv_bfloat16* __restrict__ wg_, const __nv_bfloat16* __restrict__ wu_,
             const __nv_bfloat16* __restrict__ wd_, __nv_bfloat16* __restrict__ out) {
  extern __shared__ __align__(1024) unsigned char smem[];
  const uint32_t sb = smem_u32(smem);
  const int tid = threadIdx.x, lane = tid & 31;
  const int warp = __shfl_sync(0xffffffffu, tid >> 5, 0);
  const uint32_t rank = blockIdx.x & 1;
  const int cl = blockIdx.x >> 1;
  int quad, qi;
  if (cl < 4) { quad = 15; qi = cl; }
  else if (cl < 36) { quad = (cl - 4) & 7; qi = (cl - 4) >> 3; }
  else { qi = (cl - 36) / 7; quad = 8 + (cl - 36) - 7 * qi; }
  const int rb = quad, hg = 2 * qi + rank;
  const int rb3 = (quad & ~1) + rank, jf = 4 * (quad & 1) + qi;

  if (warp < 8) {
    asm volatile("setmaxnreg.inc.sync.aligned.u32 240;");
    if (lane == 0) {
#pragma unroll 1
      for (int d = warp; d + 9 < NSTAGE; d += 8) {
        mbar_init(sb + SM_EMPTY + d * 8, st_empty_cnt(d));
        {
          mbar_init(sb + SM_FULL + (d + 9) * 8, 1);
          mbar_expect_tx(sb + SM_FULL + (d + 9) * 8, d + 9 >= ST_D ? 22528 : SLOT);
        }
      }
      asm volatile("fence.mbarrier_init.release.cluster;" ::: "memory");
    }
    __syncwarp();
    bar_sync(0, 352);
    asm volatile("barrier.cluster.arrive.relaxed.aligned;" ::: "memory");
    const int wg = warp >> 2, wq = warp & 3, g = lane >> 2, t = lane & 3;
    const bool lead = (tid & 127) == 0;
    const uint32_t db = ((SBASE ? (uint32_t)SBASE : (sb & 0x3FFFF)) >> 4) | (512u << 16);
    auto release = [&](int d) {
      const int s = d + NSLOT;
      mbar_arrive_cluster(sb + SM_EMPTY + d * 8, s >= ST_GU ? (uint32_t)(s & 1) : rank);
    };
    const uint32_t lrow = (uint32_t)(wq * 16 + (lane & 7) + ((lane >> 3) & 1) * 8) * 128;
    const uint32_t lx = lane & 7, lhi = lane >> 4;
    if (wg == 1) bar_arrive(4, 256);

    float r0, r1;
    uint32_t E[4][8];
    uint32_t T = 0;
    {
      uint32_t A[32][4];
      const int sx = wg ? ST_X1 : ST_X0;
      {
        const uint32_t base = sb + sx * SLOT + lrow;
        float cs[2][4], c0[2][4], c1[2][4];
#pragma unroll
        for (int i = 0; i < 4; i++) { cs[0][i] = cs[1][i] = c0[0][i] = c0[1][i] = c1[0][i] = c1[1][i] = 0.f; }
#pragma unroll
        for (int c = 0; c < 8; c++) {
          if (c % 3 == 0) mbar_wait(sb + SM_FULL + (sx + c / 3) * 8);
#pragma unroll
          for (int k = 0; k < 4; k++) ldsm4(A[4 * c + k], base + c * 8192 + (((2 * k + lhi) ^ lx) << 4));
#pragma unroll
          for (int k = 0; k < 4; k++) {
            const uint32_t (&f)[4] = A[4 * c + k];
            mma16816(cs[k & 1], f, 0x3F803F80u, 0x3F803F80u);
            mma16816(c0[k & 1], f, f[0], f[2]);
            mma16816(c1[k & 1], f, f[1], f[3]);
          }
        }
        const float s0 = (cs[0][0] + cs[1][0]) * (1.f / 512.f), s1 = (cs[0][2] + cs[1][2]) * (1.f / 512.f);
        asm volatile("barrier.cluster.wait.aligned;" ::: "memory");
        if (lane < 3) release(sx + lane);
        const uint32_t m0 = pack2(s0, s0), m1 = pack2(s1, s1);
        float q0 = (g & 1) ? c0[0][1] + c0[1][1] : c0[0][0] + c0[1][0];
        float q1 = (g & 1) ? c1[0][3] + c1[1][3] : c1[0][2] + c1[1][2];
        q0 = __shfl_sync(0xffffffffu, q0, (lane & ~3) | (g >> 1));
        q1 = __shfl_sync(0xffffffffu, q1, (lane & ~3) | (g >> 1));
        r0 = rsqrtf(fmaxf(q0 * (1.f / 512.f) - s0 * s0, 0.f) + 1e-5f);
        r1 = rsqrtf(fmaxf(q1 * (1.f / 512.f) - s1 * s1, 0.f) + 1e-5f);
#pragma unroll
        for (int ks = 0; ks < 32; ks++) {
          A[ks][0] = hsub2(A[ks][0], m0); A[ks][1] = hsub2(A[ks][1], m1);
          A[ks][2] = hsub2(A[ks][2], m0); A[ks][3] = hsub2(A[ks][3], m1);
        }
      }
      TSTAMP(1);
      const uint32_t wpa = sb + SM_WPHI + ((lane & 7) + ((lane >> 3) & 1) * 8) * 32 + lhi * 16;
      const uint32_t scr = sb + (wg ? (ST_SCR1 % NSLOT) : (ST_SCR0 % NSLOT)) * SLOT;
#pragma unroll 1
      for (int ps = 0; ps < 3; ps++) {
        const int st0 = ps == 0 ? ST_WK : (ps == 1 ? ST_WV : ST_WQ);
        const uint32_t wdesc = DESC((ps == 0 ? ST_WK % NSLOT : (ps == 1 ? ST_WV % NSLOT : ST_WQ % NSLOT)) * SLOT);
        float acc[32];
        bar_sync(4 + wg, 256);
#pragma unroll
        for (int i = 0; i < 3; i++) {
          mbar_wait(sb + SM_FULL + (st0 + i) * 8);
          wg_fence();
#pragma unroll
          for (int kk = 0; kk < (i < 2 ? 12 : 8); kk++)
            wgmma_rs_n64(acc, A[12 * i + kk], wdesc + ((i * SLOT + kk * 2048) >> 4), (i | kk) != 0);
          wg_commit();
          if (i == 1) { wg_wait<1>(); if (lead) release(st0); }
        }
        if (ps == 0 || wg == 0) bar_arrive(4 + (wg ^ 1), 256);
        uint32_t a[4][4], b[4][4];
        mbar_wait(sb + SM_MISCB);
        T = (*reinterpret_cast<volatile unsigned*>(smem + SM_EPOCH) & 1) ^ 1;
#pragma unroll
        for (int h = 0; h < 4; h++) ldsm4t(b[h], wpa + h * 512);
        wg_wait<0>();
        if ((tid & 127) < 2) release(st0 + 1 + (tid & 1));
        TSTAMP(2 + 2 * ps);
#pragma unroll
        for (int h = 0; h < 4; h++) {
          a[h][0] = pack2(acc[8 * h + 0] * r0, acc[8 * h + 1] * r0); a[h][1] = pack2(acc[8 * h + 2] * r1, acc[8 * h + 3] * r1);
          a[h][2] = pack2(acc[8 * h + 4] * r0, acc[8 * h + 5] * r0); a[h][3] = pack2(acc[8 * h + 6] * r1, acc[8 * h + 7] * r1);
        }
        if (ps != 1) {
          {
            float pp[4][2][4];
#pragma unroll
            for (int h = 0; h < 4; h++) {
#pragma unroll
              for (int i = 0; i < 4; i++) { pp[h][0][i] = 0.f; pp[h][1][i] = 0.f; }
              mma16816(pp[h][0], a[h], b[h][0], b[h][1]);
              mma16816(pp[h][1], a[h], b[h][2], b[h][3]);
            }
#pragma unroll
            for (int h = 0; h < 4; h++) {
              a[h][0] = pack2(pp[h][0][0], pp[h][0][1]); a[h][1] = pack2(pp[h][0][2], pp[h][0][3]);
              a[h][2] = pack2(pp[h][1][0], pp[h][1][1]); a[h][3] = pack2(pp[h][1][2], pp[h][1][3]);
            }
          }
          if (ps == 0) mbar_wait(sb + SM_EMPTY + (wg ? ST_SCR1 - NSLOT : ST_SCR0 - NSLOT) * 8);
#pragma unroll 1
          for (int hp = 0; hp < 2; hp++) {
            float e[2][16];
            feat_exp(a[0], e[0]);
            feat_exp(a[1], e[1]);
            if (ps == 0) {
#pragma unroll
              for (int h = 0; h < 2; h++) {
                const float (&f)[16] = e[h];
                float sp0 = (f[0] + f[1]) + (f[4] + f[5]), sp1 = (f[2] + f[3]) + (f[6] + f[7]);
                float sn0 = (f[8] + f[9]) + (f[12] + f[13]), sn1 = (f[10] + f[11]) + (f[14] + f[15]);
                sp0 += __shfl_xor_sync(0xffffffffu, sp0, 1); sp1 += __shfl_xor_sync(0xffffffffu, sp1, 1);
                sn0 += __shfl_xor_sync(0xffffffffu, sn0, 1); sn1 += __shfl_xor_sync(0xffffffffu, sn1, 1);
                sp0 += __shfl_xor_sync(0xffffffffu, sp0, 2); sp1 += __shfl_xor_sync(0xffffffffu, sp1, 2);
                sn0 += __shfl_xor_sync(0xffffffffu, sn0, 2); sn1 += __shfl_xor_sync(0xffffffffu, sn1, 2);
                sp0 = rcp(sp0); sp1 = rcp(sp1); sn0 = rcp(sn0); sn1 = rcp(sn1);
                const uint32_t dst = scr + hp * 8192 + lrow;
                stsm4(dst + (((h * 4 + lhi) ^ lx) << 4), pack2(f[0] * sp0, f[1] * sp0), pack2(f[2] * sp1, f[3] * sp1),
                      pack2(f[4] * sp0, f[5] * sp0), pack2(f[6] * sp1, f[7] * sp1));
                stsm4(dst + (((h * 4 + 2 + lhi) ^ lx) << 4), pack2(f[8] * sn0, f[9] * sn0), pack2(f[10] * sn1, f[11] * sn1),
                      pack2(f[12] * sn0, f[13] * sn0), pack2(f[14] * sn1, f[15] * sn1));
              }
            } else {
#pragma unroll
              for (int i = 0; i < 16; i++) {
                A[i >> 2][i & 3] = A[4 + (i >> 2)][i & 3];
                A[4 + (i >> 2)][i & 3] = pack2(e[i >> 3][2 * (i & 7)], e[i >> 3][2 * (i & 7) + 1]);
              }
            }
#pragma unroll
            for (int i = 0; i < 4; i++) { a[0][i] = a[2][i]; a[1][i] = a[3][i]; }
          }
        } else {
#pragma unroll
          for (int h = 0; h < 4; h++) stsm4(scr + 16384 + lrow + (((2 * h + lhi) ^ lx) << 4), a[h][0], a[h][1], a[h][2], a[h][3]);
          fence_async_smem();
          bar_sync(3, 256);
          float kv[36];
          wg_fence();
#pragma unroll
          for (int ks = 0; ks < 8; ks++) {
            const uint32_t sk = (ks < 4 ? (ST_SCR0 % NSLOT) : (ST_SCR1 % NSLOT)) * SLOT + (ks & 3) * 2048;
            const uint32_t dv = (DESC(sk + 16384) & 0xFFFFu) | (((SM_ONES - sk - 16384) >> 4) << 16);
            wgmma_ss_n72_t11(kv, DESC(sk) + wg * 512, dv, ks != 0);
          }
          wg_commit();
          if (wg == 1) bar_arrive(4, 256);
          wg_wait<0>();
          if (lead) { mbar_arrive(sb + SM_EMPTY + ST_SCR0 * 8); mbar_arrive(sb + SM_EMPTY + ST_SCR1 * 8); }
          const int hl = 2 * wg + (wq >> 1), f = (wq & 1) * 16 + g;
          float* kvp = &g_kv[T ^ 1][((hg * 4 + hl) * 32 + f) * 16 + 2 * t];
          float* zp = &g_z[T ^ 1][(hg * 4 + hl) * 32 + f];
          float c[8];
#pragma unroll
          for (int i = 0; i < 8; i++) c[i] = hl >= 2 ? (hl == 3 ? kv[24 + i] : kv[16 + i]) : (hl == 1 ? kv[8 + i] : kv[i]);
#pragma unroll
          for (int n = 0; n < 2; n++) {
            asm volatile("red.relaxed.gpu.global.add.v2.f32 [%0], {%1,%2};" ::"l"(kvp + n * 8), "f"(c[4 * n]), "f"(c[4 * n + 1]) : "memory");
            asm volatile("red.relaxed.gpu.global.add.v2.f32 [%0], {%1,%2};" ::"l"(kvp + n * 8 + 128), "f"(c[4 * n + 2]), "f"(c[4 * n + 3]) : "memory");
          }
          if (t < 2) asm volatile("red.relaxed.gpu.global.add.f32 [%0], %1;" ::"l"(zp + t * 8), "f"(t ? kv[34] : kv[32]) : "memory");
          bar_arrive(6 + wg, 160);
        }
        TSTAMP(3 + 2 * ps);
      }
#pragma unroll
      for (int i = 0; i < 32; i++) E[i >> 3][i & 7] = A[i >> 2][i & 3];
    }
    const int rh = 2 * rb + wg;
#define IDF ((g >> 1) == t ? ((g & 1) ? 0x3F800000u : 0x00003F80u) : 0u)
    const uint32_t xb = sb + 2 * SLOT + wq * 2048 + lane * 16;
    mbar_wait(sb + SM_KVB);
    {
      const int r = tid & 127;
      const float4* src = reinterpret_cast<const float4*>(smem + SM_KV32) + r;
#pragma unroll
      for (int i = 0; i < 4; i++) {
        const float4 a = src[i * 128];
        *reinterpret_cast<uint2*>(smem + SM_KVS + (i * 32 + (r >> 2)) * 48 + (r & 3) * 8) = make_uint2(pack2(a.x, a.y), pack2(a.z, a.w));
      }
      const uint32_t zz = pack2(reinterpret_cast<const float*>(smem + SM_ONES)[r], 1.0f);
      *reinterpret_cast<uint4*>(smem + SM_KVS + r * 48 + 32) = make_uint4(zz, zz, zz, zz);
      bar_sync(1 + wg, 128);
    }
    TSTAMP(8);
    {
      uint4* op = &g_o[rh][hg][wq][0][lane];
#pragma unroll
      for (int h = 0; h < 4; h++) {
        uint32_t b0[4], b1[4], b2[4];
        const uint32_t kb = sb + SM_KVS + (h * 32 + lane) * 48;
        ldsm4t(b0, kb); ldsm4t(b1, kb + 16); ldsm4t(b2, kb + 32);
        const uint32_t ep[4] = {E[h][0], E[h][1], E[h][2], E[h][3]}, en[4] = {E[h][4], E[h][5], E[h][6], E[h][7]};
        float np0[4] = {0, 0, 0, 0}, np1[4] = {0, 0, 0, 0}, nn0[4] = {0, 0, 0, 0}, nn1[4] = {0, 0, 0, 0}, dp[4] = {0, 0, 0, 0}, dn[4] = {0, 0, 0, 0};
        mma16816(dp, ep, b2[0], b2[1]);  mma16816(dn, en, b2[2], b2[3]);
        mma16816(np0, ep, b0[0], b0[1]); mma16816(nn0, en, b0[2], b0[3]);
        mma16816(np1, ep, b1[0], b1[1]); mma16816(nn1, en, b1[2], b1[3]);
        const float i0 = rcp(fmaf(dp[0], dn[1], fmaf(dn[0], dp[1], 1e-6f * dp[1] * dn[1])));
        const float i1 = rcp(fmaf(dp[2], dn[3], fmaf(dn[2], dp[3], 1e-6f * dp[3] * dn[3])));
        const float cp0 = dn[1] * i0, cn0 = dp[1] * i0, cp1 = dn[3] * i1, cn1 = dp[3] * i1;
        st_rlx4(op + h * 32,
                tg(pack2(fmaf(np0[0], cp0, nn0[0] * cn0), fmaf(np0[1], cp0, nn0[1] * cn0)), T),
                pack2(fmaf(np0[2], cp1, nn0[2] * cn1), fmaf(np0[3], cp1, nn0[3] * cn1)),
                pack2(fmaf(np1[0], cp0, nn1[0] * cn0), fmaf(np1[1], cp0, nn1[1] * cn0)),
                pack2(fmaf(np1[2], cp1, nn1[2] * cn1), fmaf(np1[3], cp1, nn1[3] * cn1)));
      }
    }
    TSTAMP(9);

    {
      uint32_t xr[4][4];
      {
        const uint32_t* xp = reinterpret_cast<const uint32_t*>(x + (size_t)(rh * 64 + wq * 16 + g) * 512 + hg * 64 + 2 * t);
#pragma unroll
        for (int i = 0; i < 8; i++) { xr[i >> 1][(i & 1) * 2] = __ldg(xp + 4 * i); xr[i >> 1][(i & 1) * 2 + 1] = __ldg(xp + 8 * 256 + 4 * i); }
      }
      uint32_t A[8][4][4];
      const uint4* op = &g_o[rh][0][wq][0][lane];
      float acc[32];
      mbar_wait(sb + SM_XF + (wg * 4) * 8);
      lds_chunk(A[0], xb); lds_chunk(A[1], xb + 8192);
#pragma unroll
      for (int p = 0; p < 4; p++) {
        chk_pair(A[2 * p], A[2 * p + 1], op + p * 1024, T);
        if (lane == 0) mbar_arrive(sb + SM_XE + (wg * 4 + p) * 8);
#pragma unroll
        for (int c = 2 * p; c < 2 * p + 2; c++) {
          if (c % 3 == 0) mbar_wait(sb + SM_FULL + (ST_WO + c / 3) * 8);
          if ((c & 1) && p < 3) {
            mbar_wait(sb + SM_XF + (wg * 4 + p + 1) * 8);
            lds_chunk(A[2 * p + 2], xb + (p + 1) * 16384); lds_chunk(A[2 * p + 3], xb + (p + 1) * 16384 + 8192);
          }
          wg_fence();
#pragma unroll
          for (int s = 0; s < 4; s++)
            wgmma_rs_n64(acc, A[c][s], DESC(((ST_WO + c / 3) % NSLOT) * SLOT + ((c % 3) * 4 + s) * 2048), (c | s) != 0);
          wg_commit();
        }
      }
      wg_wait<0>();
      if ((tid & 127) < 3) release(ST_WO + (tid & 127));
      TSTAMP(10);
      add_frag(acc, xr, IDF);
      uint32_t hw[4][4];
      uint4* hp_ = &g_h[rh][hg][wq][0][lane];
      float cs[4] = {0.f, 0.f, 0.f, 0.f}, c0[4] = {0.f, 0.f, 0.f, 0.f}, c1[4] = {0.f, 0.f, 0.f, 0.f};
      uint32_t hx = T;
#pragma unroll
      for (int s = 0; s < 4; s++) {
#pragma unroll
        for (int r = 0; r < 4; r++) hw[s][r] = pack2(acc[8 * s + 2 * r], acc[8 * s + 2 * r + 1]);
        st_rlx4(hp_ + s * 32, tg(hw[s][0], T), hw[s][1], hw[s][2], hw[s][3]);
        mma16816(cs, hw[s], 0x3F803F80u, 0x3F803F80u);
        mma16816(c0, hw[s], hw[s][0], hw[s][2]);
        mma16816(c1, hw[s], hw[s][1], hw[s][3]);
        hx |= (hw[s][0] & 1u) << (s + 1);
      }
      if (t == (g >> 1)) {
        st_rlx2(&g_st[rh][hg][wq * 16 + g], tg(__float_as_uint(cs[0]), T), __float_as_uint((g & 1) ? c0[1] : c0[0]));
        st_rlx2(&g_st[rh][hg][wq * 16 + g + 8], tg(__float_as_uint(cs[2]), T), __float_as_uint((g & 1) ? c1[3] : c1[2]));
      }
      st_rlx1(&g_hx[rh][hg][wq][lane], hx);
    }
    TSTAMP(11);

    const int rh3 = 2 * rb3 + wg;
    uint32_t HH[11][4];
    {
      uint32_t A[8][4][4];
      const uint4* hp_ = &g_h[rh3][0][wq][0][lane];
      uint4* hhp = &g_hh[rh3][jf][0][wq][lane];
      const uint32_t dg = (db & 0xFFFFu) | (256u << 16);
      uint32_t m0, m1;
      mbar_wait(sb + SM_XF + ((2 + wg) * 4) * 8);
      lds_chunk(A[0], xb); lds_chunk(A[1], xb + 8192);
      {
        const uint2* sp = &g_st[rh3][2 * t][wq * 16 + g];
        const uint2* ss = reinterpret_cast<const uint2*>(smem + SM_KV32 + wg * 4096) + 2 * t * 64 + wq * 16 + g;
        uint2 a0 = ss[0], a1 = ss[64], b0 = ss[8], b1 = ss[72];
        int it = 0;
#pragma unroll 1
        while (__any_sync(0xffffffffu, bad4(a0.x, a1.x, b0.x, b1.x, T))) {
          ld_rlx2(a0.x, a0.y, sp); ld_rlx2(a1.x, a1.y, sp + 64); ld_rlx2(b0.x, b0.y, sp + 8); ld_rlx2(b1.x, b1.y, sp + 72);
          if (++it > (1 << 18)) break;
        }
        float s0 = __uint_as_float(a0.x) + __uint_as_float(a1.x), q0 = __uint_as_float(a0.y) + __uint_as_float(a1.y);
        float s1 = __uint_as_float(b0.x) + __uint_as_float(b1.x), q1 = __uint_as_float(b0.y) + __uint_as_float(b1.y);
        s0 += __shfl_xor_sync(0xffffffffu, s0, 1); s1 += __shfl_xor_sync(0xffffffffu, s1, 1);
        q0 += __shfl_xor_sync(0xffffffffu, q0, 1); q1 += __shfl_xor_sync(0xffffffffu, q1, 1);
        s0 += __shfl_xor_sync(0xffffffffu, s0, 2); s1 += __shfl_xor_sync(0xffffffffu, s1, 2);
        q0 += __shfl_xor_sync(0xffffffffu, q0, 2); q1 += __shfl_xor_sync(0xffffffffu, q1, 2);
        s0 *= (1.f / 512.f); s1 *= (1.f / 512.f);
        r0 = rcp(fmaxf(q0 * (1.f / 512.f) - s0 * s0, 0.f) + 1e-5f);
        r1 = rcp(fmaxf(q1 * (1.f / 512.f) - s1 * s1, 0.f) + 1e-5f);
        m0 = pack2(s0, s0); m1 = pack2(s1, s1);
      }
      TSTAMP(12);
#define UOFF(u) ((((ST_GU + (u) / 3) % NSLOT) * SLOT + ((u) % 3) * 8192) >> 4)
#define UNIT_PRE(u)  do { if ((u) % 3 == 0) mbar_wait(sb + SM_FULL + (ST_GU + (u) / 3) * 8); } while (0)
#define UNIT_POST(u) do { wg_commit(); if ((u) % 3 == 1 && (u) > 3) { wg_wait<2>(); if (lead) release(ST_GU + (u) / 3 - 1); } } while (0)
      float acc[64];
      const int rz = blockIdx.y;
#pragma unroll
      for (int ps = 0; ps < 2; ps++) {
        wg_fence();
#pragma unroll
        for (int k = 0; k < 16; k++) {
          const int u = 16 * ps + k, c = k >> 1;
          if (ps == 0 && k < 5 && k != 1) {
            const int p = k > 0 ? k - 1 : 0;
            chk_pair(A[2 * p], A[2 * p + 1], hp_ + p * 1024, T);
            if (lane == 0) {
              if (wg == 0) mbar_arrive(sb + SM_XE + (8 + p) * 8);
              else if (p > 0) release(ST_XC + p - 1);
            }
          }
          if (ps == 0 && k >= 1 && k < 4) {
            const int p = k;
            mbar_wait(sb + SM_XF + ((2 + wg) * 4 + p) * 8);
            lds_chunk(A[2 * p], xb + p * 16384);
            lds_chunk(A[2 * p + 1], xb + p * 16384 + 8192);
          }
          if (ps == 0 && (k & 1) == 0) {
#pragma unroll
            for (int s = 0; s < 4; s++) {
              A[c][s][0] = hsub2(A[c][s][0], m0); A[c][s][1] = hsub2(A[c][s][1], m1);
              A[c][s][2] = hsub2(A[c][s][2], m0); A[c][s][3] = hsub2(A[c][s][3], m1);
            }
            wg_fence();
          }
          UNIT_PRE(u);
          wgmma_rs_n128(acc, A[c][(k & 1) * 2], dg + UOFF(u), k != 0 ? 1 : (ps ? rz : 0));
          wgmma_rs_n128(acc, A[c][(k & 1) * 2 + 1], dg + UOFF(u) + 128, 1);
          UNIT_POST(u);
        }
        wg_wait<0>();
#pragma unroll
        for (int s = 0; s < 4; s++) {
          uint32_t (&hh)[4] = HH[4 + s];
          hh[0] = tg(pack2(acc[8 * s + 0] * acc[32 + 8 * s + 0] * r0, acc[8 * s + 1] * acc[32 + 8 * s + 1] * r0), T);
          hh[1] = pack2(acc[8 * s + 2] * acc[32 + 8 * s + 2] * r1, acc[8 * s + 3] * acc[32 + 8 * s + 3] * r1);
          hh[2] = pack2(acc[8 * s + 4] * acc[32 + 8 * s + 4] * r0, acc[8 * s + 5] * acc[32 + 8 * s + 5] * r0);
          hh[3] = pack2(acc[8 * s + 6] * acc[32 + 8 * s + 6] * r1, acc[8 * s + 7] * acc[32 + 8 * s + 7] * r1);
          st_rlx4(hhp + (4 * ps + s) * 128, hh[0], hh[1], hh[2], hh[3]);
        }
      }
      {
        float ag[24], au[24];
        bar_sync(1 + wg, 128);
        wg_fence();
#pragma unroll
        for (int k = 0; k < 16; k++) {
          const int u = 32 + k, c = k >> 1;
          UNIT_PRE(u);
          wgmma_rs_n48(ag, A[c][(k & 1) * 2], dg + UOFF(u), k != 0);
          wgmma_rs_n48(au, A[c][(k & 1) * 2], dg + UOFF(u) + 256, k != 0);
          wgmma_rs_n48(ag, A[c][(k & 1) * 2 + 1], dg + UOFF(u) + 128, 1);
          wgmma_rs_n48(au, A[c][(k & 1) * 2 + 1], dg + UOFF(u) + 256 + 128, 1);
          UNIT_POST(u);
        }
        wg_wait<0>();
        TSTAMP(13);
#pragma unroll
        for (int s = 0; s < 4; s++) ld_rlx4(HH[s], hhp + s * 128);
#pragma unroll
        for (int s = 0; s < 3; s++) {
          uint32_t (&hh)[4] = HH[8 + s];
          hh[0] = tg(pack2(ag[8 * s + 0] * au[8 * s + 0] * r0, ag[8 * s + 1] * au[8 * s + 1] * r0), T);
          hh[1] = pack2(ag[8 * s + 2] * au[8 * s + 2] * r1, ag[8 * s + 3] * au[8 * s + 3] * r1);
          hh[2] = pack2(ag[8 * s + 4] * au[8 * s + 4] * r0, ag[8 * s + 5] * au[8 * s + 5] * r0);
          hh[3] = pack2(ag[8 * s + 6] * au[8 * s + 6] * r1, ag[8 * s + 7] * au[8 * s + 7] * r1);
          st_rlx4(hhp + (8 + s) * 128, hh[0], hh[1], hh[2], hh[3]);
        }
      }
    }
    TSTAMP(14);

    {
      float ac[3][32], acc[32];
      uint32_t PH[11][4], hr[4][4];
      const int m = jf >> 1, oc = (jf & 1) * 4 + m;
      const uint4* pp = &g_hh[rh3][jf ^ 1][0][wq][lane];
      bar_arrive(8 + wg, 256);
#pragma unroll
      for (int s = 0; s < 8; s++) ld_rlx4(PH[s], pp + s * 128);
      wg_fence();
#pragma unroll
      for (int k = 0; k < 3; k++) {
        mbar_wait(sb + SM_FULL + (ST_D + k) * 8);
        if (k == 2) {
#pragma unroll
          for (int s = 8; s < 11; s++) ld_rlx4(PH[s], pp + s * 128);
        }
#pragma unroll
        for (int s = 4; s < 11; s++) wgmma_rs_n64(ac[k], HH[s], DESC(((ST_D + k) % NSLOT) * SLOT + s * 2048), s != 4);
        if (k == 0) wg_fence();
#pragma unroll
        for (int s = 0; s < 4; s++) wgmma_rs_n64(ac[k], HH[s], DESC(((ST_D + k) % NSLOT) * SLOT + s * 2048), 1);
      }
      wg_commit();
      {
        int it = 0;
#pragma unroll 1
        while (__any_sync(0xffffffffu, bad4(PH[0][0], PH[1][0], PH[2][0], PH[3][0], T) | bad4(PH[4][0], PH[5][0], PH[6][0], PH[7][0], T) |
                                       bad4(PH[8][0], PH[9][0], PH[10][0], T, T))) {
#pragma unroll
          for (int s = 0; s < 11; s++) ld_rlx4(PH[s], pp + s * 128);
          if (++it > (1 << 18)) break;
        }
      }
      TSTAMP(20);
      uint4* outb = &g_part[rh3][(jf & 1) * 4][m][wq][0][lane];
#pragma unroll
      for (int k = 0; k < 4; k++) {
        mbar_wait(sb + SM_FULL + (ST_D + 3 + k) * 8);
        wg_fence();
#pragma unroll
        for (int s = 0; s < 11; s++) {
          if (k < 3) wgmma_rs_n64(ac[k], PH[s], DESC(((ST_D + 3 + k) % NSLOT) * SLOT + s * 2048), 1);
          else wgmma_rs_n64(acc, HH[s], DESC(((ST_D + 6) % NSLOT) * SLOT + s * 2048), s != 0);
        }
        wg_commit();
        if (k > 0) {
          wg_wait<1>();
          const float (&a)[32] = ac[k - 1];
          uint4* p = outb + ((m + k) & 3) * 2048;
#pragma unroll
          for (int s = 0; s < 4; s++)
            st_rlx4(p + s * 32, tg(pack2(a[8 * s + 0], a[8 * s + 1]), T), pack2(a[8 * s + 2], a[8 * s + 3]),
                    pack2(a[8 * s + 4], a[8 * s + 5]), pack2(a[8 * s + 6], a[8 * s + 7]));
        }
      }
      ld_chunk(hr, &g_h[rh3][oc][wq][0][lane]);
      mbar_wait(sb + SM_FULL + (ST_D + 7) * 8);
      wg_fence();
#pragma unroll
      for (int s = 0; s < 11; s++) wgmma_rs_n64(acc, PH[s], DESC(((ST_D + 7) % NSLOT) * SLOT + s * 2048), 1);
      wg_commit();
      uint32_t hx = ld_rlx1(&g_hx[rh3][oc][wq][lane]);
      uint32_t in[3][4][4];
      const uint4* inb = &g_part[rh3][oc][0][wq][0][lane];
      {
        const uint32_t* hint = reinterpret_cast<const uint32_t*>(&g_part[rh3][oc][(m - 1 - lane) & 3][wq][3][31]);
        uint32_t ready = 0; int it = 0;
#pragma unroll
        for (int q = 0; q < 3; q++) {
#pragma unroll 1
          while (!((ready >> q) & 1)) {
            ready = __ballot_sync(0xffffffffu, ((ld_rlx1(hint) ^ T) & 1) == 0);
            if (++it > (1 << 18)) break;
          }
          ld_chunk(in[q], inb + ((m - 1 - q) & 3) * 512);
        }
#pragma unroll 1
        while (__any_sync(0xffffffffu, bad4(in[0][0][0], in[0][1][0], in[0][2][0], in[0][3][0], T) | bad4(in[1][0][0], in[1][1][0], in[1][2][0], in[1][3][0], T) |
                                       bad4(in[2][0][0], in[2][1][0], in[2][2][0], in[2][3][0], T) | ((hx ^ T) & 1))) {
#pragma unroll
          for (int q = 0; q < 3; q++) ld_chunk(in[q], inb + ((m - 1 - q) & 3) * 512);
          hx = ld_rlx1(&g_hx[rh3][oc][wq][lane]);
          if (++it > (1 << 18)) break;
        }
      }
      wg_wait<0>();
      TSTAMP(15);
#pragma unroll
      for (int s = 0; s < 4; s++) hr[s][0] = (hr[s][0] & 0xFFFFFFFEu) | ((hx >> (s + 1)) & 1u);
      add_frag(acc, hr, IDF); add_frag(acc, in[0], IDF); add_frag(acc, in[1], IDF); add_frag(acc, in[2], IDF);
      bar_sync(9 - wg, 256);
      const uint32_t ob = sb + ((ST_D - 1) % NSLOT) * SLOT + wg * 8192;
#pragma unroll
      for (int s = 0; s < 4; s++)
        stsm4(ob + lrow + (((2 * s + lhi) ^ lx) << 4), pack2(acc[8 * s + 0], acc[8 * s + 1]), pack2(acc[8 * s + 2], acc[8 * s + 3]),
              pack2(acc[8 * s + 4], acc[8 * s + 5]), pack2(acc[8 * s + 6], acc[8 * s + 7]));
      __syncwarp();
#pragma unroll
      for (int i = 0; i < 4; i++) {
        const int row = wq * 16 + i * 4 + (lane >> 3);
        uint4 v;
        asm volatile("ld.shared.v4.b32 {%0,%1,%2,%3}, [%4];" : "=r"(v.x), "=r"(v.y), "=r"(v.z), "=r"(v.w)
                     : "r"(ob + row * 128 + ((lx ^ (row & 7)) << 4)) : "memory");
        asm volatile("st.global.v4.b32 [%0], {%1,%2,%3,%4};" ::"l"(out + (size_t)(rh3 * 64 + row) * 512 + oc * 64 + lx * 8),
                     "r"(v.x), "r"(v.y), "r"(v.z), "r"(v.w) : "memory");
      }
    }
    TSTAMP(16);
    asm volatile("barrier.cluster.arrive.relaxed.aligned;" ::: "memory");
    asm volatile("barrier.cluster.wait.aligned;" ::: "memory");
  } else {
    asm volatile("setmaxnreg.dec.sync.aligned.u32 24;");
    if (lane == 0) {
      if (warp == 8) {
#pragma unroll
        for (int k = 0; k < 9; k++) {
          const int s = k < 3 ? k : (k < 6 ? k + 3 : k - 3);
          const uint32_t bar = sb + SM_FULL + s * 8;
          mbar_init(bar, 1);
          mbar_expect_tx(bar, SLOT);
          if (s >= 3 && s < 6) tma2d(sb + s * SLOT, &maps.w, 512 + hg * 64, (s - 3) * 192, bar);
          else tma3d(sb + s * SLOT, &maps.x, 0, rb * 128 + (s >= 6 ? 64 : 0), 3 * (s % 3), bar);
        }
      } else if (warp == 9) {
        mbar_init(sb + SM_MISCB, 2);
        mbar_init(sb + SM_KVB, 32);
        mbar_expect_tx(sb + SM_MISCB, 2048);
        bulk_g2s(sb + SM_WPHI, wphi + hg * 1024, 2048, sb + SM_MISCB);
      } else if (warp == 10) {
#pragma unroll 1
        for (int i = 0; i < 16; i++) {
          mbar_init(sb + SM_XF + i * 8, 1);
          mbar_expect_tx(sb + SM_XF + i * 8, (i == 8 || i == 12) ? 20480 : 16384);
          if (i < 12) mbar_init(sb + SM_XE + i * 8, 4);
        }
      } else {
        *reinterpret_cast<volatile unsigned*>(smem + SM_EPOCH) = atomicAdd(&g_start, 1u) / NCTA;
      }
      asm volatile("fence.mbarrier_init.release.cluster;" ::: "memory");
    }
    __syncwarp();
    if (warp != 11) bar_sync(0, 352);
    asm volatile("barrier.cluster.arrive.relaxed.aligned;" ::: "memory");
    if (warp == 8) {
      asm volatile("barrier.cluster.wait.aligned;" ::: "memory");
      if (lane == 0) {
        const CUtensorMap* mg = jf == 7 ? &maps.g7 : &maps.g;
        const CUtensorMap* mu = jf == 7 ? &maps.u7 : &maps.u;
        asm volatile("prefetch.tensormap [%0];" ::"l"(&maps.wo) : "memory");
        asm volatile("prefetch.tensormap [%0];" ::"l"(mg) : "memory");
        asm volatile("prefetch.tensormap [%0];" ::"l"(mu) : "memory");
        asm volatile("prefetch.tensormap [%0];" ::"l"(&maps.d) : "memory");
#pragma unroll 1
        for (int s = ST_WV; s < ST_XC; s++) {
          if (s == ST_SCR1) continue;
          mbar_wait(sb + SM_EMPTY + (s - 9) * 8);
          const uint32_t dst = sb + (s >= 18 ? s - 18 : s - 9) * SLOT, bar = sb + SM_FULL + s * 8;
          if (s < ST_WO) tma2d(dst, &maps.w, (s < ST_WQ ? 1024 : 0) + hg * 64, (s < ST_WQ ? s - ST_WV : s - ST_WQ) * 192, bar);
          else { mbar_wait(bar - 8); tma2d(dst, &maps.wo, hg * 64, (s - ST_WO) * 192, bar); }
        }
        const int jc = jf == 7 ? 0 : jf;
        int slot = (ST_GU + 1 - rank) % NSLOT;
#pragma unroll 1
        for (int s = ST_GU + 1 - rank; s < NSTAGE; s += 2) {
          mbar_wait(sb + SM_EMPTY + (s - 9) * 8);
          if (s > ST_GU && s < ST_GU + THR) mbar_wait(sb + SM_FULL + (s - 1) * 8);
          const uint32_t dst = sb + slot * SLOT, bar = sb + SM_FULL + s * 8;
          if (s < ST_D) {
#pragma unroll 1
            for (int i = 0; i < 3; i++) {
              const int u = (s - ST_GU) * 3 + i;
              tma3d_mc(dst + i * 8192, mg, (u >> 4) * 64, jc, (u & 15) * 32, bar);
              tma3d_mc(dst + i * 8192 + 4096, mu, (u >> 4) * 64, jc, (u & 15) * 32, bar);
            }
          } else {
            const int i = s - ST_D, k = i < 3 ? i : (i < 6 ? i - 3 : 3), pt = (i >= 3 && i != 6) ? 1 : 0;
            tma2d_mc(dst, &maps.d, ((jf & 1) * 4 + (((jf >> 1) + 1 + k) & 3)) * 64, (jf ^ pt) * 176, bar);
          }
          slot += 2; if (slot >= NSLOT) slot -= NSLOT;
        }
      }
      __syncwarp();
    } else {
      asm volatile("barrier.cluster.wait.aligned;" ::: "memory");
      if (warp == 11) {
#pragma unroll
        for (int i = 0; i < 4; i++)
          reinterpret_cast<uint4*>(smem + SM_ONES)[lane + 32 * i] = make_uint4(0x3F803F80u, 0x3F803F80u, 0x3F803F80u, 0x3F803F80u);
        fence_async_smem();
        __syncwarp();
        if (lane == 0) mbar_arrive(sb + SM_MISCB);
      }
      mbar_wait(sb + SM_MISCB);
      const unsigned epoch = *reinterpret_cast<volatile unsigned*>(smem + SM_EPOCH);
      const uint32_t T = (epoch & 1) ^ 1;
      if (warp == 11) {
        reinterpret_cast<float4*>(&g_kv[T][blockIdx.x * 128])[lane] = make_float4(0.f, 0.f, 0.f, 0.f);
        if (lane < 8) g_z[T][blockIdx.x * 8 + lane] = 0.f;
        mbar_wait(sb + SM_FULL + (ST_WK + 2) * 8);
        if (lane == 0) {
          asm volatile("cp.async.bulk.prefetch.L2.global [%0], 4096;" ::"l"((const char*)wo + blockIdx.x * 4096) : "memory");
          asm volatile("cp.async.bulk.prefetch.L2.global [%0], 11008;" ::"l"((const char*)wg_ + blockIdx.x * 11008) : "memory");
          asm volatile("cp.async.bulk.prefetch.L2.global [%0], 11008;" ::"l"((const char*)wu_ + blockIdx.x * 11008) : "memory");
          asm volatile("cp.async.bulk.prefetch.L2.global [%0], 11008;" ::"l"((const char*)wd_ + blockIdx.x * 11008) : "memory");
          const unsigned target = (epoch + 1) * 32;
          unsigned v; int it = 0;
#pragma unroll 1
          do {
            asm volatile("ld.acquire.gpu.global.u32 %0, [%1];" : "=r"(v) : "l"(&g_kvcnt[hg * 32]) : "memory");
            if (++it > (1 << 18)) break;
          } while ((int)(v - target) < 0);
          TS2(0, 26);
        }
        __syncwarp();
        {
          const char* src = reinterpret_cast<const char*>(&g_kv[T ^ 1][hg * 2048]) + lane * 16;
#pragma unroll 4
          for (int i = 0; i < 16; i++)
            asm volatile("cp.async.cg.shared.global [%0], [%1], 16;" ::"r"(sb + SM_KV32 + lane * 16 + i * 512), "l"(src + i * 512) : "memory");
          asm volatile("cp.async.cg.shared.global [%0], [%1], 16;" ::"r"(sb + SM_ONES + lane * 16), "l"(&g_z[T ^ 1][hg * 128 + lane * 4]) : "memory");
          asm volatile("cp.async.mbarrier.arrive.noinc.shared::cta.b64 [%0];" ::"r"(sb + SM_KVB) : "memory");
        }
      } else {
        const int w = warp - 9;
        st_rlx4(reinterpret_cast<uint4*>(&g_st[2 * rb + w][hg][0]) + lane, T ^ 1, T ^ 1, T ^ 1, T ^ 1);
        if (lane < 8) st_rlx4(&g_o[2 * rb + w][hg][lane >> 1][3][30 + (lane & 1)], T ^ 1, T ^ 1, T ^ 1, T ^ 1);
        st_rlx4(&g_part[2 * rb3 + w][(jf & 1) * 4 + (lane >> 3)][jf >> 1][(lane >> 1) & 3][3][30 + (lane & 1)], T ^ 1, T ^ 1, T ^ 1, T ^ 1);
        bar_sync(6 + w, 160);
        if (lane == 0) {
          asm volatile("fence.acq_rel.gpu;" ::: "memory");
          TS2(w, 25);
          asm volatile("red.relaxed.gpu.global.add.u32 [%0], 1;" ::"l"(&g_kvcnt[hg * 32]) : "memory");
        }
        mbar_wait(sb + SM_KVB);
        if (w == 0) { mbar_wait(sb + SM_EMPTY + 11 * 8); mbar_wait(sb + SM_EMPTY + 12 * 8); mbar_wait(sb + SM_EMPTY + 13 * 8); }
#pragma unroll 1
        for (int ph = 0; ph < 2; ph++) {
          const int use = 2 * ph + w, r = ph ? 2 * rb3 + w : 2 * rb + w;
          const uint32_t* pw = ph ? reinterpret_cast<const uint32_t*>(&g_st[r][lane >> 2][(lane & 3) * 16 + 15])
                                  : reinterpret_cast<const uint32_t*>(&g_o[r][lane >> 2][lane & 3][3][31]);
          const char* src = reinterpret_cast<const char*>(ph ? &g_h[r][0][0][0][0] : &g_o[r][0][0][0][0]);
          const uint32_t bf = sb + SM_XF + use * 32, be = sb + SM_XE + (use - 1) * 32;
          if (ph) mbar_wait(sb + SM_XE + w * 32 + 24);
          int it = 0;
#pragma unroll 1
          while (__any_sync(0xffffffffu, (ld_rlx1(pw) ^ T) & 1)) { if (++it > (1 << 18)) break; }
          if (lane == 0) {
            TS2(w, 27 + ph);
            if (use > 0) mbar_wait(be);
            if (ph) bulk_g2s(sb + SM_KV32 + w * 4096, &g_st[r][0][0], 4096, bf);
#pragma unroll
            for (int p = 0; p < 4; p++) {
              if (p > 0 && use > 0) mbar_wait(be + p * 8);
              bulk_g2s(sb + 2 * SLOT + p * 16384, src + p * 16384, 16384, bf + p * 8);
            }
          }
          __syncwarp();
        }
      }
    }
    asm volatile("barrier.cluster.arrive.relaxed.aligned;" ::: "memory");
    asm volatile("barrier.cluster.wait.aligned;" ::: "memory");
  }
}

typedef CUresult (*EncodeFn)(CUtensorMap*, CUtensorMapDataType, cuuint32_t, void*, const cuuint64_t*, const cuuint64_t*,
                             const cuuint32_t*, const cuuint32_t*, CUtensorMapInterleave, CUtensorMapSwizzle,
                             CUtensorMapL2promotion, CUtensorMapFloatOOBfill);

void encode(EncodeFn fn, CUtensorMap* m, const void* base, int rank, const cuuint64_t* dims, const cuuint64_t* strides,
            const cuuint32_t* box) {
  cuuint32_t es[3] = {1, 1, 1};
  fn(m, CU_TENSOR_MAP_DATA_TYPE_BFLOAT16, (cuuint32_t)rank, const_cast<void*>(base), dims, strides, box, es,
     CU_TENSOR_MAP_INTERLEAVE_NONE, CU_TENSOR_MAP_SWIZZLE_128B, CU_TENSOR_MAP_L2_PROMOTION_L2_256B,
     CU_TENSOR_MAP_FLOAT_OOB_FILL_NONE);
}

}

extern "C" void kernel_launch(void* const* d_in, const int* in_sizes, int n_in, void* d_out, int out_size) {
  (void)in_sizes; (void)n_in; (void)out_size;
  const __nv_bfloat16* x    = (const __nv_bfloat16*)d_in[0];
  const __nv_bfloat16* wqkv = (const __nv_bfloat16*)d_in[1];
  const __nv_bfloat16* wphi = (const __nv_bfloat16*)d_in[2];
  const __nv_bfloat16* wo   = (const __nv_bfloat16*)d_in[3];
  const __nv_bfloat16* wg   = (const __nv_bfloat16*)d_in[5];
  const __nv_bfloat16* wu   = (const __nv_bfloat16*)d_in[6];
  const __nv_bfloat16* wd   = (const __nv_bfloat16*)d_in[7];

  static EncodeFn fn = nullptr;
  static int reserved = 0;
  if (!fn) {
    void* p = nullptr;
    cudaDriverEntryPointQueryResult qr;
    cudaGetDriverEntryPoint("cuTensorMapEncodeTiled", &p, cudaEnableDefault, &qr);
    fn = (EncodeFn)p;
    cudaFuncSetAttribute(fused_kernel<1024>, cudaFuncAttributeMaxDynamicSharedMemorySize, SM_TOTAL);
    cudaFuncSetAttribute(fused_kernel<0>, cudaFuncAttributeMaxDynamicSharedMemorySize, SM_TOTAL);
    int dev = 0;
    cudaGetDevice(&dev);
    cudaDeviceGetAttribute(&reserved, cudaDevAttrReservedSharedMemoryPerBlock, dev);
  }
  Maps maps;
  {
    cuuint64_t d[3] = {64, 2048, 8}, s[2] = {1024, 128}; cuuint32_t b[3] = {64, 64, 3};
    encode(fn, &maps.x, x, 3, d, s, b);
  }
  {
    cuuint64_t d[2] = {1536, 512}, s[1] = {3072}; cuuint32_t b[2] = {64, 192};
    encode(fn, &maps.w, wqkv, 2, d, s, b);
  }
  {
    cuuint64_t d[2] = {512, 512}, s[1] = {1024}; cuuint32_t b[2] = {64, 192};
    encode(fn, &maps.wo, wo, 2, d, s, b);
  }
  {
    cuuint64_t d[3] = {176, 7, 512}, d7[3] = {144, 1, 512}, s[2] = {352, 2752}; cuuint32_t b[3] = {64, 1, 32};
    encode(fn, &maps.g, wg, 3, d, s, b);
    encode(fn, &maps.u, wu, 3, d, s, b);
    encode(fn, &maps.g7, wg + 1232, 3, d7, s, b);
    encode(fn, &maps.u7, wu + 1232, 3, d7, s, b);
  }
  {
    cuuint64_t d[2] = {512, 1376}, s[1] = {1024}; cuuint32_t b[2] = {64, 176};
    encode(fn, &maps.d, wd, 2, d, s, b);
  }
  if (reserved == 1024) fused_kernel<1024><<<NCTA, 384, SM_TOTAL>>>(maps, x, wphi, wo, wg, wu, wd, (__nv_bfloat16*)d_out);
  else fused_kernel<0><<<NCTA, 384, SM_TOTAL>>>(maps, x, wphi, wo, wg, wu, wd, (__nv_bfloat16*)d_out);
}
```

```cpp
#include <cuda_runtime.h>
#include <cuda_bf16.h>
#include <cuda.h>
#include <stdint.h>

#define PROF 0

#define SAFE_WAIT 0
#define THR 6

namespace {

constexpr int NCTA   = 128;
constexpr int SLOT   = 24576;
constexpr int NSLOT  = 9;
constexpr int NSTAGE = 47;

constexpr int ST_X0   = 0;
constexpr int ST_WK   = 3;
constexpr int ST_X1   = 6;
constexpr int ST_SCR0 = 9;
constexpr int ST_WV   = 10;
constexpr int ST_SCR1 = 13;
constexpr int ST_WQ   = 14;
constexpr int ST_WO   = 17;
constexpr int ST_XC   = 20;
constexpr int ST_GU   = 23;
constexpr int ST_D    = 39;

__host__ __device__ constexpr int st_empty_cnt(int d) {
  return ((d < 3 || (d >= 6 && d < 9) || (d >= ST_XC && d < ST_GU)) ? 4 : 2) * (d + 9 >= ST_GU ? 2 : 1);
}

constexpr int SM_ONES = NSLOT * SLOT;
constexpr int SM_WPHI = SM_ONES + 2048;
constexpr int SM_KVS  = SM_WPHI + 2048;
constexpr int SM_KV32 = 4 * SLOT + 16384;
constexpr int SM_BAR  = SM_KVS + 6144;
constexpr int SM_FULL  = SM_BAR;
constexpr int SM_EMPTY = SM_BAR + NSTAGE * 8;
constexpr int SM_MISCB = SM_BAR + 2 * NSTAGE * 8;
constexpr int SM_KVB   = SM_MISCB + 8;
constexpr int SM_EPOCH = SM_KVB + 8;
constexpr int SM_XF    = SM_EPOCH + 8;
constexpr int SM_XE    = SM_XF + 16 * 8;
constexpr int SM_TOTAL = SM_BAR + 1024;

static_assert(SM_TOTAL == 232448 && SM_XE + 12 * 8 <= SM_TOTAL, "smem budget");

struct Maps { CUtensorMap x, w, wo, g, u, g7, u7, d; };

__device__ uint4    g_o[32][8][4][4][32];
__device__ uint4    g_h[32][8][4][4][32];
__device__ uint32_t g_hx[32][8][4][32];
__device__ uint2    g_st[32][8][64];
__device__ uint4    g_hh[32][8][11][4][32];
__device__ uint4    g_part[32][8][4][4][4][32];
__device__ float    g_kv[2][32 * 32 * 16];
__device__ float    g_z[2][32 * 32];
__device__ unsigned g_kvcnt[8 * 32];
__device__ unsigned g_start;

__device__ __forceinline__ uint32_t smem_u32(const void* p) { return (uint32_t)__cvta_generic_to_shared(p); }
__device__ __forceinline__ void mbar_init(uint32_t bar, int cnt) {
  asm volatile("mbarrier.init.shared::cta.b64 [%0], %1;" ::"r"(bar), "r"(cnt) : "memory");
}
__device__ __forceinline__ void mbar_expect_tx(uint32_t bar, uint32_t bytes) {
  asm volatile("mbarrier.arrive.expect_tx.shared::cta.b64 _, [%0], %1;" ::"r"(bar), "r"(bytes) : "memory");
}
__device__ __forceinline__ void mbar_arrive(uint32_t bar) {
  asm volatile("mbarrier.arrive.shared::cta.b64 _, [%0];" ::"r"(bar) : "memory");
}
__device__ __forceinline__ void mbar_arrive_cluster(uint32_t bar, uint32_t rank) {
  asm volatile("{\n.reg .b32 ra;\nmapa.shared::cluster.u32 ra, %0, %1;\n"
               "mbarrier.arrive.shared::cluster.b64 _, [ra];\n}" ::"r"(bar), "r"(rank) : "memory");
}
__device__ __forceinline__ void mbar_wait_p(uint32_t bar, uint32_t parity) {
  asm volatile("{\n.reg .pred p;\nW: mbarrier.try_wait.parity.shared::cta.b64 p, [%0], %1;\n@!p bra W;\n}" ::"r"(bar), "r"(parity) : "memory");
}
__device__ __forceinline__ void mbar_wait(uint32_t bar) { mbar_wait_p(bar, 0); }
__device__ __forceinline__ bool elect_one() {
  uint32_t p;
  asm volatile("{\n.reg .pred P;\nelect.sync _|P, 0xffffffff;\nselp.u32 %0, 1, 0, P;\n}" : "=r"(p));
  return p != 0;
}
__device__ __forceinline__ void bar_sync(int id, int n)   { asm volatile("bar.sync %0, %1;" ::"r"(id), "r"(n) : "memory"); }
__device__ __forceinline__ void bar_arrive(int id, int n) { asm volatile("bar.arrive %0, %1;" ::"r"(id), "r"(n) : "memory"); }
__device__ __forceinline__ void fence_async_smem() { asm volatile("fence.proxy.async.shared::cta;" ::: "memory"); }
__device__ __forceinline__ void wg_fence()  { asm volatile("wgmma.fence.sync.aligned;" ::: "memory"); }
__device__ __forceinline__ void wg_commit() { asm volatile("wgmma.commit_group.sync.aligned;" ::: "memory"); }
template <int N> __device__ __forceinline__ void wg_wait() { asm volatile("wgmma.wait_group.sync.aligned %0;" ::"n"(N) : "memory"); }
#define DESC(off) (db + ((uint32_t)(off) >> 4))
__device__ __forceinline__ void tma2d(uint32_t dst, const CUtensorMap* m, int c0, int c1, uint32_t bar) {
  asm volatile("cp.async.bulk.tensor.2d.shared::cluster.global.mbarrier::complete_tx::bytes [%0], [%1, {%3, %4}], [%2];"
               ::"r"(dst), "l"(m), "r"(bar), "r"(c0), "r"(c1) : "memory");
}
__device__ __forceinline__ void tma2d_mc(uint32_t dst, const CUtensorMap* m, int c0, int c1, uint32_t bar) {
  asm volatile("cp.async.bulk.tensor.2d.shared::cluster.global.mbarrier::complete_tx::bytes.multicast::cluster [%0], [%1, {%3, %4}], [%2], %5;"
               ::"r"(dst), "l"(m), "r"(bar), "r"(c0), "r"(c1), "h"((uint16_t)3) : "memory");
}
__device__ __forceinline__ void tma3d(uint32_t dst, const CUtensorMap* m, int c0, int c1, int c2, uint32_t bar) {
  asm volatile("cp.async.bulk.tensor.3d.shared::cluster.global.mbarrier::complete_tx::bytes [%0], [%1, {%3, %4, %5}], [%2];"
               ::"r"(dst), "l"(m), "r"(bar), "r"(c0), "r"(c1), "r"(c2) : "memory");
}
__device__ __forceinline__ void tma3d_mc(uint32_t dst, const CUtensorMap* m, int c0, int c1, int c2, uint32_t bar) {
  asm volatile("cp.async.bulk.tensor.3d.shared::cluster.global.mbarrier::complete_tx::bytes.multicast::cluster [%0], [%1, {%3, %4, %5}], [%2], %6;"
               ::"r"(dst), "l"(m), "r"(bar), "r"(c0), "r"(c1), "r"(c2), "h"((uint16_t)3) : "memory");
}
__device__ __forceinline__ void ldsm4(uint32_t (&r)[4], uint32_t addr) {
  asm volatile("ldmatrix.sync.aligned.m8n8.x4.shared.b16 {%0,%1,%2,%3}, [%4];"
               : "=r"(r[0]), "=r"(r[1]), "=r"(r[2]), "=r"(r[3]) : "r"(addr) : "memory");
}
__device__ __forceinline__ void ldsm4t(uint32_t (&r)[4], uint32_t addr) {
  asm volatile("ldmatrix.sync.aligned.m8n8.x4.trans.shared.b16 {%0,%1,%2,%3}, [%4];"
               : "=r"(r[0]), "=r"(r[1]), "=r"(r[2]), "=r"(r[3]) : "r"(addr) : "memory");
}
__device__ __forceinline__ void stsm4(uint32_t addr, uint32_t r0, uint32_t r1, uint32_t r2, uint32_t r3) {
  asm volatile("stmatrix.sync.aligned.m8n8.x4.shared.b16 [%0], {%1,%2,%3,%4};"
               ::"r"(addr), "r"(r0), "r"(r1), "r"(r2), "r"(r3) : "memory");
}
__device__ __forceinline__ void mma16816(float (&c)[4], const uint32_t (&a)[4], uint32_t b0, uint32_t b1) {
  asm volatile("mma.sync.aligned.m16n8k16.row.col.f32.bf16.bf16.f32 {%0,%1,%2,%3},{%4,%5,%6,%7},{%8,%9},{%0,%1,%2,%3};"
               : "+f"(c[0]), "+f"(c[1]), "+f"(c[2]), "+f"(c[3])
               : "r"(a[0]), "r"(a[1]), "r"(a[2]), "r"(a[3]), "r"(b0), "r"(b1));
}
__device__ __forceinline__ void add_frag(float (&c)[32], const uint32_t (&a)[4][4], uint32_t id) {
#pragma unroll
  for (int s = 0; s < 4; s++) {
    mma16816(*reinterpret_cast<float (*)[4]>(&c[8 * s]), a[s], id, 0u);
    mma16816(*reinterpret_cast<float (*)[4]>(&c[8 * s + 4]), a[s], 0u, id);
  }
}
__device__ __forceinline__ uint32_t pack2(float lo, float hi) {
  uint32_t r; asm("cvt.rn.bf16x2.f32 %0, %1, %2;" : "=r"(r) : "f"(hi), "f"(lo)); return r;
}
__device__ __forceinline__ float blo(uint32_t w) { return __uint_as_float(w << 16); }
__device__ __forceinline__ float bhi(uint32_t w) { return __uint_as_float(w & 0xFFFF0000u); }
__device__ __forceinline__ uint32_t hsub2(uint32_t a, uint32_t b) { uint32_t r; asm("sub.rn.bf16x2 %0, %1, %2;" : "=r"(r) : "r"(a), "r"(b)); return r; }
__device__ __forceinline__ uint32_t hmax2(uint32_t a, uint32_t b) { uint32_t r; asm("max.bf16x2 %0, %1, %2;" : "=r"(r) : "r"(a), "r"(b)); return r; }
__device__ __forceinline__ uint32_t hmin2(uint32_t a, uint32_t b) { uint32_t r; asm("min.bf16x2 %0, %1, %2;" : "=r"(r) : "r"(a), "r"(b)); return r; }
__device__ __forceinline__ float ex2(float x) { float r; asm("ex2.approx.ftz.f32 %0, %1;" : "=f"(r) : "f"(x)); return r; }
__device__ __forceinline__ float rcp(float x) { float r; asm("rcp.approx.ftz.f32 %0, %1;" : "=f"(r) : "f"(x)); return r; }
__device__ __forceinline__ void ld_rlx4(uint32_t (&r)[4], const uint4* p) {
  asm volatile("{\n.reg .b128 v;\nld.relaxed.gpu.global.b128 v, [%4];\nmov.b128 {%0,%1,%2,%3}, v;\n}"
               : "=r"(r[0]), "=r"(r[1]), "=r"(r[2]), "=r"(r[3]) : "l"(p) : "memory");
}
__device__ __forceinline__ void st_rlx4(uint4* p, uint32_t a, uint32_t b, uint32_t c, uint32_t d) {
  asm volatile("{\n.reg .b128 v;\nmov.b128 v, {%1,%2,%3,%4};\nst.relaxed.gpu.global.b128 [%0], v;\n}"
               ::"l"(p), "r"(a), "r"(b), "r"(c), "r"(d) : "memory");
}
__device__ __forceinline__ void st_rlx2(uint2* p, uint32_t a, uint32_t b) {
  asm volatile("{\n.reg .b64 v;\nmov.b64 v, {%1,%2};\nst.relaxed.gpu.global.b64 [%0], v;\n}" ::"l"(p), "r"(a), "r"(b) : "memory");
}
__device__ __forceinline__ uint32_t ld_rlx1(const uint32_t* p) {
  uint32_t r; asm volatile("ld.relaxed.gpu.global.b32 %0, [%1];" : "=r"(r) : "l"(p) : "memory"); return r;
}
__device__ __forceinline__ void st_rlx1(uint32_t* p, uint32_t a) {
  asm volatile("st.relaxed.gpu.global.b32 [%0], %1;" ::"l"(p), "r"(a) : "memory");
}
__device__ __forceinline__ void ld_rlx2(uint32_t& a, uint32_t& b, const uint2* p) {
  asm volatile("{\n.reg .b64 v;\nld.relaxed.gpu.b64 v, [%2];\nmov.b64 {%0,%1}, v;\n}" : "=r"(a), "=r"(b) : "l"(p) : "memory");
}
__device__ __forceinline__ void bulk_g2s(uint32_t dst, const void* src, uint32_t bytes, uint32_t bar) {
  asm volatile("cp.async.bulk.shared::cluster.global.mbarrier::complete_tx::bytes [%0], [%1], %2, [%3];"
               ::"r"(dst), "l"(src), "r"(bytes), "r"(bar) : "memory");
}
__device__ __forceinline__ uint32_t tg(uint32_t w, uint32_t T) { return (w & 0xFFFFFFFEu) | T; }
__device__ __forceinline__ uint32_t bad4(uint32_t a, uint32_t b, uint32_t c, uint32_t d, uint32_t T) {
  uint32_t u, v;
  asm("lop3.b32 %0, %1, %2, %3, 0x7E;" : "=r"(u) : "r"(a), "r"(b), "r"(T));
  asm("lop3.b32 %0, %1, %2, %3, 0x7E;" : "=r"(v) : "r"(c), "r"(d), "r"(T));
  asm("lop3.b32 %0, %1, %2, 1, 0xA8;" : "=r"(u) : "r"(u), "r"(v));
  return u;
}

__device__ __forceinline__ void ld_chunk(uint32_t (&a)[4][4], const uint4* p) {
#pragma unroll
  for (int s = 0; s < 4; s++) ld_rlx4(a[s], p + s * 32);
}
__device__ __forceinline__ void get_pair(uint32_t (&a)[4][4], uint32_t (&b)[4][4], const uint4* sp, const uint4* gp, uint32_t T) {
  int it = 0;
#pragma unroll 1
  do {
#pragma unroll
    for (int s = 0; s < 8; s++) {
      uint32_t (&r)[4] = s < 4 ? a[s & 3] : b[s & 3];
      asm volatile("{\n.reg .b128 v;\nld.relaxed.gpu.b128 v, [%4];\nmov.b128 {%0,%1,%2,%3}, v;\n}"
                   : "=r"(r[0]), "=r"(r[1]), "=r"(r[2]), "=r"(r[3]) : "l"(sp + (s >> 2) * 512 + (s & 3) * 32) : "memory");
    }
    sp = gp;
  } while (__any_sync(0xffffffffu, bad4(a[0][0], a[1][0], a[2][0], a[3][0], T) | bad4(b[0][0], b[1][0], b[2][0], b[3][0], T)) && ++it < (1 << 18));
}

__device__ __forceinline__ void wgmma_rs_n48(float (&d)[24], const uint32_t (&a)[4], uint32_t descB, int scaleD) {
  asm volatile("{\n.reg .pred p;\n.reg .b64 db;\nsetp.ne.b32 p, %29, 0;\nmov.b64 db, {%28, 0x40000040};\n"
    "wgmma.mma_async.sync.aligned.m64n48k16.f32.bf16.bf16 {%0,%1,%2,%3,%4,%5,%6,%7,%8,%9,%10,%11,%12,%13,%14,%15,%16,%17,%18,%19,%20,%21,%22,%23}, {%24,%25,%26,%27}, db, p, 1, 1, 1;\n}\n"
    : "+f"(d[0]),"+f"(d[1]),"+f"(d[2]),"+f"(d[3]),"+f"(d[4]),"+f"(d[5]),"+f"(d[6]),"+f"(d[7]),"+f"(d[8]),"+f"(d[9]),"+f"(d[10]),"+f"(d[11]),"+f"(d[12]),"+f"(d[13]),"+f"(d[14]),"+f"(d[15]),"+f"(d[16]),"+f"(d[17]),"+f"(d[18]),"+f"(d[19]),"+f"(d[20]),"+f"(d[21]),"+f"(d[22]),"+f"(d[23])
    : "r"(a[0]), "r"(a[1]), "r"(a[2]), "r"(a[3]), "r"(descB), "r"(scaleD));
}
__device__ __forceinline__ void wgmma_rs_n64(float (&d)[32], const uint32_t (&a)[4], uint32_t descB, int scaleD) {
  asm volatile("{\n.reg .pred p;\n.reg .b64 db;\nsetp.ne.b32 p, %37, 0;\nmov.b64 db, {%36, 0x40000040};\n"
    "wgmma.mma_async.sync.aligned.m64n64k16.f32.bf16.bf16 {%0,%1,%2,%3,%4,%5,%6,%7,%8,%9,%10,%11,%12,%13,%14,%15,%16,%17,%18,%19,%20,%21,%22,%23,%24,%25,%26,%27,%28,%29,%30,%31}, {%32,%33,%34,%35}, db, p, 1, 1, 1;\n}\n"
    : "+f"(d[0]),"+f"(d[1]),"+f"(d[2]),"+f"(d[3]),"+f"(d[4]),"+f"(d[5]),"+f"(d[6]),"+f"(d[7]),"+f"(d[8]),"+f"(d[9]),"+f"(d[10]),"+f"(d[11]),"+f"(d[12]),"+f"(d[13]),"+f"(d[14]),"+f"(d[15]),"+f"(d[16]),"+f"(d[17]),"+f"(d[18]),"+f"(d[19]),"+f"(d[20]),"+f"(d[21]),"+f"(d[22]),"+f"(d[23]),"+f"(d[24]),"+f"(d[25]),"+f"(d[26]),"+f"(d[27]),"+f"(d[28]),"+f"(d[29]),"+f"(d[30]),"+f"(d[31])
    : "r"(a[0]), "r"(a[1]), "r"(a[2]), "r"(a[3]), "r"(descB), "r"(scaleD));
}
__device__ __forceinline__ void wgmma_rs_n128(float (&d)[64], const uint32_t (&a)[4], uint32_t descB, int scaleD) {
  asm volatile("{\n.reg .pred p;\n.reg .b64 db;\nsetp.ne.b32 p, %69, 0;\nmov.b64 db, {%68, 0x40000040};\n"
    "wgmma.mma_async.sync.aligned.m64n128k16.f32.bf16.bf16 {%0,%1,%2,%3,%4,%5,%6,%7,%8,%9,%10,%11,%12,%13,%14,%15,%16,%17,%18,%19,%20,%21,%22,%23,%24,%25,%26,%27,%28,%29,%30,%31,%32,%33,%34,%35,%36,%37,%38,%39,%40,%41,%42,%43,%44,%45,%46,%47,%48,%49,%50,%51,%52,%53,%54,%55,%56,%57,%58,%59,%60,%61,%62,%63}, {%64,%65,%66,%67}, db, p, 1, 1, 1;\n}\n"
    : "+f"(d[0]),"+f"(d[1]),"+f"(d[2]),"+f"(d[3]),"+f"(d[4]),"+f"(d[5]),"+f"(d[6]),"+f"(d[7]),"+f"(d[8]),"+f"(d[9]),"+f"(d[10]),"+f"(d[11]),"+f"(d[12]),"+f"(d[13]),"+f"(d[14]),"+f"(d[15]),"+f"(d[16]),"+f"(d[17]),"+f"(d[18]),"+f"(d[19]),"+f"(d[20]),"+f"(d[21]),"+f"(d[22]),"+f"(d[23]),"+f"(d[24]),"+f"(d[25]),"+f"(d[26]),"+f"(d[27]),"+f"(d[28]),"+f"(d[29]),"+f"(d[30]),"+f"(d[31]),"+f"(d[32]),"+f"(d[33]),"+f"(d[34]),"+f"(d[35]),"+f"(d[36]),"+f"(d[37]),"+f"(d[38]),"+f"(d[39]),"+f"(d[40]),"+f"(d[41]),"+f"(d[42]),"+f"(d[43]),"+f"(d[44]),"+f"(d[45]),"+f"(d[46]),"+f"(d[47]),"+f"(d[48]),"+f"(d[49]),"+f"(d[50]),"+f"(d[51]),"+f"(d[52]),"+f"(d[53]),"+f"(d[54]),"+f"(d[55]),"+f"(d[56]),"+f"(d[57]),"+f"(d[58]),"+f"(d[59]),"+f"(d[60]),"+f"(d[61]),"+f"(d[62]),"+f"(d[63])
    : "r"(a[0]), "r"(a[1]), "r"(a[2]), "r"(a[3]), "r"(descB), "r"(scaleD));
}
__device__ __forceinline__ void wgmma_ss_n72_t11(float (&d)[36], uint32_t descA, uint32_t descB, int scaleD) {
  asm volatile("{\n.reg .pred p;\n.reg .b64 da, db;\nsetp.ne.b32 p, %38, 0;\nmov.b64 da, {%36, 0x40000040};\nmov.b64 db, {%37, 0x40000040};\n"
    "wgmma.mma_async.sync.aligned.m64n72k16.f32.bf16.bf16 {%0,%1,%2,%3,%4,%5,%6,%7,%8,%9,%10,%11,%12,%13,%14,%15,%16,%17,%18,%19,%20,%21,%22,%23,%24,%25,%26,%27,%28,%29,%30,%31,%32,%33,%34,%35}, da, db, p, 1, 1, 1, 1;\n}\n"
    : "+f"(d[0]),"+f"(d[1]),"+f"(d[2]),"+f"(d[3]),"+f"(d[4]),"+f"(d[5]),"+f"(d[6]),"+f"(d[7]),"+f"(d[8]),"+f"(d[9]),"+f"(d[10]),"+f"(d[11]),"+f"(d[12]),"+f"(d[13]),"+f"(d[14]),"+f"(d[15]),"+f"(d[16]),"+f"(d[17]),"+f"(d[18]),"+f"(d[19]),"+f"(d[20]),"+f"(d[21]),"+f"(d[22]),"+f"(d[23]),"+f"(d[24]),"+f"(d[25]),"+f"(d[26]),"+f"(d[27]),"+f"(d[28]),"+f"(d[29]),"+f"(d[30]),"+f"(d[31]),"+f"(d[32]),"+f"(d[33]),"+f"(d[34]),"+f"(d[35])
    : "r"(descA), "r"(descB), "r"(scaleD));
}

#define TSTAMP(i) do {} while (0)
#define TS2(w, i) do {} while (0)

constexpr float LOG2E = 1.4426950408889634f;

__device__ __forceinline__ void feat_exp(const uint32_t (&P)[4], float (&e)[16]) {
  uint32_t a = hmax2(P[0], P[2]), b = hmax2(P[1], P[3]);
  uint32_t mx = hmax2(__byte_perm(a, b, 0x5410), __byte_perm(a, b, 0x7632));
  a = hmin2(P[0], P[2]); b = hmin2(P[1], P[3]);
  uint32_t mn = hmin2(__byte_perm(a, b, 0x5410), __byte_perm(a, b, 0x7632));
  mx = hmax2(mx, __shfl_xor_sync(0xffffffffu, mx, 1));
  mn = hmin2(mn, __shfl_xor_sync(0xffffffffu, mn, 1));
  mx = hmax2(mx, __shfl_xor_sync(0xffffffffu, mx, 2));
  mn = hmin2(mn, __shfl_xor_sync(0xffffffffu, mn, 2));
  float mx0 = -blo(mx) * LOG2E, mx1 = -bhi(mx) * LOG2E, mn0 = blo(mn) * LOG2E, mn1 = bhi(mn) * LOG2E;
  float v[8] = {blo(P[0]), bhi(P[0]), blo(P[1]), bhi(P[1]), blo(P[2]), bhi(P[2]), blo(P[3]), bhi(P[3])};
#pragma unroll
  for (int i = 0; i < 8; i++) {
    bool r1 = (i >> 1) & 1;
    e[i]     = ex2(fmaf(v[i],  LOG2E, r1 ? mx1 : mx0));
    e[8 + i] = ex2(fmaf(v[i], -LOG2E, r1 ? mn1 : mn0));
  }
}

template <int SBASE>
__global__ void __cluster_dims__(2, 1, 1) __launch_bounds__(384, 1)
fused_kernel(const __grid_constant__ Maps maps, const __nv_bfloat16* __restrict__ x, const __nv_bfloat16* __restrict__ wphi,
             const __nv_bfloat16* __restrict__ wo, const __nv_bfloat16* __restrict__ wg_, const __nv_bfloat16* __restrict__ wu_,
             const __nv_bfloat16* __restrict__ wd_, __nv_bfloat16* __restrict__ out) {
  extern __shared__ __align__(1024) unsigned char smem[];
  const uint32_t sb = smem_u32(smem);
  const int tid = threadIdx.x, lane = tid & 31;
  const int warp = __shfl_sync(0xffffffffu, tid >> 5, 0);
  const uint32_t rank = blockIdx.x & 1;
  const int cl = blockIdx.x >> 1;
  int quad, qi;
  if (cl < 4) { quad = 15; qi = cl; }
  else if (cl < 36) { quad = (cl - 4) & 7; qi = (cl - 4) >> 3; }
  else { qi = (cl - 36) / 7; quad = 8 + (cl - 36) - 7 * qi; }
  const int rb = quad, hg = 2 * qi + rank;
  const int rb3 = (quad & ~1) + rank, jf = 4 * (quad & 1) + qi;

  if (warp < 8) {
    asm volatile("setmaxnreg.inc.sync.aligned.u32 240;");
    if (elect_one()) {
#pragma unroll 1
      for (int d = warp; d + 9 < NSTAGE; d += 8) {
        mbar_init(sb + SM_EMPTY + d * 8, st_empty_cnt(d));
        {
          mbar_init(sb + SM_FULL + (d + 9) * 8, 1);
          mbar_expect_tx(sb + SM_FULL + (d + 9) * 8, d + 9 >= ST_D ? 22528 : SLOT);
        }
      }
      asm volatile("fence.mbarrier_init.release.cluster;" ::: "memory");
    }
    __syncwarp();
    bar_sync(0, 352);
    asm volatile("barrier.cluster.arrive.relaxed.aligned;" ::: "memory");
    const int wg = warp >> 2, wq = warp & 3, g = lane >> 2, t = lane & 3;
    const bool lead = (tid & 127) == 0;
    const uint32_t db = ((SBASE ? (uint32_t)SBASE : (sb & 0x3FFFF)) >> 4) | (512u << 16);
    auto release = [&](int d) {
      const int s = d + NSLOT;
      mbar_arrive_cluster(sb + SM_EMPTY + d * 8, s >= ST_GU ? (uint32_t)(s & 1) : rank);
    };
    const uint32_t lrow = (uint32_t)(wq * 16 + (lane & 7) + ((lane >> 3) & 1) * 8) * 128;
    const uint32_t lx = lane & 7, lhi = lane >> 4;
    if (wg == 1) bar_arrive(4, 256);

    float r0, r1;
    uint32_t E[4][8];
    uint32_t T = 0;
    {
      uint32_t A[32][4];
      const int sx = wg ? ST_X1 : ST_X0;
      {
        const uint32_t base = sb + sx * SLOT + lrow, baseb = sb + sx * SLOT + (wq * 16 + lx + lhi * 8) * 128;
        float cs[2][4], c0[2][4], c1[2][4];
#pragma unroll
        for (int i = 0; i < 4; i++) { cs[0][i] = cs[1][i] = c0[0][i] = c0[1][i] = c1[0][i] = c1[1][i] = 0.f; }
#pragma unroll
        for (int c = 0; c < 8; c++) {
          if (c % 3 == 0) mbar_wait(sb + SM_FULL + (sx + c / 3) * 8);
#pragma unroll
          for (int k = 0; k < 4; k++) ldsm4(A[4 * c + k], base + c * 8192 + (((2 * k + lhi) ^ lx) << 4));
#pragma unroll
          for (int k = 0; k < 4; k++) {
            const uint32_t (&f)[4] = A[4 * c + k];
            uint32_t bt[4];
            ldsm4(bt, baseb + c * 8192 + (((2 * k + ((lane >> 3) & 1)) ^ lx) << 4));
            mma16816(cs[k & 1], f, 0x3F803F80u, 0x3F803F80u);
            mma16816(c0[k & 1], f, bt[0], bt[1]);
            mma16816(c1[k & 1], f, bt[2], bt[3]);
          }
        }
        const float s0 = (cs[0][0] + cs[1][0]) * (1.f / 512.f), s1 = (cs[0][2] + cs[1][2]) * (1.f / 512.f);
        asm volatile("barrier.cluster.wait.aligned;" ::: "memory");
        if (lane < 3) release(sx + lane);
        const uint32_t m0 = pack2(s0, s0), m1 = pack2(s1, s1);
        float q0 = (g & 1) ? c0[0][1] + c0[1][1] : c0[0][0] + c0[1][0];
        float q1 = (g & 1) ? c1[0][3] + c1[1][3] : c1[0][2] + c1[1][2];
        q0 = __shfl_sync(0xffffffffu, q0, (lane & ~3) | (g >> 1));
        q1 = __shfl_sync(0xffffffffu, q1, (lane & ~3) | (g >> 1));
        r0 = rsqrtf(fmaxf(q0 * (1.f / 512.f) - s0 * s0, 0.f) + 1e-5f);
        r1 = rsqrtf(fmaxf(q1 * (1.f / 512.f) - s1 * s1, 0.f) + 1e-5f);
#pragma unroll
        for (int ks = 0; ks < 32; ks++) {
          A[ks][0] = hsub2(A[ks][0], m0); A[ks][1] = hsub2(A[ks][1], m1);
          A[ks][2] = hsub2(A[ks][2], m0); A[ks][3] = hsub2(A[ks][3], m1);
        }
      }
      TSTAMP(1);
      const uint32_t wpa = sb + SM_WPHI + ((lane & 7) + ((lane >> 3) & 1) * 8) * 32 + lhi * 16;
      const uint32_t scr = sb + (wg ? (ST_SCR1 % NSLOT) : (ST_SCR0 % NSLOT)) * SLOT;
#pragma unroll 1
      for (int ps = 0; ps < 3; ps++) {
        const int st0 = ps == 0 ? ST_WK : (ps == 1 ? ST_WV : ST_WQ);
        const uint32_t wdesc = DESC((ps == 0 ? ST_WK % NSLOT : (ps == 1 ? ST_WV % NSLOT : ST_WQ % NSLOT)) * SLOT);
        float acc[32];
        bar_sync(4 + wg, 256);
#pragma unroll
        for (int i = 0; i < 3; i++) {
          mbar_wait(sb + SM_FULL + (st0 + i) * 8);
          wg_fence();
#pragma unroll
          for (int kk = 0; kk < (i < 2 ? 12 : 8); kk++)
            wgmma_rs_n64(acc, A[12 * i + kk], wdesc + ((i * SLOT + kk * 2048) >> 4), (i | kk) != 0);
          wg_commit();
          if (i == 1) { wg_wait<1>(); if (lead) release(st0); }
        }
        if (ps == 0 || wg == 0) bar_arrive(4 + (wg ^ 1), 256);
        uint32_t a[4][4], b[4][4];
        mbar_wait(sb + SM_MISCB);
        T = (*reinterpret_cast<volatile unsigned*>(smem + SM_EPOCH) & 1) ^ 1;
#pragma unroll
        for (int h = 0; h < 4; h++) ldsm4t(b[h], wpa + h * 512);
        wg_wait<0>();
        if ((tid & 127) < 2) release(st0 + 1 + (tid & 1));
        TSTAMP(2 + 2 * ps);
#pragma unroll
        for (int h = 0; h < 4; h++) {
          a[h][0] = pack2(acc[8 * h + 0] * r0, acc[8 * h + 1] * r0); a[h][1] = pack2(acc[8 * h + 2] * r1, acc[8 * h + 3] * r1);
          a[h][2] = pack2(acc[8 * h + 4] * r0, acc[8 * h + 5] * r0); a[h][3] = pack2(acc[8 * h + 6] * r1, acc[8 * h + 7] * r1);
        }
        if (ps != 1) {
          {
            float pp[4][2][4];
#pragma unroll
            for (int h = 0; h < 4; h++) {
#pragma unroll
              for (int i = 0; i < 4; i++) { pp[h][0][i] = 0.f; pp[h][1][i] = 0.f; }
              mma16816(pp[h][0], a[h], b[h][0], b[h][1]);
              mma16816(pp[h][1], a[h], b[h][2], b[h][3]);
            }
#pragma unroll
            for (int h = 0; h < 4; h++) {
              a[h][0] = pack2(pp[h][0][0], pp[h][0][1]); a[h][1] = pack2(pp[h][0][2], pp[h][0][3]);
              a[h][2] = pack2(pp[h][1][0], pp[h][1][1]); a[h][3] = pack2(pp[h][1][2], pp[h][1][3]);
            }
          }
          if (ps == 0) mbar_wait(sb + SM_EMPTY + (wg ? ST_SCR1 - NSLOT : ST_SCR0 - NSLOT) * 8);
#pragma unroll 1
          for (int hp = 0; hp < 2; hp++) {
            float e[2][16];
            feat_exp(a[0], e[0]);
            feat_exp(a[1], e[1]);
            if (ps == 0) {
#pragma unroll
              for (int h = 0; h < 2; h++) {
                const float (&f)[16] = e[h];
                float sp0 = (f[0] + f[1]) + (f[4] + f[5]), sp1 = (f[2] + f[3]) + (f[6] + f[7]);
                float sn0 = (f[8] + f[9]) + (f[12] + f[13]), sn1 = (f[10] + f[11]) + (f[14] + f[15]);
                sp0 += __shfl_xor_sync(0xffffffffu, sp0, 1); sp1 += __shfl_xor_sync(0xffffffffu, sp1, 1);
                sn0 += __shfl_xor_sync(0xffffffffu, sn0, 1); sn1 += __shfl_xor_sync(0xffffffffu, sn1, 1);
                sp0 += __shfl_xor_sync(0xffffffffu, sp0, 2); sp1 += __shfl_xor_sync(0xffffffffu, sp1, 2);
                sn0 += __shfl_xor_sync(0xffffffffu, sn0, 2); sn1 += __shfl_xor_sync(0xffffffffu, sn1, 2);
                sp0 = rcp(sp0); sp1 = rcp(sp1); sn0 = rcp(sn0); sn1 = rcp(sn1);
                const uint32_t dst = scr + hp * 8192 + lrow;
                stsm4(dst + (((h * 4 + lhi) ^ lx) << 4), pack2(f[0] * sp0, f[1] * sp0), pack2(f[2] * sp1, f[3] * sp1),
                      pack2(f[4] * sp0, f[5] * sp0), pack2(f[6] * sp1, f[7] * sp1));
                stsm4(dst + (((h * 4 + 2 + lhi) ^ lx) << 4), pack2(f[8] * sn0, f[9] * sn0), pack2(f[10] * sn1, f[11] * sn1),
                      pack2(f[12] * sn0, f[13] * sn0), pack2(f[14] * sn1, f[15] * sn1));
              }
            } else {
#pragma unroll
              for (int i = 0; i < 16; i++) {
                A[i >> 2][i & 3] = A[4 + (i >> 2)][i & 3];
                A[4 + (i >> 2)][i & 3] = pack2(e[i >> 3][2 * (i & 7)], e[i >> 3][2 * (i & 7) + 1]);
              }
            }
#pragma unroll
            for (int i = 0; i < 4; i++) { a[0][i] = a[2][i]; a[1][i] = a[3][i]; }
          }
        } else {
#pragma unroll
          for (int h = 0; h < 4; h++) stsm4(scr + 16384 + lrow + (((2 * h + lhi) ^ lx) << 4), a[h][0], a[h][1], a[h][2], a[h][3]);
          fence_async_smem();
          bar_sync(3, 256);
          float kv[36];
          wg_fence();
#pragma unroll
          for (int ks = 0; ks < 8; ks++) {
            const uint32_t sk = (ks < 4 ? (ST_SCR0 % NSLOT) : (ST_SCR1 % NSLOT)) * SLOT + (ks & 3) * 2048;
            const uint32_t dv = (DESC(sk + 16384) & 0xFFFFu) | (((SM_ONES - sk - 16384) >> 4) << 16);
            wgmma_ss_n72_t11(kv, DESC(sk) + wg * 512, dv, ks != 0);
          }
          wg_commit();
          if (wg == 1) bar_arrive(4, 256);
          wg_wait<0>();
          if (lead) { mbar_arrive(sb + SM_EMPTY + ST_SCR0 * 8); mbar_arrive(sb + SM_EMPTY + ST_SCR1 * 8); }
          const int hl = 2 * wg + (wq >> 1), f = (wq & 1) * 16 + g;
          float* kvp = &g_kv[T ^ 1][((hg * 4 + hl) * 32 + f) * 16 + 2 * t];
          float* zp = &g_z[T ^ 1][(hg * 4 + hl) * 32 + f];
          float c[8];
#pragma unroll
          for (int i = 0; i < 8; i++) c[i] = hl >= 2 ? (hl == 3 ? kv[24 + i] : kv[16 + i]) : (hl == 1 ? kv[8 + i] : kv[i]);
#pragma unroll
          for (int n = 0; n < 2; n++) {
            asm volatile("red.relaxed.gpu.global.add.v2.f32 [%0], {%1,%2};" ::"l"(kvp + n * 8), "f"(c[4 * n]), "f"(c[4 * n + 1]) : "memory");
            asm volatile("red.relaxed.gpu.global.add.v2.f32 [%0], {%1,%2};" ::"l"(kvp + n * 8 + 128), "f"(c[4 * n + 2]), "f"(c[4 * n + 3]) : "memory");
          }
          if (t < 2) asm volatile("red.relaxed.gpu.global.add.f32 [%0], %1;" ::"l"(zp + t * 8), "f"(t ? kv[34] : kv[32]) : "memory");
          bar_arrive(6 + wg, 160);
        }
        TSTAMP(3 + 2 * ps);
      }
#pragma unroll
      for (int i = 0; i < 32; i++) E[i >> 3][i & 7] = A[i >> 2][i & 3];
    }
    const int rh = 2 * rb + wg;
#define IDF ((g >> 1) == t ? ((g & 1) ? 0x3F800000u : 0x00003F80u) : 0u)
    const uint4* xb = reinterpret_cast<const uint4*>(smem + 2 * SLOT) + wq * 128 + lane;
    mbar_wait(sb + SM_KVB);
    {
      const int r = tid & 127;
      const float4* src = reinterpret_cast<const float4*>(smem + SM_KV32) + r;
#pragma unroll
      for (int i = 0; i < 4; i++) {
        const float4 a = src[i * 128];
        *reinterpret_cast<uint2*>(smem + SM_KVS + (i * 32 + (r >> 2)) * 48 + (r & 3) * 8) = make_uint2(pack2(a.x, a.y), pack2(a.z, a.w));
      }
      const uint32_t zz = pack2(reinterpret_cast<const float*>(smem + SM_ONES)[r], 1.0f);
      *reinterpret_cast<uint4*>(smem + SM_KVS + r * 48 + 32) = make_uint4(zz, zz, zz, zz);
      bar_sync(1 + wg, 128);
    }
    TSTAMP(8);
    {
      uint4* op = &g_o[rh][hg][wq][0][lane];
#pragma unroll 1
      for (int hp = 0; hp < 2; hp++) {
#pragma unroll
      for (int h = 0; h < 2; h++) {
        uint32_t b0[4], b1[4], b2[4];
        const uint32_t kb = sb + SM_KVS + ((2 * hp + h) * 32 + lane) * 48;
        ldsm4t(b0, kb); ldsm4t(b1, kb + 16); ldsm4t(b2, kb + 32);
        const uint32_t ep[4] = {E[h][0], E[h][1], E[h][2], E[h][3]}, en[4] = {E[h][4], E[h][5], E[h][6], E[h][7]};
        float np0[4] = {0, 0, 0, 0}, np1[4] = {0, 0, 0, 0}, nn0[4] = {0, 0, 0, 0}, nn1[4] = {0, 0, 0, 0}, dp[4] = {0, 0, 0, 0}, dn[4] = {0, 0, 0, 0};
        mma16816(dp, ep, b2[0], b2[1]);  mma16816(dn, en, b2[2], b2[3]);
        mma16816(np0, ep, b0[0], b0[1]); mma16816(nn0, en, b0[2], b0[3]);
        mma16816(np1, ep, b1[0], b1[1]); mma16816(nn1, en, b1[2], b1[3]);
        const float i0 = rcp(fmaf(dp[0], dn[1], fmaf(dn[0], dp[1], 1e-6f * dp[1] * dn[1])));
        const float i1 = rcp(fmaf(dp[2], dn[3], fmaf(dn[2], dp[3], 1e-6f * dp[3] * dn[3])));
        const float cp0 = dn[1] * i0, cn0 = dp[1] * i0, cp1 = dn[3] * i1, cn1 = dp[3] * i1;
        st_rlx4(op + (2 * hp + h) * 32,
                tg(pack2(fmaf(np0[0], cp0, nn0[0] * cn0), fmaf(np0[1], cp0, nn0[1] * cn0)), T),
                pack2(fmaf(np0[2], cp1, nn0[2] * cn1), fmaf(np0[3], cp1, nn0[3] * cn1)),
                pack2(fmaf(np1[0], cp0, nn1[0] * cn0), fmaf(np1[1], cp0, nn1[1] * cn0)),
                pack2(fmaf(np1[2], cp1, nn1[2] * cn1), fmaf(np1[3], cp1, nn1[3] * cn1)));
      }
#pragma unroll
        for (int i = 0; i < 8; i++) { E[0][i] = E[2][i]; E[1][i] = E[3][i]; }
      }
    }
    TSTAMP(9);

    {
      uint32_t xr[4][4];
      {
        const uint32_t* xp = reinterpret_cast<const uint32_t*>(x + (size_t)(rh * 64 + wq * 16 + g) * 512 + hg * 64 + 2 * t);
#pragma unroll
        for (int i = 0; i < 8; i++) { xr[i >> 1][(i & 1) * 2] = __ldg(xp + 4 * i); xr[i >> 1][(i & 1) * 2 + 1] = __ldg(xp + 8 * 256 + 4 * i); }
      }
      uint32_t A[8][4][4];
      const uint4* op = &g_o[rh][0][wq][0][lane];
      float acc[32];
#pragma unroll
      for (int i = 0; i < 32; i++) acc[i] = 0.f;
      add_frag(acc, xr, IDF);
#pragma unroll
      for (int p = 0; p < 4; p++) {
        mbar_wait(sb + SM_XF + (wg * 4 + p) * 8);
        get_pair(A[2 * p], A[2 * p + 1], xb + p * 1024, op + p * 1024, T);
        if (lane == 0) mbar_arrive(sb + SM_XE + (wg * 4 + p) * 8);
        if (p != 2) mbar_wait(sb + SM_FULL + (ST_WO + (p + 1) / 2) * 8);
        wg_fence();
#pragma unroll
        for (int c = 2 * p; c < 2 * p + 2; c++)
#pragma unroll
          for (int s = 0; s < 4; s++)
            wgmma_rs_n64(acc, A[c][s], DESC(((ST_WO + c / 3) % NSLOT) * SLOT + ((c % 3) * 4 + s) * 2048), 1);
      }
      wg_commit();
      wg_wait<0>();
      if ((tid & 127) < 3) release(ST_WO + (tid & 127));
      TSTAMP(10);
      uint32_t hw[4][4];
      uint4* hp_ = &g_h[rh][hg][wq][0][lane];
      float cs[4][4], c0[4][4], c1[4][4];
      uint32_t hx = T;
#pragma unroll
      for (int s = 0; s < 4; s++) {
#pragma unroll
        for (int r = 0; r < 4; r++) { hw[s][r] = pack2(acc[8 * s + 2 * r], acc[8 * s + 2 * r + 1]); cs[s][r] = c0[s][r] = c1[s][r] = 0.f; }
        st_rlx4(hp_ + s * 32, tg(hw[s][0], T), hw[s][1], hw[s][2], hw[s][3]);
        hx |= (hw[s][0] & 1u) << (s + 1);
      }
#pragma unroll
      for (int s = 0; s < 4; s++) {
        mma16816(cs[s], hw[s], 0x3F803F80u, 0x3F803F80u);
        mma16816(c0[s], hw[s], hw[s][0], hw[s][2]);
        mma16816(c1[s], hw[s], hw[s][1], hw[s][3]);
      }
      if (t == (g >> 1)) {
        const float q0 = (g & 1) ? (c0[0][1] + c0[1][1]) + (c0[2][1] + c0[3][1]) : (c0[0][0] + c0[1][0]) + (c0[2][0] + c0[3][0]);
        const float q1 = (g & 1) ? (c1[0][3] + c1[1][3]) + (c1[2][3] + c1[3][3]) : (c1[0][2] + c1[1][2]) + (c1[2][2] + c1[3][2]);
        st_rlx2(&g_st[rh][hg][wq * 16 + g], tg(__float_as_uint((cs[0][0] + cs[1][0]) + (cs[2][0] + cs[3][0])), T), __float_as_uint(q0));
        st_rlx2(&g_st[rh][hg][wq * 16 + g + 8], tg(__float_as_uint((cs[0][2] + cs[1][2]) + (cs[2][2] + cs[3][2])), T), __float_as_uint(q1));
      }
      st_rlx1(&g_hx[rh][hg][wq][lane], hx);
    }
    TSTAMP(11);

    const int rh3 = 2 * rb3 + wg;
    uint32_t HH[11][4];
    {
      uint32_t A[8][4][4];
      const uint4* hp_ = &g_h[rh3][0][wq][0][lane];
      uint4* hhp = &g_hh[rh3][jf][0][wq][lane];
      const uint32_t dg = (db & 0xFFFFu) | (256u << 16);
      uint32_t m0, m1;
      mbar_wait(sb + SM_XF + ((2 + wg) * 4) * 8);
      {
        const uint2* sp = reinterpret_cast<const uint2*>(smem + SM_KV32 + wg * 4096) + 2 * t * 64 + wq * 16 + g;
        uint2 a0, a1, b0, b1;
        int it = 0;
#pragma unroll 1
        do {
          ld_rlx2(a0.x, a0.y, sp); ld_rlx2(a1.x, a1.y, sp + 64); ld_rlx2(b0.x, b0.y, sp + 8); ld_rlx2(b1.x, b1.y, sp + 72);
          sp = &g_st[rh3][2 * t][wq * 16 + g];
        } while (__any_sync(0xffffffffu, bad4(a0.x, a1.x, b0.x, b1.x, T)) && ++it < (1 << 18));
        float s0 = __uint_as_float(a0.x) + __uint_as_float(a1.x), q0 = __uint_as_float(a0.y) + __uint_as_float(a1.y);
        float s1 = __uint_as_float(b0.x) + __uint_as_float(b1.x), q1 = __uint_as_float(b0.y) + __uint_as_float(b1.y);
        s0 += __shfl_xor_sync(0xffffffffu, s0, 1); s1 += __shfl_xor_sync(0xffffffffu, s1, 1);
        q0 += __shfl_xor_sync(0xffffffffu, q0, 1); q1 += __shfl_xor_sync(0xffffffffu, q1, 1);
        s0 += __shfl_xor_sync(0xffffffffu, s0, 2); s1 += __shfl_xor_sync(0xffffffffu, s1, 2);
        q0 += __shfl_xor_sync(0xffffffffu, q0, 2); q1 += __shfl_xor_sync(0xffffffffu, q1, 2);
        s0 *= (1.f / 512.f); s1 *= (1.f / 512.f);
        r0 = rcp(fmaxf(q0 * (1.f / 512.f) - s0 * s0, 0.f) + 1e-5f);
        r1 = rcp(fmaxf(q1 * (1.f / 512.f) - s1 * s1, 0.f) + 1e-5f);
        m0 = pack2(s0, s0); m1 = pack2(s1, s1);
      }
      TSTAMP(12);
#define UOFF(u) ((((ST_GU + (u) / 3) % NSLOT) * SLOT + ((u) % 3) * 8192) >> 4)
#define UNIT_PRE(u)  do { if ((u) % 3 == 0) mbar_wait(sb + SM_FULL + (ST_GU + (u) / 3) * 8); } while (0)
#define UNIT_POST(u) do { wg_commit(); if ((u) % 3 == 1 && (u) > 3) { wg_wait<2>(); if (lead) release(ST_GU + (u) / 3 - 1); } } while (0)
      float acc[64];
      const int rz = blockIdx.y;
#pragma unroll
      for (int ps = 0; ps < 2; ps++) {
        wg_fence();
#pragma unroll
        for (int k = 0; k < 16; k++) {
          const int u = 16 * ps + k, c = k >> 1;
          if (ps == 0 && k < 4) {
            if (k > 0) mbar_wait(sb + SM_XF + ((2 + wg) * 4 + k) * 8);
            get_pair(A[2 * k], A[2 * k + 1], xb + k * 1024, hp_ + k * 1024, T);
            if (lane == 0) {
              if (wg == 0) mbar_arrive(sb + SM_XE + (8 + k) * 8);
              else if (k > 0) release(ST_XC + k - 1);
            }
          }
          if (ps == 0 && (k & 1) == 0) {
#pragma unroll
            for (int s = 0; s < 4; s++) {
              A[c][s][0] = hsub2(A[c][s][0], m0); A[c][s][1] = hsub2(A[c][s][1], m1);
              A[c][s][2] = hsub2(A[c][s][2], m0); A[c][s][3] = hsub2(A[c][s][3], m1);
            }
            wg_fence();
          }
          UNIT_PRE(u);
          wgmma_rs_n128(acc, A[c][(k & 1) * 2], dg + UOFF(u), k != 0 ? 1 : (ps ? rz : 0));
          wgmma_rs_n128(acc, A[c][(k & 1) * 2 + 1], dg + UOFF(u) + 128, 1);
          UNIT_POST(u);
        }
        wg_wait<0>();
#pragma unroll
        for (int s = 0; s < 4; s++) {
          uint32_t (&hh)[4] = HH[4 + s];
          hh[0] = tg(pack2(acc[8 * s + 0] * acc[32 + 8 * s + 0] * r0, acc[8 * s + 1] * acc[32 + 8 * s + 1] * r0), T);
          hh[1] = pack2(acc[8 * s + 2] * acc[32 + 8 * s + 2] * r1, acc[8 * s + 3] * acc[32 + 8 * s + 3] * r1);
          hh[2] = pack2(acc[8 * s + 4] * acc[32 + 8 * s + 4] * r0, acc[8 * s + 5] * acc[32 + 8 * s + 5] * r0);
          hh[3] = pack2(acc[8 * s + 6] * acc[32 + 8 * s + 6] * r1, acc[8 * s + 7] * acc[32 + 8 * s + 7] * r1);
          st_rlx4(hhp + (4 * ps + s) * 128, hh[0], hh[1], hh[2], hh[3]);
        }
      }
      {
        float ag[24], au[24];
        bar_sync(1 + wg, 128);
        wg_fence();
#pragma unroll
        for (int k = 0; k < 16; k++) {
          const int u = 32 + k, c = k >> 1;
          UNIT_PRE(u);
          wgmma_rs_n48(ag, A[c][(k & 1) * 2], dg + UOFF(u), k != 0);
          wgmma_rs_n48(au, A[c][(k & 1) * 2], dg + UOFF(u) + 256, k != 0);
          wgmma_rs_n48(ag, A[c][(k & 1) * 2 + 1], dg + UOFF(u) + 128, 1);
          wgmma_rs_n48(au, A[c][(k & 1) * 2 + 1], dg + UOFF(u) + 256 + 128, 1);
          UNIT_POST(u);
        }
        wg_wait<0>();
        TSTAMP(13);
#pragma unroll
        for (int s = 0; s < 4; s++) ld_rlx4(HH[s], hhp + s * 128);
#pragma unroll
        for (int s = 0; s < 3; s++) {
          uint32_t (&hh)[4] = HH[8 + s];
          hh[0] = tg(pack2(ag[8 * s + 0] * au[8 * s + 0] * r0, ag[8 * s + 1] * au[8 * s + 1] * r0), T);
          hh[1] = pack2(ag[8 * s + 2] * au[8 * s + 2] * r1, ag[8 * s + 3] * au[8 * s + 3] * r1);
          hh[2] = pack2(ag[8 * s + 4] * au[8 * s + 4] * r0, ag[8 * s + 5] * au[8 * s + 5] * r0);
          hh[3] = pack2(ag[8 * s + 6] * au[8 * s + 6] * r1, ag[8 * s + 7] * au[8 * s + 7] * r1);
          st_rlx4(hhp + (8 + s) * 128, hh[0], hh[1], hh[2], hh[3]);
        }
      }
    }
    TSTAMP(14);

    {
      float ac[3][32], acc[32];
      uint32_t PH[11][4], hr[4][4];
      const int m = jf >> 1, oc = (jf & 1) * 4 + m;
      const uint4* pp = &g_hh[rh3][jf ^ 1][0][wq][lane];
      bar_arrive(8 + wg, 256);
#pragma unroll
      for (int s = 0; s < 8; s++) ld_rlx4(PH[s], pp + s * 128);
      wg_fence();
#pragma unroll
      for (int k = 0; k < 3; k++) {
        mbar_wait(sb + SM_FULL + (ST_D + k) * 8);
        if (k == 2) {
#pragma unroll
          for (int s = 8; s < 11; s++) ld_rlx4(PH[s], pp + s * 128);
        }
#pragma unroll
        for (int s = 4; s < 11; s++) wgmma_rs_n64(ac[k], HH[s], DESC(((ST_D + k) % NSLOT) * SLOT + s * 2048), s != 4);
        if (k == 0) wg_fence();
#pragma unroll
        for (int s = 0; s < 4; s++) wgmma_rs_n64(ac[k], HH[s], DESC(((ST_D + k) % NSLOT) * SLOT + s * 2048), 1);
      }
      wg_commit();
      {
        int it = 0;
#pragma unroll 1
        while (__any_sync(0xffffffffu, bad4(PH[0][0], PH[1][0], PH[2][0], PH[3][0], T) | bad4(PH[4][0], PH[5][0], PH[6][0], PH[7][0], T) |
                                       bad4(PH[8][0], PH[9][0], PH[10][0], T, T))) {
#pragma unroll
          for (int s = 0; s < 11; s++) ld_rlx4(PH[s], pp + s * 128);
          if (++it > (1 << 18)) break;
        }
      }
      TSTAMP(20);
      uint4* outb = &g_part[rh3][(jf & 1) * 4][m][wq][0][lane];
#pragma unroll
      for (int k = 0; k < 4; k++) {
        mbar_wait(sb + SM_FULL + (ST_D + 3 + k) * 8);
        wg_fence();
#pragma unroll
        for (int s = 0; s < 11; s++) {
          if (k < 3) wgmma_rs_n64(ac[k], PH[s], DESC(((ST_D + 3 + k) % NSLOT) * SLOT + s * 2048), 1);
          else wgmma_rs_n64(acc, HH[s], DESC(((ST_D + 6) % NSLOT) * SLOT + s * 2048), s != 0);
        }
        wg_commit();
        if (k > 0) {
          wg_wait<1>();
          const float (&a)[32] = ac[k - 1];
          uint4* p = outb + ((m + k) & 3) * 2048;
#pragma unroll
          for (int s = 0; s < 4; s++)
            st_rlx4(p + s * 32, tg(pack2(a[8 * s + 0], a[8 * s + 1]), T), pack2(a[8 * s + 2], a[8 * s + 3]),
                    pack2(a[8 * s + 4], a[8 * s + 5]), pack2(a[8 * s + 6], a[8 * s + 7]));
        }
      }
      ld_chunk(hr, &g_h[rh3][oc][wq][0][lane]);
      mbar_wait(sb + SM_FULL + (ST_D + 7) * 8);
      wg_fence();
#pragma unroll
      for (int s = 0; s < 11; s++) wgmma_rs_n64(acc, PH[s], DESC(((ST_D + 7) % NSLOT) * SLOT + s * 2048), 1);
      wg_commit();
      uint32_t hx = ld_rlx1(&g_hx[rh3][oc][wq][lane]);
      uint32_t in[3][4][4];
      const uint4* inb = &g_part[rh3][oc][0][wq][0][lane];
      {
        const uint32_t* hint = reinterpret_cast<const uint32_t*>(&g_part[rh3][oc][(m - 1 - lane) & 3][wq][3][31]);
        uint32_t ready = 0; int it = 0;
#pragma unroll
        for (int q = 0; q < 3; q++) {
#pragma unroll 1
          while (!((ready >> q) & 1)) {
            ready = __ballot_sync(0xffffffffu, ((ld_rlx1(hint) ^ T) & 1) == 0);
            if (++it > (1 << 18)) break;
          }
          ld_chunk(in[q], inb + ((m - 1 - q) & 3) * 512);
        }
#pragma unroll 1
        while (__any_sync(0xffffffffu, bad4(in[0][0][0], in[0][1][0], in[0][2][0], in[0][3][0], T) | bad4(in[1][0][0], in[1][1][0], in[1][2][0], in[1][3][0], T) |
                                       bad4(in[2][0][0], in[2][1][0], in[2][2][0], in[2][3][0], T) | ((hx ^ T) & 1))) {
#pragma unroll
          for (int q = 0; q < 3; q++) ld_chunk(in[q], inb + ((m - 1 - q) & 3) * 512);
          hx = ld_rlx1(&g_hx[rh3][oc][wq][lane]);
          if (++it > (1 << 18)) break;
        }
      }
      wg_wait<0>();
      TSTAMP(15);
#pragma unroll
      for (int s = 0; s < 4; s++) hr[s][0] = (hr[s][0] & 0xFFFFFFFEu) | ((hx >> (s + 1)) & 1u);
      add_frag(acc, hr, IDF); add_frag(acc, in[0], IDF); add_frag(acc, in[1], IDF); add_frag(acc, in[2], IDF);
      bar_sync(9 - wg, 256);
      const uint32_t ob = sb + ((ST_D - 1) % NSLOT) * SLOT + wg * 8192;
#pragma unroll
      for (int s = 0; s < 4; s++)
        stsm4(ob + lrow + (((2 * s + lhi) ^ lx) << 4), pack2(acc[8 * s + 0], acc[8 * s + 1]), pack2(acc[8 * s + 2], acc[8 * s + 3]),
              pack2(acc[8 * s + 4], acc[8 * s + 5]), pack2(acc[8 * s + 6], acc[8 * s + 7]));
      __syncwarp();
#pragma unroll
      for (int i = 0; i < 4; i++) {
        const int row = wq * 16 + i * 4 + (lane >> 3);
        uint4 v;
        asm volatile("ld.shared.v4.b32 {%0,%1,%2,%3}, [%4];" : "=r"(v.x), "=r"(v.y), "=r"(v.z), "=r"(v.w)
                     : "r"(ob + row * 128 + ((lx ^ (row & 7)) << 4)) : "memory");
        asm volatile("st.global.v4.b32 [%0], {%1,%2,%3,%4};" ::"l"(out + (size_t)(rh3 * 64 + row) * 512 + oc * 64 + lx * 8),
                     "r"(v.x), "r"(v.y), "r"(v.z), "r"(v.w) : "memory");
      }
    }
    TSTAMP(16);
    asm volatile("barrier.cluster.arrive.relaxed.aligned;" ::: "memory");
    asm volatile("barrier.cluster.wait.aligned;" ::: "memory");
  } else {
    asm volatile("setmaxnreg.dec.sync.aligned.u32 24;");
    if (elect_one()) {
      if (warp == 8) {
#pragma unroll
        for (int k = 0; k < 9; k++) {
          const int s = k < 3 ? k : (k < 6 ? k + 3 : k - 3);
          const uint32_t bar = sb + SM_FULL + s * 8;
          mbar_init(bar, 1);
          mbar_expect_tx(bar, SLOT);
          if (s >= 3 && s < 6) tma2d(sb + s * SLOT, &maps.w, 512 + hg * 64, (s - 3) * 192, bar);
          else tma3d(sb + s * SLOT, &maps.x, 0, rb * 128 + (s >= 6 ? 64 : 0), 3 * (s % 3), bar);
        }
      } else if (warp == 9) {
        mbar_init(sb + SM_MISCB, 2);
        mbar_init(sb + SM_KVB, 32);
        mbar_expect_tx(sb + SM_MISCB, 2048);
        bulk_g2s(sb + SM_WPHI, wphi + hg * 1024, 2048, sb + SM_MISCB);
      } else if (warp == 10) {
#pragma unroll 1
        for (int i = 0; i < 16; i++) {
          mbar_init(sb + SM_XF + i * 8, 1);
          mbar_expect_tx(sb + SM_XF + i * 8, (i == 8 || i == 12) ? 20480 : 16384);
          if (i < 12) mbar_init(sb + SM_XE + i * 8, 4);
        }
      } else {
        *reinterpret_cast<volatile unsigned*>(smem + SM_EPOCH) = atomicAdd(&g_start, 1u) / NCTA;
      }
      asm volatile("fence.mbarrier_init.release.cluster;" ::: "memory");
    }
    __syncwarp();
    if (warp != 11) bar_sync(0, 352);
    asm volatile("barrier.cluster.arrive.relaxed.aligned;" ::: "memory");
    if (warp == 8) {
      asm volatile("barrier.cluster.wait.aligned;" ::: "memory");
      if (elect_one()) {
        const CUtensorMap* mg = jf == 7 ? &maps.g7 : &maps.g;
        const CUtensorMap* mu = jf == 7 ? &maps.u7 : &maps.u;
        asm volatile("prefetch.tensormap [%0];" ::"l"(&maps.wo) : "memory");
        asm volatile("prefetch.tensormap [%0];" ::"l"(mg) : "memory");
        asm volatile("prefetch.tensormap [%0];" ::"l"(mu) : "memory");
        asm volatile("prefetch.tensormap [%0];" ::"l"(&maps.d) : "memory");
#pragma unroll 1
        for (int s = ST_WV; s < ST_XC; s++) {
          if (s == ST_SCR1) continue;
          mbar_wait(sb + SM_EMPTY + (s - 9) * 8);
          const uint32_t dst = sb + (s >= 18 ? s - 18 : s - 9) * SLOT, bar = sb + SM_FULL + s * 8;
          if (s < ST_WO) tma2d(dst, &maps.w, (s < ST_WQ ? 1024 : 0) + hg * 64, (s < ST_WQ ? s - ST_WV : s - ST_WQ) * 192, bar);
          else { mbar_wait(bar - 8); tma2d(dst, &maps.wo, hg * 64, (s - ST_WO) * 192, bar); }
        }
        const int jc = jf == 7 ? 0 : jf;
        int slot = (ST_GU + 1 - rank) % NSLOT;
#pragma unroll 1
        for (int s = ST_GU + 1 - rank; s < NSTAGE; s += 2) {
          mbar_wait(sb + SM_EMPTY + (s - 9) * 8);
          if (s > ST_GU && s < ST_GU + THR) mbar_wait(sb + SM_FULL + (s - 1) * 8);
          const uint32_t dst = sb + slot * SLOT, bar = sb + SM_FULL + s * 8;
          if (s < ST_D) {
#pragma unroll 1
            for (int i = 0; i < 3; i++) {
              const int u = (s - ST_GU) * 3 + i;
              tma3d_mc(dst + i * 8192, mg, (u >> 4) * 64, jc, (u & 15) * 32, bar);
              tma3d_mc(dst + i * 8192 + 4096, mu, (u >> 4) * 64, jc, (u & 15) * 32, bar);
            }
          } else {
            const int i = s - ST_D, k = i < 3 ? i : (i < 6 ? i - 3 : 3), pt = (i >= 3 && i != 6) ? 1 : 0;
            tma2d_mc(dst, &maps.d, ((jf & 1) * 4 + (((jf >> 1) + 1 + k) & 3)) * 64, (jf ^ pt) * 176, bar);
          }
          slot += 2; if (slot >= NSLOT) slot -= NSLOT;
        }
      }
      __syncwarp();
    } else {
      asm volatile("barrier.cluster.wait.aligned;" ::: "memory");
      if (warp == 11) {
#pragma unroll
        for (int i = 0; i < 4; i++)
          reinterpret_cast<uint4*>(smem + SM_ONES)[lane + 32 * i] = make_uint4(0x3F803F80u, 0x3F803F80u, 0x3F803F80u, 0x3F803F80u);
        fence_async_smem();
        __syncwarp();
        if (lane == 0) mbar_arrive(sb + SM_MISCB);
      }
      mbar_wait(sb + SM_MISCB);
      const unsigned epoch = *reinterpret_cast<volatile unsigned*>(smem + SM_EPOCH);
      const uint32_t T = (epoch & 1) ^ 1;
      if (warp == 11) {
        reinterpret_cast<float4*>(&g_kv[T][blockIdx.x * 128])[lane] = make_float4(0.f, 0.f, 0.f, 0.f);
        if (lane < 8) g_z[T][blockIdx.x * 8 + lane] = 0.f;
        mbar_wait(sb + SM_FULL + (ST_WK + 2) * 8);
        if (elect_one()) {
          asm volatile("cp.async.bulk.prefetch.L2.global [%0], 4096;" ::"l"((const char*)wo + blockIdx.x * 4096) : "memory");
          asm volatile("cp.async.bulk.prefetch.L2.global [%0], 11008;" ::"l"((const char*)wg_ + blockIdx.x * 11008) : "memory");
          asm volatile("cp.async.bulk.prefetch.L2.global [%0], 11008;" ::"l"((const char*)wu_ + blockIdx.x * 11008) : "memory");
          asm volatile("cp.async.bulk.prefetch.L2.global [%0], 11008;" ::"l"((const char*)wd_ + blockIdx.x * 11008) : "memory");
          const unsigned target = (epoch + 1) * 32;
          unsigned v; int it = 0;
#pragma unroll 1
          do {
            asm volatile("ld.acquire.gpu.global.u32 %0, [%1];" : "=r"(v) : "l"(&g_kvcnt[hg * 32]) : "memory");
            if (++it > (1 << 18)) break;
          } while ((int)(v - target) < 0);
          TS2(0, 26);
        }
        __syncwarp();
        {
          const char* src = reinterpret_cast<const char*>(&g_kv[T ^ 1][hg * 2048]) + lane * 16;
#pragma unroll 4
          for (int i = 0; i < 16; i++)
            asm volatile("cp.async.cg.shared.global [%0], [%1], 16;" ::"r"(sb + SM_KV32 + lane * 16 + i * 512), "l"(src + i * 512) : "memory");
          asm volatile("cp.async.cg.shared.global [%0], [%1], 16;" ::"r"(sb + SM_ONES + lane * 16), "l"(&g_z[T ^ 1][hg * 128 + lane * 4]) : "memory");
          asm volatile("cp.async.mbarrier.arrive.noinc.shared::cta.b64 [%0];" ::"r"(sb + SM_KVB) : "memory");
        }
      } else {
        const int w = warp - 9;
        st_rlx4(reinterpret_cast<uint4*>(&g_st[2 * rb + w][hg][0]) + lane, T ^ 1, T ^ 1, T ^ 1, T ^ 1);
        if (lane < 8) st_rlx4(&g_o[2 * rb + w][hg][lane >> 1][3][30 + (lane & 1)], T ^ 1, T ^ 1, T ^ 1, T ^ 1);
        st_rlx4(&g_part[2 * rb3 + w][(jf & 1) * 4 + (lane >> 3)][jf >> 1][(lane >> 1) & 3][3][30 + (lane & 1)], T ^ 1, T ^ 1, T ^ 1, T ^ 1);
        bar_sync(6 + w, 160);
        if (elect_one()) {
          asm volatile("fence.release.gpu;" ::: "memory");
          TS2(w, 25);
          asm volatile("red.relaxed.gpu.global.add.u32 [%0], 1;" ::"l"(&g_kvcnt[hg * 32]) : "memory");
        }
        mbar_wait(sb + SM_KVB);
        if (w == 0) { mbar_wait(sb + SM_EMPTY + 11 * 8); mbar_wait(sb + SM_EMPTY + 12 * 8); mbar_wait(sb + SM_EMPTY + 13 * 8); }
#pragma unroll 1
        for (int ph = 0; ph < 2; ph++) {
          const int use = 2 * ph + w, r = ph ? 2 * rb3 + w : 2 * rb + w;
          const uint32_t* pw = ph ? reinterpret_cast<const uint32_t*>(&g_st[r][lane >> 2][(lane & 3) * 16 + 15])
                                  : reinterpret_cast<const uint32_t*>(&g_o[r][lane >> 2][lane & 3][3][31]);
          const char* src = reinterpret_cast<const char*>(ph ? &g_h[r][0][0][0][0] : &g_o[r][0][0][0][0]);
          const uint32_t bf = sb + SM_XF + use * 32, be = sb + SM_XE + (use - 1) * 32;
          if (ph) mbar_wait(sb + SM_XE + w * 32 + 24);
          int it = 0;
#pragma unroll 1
          while (__any_sync(0xffffffffu, (ld_rlx1(pw) ^ T) & 1)) { if (++it > (1 << 18)) break; }
          if (elect_one()) {
            TS2(w, 27 + ph);
            if (use > 0) mbar_wait(be);
            if (ph) bulk_g2s(sb + SM_KV32 + w * 4096, &g_st[r][0][0], 4096, bf);
#pragma unroll
            for (int p = 0; p < 4; p++) {
              if (p > 0 && use > 0) mbar_wait(be + p * 8);
              bulk_g2s(sb + 2 * SLOT + p * 16384, src + p * 16384, 16384, bf + p * 8);
            }
          }
          __syncwarp();
        }
      }
    }
    asm volatile("barrier.cluster.arrive.relaxed.aligned;" ::: "memory");
    asm volatile("barrier.cluster.wait.aligned;" ::: "memory");
  }
}

typedef CUresult (*EncodeFn)(CUtensorMap*, CUtensorMapDataType, cuuint32_t, void*, const cuuint64_t*, const cuuint64_t*,
                             const cuuint32_t*, const cuuint32_t*, CUtensorMapInterleave, CUtensorMapSwizzle,
                             CUtensorMapL2promotion, CUtensorMapFloatOOBfill);

void encode(EncodeFn fn, CUtensorMap* m, const void* base, int rank, const cuuint64_t* dims, const cuuint64_t* strides,
            const cuuint32_t* box) {
  cuuint32_t es[3] = {1, 1, 1};
  fn(m, CU_TENSOR_MAP_DATA_TYPE_BFLOAT16, (cuuint32_t)rank, const_cast<void*>(base), dims, strides, box, es,
     CU_TENSOR_MAP_INTERLEAVE_NONE, CU_TENSOR_MAP_SWIZZLE_128B, CU_TENSOR_MAP_L2_PROMOTION_L2_256B,
     CU_TENSOR_MAP_FLOAT_OOB_FILL_NONE);
}

}

extern "C" void kernel_launch(void* const* d_in, const int* in_sizes, int n_in, void* d_out, int out_size) {
  (void)in_sizes; (void)n_in; (void)out_size;
  const __nv_bfloat16* x    = (const __nv_bfloat16*)d_in[0];
  const __nv_bfloat16* wqkv = (const __nv_bfloat16*)d_in[1];
  const __nv_bfloat16* wphi = (const __nv_bfloat16*)d_in[2];
  const __nv_bfloat16* wo   = (const __nv_bfloat16*)d_in[3];
  const __nv_bfloat16* wg   = (const __nv_bfloat16*)d_in[5];
  const __nv_bfloat16* wu   = (const __nv_bfloat16*)d_in[6];
  const __nv_bfloat16* wd   = (const __nv_bfloat16*)d_in[7];

  static EncodeFn fn = nullptr;
  static int reserved = 0;
  if (!fn) {
    void* p = nullptr;
    cudaDriverEntryPointQueryResult qr;
    cudaGetDriverEntryPoint("cuTensorMapEncodeTiled", &p, cudaEnableDefault, &qr);
    fn = (EncodeFn)p;
    cudaFuncSetAttribute(fused_kernel<1024>, cudaFuncAttributeMaxDynamicSharedMemorySize, SM_TOTAL);
    cudaFuncSetAttribute(fused_kernel<0>, cudaFuncAttributeMaxDynamicSharedMemorySize, SM_TOTAL);
    int dev = 0;
    cudaGetDevice(&dev);
    cudaDeviceGetAttribute(&reserved, cudaDevAttrReservedSharedMemoryPerBlock, dev);
  }
  Maps maps;
  {
    cuuint64_t d[3] = {64, 2048, 8}, s[2] = {1024, 128}; cuuint32_t b[3] = {64, 64, 3};
    encode(fn, &maps.x, x, 3, d, s, b);
  }
  {
    cuuint64_t d[2] = {1536, 512}, s[1] = {3072}; cuuint32_t b[2] = {64, 192};
    encode(fn, &maps.w, wqkv, 2, d, s, b);
  }
  {
    cuuint64_t d[2] = {512, 512}, s[1] = {1024}; cuuint32_t b[2] = {64, 192};
    encode(fn, &maps.wo, wo, 2, d, s, b);
  }
  {
    cuuint64_t d[3] = {176, 7, 512}, d7[3] = {144, 1, 512}, s[2] = {352, 2752}; cuuint32_t b[3] = {64, 1, 32};
    encode(fn, &maps.g, wg, 3, d, s, b);
    encode(fn, &maps.u, wu, 3, d, s, b);
    encode(fn, &maps.g7, wg + 1232, 3, d7, s, b);
    encode(fn, &maps.u7, wu + 1232, 3, d7, s, b);
  }
  {
    cuuint64_t d[2] = {512, 1376}, s[1] = {1024}; cuuint32_t b[2] = {64, 176};
    encode(fn, &maps.d, wd, 2, d, s, b);
  }
  if (reserved == 1024) fused_kernel<1024><<<NCTA, 384, SM_TOTAL>>>(maps, x, wphi, wo, wg, wu, wd, (__nv_bfloat16*)d_out);
  else fused_kernel<0><<<NCTA, 384, SM_TOTAL>>>(maps, x, wphi, wo, wg, wu, wd, (__nv_bfloat16*)d_out);
}
```

```cpp
#include <cuda_runtime.h>
#include <cuda_bf16.h>
#include <cuda.h>
#include <stdint.h>

#define PROF 0

#define SAFE_WAIT 0
#define VAR 0
#define POLLV 0
#define THR 6

namespace {

constexpr int NCTA   = 128;
constexpr int SLOT   = 24576;
constexpr int NSLOT  = 9;
constexpr int NSTAGE = 47;

constexpr int ST_X0   = 0;
constexpr int ST_WK   = 3;
constexpr int ST_X1   = 6;
constexpr int ST_SCR0 = 9;
constexpr int ST_WV   = 10;
constexpr int ST_SCR1 = 13;
constexpr int ST_WQ   = 14;
constexpr int ST_WO   = 17;
constexpr int ST_XC   = 20;
constexpr int ST_GU   = 23;
constexpr int ST_D    = 39;

__host__ __device__ constexpr int st_empty_cnt(int d) {
  return ((d < 3 || (d >= 6 && d < 9) || (d >= ST_XC && d < ST_GU)) ? 4 : 2) * (d + 9 >= ST_GU ? 2 : 1);
}

constexpr int SM_ONES = NSLOT * SLOT;
constexpr int SM_WPHI = SM_ONES + 2048;
constexpr int SM_KVS  = SM_WPHI + 2048;
constexpr int SM_KV32 = 4 * SLOT + 16384;
constexpr int SM_BAR  = SM_KVS + 6144;
constexpr int SM_FULL  = SM_BAR;
constexpr int SM_EMPTY = SM_BAR + NSTAGE * 8;
constexpr int SM_MISCB = SM_BAR + 2 * NSTAGE * 8;
constexpr int SM_KVB   = SM_MISCB + 8;
constexpr int SM_EPOCH = SM_KVB + 8;
constexpr int SM_XF    = SM_EPOCH + 8;
constexpr int SM_XE    = SM_XF + 16 * 8;
constexpr int SM_TOTAL = SM_BAR + 1024;

static_assert(SM_TOTAL == 232448 && SM_XE + 12 * 8 <= SM_TOTAL, "smem budget");

struct Maps { CUtensorMap x, w, wo, g, u, g7, u7, d; };

__device__ uint4    g_o[32][8][4][4][32];
__device__ uint4    g_h[32][8][4][4][32];
__device__ uint32_t g_hx[32][8][4][32];
__device__ uint2    g_st[32][8][64];
__device__ uint4    g_hh[32][8][11][4][32];
__device__ uint4    g_part[32][8][4][4][4][32];
__device__ float    g_kv[2][32 * 32 * 16];
__device__ float    g_z[2][32 * 32];
__device__ unsigned g_kvcnt[8 * 32];
__device__ unsigned g_start;

__device__ __forceinline__ uint32_t smem_u32(const void* p) { return (uint32_t)__cvta_generic_to_shared(p); }
__device__ __forceinline__ void mbar_init(uint32_t bar, int cnt) {
  asm volatile("mbarrier.init.shared::cta.b64 [%0], %1;" ::"r"(bar), "r"(cnt) : "memory");
}
__device__ __forceinline__ void mbar_expect_tx(uint32_t bar, uint32_t bytes) {
  asm volatile("mbarrier.arrive.expect_tx.shared::cta.b64 _, [%0], %1;" ::"r"(bar), "r"(bytes) : "memory");
}
__device__ __forceinline__ void mbar_arrive(uint32_t bar) {
  asm volatile("mbarrier.arrive.shared::cta.b64 _, [%0];" ::"r"(bar) : "memory");
}
__device__ __forceinline__ void mbar_arrive_cluster(uint32_t bar, uint32_t rank) {
  asm volatile("{\n.reg .b32 ra;\nmapa.shared::cluster.u32 ra, %0, %1;\n"
               "mbarrier.arrive.shared::cluster.b64 _, [ra];\n}" ::"r"(bar), "r"(rank) : "memory");
}
__device__ __forceinline__ void mbar_wait_p(uint32_t bar, uint32_t parity) {
  asm volatile("{\n.reg .pred p;\nW: mbarrier.try_wait.parity.shared::cta.b64 p, [%0], %1;\n@!p bra W;\n}" ::"r"(bar), "r"(parity) : "memory");
}
__device__ __forceinline__ void mbar_wait(uint32_t bar) { mbar_wait_p(bar, 0); }
__device__ __forceinline__ bool elect_one() {
  uint32_t p;
  asm volatile("{\n.reg .pred P;\nelect.sync _|P, 0xffffffff;\nselp.u32 %0, 1, 0, P;\n}" : "=r"(p));
  return p != 0;
}
__device__ __forceinline__ void bar_sync(int id, int n)   { asm volatile("bar.sync %0, %1;" ::"r"(id), "r"(n) : "memory"); }
__device__ __forceinline__ void bar_arrive(int id, int n) { asm volatile("bar.arrive %0, %1;" ::"r"(id), "r"(n) : "memory"); }
__device__ __forceinline__ void fence_async_smem() { asm volatile("fence.proxy.async.shared::cta;" ::: "memory"); }
__device__ __forceinline__ void wg_fence()  { asm volatile("wgmma.fence.sync.aligned;" ::: "memory"); }
__device__ __forceinline__ void wg_commit() { asm volatile("wgmma.commit_group.sync.aligned;" ::: "memory"); }
template <int N> __device__ __forceinline__ void wg_wait() { asm volatile("wgmma.wait_group.sync.aligned %0;" ::"n"(N) : "memory"); }
#define DESC(off) (db + ((uint32_t)(off) >> 4))
__device__ __forceinline__ void tma2d(uint32_t dst, const CUtensorMap* m, int c0, int c1, uint32_t bar) {
  asm volatile("cp.async.bulk.tensor.2d.shared::cluster.global.mbarrier::complete_tx::bytes [%0], [%1, {%3, %4}], [%2];"
               ::"r"(dst), "l"(m), "r"(bar), "r"(c0), "r"(c1) : "memory");
}
__device__ __forceinline__ void tma2d_mc(uint32_t dst, const CUtensorMap* m, int c0, int c1, uint32_t bar) {
  asm volatile("cp.async.bulk.tensor.2d.shared::cluster.global.mbarrier::complete_tx::bytes.multicast::cluster [%0], [%1, {%3, %4}], [%2], %5;"
               ::"r"(dst), "l"(m), "r"(bar), "r"(c0), "r"(c1), "h"((uint16_t)3) : "memory");
}
__device__ __forceinline__ void tma3d(uint32_t dst, const CUtensorMap* m, int c0, int c1, int c2, uint32_t bar) {
  asm volatile("cp.async.bulk.tensor.3d.shared::cluster.global.mbarrier::complete_tx::bytes [%0], [%1, {%3, %4, %5}], [%2];"
               ::"r"(dst), "l"(m), "r"(bar), "r"(c0), "r"(c1), "r"(c2) : "memory");
}
__device__ __forceinline__ void tma3d_mc(uint32_t dst, const CUtensorMap* m, int c0, int c1, int c2, uint32_t bar) {
  asm volatile("cp.async.bulk.tensor.3d.shared::cluster.global.mbarrier::complete_tx::bytes.multicast::cluster [%0], [%1, {%3, %4, %5}], [%2], %6;"
               ::"r"(dst), "l"(m), "r"(bar), "r"(c0), "r"(c1), "r"(c2), "h"((uint16_t)3) : "memory");
}
__device__ __forceinline__ void ldsm4(uint32_t (&r)[4], uint32_t addr) {
  asm volatile("ldmatrix.sync.aligned.m8n8.x4.shared.b16 {%0,%1,%2,%3}, [%4];"
               : "=r"(r[0]), "=r"(r[1]), "=r"(r[2]), "=r"(r[3]) : "r"(addr) : "memory");
}
__device__ __forceinline__ void ldsm4t(uint32_t (&r)[4], uint32_t addr) {
  asm volatile("ldmatrix.sync.aligned.m8n8.x4.trans.shared.b16 {%0,%1,%2,%3}, [%4];"
               : "=r"(r[0]), "=r"(r[1]), "=r"(r[2]), "=r"(r[3]) : "r"(addr) : "memory");
}
__device__ __forceinline__ void stsm4(uint32_t addr, uint32_t r0, uint32_t r1, uint32_t r2, uint32_t r3) {
  asm volatile("stmatrix.sync.aligned.m8n8.x4.shared.b16 [%0], {%1,%2,%3,%4};"
               ::"r"(addr), "r"(r0), "r"(r1), "r"(r2), "r"(r3) : "memory");
}
__device__ __forceinline__ void mma16816(float (&c)[4], const uint32_t (&a)[4], uint32_t b0, uint32_t b1) {
  asm volatile("mma.sync.aligned.m16n8k16.row.col.f32.bf16.bf16.f32 {%0,%1,%2,%3},{%4,%5,%6,%7},{%8,%9},{%0,%1,%2,%3};"
               : "+f"(c[0]), "+f"(c[1]), "+f"(c[2]), "+f"(c[3])
               : "r"(a[0]), "r"(a[1]), "r"(a[2]), "r"(a[3]), "r"(b0), "r"(b1));
}
__device__ __forceinline__ void add_frag(float (&c)[32], const uint32_t (&a)[4][4], uint32_t id) {
#pragma unroll
  for (int i = 0; i < 8; i++)
    asm volatile("mma.sync.aligned.m16n8k8.row.col.f32.bf16.bf16.f32 {%0,%1,%2,%3},{%4,%5},{%6},{%0,%1,%2,%3};"
                 : "+f"(c[4 * i]), "+f"(c[4 * i + 1]), "+f"(c[4 * i + 2]), "+f"(c[4 * i + 3])
                 : "r"(a[i >> 1][(i & 1) * 2]), "r"(a[i >> 1][(i & 1) * 2 + 1]), "r"(id));
}
__device__ __forceinline__ uint32_t pack2(float lo, float hi) {
  uint32_t r; asm("cvt.rn.bf16x2.f32 %0, %1, %2;" : "=r"(r) : "f"(hi), "f"(lo)); return r;
}
__device__ __forceinline__ float blo(uint32_t w) { return __uint_as_float(w << 16); }
__device__ __forceinline__ float bhi(uint32_t w) { return __uint_as_float(w & 0xFFFF0000u); }
__device__ __forceinline__ uint32_t hsub2(uint32_t a, uint32_t b) { uint32_t r; asm("sub.rn.bf16x2 %0, %1, %2;" : "=r"(r) : "r"(a), "r"(b)); return r; }
__device__ __forceinline__ uint32_t hmax2(uint32_t a, uint32_t b) { uint32_t r; asm("max.bf16x2 %0, %1, %2;" : "=r"(r) : "r"(a), "r"(b)); return r; }
__device__ __forceinline__ uint32_t hmin2(uint32_t a, uint32_t b) { uint32_t r; asm("min.bf16x2 %0, %1, %2;" : "=r"(r) : "r"(a), "r"(b)); return r; }
__device__ __forceinline__ float ex2(float x) { float r; asm("ex2.approx.ftz.f32 %0, %1;" : "=f"(r) : "f"(x)); return r; }
__device__ __forceinline__ float rcp(float x) { float r; asm("rcp.approx.ftz.f32 %0, %1;" : "=f"(r) : "f"(x)); return r; }
__device__ __forceinline__ void ld_rlx4(uint32_t (&r)[4], const uint4* p) {
  asm volatile("{\n.reg .b128 v;\nld.relaxed.gpu.global.b128 v, [%4];\nmov.b128 {%0,%1,%2,%3}, v;\n}"
               : "=r"(r[0]), "=r"(r[1]), "=r"(r[2]), "=r"(r[3]) : "l"(p) : "memory");
}
__device__ __forceinline__ void st_rlx4(uint4* p, uint32_t a, uint32_t b, uint32_t c, uint32_t d) {
  asm volatile("{\n.reg .b128 v;\nmov.b128 v, {%1,%2,%3,%4};\nst.relaxed.gpu.global.b128 [%0], v;\n}"
               ::"l"(p), "r"(a), "r"(b), "r"(c), "r"(d) : "memory");
}
__device__ __forceinline__ void st_rlx2(uint2* p, uint32_t a, uint32_t b) {
  asm volatile("{\n.reg .b64 v;\nmov.b64 v, {%1,%2};\nst.relaxed.gpu.global.b64 [%0], v;\n}" ::"l"(p), "r"(a), "r"(b) : "memory");
}
__device__ __forceinline__ uint32_t ld_rlx1(const uint32_t* p) {
  uint32_t r; asm volatile("ld.relaxed.gpu.global.b32 %0, [%1];" : "=r"(r) : "l"(p) : "memory"); return r;
}
__device__ __forceinline__ void st_rlx1(uint32_t* p, uint32_t a) {
  asm volatile("st.relaxed.gpu.global.b32 [%0], %1;" ::"l"(p), "r"(a) : "memory");
}
__device__ __forceinline__ void ld_rlx2(uint32_t& a, uint32_t& b, const uint2* p) {
  asm volatile("{\n.reg .b64 v;\nld.relaxed.gpu.b64 v, [%2];\nmov.b64 {%0,%1}, v;\n}" : "=r"(a), "=r"(b) : "l"(p) : "memory");
}
__device__ __forceinline__ void bulk_g2s(uint32_t dst, const void* src, uint32_t bytes, uint32_t bar) {
  asm volatile("cp.async.bulk.shared::cluster.global.mbarrier::complete_tx::bytes [%0], [%1], %2, [%3];"
               ::"r"(dst), "l"(src), "r"(bytes), "r"(bar) : "memory");
}
__device__ __forceinline__ uint32_t tg(uint32_t w, uint32_t T) { return (w & 0xFFFFFFFEu) | T; }
__device__ __forceinline__ uint32_t bad4(uint32_t a, uint32_t b, uint32_t c, uint32_t d, uint32_t T) {
  uint32_t u, v;
  asm("lop3.b32 %0, %1, %2, %3, 0x7E;" : "=r"(u) : "r"(a), "r"(b), "r"(T));
  asm("lop3.b32 %0, %1, %2, %3, 0x7E;" : "=r"(v) : "r"(c), "r"(d), "r"(T));
  asm("lop3.b32 %0, %1, %2, 1, 0xA8;" : "=r"(u) : "r"(u), "r"(v));
  return u;
}

__device__ __forceinline__ void ld_chunk(uint32_t (&a)[4][4], const uint4* p) {
#pragma unroll
  for (int s = 0; s < 4; s++) ld_rlx4(a[s], p + s * 32);
}
__device__ __forceinline__ void get_pair(uint32_t (&a)[4][4], uint32_t (&b)[4][4], const uint4* sp, const uint4* gp, uint32_t T) {
  int it = 0;
#pragma unroll 1
  do {
#pragma unroll
    for (int s = 0; s < 8; s++) {
      uint32_t (&r)[4] = s < 4 ? a[s & 3] : b[s & 3];
      asm volatile("{\n.reg .b128 v;\nld.relaxed.gpu.b128 v, [%4];\nmov.b128 {%0,%1,%2,%3}, v;\n}"
                   : "=r"(r[0]), "=r"(r[1]), "=r"(r[2]), "=r"(r[3]) : "l"(sp + (s >> 2) * 512 + (s & 3) * 32) : "memory");
    }
    sp = gp;
  } while (__any_sync(0xffffffffu, bad4(a[0][0], a[1][0], a[2][0], a[3][0], T) | bad4(b[0][0], b[1][0], b[2][0], b[3][0], T)) && ++it < (1 << 18));
}

__device__ __forceinline__ void wgmma_rs_n48(float (&d)[24], const uint32_t (&a)[4], uint32_t descB, int scaleD) {
  asm volatile("{\n.reg .pred p;\n.reg .b64 db;\nsetp.ne.b32 p, %29, 0;\nmov.b64 db, {%28, 0x40000040};\n"
    "wgmma.mma_async.sync.aligned.m64n48k16.f32.bf16.bf16 {%0,%1,%2,%3,%4,%5,%6,%7,%8,%9,%10,%11,%12,%13,%14,%15,%16,%17,%18,%19,%20,%21,%22,%23}, {%24,%25,%26,%27}, db, p, 1, 1, 1;\n}\n"
    : "+f"(d[0]),"+f"(d[1]),"+f"(d[2]),"+f"(d[3]),"+f"(d[4]),"+f"(d[5]),"+f"(d[6]),"+f"(d[7]),"+f"(d[8]),"+f"(d[9]),"+f"(d[10]),"+f"(d[11]),"+f"(d[12]),"+f"(d[13]),"+f"(d[14]),"+f"(d[15]),"+f"(d[16]),"+f"(d[17]),"+f"(d[18]),"+f"(d[19]),"+f"(d[20]),"+f"(d[21]),"+f"(d[22]),"+f"(d[23])
    : "r"(a[0]), "r"(a[1]), "r"(a[2]), "r"(a[3]), "r"(descB), "r"(scaleD));
}
__device__ __forceinline__ void wgmma_rs_n64(float (&d)[32], const uint32_t (&a)[4], uint32_t descB, int scaleD) {
  asm volatile("{\n.reg .pred p;\n.reg .b64 db;\nsetp.ne.b32 p, %37, 0;\nmov.b64 db, {%36, 0x40000040};\n"
    "wgmma.mma_async.sync.aligned.m64n64k16.f32.bf16.bf16 {%0,%1,%2,%3,%4,%5,%6,%7,%8,%9,%10,%11,%12,%13,%14,%15,%16,%17,%18,%19,%20,%21,%22,%23,%24,%25,%26,%27,%28,%29,%30,%31}, {%32,%33,%34,%35}, db, p, 1, 1, 1;\n}\n"
    : "+f"(d[0]),"+f"(d[1]),"+f"(d[2]),"+f"(d[3]),"+f"(d[4]),"+f"(d[5]),"+f"(d[6]),"+f"(d[7]),"+f"(d[8]),"+f"(d[9]),"+f"(d[10]),"+f"(d[11]),"+f"(d[12]),"+f"(d[13]),"+f"(d[14]),"+f"(d[15]),"+f"(d[16]),"+f"(d[17]),"+f"(d[18]),"+f"(d[19]),"+f"(d[20]),"+f"(d[21]),"+f"(d[22]),"+f"(d[23]),"+f"(d[24]),"+f"(d[25]),"+f"(d[26]),"+f"(d[27]),"+f"(d[28]),"+f"(d[29]),"+f"(d[30]),"+f"(d[31])
    : "r"(a[0]), "r"(a[1]), "r"(a[2]), "r"(a[3]), "r"(descB), "r"(scaleD));
}
__device__ __forceinline__ void wgmma_rs_n128(float (&d)[64], const uint32_t (&a)[4], uint32_t descB, int scaleD) {
  asm volatile("{\n.reg .pred p;\n.reg .b64 db;\nsetp.ne.b32 p, %69, 0;\nmov.b64 db, {%68, 0x40000040};\n"
    "wgmma.mma_async.sync.aligned.m64n128k16.f32.bf16.bf16 {%0,%1,%2,%3,%4,%5,%6,%7,%8,%9,%10,%11,%12,%13,%14,%15,%16,%17,%18,%19,%20,%21,%22,%23,%24,%25,%26,%27,%28,%29,%30,%31,%32,%33,%34,%35,%36,%37,%38,%39,%40,%41,%42,%43,%44,%45,%46,%47,%48,%49,%50,%51,%52,%53,%54,%55,%56,%57,%58,%59,%60,%61,%62,%63}, {%64,%65,%66,%67}, db, p, 1, 1, 1;\n}\n"
    : "+f"(d[0]),"+f"(d[1]),"+f"(d[2]),"+f"(d[3]),"+f"(d[4]),"+f"(d[5]),"+f"(d[6]),"+f"(d[7]),"+f"(d[8]),"+f"(d[9]),"+f"(d[10]),"+f"(d[11]),"+f"(d[12]),"+f"(d[13]),"+f"(d[14]),"+f"(d[15]),"+f"(d[16]),"+f"(d[17]),"+f"(d[18]),"+f"(d[19]),"+f"(d[20]),"+f"(d[21]),"+f"(d[22]),"+f"(d[23]),"+f"(d[24]),"+f"(d[25]),"+f"(d[26]),"+f"(d[27]),"+f"(d[28]),"+f"(d[29]),"+f"(d[30]),"+f"(d[31]),"+f"(d[32]),"+f"(d[33]),"+f"(d[34]),"+f"(d[35]),"+f"(d[36]),"+f"(d[37]),"+f"(d[38]),"+f"(d[39]),"+f"(d[40]),"+f"(d[41]),"+f"(d[42]),"+f"(d[43]),"+f"(d[44]),"+f"(d[45]),"+f"(d[46]),"+f"(d[47]),"+f"(d[48]),"+f"(d[49]),"+f"(d[50]),"+f"(d[51]),"+f"(d[52]),"+f"(d[53]),"+f"(d[54]),"+f"(d[55]),"+f"(d[56]),"+f"(d[57]),"+f"(d[58]),"+f"(d[59]),"+f"(d[60]),"+f"(d[61]),"+f"(d[62]),"+f"(d[63])
    : "r"(a[0]), "r"(a[1]), "r"(a[2]), "r"(a[3]), "r"(descB), "r"(scaleD));
}
__device__ __forceinline__ void wgmma_ss_n72_t11(float (&d)[36], uint32_t descA, uint32_t descB, int scaleD) {
  asm volatile("{\n.reg .pred p;\n.reg .b64 da, db;\nsetp.ne.b32 p, %38, 0;\nmov.b64 da, {%36, 0x40000040};\nmov.b64 db, {%37, 0x40000040};\n"
    "wgmma.mma_async.sync.aligned.m64n72k16.f32.bf16.bf16 {%0,%1,%2,%3,%4,%5,%6,%7,%8,%9,%10,%11,%12,%13,%14,%15,%16,%17,%18,%19,%20,%21,%22,%23,%24,%25,%26,%27,%28,%29,%30,%31,%32,%33,%34,%35}, da, db, p, 1, 1, 1, 1;\n}\n"
    : "+f"(d[0]),"+f"(d[1]),"+f"(d[2]),"+f"(d[3]),"+f"(d[4]),"+f"(d[5]),"+f"(d[6]),"+f"(d[7]),"+f"(d[8]),"+f"(d[9]),"+f"(d[10]),"+f"(d[11]),"+f"(d[12]),"+f"(d[13]),"+f"(d[14]),"+f"(d[15]),"+f"(d[16]),"+f"(d[17]),"+f"(d[18]),"+f"(d[19]),"+f"(d[20]),"+f"(d[21]),"+f"(d[22]),"+f"(d[23]),"+f"(d[24]),"+f"(d[25]),"+f"(d[26]),"+f"(d[27]),"+f"(d[28]),"+f"(d[29]),"+f"(d[30]),"+f"(d[31]),"+f"(d[32]),"+f"(d[33]),"+f"(d[34]),"+f"(d[35])
    : "r"(descA), "r"(descB), "r"(scaleD));
}

#define TSTAMP(i) do {} while (0)
#define TS2(w, i) do {} while (0)

constexpr float LOG2E = 1.4426950408889634f;

__device__ __forceinline__ void feat_exp(const uint32_t (&P)[4], float (&e)[16]) {
  uint32_t a = hmax2(P[0], P[2]), b = hmax2(P[1], P[3]);
  uint32_t mx = hmax2(__byte_perm(a, b, 0x5410), __byte_perm(a, b, 0x7632));
  a = hmin2(P[0], P[2]); b = hmin2(P[1], P[3]);
  uint32_t mn = hmin2(__byte_perm(a, b, 0x5410), __byte_perm(a, b, 0x7632));
  mx = hmax2(mx, __shfl_xor_sync(0xffffffffu, mx, 1));
  mn = hmin2(mn, __shfl_xor_sync(0xffffffffu, mn, 1));
  mx = hmax2(mx, __shfl_xor_sync(0xffffffffu, mx, 2));
  mn = hmin2(mn, __shfl_xor_sync(0xffffffffu, mn, 2));
  float mx0 = -blo(mx) * LOG2E, mx1 = -bhi(mx) * LOG2E, mn0 = blo(mn) * LOG2E, mn1 = bhi(mn) * LOG2E;
  float v[8] = {blo(P[0]), bhi(P[0]), blo(P[1]), bhi(P[1]), blo(P[2]), bhi(P[2]), blo(P[3]), bhi(P[3])};
#pragma unroll
  for (int i = 0; i < 8; i++) {
    bool r1 = (i >> 1) & 1;
    e[i]     = ex2(fmaf(v[i],  LOG2E, r1 ? mx1 : mx0));
    e[8 + i] = ex2(fmaf(v[i], -LOG2E, r1 ? mn1 : mn0));
  }
}

template <int SBASE>
__global__ void __cluster_dims__(2, 1, 1) __launch_bounds__(384, 1)
fused_kernel(const __grid_constant__ Maps maps, const __nv_bfloat16* __restrict__ x, const __nv_bfloat16* __restrict__ wphi,
             const __nv_bfloat16* __restrict__ wo, const __nv_bfloat16* __restrict__ wg_, const __nv_bfloat16* __restrict__ wu_,
             const __nv_bfloat16* __restrict__ wd_, __nv_bfloat16* __restrict__ out) {
  extern __shared__ __align__(1024) unsigned char smem[];
  const uint32_t sb = smem_u32(smem);
  const int tid = threadIdx.x, lane = tid & 31;
  const int warp = __shfl_sync(0xffffffffu, tid >> 5, 0);
  const uint32_t rank = blockIdx.x & 1;
  const int cl = blockIdx.x >> 1;
  int quad, qi;
  if (cl < 4) { quad = 15; qi = cl; }
  else if (cl < 36) { quad = (cl - 4) & 7; qi = (cl - 4) >> 3; }
  else { qi = (cl - 36) / 7; quad = 8 + (cl - 36) - 7 * qi; }
  const int rb = quad, hg = 2 * qi + rank;
  const int rb3 = (quad & ~1) + rank, jf = 4 * (quad & 1) + qi;

  if (warp < 8) {
    asm volatile("setmaxnreg.inc.sync.aligned.u32 240;");
    if (elect_one()) {
#pragma unroll 1
      for (int d = warp; d + 9 < NSTAGE; d += 8) {
        mbar_init(sb + SM_EMPTY + d * 8, st_empty_cnt(d));
        {
          mbar_init(sb + SM_FULL + (d + 9) * 8, 1);
          mbar_expect_tx(sb + SM_FULL + (d + 9) * 8, d + 9 >= ST_D ? 22528 : SLOT);
        }
      }
      asm volatile("fence.mbarrier_init.release.cluster;" ::: "memory");
    }
    __syncwarp();
    bar_sync(0, 352);
    asm volatile("barrier.cluster.arrive.relaxed.aligned;" ::: "memory");
    const int wg = warp >> 2, wq = warp & 3, g = lane >> 2, t = lane & 3;
    const bool lead = (tid & 127) == 0;
    const uint32_t db = ((SBASE ? (uint32_t)SBASE : (sb & 0x3FFFF)) >> 4) | (512u << 16);
    auto release = [&](int d) {
      const int s = d + NSLOT;
      mbar_arrive_cluster(sb + SM_EMPTY + d * 8, s >= ST_GU ? (uint32_t)(s & 1) : rank);
    };
    const uint32_t lrow = (uint32_t)(wq * 16 + (lane & 7) + ((lane >> 3) & 1) * 8) * 128;
    const uint32_t lx = lane & 7, lhi = lane >> 4;
    if (wg == 1) bar_arrive(4, 256);

    float r0, r1;
    uint32_t E[4][8];
    uint32_t T = 0;
    {
      uint32_t A[32][4];
      const int sx = wg ? ST_X1 : ST_X0;
      {
        const uint32_t base = sb + sx * SLOT + lrow, baseb = sb + sx * SLOT + (wq * 16 + lx + lhi * 8) * 128;
        float cs[2][4], c0[2][4], c1[2][4];
#pragma unroll
        for (int i = 0; i < 4; i++) { cs[0][i] = cs[1][i] = c0[0][i] = c0[1][i] = c1[0][i] = c1[1][i] = 0.f; }
#pragma unroll
        for (int c = 0; c < 8; c++) {
          if (c % 3 == 0) mbar_wait(sb + SM_FULL + (sx + c / 3) * 8);
#pragma unroll
          for (int k = 0; k < 4; k++) ldsm4(A[4 * c + k], base + c * 8192 + (((2 * k + lhi) ^ lx) << 4));
#pragma unroll
          for (int k = 0; k < 4; k++) {
            const uint32_t (&f)[4] = A[4 * c + k];
            uint32_t bt[4];
            ldsm4(bt, baseb + c * 8192 + (((2 * k + ((lane >> 3) & 1)) ^ lx) << 4));
            mma16816(cs[k & 1], f, 0x3F803F80u, 0x3F803F80u);
            mma16816(c0[k & 1], f, bt[0], bt[1]);
            mma16816(c1[k & 1], f, bt[2], bt[3]);
          }
        }
        const float s0 = (cs[0][0] + cs[1][0]) * (1.f / 512.f), s1 = (cs[0][2] + cs[1][2]) * (1.f / 512.f);
        asm volatile("barrier.cluster.wait.aligned;" ::: "memory");
        if (lane < 3) release(sx + lane);
        const uint32_t m0 = pack2(s0, s0), m1 = pack2(s1, s1);
        float q0 = (g & 1) ? c0[0][1] + c0[1][1] : c0[0][0] + c0[1][0];
        float q1 = (g & 1) ? c1[0][3] + c1[1][3] : c1[0][2] + c1[1][2];
        q0 = __shfl_sync(0xffffffffu, q0, (lane & ~3) | (g >> 1));
        q1 = __shfl_sync(0xffffffffu, q1, (lane & ~3) | (g >> 1));
        r0 = rsqrtf(fmaxf(q0 * (1.f / 512.f) - s0 * s0, 0.f) + 1e-5f);
        r1 = rsqrtf(fmaxf(q1 * (1.f / 512.f) - s1 * s1, 0.f) + 1e-5f);
#pragma unroll
        for (int ks = 0; ks < 32; ks++) {
          A[ks][0] = hsub2(A[ks][0], m0); A[ks][1] = hsub2(A[ks][1], m1);
          A[ks][2] = hsub2(A[ks][2], m0); A[ks][3] = hsub2(A[ks][3], m1);
        }
      }
      TSTAMP(1);
      const uint32_t wpa = sb + SM_WPHI + ((lane & 7) + ((lane >> 3) & 1) * 8) * 32 + lhi * 16;
      const uint32_t scr = sb + (wg ? (ST_SCR1 % NSLOT) : (ST_SCR0 % NSLOT)) * SLOT;
#pragma unroll 1
      for (int ps = 0; ps < 3; ps++) {
        const int st0 = ps == 0 ? ST_WK : (ps == 1 ? ST_WV : ST_WQ);
        const uint32_t wdesc = DESC((ps == 0 ? ST_WK % NSLOT : (ps == 1 ? ST_WV % NSLOT : ST_WQ % NSLOT)) * SLOT);
        float acc[32];
        bar_sync(4 + wg, 256);
#pragma unroll
        for (int i = 0; i < 3; i++) {
          mbar_wait(sb + SM_FULL + (st0 + i) * 8);
          wg_fence();
#pragma unroll
          for (int kk = 0; kk < (i < 2 ? 12 : 8); kk++)
            wgmma_rs_n64(acc, A[12 * i + kk], wdesc + ((i * SLOT + kk * 2048) >> 4), (i | kk) != 0);
          wg_commit();
          if (i == 1) { wg_wait<1>(); if (lead) release(st0); }
        }
        if (ps == 0 || wg == 0) bar_arrive(4 + (wg ^ 1), 256);
        uint32_t a[4][4], b[4][4];
        mbar_wait(sb + SM_MISCB);
        T = (*reinterpret_cast<volatile unsigned*>(smem + SM_EPOCH) & 1) ^ 1;
#pragma unroll
        for (int h = 0; h < 4; h++) ldsm4t(b[h], wpa + h * 512);
        wg_wait<0>();
        if ((tid & 127) < 2) release(st0 + 1 + (tid & 1));
        TSTAMP(2 + 2 * ps);
#pragma unroll
        for (int h = 0; h < 4; h++) {
          a[h][0] = pack2(acc[8 * h + 0] * r0, acc[8 * h + 1] * r0); a[h][1] = pack2(acc[8 * h + 2] * r1, acc[8 * h + 3] * r1);
          a[h][2] = pack2(acc[8 * h + 4] * r0, acc[8 * h + 5] * r0); a[h][3] = pack2(acc[8 * h + 6] * r1, acc[8 * h + 7] * r1);
        }
        if (ps != 1) {
          {
            float pp[4][2][4];
#pragma unroll
            for (int h = 0; h < 4; h++) {
#pragma unroll
              for (int i = 0; i < 4; i++) { pp[h][0][i] = 0.f; pp[h][1][i] = 0.f; }
              mma16816(pp[h][0], a[h], b[h][0], b[h][1]);
              mma16816(pp[h][1], a[h], b[h][2], b[h][3]);
            }
#pragma unroll
            for (int h = 0; h < 4; h++) {
              a[h][0] = pack2(pp[h][0][0], pp[h][0][1]); a[h][1] = pack2(pp[h][0][2], pp[h][0][3]);
              a[h][2] = pack2(pp[h][1][0], pp[h][1][1]); a[h][3] = pack2(pp[h][1][2], pp[h][1][3]);
            }
          }
          if (ps == 0) mbar_wait(sb + SM_EMPTY + (wg ? ST_SCR1 - NSLOT : ST_SCR0 - NSLOT) * 8);
#pragma unroll 1
          for (int hp = 0; hp < 2; hp++) {
            float e[2][16];
            feat_exp(a[0], e[0]);
            feat_exp(a[1], e[1]);
            if (ps == 0) {
#pragma unroll
              for (int h = 0; h < 2; h++) {
                const float (&f)[16] = e[h];
                float sp0 = (f[0] + f[1]) + (f[4] + f[5]), sp1 = (f[2] + f[3]) + (f[6] + f[7]);
                float sn0 = (f[8] + f[9]) + (f[12] + f[13]), sn1 = (f[10] + f[11]) + (f[14] + f[15]);
                sp0 += __shfl_xor_sync(0xffffffffu, sp0, 1); sp1 += __shfl_xor_sync(0xffffffffu, sp1, 1);
                sn0 += __shfl_xor_sync(0xffffffffu, sn0, 1); sn1 += __shfl_xor_sync(0xffffffffu, sn1, 1);
                sp0 += __shfl_xor_sync(0xffffffffu, sp0, 2); sp1 += __shfl_xor_sync(0xffffffffu, sp1, 2);
                sn0 += __shfl_xor_sync(0xffffffffu, sn0, 2); sn1 += __shfl_xor_sync(0xffffffffu, sn1, 2);
                sp0 = rcp(sp0); sp1 = rcp(sp1); sn0 = rcp(sn0); sn1 = rcp(sn1);
                const uint32_t dst = scr + hp * 8192 + lrow;
                stsm4(dst + (((h * 4 + lhi) ^ lx) << 4), pack2(f[0] * sp0, f[1] * sp0), pack2(f[2] * sp1, f[3] * sp1),
                      pack2(f[4] * sp0, f[5] * sp0), pack2(f[6] * sp1, f[7] * sp1));
                stsm4(dst + (((h * 4 + 2 + lhi) ^ lx) << 4), pack2(f[8] * sn0, f[9] * sn0), pack2(f[10] * sn1, f[11] * sn1),
                      pack2(f[12] * sn0, f[13] * sn0), pack2(f[14] * sn1, f[15] * sn1));
              }
            } else {
#pragma unroll
              for (int i = 0; i < 16; i++) {
                A[i >> 2][i & 3] = A[4 + (i >> 2)][i & 3];
                A[4 + (i >> 2)][i & 3] = pack2(e[i >> 3][2 * (i & 7)], e[i >> 3][2 * (i & 7) + 1]);
              }
            }
#pragma unroll
            for (int i = 0; i < 4; i++) { a[0][i] = a[2][i]; a[1][i] = a[3][i]; }
          }
        } else {
#pragma unroll
          for (int h = 0; h < 4; h++) stsm4(scr + 16384 + lrow + (((2 * h + lhi) ^ lx) << 4), a[h][0], a[h][1], a[h][2], a[h][3]);
          fence_async_smem();
          bar_sync(3, 256);
          float kv[36];
          wg_fence();
#pragma unroll
          for (int ks = 0; ks < 8; ks++) {
            const uint32_t sk = (ks < 4 ? (ST_SCR0 % NSLOT) : (ST_SCR1 % NSLOT)) * SLOT + (ks & 3) * 2048;
            const uint32_t dv = (DESC(sk + 16384) & 0xFFFFu) | (((SM_ONES - sk - 16384) >> 4) << 16);
            wgmma_ss_n72_t11(kv, DESC(sk) + wg * 512, dv, ks != 0);
          }
          wg_commit();
          if (wg == 1) bar_arrive(4, 256);
          wg_wait<0>();
          if (lead) { mbar_arrive(sb + SM_EMPTY + ST_SCR0 * 8); mbar_arrive(sb + SM_EMPTY + ST_SCR1 * 8); }
          const int hl = 2 * wg + (wq >> 1), f = (wq & 1) * 16 + g;
          float* kvp = &g_kv[T ^ 1][((hg * 4 + hl) * 32 + f) * 16 + 2 * t];
          float* zp = &g_z[T ^ 1][(hg * 4 + hl) * 32 + f];
          float c[8];
#pragma unroll
          for (int i = 0; i < 8; i++) c[i] = hl >= 2 ? (hl == 3 ? kv[24 + i] : kv[16 + i]) : (hl == 1 ? kv[8 + i] : kv[i]);
#pragma unroll
          for (int n = 0; n < 2; n++) {
            asm volatile("red.relaxed.gpu.global.add.v2.f32 [%0], {%1,%2};" ::"l"(kvp + n * 8), "f"(c[4 * n]), "f"(c[4 * n + 1]) : "memory");
            asm volatile("red.relaxed.gpu.global.add.v2.f32 [%0], {%1,%2};" ::"l"(kvp + n * 8 + 128), "f"(c[4 * n + 2]), "f"(c[4 * n + 3]) : "memory");
          }
          if (t < 2) asm volatile("red.relaxed.gpu.global.add.f32 [%0], %1;" ::"l"(zp + t * 8), "f"(t ? kv[34] : kv[32]) : "memory");
          bar_arrive(6 + wg, 160);
        }
        TSTAMP(3 + 2 * ps);
      }
#pragma unroll
      for (int i = 0; i < 32; i++) E[i >> 3][i & 7] = A[i >> 2][i & 3];
    }
    const int rh = 2 * rb + wg;
#define IDF ((g >> 1) == t ? ((g & 1) ? 0x3F800000u : 0x00003F80u) : 0u)
    const uint4* xb = reinterpret_cast<const uint4*>(smem + 2 * SLOT) + wq * 128 + lane;
    mbar_wait(sb + SM_KVB);
    {
      const int r = tid & 127;
      const float4* src = reinterpret_cast<const float4*>(smem + SM_KV32) + r;
#pragma unroll
      for (int i = 0; i < 4; i++) {
        const float4 a = src[i * 128];
        *reinterpret_cast<uint2*>(smem + SM_KVS + (i * 32 + (r >> 2)) * 48 + (r & 3) * 8) = make_uint2(pack2(a.x, a.y), pack2(a.z, a.w));
      }
      const uint32_t zz = pack2(reinterpret_cast<const float*>(smem + SM_ONES)[r], 1.0f);
      *reinterpret_cast<uint4*>(smem + SM_KVS + r * 48 + 32) = make_uint4(zz, zz, zz, zz);
      bar_sync(1 + wg, 128);
    }
    TSTAMP(8);
    {
      uint4* op = &g_o[rh][hg][wq][0][lane];
#pragma unroll 1
      for (int hp = 0; hp < 2; hp++) {
#pragma unroll
      for (int h = 0; h < 2; h++) {
        uint32_t b0[4], b1[4], b2[4];
        const uint32_t kb = sb + SM_KVS + ((2 * hp + h) * 32 + lane) * 48;
        ldsm4t(b0, kb); ldsm4t(b1, kb + 16); ldsm4t(b2, kb + 32);
        const uint32_t ep[4] = {E[h][0], E[h][1], E[h][2], E[h][3]}, en[4] = {E[h][4], E[h][5], E[h][6], E[h][7]};
        float np0[4] = {0, 0, 0, 0}, np1[4] = {0, 0, 0, 0}, nn0[4] = {0, 0, 0, 0}, nn1[4] = {0, 0, 0, 0}, dp[4] = {0, 0, 0, 0}, dn[4] = {0, 0, 0, 0};
        mma16816(dp, ep, b2[0], b2[1]);  mma16816(dn, en, b2[2], b2[3]);
        mma16816(np0, ep, b0[0], b0[1]); mma16816(nn0, en, b0[2], b0[3]);
        mma16816(np1, ep, b1[0], b1[1]); mma16816(nn1, en, b1[2], b1[3]);
        const float i0 = rcp(fmaf(dp[0], dn[1], fmaf(dn[0], dp[1], 1e-6f * dp[1] * dn[1])));
        const float i1 = rcp(fmaf(dp[2], dn[3], fmaf(dn[2], dp[3], 1e-6f * dp[3] * dn[3])));
        const float cp0 = dn[1] * i0, cn0 = dp[1] * i0, cp1 = dn[3] * i1, cn1 = dp[3] * i1;
        st_rlx4(op + (2 * hp + h) * 32,
                tg(pack2(fmaf(np0[0], cp0, nn0[0] * cn0), fmaf(np0[1], cp0, nn0[1] * cn0)), T),
                pack2(fmaf(np0[2], cp1, nn0[2] * cn1), fmaf(np0[3], cp1, nn0[3] * cn1)),
                pack2(fmaf(np1[0], cp0, nn1[0] * cn0), fmaf(np1[1], cp0, nn1[1] * cn0)),
                pack2(fmaf(np1[2], cp1, nn1[2] * cn1), fmaf(np1[3], cp1, nn1[3] * cn1)));
      }
#pragma unroll
        for (int i = 0; i < 8; i++) { E[0][i] = E[2][i]; E[1][i] = E[3][i]; }
      }
    }
    TSTAMP(9);

    {
      uint32_t xr[4][4];
      {
        const uint32_t* xp = reinterpret_cast<const uint32_t*>(x + (size_t)(rh * 64 + wq * 16 + g) * 512 + hg * 64 + 2 * t);
#pragma unroll
        for (int i = 0; i < 8; i++) { xr[i >> 1][(i & 1) * 2] = __ldg(xp + 4 * i); xr[i >> 1][(i & 1) * 2 + 1] = __ldg(xp + 8 * 256 + 4 * i); }
      }
      uint32_t A[8][4][4];
      const uint4* op = &g_o[rh][0][wq][0][lane];
      float acc[32];
#pragma unroll
      for (int i = 0; i < 32; i++) acc[i] = 0.f;
      add_frag(acc, xr, IDF);
#pragma unroll
      for (int p = 0; p < 4; p++) {
        mbar_wait(sb + SM_XF + (wg * 4 + p) * 8);
        get_pair(A[2 * p], A[2 * p + 1], xb + p * 1024, op + p * 1024, T);
        if (lane == 0) mbar_arrive(sb + SM_XE + (wg * 4 + p) * 8);
        if (p != 2) mbar_wait(sb + SM_FULL + (ST_WO + (p + 1) / 2) * 8);
        wg_fence();
#pragma unroll
        for (int c = 2 * p; c < 2 * p + 2; c++)
#pragma unroll
          for (int s = 0; s < 4; s++)
            wgmma_rs_n64(acc, A[c][s], DESC(((ST_WO + c / 3) % NSLOT) * SLOT + ((c % 3) * 4 + s) * 2048), 1);
      }
      wg_commit();
      wg_wait<0>();
      if ((tid & 127) < 3) release(ST_WO + (tid & 127));
      TSTAMP(10);
      uint32_t hw[4][4];
      uint4* hp_ = &g_h[rh][hg][wq][0][lane];
      float cs[4][4], c0[4][4], c1[4][4];
      uint32_t hx = T;
#pragma unroll
      for (int s = 0; s < 4; s++) {
#pragma unroll
        for (int r = 0; r < 4; r++) { hw[s][r] = pack2(acc[8 * s + 2 * r], acc[8 * s + 2 * r + 1]); cs[s][r] = c0[s][r] = c1[s][r] = 0.f; }
        st_rlx4(hp_ + s * 32, tg(hw[s][0], T), hw[s][1], hw[s][2], hw[s][3]);
        hx |= (hw[s][0] & 1u) << (s + 1);
      }
#pragma unroll
      for (int s = 0; s < 4; s++) {
        mma16816(cs[s], hw[s], 0x3F803F80u, 0x3F803F80u);
        mma16816(c0[s], hw[s], hw[s][0], hw[s][2]);
        mma16816(c1[s], hw[s], hw[s][1], hw[s][3]);
      }
      if (t == (g >> 1)) {
        const float q0 = (g & 1) ? (c0[0][1] + c0[1][1]) + (c0[2][1] + c0[3][1]) : (c0[0][0] + c0[1][0]) + (c0[2][0] + c0[3][0]);
        const float q1 = (g & 1) ? (c1[0][3] + c1[1][3]) + (c1[2][3] + c1[3][3]) : (c1[0][2] + c1[1][2]) + (c1[2][2] + c1[3][2]);
        st_rlx2(&g_st[rh][hg][wq * 16 + g], tg(__float_as_uint((cs[0][0] + cs[1][0]) + (cs[2][0] + cs[3][0])), T), __float_as_uint(q0));
        st_rlx2(&g_st[rh][hg][wq * 16 + g + 8], tg(__float_as_uint((cs[0][2] + cs[1][2]) + (cs[2][2] + cs[3][2])), T), __float_as_uint(q1));
      }
      st_rlx1(&g_hx[rh][hg][wq][lane], hx);
    }
    TSTAMP(11);

    const int rh3 = 2 * rb3 + wg;
    uint32_t HH[11][4], PH[11][4];
    const uint4* pp = &g_hh[rh3][jf ^ 1][0][wq][lane];
    {
      uint32_t A[8][4][4];
      const uint4* hp_ = &g_h[rh3][0][wq][0][lane];
      uint4* hhp = &g_hh[rh3][jf][0][wq][lane];
      const uint32_t dg = (db & 0xFFFFu) | (256u << 16);
      uint32_t m0, m1;
      mbar_wait(sb + SM_XF + ((2 + wg) * 4) * 8);
      {
        const uint2* sp = reinterpret_cast<const uint2*>(smem + SM_KV32 + wg * 4096) + 2 * t * 64 + wq * 16 + g;
        uint2 a0, a1, b0, b1;
        int it = 0;
#pragma unroll 1
        do {
          ld_rlx2(a0.x, a0.y, sp); ld_rlx2(a1.x, a1.y, sp + 64); ld_rlx2(b0.x, b0.y, sp + 8); ld_rlx2(b1.x, b1.y, sp + 72);
          sp = &g_st[rh3][2 * t][wq * 16 + g];
        } while (__any_sync(0xffffffffu, bad4(a0.x, a1.x, b0.x, b1.x, T)) && ++it < (1 << 18));
        float s0 = __uint_as_float(a0.x) + __uint_as_float(a1.x), q0 = __uint_as_float(a0.y) + __uint_as_float(a1.y);
        float s1 = __uint_as_float(b0.x) + __uint_as_float(b1.x), q1 = __uint_as_float(b0.y) + __uint_as_float(b1.y);
        s0 += __shfl_xor_sync(0xffffffffu, s0, 1); s1 += __shfl_xor_sync(0xffffffffu, s1, 1);
        q0 += __shfl_xor_sync(0xffffffffu, q0, 1); q1 += __shfl_xor_sync(0xffffffffu, q1, 1);
        s0 += __shfl_xor_sync(0xffffffffu, s0, 2); s1 += __shfl_xor_sync(0xffffffffu, s1, 2);
        q0 += __shfl_xor_sync(0xffffffffu, q0, 2); q1 += __shfl_xor_sync(0xffffffffu, q1, 2);
        s0 *= (1.f / 512.f); s1 *= (1.f / 512.f);
        r0 = rcp(fmaxf(q0 * (1.f / 512.f) - s0 * s0, 0.f) + 1e-5f);
        r1 = rcp(fmaxf(q1 * (1.f / 512.f) - s1 * s1, 0.f) + 1e-5f);
        m0 = pack2(s0, s0); m1 = pack2(s1, s1);
      }
      TSTAMP(12);
#define UOFF(u) ((((ST_GU + (u) / 3) % NSLOT) * SLOT + ((u) % 3) * 8192) >> 4)
#define UNIT_PRE(u)  do { if ((u) % 3 == 0) mbar_wait(sb + SM_FULL + (ST_GU + (u) / 3) * 8); } while (0)
#define UNIT_POST(u) do { wg_commit(); if ((u) % 3 == 1 && (u) > 3) { wg_wait<2>(); if (lead) release(ST_GU + (u) / 3 - 1); } } while (0)
      float acc[64];
      const int rz = blockIdx.y;
#pragma unroll
      for (int ps = 0; ps < 2; ps++) {
        wg_fence();
#pragma unroll
        for (int k = 0; k < 16; k++) {
          const int u = 16 * ps + k, c = k >> 1;
          if (ps == 0 && k < 4) {
            if (k > 0) mbar_wait(sb + SM_XF + ((2 + wg) * 4 + k) * 8);
            get_pair(A[2 * k], A[2 * k + 1], xb + k * 1024, hp_ + k * 1024, T);
            if (lane == 0) {
              if (wg == 0) mbar_arrive(sb + SM_XE + (8 + k) * 8);
              else if (k > 0) release(ST_XC + k - 1);
            }
          }
          if (ps == 0 && (k & 1) == 0) {
#pragma unroll
            for (int s = 0; s < 4; s++) {
              A[c][s][0] = hsub2(A[c][s][0], m0); A[c][s][1] = hsub2(A[c][s][1], m1);
              A[c][s][2] = hsub2(A[c][s][2], m0); A[c][s][3] = hsub2(A[c][s][3], m1);
            }
            wg_fence();
          }
          UNIT_PRE(u);
          wgmma_rs_n128(acc, A[c][(k & 1) * 2], dg + UOFF(u), k != 0 ? 1 : (ps ? rz : 0));
          wgmma_rs_n128(acc, A[c][(k & 1) * 2 + 1], dg + UOFF(u) + 128, 1);
          UNIT_POST(u);
        }
        wg_wait<0>();
#pragma unroll
        for (int s = 0; s < 4; s++) {
          uint32_t (&hh)[4] = HH[4 + s];
          hh[0] = tg(pack2(acc[8 * s + 0] * acc[32 + 8 * s + 0] * r0, acc[8 * s + 1] * acc[32 + 8 * s + 1] * r0), T);
          hh[1] = pack2(acc[8 * s + 2] * acc[32 + 8 * s + 2] * r1, acc[8 * s + 3] * acc[32 + 8 * s + 3] * r1);
          hh[2] = pack2(acc[8 * s + 4] * acc[32 + 8 * s + 4] * r0, acc[8 * s + 5] * acc[32 + 8 * s + 5] * r0);
          hh[3] = pack2(acc[8 * s + 6] * acc[32 + 8 * s + 6] * r1, acc[8 * s + 7] * acc[32 + 8 * s + 7] * r1);
          st_rlx4(hhp + (4 * ps + s) * 128, hh[0], hh[1], hh[2], hh[3]);
        }
      }
      {
        float ag[24], au[24];
        bar_sync(1 + wg, 128);
        wg_fence();
#pragma unroll
        for (int k = 0; k < 16; k++) {
          const int u = 32 + k, c = k >> 1;
          if (k == 6) {
#pragma unroll
            for (int s = 0; s < 4; s++) ld_rlx4(HH[s], hhp + s * 128);
          }
          if (k == 12) {
#pragma unroll
            for (int s = 0; s < 8; s++) ld_rlx4(PH[s], pp + s * 128);
          }
          UNIT_PRE(u);
          wgmma_rs_n48(ag, A[c][(k & 1) * 2], dg + UOFF(u), k != 0);
          wgmma_rs_n48(au, A[c][(k & 1) * 2], dg + UOFF(u) + 256, k != 0);
          wgmma_rs_n48(ag, A[c][(k & 1) * 2 + 1], dg + UOFF(u) + 128, 1);
          wgmma_rs_n48(au, A[c][(k & 1) * 2 + 1], dg + UOFF(u) + 256 + 128, 1);
          UNIT_POST(u);
        }
        wg_wait<0>();
        TSTAMP(13);
#pragma unroll
        for (int s = 0; s < 3; s++) {
          uint32_t (&hh)[4] = HH[8 + s];
          hh[0] = tg(pack2(ag[8 * s + 0] * au[8 * s + 0] * r0, ag[8 * s + 1] * au[8 * s + 1] * r0), T);
          hh[1] = pack2(ag[8 * s + 2] * au[8 * s + 2] * r1, ag[8 * s + 3] * au[8 * s + 3] * r1);
          hh[2] = pack2(ag[8 * s + 4] * au[8 * s + 4] * r0, ag[8 * s + 5] * au[8 * s + 5] * r0);
          hh[3] = pack2(ag[8 * s + 6] * au[8 * s + 6] * r1, ag[8 * s + 7] * au[8 * s + 7] * r1);
          st_rlx4(hhp + (8 + s) * 128, hh[0], hh[1], hh[2], hh[3]);
        }
      }
    }
    TSTAMP(14);

    {
      float ac[3][32], acc[32];
      uint32_t hr[4][4];
      const int m = jf >> 1, oc = (jf & 1) * 4 + m;
      bar_arrive(8 + wg, 256);
      wg_fence();
#pragma unroll
      for (int k = 0; k < 3; k++) {
        mbar_wait(sb + SM_FULL + (ST_D + k) * 8);
        if (k == 2) {
#pragma unroll
          for (int s = 8; s < 11; s++) ld_rlx4(PH[s], pp + s * 128);
        }
#pragma unroll
        for (int s = 0; s < 11; s++) wgmma_rs_n64(ac[k], HH[s], DESC(((ST_D + k) % NSLOT) * SLOT + s * 2048), s != 0);
      }
      wg_commit();
      {
        int it = 0;
#pragma unroll 1
        while (__any_sync(0xffffffffu, bad4(PH[0][0], PH[1][0], PH[2][0], PH[3][0], T) | bad4(PH[4][0], PH[5][0], PH[6][0], PH[7][0], T) |
                                       bad4(PH[8][0], PH[9][0], PH[10][0], T, T))) {
#pragma unroll
          for (int s = 0; s < 11; s++) ld_rlx4(PH[s], pp + s * 128);
          if (++it > (1 << 18)) break;
        }
      }
      TSTAMP(20);
      uint4* outb = &g_part[rh3][(jf & 1) * 4][m][wq][0][lane];
#pragma unroll
      for (int k = 0; k < 4; k++) {
        mbar_wait(sb + SM_FULL + (ST_D + 3 + k) * 8);
        wg_fence();
#pragma unroll
        for (int s = 0; s < 11; s++) {
          if (k < 3) wgmma_rs_n64(ac[k], PH[s], DESC(((ST_D + 3 + k) % NSLOT) * SLOT + s * 2048), 1);
          else wgmma_rs_n64(acc, HH[s], DESC(((ST_D + 6) % NSLOT) * SLOT + s * 2048), s != 0);
        }
        wg_commit();
        if (k > 0) {
          wg_wait<1>();
          const float (&a)[32] = ac[k - 1];
          uint4* p = outb + ((m + k) & 3) * 2048;
#pragma unroll
          for (int s = 0; s < 4; s++)
            st_rlx4(p + s * 32, tg(pack2(a[8 * s + 0], a[8 * s + 1]), T), pack2(a[8 * s + 2], a[8 * s + 3]),
                    pack2(a[8 * s + 4], a[8 * s + 5]), pack2(a[8 * s + 6], a[8 * s + 7]));
        }
      }
      uint32_t in[3][4][4], hx;
      const uint4* inb = &g_part[rh3][oc][0][wq][0][lane];
      ld_chunk(hr, &g_h[rh3][oc][wq][0][lane]);
      ld_chunk(in[0], inb + ((m - 1) & 3) * 512);
      mbar_wait(sb + SM_FULL + (ST_D + 7) * 8);
      wg_fence();
#pragma unroll
      for (int s = 0; s < 11; s++) wgmma_rs_n64(acc, PH[s], DESC(((ST_D + 7) % NSLOT) * SLOT + s * 2048), 1);
      wg_commit();
      {
        int it = 0;
        bool again;
#pragma unroll 1
        do {
          if (it > 0) ld_chunk(in[0], inb + ((m - 1) & 3) * 512);
          ld_chunk(in[1], inb + ((m - 2) & 3) * 512);
          ld_chunk(in[2], inb + ((m - 3) & 3) * 512);
          hx = ld_rlx1(&g_hx[rh3][oc][wq][lane]);
          again = __any_sync(0xffffffffu, bad4(in[0][0][0], in[0][1][0], in[0][2][0], in[0][3][0], T) | bad4(in[1][0][0], in[1][1][0], in[1][2][0], in[1][3][0], T) |
                                          bad4(in[2][0][0], in[2][1][0], in[2][2][0], in[2][3][0], T) | ((hx ^ T) & 1));
        } while (again && ++it < (1 << 18));
      }
      wg_wait<0>();
      TSTAMP(15);
#pragma unroll
      for (int s = 0; s < 4; s++) hr[s][0] = (hr[s][0] & 0xFFFFFFFEu) | ((hx >> (s + 1)) & 1u);
      add_frag(acc, hr, IDF); add_frag(acc, in[0], IDF); add_frag(acc, in[1], IDF); add_frag(acc, in[2], IDF);
      bar_sync(9 - wg, 256);
      const uint32_t ob = sb + ((ST_D - 1) % NSLOT) * SLOT + wg * 8192;
#pragma unroll
      for (int s = 0; s < 4; s++)
        stsm4(ob + lrow + (((2 * s + lhi) ^ lx) << 4), pack2(acc[8 * s + 0], acc[8 * s + 1]), pack2(acc[8 * s + 2], acc[8 * s + 3]),
              pack2(acc[8 * s + 4], acc[8 * s + 5]), pack2(acc[8 * s + 6], acc[8 * s + 7]));
      __syncwarp();
#pragma unroll
      for (int i = 0; i < 4; i++) {
        const int row = wq * 16 + i * 4 + (lane >> 3);
        uint4 v;
        asm volatile("ld.shared.v4.b32 {%0,%1,%2,%3}, [%4];" : "=r"(v.x), "=r"(v.y), "=r"(v.z), "=r"(v.w)
                     : "r"(ob + row * 128 + ((lx ^ (row & 7)) << 4)) : "memory");
        asm volatile("st.global.v4.b32 [%0], {%1,%2,%3,%4};" ::"l"(out + (size_t)(rh3 * 64 + row) * 512 + oc * 64 + lx * 8),
                     "r"(v.x), "r"(v.y), "r"(v.z), "r"(v.w) : "memory");
      }
    }
    TSTAMP(16);
    asm volatile("barrier.cluster.arrive.relaxed.aligned;" ::: "memory");
    asm volatile("barrier.cluster.wait.aligned;" ::: "memory");
  } else {
    asm volatile("setmaxnreg.dec.sync.aligned.u32 24;");
    if (elect_one()) {
      if (warp == 8) {
#pragma unroll
        for (int k = 0; k < 9; k++) {
          const int s = k < 3 ? k : (k < 6 ? k + 3 : k - 3);
          const uint32_t bar = sb + SM_FULL + s * 8;
          mbar_init(bar, 1);
          mbar_expect_tx(bar, SLOT);
          if (s >= 3 && s < 6) tma2d(sb + s * SLOT, &maps.w, 512 + hg * 64, (s - 3) * 192, bar);
          else tma3d(sb + s * SLOT, &maps.x, 0, rb * 128 + (s >= 6 ? 64 : 0), 3 * (s % 3), bar);
        }
      } else if (warp == 9) {
        mbar_init(sb + SM_MISCB, 2);
        mbar_init(sb + SM_KVB, 32);
        mbar_expect_tx(sb + SM_MISCB, 2048);
        bulk_g2s(sb + SM_WPHI, wphi + hg * 1024, 2048, sb + SM_MISCB);
      } else if (warp == 10) {
#pragma unroll 1
        for (int i = 0; i < 16; i++) {
          mbar_init(sb + SM_XF + i * 8, 1);
          mbar_expect_tx(sb + SM_XF + i * 8, (i == 8 || i == 12) ? 20480 : 16384);
          if (i < 12) mbar_init(sb + SM_XE + i * 8, 4);
        }
      } else {
        *reinterpret_cast<volatile unsigned*>(smem + SM_EPOCH) = atomicAdd(&g_start, 1u) / NCTA;
      }
      asm volatile("fence.mbarrier_init.release.cluster;" ::: "memory");
    }
    __syncwarp();
    if (warp != 11) bar_sync(0, 352);
    asm volatile("barrier.cluster.arrive.relaxed.aligned;" ::: "memory");
    if (warp == 8) {
      asm volatile("barrier.cluster.wait.aligned;" ::: "memory");
      if (elect_one()) {
        const CUtensorMap* mg = jf == 7 ? &maps.g7 : &maps.g;
        const CUtensorMap* mu = jf == 7 ? &maps.u7 : &maps.u;
        asm volatile("prefetch.tensormap [%0];" ::"l"(&maps.wo) : "memory");
        asm volatile("prefetch.tensormap [%0];" ::"l"(mg) : "memory");
        asm volatile("prefetch.tensormap [%0];" ::"l"(mu) : "memory");
        asm volatile("prefetch.tensormap [%0];" ::"l"(&maps.d) : "memory");
#pragma unroll 1
        for (int s = ST_WV; s < ST_XC; s++) {
          if (s == ST_SCR1) continue;
          mbar_wait(sb + SM_EMPTY + (s - 9) * 8);
          const uint32_t dst = sb + (s >= 18 ? s - 18 : s - 9) * SLOT, bar = sb + SM_FULL + s * 8;
          if (s < ST_WO) tma2d(dst, &maps.w, (s < ST_WQ ? 1024 : 0) + hg * 64, (s < ST_WQ ? s - ST_WV : s - ST_WQ) * 192, bar);
          else { mbar_wait(bar - 8); tma2d(dst, &maps.wo, hg * 64, (s - ST_WO) * 192, bar); }
        }
        const int jc = jf == 7 ? 0 : jf;
        int slot = (ST_GU + 1 - rank) % NSLOT;
#pragma unroll 1
        for (int s = ST_GU + 1 - rank; s < NSTAGE; s += 2) {
          mbar_wait(sb + SM_EMPTY + (s - 9) * 8);
          if (s > ST_GU && s < ST_GU + THR) mbar_wait(sb + SM_FULL + (s - 1) * 8);
          const uint32_t dst = sb + slot * SLOT, bar = sb + SM_FULL + s * 8;
          if (s < ST_D) {
#pragma unroll 1
            for (int i = 0; i < 3; i++) {
              const int u = (s - ST_GU) * 3 + i;
              tma3d_mc(dst + i * 8192, mg, (u >> 4) * 64, jc, (u & 15) * 32, bar);
              tma3d_mc(dst + i * 8192 + 4096, mu, (u >> 4) * 64, jc, (u & 15) * 32, bar);
            }
          } else {
            const int i = s - ST_D, k = i < 3 ? i : (i < 6 ? i - 3 : 3), pt = (i >= 3 && i != 6) ? 1 : 0;
            tma2d_mc(dst, &maps.d, ((jf & 1) * 4 + (((jf >> 1) + 1 + k) & 3)) * 64, (jf ^ pt) * 176, bar);
          }
          slot += 2; if (slot >= NSLOT) slot -= NSLOT;
        }
      }
      __syncwarp();
    } else {
      asm volatile("barrier.cluster.wait.aligned;" ::: "memory");
      if (warp == 11) {
#pragma unroll
        for (int i = 0; i < 4; i++)
          reinterpret_cast<uint4*>(smem + SM_ONES)[lane + 32 * i] = make_uint4(0x3F803F80u, 0x3F803F80u, 0x3F803F80u, 0x3F803F80u);
        fence_async_smem();
        __syncwarp();
        if (lane == 0) mbar_arrive(sb + SM_MISCB);
      }
      mbar_wait(sb + SM_MISCB);
      const unsigned epoch = *reinterpret_cast<volatile unsigned*>(smem + SM_EPOCH);
      const uint32_t T = (epoch & 1) ^ 1;
      if (warp == 11) {
        reinterpret_cast<float4*>(&g_kv[T][blockIdx.x * 128])[lane] = make_float4(0.f, 0.f, 0.f, 0.f);
        if (lane < 8) g_z[T][blockIdx.x * 8 + lane] = 0.f;
        mbar_wait(sb + SM_FULL + (ST_WK + 2) * 8);
        if (elect_one()) {
          asm volatile("cp.async.bulk.prefetch.L2.global [%0], 4096;" ::"l"((const char*)wo + blockIdx.x * 4096) : "memory");
          asm volatile("cp.async.bulk.prefetch.L2.global [%0], 11008;" ::"l"((const char*)wg_ + blockIdx.x * 11008) : "memory");
          asm volatile("cp.async.bulk.prefetch.L2.global [%0], 11008;" ::"l"((const char*)wu_ + blockIdx.x * 11008) : "memory");
          asm volatile("cp.async.bulk.prefetch.L2.global [%0], 11008;" ::"l"((const char*)wd_ + blockIdx.x * 11008) : "memory");
          const unsigned target = (epoch + 1) * 32;
          unsigned v; int it = 0;
#pragma unroll 1
          do {
            asm volatile("ld.acquire.gpu.global.u32 %0, [%1];" : "=r"(v) : "l"(&g_kvcnt[hg * 32]) : "memory");
            if (++it > (1 << 18)) break;
          } while ((int)(v - target) < 0);
          TS2(0, 26);
        }
        __syncwarp();
        {
          const char* src = reinterpret_cast<const char*>(&g_kv[T ^ 1][hg * 2048]) + lane * 16;
#pragma unroll 4
          for (int i = 0; i < 16; i++)
            asm volatile("cp.async.cg.shared.global [%0], [%1], 16;" ::"r"(sb + SM_KV32 + lane * 16 + i * 512), "l"(src + i * 512) : "memory");
          asm volatile("cp.async.cg.shared.global [%0], [%1], 16;" ::"r"(sb + SM_ONES + lane * 16), "l"(&g_z[T ^ 1][hg * 128 + lane * 4]) : "memory");
          asm volatile("cp.async.mbarrier.arrive.noinc.shared::cta.b64 [%0];" ::"r"(sb + SM_KVB) : "memory");
        }
      } else {
        const int w = warp - 9;
        st_rlx4(reinterpret_cast<uint4*>(&g_st[2 * rb + w][hg][0]) + lane, T ^ 1, T ^ 1, T ^ 1, T ^ 1);
        if (lane < 8) st_rlx4(&g_o[2 * rb + w][hg][lane >> 1][3][30 + (lane & 1)], T ^ 1, T ^ 1, T ^ 1, T ^ 1);
        bar_sync(6 + w, 160);
        if (elect_one()) {
          asm volatile("fence.release.gpu;" ::: "memory");
          TS2(w, 25);
          asm volatile("red.relaxed.gpu.global.add.u32 [%0], 1;" ::"l"(&g_kvcnt[hg * 32]) : "memory");
        }
        mbar_wait(sb + SM_KVB);
        if (w == 0) { mbar_wait(sb + SM_EMPTY + 11 * 8); mbar_wait(sb + SM_EMPTY + 12 * 8); mbar_wait(sb + SM_EMPTY + 13 * 8); }
#pragma unroll 1
        for (int ph = 0; ph < 2; ph++) {
          const int use = 2 * ph + w, r = ph ? 2 * rb3 + w : 2 * rb + w;
          const uint32_t* pw = ph ? reinterpret_cast<const uint32_t*>(&g_st[r][lane >> 2][(lane & 3) * 16 + 15])
                                  : reinterpret_cast<const uint32_t*>(&g_o[r][lane >> 2][lane & 3][3][31]);
          const char* src = reinterpret_cast<const char*>(ph ? &g_h[r][0][0][0][0] : &g_o[r][0][0][0][0]);
          const uint32_t bf = sb + SM_XF + use * 32, be = sb + SM_XE + (use - 1) * 32;
          if (ph) mbar_wait(sb + SM_XE + w * 32 + 24);
          int it = 0;
#pragma unroll 1
          while (__any_sync(0xffffffffu, (ld_rlx1(pw) ^ T) & 1)) { if (++it > (1 << 18)) break; }
          if (elect_one()) {
            TS2(w, 27 + ph);
            if (use > 0) mbar_wait(be);
            if (ph) bulk_g2s(sb + SM_KV32 + w * 4096, &g_st[r][0][0], 4096, bf);
#pragma unroll
            for (int p = 0; p < 4; p++) {
              if (p > 0 && use > 0) mbar_wait(be + p * 8);
              bulk_g2s(sb + 2 * SLOT + p * 16384, src + p * 16384, 16384, bf + p * 8);
            }
          }
          __syncwarp();
        }
      }
    }
    asm volatile("barrier.cluster.arrive.relaxed.aligned;" ::: "memory");
    asm volatile("barrier.cluster.wait.aligned;" ::: "memory");
  }
}

typedef CUresult (*EncodeFn)(CUtensorMap*, CUtensorMapDataType, cuuint32_t, void*, const cuuint64_t*, const cuuint64_t*,
                             const cuuint32_t*, const cuuint32_t*, CUtensorMapInterleave, CUtensorMapSwizzle,
                             CUtensorMapL2promotion, CUtensorMapFloatOOBfill);

void encode(EncodeFn fn, CUtensorMap* m, const void* base, int rank, const cuuint64_t* dims, const cuuint64_t* strides,
            const cuuint32_t* box) {
  cuuint32_t es[3] = {1, 1, 1};
  fn(m, CU_TENSOR_MAP_DATA_TYPE_BFLOAT16, (cuuint32_t)rank, const_cast<void*>(base), dims, strides, box, es,
     CU_TENSOR_MAP_INTERLEAVE_NONE, CU_TENSOR_MAP_SWIZZLE_128B, CU_TENSOR_MAP_L2_PROMOTION_L2_256B,
     CU_TENSOR_MAP_FLOAT_OOB_FILL_NONE);
}

}

extern "C" void kernel_launch(void* const* d_in, const int* in_sizes, int n_in, void* d_out, int out_size) {
  (void)in_sizes; (void)n_in; (void)out_size;
  const __nv_bfloat16* x    = (const __nv_bfloat16*)d_in[0];
  const __nv_bfloat16* wqkv = (const __nv_bfloat16*)d_in[1];
  const __nv_bfloat16* wphi = (const __nv_bfloat16*)d_in[2];
  const __nv_bfloat16* wo   = (const __nv_bfloat16*)d_in[3];
  const __nv_bfloat16* wg   = (const __nv_bfloat16*)d_in[5];
  const __nv_bfloat16* wu   = (const __nv_bfloat16*)d_in[6];
  const __nv_bfloat16* wd   = (const __nv_bfloat16*)d_in[7];

  static EncodeFn fn = nullptr;
  static int reserved = 0;
  if (!fn) {
    void* p = nullptr;
    cudaDriverEntryPointQueryResult qr;
    cudaGetDriverEntryPoint("cuTensorMapEncodeTiled", &p, cudaEnableDefault, &qr);
    fn = (EncodeFn)p;
    cudaFuncSetAttribute(fused_kernel<1024>, cudaFuncAttributeMaxDynamicSharedMemorySize, SM_TOTAL);
    cudaFuncSetAttribute(fused_kernel<0>, cudaFuncAttributeMaxDynamicSharedMemorySize, SM_TOTAL);
    int dev = 0;
    cudaGetDevice(&dev);
    cudaDeviceGetAttribute(&reserved, cudaDevAttrReservedSharedMemoryPerBlock, dev);
  }
  Maps maps;
  {
    cuuint64_t d[3] = {64, 2048, 8}, s[2] = {1024, 128}; cuuint32_t b[3] = {64, 64, 3};
    encode(fn, &maps.x, x, 3, d, s, b);
  }
  {
    cuuint64_t d[2] = {1536, 512}, s[1] = {3072}; cuuint32_t b[2] = {64, 192};
    encode(fn, &maps.w, wqkv, 2, d, s, b);
  }
  {
    cuuint64_t d[2] = {512, 512}, s[1] = {1024}; cuuint32_t b[2] = {64, 192};
    encode(fn, &maps.wo, wo, 2, d, s, b);
  }
  {
    cuuint64_t d[3] = {176, 7, 512}, d7[3] = {144, 1, 512}, s[2] = {352, 2752}; cuuint32_t b[3] = {64, 1, 32};
    encode(fn, &maps.g, wg, 3, d, s, b);
    encode(fn, &maps.u, wu, 3, d, s, b);
    encode(fn, &maps.g7, wg + 1232, 3, d7, s, b);
    encode(fn, &maps.u7, wu + 1232, 3, d7, s, b);
  }
  {
    cuuint64_t d[2] = {512, 1376}, s[1] = {1024}; cuuint32_t b[2] = {64, 176};
    encode(fn, &maps.d, wd, 2, d, s, b);
  }
  if (reserved == 1024) fused_kernel<1024><<<NCTA, 384, SM_TOTAL>>>(maps, x, wphi, wo, wg, wu, wd, (__nv_bfloat16*)d_out);
  else fused_kernel<0><<<NCTA, 384, SM_TOTAL>>>(maps, x, wphi, wo, wg, wu, wd, (__nv_bfloat16*)d_out);
}
```

```cpp
#include <cuda_runtime.h>
#include <cuda_bf16.h>
#include <cuda.h>
#include <stdint.h>

#define PROF 0

#define SAFE_WAIT 0
#define VAR 0
#define POLLV 0
#define THR 6

namespace {

constexpr int NCTA   = 128;
constexpr int SLOT   = 24576;
constexpr int NSLOT  = 9;
constexpr int NSTAGE = 47;

constexpr int ST_X0   = 0;
constexpr int ST_WK   = 3;
constexpr int ST_X1   = 6;
constexpr int ST_SCR0 = 9;
constexpr int ST_WV   = 10;
constexpr int ST_SCR1 = 13;
constexpr int ST_WQ   = 14;
constexpr int ST_WO   = 17;
constexpr int ST_XC   = 20;
constexpr int ST_GU   = 23;
constexpr int ST_D    = 39;

__host__ __device__ constexpr int st_empty_cnt(int d) {
  return ((d < 3 || (d >= 6 && d < 9) || (d >= ST_XC && d < ST_GU)) ? 4 : 2) * (d + 9 >= ST_GU ? 2 : 1);
}

constexpr int SM_ONES = NSLOT * SLOT;
constexpr int SM_WPHI = SM_ONES + 2048;
constexpr int SM_KVS  = SM_WPHI + 2048;
constexpr int SM_KV32 = 4 * SLOT + 16384;
constexpr int SM_BAR  = SM_KVS + 6144;
constexpr int SM_FULL  = SM_BAR;
constexpr int SM_EMPTY = SM_BAR + NSTAGE * 8;
constexpr int SM_MISCB = SM_BAR + 2 * NSTAGE * 8;
constexpr int SM_KVB   = SM_MISCB + 8;
constexpr int SM_EPOCH = SM_KVB + 8;
constexpr int SM_XF    = SM_EPOCH + 8;
constexpr int SM_XE    = SM_XF + 16 * 8;
constexpr int SM_TOTAL = SM_BAR + 1024;

static_assert(SM_TOTAL == 232448 && SM_XE + 12 * 8 <= SM_TOTAL, "smem budget");

struct Maps { CUtensorMap x, w, wo, g, u, g7, u7, d; };

__device__ uint4    g_o[32][8][4][4][32];
__device__ uint4    g_h[32][8][4][4][32];
__device__ uint32_t g_hx[32][8][4][32];
__device__ uint2    g_st[32][8][64];
__device__ uint4    g_hh[32][8][11][4][32];
__device__ uint4    g_part[32][8][4][4][4][32];
__device__ float    g_kv[2][32 * 32 * 16];
__device__ float    g_z[2][32 * 32];
__device__ unsigned g_kvcnt[8 * 32];
__device__ unsigned g_start;

__device__ __forceinline__ uint32_t smem_u32(const void* p) { return (uint32_t)__cvta_generic_to_shared(p); }
__device__ __forceinline__ void mbar_init(uint32_t bar, int cnt) {
  asm volatile("mbarrier.init.shared::cta.b64 [%0], %1;" ::"r"(bar), "r"(cnt) : "memory");
}
__device__ __forceinline__ void mbar_expect_tx(uint32_t bar, uint32_t bytes) {
  asm volatile("mbarrier.arrive.expect_tx.shared::cta.b64 _, [%0], %1;" ::"r"(bar), "r"(bytes) : "memory");
}
__device__ __forceinline__ void mbar_arrive(uint32_t bar) {
  asm volatile("mbarrier.arrive.shared::cta.b64 _, [%0];" ::"r"(bar) : "memory");
}
__device__ __forceinline__ void mbar_arrive_cluster(uint32_t bar, uint32_t rank) {
  asm volatile("{\n.reg .b32 ra;\nmapa.shared::cluster.u32 ra, %0, %1;\n"
               "mbarrier.arrive.shared::cluster.b64 _, [ra];\n}" ::"r"(bar), "r"(rank) : "memory");
}
__device__ __forceinline__ void mbar_wait_p(uint32_t bar, uint32_t parity) {
  asm volatile("{\n.reg .pred p;\nW: mbarrier.try_wait.parity.shared::cta.b64 p, [%0], %1;\n@!p bra W;\n}" ::"r"(bar), "r"(parity) : "memory");
}
__device__ __forceinline__ void mbar_wait(uint32_t bar) { mbar_wait_p(bar, 0); }
__device__ __forceinline__ bool elect_one() {
  uint32_t p;
  asm volatile("{\n.reg .pred P;\nelect.sync _|P, 0xffffffff;\nselp.u32 %0, 1, 0, P;\n}" : "=r"(p));
  return p != 0;
}
__device__ __forceinline__ void bar_sync(int id, int n)   { asm volatile("bar.sync %0, %1;" ::"r"(id), "r"(n) : "memory"); }
__device__ __forceinline__ void bar_arrive(int id, int n) { asm volatile("bar.arrive %0, %1;" ::"r"(id), "r"(n) : "memory"); }
__device__ __forceinline__ void fence_async_smem() { asm volatile("fence.proxy.async.shared::cta;" ::: "memory"); }
__device__ __forceinline__ void wg_fence()  { asm volatile("wgmma.fence.sync.aligned;" ::: "memory"); }
__device__ __forceinline__ void wg_commit() { asm volatile("wgmma.commit_group.sync.aligned;" ::: "memory"); }
template <int N> __device__ __forceinline__ void wg_wait() { asm volatile("wgmma.wait_group.sync.aligned %0;" ::"n"(N) : "memory"); }
#define DESC(off) (db + ((uint32_t)(off) >> 4))
__device__ __forceinline__ void tma2d(uint32_t dst, const CUtensorMap* m, int c0, int c1, uint32_t bar) {
  asm volatile("cp.async.bulk.tensor.2d.shared::cluster.global.mbarrier::complete_tx::bytes [%0], [%1, {%3, %4}], [%2];"
               ::"r"(dst), "l"(m), "r"(bar), "r"(c0), "r"(c1) : "memory");
}
__device__ __forceinline__ void tma2d_mc(uint32_t dst, const CUtensorMap* m, int c0, int c1, uint32_t bar) {
  asm volatile("cp.async.bulk.tensor.2d.shared::cluster.global.mbarrier::complete_tx::bytes.multicast::cluster [%0], [%1, {%3, %4}], [%2], %5;"
               ::"r"(dst), "l"(m), "r"(bar), "r"(c0), "r"(c1), "h"((uint16_t)3) : "memory");
}
__device__ __forceinline__ void tma3d(uint32_t dst, const CUtensorMap* m, int c0, int c1, int c2, uint32_t bar) {
  asm volatile("cp.async.bulk.tensor.3d.shared::cluster.global.mbarrier::complete_tx::bytes [%0], [%1, {%3, %4, %5}], [%2];"
               ::"r"(dst), "l"(m), "r"(bar), "r"(c0), "r"(c1), "r"(c2) : "memory");
}
__device__ __forceinline__ void tma3d_mc(uint32_t dst, const CUtensorMap* m, int c0, int c1, int c2, uint32_t bar) {
  asm volatile("cp.async.bulk.tensor.3d.shared::cluster.global.mbarrier::complete_tx::bytes.multicast::cluster [%0], [%1, {%3, %4, %5}], [%2], %6;"
               ::"r"(dst), "l"(m), "r"(bar), "r"(c0), "r"(c1), "r"(c2), "h"((uint16_t)3) : "memory");
}
__device__ __forceinline__ void ldsm4(uint32_t (&r)[4], uint32_t addr) {
  asm volatile("ldmatrix.sync.aligned.m8n8.x4.shared.b16 {%0,%1,%2,%3}, [%4];"
               : "=r"(r[0]), "=r"(r[1]), "=r"(r[2]), "=r"(r[3]) : "r"(addr) : "memory");
}
__device__ __forceinline__ void ldsm4t(uint32_t (&r)[4], uint32_t addr) {
  asm volatile("ldmatrix.sync.aligned.m8n8.x4.trans.shared.b16 {%0,%1,%2,%3}, [%4];"
               : "=r"(r[0]), "=r"(r[1]), "=r"(r[2]), "=r"(r[3]) : "r"(addr) : "memory");
}
__device__ __forceinline__ void stsm4(uint32_t addr, uint32_t r0, uint32_t r1, uint32_t r2, uint32_t r3) {
  asm volatile("stmatrix.sync.aligned.m8n8.x4.shared.b16 [%0], {%1,%2,%3,%4};"
               ::"r"(addr), "r"(r0), "r"(r1), "r"(r2), "r"(r3) : "memory");
}
__device__ __forceinline__ void mma16816(float (&c)[4], const uint32_t (&a)[4], uint32_t b0, uint32_t b1) {
  asm volatile("mma.sync.aligned.m16n8k16.row.col.f32.bf16.bf16.f32 {%0,%1,%2,%3},{%4,%5,%6,%7},{%8,%9},{%0,%1,%2,%3};"
               : "+f"(c[0]), "+f"(c[1]), "+f"(c[2]), "+f"(c[3])
               : "r"(a[0]), "r"(a[1]), "r"(a[2]), "r"(a[3]), "r"(b0), "r"(b1));
}
__device__ __forceinline__ void add_frag(float (&c)[32], const uint32_t (&a)[4][4], uint32_t id) {
#pragma unroll
  for (int i = 0; i < 8; i++)
    asm volatile("mma.sync.aligned.m16n8k8.row.col.f32.bf16.bf16.f32 {%0,%1,%2,%3},{%4,%5},{%6},{%0,%1,%2,%3};"
                 : "+f"(c[4 * i]), "+f"(c[4 * i + 1]), "+f"(c[4 * i + 2]), "+f"(c[4 * i + 3])
                 : "r"(a[i >> 1][(i & 1) * 2]), "r"(a[i >> 1][(i & 1) * 2 + 1]), "r"(id));
}
__device__ __forceinline__ uint32_t pack2(float lo, float hi) {
  uint32_t r; asm("cvt.rn.bf16x2.f32 %0, %1, %2;" : "=r"(r) : "f"(hi), "f"(lo)); return r;
}
__device__ __forceinline__ float blo(uint32_t w) { return __uint_as_float(w << 16); }
__device__ __forceinline__ float bhi(uint32_t w) { return __uint_as_float(w & 0xFFFF0000u); }
__device__ __forceinline__ uint32_t hsub2(uint32_t a, uint32_t b) { uint32_t r; asm("sub.rn.bf16x2 %0, %1, %2;" : "=r"(r) : "r"(a), "r"(b)); return r; }
__device__ __forceinline__ uint32_t hmax2(uint32_t a, uint32_t b) { uint32_t r; asm("max.bf16x2 %0, %1, %2;" : "=r"(r) : "r"(a), "r"(b)); return r; }
__device__ __forceinline__ uint32_t hmin2(uint32_t a, uint32_t b) { uint32_t r; asm("min.bf16x2 %0, %1, %2;" : "=r"(r) : "r"(a), "r"(b)); return r; }
__device__ __forceinline__ float ex2(float x) { float r; asm("ex2.approx.ftz.f32 %0, %1;" : "=f"(r) : "f"(x)); return r; }
__device__ __forceinline__ float rcp(float x) { float r; asm("rcp.approx.ftz.f32 %0, %1;" : "=f"(r) : "f"(x)); return r; }
__device__ __forceinline__ void ld_rlx4(uint32_t (&r)[4], const uint4* p) {
  asm volatile("{\n.reg .b128 v;\nld.relaxed.gpu.global.b128 v, [%4];\nmov.b128 {%0,%1,%2,%3}, v;\n}"
               : "=r"(r[0]), "=r"(r[1]), "=r"(r[2]), "=r"(r[3]) : "l"(p) : "memory");
}
__device__ __forceinline__ void st_rlx4(uint4* p, uint32_t a, uint32_t b, uint32_t c, uint32_t d) {
  asm volatile("{\n.reg .b128 v;\nmov.b128 v, {%1,%2,%3,%4};\nst.relaxed.gpu.global.b128 [%0], v;\n}"
               ::"l"(p), "r"(a), "r"(b), "r"(c), "r"(d) : "memory");
}
__device__ __forceinline__ void st_rlx2(uint2* p, uint32_t a, uint32_t b) {
  asm volatile("{\n.reg .b64 v;\nmov.b64 v, {%1,%2};\nst.relaxed.gpu.global.b64 [%0], v;\n}" ::"l"(p), "r"(a), "r"(b) : "memory");
}
__device__ __forceinline__ uint32_t ld_rlx1(const uint32_t* p) {
  uint32_t r; asm volatile("ld.relaxed.gpu.global.b32 %0, [%1];" : "=r"(r) : "l"(p) : "memory"); return r;
}
__device__ __forceinline__ void st_rlx1(uint32_t* p, uint32_t a) {
  asm volatile("st.relaxed.gpu.global.b32 [%0], %1;" ::"l"(p), "r"(a) : "memory");
}
__device__ __forceinline__ void ld_rlx2(uint32_t& a, uint32_t& b, const uint2* p) {
  asm volatile("{\n.reg .b64 v;\nld.relaxed.gpu.b64 v, [%2];\nmov.b64 {%0,%1}, v;\n}" : "=r"(a), "=r"(b) : "l"(p) : "memory");
}
__device__ __forceinline__ void bulk_g2s(uint32_t dst, const void* src, uint32_t bytes, uint32_t bar) {
  asm volatile("cp.async.bulk.shared::cluster.global.mbarrier::complete_tx::bytes [%0], [%1], %2, [%3];"
               ::"r"(dst), "l"(src), "r"(bytes), "r"(bar) : "memory");
}
__device__ __forceinline__ uint32_t tg(uint32_t w, uint32_t T) { return (w & 0xFFFFFFFEu) | T; }
__device__ __forceinline__ uint32_t bad4(uint32_t a, uint32_t b, uint32_t c, uint32_t d, uint32_t T) {
  uint32_t u, v;
  asm("lop3.b32 %0, %1, %2, %3, 0x7E;" : "=r"(u) : "r"(a), "r"(b), "r"(T));
  asm("lop3.b32 %0, %1, %2, %3, 0x7E;" : "=r"(v) : "r"(c), "r"(d), "r"(T));
  asm("lop3.b32 %0, %1, %2, 1, 0xA8;" : "=r"(u) : "r"(u), "r"(v));
  return u;
}

__device__ __forceinline__ void ld_chunk(uint32_t (&a)[4][4], const uint4* p) {
#pragma unroll
  for (int s = 0; s < 4; s++) ld_rlx4(a[s], p + s * 32);
}
__device__ __forceinline__ void get_pair(uint32_t (&a)[4][4], uint32_t (&b)[4][4], const uint4* sp, const uint4* gp, uint32_t T) {
  int it = 0;
#pragma unroll 1
  do {
#pragma unroll
    for (int s = 0; s < 8; s++) {
      uint32_t (&r)[4] = s < 4 ? a[s & 3] : b[s & 3];
      asm volatile("{\n.reg .b128 v;\nld.relaxed.gpu.b128 v, [%4];\nmov.b128 {%0,%1,%2,%3}, v;\n}"
                   : "=r"(r[0]), "=r"(r[1]), "=r"(r[2]), "=r"(r[3]) : "l"(sp + (s >> 2) * 512 + (s & 3) * 32) : "memory");
    }
    sp = gp;
  } while (__any_sync(0xffffffffu, bad4(a[0][0], a[1][0], a[2][0], a[3][0], T) | bad4(b[0][0], b[1][0], b[2][0], b[3][0], T)) && ++it < (1 << 18));
}

__device__ __forceinline__ void wgmma_rs_n48(float (&d)[24], const uint32_t (&a)[4], uint32_t descB, int scaleD) {
  asm volatile("{\n.reg .pred p;\n.reg .b64 db;\nsetp.ne.b32 p, %29, 0;\nmov.b64 db, {%28, 0x40000040};\n"
    "wgmma.mma_async.sync.aligned.m64n48k16.f32.bf16.bf16 {%0,%1,%2,%3,%4,%5,%6,%7,%8,%9,%10,%11,%12,%13,%14,%15,%16,%17,%18,%19,%20,%21,%22,%23}, {%24,%25,%26,%27}, db, p, 1, 1, 1;\n}\n"
    : "+f"(d[0]),"+f"(d[1]),"+f"(d[2]),"+f"(d[3]),"+f"(d[4]),"+f"(d[5]),"+f"(d[6]),"+f"(d[7]),"+f"(d[8]),"+f"(d[9]),"+f"(d[10]),"+f"(d[11]),"+f"(d[12]),"+f"(d[13]),"+f"(d[14]),"+f"(d[15]),"+f"(d[16]),"+f"(d[17]),"+f"(d[18]),"+f"(d[19]),"+f"(d[20]),"+f"(d[21]),"+f"(d[22]),"+f"(d[23])
    : "r"(a[0]), "r"(a[1]), "r"(a[2]), "r"(a[3]), "r"(descB), "r"(scaleD));
}
__device__ __forceinline__ void wgmma_rs_n64(float (&d)[32], const uint32_t (&a)[4], uint32_t descB, int scaleD) {
  asm volatile("{\n.reg .pred p;\n.reg .b64 db;\nsetp.ne.b32 p, %37, 0;\nmov.b64 db, {%36, 0x40000040};\n"
    "wgmma.mma_async.sync.aligned.m64n64k16.f32.bf16.bf16 {%0,%1,%2,%3,%4,%5,%6,%7,%8,%9,%10,%11,%12,%13,%14,%15,%16,%17,%18,%19,%20,%21,%22,%23,%24,%25,%26,%27,%28,%29,%30,%31}, {%32,%33,%34,%35}, db, p, 1, 1, 1;\n}\n"
    : "+f"(d[0]),"+f"(d[1]),"+f"(d[2]),"+f"(d[3]),"+f"(d[4]),"+f"(d[5]),"+f"(d[6]),"+f"(d[7]),"+f"(d[8]),"+f"(d[9]),"+f"(d[10]),"+f"(d[11]),"+f"(d[12]),"+f"(d[13]),"+f"(d[14]),"+f"(d[15]),"+f"(d[16]),"+f"(d[17]),"+f"(d[18]),"+f"(d[19]),"+f"(d[20]),"+f"(d[21]),"+f"(d[22]),"+f"(d[23]),"+f"(d[24]),"+f"(d[25]),"+f"(d[26]),"+f"(d[27]),"+f"(d[28]),"+f"(d[29]),"+f"(d[30]),"+f"(d[31])
    : "r"(a[0]), "r"(a[1]), "r"(a[2]), "r"(a[3]), "r"(descB), "r"(scaleD));
}
__device__ __forceinline__ void wgmma_rs_n128(float (&d)[64], const uint32_t (&a)[4], uint32_t descB, int scaleD) {
  asm volatile("{\n.reg .pred p;\n.reg .b64 db;\nsetp.ne.b32 p, %69, 0;\nmov.b64 db, {%68, 0x40000040};\n"
    "wgmma.mma_async.sync.aligned.m64n128k16.f32.bf16.bf16 {%0,%1,%2,%3,%4,%5,%6,%7,%8,%9,%10,%11,%12,%13,%14,%15,%16,%17,%18,%19,%20,%21,%22,%23,%24,%25,%26,%27,%28,%29,%30,%31,%32,%33,%34,%35,%36,%37,%38,%39,%40,%41,%42,%43,%44,%45,%46,%47,%48,%49,%50,%51,%52,%53,%54,%55,%56,%57,%58,%59,%60,%61,%62,%63}, {%64,%65,%66,%67}, db, p, 1, 1, 1;\n}\n"
    : "+f"(d[0]),"+f"(d[1]),"+f"(d[2]),"+f"(d[3]),"+f"(d[4]),"+f"(d[5]),"+f"(d[6]),"+f"(d[7]),"+f"(d[8]),"+f"(d[9]),"+f"(d[10]),"+f"(d[11]),"+f"(d[12]),"+f"(d[13]),"+f"(d[14]),"+f"(d[15]),"+f"(d[16]),"+f"(d[17]),"+f"(d[18]),"+f"(d[19]),"+f"(d[20]),"+f"(d[21]),"+f"(d[22]),"+f"(d[23]),"+f"(d[24]),"+f"(d[25]),"+f"(d[26]),"+f"(d[27]),"+f"(d[28]),"+f"(d[29]),"+f"(d[30]),"+f"(d[31]),"+f"(d[32]),"+f"(d[33]),"+f"(d[34]),"+f"(d[35]),"+f"(d[36]),"+f"(d[37]),"+f"(d[38]),"+f"(d[39]),"+f"(d[40]),"+f"(d[41]),"+f"(d[42]),"+f"(d[43]),"+f"(d[44]),"+f"(d[45]),"+f"(d[46]),"+f"(d[47]),"+f"(d[48]),"+f"(d[49]),"+f"(d[50]),"+f"(d[51]),"+f"(d[52]),"+f"(d[53]),"+f"(d[54]),"+f"(d[55]),"+f"(d[56]),"+f"(d[57]),"+f"(d[58]),"+f"(d[59]),"+f"(d[60]),"+f"(d[61]),"+f"(d[62]),"+f"(d[63])
    : "r"(a[0]), "r"(a[1]), "r"(a[2]), "r"(a[3]), "r"(descB), "r"(scaleD));
}
__device__ __forceinline__ void wgmma_ss_n72_t11(float (&d)[36], uint32_t descA, uint32_t descB, int scaleD) {
  asm volatile("{\n.reg .pred p;\n.reg .b64 da, db;\nsetp.ne.b32 p, %38, 0;\nmov.b64 da, {%36, 0x40000040};\nmov.b64 db, {%37, 0x40000040};\n"
    "wgmma.mma_async.sync.aligned.m64n72k16.f32.bf16.bf16 {%0,%1,%2,%3,%4,%5,%6,%7,%8,%9,%10,%11,%12,%13,%14,%15,%16,%17,%18,%19,%20,%21,%22,%23,%24,%25,%26,%27,%28,%29,%30,%31,%32,%33,%34,%35}, da, db, p, 1, 1, 1, 1;\n}\n"
    : "+f"(d[0]),"+f"(d[1]),"+f"(d[2]),"+f"(d[3]),"+f"(d[4]),"+f"(d[5]),"+f"(d[6]),"+f"(d[7]),"+f"(d[8]),"+f"(d[9]),"+f"(d[10]),"+f"(d[11]),"+f"(d[12]),"+f"(d[13]),"+f"(d[14]),"+f"(d[15]),"+f"(d[16]),"+f"(d[17]),"+f"(d[18]),"+f"(d[19]),"+f"(d[20]),"+f"(d[21]),"+f"(d[22]),"+f"(d[23]),"+f"(d[24]),"+f"(d[25]),"+f"(d[26]),"+f"(d[27]),"+f"(d[28]),"+f"(d[29]),"+f"(d[30]),"+f"(d[31]),"+f"(d[32]),"+f"(d[33]),"+f"(d[34]),"+f"(d[35])
    : "r"(descA), "r"(descB), "r"(scaleD));
}

#define TSTAMP(i) do {} while (0)
#define TS2(w, i) do {} while (0)

constexpr float LOG2E = 1.4426950408889634f;

__device__ __forceinline__ void feat_exp(const uint32_t (&P)[4], float (&e)[16]) {
  uint32_t a = hmax2(P[0], P[2]), b = hmax2(P[1], P[3]);
  uint32_t mx = hmax2(__byte_perm(a, b, 0x5410), __byte_perm(a, b, 0x7632));
  a = hmin2(P[0], P[2]); b = hmin2(P[1], P[3]);
  uint32_t mn = hmin2(__byte_perm(a, b, 0x5410), __byte_perm(a, b, 0x7632));
  mx = hmax2(mx, __shfl_xor_sync(0xffffffffu, mx, 1));
  mn = hmin2(mn, __shfl_xor_sync(0xffffffffu, mn, 1));
  mx = hmax2(mx, __shfl_xor_sync(0xffffffffu, mx, 2));
  mn = hmin2(mn, __shfl_xor_sync(0xffffffffu, mn, 2));
  float mx0 = -blo(mx) * LOG2E, mx1 = -bhi(mx) * LOG2E, mn0 = blo(mn) * LOG2E, mn1 = bhi(mn) * LOG2E;
  float v[8] = {blo(P[0]), bhi(P[0]), blo(P[1]), bhi(P[1]), blo(P[2]), bhi(P[2]), blo(P[3]), bhi(P[3])};
#pragma unroll
  for (int i = 0; i < 8; i++) {
    bool r1 = (i >> 1) & 1;
    e[i]     = ex2(fmaf(v[i],  LOG2E, r1 ? mx1 : mx0));
    e[8 + i] = ex2(fmaf(v[i], -LOG2E, r1 ? mn1 : mn0));
  }
}

template <int SBASE>
__global__ void __cluster_dims__(2, 1, 1) __launch_bounds__(384, 1)
fused_kernel(const __grid_constant__ Maps maps, const __nv_bfloat16* __restrict__ x, const __nv_bfloat16* __restrict__ wphi,
             const __nv_bfloat16* __restrict__ wo, const __nv_bfloat16* __restrict__ wg_, const __nv_bfloat16* __restrict__ wu_,
             const __nv_bfloat16* __restrict__ wd_, __nv_bfloat16* __restrict__ out) {
  extern __shared__ __align__(1024) unsigned char smem[];
  const uint32_t sb = smem_u32(smem);
  const int tid = threadIdx.x, lane = tid & 31;
  const int warp = __shfl_sync(0xffffffffu, tid >> 5, 0);
  const uint32_t rank = blockIdx.x & 1;
  const int cl = blockIdx.x >> 1;
  int quad, qi;
  if (cl < 4) { quad = 15; qi = cl; }
  else if (cl < 36) { quad = (cl - 4) & 7; qi = (cl - 4) >> 3; }
  else { qi = (cl - 36) / 7; quad = 8 + (cl - 36) - 7 * qi; }
  const int rb = quad, hg = 2 * qi + rank;
  const int rb3 = (quad & ~1) + rank, jf = 4 * (quad & 1) + qi;

  if (warp < 8) {
    asm volatile("setmaxnreg.inc.sync.aligned.u32 240;");
    if (elect_one()) {
#pragma unroll 1
      for (int d = warp; d + 9 < NSTAGE; d += 8) {
        mbar_init(sb + SM_EMPTY + d * 8, st_empty_cnt(d));
        {
          mbar_init(sb + SM_FULL + (d + 9) * 8, 1);
          mbar_expect_tx(sb + SM_FULL + (d + 9) * 8, d + 9 >= ST_D ? 22528 : SLOT);
        }
      }
      asm volatile("fence.mbarrier_init.release.cluster;" ::: "memory");
    }
    __syncwarp();
    bar_sync(0, 352);
    asm volatile("barrier.cluster.arrive.relaxed.aligned;" ::: "memory");
    const int wg = warp >> 2, wq = warp & 3, g = lane >> 2, t = lane & 3;
    const bool lead = (tid & 127) == 0;
    const uint32_t db = ((SBASE ? (uint32_t)SBASE : (sb & 0x3FFFF)) >> 4) | (512u << 16);
    auto release = [&](int d) {
      const int s = d + NSLOT;
      mbar_arrive_cluster(sb + SM_EMPTY + d * 8, s >= ST_GU ? (uint32_t)(s & 1) : rank);
    };
    const uint32_t lrow = (uint32_t)(wq * 16 + (lane & 7) + ((lane >> 3) & 1) * 8) * 128;
    const uint32_t lx = lane & 7, lhi = lane >> 4;
    if (wg == 1) bar_arrive(4, 256);

    float r0, r1;
    uint32_t E[4][8];
    uint32_t T = 0;
    {
      uint32_t A[32][4];
      const int sx = wg ? ST_X1 : ST_X0;
      {
        const uint32_t base = sb + sx * SLOT + lrow, baseb = sb + sx * SLOT + (wq * 16 + lx + lhi * 8) * 128;
        float cs[2][4], c0[2][4], c1[2][4];
#pragma unroll
        for (int i = 0; i < 4; i++) { cs[0][i] = cs[1][i] = c0[0][i] = c0[1][i] = c1[0][i] = c1[1][i] = 0.f; }
#pragma unroll
        for (int c = 0; c < 8; c++) {
          if (c % 3 == 0) mbar_wait(sb + SM_FULL + (sx + c / 3) * 8);
#pragma unroll
          for (int k = 0; k < 4; k++) ldsm4(A[4 * c + k], base + c * 8192 + (((2 * k + lhi) ^ lx) << 4));
#pragma unroll
          for (int k = 0; k < 4; k++) {
            const uint32_t (&f)[4] = A[4 * c + k];
            uint32_t bt[4];
            ldsm4(bt, baseb + c * 8192 + (((2 * k + ((lane >> 3) & 1)) ^ lx) << 4));
            mma16816(cs[k & 1], f, 0x3F803F80u, 0x3F803F80u);
            mma16816(c0[k & 1], f, bt[0], bt[1]);
            mma16816(c1[k & 1], f, bt[2], bt[3]);
          }
        }
        const float s0 = (cs[0][0] + cs[1][0]) * (1.f / 512.f), s1 = (cs[0][2] + cs[1][2]) * (1.f / 512.f);
        asm volatile("barrier.cluster.wait.aligned;" ::: "memory");
        if (lane < 3) release(sx + lane);
        const uint32_t m0 = pack2(s0, s0), m1 = pack2(s1, s1);
        float q0 = (g & 1) ? c0[0][1] + c0[1][1] : c0[0][0] + c0[1][0];
        float q1 = (g & 1) ? c1[0][3] + c1[1][3] : c1[0][2] + c1[1][2];
        q0 = __shfl_sync(0xffffffffu, q0, (lane & ~3) | (g >> 1));
        q1 = __shfl_sync(0xffffffffu, q1, (lane & ~3) | (g >> 1));
        r0 = rsqrtf(fmaxf(q0 * (1.f / 512.f) - s0 * s0, 0.f) + 1e-5f);
        r1 = rsqrtf(fmaxf(q1 * (1.f / 512.f) - s1 * s1, 0.f) + 1e-5f);
#pragma unroll
        for (int ks = 0; ks < 32; ks++) {
          A[ks][0] = hsub2(A[ks][0], m0); A[ks][1] = hsub2(A[ks][1], m1);
          A[ks][2] = hsub2(A[ks][2], m0); A[ks][3] = hsub2(A[ks][3], m1);
        }
      }
      TSTAMP(1);
      const uint32_t wpa = sb + SM_WPHI + ((lane & 7) + ((lane >> 3) & 1) * 8) * 32 + lhi * 16;
      const uint32_t scr = sb + (wg ? (ST_SCR1 % NSLOT) : (ST_SCR0 % NSLOT)) * SLOT;
#pragma unroll 1
      for (int ps = 0; ps < 3; ps++) {
        const int st0 = ps == 0 ? ST_WK : (ps == 1 ? ST_WV : ST_WQ);
        const uint32_t wdesc = DESC((ps == 0 ? ST_WK % NSLOT : (ps == 1 ? ST_WV % NSLOT : ST_WQ % NSLOT)) * SLOT);
        float acc[32];
        bar_sync(4 + wg, 256);
#pragma unroll
        for (int i = 0; i < 3; i++) {
          mbar_wait(sb + SM_FULL + (st0 + i) * 8);
          wg_fence();
#pragma unroll
          for (int kk = 0; kk < (i < 2 ? 12 : 8); kk++)
            wgmma_rs_n64(acc, A[12 * i + kk], wdesc + ((i * SLOT + kk * 2048) >> 4), (i | kk) != 0);
          wg_commit();
          if (i == 1) { wg_wait<1>(); if (lead) release(st0); }
        }
        if (ps == 0 || wg == 0) bar_arrive(4 + (wg ^ 1), 256);
        uint32_t a[4][4], b[4][4];
        mbar_wait(sb + SM_MISCB);
        T = (*reinterpret_cast<volatile unsigned*>(smem + SM_EPOCH) & 1) ^ 1;
#pragma unroll
        for (int h = 0; h < 4; h++) ldsm4t(b[h], wpa + h * 512);
        wg_wait<0>();
        if ((tid & 127) < 2) release(st0 + 1 + (tid & 1));
        TSTAMP(2 + 2 * ps);
#pragma unroll
        for (int h = 0; h < 4; h++) {
          a[h][0] = pack2(acc[8 * h + 0] * r0, acc[8 * h + 1] * r0); a[h][1] = pack2(acc[8 * h + 2] * r1, acc[8 * h + 3] * r1);
          a[h][2] = pack2(acc[8 * h + 4] * r0, acc[8 * h + 5] * r0); a[h][3] = pack2(acc[8 * h + 6] * r1, acc[8 * h + 7] * r1);
        }
        if (ps != 1) {
          {
            float pp[4][2][4];
#pragma unroll
            for (int h = 0; h < 4; h++) {
#pragma unroll
              for (int i = 0; i < 4; i++) { pp[h][0][i] = 0.f; pp[h][1][i] = 0.f; }
              mma16816(pp[h][0], a[h], b[h][0], b[h][1]);
              mma16816(pp[h][1], a[h], b[h][2], b[h][3]);
            }
#pragma unroll
            for (int h = 0; h < 4; h++) {
              a[h][0] = pack2(pp[h][0][0], pp[h][0][1]); a[h][1] = pack2(pp[h][0][2], pp[h][0][3]);
              a[h][2] = pack2(pp[h][1][0], pp[h][1][1]); a[h][3] = pack2(pp[h][1][2], pp[h][1][3]);
            }
          }
          if (ps == 0) mbar_wait(sb + SM_EMPTY + (wg ? ST_SCR1 - NSLOT : ST_SCR0 - NSLOT) * 8);
#pragma unroll 1
          for (int hp = 0; hp < 2; hp++) {
            float e[2][16];
            feat_exp(a[0], e[0]);
            feat_exp(a[1], e[1]);
            if (ps == 0) {
#pragma unroll
              for (int h = 0; h < 2; h++) {
                const float (&f)[16] = e[h];
                float sp0 = (f[0] + f[1]) + (f[4] + f[5]), sp1 = (f[2] + f[3]) + (f[6] + f[7]);
                float sn0 = (f[8] + f[9]) + (f[12] + f[13]), sn1 = (f[10] + f[11]) + (f[14] + f[15]);
                sp0 += __shfl_xor_sync(0xffffffffu, sp0, 1); sp1 += __shfl_xor_sync(0xffffffffu, sp1, 1);
                sn0 += __shfl_xor_sync(0xffffffffu, sn0, 1); sn1 += __shfl_xor_sync(0xffffffffu, sn1, 1);
                sp0 += __shfl_xor_sync(0xffffffffu, sp0, 2); sp1 += __shfl_xor_sync(0xffffffffu, sp1, 2);
                sn0 += __shfl_xor_sync(0xffffffffu, sn0, 2); sn1 += __shfl_xor_sync(0xffffffffu, sn1, 2);
                sp0 = rcp(sp0); sp1 = rcp(sp1); sn0 = rcp(sn0); sn1 = rcp(sn1);
                const uint32_t dst = scr + hp * 8192 + lrow;
                stsm4(dst + (((h * 4 + lhi) ^ lx) << 4), pack2(f[0] * sp0, f[1] * sp0), pack2(f[2] * sp1, f[3] * sp1),
                      pack2(f[4] * sp0, f[5] * sp0), pack2(f[6] * sp1, f[7] * sp1));
                stsm4(dst + (((h * 4 + 2 + lhi) ^ lx) << 4), pack2(f[8] * sn0, f[9] * sn0), pack2(f[10] * sn1, f[11] * sn1),
                      pack2(f[12] * sn0, f[13] * sn0), pack2(f[14] * sn1, f[15] * sn1));
              }
            } else {
#pragma unroll
              for (int i = 0; i < 16; i++) {
                A[i >> 2][i & 3] = A[4 + (i >> 2)][i & 3];
                A[4 + (i >> 2)][i & 3] = pack2(e[i >> 3][2 * (i & 7)], e[i >> 3][2 * (i & 7) + 1]);
              }
            }
#pragma unroll
            for (int i = 0; i < 4; i++) { a[0][i] = a[2][i]; a[1][i] = a[3][i]; }
          }
        } else {
#pragma unroll
          for (int h = 0; h < 4; h++) stsm4(scr + 16384 + lrow + (((2 * h + lhi) ^ lx) << 4), a[h][0], a[h][1], a[h][2], a[h][3]);
          fence_async_smem();
          bar_sync(3, 256);
          float kv[36];
          wg_fence();
#pragma unroll
          for (int ks = 0; ks < 8; ks++) {
            const uint32_t sk = (ks < 4 ? (ST_SCR0 % NSLOT) : (ST_SCR1 % NSLOT)) * SLOT + (ks & 3) * 2048;
            const uint32_t dv = (DESC(sk + 16384) & 0xFFFFu) | (((SM_ONES - sk - 16384) >> 4) << 16);
            wgmma_ss_n72_t11(kv, DESC(sk) + wg * 512, dv, ks != 0);
          }
          wg_commit();
          if (wg == 1) bar_arrive(4, 256);
          wg_wait<0>();
          if (lead) { mbar_arrive(sb + SM_EMPTY + ST_SCR0 * 8); mbar_arrive(sb + SM_EMPTY + ST_SCR1 * 8); }
          const int hl = 2 * wg + (wq >> 1), f = (wq & 1) * 16 + g;
          float* kvp = &g_kv[T ^ 1][((hg * 4 + hl) * 32 + f) * 16 + 2 * t];
          float* zp = &g_z[T ^ 1][(hg * 4 + hl) * 32 + f];
          float c[8];
#pragma unroll
          for (int i = 0; i < 8; i++) c[i] = hl >= 2 ? (hl == 3 ? kv[24 + i] : kv[16 + i]) : (hl == 1 ? kv[8 + i] : kv[i]);
#pragma unroll
          for (int n = 0; n < 2; n++) {
            asm volatile("red.relaxed.gpu.global.add.v2.f32 [%0], {%1,%2};" ::"l"(kvp + n * 8), "f"(c[4 * n]), "f"(c[4 * n + 1]) : "memory");
            asm volatile("red.relaxed.gpu.global.add.v2.f32 [%0], {%1,%2};" ::"l"(kvp + n * 8 + 128), "f"(c[4 * n + 2]), "f"(c[4 * n + 3]) : "memory");
          }
          if (t < 2) asm volatile("red.relaxed.gpu.global.add.f32 [%0], %1;" ::"l"(zp + t * 8), "f"(t ? kv[34] : kv[32]) : "memory");
          bar_arrive(6 + wg, 160);
        }
        TSTAMP(3 + 2 * ps);
      }
#pragma unroll
      for (int i = 0; i < 32; i++) E[i >> 3][i & 7] = A[i >> 2][i & 3];
    }
    const int rh = 2 * rb + wg;
#define IDF ((g >> 1) == t ? ((g & 1) ? 0x3F800000u : 0x00003F80u) : 0u)
    const uint4* xb = reinterpret_cast<const uint4*>(smem + 2 * SLOT) + wq * 128 + lane;
    mbar_wait(sb + SM_KVB);
    {
      const int r = tid & 127;
      const float4* src = reinterpret_cast<const float4*>(smem + SM_KV32) + r;
#pragma unroll
      for (int i = 0; i < 4; i++) {
        const float4 a = src[i * 128];
        *reinterpret_cast<uint2*>(smem + SM_KVS + (i * 32 + (r >> 2)) * 48 + (r & 3) * 8) = make_uint2(pack2(a.x, a.y), pack2(a.z, a.w));
      }
      const uint32_t zz = pack2(reinterpret_cast<const float*>(smem + SM_ONES)[r], 1.0f);
      *reinterpret_cast<uint4*>(smem + SM_KVS + r * 48 + 32) = make_uint4(zz, zz, zz, zz);
      bar_sync(1 + wg, 128);
    }
    TSTAMP(8);
    {
      uint4* op = &g_o[rh][hg][wq][0][lane];
#pragma unroll 1
      for (int hp = 0; hp < 2; hp++) {
#pragma unroll
      for (int h = 0; h < 2; h++) {
        uint32_t b0[4], b1[4], b2[4];
        const uint32_t kb = sb + SM_KVS + ((2 * hp + h) * 32 + lane) * 48;
        ldsm4t(b0, kb); ldsm4t(b1, kb + 16); ldsm4t(b2, kb + 32);
        const uint32_t ep[4] = {E[h][0], E[h][1], E[h][2], E[h][3]}, en[4] = {E[h][4], E[h][5], E[h][6], E[h][7]};
        float np0[4] = {0, 0, 0, 0}, np1[4] = {0, 0, 0, 0}, nn0[4] = {0, 0, 0, 0}, nn1[4] = {0, 0, 0, 0}, dp[4] = {0, 0, 0, 0}, dn[4] = {0, 0, 0, 0};
        mma16816(dp, ep, b2[0], b2[1]);  mma16816(dn, en, b2[2], b2[3]);
        mma16816(np0, ep, b0[0], b0[1]); mma16816(nn0, en, b0[2], b0[3]);
        mma16816(np1, ep, b1[0], b1[1]); mma16816(nn1, en, b1[2], b1[3]);
        const float i0 = rcp(fmaf(dp[0], dn[1], fmaf(dn[0], dp[1], 1e-6f * dp[1] * dn[1])));
        const float i1 = rcp(fmaf(dp[2], dn[3], fmaf(dn[2], dp[3], 1e-6f * dp[3] * dn[3])));
        const float cp0 = dn[1] * i0, cn0 = dp[1] * i0, cp1 = dn[3] * i1, cn1 = dp[3] * i1;
        st_rlx4(op + (2 * hp + h) * 32,
                tg(pack2(fmaf(np0[0], cp0, nn0[0] * cn0), fmaf(np0[1], cp0, nn0[1] * cn0)), T),
                pack2(fmaf(np0[2], cp1, nn0[2] * cn1), fmaf(np0[3], cp1, nn0[3] * cn1)),
                pack2(fmaf(np1[0], cp0, nn1[0] * cn0), fmaf(np1[1], cp0, nn1[1] * cn0)),
                pack2(fmaf(np1[2], cp1, nn1[2] * cn1), fmaf(np1[3], cp1, nn1[3] * cn1)));
      }
#pragma unroll
        for (int i = 0; i < 8; i++) { E[0][i] = E[2][i]; E[1][i] = E[3][i]; }
      }
    }
    TSTAMP(9);

    {
      uint32_t xr[4][4];
      {
        const uint32_t* xp = reinterpret_cast<const uint32_t*>(x + (size_t)(rh * 64 + wq * 16 + g) * 512 + hg * 64 + 2 * t);
#pragma unroll
        for (int i = 0; i < 8; i++) { xr[i >> 1][(i & 1) * 2] = __ldg(xp + 4 * i); xr[i >> 1][(i & 1) * 2 + 1] = __ldg(xp + 8 * 256 + 4 * i); }
      }
      uint32_t A[8][4][4];
      const uint4* op = &g_o[rh][0][wq][0][lane];
      float acc[32];
#pragma unroll
      for (int i = 0; i < 32; i++) acc[i] = 0.f;
      add_frag(acc, xr, IDF);
#pragma unroll
      for (int p = 0; p < 4; p++) {
        mbar_wait(sb + SM_XF + (wg * 4 + p) * 8);
        get_pair(A[2 * p], A[2 * p + 1], xb + p * 1024, op + p * 1024, T);
        if (lane == 0) mbar_arrive(sb + SM_XE + (wg * 4 + p) * 8);
        if (p != 2) mbar_wait(sb + SM_FULL + (ST_WO + (p + 1) / 2) * 8);
        wg_fence();
#pragma unroll
        for (int c = 2 * p; c < 2 * p + 2; c++)
#pragma unroll
          for (int s = 0; s < 4; s++)
            wgmma_rs_n64(acc, A[c][s], DESC(((ST_WO + c / 3) % NSLOT) * SLOT + ((c % 3) * 4 + s) * 2048), 1);
      }
      wg_commit();
      wg_wait<0>();
      if ((tid & 127) < 3) release(ST_WO + (tid & 127));
      TSTAMP(10);
      uint32_t hw[4][4];
      uint4* hp_ = &g_h[rh][hg][wq][0][lane];
      float cs[4][4], c0[4][4], c1[4][4];
      uint32_t hx = T;
#pragma unroll
      for (int s = 0; s < 4; s++) {
#pragma unroll
        for (int r = 0; r < 4; r++) { hw[s][r] = pack2(acc[8 * s + 2 * r], acc[8 * s + 2 * r + 1]); cs[s][r] = c0[s][r] = c1[s][r] = 0.f; }
        st_rlx4(hp_ + s * 32, tg(hw[s][0], T), hw[s][1], hw[s][2], hw[s][3]);
        hx |= (hw[s][0] & 1u) << (s + 1);
      }
#pragma unroll
      for (int s = 0; s < 4; s++) {
        mma16816(cs[s], hw[s], 0x3F803F80u, 0x3F803F80u);
        mma16816(c0[s], hw[s], hw[s][0], hw[s][2]);
        mma16816(c1[s], hw[s], hw[s][1], hw[s][3]);
      }
      if (t == (g >> 1)) {
        const float q0 = (g & 1) ? (c0[0][1] + c0[1][1]) + (c0[2][1] + c0[3][1]) : (c0[0][0] + c0[1][0]) + (c0[2][0] + c0[3][0]);
        const float q1 = (g & 1) ? (c1[0][3] + c1[1][3]) + (c1[2][3] + c1[3][3]) : (c1[0][2] + c1[1][2]) + (c1[2][2] + c1[3][2]);
        st_rlx2(&g_st[rh][hg][wq * 16 + g], tg(__float_as_uint((cs[0][0] + cs[1][0]) + (cs[2][0] + cs[3][0])), T), __float_as_uint(q0));
        st_rlx2(&g_st[rh][hg][wq * 16 + g + 8], tg(__float_as_uint((cs[0][2] + cs[1][2]) + (cs[2][2] + cs[3][2])), T), __float_as_uint(q1));
      }
      st_rlx1(&g_hx[rh][hg][wq][lane], hx);
    }
    TSTAMP(11);

    const int rh3 = 2 * rb3 + wg;
    uint32_t HH[11][4], PH[11][4];
    const uint4* pp = &g_hh[rh3][jf ^ 1][0][wq][lane];
    {
      uint32_t A[8][4][4];
      const uint4* hp_ = &g_h[rh3][0][wq][0][lane];
      uint4* hhp = &g_hh[rh3][jf][0][wq][lane];
      const uint32_t dg = (db & 0xFFFFu) | (256u << 16);
      uint32_t m0, m1;
      mbar_wait(sb + SM_XF + ((2 + wg) * 4) * 8);
      {
        const uint2* sp = reinterpret_cast<const uint2*>(smem + SM_KV32 + wg * 4096) + 2 * t * 64 + wq * 16 + g;
        uint2 a0, a1, b0, b1;
        int it = 0;
#pragma unroll 1
        do {
          ld_rlx2(a0.x, a0.y, sp); ld_rlx2(a1.x, a1.y, sp + 64); ld_rlx2(b0.x, b0.y, sp + 8); ld_rlx2(b1.x, b1.y, sp + 72);
          sp = &g_st[rh3][2 * t][wq * 16 + g];
        } while (__any_sync(0xffffffffu, bad4(a0.x, a1.x, b0.x, b1.x, T)) && ++it < (1 << 18));
        float s0 = __uint_as_float(a0.x) + __uint_as_float(a1.x), q0 = __uint_as_float(a0.y) + __uint_as_float(a1.y);
        float s1 = __uint_as_float(b0.x) + __uint_as_float(b1.x), q1 = __uint_as_float(b0.y) + __uint_as_float(b1.y);
        s0 += __shfl_xor_sync(0xffffffffu, s0, 1); s1 += __shfl_xor_sync(0xffffffffu, s1, 1);
        q0 += __shfl_xor_sync(0xffffffffu, q0, 1); q1 += __shfl_xor_sync(0xffffffffu, q1, 1);
        s0 += __shfl_xor_sync(0xffffffffu, s0, 2); s1 += __shfl_xor_sync(0xffffffffu, s1, 2);
        q0 += __shfl_xor_sync(0xffffffffu, q0, 2); q1 += __shfl_xor_sync(0xffffffffu, q1, 2);
        s0 *= (1.f / 512.f); s1 *= (1.f / 512.f);
        r0 = rcp(fmaxf(q0 * (1.f / 512.f) - s0 * s0, 0.f) + 1e-5f);
        r1 = rcp(fmaxf(q1 * (1.f / 512.f) - s1 * s1, 0.f) + 1e-5f);
        m0 = pack2(s0, s0); m1 = pack2(s1, s1);
      }
      TSTAMP(12);
#define UOFF(u) ((((ST_GU + (u) / 3) % NSLOT) * SLOT + ((u) % 3) * 8192) >> 4)
#define UNIT_PRE(u)  do { if ((u) % 3 == 0) mbar_wait(sb + SM_FULL + (ST_GU + (u) / 3) * 8); } while (0)
#define UNIT_POST(u) do { wg_commit(); if ((u) % 3 == 1 && (u) > 3) { wg_wait<2>(); if (lead) release(ST_GU + (u) / 3 - 1); } } while (0)
      float acc[64];
      const int rz = blockIdx.y;
#pragma unroll
      for (int ps = 0; ps < 2; ps++) {
        wg_fence();
#pragma unroll
        for (int k = 0; k < 16; k++) {
          const int u = 16 * ps + k, c = k >> 1;
          if (ps == 0 && k < 4) {
            if (k > 0) mbar_wait(sb + SM_XF + ((2 + wg) * 4 + k) * 8);
            get_pair(A[2 * k], A[2 * k + 1], xb + k * 1024, hp_ + k * 1024, T);
            if (lane == 0) {
              if (wg == 0) mbar_arrive(sb + SM_XE + (8 + k) * 8);
              else if (k > 0) release(ST_XC + k - 1);
            }
          }
          if (ps == 0 && (k & 1) == 0) {
#pragma unroll
            for (int s = 0; s < 4; s++) {
              A[c][s][0] = hsub2(A[c][s][0], m0); A[c][s][1] = hsub2(A[c][s][1], m1);
              A[c][s][2] = hsub2(A[c][s][2], m0); A[c][s][3] = hsub2(A[c][s][3], m1);
            }
            wg_fence();
          }
          UNIT_PRE(u);
          wgmma_rs_n128(acc, A[c][(k & 1) * 2], dg + UOFF(u), k != 0 ? 1 : (ps ? rz : 0));
          wgmma_rs_n128(acc, A[c][(k & 1) * 2 + 1], dg + UOFF(u) + 128, 1);
          UNIT_POST(u);
        }
        wg_wait<0>();
#pragma unroll
        for (int s = 0; s < 4; s++) {
          uint32_t (&hh)[4] = HH[4 + s];
          hh[0] = tg(pack2(acc[8 * s + 0] * acc[32 + 8 * s + 0] * r0, acc[8 * s + 1] * acc[32 + 8 * s + 1] * r0), T);
          hh[1] = pack2(acc[8 * s + 2] * acc[32 + 8 * s + 2] * r1, acc[8 * s + 3] * acc[32 + 8 * s + 3] * r1);
          hh[2] = pack2(acc[8 * s + 4] * acc[32 + 8 * s + 4] * r0, acc[8 * s + 5] * acc[32 + 8 * s + 5] * r0);
          hh[3] = pack2(acc[8 * s + 6] * acc[32 + 8 * s + 6] * r1, acc[8 * s + 7] * acc[32 + 8 * s + 7] * r1);
          st_rlx4(hhp + (4 * ps + s) * 128, hh[0], hh[1], hh[2], hh[3]);
        }
      }
      {
        float ag[24], au[24];
        const uint32_t* ph7 = reinterpret_cast<const uint32_t*>(&g_hh[rh3][jf ^ 1][7][wq][31]);
        uint32_t hv = 0;
        bar_sync(1 + wg, 128);
        wg_fence();
#pragma unroll
        for (int k = 0; k < 16; k++) {
          const int u = 32 + k, c = k >> 1;
          if (k == 6) {
#pragma unroll
            for (int s = 0; s < 4; s++) ld_rlx4(HH[s], hhp + s * 128);
          }
          if (k == 9) hv = ld_rlx1(ph7);
          if (k == 12) {
            int it = 0;
#pragma unroll 1
            while (((hv ^ T) & 1) && ++it < (1 << 18)) hv = ld_rlx1(ph7);
#pragma unroll
            for (int s = 0; s < 8; s++) ld_rlx4(PH[s], pp + s * 128);
          }
          UNIT_PRE(u);
          wgmma_rs_n48(ag, A[c][(k & 1) * 2], dg + UOFF(u), k != 0);
          wgmma_rs_n48(au, A[c][(k & 1) * 2], dg + UOFF(u) + 256, k != 0);
          wgmma_rs_n48(ag, A[c][(k & 1) * 2 + 1], dg + UOFF(u) + 128, 1);
          wgmma_rs_n48(au, A[c][(k & 1) * 2 + 1], dg + UOFF(u) + 256 + 128, 1);
          UNIT_POST(u);
        }
        wg_wait<0>();
        TSTAMP(13);
#pragma unroll
        for (int s = 0; s < 3; s++) {
          uint32_t (&hh)[4] = HH[8 + s];
          hh[0] = tg(pack2(ag[8 * s + 0] * au[8 * s + 0] * r0, ag[8 * s + 1] * au[8 * s + 1] * r0), T);
          hh[1] = pack2(ag[8 * s + 2] * au[8 * s + 2] * r1, ag[8 * s + 3] * au[8 * s + 3] * r1);
          hh[2] = pack2(ag[8 * s + 4] * au[8 * s + 4] * r0, ag[8 * s + 5] * au[8 * s + 5] * r0);
          hh[3] = pack2(ag[8 * s + 6] * au[8 * s + 6] * r1, ag[8 * s + 7] * au[8 * s + 7] * r1);
          st_rlx4(hhp + (8 + s) * 128, hh[0], hh[1], hh[2], hh[3]);
        }
      }
    }
    TSTAMP(14);

    {
      float ac[3][32], acc[32];
      uint32_t hr[4][4];
      const int m = jf >> 1, oc = (jf & 1) * 4 + m;
      const uint32_t* ph10 = reinterpret_cast<const uint32_t*>(&g_hh[rh3][jf ^ 1][10][wq][31]);
      uint32_t hv = 0;
      bar_arrive(8 + wg, 256);
      wg_fence();
#pragma unroll
      for (int k = 0; k < 3; k++) {
        mbar_wait(sb + SM_FULL + (ST_D + k) * 8);
        if (k == 1) hv = ld_rlx1(ph10);
#pragma unroll
        for (int s = 0; s < 11; s++) {
          if (k == 2 && s == 4) {
            int it = 0;
#pragma unroll 1
            while (((hv ^ T) & 1) && ++it < (1 << 18)) hv = ld_rlx1(ph10);
#pragma unroll
            for (int i = 8; i < 11; i++) ld_rlx4(PH[i], pp + i * 128);
          }
          wgmma_rs_n64(ac[k], HH[s], DESC(((ST_D + k) % NSLOT) * SLOT + s * 2048), s != 0);
        }
      }
      wg_commit();
      {
        int it = 0;
#pragma unroll 1
        while (__any_sync(0xffffffffu, bad4(PH[0][0], PH[1][0], PH[2][0], PH[3][0], T) | bad4(PH[4][0], PH[5][0], PH[6][0], PH[7][0], T) |
                                       bad4(PH[8][0], PH[9][0], PH[10][0], T, T))) {
#pragma unroll
          for (int s = 0; s < 11; s++) ld_rlx4(PH[s], pp + s * 128);
          if (++it > (1 << 18)) break;
        }
      }
      TSTAMP(20);
      uint4* outb = &g_part[rh3][(jf & 1) * 4][m][wq][0][lane];
#pragma unroll
      for (int k = 0; k < 4; k++) {
        mbar_wait(sb + SM_FULL + (ST_D + 3 + k) * 8);
        wg_fence();
#pragma unroll
        for (int s = 0; s < 11; s++) {
          if (k < 3) wgmma_rs_n64(ac[k], PH[s], DESC(((ST_D + 3 + k) % NSLOT) * SLOT + s * 2048), 1);
          else wgmma_rs_n64(acc, HH[s], DESC(((ST_D + 6) % NSLOT) * SLOT + s * 2048), s != 0);
        }
        wg_commit();
        if (k > 0) {
          wg_wait<1>();
          const float (&a)[32] = ac[k - 1];
          uint4* p = outb + ((m + k) & 3) * 2048;
#pragma unroll
          for (int s = 0; s < 4; s++)
            st_rlx4(p + s * 32, tg(pack2(a[8 * s + 0], a[8 * s + 1]), T), pack2(a[8 * s + 2], a[8 * s + 3]),
                    pack2(a[8 * s + 4], a[8 * s + 5]), pack2(a[8 * s + 6], a[8 * s + 7]));
        }
      }
      uint32_t in[3][4][4];
      const uint4* inb = &g_part[rh3][oc][0][wq][0][lane];
      const uint32_t* hint = reinterpret_cast<const uint32_t*>(&g_part[rh3][oc][(m - 1 - lane) & 3][wq][3][31]);
      ld_chunk(hr, &g_h[rh3][oc][wq][0][lane]);
      uint32_t hx = ld_rlx1(&g_hx[rh3][oc][wq][lane]);
      hv = ld_rlx1(hint);
      mbar_wait(sb + SM_FULL + (ST_D + 7) * 8);
      wg_fence();
#pragma unroll
      for (int s = 0; s < 11; s++) wgmma_rs_n64(acc, PH[s], DESC(((ST_D + 7) % NSLOT) * SLOT + s * 2048), 1);
      wg_commit();
      {
        uint32_t ready = __ballot_sync(0xffffffffu, ((hv ^ T) & 1) == 0); int it = 0;
#pragma unroll
        for (int q = 0; q < 3; q++) {
#pragma unroll 1
          while (!((ready >> q) & 1)) {
            ready = __ballot_sync(0xffffffffu, ((ld_rlx1(hint) ^ T) & 1) == 0);
            if (++it > (1 << 18)) break;
          }
          ld_chunk(in[q], inb + ((m - 1 - q) & 3) * 512);
        }
#pragma unroll 1
        while (__any_sync(0xffffffffu, bad4(in[0][0][0], in[0][1][0], in[0][2][0], in[0][3][0], T) | bad4(in[1][0][0], in[1][1][0], in[1][2][0], in[1][3][0], T) |
                                       bad4(in[2][0][0], in[2][1][0], in[2][2][0], in[2][3][0], T) | ((hx ^ T) & 1))) {
#pragma unroll
          for (int q = 0; q < 3; q++) ld_chunk(in[q], inb + ((m - 1 - q) & 3) * 512);
          hx = ld_rlx1(&g_hx[rh3][oc][wq][lane]);
          if (++it > (1 << 18)) break;
        }
      }
      wg_wait<0>();
      TSTAMP(15);
#pragma unroll
      for (int s = 0; s < 4; s++) hr[s][0] = (hr[s][0] & 0xFFFFFFFEu) | ((hx >> (s + 1)) & 1u);
      add_frag(acc, hr, IDF); add_frag(acc, in[0], IDF); add_frag(acc, in[1], IDF); add_frag(acc, in[2], IDF);
      bar_sync(9 - wg, 256);
      const uint32_t ob = sb + ((ST_D - 1) % NSLOT) * SLOT + wg * 8192;
#pragma unroll
      for (int s = 0; s < 4; s++)
        stsm4(ob + lrow + (((2 * s + lhi) ^ lx) << 4), pack2(acc[8 * s + 0], acc[8 * s + 1]), pack2(acc[8 * s + 2], acc[8 * s + 3]),
              pack2(acc[8 * s + 4], acc[8 * s + 5]), pack2(acc[8 * s + 6], acc[8 * s + 7]));
      __syncwarp();
#pragma unroll
      for (int i = 0; i < 4; i++) {
        const int row = wq * 16 + i * 4 + (lane >> 3);
        uint4 v;
        asm volatile("ld.shared.v4.b32 {%0,%1,%2,%3}, [%4];" : "=r"(v.x), "=r"(v.y), "=r"(v.z), "=r"(v.w)
                     : "r"(ob + row * 128 + ((lx ^ (row & 7)) << 4)) : "memory");
        asm volatile("st.global.v4.b32 [%0], {%1,%2,%3,%4};" ::"l"(out + (size_t)(rh3 * 64 + row) * 512 + oc * 64 + lx * 8),
                     "r"(v.x), "r"(v.y), "r"(v.z), "r"(v.w) : "memory");
      }
    }
    TSTAMP(16);
    asm volatile("barrier.cluster.arrive.relaxed.aligned;" ::: "memory");
    asm volatile("barrier.cluster.wait.aligned;" ::: "memory");
  } else {
    asm volatile("setmaxnreg.dec.sync.aligned.u32 24;");
    if (elect_one()) {
      if (warp == 8) {
#pragma unroll
        for (int k = 0; k < 9; k++) {
          const int s = k < 3 ? k : (k < 6 ? k + 3 : k - 3);
          const uint32_t bar = sb + SM_FULL + s * 8;
          mbar_init(bar, 1);
          mbar_expect_tx(bar, SLOT);
          if (s >= 3 && s < 6) tma2d(sb + s * SLOT, &maps.w, 512 + hg * 64, (s - 3) * 192, bar);
          else tma3d(sb + s * SLOT, &maps.x, 0, rb * 128 + (s >= 6 ? 64 : 0), 3 * (s % 3), bar);
        }
      } else if (warp == 9) {
        mbar_init(sb + SM_MISCB, 2);
        mbar_init(sb + SM_KVB, 32);
        mbar_expect_tx(sb + SM_MISCB, 2048);
        bulk_g2s(sb + SM_WPHI, wphi + hg * 1024, 2048, sb + SM_MISCB);
      } else if (warp == 10) {
#pragma unroll 1
        for (int i = 0; i < 16; i++) {
          mbar_init(sb + SM_XF + i * 8, 1);
          mbar_expect_tx(sb + SM_XF + i * 8, (i == 8 || i == 12) ? 20480 : 16384);
          if (i < 12) mbar_init(sb + SM_XE + i * 8, 4);
        }
      } else {
        *reinterpret_cast<volatile unsigned*>(smem + SM_EPOCH) = atomicAdd(&g_start, 1u) / NCTA;
      }
      asm volatile("fence.mbarrier_init.release.cluster;" ::: "memory");
    }
    __syncwarp();
    if (warp != 11) bar_sync(0, 352);
    asm volatile("barrier.cluster.arrive.relaxed.aligned;" ::: "memory");
    if (warp == 8) {
      asm volatile("barrier.cluster.wait.aligned;" ::: "memory");
      if (elect_one()) {
        const CUtensorMap* mg = jf == 7 ? &maps.g7 : &maps.g;
        const CUtensorMap* mu = jf == 7 ? &maps.u7 : &maps.u;
        asm volatile("prefetch.tensormap [%0];" ::"l"(&maps.wo) : "memory");
        asm volatile("prefetch.tensormap [%0];" ::"l"(mg) : "memory");
        asm volatile("prefetch.tensormap [%0];" ::"l"(mu) : "memory");
        asm volatile("prefetch.tensormap [%0];" ::"l"(&maps.d) : "memory");
#pragma unroll 1
        for (int s = ST_WV; s < ST_XC; s++) {
          if (s == ST_SCR1) continue;
          mbar_wait(sb + SM_EMPTY + (s - 9) * 8);
          const uint32_t dst = sb + (s >= 18 ? s - 18 : s - 9) * SLOT, bar = sb + SM_FULL + s * 8;
          if (s < ST_WO) tma2d(dst, &maps.w, (s < ST_WQ ? 1024 : 0) + hg * 64, (s < ST_WQ ? s - ST_WV : s - ST_WQ) * 192, bar);
          else { mbar_wait(bar - 8); tma2d(dst, &maps.wo, hg * 64, (s - ST_WO) * 192, bar); }
        }
        const int jc = jf == 7 ? 0 : jf;
        int slot = (ST_GU + 1 - rank) % NSLOT;
#pragma unroll 1
        for (int s = ST_GU + 1 - rank; s < NSTAGE; s += 2) {
          mbar_wait(sb + SM_EMPTY + (s - 9) * 8);
          if (s > ST_GU && s < ST_GU + THR) mbar_wait(sb + SM_FULL + (s - 1) * 8);
          const uint32_t dst = sb + slot * SLOT, bar = sb + SM_FULL + s * 8;
          if (s < ST_D) {
#pragma unroll 1
            for (int i = 0; i < 3; i++) {
              const int u = (s - ST_GU) * 3 + i;
              tma3d_mc(dst + i * 8192, mg, (u >> 4) * 64, jc, (u & 15) * 32, bar);
              tma3d_mc(dst + i * 8192 + 4096, mu, (u >> 4) * 64, jc, (u & 15) * 32, bar);
            }
          } else {
            const int i = s - ST_D, k = i < 3 ? i : (i < 6 ? i - 3 : 3), pt = (i >= 3 && i != 6) ? 1 : 0;
            tma2d_mc(dst, &maps.d, ((jf & 1) * 4 + (((jf >> 1) + 1 + k) & 3)) * 64, (jf ^ pt) * 176, bar);
          }
          slot += 2; if (slot >= NSLOT) slot -= NSLOT;
        }
      }
      __syncwarp();
    } else {
      asm volatile("barrier.cluster.wait.aligned;" ::: "memory");
      if (warp == 11) {
#pragma unroll
        for (int i = 0; i < 4; i++)
          reinterpret_cast<uint4*>(smem + SM_ONES)[lane + 32 * i] = make_uint4(0x3F803F80u, 0x3F803F80u, 0x3F803F80u, 0x3F803F80u);
        fence_async_smem();
        __syncwarp();
        if (lane == 0) mbar_arrive(sb + SM_MISCB);
      }
      mbar_wait(sb + SM_MISCB);
      const unsigned epoch = *reinterpret_cast<volatile unsigned*>(smem + SM_EPOCH);
      const uint32_t T = (epoch & 1) ^ 1;
      if (warp == 11) {
        reinterpret_cast<float4*>(&g_kv[T][blockIdx.x * 128])[lane] = make_float4(0.f, 0.f, 0.f, 0.f);
        if (lane < 8) g_z[T][blockIdx.x * 8 + lane] = 0.f;
        mbar_wait(sb + SM_FULL + (ST_WK + 2) * 8);
        if (elect_one()) {
          asm volatile("cp.async.bulk.prefetch.L2.global [%0], 4096;" ::"l"((const char*)wo + blockIdx.x * 4096) : "memory");
          asm volatile("cp.async.bulk.prefetch.L2.global [%0], 11008;" ::"l"((const char*)wg_ + blockIdx.x * 11008) : "memory");
          asm volatile("cp.async.bulk.prefetch.L2.global [%0], 11008;" ::"l"((const char*)wu_ + blockIdx.x * 11008) : "memory");
          asm volatile("cp.async.bulk.prefetch.L2.global [%0], 11008;" ::"l"((const char*)wd_ + blockIdx.x * 11008) : "memory");
          const unsigned target = (epoch + 1) * 32;
          unsigned v; int it = 0;
#pragma unroll 1
          do {
            asm volatile("ld.acquire.gpu.global.u32 %0, [%1];" : "=r"(v) : "l"(&g_kvcnt[hg * 32]) : "memory");
            if (++it > (1 << 18)) break;
          } while ((int)(v - target) < 0);
          TS2(0, 26);
        }
        __syncwarp();
        {
          const char* src = reinterpret_cast<const char*>(&g_kv[T ^ 1][hg * 2048]) + lane * 16;
#pragma unroll 4
          for (int i = 0; i < 16; i++)
            asm volatile("cp.async.cg.shared.global [%0], [%1], 16;" ::"r"(sb + SM_KV32 + lane * 16 + i * 512), "l"(src + i * 512) : "memory");
          asm volatile("cp.async.cg.shared.global [%0], [%1], 16;" ::"r"(sb + SM_ONES + lane * 16), "l"(&g_z[T ^ 1][hg * 128 + lane * 4]) : "memory");
          asm volatile("cp.async.mbarrier.arrive.noinc.shared::cta.b64 [%0];" ::"r"(sb + SM_KVB) : "memory");
        }
      } else {
        const int w = warp - 9;
        st_rlx4(reinterpret_cast<uint4*>(&g_st[2 * rb + w][hg][0]) + lane, T ^ 1, T ^ 1, T ^ 1, T ^ 1);
        if (lane < 8) st_rlx4(&g_o[2 * rb + w][hg][lane >> 1][3][30 + (lane & 1)], T ^ 1, T ^ 1, T ^ 1, T ^ 1);
        st_rlx4(&g_part[2 * rb3 + w][(jf & 1) * 4 + (lane >> 3)][jf >> 1][(lane >> 1) & 3][3][30 + (lane & 1)], T ^ 1, T ^ 1, T ^ 1, T ^ 1);
        if (lane < 16) st_rlx4(&g_hh[2 * rb3 + w][jf][7 + (lane >> 3) * 3][(lane >> 1) & 3][30 + (lane & 1)], T ^ 1, T ^ 1, T ^ 1, T ^ 1);
        bar_sync(6 + w, 160);
        if (elect_one()) {
          asm volatile("fence.release.gpu;" ::: "memory");
          TS2(w, 25);
          asm volatile("red.relaxed.gpu.global.add.u32 [%0], 1;" ::"l"(&g_kvcnt[hg * 32]) : "memory");
        }
        mbar_wait(sb + SM_KVB);
        if (w == 0) { mbar_wait(sb + SM_EMPTY + 11 * 8); mbar_wait(sb + SM_EMPTY + 12 * 8); mbar_wait(sb + SM_EMPTY + 13 * 8); }
#pragma unroll 1
        for (int ph = 0; ph < 2; ph++) {
          const int use = 2 * ph + w, r = ph ? 2 * rb3 + w : 2 * rb + w;
          const uint32_t* pw = ph ? reinterpret_cast<const uint32_t*>(&g_st[r][lane >> 2][(lane & 3) * 16 + 15])
                                  : reinterpret_cast<const uint32_t*>(&g_o[r][lane >> 2][lane & 3][3][31]);
          const char* src = reinterpret_cast<const char*>(ph ? &g_h[r][0][0][0][0] : &g_o[r][0][0][0][0]);
          const uint32_t bf = sb + SM_XF + use * 32, be = sb + SM_XE + (use - 1) * 32;
          if (ph) mbar_wait(sb + SM_XE + w * 32 + 24);
          int it = 0;
#pragma unroll 1
          while (__any_sync(0xffffffffu, (ld_rlx1(pw) ^ T) & 1)) { if (++it > (1 << 18)) break; }
          if (elect_one()) {
            TS2(w, 27 + ph);
            if (use > 0) mbar_wait(be);
            if (ph) bulk_g2s(sb + SM_KV32 + w * 4096, &g_st[r][0][0], 4096, bf);
#pragma unroll
            for (int p = 0; p < 4; p++) {
              if (p > 0 && use > 0) mbar_wait(be + p * 8);
              bulk_g2s(sb + 2 * SLOT + p * 16384, src + p * 16384, 16384, bf + p * 8);
            }
          }
          __syncwarp();
        }
      }
    }
    asm volatile("barrier.cluster.arrive.relaxed.aligned;" ::: "memory");
    asm volatile("barrier.cluster.wait.aligned;" ::: "memory");
  }
}

typedef CUresult (*EncodeFn)(CUtensorMap*, CUtensorMapDataType, cuuint32_t, void*, const cuuint64_t*, const cuuint64_t*,
                             const cuuint32_t*, const cuuint32_t*, CUtensorMapInterleave, CUtensorMapSwizzle,
                             CUtensorMapL2promotion, CUtensorMapFloatOOBfill);

void encode(EncodeFn fn, CUtensorMap* m, const void* base, int rank, const cuuint64_t* dims, const cuuint64_t* strides,
            const cuuint32_t* box) {
  cuuint32_t es[3] = {1, 1, 1};
  fn(m, CU_TENSOR_MAP_DATA_TYPE_BFLOAT16, (cuuint32_t)rank, const_cast<void*>(base), dims, strides, box, es,
     CU_TENSOR_MAP_INTERLEAVE_NONE, CU_TENSOR_MAP_SWIZZLE_128B, CU_TENSOR_MAP_L2_PROMOTION_L2_256B,
     CU_TENSOR_MAP_FLOAT_OOB_FILL_NONE);
}

}

extern "C" void kernel_launch(void* const* d_in, const int* in_sizes, int n_in, void* d_out, int out_size) {
  (void)in_sizes; (void)n_in; (void)out_size;
  const __nv_bfloat16* x    = (const __nv_bfloat16*)d_in[0];
  const __nv_bfloat16* wqkv = (const __nv_bfloat16*)d_in[1];
  const __nv_bfloat16* wphi = (const __nv_bfloat16*)d_in[2];
  const __nv_bfloat16* wo   = (const __nv_bfloat16*)d_in[3];
  const __nv_bfloat16* wg   = (const __nv_bfloat16*)d_in[5];
  const __nv_bfloat16* wu   = (const __nv_bfloat16*)d_in[6];
  const __nv_bfloat16* wd   = (const __nv_bfloat16*)d_in[7];

  static EncodeFn fn = nullptr;
  static int reserved = 0;
  if (!fn) {
    void* p = nullptr;
    cudaDriverEntryPointQueryResult qr;
    cudaGetDriverEntryPoint("cuTensorMapEncodeTiled", &p, cudaEnableDefault, &qr);
    fn = (EncodeFn)p;
    cudaFuncSetAttribute(fused_kernel<1024>, cudaFuncAttributeMaxDynamicSharedMemorySize, SM_TOTAL);
    cudaFuncSetAttribute(fused_kernel<0>, cudaFuncAttributeMaxDynamicSharedMemorySize, SM_TOTAL);
    int dev = 0;
    cudaGetDevice(&dev);
    cudaDeviceGetAttribute(&reserved, cudaDevAttrReservedSharedMemoryPerBlock, dev);
  }
  Maps maps;
  {
    cuuint64_t d[3] = {64, 2048, 8}, s[2] = {1024, 128}; cuuint32_t b[3] = {64, 64, 3};
    encode(fn, &maps.x, x, 3, d, s, b);
  }
  {
    cuuint64_t d[2] = {1536, 512}, s[1] = {3072}; cuuint32_t b[2] = {64, 192};
    encode(fn, &maps.w, wqkv, 2, d, s, b);
  }
  {
    cuuint64_t d[2] = {512, 512}, s[1] = {1024}; cuuint32_t b[2] = {64, 192};
    encode(fn, &maps.wo, wo, 2, d, s, b);
  }
  {
    cuuint64_t d[3] = {176, 7, 512}, d7[3] = {144, 1, 512}, s[2] = {352, 2752}; cuuint32_t b[3] = {64, 1, 32};
    encode(fn, &maps.g, wg, 3, d, s, b);
    encode(fn, &maps.u, wu, 3, d, s, b);
    encode(fn, &maps.g7, wg + 1232, 3, d7, s, b);
    encode(fn, &maps.u7, wu + 1232, 3, d7, s, b);
  }
  {
    cuuint64_t d[2] = {512, 1376}, s[1] = {1024}; cuuint32_t b[2] = {64, 176};
    encode(fn, &maps.d, wd, 2, d, s, b);
  }
  if (reserved == 1024) fused_kernel<1024><<<NCTA, 384, SM_TOTAL>>>(maps, x, wphi, wo, wg, wu, wd, (__nv_bfloat16*)d_out);
  else fused_kernel<0><<<NCTA, 384, SM_TOTAL>>>(maps, x, wphi, wo, wg, wu, wd, (__nv_bfloat16*)d_out);
}
```

```cpp
#include <cuda_runtime.h>
#include <cuda_bf16.h>
#include <cuda.h>
#include <stdint.h>

#define PROF 0

#define SAFE_WAIT 0
#define OPRIO 1
#define THR 6

namespace {

constexpr int NCTA   = 128;
constexpr int SLOT   = 24576;
constexpr int NSLOT  = 9;
constexpr int NSTAGE = 47;

constexpr int ST_X0   = 0;
constexpr int ST_WK   = 3;
constexpr int ST_X1   = 6;
constexpr int ST_SCR0 = 9;
constexpr int ST_WV   = 10;
constexpr int ST_SCR1 = 13;
constexpr int ST_WQ   = 14;
constexpr int ST_WO   = 17;
constexpr int ST_XC   = 20;
constexpr int ST_GU   = 23;
constexpr int ST_D    = 39;

__host__ __device__ constexpr int st_empty_cnt(int d) {
  return ((d < 3 || (d >= 6 && d < 9) || (d >= ST_XC && d < ST_GU)) ? 4 : 2) * (d + 9 >= ST_GU ? 2 : 1);
}

constexpr uint32_t SM_BASE = 1024;
constexpr int SM_ONES = NSLOT * SLOT;
constexpr int SM_WPHI = SM_ONES + 2048;
constexpr int SM_KVS  = SM_WPHI + 2048;
constexpr int SM_KV32 = 4 * SLOT + 16384;
constexpr int SM_BAR  = SM_KVS + 6144;
constexpr int SM_FULL  = SM_BAR;
constexpr int SM_EMPTY = SM_BAR + NSTAGE * 8;
constexpr int SM_MISCB = SM_BAR + 2 * NSTAGE * 8;
constexpr int SM_KVB   = SM_MISCB + 8;
constexpr int SM_EPOCH = SM_KVB + 8;
constexpr int SM_XF    = SM_EPOCH + 8;
constexpr int SM_XE    = SM_XF + 16 * 8;
constexpr int SM_TOTAL = SM_BAR + 1024;

static_assert(SM_TOTAL == 232448 && SM_XE + 12 * 8 <= SM_TOTAL, "smem budget");

struct Maps { CUtensorMap x, w, wo, g, u, g7, u7, d; };

__device__ uint4    g_o[32][8][4][4][32];
__device__ uint4    g_h[32][8][4][4][32];
__device__ uint32_t g_hx[32][8][4][32];
__device__ uint2    g_st[32][8][64];
__device__ uint4    g_hh[32][8][11][4][32];
__device__ uint4    g_part[32][8][4][4][4][32];
__device__ float    g_kv[2][32 * 32 * 16];
__device__ float    g_z[2][32 * 32];
__device__ unsigned g_kvcnt[8 * 32];
__device__ unsigned g_start;

__device__ __forceinline__ uint32_t smem_u32(const void* p) { return (uint32_t)__cvta_generic_to_shared(p); }
__device__ __forceinline__ void mbar_init(uint32_t bar, int cnt) {
  asm volatile("mbarrier.init.shared::cta.b64 [%0], %1;" ::"r"(bar), "r"(cnt) : "memory");
}
__device__ __forceinline__ void mbar_expect_tx(uint32_t bar, uint32_t bytes) {
  asm volatile("mbarrier.arrive.expect_tx.shared::cta.b64 _, [%0], %1;" ::"r"(bar), "r"(bytes) : "memory");
}
__device__ __forceinline__ void mbar_arrive(uint32_t bar) {
  asm volatile("mbarrier.arrive.shared::cta.b64 _, [%0];" ::"r"(bar) : "memory");
}
__device__ __forceinline__ void mbar_arrive_cluster(uint32_t bar, uint32_t rank) {
  asm volatile("{\n.reg .b32 ra;\nmapa.shared::cluster.u32 ra, %0, %1;\n"
               "mbarrier.arrive.shared::cluster.b64 _, [ra];\n}" ::"r"(bar), "r"(rank) : "memory");
}
__device__ __forceinline__ void mbar_wait_p(uint32_t bar, uint32_t parity) {
  asm volatile("{\n.reg .pred p;\nW: mbarrier.try_wait.parity.shared::cta.b64 p, [%0], %1;\n@!p bra W;\n}" ::"r"(bar), "r"(parity) : "memory");
}
__device__ __forceinline__ void mbar_wait(uint32_t bar) { mbar_wait_p(bar, 0); }
__device__ __forceinline__ bool elect_one() {
  uint32_t p;
  asm volatile("{\n.reg .pred P;\nelect.sync _|P, 0xffffffff;\nselp.u32 %0, 1, 0, P;\n}" : "=r"(p));
  return p != 0;
}
__device__ __forceinline__ void bar_sync(int id, int n)   { asm volatile("bar.sync %0, %1;" ::"r"(id), "r"(n) : "memory"); }
__device__ __forceinline__ void bar_arrive(int id, int n) { asm volatile("bar.arrive %0, %1;" ::"r"(id), "r"(n) : "memory"); }
__device__ __forceinline__ void fence_async_smem() { asm volatile("fence.proxy.async.shared::cta;" ::: "memory"); }
__device__ __forceinline__ void wg_fence()  { asm volatile("wgmma.fence.sync.aligned;" ::: "memory"); }
__device__ __forceinline__ void wg_commit() { asm volatile("wgmma.commit_group.sync.aligned;" ::: "memory"); }
template <int N> __device__ __forceinline__ void wg_wait() { asm volatile("wgmma.wait_group.sync.aligned %0;" ::"n"(N) : "memory"); }
#define DESC(off) (db + ((uint32_t)(off) >> 4))
__device__ __forceinline__ void tma2d(uint32_t dst, const CUtensorMap* m, int c0, int c1, uint32_t bar) {
  asm volatile("cp.async.bulk.tensor.2d.shared::cluster.global.mbarrier::complete_tx::bytes [%0], [%1, {%3, %4}], [%2];"
               ::"r"(dst), "l"(m), "r"(bar), "r"(c0), "r"(c1) : "memory");
}
__device__ __forceinline__ void tma2d_mc(uint32_t dst, const CUtensorMap* m, int c0, int c1, uint32_t bar) {
  asm volatile("cp.async.bulk.tensor.2d.shared::cluster.global.mbarrier::complete_tx::bytes.multicast::cluster [%0], [%1, {%3, %4}], [%2], %5;"
               ::"r"(dst), "l"(m), "r"(bar), "r"(c0), "r"(c1), "h"((uint16_t)3) : "memory");
}
__device__ __forceinline__ void tma3d(uint32_t dst, const CUtensorMap* m, int c0, int c1, int c2, uint32_t bar) {
  asm volatile("cp.async.bulk.tensor.3d.shared::cluster.global.mbarrier::complete_tx::bytes [%0], [%1, {%3, %4, %5}], [%2];"
               ::"r"(dst), "l"(m), "r"(bar), "r"(c0), "r"(c1), "r"(c2) : "memory");
}
__device__ __forceinline__ void tma3d_mc(uint32_t dst, const CUtensorMap* m, int c0, int c1, int c2, uint32_t bar) {
  asm volatile("cp.async.bulk.tensor.3d.shared::cluster.global.mbarrier::complete_tx::bytes.multicast::cluster [%0], [%1, {%3, %4, %5}], [%2], %6;"
               ::"r"(dst), "l"(m), "r"(bar), "r"(c0), "r"(c1), "r"(c2), "h"((uint16_t)3) : "memory");
}
__device__ __forceinline__ void ldsm4(uint32_t (&r)[4], uint32_t addr) {
  asm volatile("ldmatrix.sync.aligned.m8n8.x4.shared.b16 {%0,%1,%2,%3}, [%4];"
               : "=r"(r[0]), "=r"(r[1]), "=r"(r[2]), "=r"(r[3]) : "r"(addr) : "memory");
}
__device__ __forceinline__ void ldsm4t(uint32_t (&r)[4], uint32_t addr) {
  asm volatile("ldmatrix.sync.aligned.m8n8.x4.trans.shared.b16 {%0,%1,%2,%3}, [%4];"
               : "=r"(r[0]), "=r"(r[1]), "=r"(r[2]), "=r"(r[3]) : "r"(addr) : "memory");
}
__device__ __forceinline__ void stsm4(uint32_t addr, uint32_t r0, uint32_t r1, uint32_t r2, uint32_t r3) {
  asm volatile("stmatrix.sync.aligned.m8n8.x4.shared.b16 [%0], {%1,%2,%3,%4};"
               ::"r"(addr), "r"(r0), "r"(r1), "r"(r2), "r"(r3) : "memory");
}
__device__ __forceinline__ void mma16816(float (&c)[4], const uint32_t (&a)[4], uint32_t b0, uint32_t b1) {
  asm volatile("mma.sync.aligned.m16n8k16.row.col.f32.bf16.bf16.f32 {%0,%1,%2,%3},{%4,%5,%6,%7},{%8,%9},{%0,%1,%2,%3};"
               : "+f"(c[0]), "+f"(c[1]), "+f"(c[2]), "+f"(c[3])
               : "r"(a[0]), "r"(a[1]), "r"(a[2]), "r"(a[3]), "r"(b0), "r"(b1));
}
__device__ __forceinline__ void add_frag(float (&c)[32], const uint32_t (&a)[4][4], uint32_t id) {
#pragma unroll
  for (int i = 0; i < 8; i++)
    asm volatile("mma.sync.aligned.m16n8k8.row.col.f32.bf16.bf16.f32 {%0,%1,%2,%3},{%4,%5},{%6},{%0,%1,%2,%3};"
                 : "+f"(c[4 * i]), "+f"(c[4 * i + 1]), "+f"(c[4 * i + 2]), "+f"(c[4 * i + 3])
                 : "r"(a[i >> 1][(i & 1) * 2]), "r"(a[i >> 1][(i & 1) * 2 + 1]), "r"(id));
}
__device__ __forceinline__ uint32_t pack2(float lo, float hi) {
  uint32_t r; asm("cvt.rn.bf16x2.f32 %0, %1, %2;" : "=r"(r) : "f"(hi), "f"(lo)); return r;
}
__device__ __forceinline__ float blo(uint32_t w) { return __uint_as_float(w << 16); }
__device__ __forceinline__ float bhi(uint32_t w) { return __uint_as_float(w & 0xFFFF0000u); }
__device__ __forceinline__ uint32_t hsub2(uint32_t a, uint32_t b) { uint32_t r; asm("sub.rn.bf16x2 %0, %1, %2;" : "=r"(r) : "r"(a), "r"(b)); return r; }
__device__ __forceinline__ uint32_t hmax2(uint32_t a, uint32_t b) { uint32_t r; asm("max.bf16x2 %0, %1, %2;" : "=r"(r) : "r"(a), "r"(b)); return r; }
__device__ __forceinline__ uint32_t hmin2(uint32_t a, uint32_t b) { uint32_t r; asm("min.bf16x2 %0, %1, %2;" : "=r"(r) : "r"(a), "r"(b)); return r; }
__device__ __forceinline__ float ex2(float x) { float r; asm("ex2.approx.ftz.f32 %0, %1;" : "=f"(r) : "f"(x)); return r; }
__device__ __forceinline__ float rcp(float x) { float r; asm("rcp.approx.ftz.f32 %0, %1;" : "=f"(r) : "f"(x)); return r; }
__device__ __forceinline__ void ld_rlx4(uint32_t (&r)[4], const uint4* p) {
  asm volatile("{\n.reg .b128 v;\nld.relaxed.gpu.global.b128 v, [%4];\nmov.b128 {%0,%1,%2,%3}, v;\n}"
               : "=r"(r[0]), "=r"(r[1]), "=r"(r[2]), "=r"(r[3]) : "l"(p) : "memory");
}
__device__ __forceinline__ void st_rlx4(uint4* p, uint32_t a, uint32_t b, uint32_t c, uint32_t d) {
  asm volatile("{\n.reg .b128 v;\nmov.b128 v, {%1,%2,%3,%4};\nst.relaxed.gpu.global.b128 [%0], v;\n}"
               ::"l"(p), "r"(a), "r"(b), "r"(c), "r"(d) : "memory");
}
__device__ __forceinline__ void st_rlx2(uint2* p, uint32_t a, uint32_t b) {
  asm volatile("{\n.reg .b64 v;\nmov.b64 v, {%1,%2};\nst.relaxed.gpu.global.b64 [%0], v;\n}" ::"l"(p), "r"(a), "r"(b) : "memory");
}
__device__ __forceinline__ uint32_t ld_rlx1(const uint32_t* p) {
  uint32_t r; asm volatile("ld.relaxed.gpu.global.b32 %0, [%1];" : "=r"(r) : "l"(p) : "memory"); return r;
}
__device__ __forceinline__ void st_rlx1(uint32_t* p, uint32_t a) {
  asm volatile("st.relaxed.gpu.global.b32 [%0], %1;" ::"l"(p), "r"(a) : "memory");
}
__device__ __forceinline__ void ld_rlx2(uint32_t& a, uint32_t& b, const uint2* p) {
  asm volatile("{\n.reg .b64 v;\nld.relaxed.gpu.b64 v, [%2];\nmov.b64 {%0,%1}, v;\n}" : "=r"(a), "=r"(b) : "l"(p) : "memory");
}
__device__ __forceinline__ void bulk_g2s(uint32_t dst, const void* src, uint32_t bytes, uint32_t bar) {
  asm volatile("cp.async.bulk.shared::cluster.global.mbarrier::complete_tx::bytes [%0], [%1], %2, [%3];"
               ::"r"(dst), "l"(src), "r"(bytes), "r"(bar) : "memory");
}
__device__ __forceinline__ uint32_t tg(uint32_t w, uint32_t T) { return (w & 0xFFFFFFFEu) | T; }
__device__ __forceinline__ uint32_t bad4(uint32_t a, uint32_t b, uint32_t c, uint32_t d, uint32_t T) {
  uint32_t u, v;
  asm("lop3.b32 %0, %1, %2, %3, 0x7E;" : "=r"(u) : "r"(a), "r"(b), "r"(T));
  asm("lop3.b32 %0, %1, %2, %3, 0x7E;" : "=r"(v) : "r"(c), "r"(d), "r"(T));
  asm("lop3.b32 %0, %1, %2, 1, 0xA8;" : "=r"(u) : "r"(u), "r"(v));
  return u;
}

__device__ __forceinline__ void ld_chunk(uint32_t (&a)[4][4], const uint4* p) {
#pragma unroll
  for (int s = 0; s < 4; s++) ld_rlx4(a[s], p + s * 32);
}
__device__ __forceinline__ void get_pair(uint32_t (&a)[4][4], uint32_t (&b)[4][4], const uint4* sp, const uint4* gp, uint32_t T) {
  int it = 0;
#pragma unroll 1
  do {
#pragma unroll
    for (int s = 0; s < 8; s++) {
      uint32_t (&r)[4] = s < 4 ? a[s & 3] : b[s & 3];
      asm volatile("{\n.reg .b128 v;\nld.relaxed.gpu.b128 v, [%4];\nmov.b128 {%0,%1,%2,%3}, v;\n}"
                   : "=r"(r[0]), "=r"(r[1]), "=r"(r[2]), "=r"(r[3]) : "l"(sp + (s >> 2) * 512 + (s & 3) * 32) : "memory");
    }
    sp = gp;
  } while (__any_sync(0xffffffffu, bad4(a[0][0], a[1][0], a[2][0], a[3][0], T) | bad4(b[0][0], b[1][0], b[2][0], b[3][0], T)) && ++it < (1 << 18));
}

__device__ __forceinline__ void wgmma_rs_n48(float (&d)[24], const uint32_t (&a)[4], uint32_t descB, int scaleD) {
  asm volatile("{\n.reg .pred p;\n.reg .b64 db;\nsetp.ne.b32 p, %29, 0;\nmov.b64 db, {%28, 0x40000040};\n"
    "wgmma.mma_async.sync.aligned.m64n48k16.f32.bf16.bf16 {%0,%1,%2,%3,%4,%5,%6,%7,%8,%9,%10,%11,%12,%13,%14,%15,%16,%17,%18,%19,%20,%21,%22,%23}, {%24,%25,%26,%27}, db, p, 1, 1, 1;\n}\n"
    : "+f"(d[0]),"+f"(d[1]),"+f"(d[2]),"+f"(d[3]),"+f"(d[4]),"+f"(d[5]),"+f"(d[6]),"+f"(d[7]),"+f"(d[8]),"+f"(d[9]),"+f"(d[10]),"+f"(d[11]),"+f"(d[12]),"+f"(d[13]),"+f"(d[14]),"+f"(d[15]),"+f"(d[16]),"+f"(d[17]),"+f"(d[18]),"+f"(d[19]),"+f"(d[20]),"+f"(d[21]),"+f"(d[22]),"+f"(d[23])
    : "r"(a[0]), "r"(a[1]), "r"(a[2]), "r"(a[3]), "r"(descB), "r"(scaleD));
}
__device__ __forceinline__ void wgmma_rs_n64(float (&d)[32], const uint32_t (&a)[4], uint32_t descB, int scaleD) {
  asm volatile("{\n.reg .pred p;\n.reg .b64 db;\nsetp.ne.b32 p, %37, 0;\nmov.b64 db, {%36, 0x40000040};\n"
    "wgmma.mma_async.sync.aligned.m64n64k16.f32.bf16.bf16 {%0,%1,%2,%3,%4,%5,%6,%7,%8,%9,%10,%11,%12,%13,%14,%15,%16,%17,%18,%19,%20,%21,%22,%23,%24,%25,%26,%27,%28,%29,%30,%31}, {%32,%33,%34,%35}, db, p, 1, 1, 1;\n}\n"
    : "+f"(d[0]),"+f"(d[1]),"+f"(d[2]),"+f"(d[3]),"+f"(d[4]),"+f"(d[5]),"+f"(d[6]),"+f"(d[7]),"+f"(d[8]),"+f"(d[9]),"+f"(d[10]),"+f"(d[11]),"+f"(d[12]),"+f"(d[13]),"+f"(d[14]),"+f"(d[15]),"+f"(d[16]),"+f"(d[17]),"+f"(d[18]),"+f"(d[19]),"+f"(d[20]),"+f"(d[21]),"+f"(d[22]),"+f"(d[23]),"+f"(d[24]),"+f"(d[25]),"+f"(d[26]),"+f"(d[27]),"+f"(d[28]),"+f"(d[29]),"+f"(d[30]),"+f"(d[31])
    : "r"(a[0]), "r"(a[1]), "r"(a[2]), "r"(a[3]), "r"(descB), "r"(scaleD));
}
__device__ __forceinline__ void wgmma_rs_n128(float (&d)[64], const uint32_t (&a)[4], uint32_t descB, int scaleD) {
  asm volatile("{\n.reg .pred p;\n.reg .b64 db;\nsetp.ne.b32 p, %69, 0;\nmov.b64 db, {%68, 0x40000040};\n"
    "wgmma.mma_async.sync.aligned.m64n128k16.f32.bf16.bf16 {%0,%1,%2,%3,%4,%5,%6,%7,%8,%9,%10,%11,%12,%13,%14,%15,%16,%17,%18,%19,%20,%21,%22,%23,%24,%25,%26,%27,%28,%29,%30,%31,%32,%33,%34,%35,%36,%37,%38,%39,%40,%41,%42,%43,%44,%45,%46,%47,%48,%49,%50,%51,%52,%53,%54,%55,%56,%57,%58,%59,%60,%61,%62,%63}, {%64,%65,%66,%67}, db, p, 1, 1, 1;\n}\n"
    : "+f"(d[0]),"+f"(d[1]),"+f"(d[2]),"+f"(d[3]),"+f"(d[4]),"+f"(d[5]),"+f"(d[6]),"+f"(d[7]),"+f"(d[8]),"+f"(d[9]),"+f"(d[10]),"+f"(d[11]),"+f"(d[12]),"+f"(d[13]),"+f"(d[14]),"+f"(d[15]),"+f"(d[16]),"+f"(d[17]),"+f"(d[18]),"+f"(d[19]),"+f"(d[20]),"+f"(d[21]),"+f"(d[22]),"+f"(d[23]),"+f"(d[24]),"+f"(d[25]),"+f"(d[26]),"+f"(d[27]),"+f"(d[28]),"+f"(d[29]),"+f"(d[30]),"+f"(d[31]),"+f"(d[32]),"+f"(d[33]),"+f"(d[34]),"+f"(d[35]),"+f"(d[36]),"+f"(d[37]),"+f"(d[38]),"+f"(d[39]),"+f"(d[40]),"+f"(d[41]),"+f"(d[42]),"+f"(d[43]),"+f"(d[44]),"+f"(d[45]),"+f"(d[46]),"+f"(d[47]),"+f"(d[48]),"+f"(d[49]),"+f"(d[50]),"+f"(d[51]),"+f"(d[52]),"+f"(d[53]),"+f"(d[54]),"+f"(d[55]),"+f"(d[56]),"+f"(d[57]),"+f"(d[58]),"+f"(d[59]),"+f"(d[60]),"+f"(d[61]),"+f"(d[62]),"+f"(d[63])
    : "r"(a[0]), "r"(a[1]), "r"(a[2]), "r"(a[3]), "r"(descB), "r"(scaleD));
}
__device__ __forceinline__ void wgmma_ss_n72_t11(float (&d)[36], uint32_t descA, uint32_t descB, int scaleD) {
  asm volatile("{\n.reg .pred p;\n.reg .b64 da, db;\nsetp.ne.b32 p, %38, 0;\nmov.b64 da, {%36, 0x40000040};\nmov.b64 db, {%37, 0x40000040};\n"
    "wgmma.mma_async.sync.aligned.m64n72k16.f32.bf16.bf16 {%0,%1,%2,%3,%4,%5,%6,%7,%8,%9,%10,%11,%12,%13,%14,%15,%16,%17,%18,%19,%20,%21,%22,%23,%24,%25,%26,%27,%28,%29,%30,%31,%32,%33,%34,%35}, da, db, p, 1, 1, 1, 1;\n}\n"
    : "+f"(d[0]),"+f"(d[1]),"+f"(d[2]),"+f"(d[3]),"+f"(d[4]),"+f"(d[5]),"+f"(d[6]),"+f"(d[7]),"+f"(d[8]),"+f"(d[9]),"+f"(d[10]),"+f"(d[11]),"+f"(d[12]),"+f"(d[13]),"+f"(d[14]),"+f"(d[15]),"+f"(d[16]),"+f"(d[17]),"+f"(d[18]),"+f"(d[19]),"+f"(d[20]),"+f"(d[21]),"+f"(d[22]),"+f"(d[23]),"+f"(d[24]),"+f"(d[25]),"+f"(d[26]),"+f"(d[27]),"+f"(d[28]),"+f"(d[29]),"+f"(d[30]),"+f"(d[31]),"+f"(d[32]),"+f"(d[33]),"+f"(d[34]),"+f"(d[35])
    : "r"(descA), "r"(descB), "r"(scaleD));
}

#define TSTAMP(i) do {} while (0)
#define TS2(w, i) do {} while (0)

constexpr float LOG2E = 1.4426950408889634f;

__device__ __forceinline__ void feat_exp(const uint32_t (&P)[4], float (&e)[16]) {
  uint32_t a = hmax2(P[0], P[2]), b = hmax2(P[1], P[3]);
  uint32_t mx = hmax2(__byte_perm(a, b, 0x5410), __byte_perm(a, b, 0x7632));
  a = hmin2(P[0], P[2]); b = hmin2(P[1], P[3]);
  uint32_t mn = hmin2(__byte_perm(a, b, 0x5410), __byte_perm(a, b, 0x7632));
  mx = hmax2(mx, __shfl_xor_sync(0xffffffffu, mx, 1));
  mn = hmin2(mn, __shfl_xor_sync(0xffffffffu, mn, 1));
  mx = hmax2(mx, __shfl_xor_sync(0xffffffffu, mx, 2));
  mn = hmin2(mn, __shfl_xor_sync(0xffffffffu, mn, 2));
  float mx0 = -blo(mx) * LOG2E, mx1 = -bhi(mx) * LOG2E, mn0 = blo(mn) * LOG2E, mn1 = bhi(mn) * LOG2E;
  float v[8] = {blo(P[0]), bhi(P[0]), blo(P[1]), bhi(P[1]), blo(P[2]), bhi(P[2]), blo(P[3]), bhi(P[3])};
#pragma unroll
  for (int i = 0; i < 8; i++) {
    bool r1 = (i >> 1) & 1;
    e[i]     = ex2(fmaf(v[i],  LOG2E, r1 ? mx1 : mx0));
    e[8 + i] = ex2(fmaf(v[i], -LOG2E, r1 ? mn1 : mn0));
  }
}

__global__ void __cluster_dims__(2, 1, 1) __launch_bounds__(384, 1)
fused_kernel(const __grid_constant__ Maps maps, const __nv_bfloat16* __restrict__ x, const __nv_bfloat16* __restrict__ wphi,
             const __nv_bfloat16* __restrict__ wo, const __nv_bfloat16* __restrict__ wg_, const __nv_bfloat16* __restrict__ wu_,
             const __nv_bfloat16* __restrict__ wd_, __nv_bfloat16* __restrict__ out) {
  extern __shared__ __align__(1024) unsigned char smem[];
  const uint32_t sb = smem_u32(smem);
  const int tid = threadIdx.x, lane = tid & 31;
  const int warp = __shfl_sync(0xffffffffu, tid >> 5, 0);
  const uint32_t rank = blockIdx.x & 1;
  const int cl = blockIdx.x >> 1;
  int quad, qi;
  if (cl < 4) { quad = 15; qi = cl; }
  else if (cl < 36) { quad = (cl - 4) & 7; qi = (cl - 4) >> 3; }
  else { qi = (cl - 36) / 7; quad = 8 + (cl - 36) - 7 * qi; }
  const int rb = quad, hg = 2 * qi + rank;
  const int rb3 = (quad & ~1) + rank, jf = 4 * (quad & 1) + qi;

  if (warp < 8) {
    asm volatile("setmaxnreg.inc.sync.aligned.u32 240;");
    if (elect_one()) {
#pragma unroll 1
      for (int d = warp; d + 9 < NSTAGE; d += 8) {
        mbar_init(sb + SM_EMPTY + d * 8, st_empty_cnt(d));
        {
          mbar_init(sb + SM_FULL + (d + 9) * 8, 1);
          mbar_expect_tx(sb + SM_FULL + (d + 9) * 8, d + 9 >= ST_D ? 22528 : SLOT);
        }
      }
      asm volatile("fence.mbarrier_init.release.cluster;" ::: "memory");
    }
    __syncwarp();
    bar_sync(0, 352);
    asm volatile("barrier.cluster.arrive.relaxed.aligned;" ::: "memory");
    const int wg = warp >> 2, wq = warp & 3, g = lane >> 2, t = lane & 3;
    const bool lead = (tid & 127) == 0;
    constexpr uint32_t db = (SM_BASE >> 4) | (512u << 16);
    auto release = [&](int d) {
      const int s = d + NSLOT;
      mbar_arrive_cluster(sb + SM_EMPTY + d * 8, s >= ST_GU ? (uint32_t)(s & 1) : rank);
    };
    const uint32_t lrow = (uint32_t)(wq * 16 + (lane & 7) + ((lane >> 3) & 1) * 8) * 128;
    const uint32_t lx = lane & 7, lhi = lane >> 4;
    if (wg == 1) bar_arrive(4, 256);

    float r0, r1;
    uint32_t E[4][8];
    uint32_t T = 0;
    {
      uint32_t A[32][4];
      const int sx = wg ? ST_X1 : ST_X0;
      {
        const uint32_t base = sb + sx * SLOT + lrow, baseb = sb + sx * SLOT + (wq * 16 + lx + lhi * 8) * 128;
        float cs[2][4], c0[2][4], c1[2][4];
#pragma unroll
        for (int i = 0; i < 4; i++) { cs[0][i] = cs[1][i] = c0[0][i] = c0[1][i] = c1[0][i] = c1[1][i] = 0.f; }
#pragma unroll
        for (int c = 0; c < 8; c++) {
          if (c % 3 == 0) mbar_wait(sb + SM_FULL + (sx + c / 3) * 8);
#pragma unroll
          for (int k = 0; k < 4; k++) ldsm4(A[4 * c + k], base + c * 8192 + (((2 * k + lhi) ^ lx) << 4));
#pragma unroll
          for (int k = 0; k < 4; k++) {
            const uint32_t (&f)[4] = A[4 * c + k];
            uint32_t bt[4];
            ldsm4(bt, baseb + c * 8192 + (((2 * k + ((lane >> 3) & 1)) ^ lx) << 4));
            mma16816(cs[k & 1], f, 0x3F803F80u, 0x3F803F80u);
            mma16816(c0[k & 1], f, bt[0], bt[1]);
            mma16816(c1[k & 1], f, bt[2], bt[3]);
          }
        }
        const float s0 = (cs[0][0] + cs[1][0]) * (1.f / 512.f), s1 = (cs[0][2] + cs[1][2]) * (1.f / 512.f);
        asm volatile("barrier.cluster.wait.aligned;" ::: "memory");
        if (lane < 3) release(sx + lane);
        const uint32_t m0 = pack2(s0, s0), m1 = pack2(s1, s1);
        float q0 = (g & 1) ? c0[0][1] + c0[1][1] : c0[0][0] + c0[1][0];
        float q1 = (g & 1) ? c1[0][3] + c1[1][3] : c1[0][2] + c1[1][2];
        q0 = __shfl_sync(0xffffffffu, q0, (lane & ~3) | (g >> 1));
        q1 = __shfl_sync(0xffffffffu, q1, (lane & ~3) | (g >> 1));
        r0 = rsqrtf(fmaxf(q0 * (1.f / 512.f) - s0 * s0, 0.f) + 1e-5f);
        r1 = rsqrtf(fmaxf(q1 * (1.f / 512.f) - s1 * s1, 0.f) + 1e-5f);
#pragma unroll
        for (int ks = 0; ks < 32; ks++) {
          A[ks][0] = hsub2(A[ks][0], m0); A[ks][1] = hsub2(A[ks][1], m1);
          A[ks][2] = hsub2(A[ks][2], m0); A[ks][3] = hsub2(A[ks][3], m1);
        }
      }
      TSTAMP(1);
      const uint32_t wpa = sb + SM_WPHI + ((lane & 7) + ((lane >> 3) & 1) * 8) * 32 + lhi * 16;
      const uint32_t scr = sb + (wg ? (ST_SCR1 % NSLOT) : (ST_SCR0 % NSLOT)) * SLOT;
#pragma unroll 1
      for (int ps = 0; ps < 3; ps++) {
        const int st0 = ps == 0 ? ST_WK : (ps == 1 ? ST_WV : ST_WQ);
        const uint32_t wdesc = DESC((ps == 0 ? ST_WK % NSLOT : (ps == 1 ? ST_WV % NSLOT : ST_WQ % NSLOT)) * SLOT);
        float acc[32];
        bar_sync(4 + wg, 256);
#pragma unroll
        for (int i = 0; i < 3; i++) {
          mbar_wait(sb + SM_FULL + (st0 + i) * 8);
          wg_fence();
#pragma unroll
          for (int kk = 0; kk < (i < 2 ? 12 : 8); kk++)
            wgmma_rs_n64(acc, A[12 * i + kk], wdesc + ((i * SLOT + kk * 2048) >> 4), (i | kk) != 0);
          wg_commit();
          if (i == 1) { wg_wait<1>(); if (lead) release(st0); }
        }
        if (ps == 1 && wg == 0) bar_arrive(5, 256);
        uint32_t a[4][4], b[4][4];
        mbar_wait(sb + SM_MISCB);
        T = (*reinterpret_cast<volatile unsigned*>(smem + SM_EPOCH) & 1) ^ 1;
#pragma unroll
        for (int h = 0; h < 4; h++) ldsm4t(b[h], wpa + h * 512);
        wg_wait<0>();
        if ((tid & 127) < 2) release(st0 + 1 + (tid & 1));
        TSTAMP(2 + 2 * ps);
#pragma unroll
        for (int h = 0; h < 4; h++) {
          a[h][0] = pack2(acc[8 * h + 0] * r0, acc[8 * h + 1] * r0); a[h][1] = pack2(acc[8 * h + 2] * r1, acc[8 * h + 3] * r1);
          a[h][2] = pack2(acc[8 * h + 4] * r0, acc[8 * h + 5] * r0); a[h][3] = pack2(acc[8 * h + 6] * r1, acc[8 * h + 7] * r1);
        }
        if (ps != 1) {
          {
            float pp[4][2][4];
#pragma unroll
            for (int h = 0; h < 4; h++) {
#pragma unroll
              for (int i = 0; i < 4; i++) { pp[h][0][i] = 0.f; pp[h][1][i] = 0.f; }
              mma16816(pp[h][0], a[h], b[h][0], b[h][1]);
              mma16816(pp[h][1], a[h], b[h][2], b[h][3]);
            }
#pragma unroll
            for (int h = 0; h < 4; h++) {
              a[h][0] = pack2(pp[h][0][0], pp[h][0][1]); a[h][1] = pack2(pp[h][0][2], pp[h][0][3]);
              a[h][2] = pack2(pp[h][1][0], pp[h][1][1]); a[h][3] = pack2(pp[h][1][2], pp[h][1][3]);
            }
          }
          if (ps == 0 || wg == 0) bar_arrive(4 + (wg ^ 1), 256);
          if (ps == 0) mbar_wait(sb + SM_EMPTY + (wg ? ST_SCR1 - NSLOT : ST_SCR0 - NSLOT) * 8);
#pragma unroll 1
          for (int hp = 0; hp < 2; hp++) {
            float e[2][16];
            feat_exp(a[0], e[0]);
            feat_exp(a[1], e[1]);
            if (ps == 0) {
#pragma unroll
              for (int h = 0; h < 2; h++) {
                const float (&f)[16] = e[h];
                float sp0 = (f[0] + f[1]) + (f[4] + f[5]), sp1 = (f[2] + f[3]) + (f[6] + f[7]);
                float sn0 = (f[8] + f[9]) + (f[12] + f[13]), sn1 = (f[10] + f[11]) + (f[14] + f[15]);
                sp0 += __shfl_xor_sync(0xffffffffu, sp0, 1); sp1 += __shfl_xor_sync(0xffffffffu, sp1, 1);
                sn0 += __shfl_xor_sync(0xffffffffu, sn0, 1); sn1 += __shfl_xor_sync(0xffffffffu, sn1, 1);
                sp0 += __shfl_xor_sync(0xffffffffu, sp0, 2); sp1 += __shfl_xor_sync(0xffffffffu, sp1, 2);
                sn0 += __shfl_xor_sync(0xffffffffu, sn0, 2); sn1 += __shfl_xor_sync(0xffffffffu, sn1, 2);
                sp0 = rcp(sp0); sp1 = rcp(sp1); sn0 = rcp(sn0); sn1 = rcp(sn1);
                const uint32_t dst = scr + hp * 8192 + lrow;
                stsm4(dst + (((h * 4 + lhi) ^ lx) << 4), pack2(f[0] * sp0, f[1] * sp0), pack2(f[2] * sp1, f[3] * sp1),
                      pack2(f[4] * sp0, f[5] * sp0), pack2(f[6] * sp1, f[7] * sp1));
                stsm4(dst + (((h * 4 + 2 + lhi) ^ lx) << 4), pack2(f[8] * sn0, f[9] * sn0), pack2(f[10] * sn1, f[11] * sn1),
                      pack2(f[12] * sn0, f[13] * sn0), pack2(f[14] * sn1, f[15] * sn1));
              }
            } else {
#pragma unroll
              for (int i = 0; i < 16; i++) {
                A[i >> 2][i & 3] = A[4 + (i >> 2)][i & 3];
                A[4 + (i >> 2)][i & 3] = pack2(e[i >> 3][2 * (i & 7)], e[i >> 3][2 * (i & 7) + 1]);
              }
            }
#pragma unroll
            for (int i = 0; i < 4; i++) { a[0][i] = a[2][i]; a[1][i] = a[3][i]; }
          }
        } else {
#pragma unroll
          for (int h = 0; h < 4; h++) stsm4(scr + 16384 + lrow + (((2 * h + lhi) ^ lx) << 4), a[h][0], a[h][1], a[h][2], a[h][3]);
          fence_async_smem();
          bar_sync(3, 256);
          float kv[36];
          wg_fence();
#pragma unroll
          for (int ks = 0; ks < 8; ks++) {
            const uint32_t sk = (ks < 4 ? (ST_SCR0 % NSLOT) : (ST_SCR1 % NSLOT)) * SLOT + (ks & 3) * 2048;
            const uint32_t dv = (DESC(sk + 16384) & 0xFFFFu) | (((SM_ONES - sk - 16384) >> 4) << 16);
            wgmma_ss_n72_t11(kv, DESC(sk) + wg * 512, dv, ks != 0);
          }
          wg_commit();
          if (wg == 1) bar_arrive(4, 256);
          wg_wait<0>();
          if (lead) { mbar_arrive(sb + SM_EMPTY + ST_SCR0 * 8); mbar_arrive(sb + SM_EMPTY + ST_SCR1 * 8); }
          const int hl = 2 * wg + (wq >> 1), f = (wq & 1) * 16 + g;
          float* kvp = &g_kv[T ^ 1][((hg * 4 + hl) * 32 + f) * 16 + 2 * t];
          float* zp = &g_z[T ^ 1][(hg * 4 + hl) * 32 + f];
          float c[8];
#pragma unroll
          for (int i = 0; i < 8; i++) c[i] = hl >= 2 ? (hl == 3 ? kv[24 + i] : kv[16 + i]) : (hl == 1 ? kv[8 + i] : kv[i]);
#pragma unroll
          for (int n = 0; n < 2; n++) {
            asm volatile("red.relaxed.gpu.global.add.v2.f32 [%0], {%1,%2};" ::"l"(kvp + n * 8), "f"(c[4 * n]), "f"(c[4 * n + 1]) : "memory");
            asm volatile("red.relaxed.gpu.global.add.v2.f32 [%0], {%1,%2};" ::"l"(kvp + n * 8 + 128), "f"(c[4 * n + 2]), "f"(c[4 * n + 3]) : "memory");
          }
          if (t < 2) asm volatile("red.relaxed.gpu.global.add.f32 [%0], %1;" ::"l"(zp + t * 8), "f"(t ? kv[34] : kv[32]) : "memory");
          bar_arrive(6 + wg, 160);
        }
        TSTAMP(3 + 2 * ps);
      }
#pragma unroll
      for (int i = 0; i < 32; i++) E[i >> 3][i & 7] = A[i >> 2][i & 3];
    }
    const int rh = 2 * rb + wg;
#define IDF ((g >> 1) == t ? ((g & 1) ? 0x3F800000u : 0x00003F80u) : 0u)
    const uint4* xb = reinterpret_cast<const uint4*>(smem + 2 * SLOT) + wq * 128 + lane;
    mbar_wait(sb + SM_KVB);
    {
      const int r = tid & 127;
      const float4* src = reinterpret_cast<const float4*>(smem + SM_KV32) + r;
#pragma unroll
      for (int i = 0; i < 4; i++) {
        const float4 a = src[i * 128];
        *reinterpret_cast<uint2*>(smem + SM_KVS + (i * 32 + (r >> 2)) * 48 + (r & 3) * 8) = make_uint2(pack2(a.x, a.y), pack2(a.z, a.w));
      }
      const uint32_t zz = pack2(reinterpret_cast<const float*>(smem + SM_ONES)[r], 1.0f);
      *reinterpret_cast<uint4*>(smem + SM_KVS + r * 48 + 32) = make_uint4(zz, zz, zz, zz);
      bar_sync(1 + wg, 128);
    }
    TSTAMP(8);
    {
      uint4* op = &g_o[rh][hg][wq][0][lane];
      if (wg == 1) bar_sync(5, 256);
#pragma unroll 1
      for (int hp = 0; hp < 2; hp++) {
#pragma unroll
      for (int h = 0; h < 2; h++) {
        uint32_t b0[4], b1[4], b2[4];
        const uint32_t kb = sb + SM_KVS + ((2 * hp + h) * 32 + lane) * 48;
        ldsm4t(b0, kb); ldsm4t(b1, kb + 16); ldsm4t(b2, kb + 32);
        const uint32_t ep[4] = {E[h][0], E[h][1], E[h][2], E[h][3]}, en[4] = {E[h][4], E[h][5], E[h][6], E[h][7]};
        float np0[4] = {0, 0, 0, 0}, np1[4] = {0, 0, 0, 0}, nn0[4] = {0, 0, 0, 0}, nn1[4] = {0, 0, 0, 0}, dp[4] = {0, 0, 0, 0}, dn[4] = {0, 0, 0, 0};
        mma16816(dp, ep, b2[0], b2[1]);  mma16816(dn, en, b2[2], b2[3]);
        mma16816(np0, ep, b0[0], b0[1]); mma16816(nn0, en, b0[2], b0[3]);
        mma16816(np1, ep, b1[0], b1[1]); mma16816(nn1, en, b1[2], b1[3]);
        const float i0 = rcp(fmaf(dp[0], dn[1], fmaf(dn[0], dp[1], 1e-6f * dp[1] * dn[1])));
        const float i1 = rcp(fmaf(dp[2], dn[3], fmaf(dn[2], dp[3], 1e-6f * dp[3] * dn[3])));
        const float cp0 = dn[1] * i0, cn0 = dp[1] * i0, cp1 = dn[3] * i1, cn1 = dp[3] * i1;
        st_rlx4(op + (2 * hp + h) * 32,
                tg(pack2(fmaf(np0[0], cp0, nn0[0] * cn0), fmaf(np0[1], cp0, nn0[1] * cn0)), T),
                pack2(fmaf(np0[2], cp1, nn0[2] * cn1), fmaf(np0[3], cp1, nn0[3] * cn1)),
                pack2(fmaf(np1[0], cp0, nn1[0] * cn0), fmaf(np1[1], cp0, nn1[1] * cn0)),
                pack2(fmaf(np1[2], cp1, nn1[2] * cn1), fmaf(np1[3], cp1, nn1[3] * cn1)));
      }
#pragma unroll
        for (int i = 0; i < 8; i++) { E[0][i] = E[2][i]; E[1][i] = E[3][i]; }
      }
    }
    if (wg == 0) bar_arrive(5, 256);
    TSTAMP(9);

    {
      uint32_t xr[4][4];
      {
        const uint32_t* xp = reinterpret_cast<const uint32_t*>(x + (size_t)(rh * 64 + wq * 16 + g) * 512 + hg * 64 + 2 * t);
#pragma unroll
        for (int i = 0; i < 8; i++) { xr[i >> 1][(i & 1) * 2] = __ldg(xp + 4 * i); xr[i >> 1][(i & 1) * 2 + 1] = __ldg(xp + 8 * 256 + 4 * i); }
      }
      uint32_t A[8][4][4];
      const uint4* op = &g_o[rh][0][wq][0][lane];
      float acc[32];
#pragma unroll
      for (int i = 0; i < 32; i++) acc[i] = 0.f;
      add_frag(acc, xr, IDF);
#pragma unroll
      for (int p = -1; p < 4; p++) {
        if (p < 3) {
          mbar_wait(sb + SM_XF + (wg * 4 + p + 1) * 8);
          if (p == -1) TSTAMP(18);
          get_pair(A[2 * p + 2], A[2 * p + 3], xb + (p + 1) * 1024, op + (p + 1) * 1024, T);
          if (lane == 0) mbar_arrive(sb + SM_XE + (wg * 4 + p + 1) * 8);
        }
        if (p == 0 && wg == 1) bar_sync(4, 256);
        if (p >= 0) {
          if (p != 2) mbar_wait(sb + SM_FULL + (ST_WO + (p + 1) / 2) * 8);
          wg_fence();
#pragma unroll
          for (int c = 2 * p; c < 2 * p + 2; c++)
#pragma unroll
            for (int s = 0; s < 4; s++)
              wgmma_rs_n64(acc, A[c][s], DESC(((ST_WO + c / 3) % NSLOT) * SLOT + ((c % 3) * 4 + s) * 2048), 1);
        }
      }
      wg_commit();
      if (wg == 0) bar_arrive(4, 256);
      wg_wait<0>();
      if ((tid & 127) < 3) release(ST_WO + (tid & 127));
      TSTAMP(10);
      uint4* hp_ = &g_h[rh][hg][wq][0][lane];
      uint32_t hx = T;
#pragma unroll
      for (int s = 0; s < 4; s++) {
        const uint32_t h0 = pack2(acc[8 * s], acc[8 * s + 1]);
        st_rlx4(hp_ + s * 32, tg(h0, T), pack2(acc[8 * s + 2], acc[8 * s + 3]), pack2(acc[8 * s + 4], acc[8 * s + 5]), pack2(acc[8 * s + 6], acc[8 * s + 7]));
        hx |= (h0 & 1u) << (s + 1);
      }
      float s0 = 0.f, s1 = 0.f, q0 = 0.f, q1 = 0.f, q2 = 0.f, q3 = 0.f;
#pragma unroll
      for (int i = 0; i < 8; i++) {
        s0 += acc[4 * i] + acc[4 * i + 1]; s1 += acc[4 * i + 2] + acc[4 * i + 3];
        q0 = fmaf(acc[4 * i], acc[4 * i], q0); q2 = fmaf(acc[4 * i + 1], acc[4 * i + 1], q2);
        q1 = fmaf(acc[4 * i + 2], acc[4 * i + 2], q1); q3 = fmaf(acc[4 * i + 3], acc[4 * i + 3], q3);
      }
      q0 += q2; q1 += q3;
      {
        const bool up = t & 2;
        float s = (up ? s1 : s0) + __shfl_xor_sync(0xffffffffu, up ? s0 : s1, 2);
        float q = (up ? q1 : q0) + __shfl_xor_sync(0xffffffffu, up ? q0 : q1, 2);
        s += __shfl_xor_sync(0xffffffffu, s, 1);
        q += __shfl_xor_sync(0xffffffffu, q, 1);
        if (!(t & 1)) st_rlx2(&g_st[rh][hg][wq * 16 + g + (t >> 1) * 8], tg(__float_as_uint(s), T), __float_as_uint(q));
      }
      st_rlx1(&g_hx[rh][hg][wq][lane], hx);
    }
    TSTAMP(11);

    const int rh3 = 2 * rb3 + wg;
    uint32_t HH[11][4], PH[11][4];
    const uint4* pp = &g_hh[rh3][jf ^ 1][0][wq][lane];
    {
      uint32_t A[8][4][4];
      const uint4* hp_ = &g_h[rh3][0][wq][0][lane];
      uint4* hhp = &g_hh[rh3][jf][0][wq][lane];
      const uint32_t dg = (db & 0xFFFFu) | (256u << 16);
      uint32_t m0, m1;
      mbar_wait(sb + SM_XF + ((2 + wg) * 4) * 8);
      TSTAMP(0);
      {
        const uint2* sp = reinterpret_cast<const uint2*>(smem + SM_KV32 + wg * 4096) + 2 * t * 64 + wq * 16 + g;
        uint2 a0, a1, b0, b1;
        int it = 0;
#pragma unroll 1
        do {
          ld_rlx2(a0.x, a0.y, sp); ld_rlx2(a1.x, a1.y, sp + 64); ld_rlx2(b0.x, b0.y, sp + 8); ld_rlx2(b1.x, b1.y, sp + 72);
          sp = &g_st[rh3][2 * t][wq * 16 + g];
        } while (__any_sync(0xffffffffu, bad4(a0.x, a1.x, b0.x, b1.x, T)) && ++it < (1 << 18));
        float s0 = __uint_as_float(a0.x) + __uint_as_float(a1.x), q0 = __uint_as_float(a0.y) + __uint_as_float(a1.y);
        float s1 = __uint_as_float(b0.x) + __uint_as_float(b1.x), q1 = __uint_as_float(b0.y) + __uint_as_float(b1.y);
        s0 += __shfl_xor_sync(0xffffffffu, s0, 1); s1 += __shfl_xor_sync(0xffffffffu, s1, 1);
        q0 += __shfl_xor_sync(0xffffffffu, q0, 1); q1 += __shfl_xor_sync(0xffffffffu, q1, 1);
        s0 += __shfl_xor_sync(0xffffffffu, s0, 2); s1 += __shfl_xor_sync(0xffffffffu, s1, 2);
        q0 += __shfl_xor_sync(0xffffffffu, q0, 2); q1 += __shfl_xor_sync(0xffffffffu, q1, 2);
        s0 *= (1.f / 512.f); s1 *= (1.f / 512.f);
        r0 = rcp(fmaxf(q0 * (1.f / 512.f) - s0 * s0, 0.f) + 1e-5f);
        r1 = rcp(fmaxf(q1 * (1.f / 512.f) - s1 * s1, 0.f) + 1e-5f);
        m0 = pack2(s0, s0); m1 = pack2(s1, s1);
      }
      TSTAMP(12);
#define UOFF(u) ((((ST_GU + (u) / 3) % NSLOT) * SLOT + ((u) % 3) * 8192) >> 4)
#define UNIT_PRE(u)  do { if ((u) % 3 == 0) mbar_wait(sb + SM_FULL + (ST_GU + (u) / 3) * 8); } while (0)
#define UNIT_POST(u) do { wg_commit(); if ((u) % 3 == 1 && (u) > 3) { wg_wait<2>(); if (lead) release(ST_GU + (u) / 3 - 1); } } while (0)
      float acc[64];
      const int rz = blockIdx.y;
#pragma unroll
      for (int ps = 0; ps < 2; ps++) {
        wg_fence();
#pragma unroll
        for (int k = 0; k < 16; k++) {
          const int u = 16 * ps + k, c = k >> 1;
          if (ps == 0 && (k == 0 || k == 4 || k == 8)) {
#pragma unroll
            for (int p = (k == 0 ? 0 : (k == 4 ? 1 : 3)); p < (k == 0 ? 1 : (k == 4 ? 3 : 4)); p++) {
              if (p > 0) mbar_wait(sb + SM_XF + ((2 + wg) * 4 + p) * 8);
              get_pair(A[2 * p], A[2 * p + 1], xb + p * 1024, hp_ + p * 1024, T);
              if (lane == 0) {
                if (wg == 0) mbar_arrive(sb + SM_XE + (8 + p) * 8);
                else if (p > 0) release(ST_XC + p - 1);
              }
            }
          }
          if (ps == 0 && (k & 1) == 0) {
#pragma unroll
            for (int s = 0; s < 4; s++) {
              A[c][s][0] = hsub2(A[c][s][0], m0); A[c][s][1] = hsub2(A[c][s][1], m1);
              A[c][s][2] = hsub2(A[c][s][2], m0); A[c][s][3] = hsub2(A[c][s][3], m1);
            }
            wg_fence();
          }
          UNIT_PRE(u);
          wgmma_rs_n128(acc, A[c][(k & 1) * 2], dg + UOFF(u), k != 0 ? 1 : (ps ? rz : 0));
          wgmma_rs_n128(acc, A[c][(k & 1) * 2 + 1], dg + UOFF(u) + 128, 1);
          UNIT_POST(u);
          if (ps == 0 && k == 7) TSTAMP(17);
        }
        wg_wait<0>();
        TSTAMP(22 + ps);
#pragma unroll
        for (int s = 0; s < 4; s++) {
          uint32_t (&hh)[4] = HH[4 + s];
          hh[0] = tg(pack2(acc[8 * s + 0] * acc[32 + 8 * s + 0], acc[8 * s + 1] * acc[32 + 8 * s + 1]), T);
          hh[1] = pack2(acc[8 * s + 2] * acc[32 + 8 * s + 2], acc[8 * s + 3] * acc[32 + 8 * s + 3]);
          hh[2] = pack2(acc[8 * s + 4] * acc[32 + 8 * s + 4], acc[8 * s + 5] * acc[32 + 8 * s + 5]);
          hh[3] = pack2(acc[8 * s + 6] * acc[32 + 8 * s + 6], acc[8 * s + 7] * acc[32 + 8 * s + 7]);
          st_rlx4(hhp + (4 * ps + s) * 128, hh[0], hh[1], hh[2], hh[3]);
        }
      }
      {
        float ag[24], au[24];
        const uint32_t* ph7 = reinterpret_cast<const uint32_t*>(&g_hh[rh3][jf ^ 1][7][wq][31]);
        uint32_t hv = 0;
        bar_sync(1 + wg, 128);
        wg_fence();
#pragma unroll
        for (int k = 0; k < 16; k++) {
          const int u = 32 + k, c = k >> 1;
          if (k == 6) {
#pragma unroll
            for (int s = 0; s < 4; s++) ld_rlx4(HH[s], hhp + s * 128);
          }
          if (k == 9) hv = ld_rlx1(ph7);
          if (k == 12) {
            int it = 0;
#pragma unroll 1
            while (((hv ^ T) & 1) && ++it < (1 << 18)) hv = ld_rlx1(ph7);
#pragma unroll
            for (int s = 0; s < 8; s++) ld_rlx4(PH[s], pp + s * 128);
          }
          UNIT_PRE(u);
          wgmma_rs_n48(ag, A[c][(k & 1) * 2], dg + UOFF(u), k != 0);
          wgmma_rs_n48(au, A[c][(k & 1) * 2], dg + UOFF(u) + 256, k != 0);
          wgmma_rs_n48(ag, A[c][(k & 1) * 2 + 1], dg + UOFF(u) + 128, 1);
          wgmma_rs_n48(au, A[c][(k & 1) * 2 + 1], dg + UOFF(u) + 256 + 128, 1);
          UNIT_POST(u);
        }
        wg_wait<0>();
        TSTAMP(13);
#pragma unroll
        for (int s = 0; s < 3; s++) {
          uint32_t (&hh)[4] = HH[8 + s];
          hh[0] = tg(pack2(ag[8 * s + 0] * au[8 * s + 0], ag[8 * s + 1] * au[8 * s + 1]), T);
          hh[1] = pack2(ag[8 * s + 2] * au[8 * s + 2], ag[8 * s + 3] * au[8 * s + 3]);
          hh[2] = pack2(ag[8 * s + 4] * au[8 * s + 4], ag[8 * s + 5] * au[8 * s + 5]);
          hh[3] = pack2(ag[8 * s + 6] * au[8 * s + 6], ag[8 * s + 7] * au[8 * s + 7]);
          st_rlx4(hhp + (8 + s) * 128, hh[0], hh[1], hh[2], hh[3]);
        }
      }
    }
    TSTAMP(14);

    {
      float ac[3][32], acc[32];
      uint32_t hr[4][4];
      const int m = jf >> 1, oc = (jf & 1) * 4 + m;
      const uint32_t* ph10 = reinterpret_cast<const uint32_t*>(&g_hh[rh3][jf ^ 1][10][wq][31]);
      uint32_t hv = 0;
      bar_arrive(8 + wg, 256);
      wg_fence();
#pragma unroll
      for (int k = 0; k < 3; k++) {
        mbar_wait(sb + SM_FULL + (ST_D + k) * 8);
        if (k == 1) hv = ld_rlx1(ph10);
#pragma unroll
        for (int s = 0; s < 11; s++) {
          if (k == 2 && s == 4) {
            int it = 0;
#pragma unroll 1
            while (((hv ^ T) & 1) && ++it < (1 << 18)) hv = ld_rlx1(ph10);
#pragma unroll
            for (int i = 8; i < 11; i++) ld_rlx4(PH[i], pp + i * 128);
          }
          wgmma_rs_n64(ac[k], HH[s], DESC(((ST_D + k) % NSLOT) * SLOT + s * 2048), s != 0);
        }
      }
      wg_commit();
      {
        int it = 0;
#pragma unroll 1
        while (__any_sync(0xffffffffu, bad4(PH[0][0], PH[1][0], PH[2][0], PH[3][0], T) | bad4(PH[4][0], PH[5][0], PH[6][0], PH[7][0], T) |
                                       bad4(PH[8][0], PH[9][0], PH[10][0], T, T))) {
#pragma unroll
          for (int s = 0; s < 11; s++) ld_rlx4(PH[s], pp + s * 128);
          if (++it > (1 << 18)) break;
        }
      }
      TSTAMP(20);
      uint4* outb = &g_part[rh3][(jf & 1) * 4][m][wq][0][lane];
#pragma unroll
      for (int k = 0; k < 4; k++) {
        mbar_wait(sb + SM_FULL + (ST_D + 3 + k) * 8);
        wg_fence();
#pragma unroll
        for (int s = 0; s < 11; s++) {
          if (k < 3) wgmma_rs_n64(ac[k], PH[s], DESC(((ST_D + 3 + k) % NSLOT) * SLOT + s * 2048), 1);
          else wgmma_rs_n64(acc, HH[s], DESC(((ST_D + 6) % NSLOT) * SLOT + s * 2048), s != 0);
        }
        wg_commit();
        if (k > 0) {
          wg_wait<1>();
          const float (&a)[32] = ac[k - 1];
          uint4* p = outb + ((m + k) & 3) * 2048;
#pragma unroll
          for (int s = 0; s < 4; s++)
            st_rlx4(p + s * 32, tg(pack2(a[8 * s + 0], a[8 * s + 1]), T), pack2(a[8 * s + 2], a[8 * s + 3]),
                    pack2(a[8 * s + 4], a[8 * s + 5]), pack2(a[8 * s + 6], a[8 * s + 7]));
        }
      }
      uint32_t in[3][4][4];
      const uint4* inb = &g_part[rh3][oc][0][wq][0][lane];
      const uint32_t* hint = reinterpret_cast<const uint32_t*>(&g_part[rh3][oc][(m - 1 - lane) & 3][wq][3][31]);
      ld_chunk(hr, &g_h[rh3][oc][wq][0][lane]);
      uint32_t hx = ld_rlx1(&g_hx[rh3][oc][wq][lane]);
      hv = ld_rlx1(hint);
      mbar_wait(sb + SM_FULL + (ST_D + 7) * 8);
      wg_fence();
#pragma unroll
      for (int s = 0; s < 11; s++) wgmma_rs_n64(acc, PH[s], DESC(((ST_D + 7) % NSLOT) * SLOT + s * 2048), 1);
      wg_commit();
      {
        int it = 0;
#pragma unroll
        for (int q = 0; q < 3; q++) {
#pragma unroll 1
          while (!((__ballot_sync(0xffffffffu, ((hv ^ T) & 1) == 0) >> q) & 1)) {
            hv = ld_rlx1(hint);
            if (++it > (1 << 18)) break;
          }
          ld_chunk(in[q], inb + ((m - 1 - q) & 3) * 512);
        }
#pragma unroll 1
        while (__any_sync(0xffffffffu, bad4(in[0][0][0], in[0][1][0], in[0][2][0], in[0][3][0], T) | bad4(in[1][0][0], in[1][1][0], in[1][2][0], in[1][3][0], T) |
                                       bad4(in[2][0][0], in[2][1][0], in[2][2][0], in[2][3][0], T) | ((hx ^ T) & 1))) {
#pragma unroll
          for (int q = 0; q < 3; q++) ld_chunk(in[q], inb + ((m - 1 - q) & 3) * 512);
          hx = ld_rlx1(&g_hx[rh3][oc][wq][lane]);
          if (++it > (1 << 18)) break;
        }
      }
      wg_wait<0>();
      TSTAMP(15);
#pragma unroll
      for (int s = 0; s < 4; s++) hr[s][0] = (hr[s][0] & 0xFFFFFFFEu) | ((hx >> (s + 1)) & 1u);
      add_frag(acc, in[0], IDF); add_frag(acc, in[1], IDF); add_frag(acc, in[2], IDF);
#pragma unroll
      for (int i = 0; i < 32; i++) acc[i] *= (i & 2) ? r1 : r0;
      add_frag(acc, hr, IDF);
      bar_sync(9 - wg, 256);
      const uint32_t ob = sb + ((ST_D - 1) % NSLOT) * SLOT + wg * 8192;
#pragma unroll
      for (int s = 0; s < 4; s++)
        stsm4(ob + lrow + (((2 * s + lhi) ^ lx) << 4), pack2(acc[8 * s + 0], acc[8 * s + 1]), pack2(acc[8 * s + 2], acc[8 * s + 3]),
              pack2(acc[8 * s + 4], acc[8 * s + 5]), pack2(acc[8 * s + 6], acc[8 * s + 7]));
      __syncwarp();
      {
        const int row = wq * 16 + (lane >> 3);
        __nv_bfloat16* op = out + (size_t)(rh3 * 64 + row) * 512 + oc * 64 + lx * 8;
#pragma unroll
        for (int i = 0; i < 4; i++) {
          uint4 v;
          asm volatile("ld.shared.v4.b32 {%0,%1,%2,%3}, [%4];" : "=r"(v.x), "=r"(v.y), "=r"(v.z), "=r"(v.w)
                       : "r"(ob + (row + i * 4) * 128 + ((lx ^ (((lane >> 3) + i * 4) & 7)) << 4)) : "memory");
          asm volatile("st.global.v4.b32 [%0], {%1,%2,%3,%4};" ::"l"(op + i * 2048), "r"(v.x), "r"(v.y), "r"(v.z), "r"(v.w) : "memory");
        }
      }
    }
    TSTAMP(16);
    asm volatile("barrier.cluster.arrive.relaxed.aligned;" ::: "memory");
    asm volatile("barrier.cluster.wait.aligned;" ::: "memory");
  } else {
    asm volatile("setmaxnreg.dec.sync.aligned.u32 24;");
    if (elect_one()) {
      if (warp == 8) {
#pragma unroll
        for (int k = 0; k < 9; k++) {
          const int s = k < 3 ? k : (k < 6 ? k + 3 : k - 3);
          const uint32_t bar = sb + SM_FULL + s * 8;
          mbar_init(bar, 1);
          mbar_expect_tx(bar, SLOT);
          if (s >= 3 && s < 6) tma2d(sb + s * SLOT, &maps.w, 512 + hg * 64, (s - 3) * 192, bar);
          else tma3d(sb + s * SLOT, &maps.x, 0, rb * 128 + (s >= 6 ? 64 : 0), 3 * (s % 3), bar);
        }
      } else if (warp == 9) {
        mbar_init(sb + SM_MISCB, 2);
        mbar_init(sb + SM_KVB, 32);
        mbar_expect_tx(sb + SM_MISCB, 2048);
        bulk_g2s(sb + SM_WPHI, wphi + hg * 1024, 2048, sb + SM_MISCB);
      } else if (warp == 10) {
        if ((sb & 0x3FFFF) != SM_BASE) __trap();
#pragma unroll 1
        for (int i = 0; i < 16; i++) {
          mbar_init(sb + SM_XF + i * 8, 1);
          mbar_expect_tx(sb + SM_XF + i * 8, (i == 8 || i == 12) ? 20480 : 16384);
          if (i < 12) mbar_init(sb + SM_XE + i * 8, 4);
        }
      } else {
        *reinterpret_cast<volatile unsigned*>(smem + SM_EPOCH) = atomicAdd(&g_start, 1u) / NCTA;
      }
      asm volatile("fence.mbarrier_init.release.cluster;" ::: "memory");
    }
    __syncwarp();
    if (warp != 11) bar_sync(0, 352);
    asm volatile("barrier.cluster.arrive.relaxed.aligned;" ::: "memory");
    if (warp == 8) {
      asm volatile("barrier.cluster.wait.aligned;" ::: "memory");
      if (elect_one()) {
        const CUtensorMap* mg = jf == 7 ? &maps.g7 : &maps.g;
        const CUtensorMap* mu = jf == 7 ? &maps.u7 : &maps.u;
        asm volatile("prefetch.tensormap [%0];" ::"l"(&maps.wo) : "memory");
        asm volatile("prefetch.tensormap [%0];" ::"l"(mg) : "memory");
        asm volatile("prefetch.tensormap [%0];" ::"l"(mu) : "memory");
        asm volatile("prefetch.tensormap [%0];" ::"l"(&maps.d) : "memory");
#pragma unroll 1
        for (int s = ST_WV; s < ST_XC; s++) {
          if (s == ST_SCR1) continue;
          mbar_wait(sb + SM_EMPTY + (s - 9) * 8);
          const uint32_t dst = sb + (s >= 18 ? s - 18 : s - 9) * SLOT, bar = sb + SM_FULL + s * 8;
          if (s < ST_WO) tma2d(dst, &maps.w, (s < ST_WQ ? 1024 : 0) + hg * 64, (s < ST_WQ ? s - ST_WV : s - ST_WQ) * 192, bar);
          else { mbar_wait(bar - 8); tma2d(dst, &maps.wo, hg * 64, (s - ST_WO) * 192, bar); }
        }
        const int jc = jf == 7 ? 0 : jf;
        int slot = (ST_GU + 1 - rank) % NSLOT;
#pragma unroll 1
        for (int s = ST_GU + 1 - rank; s < NSTAGE; s += 2) {
          mbar_wait(sb + SM_EMPTY + (s - 9) * 8);
          if (s > ST_GU && s < ST_GU + THR) mbar_wait(sb + SM_FULL + (s - 1) * 8);
          const uint32_t dst = sb + slot * SLOT, bar = sb + SM_FULL + s * 8;
          if (s < ST_D) {
#pragma unroll 1
            for (int i = 0; i < 3; i++) {
              const int u = (s - ST_GU) * 3 + i;
              tma3d_mc(dst + i * 8192, mg, (u >> 4) * 64, jc, (u & 15) * 32, bar);
              tma3d_mc(dst + i * 8192 + 4096, mu, (u >> 4) * 64, jc, (u & 15) * 32, bar);
            }
          } else {
            const int i = s - ST_D, k = i < 3 ? i : (i < 6 ? i - 3 : 3), pt = (i >= 3 && i != 6) ? 1 : 0;
            tma2d_mc(dst, &maps.d, ((jf & 1) * 4 + (((jf >> 1) + 1 + k) & 3)) * 64, (jf ^ pt) * 176, bar);
          }
          slot += 2; if (slot >= NSLOT) slot -= NSLOT;
        }
      }
      __syncwarp();
    } else {
      asm volatile("barrier.cluster.wait.aligned;" ::: "memory");
      if (warp == 11) {
#pragma unroll
        for (int i = 0; i < 4; i++)
          reinterpret_cast<uint4*>(smem + SM_ONES)[lane + 32 * i] = make_uint4(0x3F803F80u, 0x3F803F80u, 0x3F803F80u, 0x3F803F80u);
        fence_async_smem();
        __syncwarp();
        if (lane == 0) mbar_arrive(sb + SM_MISCB);
      }
      mbar_wait(sb + SM_MISCB);
      const unsigned epoch = *reinterpret_cast<volatile unsigned*>(smem + SM_EPOCH);
      const uint32_t T = (epoch & 1) ^ 1;
      if (warp == 11) {
        reinterpret_cast<float4*>(&g_kv[T][blockIdx.x * 128])[lane] = make_float4(0.f, 0.f, 0.f, 0.f);
        if (lane < 8) g_z[T][blockIdx.x * 8 + lane] = 0.f;
        mbar_wait(sb + SM_FULL + (ST_WK + 2) * 8);
        if (elect_one()) {
          asm volatile("cp.async.bulk.prefetch.L2.global [%0], 4096;" ::"l"((const char*)wo + blockIdx.x * 4096) : "memory");
          asm volatile("cp.async.bulk.prefetch.L2.global [%0], 11008;" ::"l"((const char*)wg_ + blockIdx.x * 11008) : "memory");
          asm volatile("cp.async.bulk.prefetch.L2.global [%0], 11008;" ::"l"((const char*)wu_ + blockIdx.x * 11008) : "memory");
          asm volatile("cp.async.bulk.prefetch.L2.global [%0], 11008;" ::"l"((const char*)wd_ + blockIdx.x * 11008) : "memory");
          const unsigned target = (epoch + 1) * 32;
          unsigned v; int it = 0;
#pragma unroll 1
          do {
            asm volatile("ld.acquire.gpu.global.u32 %0, [%1];" : "=r"(v) : "l"(&g_kvcnt[hg * 32]) : "memory");
            if (++it > (1 << 18)) break;
          } while ((int)(v - target) < 0);
          TS2(0, 26);
        }
        __syncwarp();
        {
          const char* src = reinterpret_cast<const char*>(&g_kv[T ^ 1][hg * 2048]) + lane * 16;
#pragma unroll 4
          for (int i = 0; i < 16; i++)
            asm volatile("cp.async.cg.shared.global [%0], [%1], 16;" ::"r"(sb + SM_KV32 + lane * 16 + i * 512), "l"(src + i * 512) : "memory");
          asm volatile("cp.async.cg.shared.global [%0], [%1], 16;" ::"r"(sb + SM_ONES + lane * 16), "l"(&g_z[T ^ 1][hg * 128 + lane * 4]) : "memory");
          asm volatile("cp.async.mbarrier.arrive.noinc.shared::cta.b64 [%0];" ::"r"(sb + SM_KVB) : "memory");
        }
      } else {
        const int w = warp - 9;
        st_rlx4(reinterpret_cast<uint4*>(&g_st[2 * rb + w][hg][0]) + lane, T ^ 1, T ^ 1, T ^ 1, T ^ 1);
        if (lane < 8) st_rlx4(&g_o[2 * rb + w][hg][lane >> 1][3][30 + (lane & 1)], T ^ 1, T ^ 1, T ^ 1, T ^ 1);
        st_rlx4(&g_part[2 * rb3 + w][(jf & 1) * 4 + (lane >> 3)][jf >> 1][(lane >> 1) & 3][3][30 + (lane & 1)], T ^ 1, T ^ 1, T ^ 1, T ^ 1);
        if (lane < 16) st_rlx4(&g_hh[2 * rb3 + w][jf][7 + (lane >> 3) * 3][(lane >> 1) & 3][30 + (lane & 1)], T ^ 1, T ^ 1, T ^ 1, T ^ 1);
        bar_sync(6 + w, 160);
        if (elect_one()) {
          asm volatile("fence.release.gpu;" ::: "memory");
          TS2(w, 25);
          asm volatile("red.relaxed.gpu.global.add.u32 [%0], 1;" ::"l"(&g_kvcnt[hg * 32]) : "memory");
        }
        mbar_wait(sb + SM_KVB);
        if (w == 0) { mbar_wait(sb + SM_EMPTY + 11 * 8); mbar_wait(sb + SM_EMPTY + 12 * 8); mbar_wait(sb + SM_EMPTY + 13 * 8); }
#pragma unroll 1
        for (int ph = 0; ph < 2; ph++) {
          const int use = 2 * ph + w, r = ph ? 2 * rb3 + w : 2 * rb + w;
          const uint32_t* pw = ph ? reinterpret_cast<const uint32_t*>(&g_st[r][lane >> 2][(lane & 3) * 16 + 15])
                                  : reinterpret_cast<const uint32_t*>(&g_o[r][lane >> 2][lane & 3][3][31]);
          const char* src = reinterpret_cast<const char*>(ph ? &g_h[r][0][0][0][0] : &g_o[r][0][0][0][0]);
          const uint32_t bf = sb + SM_XF + use * 32, be = sb + SM_XE + (use - 1) * 32;
          if (ph) mbar_wait(sb + SM_XE + w * 32 + 24);
          int it = 0;
#pragma unroll 1
          while (__any_sync(0xffffffffu, (ld_rlx1(pw) ^ T) & 1)) { if (++it > (1 << 18)) break; }
          if (elect_one()) {
            TS2(w, 27 + ph);
            if (use > 0) mbar_wait(be);
            if (ph) bulk_g2s(sb + SM_KV32 + w * 4096, &g_st[r][0][0], 4096, bf);
#pragma unroll
            for (int p = 0; p < 4; p++) {
              if (p > 0 && use > 0) mbar_wait(be + p * 8);
              bulk_g2s(sb + 2 * SLOT + p * 16384, src + p * 16384, 16384, bf + p * 8);
            }
          }
          __syncwarp();
        }
      }
    }
    asm volatile("barrier.cluster.arrive.relaxed.aligned;" ::: "memory");
    asm volatile("barrier.cluster.wait.aligned;" ::: "memory");
  }
}

typedef CUresult (*EncodeFn)(CUtensorMap*, CUtensorMapDataType, cuuint32_t, void*, const cuuint64_t*, const cuuint64_t*,
                             const cuuint32_t*, const cuuint32_t*, CUtensorMapInterleave, CUtensorMapSwizzle,
                             CUtensorMapL2promotion, CUtensorMapFloatOOBfill);

void encode(EncodeFn fn, CUtensorMap* m, const void* base, int rank, const cuuint64_t* dims, const cuuint64_t* strides,
            const cuuint32_t* box) {
  cuuint32_t es[3] = {1, 1, 1};
  fn(m, CU_TENSOR_MAP_DATA_TYPE_BFLOAT16, (cuuint32_t)rank, const_cast<void*>(base), dims, strides, box, es,
     CU_TENSOR_MAP_INTERLEAVE_NONE, CU_TENSOR_MAP_SWIZZLE_128B, CU_TENSOR_MAP_L2_PROMOTION_L2_256B,
     CU_TENSOR_MAP_FLOAT_OOB_FILL_NONE);
}

}

extern "C" void kernel_launch(void* const* d_in, const int* in_sizes, int n_in, void* d_out, int out_size) {
  (void)in_sizes; (void)n_in; (void)out_size;
  const __nv_bfloat16* x    = (const __nv_bfloat16*)d_in[0];
  const __nv_bfloat16* wqkv = (const __nv_bfloat16*)d_in[1];
  const __nv_bfloat16* wphi = (const __nv_bfloat16*)d_in[2];
  const __nv_bfloat16* wo   = (const __nv_bfloat16*)d_in[3];
  const __nv_bfloat16* wg   = (const __nv_bfloat16*)d_in[5];
  const __nv_bfloat16* wu   = (const __nv_bfloat16*)d_in[6];
  const __nv_bfloat16* wd   = (const __nv_bfloat16*)d_in[7];

  static EncodeFn fn = nullptr;
  if (!fn) {
    void* p = nullptr;
    cudaDriverEntryPointQueryResult qr;
    cudaGetDriverEntryPoint("cuTensorMapEncodeTiled", &p, cudaEnableDefault, &qr);
    fn = (EncodeFn)p;
    cudaFuncSetAttribute(fused_kernel, cudaFuncAttributeMaxDynamicSharedMemorySize, SM_TOTAL);
  }
  Maps maps;
  {
    cuuint64_t d[3] = {64, 2048, 8}, s[2] = {1024, 128}; cuuint32_t b[3] = {64, 64, 3};
    encode(fn, &maps.x, x, 3, d, s, b);
  }
  {
    cuuint64_t d[2] = {1536, 512}, s[1] = {3072}; cuuint32_t b[2] = {64, 192};
    encode(fn, &maps.w, wqkv, 2, d, s, b);
  }
  {
    cuuint64_t d[2] = {512, 512}, s[1] = {1024}; cuuint32_t b[2] = {64, 192};
    encode(fn, &maps.wo, wo, 2, d, s, b);
  }
  {
    cuuint64_t d[3] = {176, 7, 512}, d7[3] = {144, 1, 512}, s[2] = {352, 2752}; cuuint32_t b[3] = {64, 1, 32};
    encode(fn, &maps.g, wg, 3, d, s, b);
    encode(fn, &maps.u, wu, 3, d, s, b);
    encode(fn, &maps.g7, wg + 1232, 3, d7, s, b);
    encode(fn, &maps.u7, wu + 1232, 3, d7, s, b);
  }
  {
    cuuint64_t d[2] = {512, 1376}, s[1] = {1024}; cuuint32_t b[2] = {64, 176};
    encode(fn, &maps.d, wd, 2, d, s, b);
  }
  fused_kernel<<<NCTA, 384, SM_TOTAL>>>(maps, x, wphi, wo, wg, wu, wd, (__nv_bfloat16*)d_out);
}
```

```cpp
#include <cuda_runtime.h>
#include <cuda_bf16.h>
#include <cuda.h>
#include <stdint.h>

#define PROF 0

#define SAFE_WAIT 0
#define OPRIO 1
#define THR 6

namespace {

constexpr int NCTA   = 128;
constexpr int SLOT   = 24576;
constexpr int NSLOT  = 9;
constexpr int NSTAGE = 47;

constexpr int ST_X0   = 0;
constexpr int ST_WK   = 3;
constexpr int ST_X1   = 6;
constexpr int ST_SCR0 = 9;
constexpr int ST_WV   = 10;
constexpr int ST_SCR1 = 13;
constexpr int ST_WQ   = 14;
constexpr int ST_WO   = 17;
constexpr int ST_XC   = 20;
constexpr int ST_GU   = 23;
constexpr int ST_D    = 39;

__host__ __device__ constexpr int st_empty_cnt(int d) {
  return ((d < 3 || (d >= 6 && d < 9) || (d >= ST_XC && d < ST_GU)) ? 4 : 2) * (d + 9 >= ST_GU ? 2 : 1);
}

constexpr uint32_t SM_BASE = 1024;
constexpr int SM_ONES = NSLOT * SLOT;
constexpr int SM_WPHI = SM_ONES + 2048;
constexpr int SM_KVS  = SM_WPHI + 2048;
constexpr int SM_KV32 = 4 * SLOT + 16384;
constexpr int SM_BAR  = SM_KVS + 6144;
constexpr int SM_FULL  = SM_BAR;
constexpr int SM_EMPTY = SM_BAR + NSTAGE * 8;
constexpr int SM_MISCB = SM_BAR + 2 * NSTAGE * 8;
constexpr int SM_KVB   = SM_MISCB + 8;
constexpr int SM_EPOCH = SM_KVB + 8;
constexpr int SM_XF    = SM_EPOCH + 8;
constexpr int SM_XE    = SM_XF + 16 * 8;
constexpr int SM_TOTAL = SM_BAR + 1024;

static_assert(SM_TOTAL == 232448 && SM_XE + 12 * 8 <= SM_TOTAL, "smem budget");

struct Maps { CUtensorMap x, w, wo, g, u, g7, u7, d; };

__device__ uint4    g_o[32][8][4][4][32];
__device__ uint4    g_h[32][8][4][4][32];
__device__ uint32_t g_hx[32][8][4][32];
__device__ uint2    g_st[32][8][64];
__device__ uint4    g_hh[32][8][11][4][32];
__device__ uint4    g_part[32][8][4][4][4][32];
__device__ __align__(128) float g_kv[2][8][2048 + 128];
__device__ unsigned g_kvcnt[8 * 32];
__device__ unsigned g_start;

__device__ __forceinline__ uint32_t smem_u32(const void* p) { return (uint32_t)__cvta_generic_to_shared(p); }
__device__ __forceinline__ void mbar_init(uint32_t bar, int cnt) {
  asm volatile("mbarrier.init.shared::cta.b64 [%0], %1;" ::"r"(bar), "r"(cnt) : "memory");
}
__device__ __forceinline__ void mbar_expect_tx(uint32_t bar, uint32_t bytes) {
  asm volatile("mbarrier.arrive.expect_tx.shared::cta.b64 _, [%0], %1;" ::"r"(bar), "r"(bytes) : "memory");
}
__device__ __forceinline__ void mbar_arrive(uint32_t bar) {
  asm volatile("mbarrier.arrive.shared::cta.b64 _, [%0];" ::"r"(bar) : "memory");
}
__device__ __forceinline__ void mbar_arrive_cluster(uint32_t bar, uint32_t rank) {
  asm volatile("{\n.reg .b32 ra;\nmapa.shared::cluster.u32 ra, %0, %1;\n"
               "mbarrier.arrive.shared::cluster.b64 _, [ra];\n}" ::"r"(bar), "r"(rank) : "memory");
}
__device__ __forceinline__ void mbar_wait_p(uint32_t bar, uint32_t parity) {
  asm volatile("{\n.reg .pred p;\nW: mbarrier.try_wait.parity.shared::cta.b64 p, [%0], %1;\n@!p bra W;\n}" ::"r"(bar), "r"(parity) : "memory");
}
__device__ __forceinline__ void mbar_wait(uint32_t bar) { mbar_wait_p(bar, 0); }
__device__ __forceinline__ bool elect_one() {
  uint32_t p;
  asm volatile("{\n.reg .pred P;\nelect.sync _|P, 0xffffffff;\nselp.u32 %0, 1, 0, P;\n}" : "=r"(p));
  return p != 0;
}
__device__ __forceinline__ void bar_sync(int id, int n)   { asm volatile("bar.sync %0, %1;" ::"r"(id), "r"(n) : "memory"); }
__device__ __forceinline__ void bar_arrive(int id, int n) { asm volatile("bar.arrive %0, %1;" ::"r"(id), "r"(n) : "memory"); }
__device__ __forceinline__ void fence_async_smem() { asm volatile("fence.proxy.async.shared::cta;" ::: "memory"); }
__device__ __forceinline__ void wg_fence()  { asm volatile("wgmma.fence.sync.aligned;" ::: "memory"); }
__device__ __forceinline__ void wg_commit() { asm volatile("wgmma.commit_group.sync.aligned;" ::: "memory"); }
template <int N> __device__ __forceinline__ void wg_wait() { asm volatile("wgmma.wait_group.sync.aligned %0;" ::"n"(N) : "memory"); }
#define DESC(off) (db + ((uint32_t)(off) >> 4))
__device__ __forceinline__ void tma2d(uint32_t dst, const CUtensorMap* m, int c0, int c1, uint32_t bar) {
  asm volatile("cp.async.bulk.tensor.2d.shared::cluster.global.mbarrier::complete_tx::bytes [%0], [%1, {%3, %4}], [%2];"
               ::"r"(dst), "l"(m), "r"(bar), "r"(c0), "r"(c1) : "memory");
}
__device__ __forceinline__ void tma2d_mc(uint32_t dst, const CUtensorMap* m, int c0, int c1, uint32_t bar) {
  asm volatile("cp.async.bulk.tensor.2d.shared::cluster.global.mbarrier::complete_tx::bytes.multicast::cluster [%0], [%1, {%3, %4}], [%2], %5;"
               ::"r"(dst), "l"(m), "r"(bar), "r"(c0), "r"(c1), "h"((uint16_t)3) : "memory");
}
__device__ __forceinline__ void tma3d(uint32_t dst, const CUtensorMap* m, int c0, int c1, int c2, uint32_t bar) {
  asm volatile("cp.async.bulk.tensor.3d.shared::cluster.global.mbarrier::complete_tx::bytes [%0], [%1, {%3, %4, %5}], [%2];"
               ::"r"(dst), "l"(m), "r"(bar), "r"(c0), "r"(c1), "r"(c2) : "memory");
}
__device__ __forceinline__ void tma3d_mc(uint32_t dst, const CUtensorMap* m, int c0, int c1, int c2, uint32_t bar) {
  asm volatile("cp.async.bulk.tensor.3d.shared::cluster.global.mbarrier::complete_tx::bytes.multicast::cluster [%0], [%1, {%3, %4, %5}], [%2], %6;"
               ::"r"(dst), "l"(m), "r"(bar), "r"(c0), "r"(c1), "r"(c2), "h"((uint16_t)3) : "memory");
}
__device__ __forceinline__ void ldsm4(uint32_t (&r)[4], uint32_t addr) {
  asm volatile("ldmatrix.sync.aligned.m8n8.x4.shared.b16 {%0,%1,%2,%3}, [%4];"
               : "=r"(r[0]), "=r"(r[1]), "=r"(r[2]), "=r"(r[3]) : "r"(addr) : "memory");
}
__device__ __forceinline__ void ldsm4t(uint32_t (&r)[4], uint32_t addr) {
  asm volatile("ldmatrix.sync.aligned.m8n8.x4.trans.shared.b16 {%0,%1,%2,%3}, [%4];"
               : "=r"(r[0]), "=r"(r[1]), "=r"(r[2]), "=r"(r[3]) : "r"(addr) : "memory");
}
__device__ __forceinline__ void stsm4(uint32_t addr, uint32_t r0, uint32_t r1, uint32_t r2, uint32_t r3) {
  asm volatile("stmatrix.sync.aligned.m8n8.x4.shared.b16 [%0], {%1,%2,%3,%4};"
               ::"r"(addr), "r"(r0), "r"(r1), "r"(r2), "r"(r3) : "memory");
}
__device__ __forceinline__ void mma16816(float (&c)[4], const uint32_t (&a)[4], uint32_t b0, uint32_t b1) {
  asm volatile("mma.sync.aligned.m16n8k16.row.col.f32.bf16.bf16.f32 {%0,%1,%2,%3},{%4,%5,%6,%7},{%8,%9},{%0,%1,%2,%3};"
               : "+f"(c[0]), "+f"(c[1]), "+f"(c[2]), "+f"(c[3])
               : "r"(a[0]), "r"(a[1]), "r"(a[2]), "r"(a[3]), "r"(b0), "r"(b1));
}
__device__ __forceinline__ void add_frag(float (&c)[32], const uint32_t (&a)[4][4], uint32_t id) {
#pragma unroll
  for (int i = 0; i < 8; i++)
    asm volatile("mma.sync.aligned.m16n8k8.row.col.f32.bf16.bf16.f32 {%0,%1,%2,%3},{%4,%5},{%6},{%0,%1,%2,%3};"
                 : "+f"(c[4 * i]), "+f"(c[4 * i + 1]), "+f"(c[4 * i + 2]), "+f"(c[4 * i + 3])
                 : "r"(a[i >> 1][(i & 1) * 2]), "r"(a[i >> 1][(i & 1) * 2 + 1]), "r"(id));
}
__device__ __forceinline__ uint32_t pack2(float lo, float hi) {
  uint32_t r; asm("cvt.rn.bf16x2.f32 %0, %1, %2;" : "=r"(r) : "f"(hi), "f"(lo)); return r;
}
__device__ __forceinline__ float blo(uint32_t w) { return __uint_as_float(w << 16); }
__device__ __forceinline__ float bhi(uint32_t w) { return __uint_as_float(w & 0xFFFF0000u); }
__device__ __forceinline__ uint32_t hsub2(uint32_t a, uint32_t b) { uint32_t r; asm("sub.rn.bf16x2 %0, %1, %2;" : "=r"(r) : "r"(a), "r"(b)); return r; }
__device__ __forceinline__ uint32_t hmax2(uint32_t a, uint32_t b) { uint32_t r; asm("max.bf16x2 %0, %1, %2;" : "=r"(r) : "r"(a), "r"(b)); return r; }
__device__ __forceinline__ uint32_t hmin2(uint32_t a, uint32_t b) { uint32_t r; asm("min.bf16x2 %0, %1, %2;" : "=r"(r) : "r"(a), "r"(b)); return r; }
__device__ __forceinline__ float ex2(float x) { float r; asm("ex2.approx.ftz.f32 %0, %1;" : "=f"(r) : "f"(x)); return r; }
__device__ __forceinline__ float rcp(float x) { float r; asm("rcp.approx.ftz.f32 %0, %1;" : "=f"(r) : "f"(x)); return r; }
__device__ __forceinline__ void ld_rlx4(uint32_t (&r)[4], const uint4* p) {
  asm volatile("{\n.reg .b128 v;\nld.relaxed.gpu.global.b128 v, [%4];\nmov.b128 {%0,%1,%2,%3}, v;\n}"
               : "=r"(r[0]), "=r"(r[1]), "=r"(r[2]), "=r"(r[3]) : "l"(p) : "memory");
}
__device__ __forceinline__ void st_rlx4(uint4* p, uint32_t a, uint32_t b, uint32_t c, uint32_t d) {
  asm volatile("{\n.reg .b128 v;\nmov.b128 v, {%1,%2,%3,%4};\nst.relaxed.gpu.global.b128 [%0], v;\n}"
               ::"l"(p), "r"(a), "r"(b), "r"(c), "r"(d) : "memory");
}
__device__ __forceinline__ void st_rlx2(uint2* p, uint32_t a, uint32_t b) {
  asm volatile("{\n.reg .b64 v;\nmov.b64 v, {%1,%2};\nst.relaxed.gpu.global.b64 [%0], v;\n}" ::"l"(p), "r"(a), "r"(b) : "memory");
}
__device__ __forceinline__ uint32_t ld_rlx1(const uint32_t* p) {
  uint32_t r; asm volatile("ld.relaxed.gpu.global.b32 %0, [%1];" : "=r"(r) : "l"(p) : "memory"); return r;
}
__device__ __forceinline__ void st_rlx1(uint32_t* p, uint32_t a) {
  asm volatile("st.relaxed.gpu.global.b32 [%0], %1;" ::"l"(p), "r"(a) : "memory");
}
__device__ __forceinline__ void ld_rlx2(uint32_t& a, uint32_t& b, const uint2* p) {
  asm volatile("{\n.reg .b64 v;\nld.relaxed.gpu.b64 v, [%2];\nmov.b64 {%0,%1}, v;\n}" : "=r"(a), "=r"(b) : "l"(p) : "memory");
}
__device__ __forceinline__ void bulk_g2s(uint32_t dst, const void* src, uint32_t bytes, uint32_t bar) {
  asm volatile("cp.async.bulk.shared::cluster.global.mbarrier::complete_tx::bytes [%0], [%1], %2, [%3];"
               ::"r"(dst), "l"(src), "r"(bytes), "r"(bar) : "memory");
}
__device__ __forceinline__ uint32_t tg(uint32_t w, uint32_t T) { return (w & 0xFFFFFFFEu) | T; }
__device__ __forceinline__ uint32_t bad4(uint32_t a, uint32_t b, uint32_t c, uint32_t d, uint32_t T) {
  uint32_t u, v;
  asm("lop3.b32 %0, %1, %2, %3, 0x7E;" : "=r"(u) : "r"(a), "r"(b), "r"(T));
  asm("lop3.b32 %0, %1, %2, %3, 0x7E;" : "=r"(v) : "r"(c), "r"(d), "r"(T));
  asm("lop3.b32 %0, %1, %2, 1, 0xA8;" : "=r"(u) : "r"(u), "r"(v));
  return u;
}

__device__ __forceinline__ void ld_chunk(uint32_t (&a)[4][4], const uint4* p) {
#pragma unroll
  for (int s = 0; s < 4; s++) ld_rlx4(a[s], p + s * 32);
}
__device__ __forceinline__ void get_pair(uint32_t (&a)[4][4], uint32_t (&b)[4][4], const uint4* sp, const uint4* gp, uint32_t T) {
  int it = 0;
#pragma unroll 1
  do {
#pragma unroll
    for (int s = 0; s < 8; s++) {
      uint32_t (&r)[4] = s < 4 ? a[s & 3] : b[s & 3];
      asm volatile("{\n.reg .b128 v;\nld.relaxed.gpu.b128 v, [%4];\nmov.b128 {%0,%1,%2,%3}, v;\n}"
                   : "=r"(r[0]), "=r"(r[1]), "=r"(r[2]), "=r"(r[3]) : "l"(sp + (s >> 2) * 512 + (s & 3) * 32) : "memory");
    }
    sp = gp;
  } while (__any_sync(0xffffffffu, bad4(a[0][0], a[1][0], a[2][0], a[3][0], T) | bad4(b[0][0], b[1][0], b[2][0], b[3][0], T)) && ++it < (1 << 18));
}

__device__ __forceinline__ void wgmma_rs_n48(float (&d)[24], const uint32_t (&a)[4], uint32_t descB, int scaleD) {
  asm volatile("{\n.reg .pred p;\n.reg .b64 db;\nsetp.ne.b32 p, %29, 0;\nmov.b64 db, {%28, 0x40000040};\n"
    "wgmma.mma_async.sync.aligned.m64n48k16.f32.bf16.bf16 {%0,%1,%2,%3,%4,%5,%6,%7,%8,%9,%10,%11,%12,%13,%14,%15,%16,%17,%18,%19,%20,%21,%22,%23}, {%24,%25,%26,%27}, db, p, 1, 1, 1;\n}\n"
    : "+f"(d[0]),"+f"(d[1]),"+f"(d[2]),"+f"(d[3]),"+f"(d[4]),"+f"(d[5]),"+f"(d[6]),"+f"(d[7]),"+f"(d[8]),"+f"(d[9]),"+f"(d[10]),"+f"(d[11]),"+f"(d[12]),"+f"(d[13]),"+f"(d[14]),"+f"(d[15]),"+f"(d[16]),"+f"(d[17]),"+f"(d[18]),"+f"(d[19]),"+f"(d[20]),"+f"(d[21]),"+f"(d[22]),"+f"(d[23])
    : "r"(a[0]), "r"(a[1]), "r"(a[2]), "r"(a[3]), "r"(descB), "r"(scaleD));
}
__device__ __forceinline__ void wgmma_rs_n64(float (&d)[32], const uint32_t (&a)[4], uint32_t descB, int scaleD) {
  asm volatile("{\n.reg .pred p;\n.reg .b64 db;\nsetp.ne.b32 p, %37, 0;\nmov.b64 db, {%36, 0x40000040};\n"
    "wgmma.mma_async.sync.aligned.m64n64k16.f32.bf16.bf16 {%0,%1,%2,%3,%4,%5,%6,%7,%8,%9,%10,%11,%12,%13,%14,%15,%16,%17,%18,%19,%20,%21,%22,%23,%24,%25,%26,%27,%28,%29,%30,%31}, {%32,%33,%34,%35}, db, p, 1, 1, 1;\n}\n"
    : "+f"(d[0]),"+f"(d[1]),"+f"(d[2]),"+f"(d[3]),"+f"(d[4]),"+f"(d[5]),"+f"(d[6]),"+f"(d[7]),"+f"(d[8]),"+f"(d[9]),"+f"(d[10]),"+f"(d[11]),"+f"(d[12]),"+f"(d[13]),"+f"(d[14]),"+f"(d[15]),"+f"(d[16]),"+f"(d[17]),"+f"(d[18]),"+f"(d[19]),"+f"(d[20]),"+f"(d[21]),"+f"(d[22]),"+f"(d[23]),"+f"(d[24]),"+f"(d[25]),"+f"(d[26]),"+f"(d[27]),"+f"(d[28]),"+f"(d[29]),"+f"(d[30]),"+f"(d[31])
    : "r"(a[0]), "r"(a[1]), "r"(a[2]), "r"(a[3]), "r"(descB), "r"(scaleD));
}
__device__ __forceinline__ void wgmma_rs_n128(float (&d)[64], const uint32_t (&a)[4], uint32_t descB, int scaleD) {
  asm volatile("{\n.reg .pred p;\n.reg .b64 db;\nsetp.ne.b32 p, %69, 0;\nmov.b64 db, {%68, 0x40000040};\n"
    "wgmma.mma_async.sync.aligned.m64n128k16.f32.bf16.bf16 {%0,%1,%2,%3,%4,%5,%6,%7,%8,%9,%10,%11,%12,%13,%14,%15,%16,%17,%18,%19,%20,%21,%22,%23,%24,%25,%26,%27,%28,%29,%30,%31,%32,%33,%34,%35,%36,%37,%38,%39,%40,%41,%42,%43,%44,%45,%46,%47,%48,%49,%50,%51,%52,%53,%54,%55,%56,%57,%58,%59,%60,%61,%62,%63}, {%64,%65,%66,%67}, db, p, 1, 1, 1;\n}\n"
    : "+f"(d[0]),"+f"(d[1]),"+f"(d[2]),"+f"(d[3]),"+f"(d[4]),"+f"(d[5]),"+f"(d[6]),"+f"(d[7]),"+f"(d[8]),"+f"(d[9]),"+f"(d[10]),"+f"(d[11]),"+f"(d[12]),"+f"(d[13]),"+f"(d[14]),"+f"(d[15]),"+f"(d[16]),"+f"(d[17]),"+f"(d[18]),"+f"(d[19]),"+f"(d[20]),"+f"(d[21]),"+f"(d[22]),"+f"(d[23]),"+f"(d[24]),"+f"(d[25]),"+f"(d[26]),"+f"(d[27]),"+f"(d[28]),"+f"(d[29]),"+f"(d[30]),"+f"(d[31]),"+f"(d[32]),"+f"(d[33]),"+f"(d[34]),"+f"(d[35]),"+f"(d[36]),"+f"(d[37]),"+f"(d[38]),"+f"(d[39]),"+f"(d[40]),"+f"(d[41]),"+f"(d[42]),"+f"(d[43]),"+f"(d[44]),"+f"(d[45]),"+f"(d[46]),"+f"(d[47]),"+f"(d[48]),"+f"(d[49]),"+f"(d[50]),"+f"(d[51]),"+f"(d[52]),"+f"(d[53]),"+f"(d[54]),"+f"(d[55]),"+f"(d[56]),"+f"(d[57]),"+f"(d[58]),"+f"(d[59]),"+f"(d[60]),"+f"(d[61]),"+f"(d[62]),"+f"(d[63])
    : "r"(a[0]), "r"(a[1]), "r"(a[2]), "r"(a[3]), "r"(descB), "r"(scaleD));
}
__device__ __forceinline__ void wgmma_ss_n72_t11(float (&d)[36], uint32_t descA, uint32_t descB, int scaleD) {
  asm volatile("{\n.reg .pred p;\n.reg .b64 da, db;\nsetp.ne.b32 p, %38, 0;\nmov.b64 da, {%36, 0x40000040};\nmov.b64 db, {%37, 0x40000040};\n"
    "wgmma.mma_async.sync.aligned.m64n72k16.f32.bf16.bf16 {%0,%1,%2,%3,%4,%5,%6,%7,%8,%9,%10,%11,%12,%13,%14,%15,%16,%17,%18,%19,%20,%21,%22,%23,%24,%25,%26,%27,%28,%29,%30,%31,%32,%33,%34,%35}, da, db, p, 1, 1, 1, 1;\n}\n"
    : "+f"(d[0]),"+f"(d[1]),"+f"(d[2]),"+f"(d[3]),"+f"(d[4]),"+f"(d[5]),"+f"(d[6]),"+f"(d[7]),"+f"(d[8]),"+f"(d[9]),"+f"(d[10]),"+f"(d[11]),"+f"(d[12]),"+f"(d[13]),"+f"(d[14]),"+f"(d[15]),"+f"(d[16]),"+f"(d[17]),"+f"(d[18]),"+f"(d[19]),"+f"(d[20]),"+f"(d[21]),"+f"(d[22]),"+f"(d[23]),"+f"(d[24]),"+f"(d[25]),"+f"(d[26]),"+f"(d[27]),"+f"(d[28]),"+f"(d[29]),"+f"(d[30]),"+f"(d[31]),"+f"(d[32]),"+f"(d[33]),"+f"(d[34]),"+f"(d[35])
    : "r"(descA), "r"(descB), "r"(scaleD));
}

#define TSTAMP(i) do {} while (0)
#define TS2(w, i) do {} while (0)

constexpr float LOG2E = 1.4426950408889634f;

__device__ __forceinline__ void feat_exp(const uint32_t (&P)[4], float (&e)[16]) {
  uint32_t a = hmax2(P[0], P[2]), b = hmax2(P[1], P[3]);
  uint32_t mx = hmax2(__byte_perm(a, b, 0x5410), __byte_perm(a, b, 0x7632));
  a = hmin2(P[0], P[2]); b = hmin2(P[1], P[3]);
  uint32_t mn = hmin2(__byte_perm(a, b, 0x5410), __byte_perm(a, b, 0x7632));
  mx = hmax2(mx, __shfl_xor_sync(0xffffffffu, mx, 1));
  mn = hmin2(mn, __shfl_xor_sync(0xffffffffu, mn, 1));
  mx = hmax2(mx, __shfl_xor_sync(0xffffffffu, mx, 2));
  mn = hmin2(mn, __shfl_xor_sync(0xffffffffu, mn, 2));
  float mx0 = -blo(mx) * LOG2E, mx1 = -bhi(mx) * LOG2E, mn0 = blo(mn) * LOG2E, mn1 = bhi(mn) * LOG2E;
  float v[8] = {blo(P[0]), bhi(P[0]), blo(P[1]), bhi(P[1]), blo(P[2]), bhi(P[2]), blo(P[3]), bhi(P[3])};
#pragma unroll
  for (int i = 0; i < 8; i++) {
    bool r1 = (i >> 1) & 1;
    e[i]     = ex2(fmaf(v[i],  LOG2E, r1 ? mx1 : mx0));
    e[8 + i] = ex2(fmaf(v[i], -LOG2E, r1 ? mn1 : mn0));
  }
}

__global__ void __cluster_dims__(2, 1, 1) __launch_bounds__(384, 1)
fused_kernel(const __grid_constant__ Maps maps, const __nv_bfloat16* __restrict__ x, const __nv_bfloat16* __restrict__ wphi,
             const __nv_bfloat16* __restrict__ wo, const __nv_bfloat16* __restrict__ wg_, const __nv_bfloat16* __restrict__ wu_,
             const __nv_bfloat16* __restrict__ wd_, __nv_bfloat16* __restrict__ out) {
  extern __shared__ __align__(1024) unsigned char smem[];
  const uint32_t sb = smem_u32(smem);
  const int tid = threadIdx.x, lane = tid & 31;
  const int warp = __shfl_sync(0xffffffffu, tid >> 5, 0);
  const uint32_t rank = blockIdx.x & 1;
  const int cl = blockIdx.x >> 1;
  int quad, qi;
  if (cl < 4) { quad = 15; qi = cl; }
  else if (cl < 36) { quad = (cl - 4) & 7; qi = (cl - 4) >> 3; }
  else { qi = (cl - 36) / 7; quad = 8 + (cl - 36) - 7 * qi; }
  const int rb = quad, hg = 2 * qi + rank;
  const int rb3 = (quad & ~1) + rank, jf = 4 * (quad & 1) + qi;

  if (warp < 8) {
    asm volatile("setmaxnreg.inc.sync.aligned.u32 240;");
    if (elect_one()) {
#pragma unroll 1
      for (int d = warp; d + 9 < NSTAGE; d += 8) {
        mbar_init(sb + SM_EMPTY + d * 8, st_empty_cnt(d));
        {
          mbar_init(sb + SM_FULL + (d + 9) * 8, 1);
          mbar_expect_tx(sb + SM_FULL + (d + 9) * 8, d + 9 >= ST_D ? 22528 : SLOT);
        }
      }
      asm volatile("fence.mbarrier_init.release.cluster;" ::: "memory");
    }
    __syncwarp();
    bar_sync(0, 352);
    asm volatile("barrier.cluster.arrive.relaxed.aligned;" ::: "memory");
    const int wg = warp >> 2, wq = warp & 3, g = lane >> 2, t = lane & 3;
    const bool lead = (tid & 127) == 0;
    constexpr uint32_t db = (SM_BASE >> 4) | (512u << 16);
    auto release = [&](int d) {
      const int s = d + NSLOT;
      mbar_arrive_cluster(sb + SM_EMPTY + d * 8, s >= ST_GU ? (uint32_t)(s & 1) : rank);
    };
    const uint32_t lrow = (uint32_t)(wq * 16 + (lane & 7) + ((lane >> 3) & 1) * 8) * 128;
    const uint32_t lx = lane & 7, lhi = lane >> 4;
    if (wg == 1) bar_arrive(4, 256);

    float r0, r1;
    uint32_t E[4][8];
    uint32_t T = 0;
    {
      uint32_t A[32][4];
      const int sx = wg ? ST_X1 : ST_X0;
      {
        const uint32_t base = sb + sx * SLOT + lrow, baseb = sb + sx * SLOT + (wq * 16 + lx + lhi * 8) * 128;
        float cs[2][4], c0[2][4], c1[2][4];
#pragma unroll
        for (int i = 0; i < 4; i++) { cs[0][i] = cs[1][i] = c0[0][i] = c0[1][i] = c1[0][i] = c1[1][i] = 0.f; }
#pragma unroll
        for (int c = 0; c < 8; c++) {
          if (c % 3 == 0) mbar_wait(sb + SM_FULL + (sx + c / 3) * 8);
#pragma unroll
          for (int k = 0; k < 4; k++) ldsm4(A[4 * c + k], base + c * 8192 + (((2 * k + lhi) ^ lx) << 4));
#pragma unroll
          for (int k = 0; k < 4; k++) {
            const uint32_t (&f)[4] = A[4 * c + k];
            uint32_t bt[4];
            ldsm4(bt, baseb + c * 8192 + (((2 * k + ((lane >> 3) & 1)) ^ lx) << 4));
            mma16816(cs[k & 1], f, 0x3F803F80u, 0x3F803F80u);
            mma16816(c0[k & 1], f, bt[0], bt[1]);
            mma16816(c1[k & 1], f, bt[2], bt[3]);
          }
        }
        const float s0 = (cs[0][0] + cs[1][0]) * (1.f / 512.f), s1 = (cs[0][2] + cs[1][2]) * (1.f / 512.f);
        asm volatile("barrier.cluster.wait.aligned;" ::: "memory");
        if (lane < 3) release(sx + lane);
        const uint32_t m0 = pack2(s0, s0), m1 = pack2(s1, s1);
        float q0 = (g & 1) ? c0[0][1] + c0[1][1] : c0[0][0] + c0[1][0];
        float q1 = (g & 1) ? c1[0][3] + c1[1][3] : c1[0][2] + c1[1][2];
        q0 = __shfl_sync(0xffffffffu, q0, (lane & ~3) | (g >> 1));
        q1 = __shfl_sync(0xffffffffu, q1, (lane & ~3) | (g >> 1));
        r0 = rsqrtf(fmaxf(q0 * (1.f / 512.f) - s0 * s0, 0.f) + 1e-5f);
        r1 = rsqrtf(fmaxf(q1 * (1.f / 512.f) - s1 * s1, 0.f) + 1e-5f);
#pragma unroll
        for (int ks = 0; ks < 32; ks++) {
          A[ks][0] = hsub2(A[ks][0], m0); A[ks][1] = hsub2(A[ks][1], m1);
          A[ks][2] = hsub2(A[ks][2], m0); A[ks][3] = hsub2(A[ks][3], m1);
        }
      }
      TSTAMP(1);
      const uint32_t wpa = sb + SM_WPHI + ((lane & 7) + ((lane >> 3) & 1) * 8) * 32 + lhi * 16;
      const uint32_t scr = sb + (wg ? (ST_SCR1 % NSLOT) : (ST_SCR0 % NSLOT)) * SLOT;
#pragma unroll 1
      for (int ps = 0; ps < 3; ps++) {
        const int st0 = ps == 0 ? ST_WK : (ps == 1 ? ST_WV : ST_WQ);
        const uint32_t wdesc = DESC((ps == 0 ? ST_WK % NSLOT : (ps == 1 ? ST_WV % NSLOT : ST_WQ % NSLOT)) * SLOT);
        float acc[32];
        bar_sync(4 + wg, 256);
#pragma unroll
        for (int i = 0; i < 3; i++) {
          mbar_wait(sb + SM_FULL + (st0 + i) * 8);
          wg_fence();
#pragma unroll
          for (int kk = 0; kk < (i < 2 ? 12 : 8); kk++)
            wgmma_rs_n64(acc, A[12 * i + kk], wdesc + ((i * SLOT + kk * 2048) >> 4), (i | kk) != 0);
          wg_commit();
          if (i == 1) { wg_wait<1>(); if (lead) release(st0); }
        }
        if (ps == 1 && wg == 0) bar_arrive(5, 256);
        uint32_t a[4][4], b[4][4];
        mbar_wait(sb + SM_MISCB);
        T = (*reinterpret_cast<volatile unsigned*>(smem + SM_EPOCH) & 1) ^ 1;
#pragma unroll
        for (int h = 0; h < 4; h++) ldsm4t(b[h], wpa + h * 512);
        wg_wait<0>();
        if ((tid & 127) < 2) release(st0 + 1 + (tid & 1));
        TSTAMP(2 + 2 * ps);
#pragma unroll
        for (int h = 0; h < 4; h++) {
          a[h][0] = pack2(acc[8 * h + 0] * r0, acc[8 * h + 1] * r0); a[h][1] = pack2(acc[8 * h + 2] * r1, acc[8 * h + 3] * r1);
          a[h][2] = pack2(acc[8 * h + 4] * r0, acc[8 * h + 5] * r0); a[h][3] = pack2(acc[8 * h + 6] * r1, acc[8 * h + 7] * r1);
        }
        if (ps != 1) {
          {
            float pp[4][2][4];
#pragma unroll
            for (int h = 0; h < 4; h++) {
#pragma unroll
              for (int i = 0; i < 4; i++) { pp[h][0][i] = 0.f; pp[h][1][i] = 0.f; }
              mma16816(pp[h][0], a[h], b[h][0], b[h][1]);
              mma16816(pp[h][1], a[h], b[h][2], b[h][3]);
            }
#pragma unroll
            for (int h = 0; h < 4; h++) {
              a[h][0] = pack2(pp[h][0][0], pp[h][0][1]); a[h][1] = pack2(pp[h][0][2], pp[h][0][3]);
              a[h][2] = pack2(pp[h][1][0], pp[h][1][1]); a[h][3] = pack2(pp[h][1][2], pp[h][1][3]);
            }
          }
          if (ps == 0 || wg == 0) bar_arrive(4 + (wg ^ 1), 256);
          if (ps == 0) mbar_wait(sb + SM_EMPTY + (wg ? ST_SCR1 - NSLOT : ST_SCR0 - NSLOT) * 8);
#pragma unroll 1
          for (int hp = 0; hp < 2; hp++) {
            float e[2][16];
            feat_exp(a[0], e[0]);
            feat_exp(a[1], e[1]);
            if (ps == 0) {
#pragma unroll
              for (int h = 0; h < 2; h++) {
                const float (&f)[16] = e[h];
                float sp0 = (f[0] + f[1]) + (f[4] + f[5]), sp1 = (f[2] + f[3]) + (f[6] + f[7]);
                float sn0 = (f[8] + f[9]) + (f[12] + f[13]), sn1 = (f[10] + f[11]) + (f[14] + f[15]);
                sp0 += __shfl_xor_sync(0xffffffffu, sp0, 1); sp1 += __shfl_xor_sync(0xffffffffu, sp1, 1);
                sn0 += __shfl_xor_sync(0xffffffffu, sn0, 1); sn1 += __shfl_xor_sync(0xffffffffu, sn1, 1);
                sp0 += __shfl_xor_sync(0xffffffffu, sp0, 2); sp1 += __shfl_xor_sync(0xffffffffu, sp1, 2);
                sn0 += __shfl_xor_sync(0xffffffffu, sn0, 2); sn1 += __shfl_xor_sync(0xffffffffu, sn1, 2);
                sp0 = rcp(sp0); sp1 = rcp(sp1); sn0 = rcp(sn0); sn1 = rcp(sn1);
                const uint32_t dst = scr + hp * 8192 + lrow;
                stsm4(dst + (((h * 4 + lhi) ^ lx) << 4), pack2(f[0] * sp0, f[1] * sp0), pack2(f[2] * sp1, f[3] * sp1),
                      pack2(f[4] * sp0, f[5] * sp0), pack2(f[6] * sp1, f[7] * sp1));
                stsm4(dst + (((h * 4 + 2 + lhi) ^ lx) << 4), pack2(f[8] * sn0, f[9] * sn0), pack2(f[10] * sn1, f[11] * sn1),
                      pack2(f[12] * sn0, f[13] * sn0), pack2(f[14] * sn1, f[15] * sn1));
              }
            } else {
#pragma unroll
              for (int i = 0; i < 16; i++) {
                A[i >> 2][i & 3] = A[4 + (i >> 2)][i & 3];
                A[4 + (i >> 2)][i & 3] = pack2(e[i >> 3][2 * (i & 7)], e[i >> 3][2 * (i & 7) + 1]);
              }
            }
#pragma unroll
            for (int i = 0; i < 4; i++) { a[0][i] = a[2][i]; a[1][i] = a[3][i]; }
          }
        } else {
#pragma unroll
          for (int h = 0; h < 4; h++) stsm4(scr + 16384 + lrow + (((2 * h + lhi) ^ lx) << 4), a[h][0], a[h][1], a[h][2], a[h][3]);
          fence_async_smem();
          bar_sync(3, 256);
          float kv[36];
          wg_fence();
#pragma unroll
          for (int ks = 0; ks < 8; ks++) {
            const uint32_t sk = (ks < 4 ? (ST_SCR0 % NSLOT) : (ST_SCR1 % NSLOT)) * SLOT + (ks & 3) * 2048;
            const uint32_t dv = (DESC(sk + 16384) & 0xFFFFu) | (((SM_ONES - sk - 16384) >> 4) << 16);
            wgmma_ss_n72_t11(kv, DESC(sk) + wg * 512, dv, ks != 0);
          }
          wg_commit();
          if (wg == 1) bar_arrive(4, 256);
          wg_wait<0>();
          if (lead) { mbar_arrive(sb + SM_EMPTY + ST_SCR0 * 8); mbar_arrive(sb + SM_EMPTY + ST_SCR1 * 8); }
          const int hl = 2 * wg + (wq >> 1), f = (wq & 1) * 16 + g;
          float* kvp = reinterpret_cast<float*>(smem + 2 * SLOT) + (hl * 32 + f) * 16 + 2 * t;
          float c[8];
#pragma unroll
          for (int i = 0; i < 8; i++) c[i] = hl >= 2 ? (hl == 3 ? kv[24 + i] : kv[16 + i]) : (hl == 1 ? kv[8 + i] : kv[i]);
#pragma unroll
          for (int n = 0; n < 2; n++) {
            *reinterpret_cast<float2*>(kvp + n * 8) = make_float2(c[4 * n], c[4 * n + 1]);
            *reinterpret_cast<float2*>(kvp + n * 8 + 128) = make_float2(c[4 * n + 2], c[4 * n + 3]);
          }
          if (t < 2) reinterpret_cast<float*>(smem + 2 * SLOT)[2048 + hl * 32 + f + t * 8] = t ? kv[34] : kv[32];
          fence_async_smem();
          bar_arrive(6, 320);
        }
        TSTAMP(3 + 2 * ps);
      }
#pragma unroll
      for (int i = 0; i < 32; i++) E[i >> 3][i & 7] = A[i >> 2][i & 3];
    }
    const int rh = 2 * rb + wg;
#define IDF ((g >> 1) == t ? ((g & 1) ? 0x3F800000u : 0x00003F80u) : 0u)
    const uint4* xb = reinterpret_cast<const uint4*>(smem + 2 * SLOT) + wq * 128 + lane;
    mbar_wait(sb + SM_KVB);
    {
      const int r = tid & 127;
      const float4* src = reinterpret_cast<const float4*>(smem + SM_KV32) + r;
#pragma unroll
      for (int i = 0; i < 4; i++) {
        const float4 a = src[i * 128];
        *reinterpret_cast<uint2*>(smem + SM_KVS + (i * 32 + (r >> 2)) * 48 + (r & 3) * 8) = make_uint2(pack2(a.x, a.y), pack2(a.z, a.w));
      }
      const uint32_t zz = pack2(reinterpret_cast<const float*>(smem + SM_ONES)[r], 1.0f);
      *reinterpret_cast<uint4*>(smem + SM_KVS + r * 48 + 32) = make_uint4(zz, zz, zz, zz);
      bar_sync(1 + wg, 128);
    }
    TSTAMP(8);
    {
      uint4* op = &g_o[rh][hg][wq][0][lane];
      if (wg == 1) bar_sync(5, 256);
#pragma unroll 1
      for (int hp = 0; hp < 2; hp++) {
#pragma unroll
      for (int h = 0; h < 2; h++) {
        uint32_t b0[4], b1[4], b2[4];
        const uint32_t kb = sb + SM_KVS + ((2 * hp + h) * 32 + lane) * 48;
        ldsm4t(b0, kb); ldsm4t(b1, kb + 16); ldsm4t(b2, kb + 32);
        const uint32_t ep[4] = {E[h][0], E[h][1], E[h][2], E[h][3]}, en[4] = {E[h][4], E[h][5], E[h][6], E[h][7]};
        float np0[4] = {0, 0, 0, 0}, np1[4] = {0, 0, 0, 0}, nn0[4] = {0, 0, 0, 0}, nn1[4] = {0, 0, 0, 0}, dp[4] = {0, 0, 0, 0}, dn[4] = {0, 0, 0, 0};
        mma16816(dp, ep, b2[0], b2[1]);  mma16816(dn, en, b2[2], b2[3]);
        mma16816(np0, ep, b0[0], b0[1]); mma16816(nn0, en, b0[2], b0[3]);
        mma16816(np1, ep, b1[0], b1[1]); mma16816(nn1, en, b1[2], b1[3]);
        const float i0 = rcp(fmaf(dp[0], dn[1], fmaf(dn[0], dp[1], 1e-6f * dp[1] * dn[1])));
        const float i1 = rcp(fmaf(dp[2], dn[3], fmaf(dn[2], dp[3], 1e-6f * dp[3] * dn[3])));
        const float cp0 = dn[1] * i0, cn0 = dp[1] * i0, cp1 = dn[3] * i1, cn1 = dp[3] * i1;
        st_rlx4(op + (2 * hp + h) * 32,
                tg(pack2(fmaf(np0[0], cp0, nn0[0] * cn0), fmaf(np0[1], cp0, nn0[1] * cn0)), T),
                pack2(fmaf(np0[2], cp1, nn0[2] * cn1), fmaf(np0[3], cp1, nn0[3] * cn1)),
                pack2(fmaf(np1[0], cp0, nn1[0] * cn0), fmaf(np1[1], cp0, nn1[1] * cn0)),
                pack2(fmaf(np1[2], cp1, nn1[2] * cn1), fmaf(np1[3], cp1, nn1[3] * cn1)));
      }
#pragma unroll
        for (int i = 0; i < 8; i++) { E[0][i] = E[2][i]; E[1][i] = E[3][i]; }
      }
    }
    if (wg == 0) bar_arrive(5, 256);
    TSTAMP(9);

    {
      uint32_t xr[4][4];
      {
        const uint32_t* xp = reinterpret_cast<const uint32_t*>(x + (size_t)(rh * 64 + wq * 16 + g) * 512 + hg * 64 + 2 * t);
#pragma unroll
        for (int i = 0; i < 8; i++) { xr[i >> 1][(i & 1) * 2] = __ldg(xp + 4 * i); xr[i >> 1][(i & 1) * 2 + 1] = __ldg(xp + 8 * 256 + 4 * i); }
      }
      uint32_t A[8][4][4];
      const uint4* op = &g_o[rh][0][wq][0][lane];
      float acc[32];
#pragma unroll
      for (int i = 0; i < 32; i++) acc[i] = 0.f;
      add_frag(acc, xr, IDF);
#pragma unroll
      for (int p = -1; p < 4; p++) {
        if (p < 3) {
          mbar_wait(sb + SM_XF + (wg * 4 + p + 1) * 8);
          if (p == -1) TSTAMP(18);
          get_pair(A[2 * p + 2], A[2 * p + 3], xb + (p + 1) * 1024, op + (p + 1) * 1024, T);
          if (lane == 0) mbar_arrive(sb + SM_XE + (wg * 4 + p + 1) * 8);
        }
        if (p == 0 && wg == 1) bar_sync(4, 256);
        if (p >= 0) {
          if (p != 2) mbar_wait(sb + SM_FULL + (ST_WO + (p + 1) / 2) * 8);
          wg_fence();
#pragma unroll
          for (int c = 2 * p; c < 2 * p + 2; c++)
#pragma unroll
            for (int s = 0; s < 4; s++)
              wgmma_rs_n64(acc, A[c][s], DESC(((ST_WO + c / 3) % NSLOT) * SLOT + ((c % 3) * 4 + s) * 2048), 1);
        }
      }
      wg_commit();
      if (wg == 0) bar_arrive(4, 256);
      wg_wait<0>();
      if ((tid & 127) < 3) release(ST_WO + (tid & 127));
      TSTAMP(10);
      uint4* hp_ = &g_h[rh][hg][wq][0][lane];
      uint32_t hx = T;
#pragma unroll
      for (int s = 0; s < 4; s++) {
        const uint32_t h0 = pack2(acc[8 * s], acc[8 * s + 1]);
        st_rlx4(hp_ + s * 32, tg(h0, T), pack2(acc[8 * s + 2], acc[8 * s + 3]), pack2(acc[8 * s + 4], acc[8 * s + 5]), pack2(acc[8 * s + 6], acc[8 * s + 7]));
        hx |= (h0 & 1u) << (s + 1);
      }
      float s0 = 0.f, s1 = 0.f, q0 = 0.f, q1 = 0.f, q2 = 0.f, q3 = 0.f;
#pragma unroll
      for (int i = 0; i < 8; i++) {
        s0 += acc[4 * i] + acc[4 * i + 1]; s1 += acc[4 * i + 2] + acc[4 * i + 3];
        q0 = fmaf(acc[4 * i], acc[4 * i], q0); q2 = fmaf(acc[4 * i + 1], acc[4 * i + 1], q2);
        q1 = fmaf(acc[4 * i + 2], acc[4 * i + 2], q1); q3 = fmaf(acc[4 * i + 3], acc[4 * i + 3], q3);
      }
      q0 += q2; q1 += q3;
      {
        const bool up = t & 2;
        float s = (up ? s1 : s0) + __shfl_xor_sync(0xffffffffu, up ? s0 : s1, 2);
        float q = (up ? q1 : q0) + __shfl_xor_sync(0xffffffffu, up ? q0 : q1, 2);
        s += __shfl_xor_sync(0xffffffffu, s, 1);
        q += __shfl_xor_sync(0xffffffffu, q, 1);
        if (!(t & 1)) st_rlx2(&g_st[rh][hg][wq * 16 + g + (t >> 1) * 8], tg(__float_as_uint(s), T), __float_as_uint(q));
      }
      st_rlx1(&g_hx[rh][hg][wq][lane], hx);
    }
    TSTAMP(11);

    const int rh3 = 2 * rb3 + wg;
    uint32_t HH[11][4], PH[11][4];
    const uint4* pp = &g_hh[rh3][jf ^ 1][0][wq][lane];
    {
      uint32_t A[8][4][4];
      const uint4* hp_ = &g_h[rh3][0][wq][0][lane];
      uint4* hhp = &g_hh[rh3][jf][0][wq][lane];
      const uint32_t dg = (db & 0xFFFFu) | (256u << 16);
      uint32_t m0, m1;
      mbar_wait(sb + SM_XF + ((2 + wg) * 4) * 8);
      TSTAMP(0);
      {
        const uint2* sp = reinterpret_cast<const uint2*>(smem + SM_KV32 + wg * 4096) + 2 * t * 64 + wq * 16 + g;
        uint2 a0, a1, b0, b1;
        int it = 0;
#pragma unroll 1
        do {
          ld_rlx2(a0.x, a0.y, sp); ld_rlx2(a1.x, a1.y, sp + 64); ld_rlx2(b0.x, b0.y, sp + 8); ld_rlx2(b1.x, b1.y, sp + 72);
          sp = &g_st[rh3][2 * t][wq * 16 + g];
        } while (__any_sync(0xffffffffu, bad4(a0.x, a1.x, b0.x, b1.x, T)) && ++it < (1 << 18));
        float s0 = __uint_as_float(a0.x) + __uint_as_float(a1.x), q0 = __uint_as_float(a0.y) + __uint_as_float(a1.y);
        float s1 = __uint_as_float(b0.x) + __uint_as_float(b1.x), q1 = __uint_as_float(b0.y) + __uint_as_float(b1.y);
        s0 += __shfl_xor_sync(0xffffffffu, s0, 1); s1 += __shfl_xor_sync(0xffffffffu, s1, 1);
        q0 += __shfl_xor_sync(0xffffffffu, q0, 1); q1 += __shfl_xor_sync(0xffffffffu, q1, 1);
        s0 += __shfl_xor_sync(0xffffffffu, s0, 2); s1 += __shfl_xor_sync(0xffffffffu, s1, 2);
        q0 += __shfl_xor_sync(0xffffffffu, q0, 2); q1 += __shfl_xor_sync(0xffffffffu, q1, 2);
        s0 *= (1.f / 512.f); s1 *= (1.f / 512.f);
        r0 = rcp(fmaxf(q0 * (1.f / 512.f) - s0 * s0, 0.f) + 1e-5f);
        r1 = rcp(fmaxf(q1 * (1.f / 512.f) - s1 * s1, 0.f) + 1e-5f);
        m0 = pack2(s0, s0); m1 = pack2(s1, s1);
      }
      TSTAMP(12);
#define UOFF(u) ((((ST_GU + (u) / 3) % NSLOT) * SLOT + ((u) % 3) * 8192) >> 4)
#define UNIT_PRE(u)  do { if ((u) % 3 == 0) mbar_wait(sb + SM_FULL + (ST_GU + (u) / 3) * 8); } while (0)
#define UNIT_POST(u) do { wg_commit(); if ((u) % 3 == 1 && (u) > 3) { wg_wait<2>(); if (lead) release(ST_GU + (u) / 3 - 1); } } while (0)
      float acc[64];
      const int rz = blockIdx.y;
#pragma unroll
      for (int ps = 0; ps < 2; ps++) {
        wg_fence();
#pragma unroll
        for (int k = 0; k < 16; k++) {
          const int u = 16 * ps + k, c = k >> 1;
          if (ps == 0 && (k == 0 || k == 4 || k == 8)) {
#pragma unroll
            for (int p = (k == 0 ? 0 : (k == 4 ? 1 : 3)); p < (k == 0 ? 1 : (k == 4 ? 3 : 4)); p++) {
              if (p > 0) mbar_wait(sb + SM_XF + ((2 + wg) * 4 + p) * 8);
              get_pair(A[2 * p], A[2 * p + 1], xb + p * 1024, hp_ + p * 1024, T);
              if (lane == 0) {
                if (wg == 0) mbar_arrive(sb + SM_XE + (8 + p) * 8);
                else if (p > 0) release(ST_XC + p - 1);
              }
            }
          }
          if (ps == 0 && (k & 1) == 0) {
#pragma unroll
            for (int s = 0; s < 4; s++) {
              A[c][s][0] = hsub2(A[c][s][0], m0); A[c][s][1] = hsub2(A[c][s][1], m1);
              A[c][s][2] = hsub2(A[c][s][2], m0); A[c][s][3] = hsub2(A[c][s][3], m1);
            }
            wg_fence();
          }
          UNIT_PRE(u);
          wgmma_rs_n128(acc, A[c][(k & 1) * 2], dg + UOFF(u), k != 0 ? 1 : (ps ? rz : 0));
          wgmma_rs_n128(acc, A[c][(k & 1) * 2 + 1], dg + UOFF(u) + 128, 1);
          UNIT_POST(u);
          if (ps == 0 && k == 7) TSTAMP(17);
        }
        wg_wait<0>();
        TSTAMP(22 + ps);
#pragma unroll
        for (int s = 0; s < 4; s++) {
          uint32_t (&hh)[4] = HH[4 + s];
          hh[0] = tg(pack2(acc[8 * s + 0] * acc[32 + 8 * s + 0], acc[8 * s + 1] * acc[32 + 8 * s + 1]), T);
          hh[1] = pack2(acc[8 * s + 2] * acc[32 + 8 * s + 2], acc[8 * s + 3] * acc[32 + 8 * s + 3]);
          hh[2] = pack2(acc[8 * s + 4] * acc[32 + 8 * s + 4], acc[8 * s + 5] * acc[32 + 8 * s + 5]);
          hh[3] = pack2(acc[8 * s + 6] * acc[32 + 8 * s + 6], acc[8 * s + 7] * acc[32 + 8 * s + 7]);
          st_rlx4(hhp + (4 * ps + s) * 128, hh[0], hh[1], hh[2], hh[3]);
        }
      }
      {
        float ag[24], au[24];
        const uint32_t* ph7 = reinterpret_cast<const uint32_t*>(&g_hh[rh3][jf ^ 1][7][wq][31]);
        uint32_t hv = 0;
        bar_sync(1 + wg, 128);
        wg_fence();
#pragma unroll
        for (int k = 0; k < 16; k++) {
          const int u = 32 + k, c = k >> 1;
          if (k == 6) {
#pragma unroll
            for (int s = 0; s < 4; s++) ld_rlx4(HH[s], hhp + s * 128);
          }
          if (k == 9) hv = ld_rlx1(ph7);
          if (k == 12) {
            int it = 0;
#pragma unroll 1
            while (((hv ^ T) & 1) && ++it < (1 << 18)) hv = ld_rlx1(ph7);
#pragma unroll
            for (int s = 0; s < 8; s++) ld_rlx4(PH[s], pp + s * 128);
          }
          UNIT_PRE(u);
          wgmma_rs_n48(ag, A[c][(k & 1) * 2], dg + UOFF(u), k != 0);
          wgmma_rs_n48(au, A[c][(k & 1) * 2], dg + UOFF(u) + 256, k != 0);
          wgmma_rs_n48(ag, A[c][(k & 1) * 2 + 1], dg + UOFF(u) + 128, 1);
          wgmma_rs_n48(au, A[c][(k & 1) * 2 + 1], dg + UOFF(u) + 256 + 128, 1);
          UNIT_POST(u);
        }
        wg_wait<0>();
        TSTAMP(13);
#pragma unroll
        for (int s = 0; s < 3; s++) {
          uint32_t (&hh)[4] = HH[8 + s];
          hh[0] = tg(pack2(ag[8 * s + 0] * au[8 * s + 0], ag[8 * s + 1] * au[8 * s + 1]), T);
          hh[1] = pack2(ag[8 * s + 2] * au[8 * s + 2], ag[8 * s + 3] * au[8 * s + 3]);
          hh[2] = pack2(ag[8 * s + 4] * au[8 * s + 4], ag[8 * s + 5] * au[8 * s + 5]);
          hh[3] = pack2(ag[8 * s + 6] * au[8 * s + 6], ag[8 * s + 7] * au[8 * s + 7]);
          st_rlx4(hhp + (8 + s) * 128, hh[0], hh[1], hh[2], hh[3]);
        }
      }
    }
    TSTAMP(14);

    {
      float ac[3][32], acc[32];
      uint32_t hr[4][4];
      const int m = jf >> 1, oc = (jf & 1) * 4 + m;
      const uint32_t* ph10 = reinterpret_cast<const uint32_t*>(&g_hh[rh3][jf ^ 1][10][wq][31]);
      uint32_t hv = 0;
      bar_arrive(8 + wg, 256);
      wg_fence();
#pragma unroll
      for (int k = 0; k < 3; k++) {
        mbar_wait(sb + SM_FULL + (ST_D + k) * 8);
        if (k == 1) hv = ld_rlx1(ph10);
#pragma unroll
        for (int s = 0; s < 11; s++) {
          if (k == 2 && s == 4) {
            int it = 0;
#pragma unroll 1
            while (((hv ^ T) & 1) && ++it < (1 << 18)) hv = ld_rlx1(ph10);
#pragma unroll
            for (int i = 8; i < 11; i++) ld_rlx4(PH[i], pp + i * 128);
          }
          wgmma_rs_n64(ac[k], HH[s], DESC(((ST_D + k) % NSLOT) * SLOT + s * 2048), s != 0);
        }
      }
      wg_commit();
      {
        int it = 0;
#pragma unroll 1
        while (__any_sync(0xffffffffu, bad4(PH[0][0], PH[1][0], PH[2][0], PH[3][0], T) | bad4(PH[4][0], PH[5][0], PH[6][0], PH[7][0], T) |
                                       bad4(PH[8][0], PH[9][0], PH[10][0], T, T))) {
#pragma unroll
          for (int s = 0; s < 11; s++) ld_rlx4(PH[s], pp + s * 128);
          if (++it > (1 << 18)) break;
        }
      }
      TSTAMP(20);
      uint4* outb = &g_part[rh3][(jf & 1) * 4][m][wq][0][lane];
#pragma unroll
      for (int k = 0; k < 4; k++) {
        mbar_wait(sb + SM_FULL + (ST_D + 3 + k) * 8);
        wg_fence();
#pragma unroll
        for (int s = 0; s < 11; s++) {
          if (k < 3) wgmma_rs_n64(ac[k], PH[s], DESC(((ST_D + 3 + k) % NSLOT) * SLOT + s * 2048), 1);
          else wgmma_rs_n64(acc, HH[s], DESC(((ST_D + 6) % NSLOT) * SLOT + s * 2048), s != 0);
        }
        wg_commit();
        if (k > 0) {
          wg_wait<1>();
          const float (&a)[32] = ac[k - 1];
          uint4* p = outb + ((m + k) & 3) * 2048;
#pragma unroll
          for (int s = 0; s < 4; s++)
            st_rlx4(p + s * 32, tg(pack2(a[8 * s + 0], a[8 * s + 1]), T), pack2(a[8 * s + 2], a[8 * s + 3]),
                    pack2(a[8 * s + 4], a[8 * s + 5]), pack2(a[8 * s + 6], a[8 * s + 7]));
        }
      }
      uint32_t in[3][4][4];
      const uint4* inb = &g_part[rh3][oc][0][wq][0][lane];
      const uint32_t* hint = reinterpret_cast<const uint32_t*>(&g_part[rh3][oc][(m - 1 - lane) & 3][wq][3][31]);
      ld_chunk(hr, &g_h[rh3][oc][wq][0][lane]);
      uint32_t hx = ld_rlx1(&g_hx[rh3][oc][wq][lane]);
      hv = ld_rlx1(hint);
      mbar_wait(sb + SM_FULL + (ST_D + 7) * 8);
      wg_fence();
#pragma unroll
      for (int s = 0; s < 11; s++) wgmma_rs_n64(acc, PH[s], DESC(((ST_D + 7) % NSLOT) * SLOT + s * 2048), 1);
      wg_commit();
      {
        int it = 0;
#pragma unroll
        for (int q = 0; q < 3; q++) {
#pragma unroll 1
          while (!((__ballot_sync(0xffffffffu, ((hv ^ T) & 1) == 0) >> q) & 1)) {
            hv = ld_rlx1(hint);
            if (++it > (1 << 18)) break;
          }
          ld_chunk(in[q], inb + ((m - 1 - q) & 3) * 512);
        }
#pragma unroll 1
        while (__any_sync(0xffffffffu, bad4(in[0][0][0], in[0][1][0], in[0][2][0], in[0][3][0], T) | bad4(in[1][0][0], in[1][1][0], in[1][2][0], in[1][3][0], T) |
                                       bad4(in[2][0][0], in[2][1][0], in[2][2][0], in[2][3][0], T) | ((hx ^ T) & 1))) {
#pragma unroll
          for (int q = 0; q < 3; q++) ld_chunk(in[q], inb + ((m - 1 - q) & 3) * 512);
          hx = ld_rlx1(&g_hx[rh3][oc][wq][lane]);
          if (++it > (1 << 18)) break;
        }
      }
      wg_wait<0>();
      TSTAMP(15);
#pragma unroll
      for (int s = 0; s < 4; s++) hr[s][0] = (hr[s][0] & 0xFFFFFFFEu) | ((hx >> (s + 1)) & 1u);
      add_frag(acc, in[0], IDF); add_frag(acc, in[1], IDF); add_frag(acc, in[2], IDF);
#pragma unroll
      for (int i = 0; i < 32; i++) acc[i] *= (i & 2) ? r1 : r0;
      add_frag(acc, hr, IDF);
      bar_sync(9 - wg, 256);
      const uint32_t ob = sb + ((ST_D - 1) % NSLOT) * SLOT + wg * 8192;
#pragma unroll
      for (int s = 0; s < 4; s++)
        stsm4(ob + lrow + (((2 * s + lhi) ^ lx) << 4), pack2(acc[8 * s + 0], acc[8 * s + 1]), pack2(acc[8 * s + 2], acc[8 * s + 3]),
              pack2(acc[8 * s + 4], acc[8 * s + 5]), pack2(acc[8 * s + 6], acc[8 * s + 7]));
      __syncwarp();
      {
        const int row = wq * 16 + (lane >> 3);
        __nv_bfloat16* op = out + (size_t)(rh3 * 64 + row) * 512 + oc * 64 + lx * 8;
#pragma unroll
        for (int i = 0; i < 4; i++) {
          uint4 v;
          asm volatile("ld.shared.v4.b32 {%0,%1,%2,%3}, [%4];" : "=r"(v.x), "=r"(v.y), "=r"(v.z), "=r"(v.w)
                       : "r"(ob + (row + i * 4) * 128 + ((lx ^ (((lane >> 3) + i * 4) & 7)) << 4)) : "memory");
          asm volatile("st.global.v4.b32 [%0], {%1,%2,%3,%4};" ::"l"(op + i * 2048), "r"(v.x), "r"(v.y), "r"(v.z), "r"(v.w) : "memory");
        }
      }
    }
    TSTAMP(16);
    asm volatile("barrier.cluster.arrive.relaxed.aligned;" ::: "memory");
    asm volatile("barrier.cluster.wait.aligned;" ::: "memory");
  } else {
    asm volatile("setmaxnreg.dec.sync.aligned.u32 24;");
    if (elect_one()) {
      if (warp == 8) {
#pragma unroll
        for (int k = 0; k < 9; k++) {
          const int s = k < 3 ? k : (k < 6 ? k + 3 : k - 3);
          const uint32_t bar = sb + SM_FULL + s * 8;
          mbar_init(bar, 1);
          mbar_expect_tx(bar, SLOT);
          if (s >= 3 && s < 6) tma2d(sb + s * SLOT, &maps.w, 512 + hg * 64, (s - 3) * 192, bar);
          else tma3d(sb + s * SLOT, &maps.x, 0, rb * 128 + (s >= 6 ? 64 : 0), 3 * (s % 3), bar);
        }
      } else if (warp == 9) {
        mbar_init(sb + SM_MISCB, 2);
        mbar_init(sb + SM_KVB, 32);
        mbar_expect_tx(sb + SM_MISCB, 2048);
        bulk_g2s(sb + SM_WPHI, wphi + hg * 1024, 2048, sb + SM_MISCB);
      } else if (warp == 10) {
        if ((sb & 0x3FFFF) != SM_BASE) __trap();
#pragma unroll 1
        for (int i = 0; i < 16; i++) {
          mbar_init(sb + SM_XF + i * 8, 1);
          mbar_expect_tx(sb + SM_XF + i * 8, (i == 8 || i == 12) ? 20480 : 16384);
          if (i < 12) mbar_init(sb + SM_XE + i * 8, 4);
        }
      } else {
        *reinterpret_cast<volatile unsigned*>(smem + SM_EPOCH) = atomicAdd(&g_start, 1u) / NCTA;
      }
      asm volatile("fence.mbarrier_init.release.cluster;" ::: "memory");
    }
    __syncwarp();
    if (warp != 11) bar_sync(0, 352);
    asm volatile("barrier.cluster.arrive.relaxed.aligned;" ::: "memory");
    if (warp == 8) {
      asm volatile("barrier.cluster.wait.aligned;" ::: "memory");
      if (elect_one()) {
        const CUtensorMap* mg = jf == 7 ? &maps.g7 : &maps.g;
        const CUtensorMap* mu = jf == 7 ? &maps.u7 : &maps.u;
        asm volatile("prefetch.tensormap [%0];" ::"l"(&maps.wo) : "memory");
        asm volatile("prefetch.tensormap [%0];" ::"l"(mg) : "memory");
        asm volatile("prefetch.tensormap [%0];" ::"l"(mu) : "memory");
        asm volatile("prefetch.tensormap [%0];" ::"l"(&maps.d) : "memory");
#pragma unroll 1
        for (int s = ST_WV; s < ST_XC; s++) {
          if (s == ST_SCR1) continue;
          mbar_wait(sb + SM_EMPTY + (s - 9) * 8);
          const uint32_t dst = sb + (s >= 18 ? s - 18 : s - 9) * SLOT, bar = sb + SM_FULL + s * 8;
          if (s < ST_WO) tma2d(dst, &maps.w, (s < ST_WQ ? 1024 : 0) + hg * 64, (s < ST_WQ ? s - ST_WV : s - ST_WQ) * 192, bar);
          else { mbar_wait(bar - 8); tma2d(dst, &maps.wo, hg * 64, (s - ST_WO) * 192, bar); }
        }
        const int jc = jf == 7 ? 0 : jf;
        int slot = (ST_GU + 1 - rank) % NSLOT;
#pragma unroll 1
        for (int s = ST_GU + 1 - rank; s < NSTAGE; s += 2) {
          mbar_wait(sb + SM_EMPTY + (s - 9) * 8);
          if (s > ST_GU && s < ST_GU + THR) mbar_wait(sb + SM_FULL + (s - 1) * 8);
          const uint32_t dst = sb + slot * SLOT, bar = sb + SM_FULL + s * 8;
          if (s < ST_D) {
#pragma unroll 1
            for (int i = 0; i < 3; i++) {
              const int u = (s - ST_GU) * 3 + i;
              tma3d_mc(dst + i * 8192, mg, (u >> 4) * 64, jc, (u & 15) * 32, bar);
              tma3d_mc(dst + i * 8192 + 4096, mu, (u >> 4) * 64, jc, (u & 15) * 32, bar);
            }
          } else {
            const int i = s - ST_D, k = i < 3 ? i : (i < 6 ? i - 3 : 3), pt = (i >= 3 && i != 6) ? 1 : 0;
            tma2d_mc(dst, &maps.d, ((jf & 1) * 4 + (((jf >> 1) + 1 + k) & 3)) * 64, (jf ^ pt) * 176, bar);
          }
          slot += 2; if (slot >= NSLOT) slot -= NSLOT;
        }
      }
      __syncwarp();
    } else {
      asm volatile("barrier.cluster.wait.aligned;" ::: "memory");
      if (warp == 11) {
#pragma unroll
        for (int i = 0; i < 4; i++)
          reinterpret_cast<uint4*>(smem + SM_ONES)[lane + 32 * i] = make_uint4(0x3F803F80u, 0x3F803F80u, 0x3F803F80u, 0x3F803F80u);
        fence_async_smem();
        __syncwarp();
        if (lane == 0) mbar_arrive(sb + SM_MISCB);
      }
      mbar_wait(sb + SM_MISCB);
      const unsigned epoch = *reinterpret_cast<volatile unsigned*>(smem + SM_EPOCH);
      const uint32_t T = (epoch & 1) ^ 1;
      if (warp == 11) {
        reinterpret_cast<float4*>(&g_kv[T][0][0] + blockIdx.x * 136)[lane] = make_float4(0.f, 0.f, 0.f, 0.f);
        if (lane < 2) reinterpret_cast<float4*>(&g_kv[T][0][0] + blockIdx.x * 136)[32 + lane] = make_float4(0.f, 0.f, 0.f, 0.f);
        mbar_wait(sb + SM_FULL + (ST_WK + 2) * 8);
        if (elect_one()) {
          asm volatile("cp.async.bulk.prefetch.L2.global [%0], 4096;" ::"l"((const char*)wo + blockIdx.x * 4096) : "memory");
          asm volatile("cp.async.bulk.prefetch.L2.global [%0], 11008;" ::"l"((const char*)wg_ + blockIdx.x * 11008) : "memory");
          asm volatile("cp.async.bulk.prefetch.L2.global [%0], 11008;" ::"l"((const char*)wu_ + blockIdx.x * 11008) : "memory");
          asm volatile("cp.async.bulk.prefetch.L2.global [%0], 11008;" ::"l"((const char*)wd_ + blockIdx.x * 11008) : "memory");
          const unsigned target = (epoch + 1) * 16;
          unsigned v; int it = 0;
#pragma unroll 1
          do {
            asm volatile("ld.acquire.gpu.global.u32 %0, [%1];" : "=r"(v) : "l"(&g_kvcnt[hg * 32]) : "memory");
            if (++it > (1 << 18)) break;
          } while ((int)(v - target) < 0);
          TS2(0, 26);
        }
        __syncwarp();
        {
          const char* src = reinterpret_cast<const char*>(&g_kv[T ^ 1][hg][0]) + lane * 16;
#pragma unroll 4
          for (int i = 0; i < 16; i++)
            asm volatile("cp.async.cg.shared.global [%0], [%1], 16;" ::"r"(sb + SM_KV32 + lane * 16 + i * 512), "l"(src + i * 512) : "memory");
          asm volatile("cp.async.cg.shared.global [%0], [%1], 16;" ::"r"(sb + SM_ONES + lane * 16), "l"(src + 8192) : "memory");
          asm volatile("cp.async.mbarrier.arrive.noinc.shared::cta.b64 [%0];" ::"r"(sb + SM_KVB) : "memory");
        }
      } else {
        const int w = warp - 9;
        st_rlx4(reinterpret_cast<uint4*>(&g_st[2 * rb + w][hg][0]) + lane, T ^ 1, T ^ 1, T ^ 1, T ^ 1);
        if (lane < 8) st_rlx4(&g_o[2 * rb + w][hg][lane >> 1][3][30 + (lane & 1)], T ^ 1, T ^ 1, T ^ 1, T ^ 1);
        st_rlx4(&g_part[2 * rb3 + w][(jf & 1) * 4 + (lane >> 3)][jf >> 1][(lane >> 1) & 3][3][30 + (lane & 1)], T ^ 1, T ^ 1, T ^ 1, T ^ 1);
        if (lane < 16) st_rlx4(&g_hh[2 * rb3 + w][jf][7 + (lane >> 3) * 3][(lane >> 1) & 3][30 + (lane & 1)], T ^ 1, T ^ 1, T ^ 1, T ^ 1);
        bar_sync(6, 320);
        if (w == 0 && elect_one()) {
          asm volatile("cp.reduce.async.bulk.global.shared::cta.bulk_group.add.f32 [%0], [%1], 8704;"
                       ::"l"(&g_kv[T ^ 1][hg][0]), "r"(sb + 2 * SLOT) : "memory");
          asm volatile("cp.async.bulk.commit_group;" ::: "memory");
          asm volatile("cp.async.bulk.wait_group 0;" ::: "memory");
          TS2(1, 25);
          asm volatile("fence.proxy.async.global;" ::: "memory");
          asm volatile("fence.release.gpu;" ::: "memory");
          TS2(0, 25);
          asm volatile("red.relaxed.gpu.global.add.u32 [%0], 1;" ::"l"(&g_kvcnt[hg * 32]) : "memory");
        }
        __syncwarp();
        mbar_wait(sb + SM_KVB);
        if (w == 0) { mbar_wait(sb + SM_EMPTY + 11 * 8); mbar_wait(sb + SM_EMPTY + 12 * 8); mbar_wait(sb + SM_EMPTY + 13 * 8); }
#pragma unroll 1
        for (int ph = 0; ph < 2; ph++) {
          const int use = 2 * ph + w, r = ph ? 2 * rb3 + w : 2 * rb + w;
          const uint32_t* pw = ph ? reinterpret_cast<const uint32_t*>(&g_st[r][lane >> 2][(lane & 3) * 16 + 15])
                                  : reinterpret_cast<const uint32_t*>(&g_o[r][lane >> 2][lane & 3][3][31]);
          const char* src = reinterpret_cast<const char*>(ph ? &g_h[r][0][0][0][0] : &g_o[r][0][0][0][0]);
          const uint32_t bf = sb + SM_XF + use * 32, be = sb + SM_XE + (use - 1) * 32;
          if (ph) mbar_wait(sb + SM_XE + w * 32 + 24);
          int it = 0;
#pragma unroll 1
          while (__any_sync(0xffffffffu, (ld_rlx1(pw) ^ T) & 1)) { if (++it > (1 << 18)) break; }
          if (elect_one()) {
            TS2(w, 27 + ph);
            if (use > 0) mbar_wait(be);
            if (ph) bulk_g2s(sb + SM_KV32 + w * 4096, &g_st[r][0][0], 4096, bf);
#pragma unroll
            for (int p = 0; p < 4; p++) {
              if (p > 0 && use > 0) mbar_wait(be + p * 8);
              bulk_g2s(sb + 2 * SLOT + p * 16384, src + p * 16384, 16384, bf + p * 8);
            }
          }
          __syncwarp();
        }
      }
    }
    asm volatile("barrier.cluster.arrive.relaxed.aligned;" ::: "memory");
    asm volatile("barrier.cluster.wait.aligned;" ::: "memory");
  }
}

typedef CUresult (*EncodeFn)(CUtensorMap*, CUtensorMapDataType, cuuint32_t, void*, const cuuint64_t*, const cuuint64_t*,
                             const cuuint32_t*, const cuuint32_t*, CUtensorMapInterleave, CUtensorMapSwizzle,
                             CUtensorMapL2promotion, CUtensorMapFloatOOBfill);

void encode(EncodeFn fn, CUtensorMap* m, const void* base, int rank, const cuuint64_t* dims, const cuuint64_t* strides,
            const cuuint32_t* box) {
  cuuint32_t es[3] = {1, 1, 1};
  fn(m, CU_TENSOR_MAP_DATA_TYPE_BFLOAT16, (cuuint32_t)rank, const_cast<void*>(base), dims, strides, box, es,
     CU_TENSOR_MAP_INTERLEAVE_NONE, CU_TENSOR_MAP_SWIZZLE_128B, CU_TENSOR_MAP_L2_PROMOTION_L2_256B,
     CU_TENSOR_MAP_FLOAT_OOB_FILL_NONE);
}

}

extern "C" void kernel_launch(void* const* d_in, const int* in_sizes, int n_in, void* d_out, int out_size) {
  (void)in_sizes; (void)n_in; (void)out_size;
  const __nv_bfloat16* x    = (const __nv_bfloat16*)d_in[0];
  const __nv_bfloat16* wqkv = (const __nv_bfloat16*)d_in[1];
  const __nv_bfloat16* wphi = (const __nv_bfloat16*)d_in[2];
  const __nv_bfloat16* wo   = (const __nv_bfloat16*)d_in[3];
  const __nv_bfloat16* wg   = (const __nv_bfloat16*)d_in[5];
  const __nv_bfloat16* wu   = (const __nv_bfloat16*)d_in[6];
  const __nv_bfloat16* wd   = (const __nv_bfloat16*)d_in[7];

  static EncodeFn fn = nullptr;
  if (!fn) {
    void* p = nullptr;
    cudaDriverEntryPointQueryResult qr;
    cudaGetDriverEntryPoint("cuTensorMapEncodeTiled", &p, cudaEnableDefault, &qr);
    fn = (EncodeFn)p;
    cudaFuncSetAttribute(fused_kernel, cudaFuncAttributeMaxDynamicSharedMemorySize, SM_TOTAL);
  }
  Maps maps;
  {
    cuuint64_t d[3] = {64, 2048, 8}, s[2] = {1024, 128}; cuuint32_t b[3] = {64, 64, 3};
    encode(fn, &maps.x, x, 3, d, s, b);
  }
  {
    cuuint64_t d[2] = {1536, 512}, s[1] = {3072}; cuuint32_t b[2] = {64, 192};
    encode(fn, &maps.w, wqkv, 2, d, s, b);
  }
  {
    cuuint64_t d[2] = {512, 512}, s[1] = {1024}; cuuint32_t b[2] = {64, 192};
    encode(fn, &maps.wo, wo, 2, d, s, b);
  }
  {
    cuuint64_t d[3] = {176, 7, 512}, d7[3] = {144, 1, 512}, s[2] = {352, 2752}; cuuint32_t b[3] = {64, 1, 32};
    encode(fn, &maps.g, wg, 3, d, s, b);
    encode(fn, &maps.u, wu, 3, d, s, b);
    encode(fn, &maps.g7, wg + 1232, 3, d7, s, b);
    encode(fn, &maps.u7, wu + 1232, 3, d7, s, b);
  }
  {
    cuuint64_t d[2] = {512, 1376}, s[1] = {1024}; cuuint32_t b[2] = {64, 176};
    encode(fn, &maps.d, wd, 2, d, s, b);
  }
  fused_kernel<<<NCTA, 384, SM_TOTAL>>>(maps, x, wphi, wo, wg, wu, wd, (__nv_bfloat16*)d_out);
}
```

```cpp
#include <cuda_runtime.h>
#include <cuda_bf16.h>
#include <cuda.h>
#include <stdint.h>

#define PROF 0

#define SAFE_WAIT 0
#define OPRIO 1
#define THR 6

namespace {

constexpr int NCTA   = 128;
constexpr int SLOT   = 24576;
constexpr int NSLOT  = 9;
constexpr int NSTAGE = 47;

constexpr int ST_X0   = 0;
constexpr int ST_WK   = 3;
constexpr int ST_X1   = 6;
constexpr int ST_SCR0 = 9;
constexpr int ST_WV   = 10;
constexpr int ST_SCR1 = 13;
constexpr int ST_WQ   = 14;
constexpr int ST_WO   = 17;
constexpr int ST_XC   = 20;
constexpr int ST_GU   = 23;
constexpr int ST_D    = 39;

__host__ __device__ constexpr int st_empty_cnt(int d) {
  return ((d < 3 || (d >= 6 && d < 9) || (d >= ST_XC && d < ST_GU)) ? 4 : 2) * (d + 9 >= ST_GU ? 2 : 1);
}

constexpr uint32_t SM_BASE = 1024;
constexpr int SM_ONES = NSLOT * SLOT;
constexpr int SM_WPHI = SM_ONES + 2048;
constexpr int SM_KVS  = SM_WPHI + 2048;
constexpr int SM_KV32 = 4 * SLOT + 16384;
constexpr int SM_BAR  = SM_KVS + 6144;
constexpr int SM_FULL  = SM_BAR;
constexpr int SM_EMPTY = SM_BAR + NSTAGE * 8;
constexpr int SM_MISCB = SM_BAR + 2 * NSTAGE * 8;
constexpr int SM_KVB   = SM_MISCB + 8;
constexpr int SM_EPOCH = SM_KVB + 8;
constexpr int SM_XF    = SM_EPOCH + 8;
constexpr int SM_XE    = SM_XF + 16 * 8;
constexpr int SM_TOTAL = SM_BAR + 1024;

static_assert(SM_TOTAL == 232448 && SM_XE + 12 * 8 <= SM_TOTAL, "smem budget");

struct Maps { CUtensorMap x, w, wo, g, u, g7, u7, d; };

__device__ uint4    g_o[32][8][4][4][32];
__device__ uint4    g_h[32][8][4][4][32];
__device__ uint32_t g_hx[32][8][4][32];
__device__ uint2    g_st[32][8][64];
__device__ uint4    g_hh[32][8][11][4][32];
__device__ uint4    g_part[32][8][4][4][4][32];
__device__ __align__(128) float g_kv[8][2048 + 128];
__device__ unsigned g_kvcnt[8 * 32];
__device__ unsigned g_start;

__device__ __forceinline__ uint32_t smem_u32(const void* p) { return (uint32_t)__cvta_generic_to_shared(p); }
__device__ __forceinline__ void mbar_init(uint32_t bar, int cnt) {
  asm volatile("mbarrier.init.shared::cta.b64 [%0], %1;" ::"r"(bar), "r"(cnt) : "memory");
}
__device__ __forceinline__ void mbar_expect_tx(uint32_t bar, uint32_t bytes) {
  asm volatile("mbarrier.arrive.expect_tx.shared::cta.b64 _, [%0], %1;" ::"r"(bar), "r"(bytes) : "memory");
}
__device__ __forceinline__ void mbar_arrive(uint32_t bar) {
  asm volatile("mbarrier.arrive.shared::cta.b64 _, [%0];" ::"r"(bar) : "memory");
}
__device__ __forceinline__ void mbar_arrive_cluster(uint32_t bar, uint32_t rank) {
  asm volatile("{\n.reg .b32 ra;\nmapa.shared::cluster.u32 ra, %0, %1;\n"
               "mbarrier.arrive.shared::cluster.b64 _, [ra];\n}" ::"r"(bar), "r"(rank) : "memory");
}
__device__ __forceinline__ void mbar_wait_p(uint32_t bar, uint32_t parity) {
  asm volatile("{\n.reg .pred p;\nW: mbarrier.try_wait.parity.shared::cta.b64 p, [%0], %1;\n@!p bra W;\n}" ::"r"(bar), "r"(parity) : "memory");
}
__device__ __forceinline__ void mbar_wait(uint32_t bar) { mbar_wait_p(bar, 0); }
__device__ __forceinline__ bool elect_one() {
  uint32_t p;
  asm volatile("{\n.reg .pred P;\nelect.sync _|P, 0xffffffff;\nselp.u32 %0, 1, 0, P;\n}" : "=r"(p));
  return p != 0;
}
__device__ __forceinline__ void bar_sync(int id, int n)   { asm volatile("bar.sync %0, %1;" ::"r"(id), "r"(n) : "memory"); }
__device__ __forceinline__ void bar_arrive(int id, int n) { asm volatile("bar.arrive %0, %1;" ::"r"(id), "r"(n) : "memory"); }
__device__ __forceinline__ void fence_async_smem() { asm volatile("fence.proxy.async.shared::cta;" ::: "memory"); }
__device__ __forceinline__ void wg_fence()  { asm volatile("wgmma.fence.sync.aligned;" ::: "memory"); }
__device__ __forceinline__ void wg_commit() { asm volatile("wgmma.commit_group.sync.aligned;" ::: "memory"); }
template <int N> __device__ __forceinline__ void wg_wait() { asm volatile("wgmma.wait_group.sync.aligned %0;" ::"n"(N) : "memory"); }
#define DESC(off) (db + ((uint32_t)(off) >> 4))
__device__ __forceinline__ void tma2d(uint32_t dst, const CUtensorMap* m, int c0, int c1, uint32_t bar) {
  asm volatile("cp.async.bulk.tensor.2d.shared::cluster.global.mbarrier::complete_tx::bytes [%0], [%1, {%3, %4}], [%2];"
               ::"r"(dst), "l"(m), "r"(bar), "r"(c0), "r"(c1) : "memory");
}
__device__ __forceinline__ void tma2d_mc(uint32_t dst, const CUtensorMap* m, int c0, int c1, uint32_t bar) {
  asm volatile("cp.async.bulk.tensor.2d.shared::cluster.global.mbarrier::complete_tx::bytes.multicast::cluster [%0], [%1, {%3, %4}], [%2], %5;"
               ::"r"(dst), "l"(m), "r"(bar), "r"(c0), "r"(c1), "h"((uint16_t)3) : "memory");
}
__device__ __forceinline__ void tma3d(uint32_t dst, const CUtensorMap* m, int c0, int c1, int c2, uint32_t bar) {
  asm volatile("cp.async.bulk.tensor.3d.shared::cluster.global.mbarrier::complete_tx::bytes [%0], [%1, {%3, %4, %5}], [%2];"
               ::"r"(dst), "l"(m), "r"(bar), "r"(c0), "r"(c1), "r"(c2) : "memory");
}
__device__ __forceinline__ void tma3d_mc(uint32_t dst, const CUtensorMap* m, int c0, int c1, int c2, uint32_t bar) {
  asm volatile("cp.async.bulk.tensor.3d.shared::cluster.global.mbarrier::complete_tx::bytes.multicast::cluster [%0], [%1, {%3, %4, %5}], [%2], %6;"
               ::"r"(dst), "l"(m), "r"(bar), "r"(c0), "r"(c1), "r"(c2), "h"((uint16_t)3) : "memory");
}
__device__ __forceinline__ void ldsm4(uint32_t (&r)[4], uint32_t addr) {
  asm volatile("ldmatrix.sync.aligned.m8n8.x4.shared.b16 {%0,%1,%2,%3}, [%4];"
               : "=r"(r[0]), "=r"(r[1]), "=r"(r[2]), "=r"(r[3]) : "r"(addr) : "memory");
}
__device__ __forceinline__ void ldsm4t(uint32_t (&r)[4], uint32_t addr) {
  asm volatile("ldmatrix.sync.aligned.m8n8.x4.trans.shared.b16 {%0,%1,%2,%3}, [%4];"
               : "=r"(r[0]), "=r"(r[1]), "=r"(r[2]), "=r"(r[3]) : "r"(addr) : "memory");
}
__device__ __forceinline__ void stsm4(uint32_t addr, uint32_t r0, uint32_t r1, uint32_t r2, uint32_t r3) {
  asm volatile("stmatrix.sync.aligned.m8n8.x4.shared.b16 [%0], {%1,%2,%3,%4};"
               ::"r"(addr), "r"(r0), "r"(r1), "r"(r2), "r"(r3) : "memory");
}
__device__ __forceinline__ void mma16816(float (&c)[4], const uint32_t (&a)[4], uint32_t b0, uint32_t b1) {
  asm volatile("mma.sync.aligned.m16n8k16.row.col.f32.bf16.bf16.f32 {%0,%1,%2,%3},{%4,%5,%6,%7},{%8,%9},{%0,%1,%2,%3};"
               : "+f"(c[0]), "+f"(c[1]), "+f"(c[2]), "+f"(c[3])
               : "r"(a[0]), "r"(a[1]), "r"(a[2]), "r"(a[3]), "r"(b0), "r"(b1));
}
__device__ __forceinline__ void add_frag(float (&c)[32], const uint32_t (&a)[4][4], uint32_t id) {
#pragma unroll
  for (int i = 0; i < 8; i++)
    asm volatile("mma.sync.aligned.m16n8k8.row.col.f32.bf16.bf16.f32 {%0,%1,%2,%3},{%4,%5},{%6},{%0,%1,%2,%3};"
                 : "+f"(c[4 * i]), "+f"(c[4 * i + 1]), "+f"(c[4 * i + 2]), "+f"(c[4 * i + 3])
                 : "r"(a[i >> 1][(i & 1) * 2]), "r"(a[i >> 1][(i & 1) * 2 + 1]), "r"(id));
}
__device__ __forceinline__ uint32_t pack2(float lo, float hi) {
  uint32_t r; asm("cvt.rn.bf16x2.f32 %0, %1, %2;" : "=r"(r) : "f"(hi), "f"(lo)); return r;
}
__device__ __forceinline__ float blo(uint32_t w) { return __uint_as_float(w << 16); }
__device__ __forceinline__ float bhi(uint32_t w) { return __uint_as_float(w & 0xFFFF0000u); }
__device__ __forceinline__ uint32_t hsub2(uint32_t a, uint32_t b) { uint32_t r; asm("sub.rn.bf16x2 %0, %1, %2;" : "=r"(r) : "r"(a), "r"(b)); return r; }
__device__ __forceinline__ uint32_t hmax2(uint32_t a, uint32_t b) { uint32_t r; asm("max.bf16x2 %0, %1, %2;" : "=r"(r) : "r"(a), "r"(b)); return r; }
__device__ __forceinline__ uint32_t hmin2(uint32_t a, uint32_t b) { uint32_t r; asm("min.bf16x2 %0, %1, %2;" : "=r"(r) : "r"(a), "r"(b)); return r; }
__device__ __forceinline__ float ex2(float x) { float r; asm("ex2.approx.ftz.f32 %0, %1;" : "=f"(r) : "f"(x)); return r; }
__device__ __forceinline__ float rcp(float x) { float r; asm("rcp.approx.ftz.f32 %0, %1;" : "=f"(r) : "f"(x)); return r; }
__device__ __forceinline__ void ld_rlx4(uint32_t (&r)[4], const uint4* p) {
  asm volatile("{\n.reg .b128 v;\nld.relaxed.gpu.global.b128 v, [%4];\nmov.b128 {%0,%1,%2,%3}, v;\n}"
               : "=r"(r[0]), "=r"(r[1]), "=r"(r[2]), "=r"(r[3]) : "l"(p) : "memory");
}
__device__ __forceinline__ void st_rlx4(uint4* p, uint32_t a, uint32_t b, uint32_t c, uint32_t d) {
  asm volatile("{\n.reg .b128 v;\nmov.b128 v, {%1,%2,%3,%4};\nst.relaxed.gpu.global.b128 [%0], v;\n}"
               ::"l"(p), "r"(a), "r"(b), "r"(c), "r"(d) : "memory");
}
__device__ __forceinline__ void st_rlx2(uint2* p, uint32_t a, uint32_t b) {
  asm volatile("{\n.reg .b64 v;\nmov.b64 v, {%1,%2};\nst.relaxed.gpu.global.b64 [%0], v;\n}" ::"l"(p), "r"(a), "r"(b) : "memory");
}
__device__ __forceinline__ uint32_t ld_rlx1(const uint32_t* p) {
  uint32_t r; asm volatile("ld.relaxed.gpu.global.b32 %0, [%1];" : "=r"(r) : "l"(p) : "memory"); return r;
}
__device__ __forceinline__ void st_rlx1(uint32_t* p, uint32_t a) {
  asm volatile("st.relaxed.gpu.global.b32 [%0], %1;" ::"l"(p), "r"(a) : "memory");
}
__device__ __forceinline__ void ld_rlx2(uint32_t& a, uint32_t& b, const uint2* p) {
  asm volatile("{\n.reg .b64 v;\nld.relaxed.gpu.b64 v, [%2];\nmov.b64 {%0,%1}, v;\n}" : "=r"(a), "=r"(b) : "l"(p) : "memory");
}
__device__ __forceinline__ void bulk_g2s(uint32_t dst, const void* src, uint32_t bytes, uint32_t bar) {
  asm volatile("cp.async.bulk.shared::cluster.global.mbarrier::complete_tx::bytes [%0], [%1], %2, [%3];"
               ::"r"(dst), "l"(src), "r"(bytes), "r"(bar) : "memory");
}
__device__ __forceinline__ uint32_t tg(uint32_t w, uint32_t T) { return (w & 0xFFFFFFFEu) | T; }
__device__ __forceinline__ uint32_t bad4(uint32_t a, uint32_t b, uint32_t c, uint32_t d, uint32_t T) {
  uint32_t u, v;
  asm("lop3.b32 %0, %1, %2, %3, 0x7E;" : "=r"(u) : "r"(a), "r"(b), "r"(T));
  asm("lop3.b32 %0, %1, %2, %3, 0x7E;" : "=r"(v) : "r"(c), "r"(d), "r"(T));
  asm("lop3.b32 %0, %1, %2, 1, 0xA8;" : "=r"(u) : "r"(u), "r"(v));
  return u;
}

__device__ __forceinline__ void ld_chunk(uint32_t (&a)[4][4], const uint4* p) {
#pragma unroll
  for (int s = 0; s < 4; s++) ld_rlx4(a[s], p + s * 32);
}
__device__ __forceinline__ void get_pair(uint32_t (&a)[4][4], uint32_t (&b)[4][4], const uint4* sp, const uint4* gp, uint32_t T) {
  int it = 0;
#pragma unroll 1
  do {
#pragma unroll
    for (int s = 0; s < 8; s++) {
      uint32_t (&r)[4] = s < 4 ? a[s & 3] : b[s & 3];
      asm volatile("{\n.reg .b128 v;\nld.relaxed.gpu.b128 v, [%4];\nmov.b128 {%0,%1,%2,%3}, v;\n}"
                   : "=r"(r[0]), "=r"(r[1]), "=r"(r[2]), "=r"(r[3]) : "l"(sp + (s >> 2) * 512 + (s & 3) * 32) : "memory");
    }
    sp = gp;
  } while (__any_sync(0xffffffffu, bad4(a[0][0], a[1][0], a[2][0], a[3][0], T) | bad4(b[0][0], b[1][0], b[2][0], b[3][0], T)) && ++it < (1 << 18));
}

__device__ __forceinline__ void wgmma_rs_n48(float (&d)[24], const uint32_t (&a)[4], uint32_t descB, int scaleD) {
  asm volatile("{\n.reg .pred p;\n.reg .b64 db;\nsetp.ne.b32 p, %29, 0;\nmov.b64 db, {%28, 0x40000040};\n"
    "wgmma.mma_async.sync.aligned.m64n48k16.f32.bf16.bf16 {%0,%1,%2,%3,%4,%5,%6,%7,%8,%9,%10,%11,%12,%13,%14,%15,%16,%17,%18,%19,%20,%21,%22,%23}, {%24,%25,%26,%27}, db, p, 1, 1, 1;\n}\n"
    : "+f"(d[0]),"+f"(d[1]),"+f"(d[2]),"+f"(d[3]),"+f"(d[4]),"+f"(d[5]),"+f"(d[6]),"+f"(d[7]),"+f"(d[8]),"+f"(d[9]),"+f"(d[10]),"+f"(d[11]),"+f"(d[12]),"+f"(d[13]),"+f"(d[14]),"+f"(d[15]),"+f"(d[16]),"+f"(d[17]),"+f"(d[18]),"+f"(d[19]),"+f"(d[20]),"+f"(d[21]),"+f"(d[22]),"+f"(d[23])
    : "r"(a[0]), "r"(a[1]), "r"(a[2]), "r"(a[3]), "r"(descB), "r"(scaleD));
}
__device__ __forceinline__ void wgmma_rs_n64(float (&d)[32], const uint32_t (&a)[4], uint32_t descB, int scaleD) {
  asm volatile("{\n.reg .pred p;\n.reg .b64 db;\nsetp.ne.b32 p, %37, 0;\nmov.b64 db, {%36, 0x40000040};\n"
    "wgmma.mma_async.sync.aligned.m64n64k16.f32.bf16.bf16 {%0,%1,%2,%3,%4,%5,%6,%7,%8,%9,%10,%11,%12,%13,%14,%15,%16,%17,%18,%19,%20,%21,%22,%23,%24,%25,%26,%27,%28,%29,%30,%31}, {%32,%33,%34,%35}, db, p, 1, 1, 1;\n}\n"
    : "+f"(d[0]),"+f"(d[1]),"+f"(d[2]),"+f"(d[3]),"+f"(d[4]),"+f"(d[5]),"+f"(d[6]),"+f"(d[7]),"+f"(d[8]),"+f"(d[9]),"+f"(d[10]),"+f"(d[11]),"+f"(d[12]),"+f"(d[13]),"+f"(d[14]),"+f"(d[15]),"+f"(d[16]),"+f"(d[17]),"+f"(d[18]),"+f"(d[19]),"+f"(d[20]),"+f"(d[21]),"+f"(d[22]),"+f"(d[23]),"+f"(d[24]),"+f"(d[25]),"+f"(d[26]),"+f"(d[27]),"+f"(d[28]),"+f"(d[29]),"+f"(d[30]),"+f"(d[31])
    : "r"(a[0]), "r"(a[1]), "r"(a[2]), "r"(a[3]), "r"(descB), "r"(scaleD));
}
__device__ __forceinline__ void wgmma_rs_n128(float (&d)[64], const uint32_t (&a)[4], uint32_t descB, int scaleD) {
  asm volatile("{\n.reg .pred p;\n.reg .b64 db;\nsetp.ne.b32 p, %69, 0;\nmov.b64 db, {%68, 0x40000040};\n"
    "wgmma.mma_async.sync.aligned.m64n128k16.f32.bf16.bf16 {%0,%1,%2,%3,%4,%5,%6,%7,%8,%9,%10,%11,%12,%13,%14,%15,%16,%17,%18,%19,%20,%21,%22,%23,%24,%25,%26,%27,%28,%29,%30,%31,%32,%33,%34,%35,%36,%37,%38,%39,%40,%41,%42,%43,%44,%45,%46,%47,%48,%49,%50,%51,%52,%53,%54,%55,%56,%57,%58,%59,%60,%61,%62,%63}, {%64,%65,%66,%67}, db, p, 1, 1, 1;\n}\n"
    : "+f"(d[0]),"+f"(d[1]),"+f"(d[2]),"+f"(d[3]),"+f"(d[4]),"+f"(d[5]),"+f"(d[6]),"+f"(d[7]),"+f"(d[8]),"+f"(d[9]),"+f"(d[10]),"+f"(d[11]),"+f"(d[12]),"+f"(d[13]),"+f"(d[14]),"+f"(d[15]),"+f"(d[16]),"+f"(d[17]),"+f"(d[18]),"+f"(d[19]),"+f"(d[20]),"+f"(d[21]),"+f"(d[22]),"+f"(d[23]),"+f"(d[24]),"+f"(d[25]),"+f"(d[26]),"+f"(d[27]),"+f"(d[28]),"+f"(d[29]),"+f"(d[30]),"+f"(d[31]),"+f"(d[32]),"+f"(d[33]),"+f"(d[34]),"+f"(d[35]),"+f"(d[36]),"+f"(d[37]),"+f"(d[38]),"+f"(d[39]),"+f"(d[40]),"+f"(d[41]),"+f"(d[42]),"+f"(d[43]),"+f"(d[44]),"+f"(d[45]),"+f"(d[46]),"+f"(d[47]),"+f"(d[48]),"+f"(d[49]),"+f"(d[50]),"+f"(d[51]),"+f"(d[52]),"+f"(d[53]),"+f"(d[54]),"+f"(d[55]),"+f"(d[56]),"+f"(d[57]),"+f"(d[58]),"+f"(d[59]),"+f"(d[60]),"+f"(d[61]),"+f"(d[62]),"+f"(d[63])
    : "r"(a[0]), "r"(a[1]), "r"(a[2]), "r"(a[3]), "r"(descB), "r"(scaleD));
}
__device__ __forceinline__ void wgmma_ss_n72_t11(float (&d)[36], uint32_t descA, uint32_t descB, int scaleD) {
  asm volatile("{\n.reg .pred p;\n.reg .b64 da, db;\nsetp.ne.b32 p, %38, 0;\nmov.b64 da, {%36, 0x40000040};\nmov.b64 db, {%37, 0x40000040};\n"
    "wgmma.mma_async.sync.aligned.m64n72k16.f32.bf16.bf16 {%0,%1,%2,%3,%4,%5,%6,%7,%8,%9,%10,%11,%12,%13,%14,%15,%16,%17,%18,%19,%20,%21,%22,%23,%24,%25,%26,%27,%28,%29,%30,%31,%32,%33,%34,%35}, da, db, p, 1, 1, 1, 1;\n}\n"
    : "+f"(d[0]),"+f"(d[1]),"+f"(d[2]),"+f"(d[3]),"+f"(d[4]),"+f"(d[5]),"+f"(d[6]),"+f"(d[7]),"+f"(d[8]),"+f"(d[9]),"+f"(d[10]),"+f"(d[11]),"+f"(d[12]),"+f"(d[13]),"+f"(d[14]),"+f"(d[15]),"+f"(d[16]),"+f"(d[17]),"+f"(d[18]),"+f"(d[19]),"+f"(d[20]),"+f"(d[21]),"+f"(d[22]),"+f"(d[23]),"+f"(d[24]),"+f"(d[25]),"+f"(d[26]),"+f"(d[27]),"+f"(d[28]),"+f"(d[29]),"+f"(d[30]),"+f"(d[31]),"+f"(d[32]),"+f"(d[33]),"+f"(d[34]),"+f"(d[35])
    : "r"(descA), "r"(descB), "r"(scaleD));
}

#define TSTAMP(i) do {} while (0)
#define TS2(w, i) do {} while (0)

constexpr float LOG2E = 1.4426950408889634f;

__device__ __forceinline__ void feat_exp(const uint32_t (&P)[4], float (&e)[16]) {
  uint32_t a = hmax2(P[0], P[2]), b = hmax2(P[1], P[3]);
  uint32_t mx = hmax2(__byte_perm(a, b, 0x5410), __byte_perm(a, b, 0x7632));
  a = hmin2(P[0], P[2]); b = hmin2(P[1], P[3]);
  uint32_t mn = hmin2(__byte_perm(a, b, 0x5410), __byte_perm(a, b, 0x7632));
  mx = hmax2(mx, __shfl_xor_sync(0xffffffffu, mx, 1));
  mn = hmin2(mn, __shfl_xor_sync(0xffffffffu, mn, 1));
  mx = hmax2(mx, __shfl_xor_sync(0xffffffffu, mx, 2));
  mn = hmin2(mn, __shfl_xor_sync(0xffffffffu, mn, 2));
  float mx0 = -blo(mx) * LOG2E, mx1 = -bhi(mx) * LOG2E, mn0 = blo(mn) * LOG2E, mn1 = bhi(mn) * LOG2E;
  float v[8] = {blo(P[0]), bhi(P[0]), blo(P[1]), bhi(P[1]), blo(P[2]), bhi(P[2]), blo(P[3]), bhi(P[3])};
#pragma unroll
  for (int i = 0; i < 8; i++) {
    bool r1 = (i >> 1) & 1;
    e[i]     = ex2(fmaf(v[i],  LOG2E, r1 ? mx1 : mx0));
    e[8 + i] = ex2(fmaf(v[i], -LOG2E, r1 ? mn1 : mn0));
  }
}

__global__ void __cluster_dims__(2, 1, 1) __launch_bounds__(384, 1)
fused_kernel(const __grid_constant__ Maps maps, const __nv_bfloat16* __restrict__ x, const __nv_bfloat16* __restrict__ wphi,
             const __nv_bfloat16* __restrict__ wo, const __nv_bfloat16* __restrict__ wg_, const __nv_bfloat16* __restrict__ wu_,
             const __nv_bfloat16* __restrict__ wd_, __nv_bfloat16* __restrict__ out) {
  extern __shared__ __align__(1024) unsigned char smem[];
  const uint32_t sb = smem_u32(smem);
  const int tid = threadIdx.x, lane = tid & 31;
  const int warp = __shfl_sync(0xffffffffu, tid >> 5, 0);
  const uint32_t rank = blockIdx.x & 1;
  const int cl = blockIdx.x >> 1;
  int quad, qi;
  if (cl < 4) { quad = 15; qi = cl; }
  else if (cl < 36) { quad = (cl - 4) & 7; qi = (cl - 4) >> 3; }
  else { qi = (cl - 36) / 7; quad = 8 + (cl - 36) - 7 * qi; }
  const int rb = quad, hg = 2 * qi + rank;
  const int rb3 = (quad & ~1) + rank, jf = 4 * (quad & 1) + qi;

  if (warp < 8) {
    asm volatile("setmaxnreg.inc.sync.aligned.u32 240;");
    if (elect_one()) {
#pragma unroll 1
      for (int d = warp; d + 9 < NSTAGE; d += 8) {
        mbar_init(sb + SM_EMPTY + d * 8, st_empty_cnt(d));
        {
          mbar_init(sb + SM_FULL + (d + 9) * 8, 1);
          mbar_expect_tx(sb + SM_FULL + (d + 9) * 8, d + 9 >= ST_D ? 22528 : SLOT);
        }
      }
      asm volatile("fence.mbarrier_init.release.cluster;" ::: "memory");
    }
    __syncwarp();
    bar_sync(0, 352);
    asm volatile("barrier.cluster.arrive.relaxed.aligned;" ::: "memory");
    const int wg = warp >> 2, wq = warp & 3, g = lane >> 2, t = lane & 3;
    const bool lead = (tid & 127) == 0;
    constexpr uint32_t db = (SM_BASE >> 4) | (512u << 16);
    auto release = [&](int d) {
      const int s = d + NSLOT;
      mbar_arrive_cluster(sb + SM_EMPTY + d * 8, s >= ST_GU ? (uint32_t)(s & 1) : rank);
    };
    const uint32_t lrow = (uint32_t)(wq * 16 + (lane & 7) + ((lane >> 3) & 1) * 8) * 128;
    const uint32_t lx = lane & 7, lhi = lane >> 4;
    if (wg == 1) bar_arrive(4, 256);

    float r0, r1;
    uint32_t E[4][8];
    uint32_t T = 0;
    {
      uint32_t A[32][4];
      const int sx = wg ? ST_X1 : ST_X0;
      {
        const uint32_t base = sb + sx * SLOT + lrow, baseb = sb + sx * SLOT + (wq * 16 + lx + lhi * 8) * 128;
        float cs[2][4], c0[2][4], c1[2][4];
#pragma unroll
        for (int i = 0; i < 4; i++) { cs[0][i] = cs[1][i] = c0[0][i] = c0[1][i] = c1[0][i] = c1[1][i] = 0.f; }
#pragma unroll
        for (int c = 0; c < 8; c++) {
          if (c % 3 == 0) mbar_wait(sb + SM_FULL + (sx + c / 3) * 8);
#pragma unroll
          for (int k = 0; k < 4; k++) ldsm4(A[4 * c + k], base + c * 8192 + (((2 * k + lhi) ^ lx) << 4));
#pragma unroll
          for (int k = 0; k < 4; k++) {
            const uint32_t (&f)[4] = A[4 * c + k];
            uint32_t bt[4];
            ldsm4(bt, baseb + c * 8192 + (((2 * k + ((lane >> 3) & 1)) ^ lx) << 4));
            mma16816(cs[k & 1], f, 0x3F803F80u, 0x3F803F80u);
            mma16816(c0[k & 1], f, bt[0], bt[1]);
            mma16816(c1[k & 1], f, bt[2], bt[3]);
          }
        }
        const float s0 = (cs[0][0] + cs[1][0]) * (1.f / 512.f), s1 = (cs[0][2] + cs[1][2]) * (1.f / 512.f);
        asm volatile("barrier.cluster.wait.aligned;" ::: "memory");
        if (lane < 3) release(sx + lane);
        const uint32_t m0 = pack2(s0, s0), m1 = pack2(s1, s1);
        float q0 = (g & 1) ? c0[0][1] + c0[1][1] : c0[0][0] + c0[1][0];
        float q1 = (g & 1) ? c1[0][3] + c1[1][3] : c1[0][2] + c1[1][2];
        q0 = __shfl_sync(0xffffffffu, q0, (lane & ~3) | (g >> 1));
        q1 = __shfl_sync(0xffffffffu, q1, (lane & ~3) | (g >> 1));
        r0 = rsqrtf(fmaxf(q0 * (1.f / 512.f) - s0 * s0, 0.f) + 1e-5f);
        r1 = rsqrtf(fmaxf(q1 * (1.f / 512.f) - s1 * s1, 0.f) + 1e-5f);
#pragma unroll
        for (int ks = 0; ks < 32; ks++) {
          A[ks][0] = hsub2(A[ks][0], m0); A[ks][1] = hsub2(A[ks][1], m1);
          A[ks][2] = hsub2(A[ks][2], m0); A[ks][3] = hsub2(A[ks][3], m1);
        }
      }
      TSTAMP(1);
      const uint32_t wpa = sb + SM_WPHI + ((lane & 7) + ((lane >> 3) & 1) * 8) * 32 + lhi * 16;
      const uint32_t scr = sb + (wg ? (ST_SCR1 % NSLOT) : (ST_SCR0 % NSLOT)) * SLOT;
#pragma unroll 1
      for (int ps = 0; ps < 3; ps++) {
        const int st0 = ps == 0 ? ST_WK : (ps == 1 ? ST_WV : ST_WQ);
        const uint32_t wdesc = DESC((ps == 0 ? ST_WK % NSLOT : (ps == 1 ? ST_WV % NSLOT : ST_WQ % NSLOT)) * SLOT);
        float acc[32];
        bar_sync(4 + wg, 256);
#pragma unroll
        for (int i = 0; i < 3; i++) {
          mbar_wait(sb + SM_FULL + (st0 + i) * 8);
          wg_fence();
#pragma unroll
          for (int kk = 0; kk < (i < 2 ? 12 : 8); kk++)
            wgmma_rs_n64(acc, A[12 * i + kk], wdesc + ((i * SLOT + kk * 2048) >> 4), (i | kk) != 0);
          wg_commit();
          if (i == 1) { wg_wait<1>(); if (lead) release(st0); }
        }
        if (ps == 1 && wg == 0) bar_arrive(5, 256);
        uint32_t a[4][4], b[4][4];
        mbar_wait(sb + SM_MISCB);
        T = (*reinterpret_cast<volatile unsigned*>(smem + SM_EPOCH) & 1) ^ 1;
#pragma unroll
        for (int h = 0; h < 4; h++) ldsm4t(b[h], wpa + h * 512);
        wg_wait<0>();
        if ((tid & 127) < 2) release(st0 + 1 + (tid & 1));
        TSTAMP(2 + 2 * ps);
#pragma unroll
        for (int h = 0; h < 4; h++) {
          a[h][0] = pack2(acc[8 * h + 0] * r0, acc[8 * h + 1] * r0); a[h][1] = pack2(acc[8 * h + 2] * r1, acc[8 * h + 3] * r1);
          a[h][2] = pack2(acc[8 * h + 4] * r0, acc[8 * h + 5] * r0); a[h][3] = pack2(acc[8 * h + 6] * r1, acc[8 * h + 7] * r1);
        }
        if (ps != 1) {
          {
            float pp[4][2][4];
#pragma unroll
            for (int h = 0; h < 4; h++) {
#pragma unroll
              for (int i = 0; i < 4; i++) { pp[h][0][i] = 0.f; pp[h][1][i] = 0.f; }
              mma16816(pp[h][0], a[h], b[h][0], b[h][1]);
              mma16816(pp[h][1], a[h], b[h][2], b[h][3]);
            }
#pragma unroll
            for (int h = 0; h < 4; h++) {
              a[h][0] = pack2(pp[h][0][0], pp[h][0][1]); a[h][1] = pack2(pp[h][0][2], pp[h][0][3]);
              a[h][2] = pack2(pp[h][1][0], pp[h][1][1]); a[h][3] = pack2(pp[h][1][2], pp[h][1][3]);
            }
          }
          if (ps == 0 || wg == 0) bar_arrive(4 + (wg ^ 1), 256);
          if (ps == 0) mbar_wait(sb + SM_EMPTY + (wg ? ST_SCR1 - NSLOT : ST_SCR0 - NSLOT) * 8);
#pragma unroll 1
          for (int hp = 0; hp < 2; hp++) {
            float e[2][16];
            feat_exp(a[0], e[0]);
            feat_exp(a[1], e[1]);
            if (ps == 0) {
#pragma unroll
              for (int h = 0; h < 2; h++) {
                const float (&f)[16] = e[h];
                float sp0 = (f[0] + f[1]) + (f[4] + f[5]), sp1 = (f[2] + f[3]) + (f[6] + f[7]);
                float sn0 = (f[8] + f[9]) + (f[12] + f[13]), sn1 = (f[10] + f[11]) + (f[14] + f[15]);
                sp0 += __shfl_xor_sync(0xffffffffu, sp0, 1); sp1 += __shfl_xor_sync(0xffffffffu, sp1, 1);
                sn0 += __shfl_xor_sync(0xffffffffu, sn0, 1); sn1 += __shfl_xor_sync(0xffffffffu, sn1, 1);
                sp0 += __shfl_xor_sync(0xffffffffu, sp0, 2); sp1 += __shfl_xor_sync(0xffffffffu, sp1, 2);
                sn0 += __shfl_xor_sync(0xffffffffu, sn0, 2); sn1 += __shfl_xor_sync(0xffffffffu, sn1, 2);
                sp0 = rcp(sp0); sp1 = rcp(sp1); sn0 = rcp(sn0); sn1 = rcp(sn1);
                const uint32_t dst = scr + hp * 8192 + lrow;
                stsm4(dst + (((h * 4 + lhi) ^ lx) << 4), pack2(f[0] * sp0, f[1] * sp0), pack2(f[2] * sp1, f[3] * sp1),
                      pack2(f[4] * sp0, f[5] * sp0), pack2(f[6] * sp1, f[7] * sp1));
                stsm4(dst + (((h * 4 + 2 + lhi) ^ lx) << 4), pack2(f[8] * sn0, f[9] * sn0), pack2(f[10] * sn1, f[11] * sn1),
                      pack2(f[12] * sn0, f[13] * sn0), pack2(f[14] * sn1, f[15] * sn1));
              }
            } else {
#pragma unroll
              for (int i = 0; i < 16; i++) {
                A[i >> 2][i & 3] = A[4 + (i >> 2)][i & 3];
                A[4 + (i >> 2)][i & 3] = pack2(e[i >> 3][2 * (i & 7)], e[i >> 3][2 * (i & 7) + 1]);
              }
            }
#pragma unroll
            for (int i = 0; i < 4; i++) { a[0][i] = a[2][i]; a[1][i] = a[3][i]; }
          }
        } else {
#pragma unroll
          for (int h = 0; h < 4; h++) stsm4(scr + 16384 + lrow + (((2 * h + lhi) ^ lx) << 4), a[h][0], a[h][1], a[h][2], a[h][3]);
          fence_async_smem();
          bar_sync(3, 256);
          float kv[36];
          wg_fence();
#pragma unroll
          for (int ks = 0; ks < 8; ks++) {
            const uint32_t sk = (ks < 4 ? (ST_SCR0 % NSLOT) : (ST_SCR1 % NSLOT)) * SLOT + (ks & 3) * 2048;
            const uint32_t dv = (DESC(sk + 16384) & 0xFFFFu) | (((SM_ONES - sk - 16384) >> 4) << 16);
            wgmma_ss_n72_t11(kv, DESC(sk) + wg * 512, dv, ks != 0);
          }
          wg_commit();
          if (wg == 1) bar_arrive(4, 256);
          wg_wait<0>();
          if (lead) { mbar_arrive(sb + SM_EMPTY + ST_SCR0 * 8); mbar_arrive(sb + SM_EMPTY + ST_SCR1 * 8); }
          const int hl = 2 * wg + (wq >> 1), f = (wq & 1) * 16 + g;
          float* kvp = reinterpret_cast<float*>(smem + 2 * SLOT) + (hl * 32 + f) * 16 + 2 * t;
          float c[8];
#pragma unroll
          for (int i = 0; i < 8; i++) c[i] = hl >= 2 ? (hl == 3 ? kv[24 + i] : kv[16 + i]) : (hl == 1 ? kv[8 + i] : kv[i]);
#pragma unroll
          for (int n = 0; n < 2; n++) {
            *reinterpret_cast<float2*>(kvp + n * 8) = make_float2(c[4 * n], c[4 * n + 1]);
            *reinterpret_cast<float2*>(kvp + n * 8 + 128) = make_float2(c[4 * n + 2], c[4 * n + 3]);
          }
          if (t < 2) reinterpret_cast<float*>(smem + 2 * SLOT)[2048 + hl * 32 + f + t * 8] = t ? kv[34] : kv[32];
          fence_async_smem();
          bar_sync(6, 320);
        }
        TSTAMP(3 + 2 * ps);
      }
#pragma unroll
      for (int i = 0; i < 32; i++) E[i >> 3][i & 7] = A[i >> 2][i & 3];
    }
    const int rh = 2 * rb + wg;
#define IDF ((g >> 1) == t ? ((g & 1) ? 0x3F800000u : 0x00003F80u) : 0u)
    const uint4* xb = reinterpret_cast<const uint4*>(smem + 2 * SLOT) + wq * 128 + lane;
    mbar_wait(sb + SM_KVB);
    {
      const int r = tid & 127;
      const float4* src = reinterpret_cast<const float4*>(smem + SM_KV32) + r;
#pragma unroll
      for (int i = 0; i < 4; i++) {
        const float4 a = src[i * 128];
        *reinterpret_cast<uint2*>(smem + SM_KVS + (i * 32 + (r >> 2)) * 48 + (r & 3) * 8) = make_uint2(pack2(a.x, a.y), pack2(a.z, a.w));
      }
      const uint32_t zz = pack2(reinterpret_cast<const float*>(smem + SM_ONES)[r], 1.0f);
      *reinterpret_cast<uint4*>(smem + SM_KVS + r * 48 + 32) = make_uint4(zz, zz, zz, zz);
      bar_sync(1 + wg, 128);
    }
    TSTAMP(8);
    {
      uint4* op = &g_o[rh][hg][wq][0][lane];
      if (wg == 1) bar_sync(5, 256);
#pragma unroll 1
      for (int hp = 0; hp < 2; hp++) {
#pragma unroll
      for (int h = 0; h < 2; h++) {
        uint32_t b0[4], b1[4], b2[4];
        const uint32_t kb = sb + SM_KVS + ((2 * hp + h) * 32 + lane) * 48;
        ldsm4t(b0, kb); ldsm4t(b1, kb + 16); ldsm4t(b2, kb + 32);
        const uint32_t ep[4] = {E[h][0], E[h][1], E[h][2], E[h][3]}, en[4] = {E[h][4], E[h][5], E[h][6], E[h][7]};
        float np0[4] = {0, 0, 0, 0}, np1[4] = {0, 0, 0, 0}, nn0[4] = {0, 0, 0, 0}, nn1[4] = {0, 0, 0, 0}, dp[4] = {0, 0, 0, 0}, dn[4] = {0, 0, 0, 0};
        mma16816(dp, ep, b2[0], b2[1]);  mma16816(dn, en, b2[2], b2[3]);
        mma16816(np0, ep, b0[0], b0[1]); mma16816(nn0, en, b0[2], b0[3]);
        mma16816(np1, ep, b1[0], b1[1]); mma16816(nn1, en, b1[2], b1[3]);
        const float i0 = rcp(fmaf(dp[0], dn[1], fmaf(dn[0], dp[1], 1e-6f * dp[1] * dn[1])));
        const float i1 = rcp(fmaf(dp[2], dn[3], fmaf(dn[2], dp[3], 1e-6f * dp[3] * dn[3])));
        const float cp0 = dn[1] * i0, cn0 = dp[1] * i0, cp1 = dn[3] * i1, cn1 = dp[3] * i1;
        st_rlx4(op + (2 * hp + h) * 32,
                tg(pack2(fmaf(np0[0], cp0, nn0[0] * cn0), fmaf(np0[1], cp0, nn0[1] * cn0)), T),
                pack2(fmaf(np0[2], cp1, nn0[2] * cn1), fmaf(np0[3], cp1, nn0[3] * cn1)),
                pack2(fmaf(np1[0], cp0, nn1[0] * cn0), fmaf(np1[1], cp0, nn1[1] * cn0)),
                pack2(fmaf(np1[2], cp1, nn1[2] * cn1), fmaf(np1[3], cp1, nn1[3] * cn1)));
      }
#pragma unroll
        for (int i = 0; i < 8; i++) { E[0][i] = E[2][i]; E[1][i] = E[3][i]; }
      }
    }
    if (wg == 0) bar_arrive(5, 256);
    TSTAMP(9);

    {
      uint32_t xr[4][4];
      {
        const uint32_t* xp = reinterpret_cast<const uint32_t*>(x + (size_t)(rh * 64 + wq * 16 + g) * 512 + hg * 64 + 2 * t);
#pragma unroll
        for (int i = 0; i < 8; i++) { xr[i >> 1][(i & 1) * 2] = __ldg(xp + 4 * i); xr[i >> 1][(i & 1) * 2 + 1] = __ldg(xp + 8 * 256 + 4 * i); }
      }
      uint32_t A[8][4][4];
      const uint4* op = &g_o[rh][0][wq][0][lane];
      float acc[32];
#pragma unroll
      for (int i = 0; i < 32; i++) acc[i] = 0.f;
      add_frag(acc, xr, IDF);
#pragma unroll
      for (int p = -1; p < 4; p++) {
        if (p < 3) {
          mbar_wait(sb + SM_XF + (wg * 4 + p + 1) * 8);
          if (p == -1) TSTAMP(18);
          get_pair(A[2 * p + 2], A[2 * p + 3], xb + (p + 1) * 1024, op + (p + 1) * 1024, T);
          if (lane == 0) mbar_arrive(sb + SM_XE + (wg * 4 + p + 1) * 8);
        }
        if (p == 0 && wg == 1) bar_sync(4, 256);
        if (p >= 0) {
          if (p != 2) mbar_wait(sb + SM_FULL + (ST_WO + (p + 1) / 2) * 8);
          wg_fence();
#pragma unroll
          for (int c = 2 * p; c < 2 * p + 2; c++)
#pragma unroll
            for (int s = 0; s < 4; s++)
              wgmma_rs_n64(acc, A[c][s], DESC(((ST_WO + c / 3) % NSLOT) * SLOT + ((c % 3) * 4 + s) * 2048), 1);
        }
      }
      wg_commit();
      if (wg == 0) bar_arrive(4, 256);
      wg_wait<0>();
      if ((tid & 127) < 3) release(ST_WO + (tid & 127));
      TSTAMP(10);
      uint4* hp_ = &g_h[rh][hg][wq][0][lane];
      uint32_t hx = T;
#pragma unroll
      for (int s = 0; s < 4; s++) {
        const uint32_t h0 = pack2(acc[8 * s], acc[8 * s + 1]);
        st_rlx4(hp_ + s * 32, tg(h0, T), pack2(acc[8 * s + 2], acc[8 * s + 3]), pack2(acc[8 * s + 4], acc[8 * s + 5]), pack2(acc[8 * s + 6], acc[8 * s + 7]));
        hx |= (h0 & 1u) << (s + 1);
      }
      float s0 = 0.f, s1 = 0.f, q0 = 0.f, q1 = 0.f, q2 = 0.f, q3 = 0.f;
#pragma unroll
      for (int i = 0; i < 8; i++) {
        s0 += acc[4 * i] + acc[4 * i + 1]; s1 += acc[4 * i + 2] + acc[4 * i + 3];
        q0 = fmaf(acc[4 * i], acc[4 * i], q0); q2 = fmaf(acc[4 * i + 1], acc[4 * i + 1], q2);
        q1 = fmaf(acc[4 * i + 2], acc[4 * i + 2], q1); q3 = fmaf(acc[4 * i + 3], acc[4 * i + 3], q3);
      }
      q0 += q2; q1 += q3;
      {
        const bool up = t & 2;
        float s = (up ? s1 : s0) + __shfl_xor_sync(0xffffffffu, up ? s0 : s1, 2);
        float q = (up ? q1 : q0) + __shfl_xor_sync(0xffffffffu, up ? q0 : q1, 2);
        s += __shfl_xor_sync(0xffffffffu, s, 1);
        q += __shfl_xor_sync(0xffffffffu, q, 1);
        if (!(t & 1)) st_rlx2(&g_st[rh][hg][wq * 16 + g + (t >> 1) * 8], tg(__float_as_uint(s), T), __float_as_uint(q));
      }
      st_rlx1(&g_hx[rh][hg][wq][lane], hx);
    }
    TSTAMP(11);

    const int rh3 = 2 * rb3 + wg;
    uint32_t HH[11][4], PH[11][4];
    const uint4* pp = &g_hh[rh3][jf ^ 1][0][wq][lane];
    {
      uint32_t A[8][4][4];
      const uint4* hp_ = &g_h[rh3][0][wq][0][lane];
      uint4* hhp = &g_hh[rh3][jf][0][wq][lane];
      const uint32_t dg = (db & 0xFFFFu) | (256u << 16);
      uint32_t m0, m1;
      mbar_wait(sb + SM_XF + ((2 + wg) * 4) * 8);
      TSTAMP(0);
      {
        const uint2* sp = reinterpret_cast<const uint2*>(smem + SM_KV32 + wg * 4096) + 2 * t * 64 + wq * 16 + g;
        uint2 a0, a1, b0, b1;
        int it = 0;
#pragma unroll 1
        do {
          ld_rlx2(a0.x, a0.y, sp); ld_rlx2(a1.x, a1.y, sp + 64); ld_rlx2(b0.x, b0.y, sp + 8); ld_rlx2(b1.x, b1.y, sp + 72);
          sp = &g_st[rh3][2 * t][wq * 16 + g];
        } while (__any_sync(0xffffffffu, bad4(a0.x, a1.x, b0.x, b1.x, T)) && ++it < (1 << 18));
        float s0 = __uint_as_float(a0.x) + __uint_as_float(a1.x), q0 = __uint_as_float(a0.y) + __uint_as_float(a1.y);
        float s1 = __uint_as_float(b0.x) + __uint_as_float(b1.x), q1 = __uint_as_float(b0.y) + __uint_as_float(b1.y);
        s0 += __shfl_xor_sync(0xffffffffu, s0, 1); s1 += __shfl_xor_sync(0xffffffffu, s1, 1);
        q0 += __shfl_xor_sync(0xffffffffu, q0, 1); q1 += __shfl_xor_sync(0xffffffffu, q1, 1);
        s0 += __shfl_xor_sync(0xffffffffu, s0, 2); s1 += __shfl_xor_sync(0xffffffffu, s1, 2);
        q0 += __shfl_xor_sync(0xffffffffu, q0, 2); q1 += __shfl_xor_sync(0xffffffffu, q1, 2);
        s0 *= (1.f / 512.f); s1 *= (1.f / 512.f);
        r0 = rcp(fmaxf(q0 * (1.f / 512.f) - s0 * s0, 0.f) + 1e-5f);
        r1 = rcp(fmaxf(q1 * (1.f / 512.f) - s1 * s1, 0.f) + 1e-5f);
        m0 = pack2(s0, s0); m1 = pack2(s1, s1);
      }
      TSTAMP(12);
#define UOFF(u) ((((ST_GU + (u) / 3) % NSLOT) * SLOT + ((u) % 3) * 8192) >> 4)
#define UNIT_PRE(u)  do { if ((u) % 3 == 0) mbar_wait(sb + SM_FULL + (ST_GU + (u) / 3) * 8); } while (0)
#define UNIT_POST(u) do { wg_commit(); if ((u) % 3 == 1 && (u) > 3) { wg_wait<2>(); if (lead) release(ST_GU + (u) / 3 - 1); } } while (0)
      float acc[64];
      const int rz = blockIdx.y;
#pragma unroll
      for (int ps = 0; ps < 2; ps++) {
        wg_fence();
#pragma unroll
        for (int k = 0; k < 16; k++) {
          const int u = 16 * ps + k, c = k >> 1;
          if (ps == 0 && (k == 0 || k == 4 || k == 8)) {
#pragma unroll
            for (int p = (k == 0 ? 0 : (k == 4 ? 1 : 3)); p < (k == 0 ? 1 : (k == 4 ? 3 : 4)); p++) {
              if (p > 0) mbar_wait(sb + SM_XF + ((2 + wg) * 4 + p) * 8);
              get_pair(A[2 * p], A[2 * p + 1], xb + p * 1024, hp_ + p * 1024, T);
              if (lane == 0) {
                if (wg == 0) mbar_arrive(sb + SM_XE + (8 + p) * 8);
                else if (p > 0) release(ST_XC + p - 1);
              }
            }
          }
          if (ps == 0 && (k & 1) == 0) {
#pragma unroll
            for (int s = 0; s < 4; s++) {
              A[c][s][0] = hsub2(A[c][s][0], m0); A[c][s][1] = hsub2(A[c][s][1], m1);
              A[c][s][2] = hsub2(A[c][s][2], m0); A[c][s][3] = hsub2(A[c][s][3], m1);
            }
            wg_fence();
          }
          UNIT_PRE(u);
          wgmma_rs_n128(acc, A[c][(k & 1) * 2], dg + UOFF(u), k != 0 ? 1 : (ps ? rz : 0));
          wgmma_rs_n128(acc, A[c][(k & 1) * 2 + 1], dg + UOFF(u) + 128, 1);
          UNIT_POST(u);
          if (ps == 0 && k == 7) TSTAMP(17);
        }
        wg_wait<0>();
        TSTAMP(22 + ps);
#pragma unroll
        for (int s = 0; s < 4; s++) {
          uint32_t (&hh)[4] = HH[4 + s];
          hh[0] = tg(pack2(acc[8 * s + 0] * acc[32 + 8 * s + 0], acc[8 * s + 1] * acc[32 + 8 * s + 1]), T);
          hh[1] = pack2(acc[8 * s + 2] * acc[32 + 8 * s + 2], acc[8 * s + 3] * acc[32 + 8 * s + 3]);
          hh[2] = pack2(acc[8 * s + 4] * acc[32 + 8 * s + 4], acc[8 * s + 5] * acc[32 + 8 * s + 5]);
          hh[3] = pack2(acc[8 * s + 6] * acc[32 + 8 * s + 6], acc[8 * s + 7] * acc[32 + 8 * s + 7]);
          st_rlx4(hhp + (4 * ps + s) * 128, hh[0], hh[1], hh[2], hh[3]);
        }
      }
      {
        float ag[24], au[24];
        const uint32_t* ph7 = reinterpret_cast<const uint32_t*>(&g_hh[rh3][jf ^ 1][7][wq][31]);
        uint32_t hv = 0;
        bar_sync(1 + wg, 128);
        wg_fence();
#pragma unroll
        for (int k = 0; k < 16; k++) {
          const int u = 32 + k, c = k >> 1;
          if (k == 6) {
#pragma unroll
            for (int s = 0; s < 4; s++) ld_rlx4(HH[s], hhp + s * 128);
          }
          if (k == 9) hv = ld_rlx1(ph7);
          if (k == 12) {
            int it = 0;
#pragma unroll 1
            while (((hv ^ T) & 1) && ++it < (1 << 18)) hv = ld_rlx1(ph7);
#pragma unroll
            for (int s = 0; s < 8; s++) ld_rlx4(PH[s], pp + s * 128);
          }
          UNIT_PRE(u);
          wgmma_rs_n48(ag, A[c][(k & 1) * 2], dg + UOFF(u), k != 0);
          wgmma_rs_n48(au, A[c][(k & 1) * 2], dg + UOFF(u) + 256, k != 0);
          wgmma_rs_n48(ag, A[c][(k & 1) * 2 + 1], dg + UOFF(u) + 128, 1);
          wgmma_rs_n48(au, A[c][(k & 1) * 2 + 1], dg + UOFF(u) + 256 + 128, 1);
          UNIT_POST(u);
        }
        wg_wait<0>();
        TSTAMP(13);
#pragma unroll
        for (int s = 0; s < 3; s++) {
          uint32_t (&hh)[4] = HH[8 + s];
          hh[0] = tg(pack2(ag[8 * s + 0] * au[8 * s + 0], ag[8 * s + 1] * au[8 * s + 1]), T);
          hh[1] = pack2(ag[8 * s + 2] * au[8 * s + 2], ag[8 * s + 3] * au[8 * s + 3]);
          hh[2] = pack2(ag[8 * s + 4] * au[8 * s + 4], ag[8 * s + 5] * au[8 * s + 5]);
          hh[3] = pack2(ag[8 * s + 6] * au[8 * s + 6], ag[8 * s + 7] * au[8 * s + 7]);
          st_rlx4(hhp + (8 + s) * 128, hh[0], hh[1], hh[2], hh[3]);
        }
      }
    }
    TSTAMP(14);

    {
      float ac[3][32], acc[32];
      uint32_t hr[4][4];
      const int m = jf >> 1, oc = (jf & 1) * 4 + m;
      const uint32_t* ph10 = reinterpret_cast<const uint32_t*>(&g_hh[rh3][jf ^ 1][10][wq][31]);
      uint32_t hv = 0;
      bar_arrive(8 + wg, 256);
      wg_fence();
#pragma unroll
      for (int k = 0; k < 3; k++) {
        mbar_wait(sb + SM_FULL + (ST_D + k) * 8);
        if (k == 1) hv = ld_rlx1(ph10);
#pragma unroll
        for (int s = 0; s < 11; s++) {
          if (k == 2 && s == 4) {
            int it = 0;
#pragma unroll 1
            while (((hv ^ T) & 1) && ++it < (1 << 18)) hv = ld_rlx1(ph10);
#pragma unroll
            for (int i = 8; i < 11; i++) ld_rlx4(PH[i], pp + i * 128);
          }
          wgmma_rs_n64(ac[k], HH[s], DESC(((ST_D + k) % NSLOT) * SLOT + s * 2048), s != 0);
        }
      }
      wg_commit();
      {
        int it = 0;
#pragma unroll 1
        while (__any_sync(0xffffffffu, bad4(PH[0][0], PH[1][0], PH[2][0], PH[3][0], T) | bad4(PH[4][0], PH[5][0], PH[6][0], PH[7][0], T) |
                                       bad4(PH[8][0], PH[9][0], PH[10][0], T, T))) {
#pragma unroll
          for (int s = 0; s < 11; s++) ld_rlx4(PH[s], pp + s * 128);
          if (++it > (1 << 18)) break;
        }
      }
      TSTAMP(20);
      uint4* outb = &g_part[rh3][(jf & 1) * 4][m][wq][0][lane];
#pragma unroll
      for (int k = 0; k < 4; k++) {
        mbar_wait(sb + SM_FULL + (ST_D + 3 + k) * 8);
        wg_fence();
#pragma unroll
        for (int s = 0; s < 11; s++) {
          if (k < 3) wgmma_rs_n64(ac[k], PH[s], DESC(((ST_D + 3 + k) % NSLOT) * SLOT + s * 2048), 1);
          else wgmma_rs_n64(acc, HH[s], DESC(((ST_D + 6) % NSLOT) * SLOT + s * 2048), s != 0);
        }
        wg_commit();
        if (k > 0) {
          wg_wait<1>();
          const float (&a)[32] = ac[k - 1];
          uint4* p = outb + ((m + k) & 3) * 2048;
#pragma unroll
          for (int s = 0; s < 4; s++)
            st_rlx4(p + s * 32, tg(pack2(a[8 * s + 0], a[8 * s + 1]), T), pack2(a[8 * s + 2], a[8 * s + 3]),
                    pack2(a[8 * s + 4], a[8 * s + 5]), pack2(a[8 * s + 6], a[8 * s + 7]));
        }
      }
      uint32_t in[3][4][4];
      const uint4* inb = &g_part[rh3][oc][0][wq][0][lane];
      const uint32_t* hint = reinterpret_cast<const uint32_t*>(&g_part[rh3][oc][(m - 1 - lane) & 3][wq][3][31]);
      ld_chunk(hr, &g_h[rh3][oc][wq][0][lane]);
      uint32_t hx = ld_rlx1(&g_hx[rh3][oc][wq][lane]);
      hv = ld_rlx1(hint);
      mbar_wait(sb + SM_FULL + (ST_D + 7) * 8);
      wg_fence();
#pragma unroll
      for (int s = 0; s < 11; s++) wgmma_rs_n64(acc, PH[s], DESC(((ST_D + 7) % NSLOT) * SLOT + s * 2048), 1);
      wg_commit();
      {
        int it = 0;
#pragma unroll
        for (int q = 0; q < 3; q++) {
#pragma unroll 1
          while (!((__ballot_sync(0xffffffffu, ((hv ^ T) & 1) == 0) >> q) & 1)) {
            hv = ld_rlx1(hint);
            if (++it > (1 << 18)) break;
          }
          ld_chunk(in[q], inb + ((m - 1 - q) & 3) * 512);
        }
#pragma unroll 1
        while (__any_sync(0xffffffffu, bad4(in[0][0][0], in[0][1][0], in[0][2][0], in[0][3][0], T) | bad4(in[1][0][0], in[1][1][0], in[1][2][0], in[1][3][0], T) |
                                       bad4(in[2][0][0], in[2][1][0], in[2][2][0], in[2][3][0], T) | ((hx ^ T) & 1))) {
#pragma unroll
          for (int q = 0; q < 3; q++) ld_chunk(in[q], inb + ((m - 1 - q) & 3) * 512);
          hx = ld_rlx1(&g_hx[rh3][oc][wq][lane]);
          if (++it > (1 << 18)) break;
        }
      }
      wg_wait<0>();
      TSTAMP(15);
#pragma unroll
      for (int s = 0; s < 4; s++) hr[s][0] = (hr[s][0] & 0xFFFFFFFEu) | ((hx >> (s + 1)) & 1u);
      add_frag(acc, in[0], IDF); add_frag(acc, in[1], IDF); add_frag(acc, in[2], IDF);
#pragma unroll
      for (int i = 0; i < 32; i++) acc[i] *= (i & 2) ? r1 : r0;
      add_frag(acc, hr, IDF);
      bar_sync(9 - wg, 256);
      const uint32_t ob = sb + ((ST_D - 1) % NSLOT) * SLOT + wg * 8192;
#pragma unroll
      for (int s = 0; s < 4; s++)
        stsm4(ob + lrow + (((2 * s + lhi) ^ lx) << 4), pack2(acc[8 * s + 0], acc[8 * s + 1]), pack2(acc[8 * s + 2], acc[8 * s + 3]),
              pack2(acc[8 * s + 4], acc[8 * s + 5]), pack2(acc[8 * s + 6], acc[8 * s + 7]));
      __syncwarp();
      {
        const int row = wq * 16 + (lane >> 3);
        __nv_bfloat16* op = out + (size_t)(rh3 * 64 + row) * 512 + oc * 64 + lx * 8;
#pragma unroll
        for (int i = 0; i < 4; i++) {
          uint4 v;
          asm volatile("ld.shared.v4.b32 {%0,%1,%2,%3}, [%4];" : "=r"(v.x), "=r"(v.y), "=r"(v.z), "=r"(v.w)
                       : "r"(ob + (row + i * 4) * 128 + ((lx ^ (((lane >> 3) + i * 4) & 7)) << 4)) : "memory");
          asm volatile("st.global.v4.b32 [%0], {%1,%2,%3,%4};" ::"l"(op + i * 2048), "r"(v.x), "r"(v.y), "r"(v.z), "r"(v.w) : "memory");
        }
      }
    }
    TSTAMP(16);
    asm volatile("barrier.cluster.arrive.relaxed.aligned;" ::: "memory");
    asm volatile("barrier.cluster.wait.aligned;" ::: "memory");
  } else {
    asm volatile("setmaxnreg.dec.sync.aligned.u32 24;");
    if (elect_one()) {
      if (warp == 8) {
#pragma unroll
        for (int k = 0; k < 9; k++) {
          const int s = k < 3 ? k : (k < 6 ? k + 3 : k - 3);
          const uint32_t bar = sb + SM_FULL + s * 8;
          mbar_init(bar, 1);
          mbar_expect_tx(bar, SLOT);
          if (s >= 3 && s < 6) tma2d(sb + s * SLOT, &maps.w, 512 + hg * 64, (s - 3) * 192, bar);
          else tma3d(sb + s * SLOT, &maps.x, 0, rb * 128 + (s >= 6 ? 64 : 0), 3 * (s % 3), bar);
        }
      } else if (warp == 9) {
        mbar_init(sb + SM_MISCB, 2);
        mbar_init(sb + SM_KVB, 32);
        mbar_expect_tx(sb + SM_MISCB, 2048);
        bulk_g2s(sb + SM_WPHI, wphi + hg * 1024, 2048, sb + SM_MISCB);
      } else if (warp == 10) {
        if ((sb & 0x3FFFF) != SM_BASE) __trap();
#pragma unroll 1
        for (int i = 0; i < 16; i++) {
          mbar_init(sb + SM_XF + i * 8, 1);
          mbar_expect_tx(sb + SM_XF + i * 8, (i == 8 || i == 12) ? 20480 : 16384);
          if (i < 12) mbar_init(sb + SM_XE + i * 8, 4);
        }
      } else {
        *reinterpret_cast<volatile unsigned*>(smem + SM_EPOCH) = atomicAdd(&g_start, 1u) / NCTA;
      }
      asm volatile("fence.mbarrier_init.release.cluster;" ::: "memory");
    }
    __syncwarp();
    if (warp != 11) bar_sync(0, 352);
    asm volatile("barrier.cluster.arrive.relaxed.aligned;" ::: "memory");
    if (warp == 8) {
      asm volatile("barrier.cluster.wait.aligned;" ::: "memory");
      if (elect_one()) {
        const CUtensorMap* mg = jf == 7 ? &maps.g7 : &maps.g;
        const CUtensorMap* mu = jf == 7 ? &maps.u7 : &maps.u;
        asm volatile("prefetch.tensormap [%0];" ::"l"(&maps.wo) : "memory");
        asm volatile("prefetch.tensormap [%0];" ::"l"(mg) : "memory");
        asm volatile("prefetch.tensormap [%0];" ::"l"(mu) : "memory");
        asm volatile("prefetch.tensormap [%0];" ::"l"(&maps.d) : "memory");
#pragma unroll 1
        for (int s = ST_WV; s < ST_XC; s++) {
          if (s == ST_SCR1) continue;
          mbar_wait(sb + SM_EMPTY + (s - 9) * 8);
          const uint32_t dst = sb + (s >= 18 ? s - 18 : s - 9) * SLOT, bar = sb + SM_FULL + s * 8;
          if (s < ST_WO) tma2d(dst, &maps.w, (s < ST_WQ ? 1024 : 0) + hg * 64, (s < ST_WQ ? s - ST_WV : s - ST_WQ) * 192, bar);
          else { mbar_wait(bar - 8); tma2d(dst, &maps.wo, hg * 64, (s - ST_WO) * 192, bar); }
        }
        const int jc = jf == 7 ? 0 : jf;
        int slot = (ST_GU + 1 - rank) % NSLOT;
#pragma unroll 1
        for (int s = ST_GU + 1 - rank; s < NSTAGE; s += 2) {
          mbar_wait(sb + SM_EMPTY + (s - 9) * 8);
          if (s > ST_GU && s < ST_GU + THR) mbar_wait(sb + SM_FULL + (s - 1) * 8);
          const uint32_t dst = sb + slot * SLOT, bar = sb + SM_FULL + s * 8;
          if (s < ST_D) {
#pragma unroll 1
            for (int i = 0; i < 3; i++) {
              const int u = (s - ST_GU) * 3 + i;
              tma3d_mc(dst + i * 8192, mg, (u >> 4) * 64, jc, (u & 15) * 32, bar);
              tma3d_mc(dst + i * 8192 + 4096, mu, (u >> 4) * 64, jc, (u & 15) * 32, bar);
            }
          } else {
            const int i = s - ST_D, k = i < 3 ? i : (i < 6 ? i - 3 : 3), pt = (i >= 3 && i != 6) ? 1 : 0;
            tma2d_mc(dst, &maps.d, ((jf & 1) * 4 + (((jf >> 1) + 1 + k) & 3)) * 64, (jf ^ pt) * 176, bar);
          }
          slot += 2; if (slot >= NSLOT) slot -= NSLOT;
        }
      }
      __syncwarp();
    } else {
      asm volatile("barrier.cluster.wait.aligned;" ::: "memory");
      if (warp == 11) {
#pragma unroll
        for (int i = 0; i < 4; i++)
          reinterpret_cast<uint4*>(smem + SM_ONES)[lane + 32 * i] = make_uint4(0x3F803F80u, 0x3F803F80u, 0x3F803F80u, 0x3F803F80u);
        fence_async_smem();
        __syncwarp();
        if (lane == 0) mbar_arrive(sb + SM_MISCB);
      }
      mbar_wait(sb + SM_MISCB);
      const unsigned epoch = *reinterpret_cast<volatile unsigned*>(smem + SM_EPOCH);
      const uint32_t T = (epoch & 1) ^ 1;
      if (warp == 11) {
        reinterpret_cast<float4*>(&g_kv[hg][rb * 136])[lane] = make_float4(0.f, 0.f, 0.f, 0.f);
        if (lane < 2) reinterpret_cast<float4*>(&g_kv[hg][rb * 136])[32 + lane] = make_float4(0.f, 0.f, 0.f, 0.f);
        __syncwarp();
        if (elect_one()) asm volatile("red.release.gpu.global.add.u32 [%0], 1;" ::"l"(&g_kvcnt[hg * 32 + 1]) : "memory");
        mbar_wait(sb + SM_FULL + (ST_WK + 2) * 8);
        if (elect_one()) {
          asm volatile("cp.async.bulk.prefetch.L2.global [%0], 4096;" ::"l"((const char*)wo + blockIdx.x * 4096) : "memory");
          asm volatile("cp.async.bulk.prefetch.L2.global [%0], 11008;" ::"l"((const char*)wg_ + blockIdx.x * 11008) : "memory");
          asm volatile("cp.async.bulk.prefetch.L2.global [%0], 11008;" ::"l"((const char*)wu_ + blockIdx.x * 11008) : "memory");
          asm volatile("cp.async.bulk.prefetch.L2.global [%0], 11008;" ::"l"((const char*)wd_ + blockIdx.x * 11008) : "memory");
          const unsigned target = (epoch + 1) * 16;
          unsigned v; int it = 0;
#pragma unroll 1
          do {
            asm volatile("ld.acquire.gpu.global.u32 %0, [%1];" : "=r"(v) : "l"(&g_kvcnt[hg * 32]) : "memory");
            if (++it > (1 << 18)) break;
          } while ((int)(v - target) < 0);
          TS2(0, 26);
        }
        __syncwarp();
        {
          const char* src = reinterpret_cast<const char*>(&g_kv[hg][0]) + lane * 16;
#pragma unroll 4
          for (int i = 0; i < 16; i++)
            asm volatile("cp.async.cg.shared.global [%0], [%1], 16;" ::"r"(sb + SM_KV32 + lane * 16 + i * 512), "l"(src + i * 512) : "memory");
          asm volatile("cp.async.cg.shared.global [%0], [%1], 16;" ::"r"(sb + SM_ONES + lane * 16), "l"(src + 8192) : "memory");
          asm volatile("cp.async.mbarrier.arrive.noinc.shared::cta.b64 [%0];" ::"r"(sb + SM_KVB) : "memory");
        }
      } else {
        const int w = warp - 9;
        st_rlx4(reinterpret_cast<uint4*>(&g_st[2 * rb + w][hg][0]) + lane, T ^ 1, T ^ 1, T ^ 1, T ^ 1);
        if (lane < 8) st_rlx4(&g_o[2 * rb + w][hg][lane >> 1][3][30 + (lane & 1)], T ^ 1, T ^ 1, T ^ 1, T ^ 1);
        st_rlx4(&g_part[2 * rb3 + w][(jf & 1) * 4 + (lane >> 3)][jf >> 1][(lane >> 1) & 3][3][30 + (lane & 1)], T ^ 1, T ^ 1, T ^ 1, T ^ 1);
        if (lane < 16) st_rlx4(&g_hh[2 * rb3 + w][jf][7 + (lane >> 3) * 3][(lane >> 1) & 3][30 + (lane & 1)], T ^ 1, T ^ 1, T ^ 1, T ^ 1);
        if (w == 0) {
          mbar_wait(sb + SM_FULL + (ST_WQ + 2) * 8);
          unsigned v; int it = 0;
#pragma unroll 1
          do {
            asm volatile("ld.acquire.gpu.global.u32 %0, [%1];" : "=r"(v) : "l"(&g_kvcnt[hg * 32 + 1]) : "memory");
          } while ((int)(v - (epoch + 1) * 16) < 0 && ++it < (1 << 18));
          asm volatile("fence.proxy.async.global;" ::: "memory");
        }
        bar_sync(6, 320);
        if (w == 0 && elect_one()) {
          asm volatile("cp.reduce.async.bulk.global.shared::cta.bulk_group.add.f32 [%0], [%1], 8704;"
                       ::"l"(&g_kv[hg][0]), "r"(sb + 2 * SLOT) : "memory");
          asm volatile("cp.async.bulk.commit_group;" ::: "memory");
          asm volatile("cp.async.bulk.wait_group 0;" ::: "memory");
          asm volatile("red.relaxed.gpu.global.add.u32 [%0], 1;" ::"l"(&g_kvcnt[hg * 32]) : "memory");
          TS2(0, 25);
        }
        __syncwarp();
        mbar_wait(sb + SM_KVB);
        if (w == 0) { mbar_wait(sb + SM_EMPTY + 11 * 8); mbar_wait(sb + SM_EMPTY + 12 * 8); mbar_wait(sb + SM_EMPTY + 13 * 8); }
#pragma unroll 1
        for (int ph = 0; ph < 2; ph++) {
          const int use = 2 * ph + w, r = ph ? 2 * rb3 + w : 2 * rb + w;
          const uint32_t* pw = ph ? reinterpret_cast<const uint32_t*>(&g_st[r][lane >> 2][(lane & 3) * 16 + 15])
                                  : reinterpret_cast<const uint32_t*>(&g_o[r][lane >> 2][lane & 3][3][31]);
          const char* src = reinterpret_cast<const char*>(ph ? &g_h[r][0][0][0][0] : &g_o[r][0][0][0][0]);
          const uint32_t bf = sb + SM_XF + use * 32, be = sb + SM_XE + (use - 1) * 32;
          if (ph) mbar_wait(sb + SM_XE + w * 32 + 24);
          int it = 0;
#pragma unroll 1
          while (__any_sync(0xffffffffu, (ld_rlx1(pw) ^ T) & 1)) { if (++it > (1 << 18)) break; }
          if (elect_one()) {
            TS2(w, 27 + ph);
            if (use > 0) mbar_wait(be);
            if (ph) bulk_g2s(sb + SM_KV32 + w * 4096, &g_st[r][0][0], 4096, bf);
#pragma unroll
            for (int p = 0; p < 4; p++) {
              if (p > 0 && use > 0) mbar_wait(be + p * 8);
              bulk_g2s(sb + 2 * SLOT + p * 16384, src + p * 16384, 16384, bf + p * 8);
            }
          }
          __syncwarp();
        }
      }
    }
    asm volatile("barrier.cluster.arrive.relaxed.aligned;" ::: "memory");
    asm volatile("barrier.cluster.wait.aligned;" ::: "memory");
  }
}

typedef CUresult (*EncodeFn)(CUtensorMap*, CUtensorMapDataType, cuuint32_t, void*, const cuuint64_t*, const cuuint64_t*,
                             const cuuint32_t*, const cuuint32_t*, CUtensorMapInterleave, CUtensorMapSwizzle,
                             CUtensorMapL2promotion, CUtensorMapFloatOOBfill);

void encode(EncodeFn fn, CUtensorMap* m, const void* base, int rank, const cuuint64_t* dims, const cuuint64_t* strides,
            const cuuint32_t* box) {
  cuuint32_t es[3] = {1, 1, 1};
  fn(m, CU_TENSOR_MAP_DATA_TYPE_BFLOAT16, (cuuint32_t)rank, const_cast<void*>(base), dims, strides, box, es,
     CU_TENSOR_MAP_INTERLEAVE_NONE, CU_TENSOR_MAP_SWIZZLE_128B, CU_TENSOR_MAP_L2_PROMOTION_L2_256B,
     CU_TENSOR_MAP_FLOAT_OOB_FILL_NONE);
}

}

extern "C" void kernel_launch(void* const* d_in, const int* in_sizes, int n_in, void* d_out, int out_size) {
  (void)in_sizes; (void)n_in; (void)out_size;
  const __nv_bfloat16* x    = (const __nv_bfloat16*)d_in[0];
  const __nv_bfloat16* wqkv = (const __nv_bfloat16*)d_in[1];
  const __nv_bfloat16* wphi = (const __nv_bfloat16*)d_in[2];
  const __nv_bfloat16* wo   = (const __nv_bfloat16*)d_in[3];
  const __nv_bfloat16* wg   = (const __nv_bfloat16*)d_in[5];
  const __nv_bfloat16* wu   = (const __nv_bfloat16*)d_in[6];
  const __nv_bfloat16* wd   = (const __nv_bfloat16*)d_in[7];

  static EncodeFn fn = nullptr;
  if (!fn) {
    void* p = nullptr;
    cudaDriverEntryPointQueryResult qr;
    cudaGetDriverEntryPoint("cuTensorMapEncodeTiled", &p, cudaEnableDefault, &qr);
    fn = (EncodeFn)p;
    cudaFuncSetAttribute(fused_kernel, cudaFuncAttributeMaxDynamicSharedMemorySize, SM_TOTAL);
  }
  Maps maps;
  {
    cuuint64_t d[3] = {64, 2048, 8}, s[2] = {1024, 128}; cuuint32_t b[3] = {64, 64, 3};
    encode(fn, &maps.x, x, 3, d, s, b);
  }
  {
    cuuint64_t d[2] = {1536, 512}, s[1] = {3072}; cuuint32_t b[2] = {64, 192};
    encode(fn, &maps.w, wqkv, 2, d, s, b);
  }
  {
    cuuint64_t d[2] = {512, 512}, s[1] = {1024}; cuuint32_t b[2] = {64, 192};
    encode(fn, &maps.wo, wo, 2, d, s, b);
  }
  {
    cuuint64_t d[3] = {176, 7, 512}, d7[3] = {144, 1, 512}, s[2] = {352, 2752}; cuuint32_t b[3] = {64, 1, 32};
    encode(fn, &maps.g, wg, 3, d, s, b);
    encode(fn, &maps.u, wu, 3, d, s, b);
    encode(fn, &maps.g7, wg + 1232, 3, d7, s, b);
    encode(fn, &maps.u7, wu + 1232, 3, d7, s, b);
  }
  {
    cuuint64_t d[2] = {512, 1376}, s[1] = {1024}; cuuint32_t b[2] = {64, 176};
    encode(fn, &maps.d, wd, 2, d, s, b);
  }
  fused_kernel<<<NCTA, 384, SM_TOTAL>>>(maps, x, wphi, wo, wg, wu, wd, (__nv_bfloat16*)d_out);
}
```

```cpp
#include <cuda_runtime.h>
#include <cuda_bf16.h>
#include <cuda.h>
#include <stdint.h>

#define PROF 0

#define SAFE_WAIT 0
#define OPRIO 1
#define THR 6

namespace {

constexpr int NCTA   = 128;
constexpr int SLOT   = 24576;
constexpr int NSLOT  = 9;
constexpr int NSTAGE = 47;

constexpr int ST_X0   = 0;
constexpr int ST_WK   = 3;
constexpr int ST_X1   = 6;
constexpr int ST_SCR0 = 9;
constexpr int ST_WV   = 10;
constexpr int ST_SCR1 = 13;
constexpr int ST_WQ   = 14;
constexpr int ST_WO   = 17;
constexpr int ST_XC   = 20;
constexpr int ST_GU   = 23;
constexpr int ST_D    = 39;

__host__ __device__ constexpr int st_empty_cnt(int d) {
  return ((d < 3 || (d >= 6 && d < 9) || (d >= ST_XC && d < ST_GU)) ? 4 : 2) * (d + 9 >= ST_GU ? 2 : 1);
}

constexpr uint32_t SM_BASE = 1024;
constexpr int SM_ONES = NSLOT * SLOT;
constexpr int SM_WPHI = SM_ONES + 2048;
constexpr int SM_KVS  = SM_WPHI + 2048;
constexpr int SM_KV32 = 4 * SLOT + 16384;
constexpr int SM_BAR  = SM_KVS + 6144;
constexpr int SM_FULL  = SM_BAR;
constexpr int SM_EMPTY = SM_BAR + NSTAGE * 8;
constexpr int SM_MISCB = SM_BAR + 2 * NSTAGE * 8;
constexpr int SM_KVB   = SM_MISCB + 8;
constexpr int SM_EPOCH = SM_KVB + 8;
constexpr int SM_XF    = SM_EPOCH + 8;
constexpr int SM_XE    = SM_XF + 16 * 8;
constexpr int SM_TOTAL = SM_BAR + 1024;

static_assert(SM_TOTAL == 232448 && SM_XE + 12 * 8 <= SM_TOTAL, "smem budget");

struct Maps { CUtensorMap x, w, wo, g, u, g7, u7, d; };

__device__ uint4    g_o[32][8][4][4][32];
__device__ uint4    g_h[32][8][4][4][32];
__device__ uint32_t g_hx[32][8][4][32];
__device__ uint2    g_st[32][8][64];
__device__ uint4    g_hh[32][8][11][4][32];
__device__ uint4    g_part[32][8][4][4][4][32];
__device__ __align__(128) float g_kv[8][2048 + 128];
__device__ unsigned g_kvcnt[8 * 32];
__device__ unsigned g_start;

__device__ __forceinline__ uint32_t smem_u32(const void* p) { return (uint32_t)__cvta_generic_to_shared(p); }
__device__ __forceinline__ void mbar_init(uint32_t bar, int cnt) {
  asm volatile("mbarrier.init.shared::cta.b64 [%0], %1;" ::"r"(bar), "r"(cnt) : "memory");
}
__device__ __forceinline__ void mbar_expect_tx(uint32_t bar, uint32_t bytes) {
  asm volatile("mbarrier.arrive.expect_tx.shared::cta.b64 _, [%0], %1;" ::"r"(bar), "r"(bytes) : "memory");
}
__device__ __forceinline__ void mbar_arrive(uint32_t bar) {
  asm volatile("mbarrier.arrive.shared::cta.b64 _, [%0];" ::"r"(bar) : "memory");
}
__device__ __forceinline__ void mbar_arrive_cluster(uint32_t bar, uint32_t rank) {
  asm volatile("{\n.reg .b32 ra;\nmapa.shared::cluster.u32 ra, %0, %1;\n"
               "mbarrier.arrive.shared::cluster.b64 _, [ra];\n}" ::"r"(bar), "r"(rank) : "memory");
}
__device__ __forceinline__ void mbar_wait_p(uint32_t bar, uint32_t parity) {
  asm volatile("{\n.reg .pred p;\nW: mbarrier.try_wait.parity.shared::cta.b64 p, [%0], %1;\n@!p bra W;\n}" ::"r"(bar), "r"(parity) : "memory");
}
__device__ __forceinline__ void mbar_wait(uint32_t bar) { mbar_wait_p(bar, 0); }
__device__ __forceinline__ bool elect_one() {
  uint32_t p;
  asm volatile("{\n.reg .pred P;\nelect.sync _|P, 0xffffffff;\nselp.u32 %0, 1, 0, P;\n}" : "=r"(p));
  return p != 0;
}
__device__ __forceinline__ void bar_sync(int id, int n)   { asm volatile("bar.sync %0, %1;" ::"r"(id), "r"(n) : "memory"); }
__device__ __forceinline__ void bar_arrive(int id, int n) { asm volatile("bar.arrive %0, %1;" ::"r"(id), "r"(n) : "memory"); }
__device__ __forceinline__ void fence_async_smem() { asm volatile("fence.proxy.async.shared::cta;" ::: "memory"); }
__device__ __forceinline__ void wg_fence()  { asm volatile("wgmma.fence.sync.aligned;" ::: "memory"); }
__device__ __forceinline__ void wg_commit() { asm volatile("wgmma.commit_group.sync.aligned;" ::: "memory"); }
template <int N> __device__ __forceinline__ void wg_wait() { asm volatile("wgmma.wait_group.sync.aligned %0;" ::"n"(N) : "memory"); }
#define DESC(off) (db + ((uint32_t)(off) >> 4))
__device__ __forceinline__ void tma2d(uint32_t dst, const CUtensorMap* m, int c0, int c1, uint32_t bar) {
  asm volatile("cp.async.bulk.tensor.2d.shared::cluster.global.mbarrier::complete_tx::bytes [%0], [%1, {%3, %4}], [%2];"
               ::"r"(dst), "l"(m), "r"(bar), "r"(c0), "r"(c1) : "memory");
}
__device__ __forceinline__ void tma2d_mc(uint32_t dst, const CUtensorMap* m, int c0, int c1, uint32_t bar) {
  asm volatile("cp.async.bulk.tensor.2d.shared::cluster.global.mbarrier::complete_tx::bytes.multicast::cluster [%0], [%1, {%3, %4}], [%2], %5;"
               ::"r"(dst), "l"(m), "r"(bar), "r"(c0), "r"(c1), "h"((uint16_t)3) : "memory");
}
__device__ __forceinline__ void tma3d(uint32_t dst, const CUtensorMap* m, int c0, int c1, int c2, uint32_t bar) {
  asm volatile("cp.async.bulk.tensor.3d.shared::cluster.global.mbarrier::complete_tx::bytes [%0], [%1, {%3, %4, %5}], [%2];"
               ::"r"(dst), "l"(m), "r"(bar), "r"(c0), "r"(c1), "r"(c2) : "memory");
}
__device__ __forceinline__ void tma3d_mc(uint32_t dst, const CUtensorMap* m, int c0, int c1, int c2, uint32_t bar) {
  asm volatile("cp.async.bulk.tensor.3d.shared::cluster.global.mbarrier::complete_tx::bytes.multicast::cluster [%0], [%1, {%3, %4, %5}], [%2], %6;"
               ::"r"(dst), "l"(m), "r"(bar), "r"(c0), "r"(c1), "r"(c2), "h"((uint16_t)3) : "memory");
}
__device__ __forceinline__ void ldsm4(uint32_t (&r)[4], uint32_t addr) {
  asm volatile("ldmatrix.sync.aligned.m8n8.x4.shared.b16 {%0,%1,%2,%3}, [%4];"
               : "=r"(r[0]), "=r"(r[1]), "=r"(r[2]), "=r"(r[3]) : "r"(addr) : "memory");
}
__device__ __forceinline__ void ldsm4t(uint32_t (&r)[4], uint32_t addr) {
  asm volatile("ldmatrix.sync.aligned.m8n8.x4.trans.shared.b16 {%0,%1,%2,%3}, [%4];"
               : "=r"(r[0]), "=r"(r[1]), "=r"(r[2]), "=r"(r[3]) : "r"(addr) : "memory");
}
__device__ __forceinline__ void stsm4(uint32_t addr, uint32_t r0, uint32_t r1, uint32_t r2, uint32_t r3) {
  asm volatile("stmatrix.sync.aligned.m8n8.x4.shared.b16 [%0], {%1,%2,%3,%4};"
               ::"r"(addr), "r"(r0), "r"(r1), "r"(r2), "r"(r3) : "memory");
}
__device__ __forceinline__ void mma16816(float (&c)[4], const uint32_t (&a)[4], uint32_t b0, uint32_t b1) {
  asm volatile("mma.sync.aligned.m16n8k16.row.col.f32.bf16.bf16.f32 {%0,%1,%2,%3},{%4,%5,%6,%7},{%8,%9},{%0,%1,%2,%3};"
               : "+f"(c[0]), "+f"(c[1]), "+f"(c[2]), "+f"(c[3])
               : "r"(a[0]), "r"(a[1]), "r"(a[2]), "r"(a[3]), "r"(b0), "r"(b1));
}
__device__ __forceinline__ void add_frag(float (&c)[32], const uint32_t (&a)[4][4], uint32_t id) {
#pragma unroll
  for (int i = 0; i < 8; i++)
    asm volatile("mma.sync.aligned.m16n8k8.row.col.f32.bf16.bf16.f32 {%0,%1,%2,%3},{%4,%5},{%6},{%0,%1,%2,%3};"
                 : "+f"(c[4 * i]), "+f"(c[4 * i + 1]), "+f"(c[4 * i + 2]), "+f"(c[4 * i + 3])
                 : "r"(a[i >> 1][(i & 1) * 2]), "r"(a[i >> 1][(i & 1) * 2 + 1]), "r"(id));
}
__device__ __forceinline__ uint32_t pack2(float lo, float hi) {
  uint32_t r; asm("cvt.rn.bf16x2.f32 %0, %1, %2;" : "=r"(r) : "f"(hi), "f"(lo)); return r;
}
__device__ __forceinline__ float blo(uint32_t w) { return __uint_as_float(w << 16); }
__device__ __forceinline__ float bhi(uint32_t w) { return __uint_as_float(w & 0xFFFF0000u); }
__device__ __forceinline__ uint32_t hsub2(uint32_t a, uint32_t b) { uint32_t r; asm("sub.rn.bf16x2 %0, %1, %2;" : "=r"(r) : "r"(a), "r"(b)); return r; }
__device__ __forceinline__ uint32_t hmax2(uint32_t a, uint32_t b) { uint32_t r; asm("max.bf16x2 %0, %1, %2;" : "=r"(r) : "r"(a), "r"(b)); return r; }
__device__ __forceinline__ uint32_t hmin2(uint32_t a, uint32_t b) { uint32_t r; asm("min.bf16x2 %0, %1, %2;" : "=r"(r) : "r"(a), "r"(b)); return r; }
__device__ __forceinline__ float ex2(float x) { float r; asm("ex2.approx.ftz.f32 %0, %1;" : "=f"(r) : "f"(x)); return r; }
__device__ __forceinline__ float rcp(float x) { float r; asm("rcp.approx.ftz.f32 %0, %1;" : "=f"(r) : "f"(x)); return r; }
__device__ __forceinline__ void ld_rlx4(uint32_t (&r)[4], const uint4* p) {
  asm volatile("{\n.reg .b128 v;\nld.relaxed.gpu.global.b128 v, [%4];\nmov.b128 {%0,%1,%2,%3}, v;\n}"
               : "=r"(r[0]), "=r"(r[1]), "=r"(r[2]), "=r"(r[3]) : "l"(p) : "memory");
}
__device__ __forceinline__ void st_rlx4(uint4* p, uint32_t a, uint32_t b, uint32_t c, uint32_t d) {
  asm volatile("{\n.reg .b128 v;\nmov.b128 v, {%1,%2,%3,%4};\nst.relaxed.gpu.global.b128 [%0], v;\n}"
               ::"l"(p), "r"(a), "r"(b), "r"(c), "r"(d) : "memory");
}
__device__ __forceinline__ void st_rlx2(uint2* p, uint32_t a, uint32_t b) {
  asm volatile("{\n.reg .b64 v;\nmov.b64 v, {%1,%2};\nst.relaxed.gpu.global.b64 [%0], v;\n}" ::"l"(p), "r"(a), "r"(b) : "memory");
}
__device__ __forceinline__ uint32_t ld_rlx1(const uint32_t* p) {
  uint32_t r; asm volatile("ld.relaxed.gpu.global.b32 %0, [%1];" : "=r"(r) : "l"(p) : "memory"); return r;
}
__device__ __forceinline__ void st_rlx1(uint32_t* p, uint32_t a) {
  asm volatile("st.relaxed.gpu.global.b32 [%0], %1;" ::"l"(p), "r"(a) : "memory");
}
__device__ __forceinline__ void ld_rlx2(uint32_t& a, uint32_t& b, const uint2* p) {
  asm volatile("{\n.reg .b64 v;\nld.relaxed.gpu.b64 v, [%2];\nmov.b64 {%0,%1}, v;\n}" : "=r"(a), "=r"(b) : "l"(p) : "memory");
}
__device__ __forceinline__ void bulk_g2s(uint32_t dst, const void* src, uint32_t bytes, uint32_t bar) {
  asm volatile("cp.async.bulk.shared::cluster.global.mbarrier::complete_tx::bytes [%0], [%1], %2, [%3];"
               ::"r"(dst), "l"(src), "r"(bytes), "r"(bar) : "memory");
}
__device__ __forceinline__ uint32_t tg(uint32_t w, uint32_t T) { return (w & 0xFFFFFFFEu) | T; }
__device__ __forceinline__ uint32_t bad4(uint32_t a, uint32_t b, uint32_t c, uint32_t d, uint32_t T) {
  uint32_t u, v;
  asm("lop3.b32 %0, %1, %2, %3, 0x7E;" : "=r"(u) : "r"(a), "r"(b), "r"(T));
  asm("lop3.b32 %0, %1, %2, %3, 0x7E;" : "=r"(v) : "r"(c), "r"(d), "r"(T));
  asm("lop3.b32 %0, %1, %2, 1, 0xA8;" : "=r"(u) : "r"(u), "r"(v));
  return u;
}

__device__ __forceinline__ void ld_chunk(uint32_t (&a)[4][4], const uint4* p) {
#pragma unroll
  for (int s = 0; s < 4; s++) ld_rlx4(a[s], p + s * 32);
}
__device__ __forceinline__ void get_pair(uint32_t (&a)[4][4], uint32_t (&b)[4][4], const uint4* sp, const uint4* gp, uint32_t T) {
  int it = 0;
#pragma unroll 1
  do {
#pragma unroll
    for (int s = 0; s < 8; s++) {
      uint32_t (&r)[4] = s < 4 ? a[s & 3] : b[s & 3];
      asm volatile("{\n.reg .b128 v;\nld.relaxed.gpu.b128 v, [%4];\nmov.b128 {%0,%1,%2,%3}, v;\n}"
                   : "=r"(r[0]), "=r"(r[1]), "=r"(r[2]), "=r"(r[3]) : "l"(sp + (s >> 2) * 512 + (s & 3) * 32) : "memory");
    }
    sp = gp;
  } while (__any_sync(0xffffffffu, bad4(a[0][0], a[1][0], a[2][0], a[3][0], T) | bad4(b[0][0], b[1][0], b[2][0], b[3][0], T)) && ++it < (1 << 18));
}

__device__ __forceinline__ void wgmma_rs_n48(float (&d)[24], const uint32_t (&a)[4], uint32_t descB, int scaleD) {
  asm volatile("{\n.reg .pred p;\n.reg .b64 db;\nsetp.ne.b32 p, %29, 0;\nmov.b64 db, {%28, 0x40000040};\n"
    "wgmma.mma_async.sync.aligned.m64n48k16.f32.bf16.bf16 {%0,%1,%2,%3,%4,%5,%6,%7,%8,%9,%10,%11,%12,%13,%14,%15,%16,%17,%18,%19,%20,%21,%22,%23}, {%24,%25,%26,%27}, db, p, 1, 1, 1;\n}\n"
    : "+f"(d[0]),"+f"(d[1]),"+f"(d[2]),"+f"(d[3]),"+f"(d[4]),"+f"(d[5]),"+f"(d[6]),"+f"(d[7]),"+f"(d[8]),"+f"(d[9]),"+f"(d[10]),"+f"(d[11]),"+f"(d[12]),"+f"(d[13]),"+f"(d[14]),"+f"(d[15]),"+f"(d[16]),"+f"(d[17]),"+f"(d[18]),"+f"(d[19]),"+f"(d[20]),"+f"(d[21]),"+f"(d[22]),"+f"(d[23])
    : "r"(a[0]), "r"(a[1]), "r"(a[2]), "r"(a[3]), "r"(descB), "r"(scaleD));
}
__device__ __forceinline__ void wgmma_rs_n64(float (&d)[32], const uint32_t (&a)[4], uint32_t descB, int scaleD) {
  asm volatile("{\n.reg .pred p;\n.reg .b64 db;\nsetp.ne.b32 p, %37, 0;\nmov.b64 db, {%36, 0x40000040};\n"
    "wgmma.mma_async.sync.aligned.m64n64k16.f32.bf16.bf16 {%0,%1,%2,%3,%4,%5,%6,%7,%8,%9,%10,%11,%12,%13,%14,%15,%16,%17,%18,%19,%20,%21,%22,%23,%24,%25,%26,%27,%28,%29,%30,%31}, {%32,%33,%34,%35}, db, p, 1, 1, 1;\n}\n"
    : "+f"(d[0]),"+f"(d[1]),"+f"(d[2]),"+f"(d[3]),"+f"(d[4]),"+f"(d[5]),"+f"(d[6]),"+f"(d[7]),"+f"(d[8]),"+f"(d[9]),"+f"(d[10]),"+f"(d[11]),"+f"(d[12]),"+f"(d[13]),"+f"(d[14]),"+f"(d[15]),"+f"(d[16]),"+f"(d[17]),"+f"(d[18]),"+f"(d[19]),"+f"(d[20]),"+f"(d[21]),"+f"(d[22]),"+f"(d[23]),"+f"(d[24]),"+f"(d[25]),"+f"(d[26]),"+f"(d[27]),"+f"(d[28]),"+f"(d[29]),"+f"(d[30]),"+f"(d[31])
    : "r"(a[0]), "r"(a[1]), "r"(a[2]), "r"(a[3]), "r"(descB), "r"(scaleD));
}
__device__ __forceinline__ void wgmma_rs_n128(float (&d)[64], const uint32_t (&a)[4], uint32_t descB, int scaleD) {
  asm volatile("{\n.reg .pred p;\n.reg .b64 db;\nsetp.ne.b32 p, %69, 0;\nmov.b64 db, {%68, 0x40000040};\n"
    "wgmma.mma_async.sync.aligned.m64n128k16.f32.bf16.bf16 {%0,%1,%2,%3,%4,%5,%6,%7,%8,%9,%10,%11,%12,%13,%14,%15,%16,%17,%18,%19,%20,%21,%22,%23,%24,%25,%26,%27,%28,%29,%30,%31,%32,%33,%34,%35,%36,%37,%38,%39,%40,%41,%42,%43,%44,%45,%46,%47,%48,%49,%50,%51,%52,%53,%54,%55,%56,%57,%58,%59,%60,%61,%62,%63}, {%64,%65,%66,%67}, db, p, 1, 1, 1;\n}\n"
    : "+f"(d[0]),"+f"(d[1]),"+f"(d[2]),"+f"(d[3]),"+f"(d[4]),"+f"(d[5]),"+f"(d[6]),"+f"(d[7]),"+f"(d[8]),"+f"(d[9]),"+f"(d[10]),"+f"(d[11]),"+f"(d[12]),"+f"(d[13]),"+f"(d[14]),"+f"(d[15]),"+f"(d[16]),"+f"(d[17]),"+f"(d[18]),"+f"(d[19]),"+f"(d[20]),"+f"(d[21]),"+f"(d[22]),"+f"(d[23]),"+f"(d[24]),"+f"(d[25]),"+f"(d[26]),"+f"(d[27]),"+f"(d[28]),"+f"(d[29]),"+f"(d[30]),"+f"(d[31]),"+f"(d[32]),"+f"(d[33]),"+f"(d[34]),"+f"(d[35]),"+f"(d[36]),"+f"(d[37]),"+f"(d[38]),"+f"(d[39]),"+f"(d[40]),"+f"(d[41]),"+f"(d[42]),"+f"(d[43]),"+f"(d[44]),"+f"(d[45]),"+f"(d[46]),"+f"(d[47]),"+f"(d[48]),"+f"(d[49]),"+f"(d[50]),"+f"(d[51]),"+f"(d[52]),"+f"(d[53]),"+f"(d[54]),"+f"(d[55]),"+f"(d[56]),"+f"(d[57]),"+f"(d[58]),"+f"(d[59]),"+f"(d[60]),"+f"(d[61]),"+f"(d[62]),"+f"(d[63])
    : "r"(a[0]), "r"(a[1]), "r"(a[2]), "r"(a[3]), "r"(descB), "r"(scaleD));
}
__device__ __forceinline__ void wgmma_ss_n72_t11(float (&d)[36], uint32_t descA, uint32_t descB, int scaleD) {
  asm volatile("{\n.reg .pred p;\n.reg .b64 da, db;\nsetp.ne.b32 p, %38, 0;\nmov.b64 da, {%36, 0x40000040};\nmov.b64 db, {%37, 0x40000040};\n"
    "wgmma.mma_async.sync.aligned.m64n72k16.f32.bf16.bf16 {%0,%1,%2,%3,%4,%5,%6,%7,%8,%9,%10,%11,%12,%13,%14,%15,%16,%17,%18,%19,%20,%21,%22,%23,%24,%25,%26,%27,%28,%29,%30,%31,%32,%33,%34,%35}, da, db, p, 1, 1, 1, 1;\n}\n"
    : "+f"(d[0]),"+f"(d[1]),"+f"(d[2]),"+f"(d[3]),"+f"(d[4]),"+f"(d[5]),"+f"(d[6]),"+f"(d[7]),"+f"(d[8]),"+f"(d[9]),"+f"(d[10]),"+f"(d[11]),"+f"(d[12]),"+f"(d[13]),"+f"(d[14]),"+f"(d[15]),"+f"(d[16]),"+f"(d[17]),"+f"(d[18]),"+f"(d[19]),"+f"(d[20]),"+f"(d[21]),"+f"(d[22]),"+f"(d[23]),"+f"(d[24]),"+f"(d[25]),"+f"(d[26]),"+f"(d[27]),"+f"(d[28]),"+f"(d[29]),"+f"(d[30]),"+f"(d[31]),"+f"(d[32]),"+f"(d[33]),"+f"(d[34]),"+f"(d[35])
    : "r"(descA), "r"(descB), "r"(scaleD));
}

#define TSTAMP(i) do {} while (0)
#define TS2(w, i) do {} while (0)

constexpr float LOG2E = 1.4426950408889634f;

__device__ __forceinline__ void feat_exp(const uint32_t (&P)[4], float (&e)[16]) {
  uint32_t a = hmax2(P[0], P[2]), b = hmax2(P[1], P[3]);
  uint32_t mx = hmax2(__byte_perm(a, b, 0x5410), __byte_perm(a, b, 0x7632));
  a = hmin2(P[0], P[2]); b = hmin2(P[1], P[3]);
  uint32_t mn = hmin2(__byte_perm(a, b, 0x5410), __byte_perm(a, b, 0x7632));
  mx = hmax2(mx, __shfl_xor_sync(0xffffffffu, mx, 1));
  mn = hmin2(mn, __shfl_xor_sync(0xffffffffu, mn, 1));
  mx = hmax2(mx, __shfl_xor_sync(0xffffffffu, mx, 2));
  mn = hmin2(mn, __shfl_xor_sync(0xffffffffu, mn, 2));
  float mx0 = -blo(mx) * LOG2E, mx1 = -bhi(mx) * LOG2E, mn0 = blo(mn) * LOG2E, mn1 = bhi(mn) * LOG2E;
  float v[8] = {blo(P[0]), bhi(P[0]), blo(P[1]), bhi(P[1]), blo(P[2]), bhi(P[2]), blo(P[3]), bhi(P[3])};
#pragma unroll
  for (int i = 0; i < 8; i++) {
    bool r1 = (i >> 1) & 1;
    e[i]     = ex2(fmaf(v[i],  LOG2E, r1 ? mx1 : mx0));
    e[8 + i] = ex2(fmaf(v[i], -LOG2E, r1 ? mn1 : mn0));
  }
}

__global__ void __cluster_dims__(2, 1, 1) __launch_bounds__(384, 1)
fused_kernel(const __grid_constant__ Maps maps, const __nv_bfloat16* __restrict__ x, const __nv_bfloat16* __restrict__ wphi,
             const __nv_bfloat16* __restrict__ wo, const __nv_bfloat16* __restrict__ wg_, const __nv_bfloat16* __restrict__ wu_,
             const __nv_bfloat16* __restrict__ wd_, __nv_bfloat16* __restrict__ out) {
  extern __shared__ __align__(1024) unsigned char smem[];
  const uint32_t sb = smem_u32(smem);
  const int tid = threadIdx.x, lane = tid & 31;
  const int warp = __shfl_sync(0xffffffffu, tid >> 5, 0);
  const uint32_t rank = blockIdx.x & 1;
  const int cl = blockIdx.x >> 1;
  int quad, qi;
  if (cl < 4) { quad = 15; qi = cl; }
  else if (cl < 36) { quad = (cl - 4) & 7; qi = (cl - 4) >> 3; }
  else { qi = (cl - 36) / 7; quad = 8 + (cl - 36) - 7 * qi; }
  const int rb = quad, hg = 2 * qi + rank;
  const int rb3 = (quad & ~1) + rank, jf = 4 * (quad & 1) + qi;

  if (warp < 8) {
    asm volatile("setmaxnreg.inc.sync.aligned.u32 240;");
    if (elect_one()) {
#pragma unroll 1
      for (int d = warp; d + 9 < NSTAGE; d += 8) {
        mbar_init(sb + SM_EMPTY + d * 8, st_empty_cnt(d));
        {
          mbar_init(sb + SM_FULL + (d + 9) * 8, 1);
          mbar_expect_tx(sb + SM_FULL + (d + 9) * 8, d + 9 >= ST_D ? 22528 : SLOT);
        }
      }
      asm volatile("fence.mbarrier_init.release.cluster;" ::: "memory");
    }
    __syncwarp();
    bar_sync(0, 352);
    asm volatile("barrier.cluster.arrive.relaxed.aligned;" ::: "memory");
    const int wg = warp >> 2, wq = warp & 3, g = lane >> 2, t = lane & 3;
    const bool lead = (tid & 127) == 0;
    constexpr uint32_t db = (SM_BASE >> 4) | (512u << 16);
    auto release = [&](int d) {
      const int s = d + NSLOT;
      mbar_arrive_cluster(sb + SM_EMPTY + d * 8, s >= ST_GU ? (uint32_t)(s & 1) : rank);
    };
    const uint32_t lrow = (uint32_t)(wq * 16 + (lane & 7) + ((lane >> 3) & 1) * 8) * 128;
    const uint32_t lx = lane & 7, lhi = lane >> 4;
    if (wg == 1) bar_arrive(4, 256);

    float r0, r1;
    uint32_t E[4][8];
    uint32_t T = 0;
    {
      uint32_t A[32][4];
      const int sx = wg ? ST_X1 : ST_X0;
      {
        const uint32_t base = sb + sx * SLOT + lrow, baseb = sb + sx * SLOT + (wq * 16 + lx + lhi * 8) * 128;
        float cs[2][4], c0[2][4], c1[2][4];
#pragma unroll
        for (int i = 0; i < 4; i++) { cs[0][i] = cs[1][i] = c0[0][i] = c0[1][i] = c1[0][i] = c1[1][i] = 0.f; }
#pragma unroll
        for (int c = 0; c < 8; c++) {
          if (c % 3 == 0) mbar_wait(sb + SM_FULL + (sx + c / 3) * 8);
#pragma unroll
          for (int k = 0; k < 4; k++) ldsm4(A[4 * c + k], base + c * 8192 + (((2 * k + lhi) ^ lx) << 4));
#pragma unroll
          for (int k = 0; k < 4; k++) {
            const uint32_t (&f)[4] = A[4 * c + k];
            uint32_t bt[4];
            ldsm4(bt, baseb + c * 8192 + (((2 * k + ((lane >> 3) & 1)) ^ lx) << 4));
            mma16816(cs[k & 1], f, 0x3F803F80u, 0x3F803F80u);
            mma16816(c0[k & 1], f, bt[0], bt[1]);
            mma16816(c1[k & 1], f, bt[2], bt[3]);
          }
        }
        const float s0 = (cs[0][0] + cs[1][0]) * (1.f / 512.f), s1 = (cs[0][2] + cs[1][2]) * (1.f / 512.f);
        asm volatile("barrier.cluster.wait.aligned;" ::: "memory");
        if (lane < 3) release(sx + lane);
        const uint32_t m0 = pack2(s0, s0), m1 = pack2(s1, s1);
        float q0 = (g & 1) ? c0[0][1] + c0[1][1] : c0[0][0] + c0[1][0];
        float q1 = (g & 1) ? c1[0][3] + c1[1][3] : c1[0][2] + c1[1][2];
        q0 = __shfl_sync(0xffffffffu, q0, (lane & ~3) | (g >> 1));
        q1 = __shfl_sync(0xffffffffu, q1, (lane & ~3) | (g >> 1));
        r0 = rsqrtf(fmaxf(q0 * (1.f / 512.f) - s0 * s0, 0.f) + 1e-5f);
        r1 = rsqrtf(fmaxf(q1 * (1.f / 512.f) - s1 * s1, 0.f) + 1e-5f);
#pragma unroll
        for (int ks = 0; ks < 32; ks++) {
          A[ks][0] = hsub2(A[ks][0], m0); A[ks][1] = hsub2(A[ks][1], m1);
          A[ks][2] = hsub2(A[ks][2], m0); A[ks][3] = hsub2(A[ks][3], m1);
        }
      }
      TSTAMP(1);
      const uint32_t wpa = sb + SM_WPHI + ((lane & 7) + ((lane >> 3) & 1) * 8) * 32 + lhi * 16;
      const uint32_t scr = sb + (wg ? (ST_SCR1 % NSLOT) : (ST_SCR0 % NSLOT)) * SLOT;
#pragma unroll 1
      for (int ps = 0; ps < 3; ps++) {
        const int st0 = ps == 0 ? ST_WK : (ps == 1 ? ST_WV : ST_WQ);
        const uint32_t wdesc = DESC((ps == 0 ? ST_WK % NSLOT : (ps == 1 ? ST_WV % NSLOT : ST_WQ % NSLOT)) * SLOT);
        float acc[32];
        bar_sync(4 + wg, 256);
#pragma unroll
        for (int i = 0; i < 3; i++) {
          mbar_wait(sb + SM_FULL + (st0 + i) * 8);
          wg_fence();
#pragma unroll
          for (int kk = 0; kk < (i < 2 ? 12 : 8); kk++)
            wgmma_rs_n64(acc, A[12 * i + kk], wdesc + ((i * SLOT + kk * 2048) >> 4), (i | kk) != 0);
          wg_commit();
          if (i == 1) { wg_wait<1>(); if (lead) release(st0); }
        }
        if (ps == 1 && wg == 0) bar_arrive(5, 256);
        uint32_t a[4][4], b[4][4];
        mbar_wait(sb + SM_MISCB);
        T = (*reinterpret_cast<volatile unsigned*>(smem + SM_EPOCH) & 1) ^ 1;
#pragma unroll
        for (int h = 0; h < 4; h++) ldsm4t(b[h], wpa + h * 512);
        wg_wait<0>();
        if ((tid & 127) < 2) release(st0 + 1 + (tid & 1));
        TSTAMP(2 + 2 * ps);
#pragma unroll
        for (int h = 0; h < 4; h++) {
          a[h][0] = pack2(acc[8 * h + 0] * r0, acc[8 * h + 1] * r0); a[h][1] = pack2(acc[8 * h + 2] * r1, acc[8 * h + 3] * r1);
          a[h][2] = pack2(acc[8 * h + 4] * r0, acc[8 * h + 5] * r0); a[h][3] = pack2(acc[8 * h + 6] * r1, acc[8 * h + 7] * r1);
        }
        if (ps != 1) {
          {
            float pp[4][2][4];
#pragma unroll
            for (int h = 0; h < 4; h++) {
#pragma unroll
              for (int i = 0; i < 4; i++) { pp[h][0][i] = 0.f; pp[h][1][i] = 0.f; }
              mma16816(pp[h][0], a[h], b[h][0], b[h][1]);
              mma16816(pp[h][1], a[h], b[h][2], b[h][3]);
            }
#pragma unroll
            for (int h = 0; h < 4; h++) {
              a[h][0] = pack2(pp[h][0][0], pp[h][0][1]); a[h][1] = pack2(pp[h][0][2], pp[h][0][3]);
              a[h][2] = pack2(pp[h][1][0], pp[h][1][1]); a[h][3] = pack2(pp[h][1][2], pp[h][1][3]);
            }
          }
          if (ps == 0 || wg == 0) bar_arrive(4 + (wg ^ 1), 256);
          if (ps == 0) mbar_wait(sb + SM_EMPTY + (wg ? ST_SCR1 - NSLOT : ST_SCR0 - NSLOT) * 8);
#pragma unroll 1
          for (int hp = 0; hp < 2; hp++) {
            float e[2][16];
            feat_exp(a[0], e[0]);
            feat_exp(a[1], e[1]);
            if (ps == 0) {
#pragma unroll
              for (int h = 0; h < 2; h++) {
                const float (&f)[16] = e[h];
                float sp0 = (f[0] + f[1]) + (f[4] + f[5]), sp1 = (f[2] + f[3]) + (f[6] + f[7]);
                float sn0 = (f[8] + f[9]) + (f[12] + f[13]), sn1 = (f[10] + f[11]) + (f[14] + f[15]);
                sp0 += __shfl_xor_sync(0xffffffffu, sp0, 1); sp1 += __shfl_xor_sync(0xffffffffu, sp1, 1);
                sn0 += __shfl_xor_sync(0xffffffffu, sn0, 1); sn1 += __shfl_xor_sync(0xffffffffu, sn1, 1);
                sp0 += __shfl_xor_sync(0xffffffffu, sp0, 2); sp1 += __shfl_xor_sync(0xffffffffu, sp1, 2);
                sn0 += __shfl_xor_sync(0xffffffffu, sn0, 2); sn1 += __shfl_xor_sync(0xffffffffu, sn1, 2);
                sp0 = rcp(sp0); sp1 = rcp(sp1); sn0 = rcp(sn0); sn1 = rcp(sn1);
                const uint32_t dst = scr + hp * 8192 + lrow;
                stsm4(dst + (((h * 4 + lhi) ^ lx) << 4), pack2(f[0] * sp0, f[1] * sp0), pack2(f[2] * sp1, f[3] * sp1),
                      pack2(f[4] * sp0, f[5] * sp0), pack2(f[6] * sp1, f[7] * sp1));
                stsm4(dst + (((h * 4 + 2 + lhi) ^ lx) << 4), pack2(f[8] * sn0, f[9] * sn0), pack2(f[10] * sn1, f[11] * sn1),
                      pack2(f[12] * sn0, f[13] * sn0), pack2(f[14] * sn1, f[15] * sn1));
              }
            } else {
#pragma unroll
              for (int i = 0; i < 16; i++) {
                A[i >> 2][i & 3] = A[4 + (i >> 2)][i & 3];
                A[4 + (i >> 2)][i & 3] = pack2(e[i >> 3][2 * (i & 7)], e[i >> 3][2 * (i & 7) + 1]);
              }
            }
#pragma unroll
            for (int i = 0; i < 4; i++) { a[0][i] = a[2][i]; a[1][i] = a[3][i]; }
          }
        } else {
#pragma unroll
          for (int h = 0; h < 4; h++) stsm4(scr + 16384 + lrow + (((2 * h + lhi) ^ lx) << 4), a[h][0], a[h][1], a[h][2], a[h][3]);
          fence_async_smem();
          bar_sync(3, 256);
          float kv[36];
          wg_fence();
#pragma unroll
          for (int ks = 0; ks < 8; ks++) {
            const uint32_t sk = (ks < 4 ? (ST_SCR0 % NSLOT) : (ST_SCR1 % NSLOT)) * SLOT + (ks & 3) * 2048;
            const uint32_t dv = (DESC(sk + 16384) & 0xFFFFu) | (((SM_ONES - sk - 16384) >> 4) << 16);
            wgmma_ss_n72_t11(kv, DESC(sk) + wg * 512, dv, ks != 0);
          }
          wg_commit();
          if (wg == 1) bar_arrive(4, 256);
          wg_wait<0>();
          if (lead) { mbar_arrive(sb + SM_EMPTY + ST_SCR0 * 8); mbar_arrive(sb + SM_EMPTY + ST_SCR1 * 8); }
          const int hl = 2 * wg + (wq >> 1), f = (wq & 1) * 16 + g;
          float* kvp = reinterpret_cast<float*>(smem + 2 * SLOT) + (hl * 32 + f) * 16 + 2 * t;
          float c[8];
#pragma unroll
          for (int i = 0; i < 8; i++) c[i] = hl >= 2 ? (hl == 3 ? kv[24 + i] : kv[16 + i]) : (hl == 1 ? kv[8 + i] : kv[i]);
#pragma unroll
          for (int n = 0; n < 2; n++) {
            *reinterpret_cast<float2*>(kvp + n * 8) = make_float2(c[4 * n], c[4 * n + 1]);
            *reinterpret_cast<float2*>(kvp + n * 8 + 128) = make_float2(c[4 * n + 2], c[4 * n + 3]);
          }
          if (t < 2) reinterpret_cast<float*>(smem + 2 * SLOT)[2048 + hl * 32 + f + t * 8] = t ? kv[34] : kv[32];
          fence_async_smem();
          bar_sync(6, 320);
        }
        TSTAMP(3 + 2 * ps);
      }
#pragma unroll
      for (int i = 0; i < 32; i++) E[i >> 3][i & 7] = A[i >> 2][i & 3];
    }
    const int rh = 2 * rb + wg;
#define IDF ((g >> 1) == t ? ((g & 1) ? 0x3F800000u : 0x00003F80u) : 0u)
    const uint4* xb = reinterpret_cast<const uint4*>(smem + 2 * SLOT) + wq * 128 + lane;
    mbar_wait(sb + SM_KVB);
    {
      const int r = tid & 127;
      const float4* src = reinterpret_cast<const float4*>(smem + SM_KV32) + r;
#pragma unroll
      for (int i = 0; i < 4; i++) {
        const float4 a = src[i * 128];
        *reinterpret_cast<uint2*>(smem + SM_KVS + (i * 32 + (r >> 2)) * 48 + (r & 3) * 8) = make_uint2(pack2(a.x, a.y), pack2(a.z, a.w));
      }
      const uint32_t zz = pack2(reinterpret_cast<const float*>(smem + SM_ONES)[r], 1.0f);
      *reinterpret_cast<uint4*>(smem + SM_KVS + r * 48 + 32) = make_uint4(zz, zz, zz, zz);
      bar_sync(1 + wg, 128);
    }
    TSTAMP(8);
    {
      uint4* op = &g_o[rh][hg][wq][0][lane];
      if (wg == 1) bar_sync(5, 256);
#pragma unroll 1
      for (int hp = 0; hp < 2; hp++) {
#pragma unroll
      for (int h = 0; h < 2; h++) {
        uint32_t b0[4], b1[4], b2[4];
        const uint32_t kb = sb + SM_KVS + ((2 * hp + h) * 32 + lane) * 48;
        ldsm4t(b0, kb); ldsm4t(b1, kb + 16); ldsm4t(b2, kb + 32);
        const uint32_t ep[4] = {E[h][0], E[h][1], E[h][2], E[h][3]}, en[4] = {E[h][4], E[h][5], E[h][6], E[h][7]};
        float np0[4] = {0, 0, 0, 0}, np1[4] = {0, 0, 0, 0}, nn0[4] = {0, 0, 0, 0}, nn1[4] = {0, 0, 0, 0}, dp[4] = {0, 0, 0, 0}, dn[4] = {0, 0, 0, 0};
        mma16816(dp, ep, b2[0], b2[1]);  mma16816(dn, en, b2[2], b2[3]);
        mma16816(np0, ep, b0[0], b0[1]); mma16816(nn0, en, b0[2], b0[3]);
        mma16816(np1, ep, b1[0], b1[1]); mma16816(nn1, en, b1[2], b1[3]);
        const float i0 = rcp(fmaf(dp[0], dn[1], fmaf(dn[0], dp[1], 1e-6f * dp[1] * dn[1])));
        const float i1 = rcp(fmaf(dp[2], dn[3], fmaf(dn[2], dp[3], 1e-6f * dp[3] * dn[3])));
        const float cp0 = dn[1] * i0, cn0 = dp[1] * i0, cp1 = dn[3] * i1, cn1 = dp[3] * i1;
        st_rlx4(op + (2 * hp + h) * 32,
                tg(pack2(fmaf(np0[0], cp0, nn0[0] * cn0), fmaf(np0[1], cp0, nn0[1] * cn0)), T),
                pack2(fmaf(np0[2], cp1, nn0[2] * cn1), fmaf(np0[3], cp1, nn0[3] * cn1)),
                pack2(fmaf(np1[0], cp0, nn1[0] * cn0), fmaf(np1[1], cp0, nn1[1] * cn0)),
                pack2(fmaf(np1[2], cp1, nn1[2] * cn1), fmaf(np1[3], cp1, nn1[3] * cn1)));
      }
#pragma unroll
        for (int i = 0; i < 8; i++) { E[0][i] = E[2][i]; E[1][i] = E[3][i]; }
      }
    }
    if (wg == 0) bar_arrive(5, 256);
    TSTAMP(9);

    {
      uint32_t xr[4][4];
      {
        const uint32_t* xp = reinterpret_cast<const uint32_t*>(x + (size_t)(rh * 64 + wq * 16 + g) * 512 + hg * 64 + 2 * t);
#pragma unroll
        for (int i = 0; i < 8; i++) { xr[i >> 1][(i & 1) * 2] = __ldg(xp + 4 * i); xr[i >> 1][(i & 1) * 2 + 1] = __ldg(xp + 8 * 256 + 4 * i); }
      }
      uint32_t A[8][4][4];
      const uint4* op = &g_o[rh][0][wq][0][lane];
      float acc[32];
#pragma unroll
      for (int i = 0; i < 32; i++) acc[i] = 0.f;
      add_frag(acc, xr, IDF);
#pragma unroll
      for (int p = -1; p < 4; p++) {
        if (p < 3) {
          mbar_wait(sb + SM_XF + (wg * 4 + p + 1) * 8);
          if (p == -1) TSTAMP(18);
          get_pair(A[2 * p + 2], A[2 * p + 3], xb + (p + 1) * 1024, op + (p + 1) * 1024, T);
          if (lane == 0) mbar_arrive(sb + SM_XE + (wg * 4 + p + 1) * 8);
        }
        if (p == 0 && wg == 1) bar_sync(4, 256);
        if (p >= 0) {
          if (p != 2) mbar_wait(sb + SM_FULL + (ST_WO + (p + 1) / 2) * 8);
          wg_fence();
#pragma unroll
          for (int c = 2 * p; c < 2 * p + 2; c++)
#pragma unroll
            for (int s = 0; s < 4; s++)
              wgmma_rs_n64(acc, A[c][s], DESC(((ST_WO + c / 3) % NSLOT) * SLOT + ((c % 3) * 4 + s) * 2048), 1);
        }
      }
      wg_commit();
      if (wg == 0) bar_arrive(4, 256);
      wg_wait<0>();
      if ((tid & 127) < 3) release(ST_WO + (tid & 127));
      TSTAMP(10);
      uint4* hp_ = &g_h[rh][hg][wq][0][lane];
      uint32_t hx = T;
#pragma unroll
      for (int s = 0; s < 4; s++) {
        const uint32_t h0 = pack2(acc[8 * s], acc[8 * s + 1]);
        st_rlx4(hp_ + s * 32, tg(h0, T), pack2(acc[8 * s + 2], acc[8 * s + 3]), pack2(acc[8 * s + 4], acc[8 * s + 5]), pack2(acc[8 * s + 6], acc[8 * s + 7]));
        hx |= (h0 & 1u) << (s + 1);
      }
      float s0 = 0.f, s1 = 0.f, q0 = 0.f, q1 = 0.f, q2 = 0.f, q3 = 0.f;
#pragma unroll
      for (int i = 0; i < 8; i++) {
        s0 += acc[4 * i] + acc[4 * i + 1]; s1 += acc[4 * i + 2] + acc[4 * i + 3];
        q0 = fmaf(acc[4 * i], acc[4 * i], q0); q2 = fmaf(acc[4 * i + 1], acc[4 * i + 1], q2);
        q1 = fmaf(acc[4 * i + 2], acc[4 * i + 2], q1); q3 = fmaf(acc[4 * i + 3], acc[4 * i + 3], q3);
      }
      q0 += q2; q1 += q3;
      {
        const bool up = t & 2;
        float s = (up ? s1 : s0) + __shfl_xor_sync(0xffffffffu, up ? s0 : s1, 2);
        float q = (up ? q1 : q0) + __shfl_xor_sync(0xffffffffu, up ? q0 : q1, 2);
        s += __shfl_xor_sync(0xffffffffu, s, 1);
        q += __shfl_xor_sync(0xffffffffu, q, 1);
        if (!(t & 1)) st_rlx2(&g_st[rh][hg][wq * 16 + g + (t >> 1) * 8], tg(__float_as_uint(s), T), __float_as_uint(q));
      }
      st_rlx1(&g_hx[rh][hg][wq][lane], hx);
    }
    TSTAMP(11);

    const int rh3 = 2 * rb3 + wg;
    uint32_t HH[11][4], PH[11][4];
    const uint4* pp = &g_hh[rh3][jf ^ 1][0][wq][lane];
    {
      uint32_t A[8][4][4];
      const uint4* hp_ = &g_h[rh3][0][wq][0][lane];
      uint4* hhp = &g_hh[rh3][jf][0][wq][lane];
      const uint32_t dg = (db & 0xFFFFu) | (256u << 16);
      uint32_t m0, m1;
      mbar_wait(sb + SM_XF + ((2 + wg) * 4) * 8);
      TSTAMP(0);
      {
        const uint2* sp = reinterpret_cast<const uint2*>(smem + SM_KV32 + wg * 4096) + 2 * t * 64 + wq * 16 + g;
        uint2 a0, a1, b0, b1;
        int it = 0;
#pragma unroll 1
        do {
          ld_rlx2(a0.x, a0.y, sp); ld_rlx2(a1.x, a1.y, sp + 64); ld_rlx2(b0.x, b0.y, sp + 8); ld_rlx2(b1.x, b1.y, sp + 72);
          sp = &g_st[rh3][2 * t][wq * 16 + g];
        } while (__any_sync(0xffffffffu, bad4(a0.x, a1.x, b0.x, b1.x, T)) && ++it < (1 << 18));
        float s0 = __uint_as_float(a0.x) + __uint_as_float(a1.x), q0 = __uint_as_float(a0.y) + __uint_as_float(a1.y);
        float s1 = __uint_as_float(b0.x) + __uint_as_float(b1.x), q1 = __uint_as_float(b0.y) + __uint_as_float(b1.y);
        s0 += __shfl_xor_sync(0xffffffffu, s0, 1); s1 += __shfl_xor_sync(0xffffffffu, s1, 1);
        q0 += __shfl_xor_sync(0xffffffffu, q0, 1); q1 += __shfl_xor_sync(0xffffffffu, q1, 1);
        s0 += __shfl_xor_sync(0xffffffffu, s0, 2); s1 += __shfl_xor_sync(0xffffffffu, s1, 2);
        q0 += __shfl_xor_sync(0xffffffffu, q0, 2); q1 += __shfl_xor_sync(0xffffffffu, q1, 2);
        s0 *= (1.f / 512.f); s1 *= (1.f / 512.f);
        r0 = rcp(fmaxf(q0 * (1.f / 512.f) - s0 * s0, 0.f) + 1e-5f);
        r1 = rcp(fmaxf(q1 * (1.f / 512.f) - s1 * s1, 0.f) + 1e-5f);
        m0 = pack2(s0, s0); m1 = pack2(s1, s1);
      }
      TSTAMP(12);
#define UOFF(u) ((((ST_GU + (u) / 3) % NSLOT) * SLOT + ((u) % 3) * 8192) >> 4)
#define UNIT_PRE(u)  do { if ((u) % 3 == 0) mbar_wait(sb + SM_FULL + (ST_GU + (u) / 3) * 8); } while (0)
#define UNIT_POST(u) do { wg_commit(); if ((u) % 3 == 1 && (u) > 3) { wg_wait<2>(); if (lead) release(ST_GU + (u) / 3 - 1); } } while (0)
      float acc[64];
      const int rz = blockIdx.y;
#pragma unroll
      for (int ps = 0; ps < 2; ps++) {
        wg_fence();
#pragma unroll
        for (int k = 0; k < 16; k++) {
          const int u = 16 * ps + k, c = k >> 1;
          if (ps == 0 && (k == 0 || k == 4 || k == 8)) {
#pragma unroll
            for (int p = (k == 0 ? 0 : (k == 4 ? 1 : 3)); p < (k == 0 ? 1 : (k == 4 ? 3 : 4)); p++) {
              if (p > 0) mbar_wait(sb + SM_XF + ((2 + wg) * 4 + p) * 8);
              get_pair(A[2 * p], A[2 * p + 1], xb + p * 1024, hp_ + p * 1024, T);
              if (lane == 0) {
                if (wg == 0) mbar_arrive(sb + SM_XE + (8 + p) * 8);
                else if (p > 0) release(ST_XC + p - 1);
              }
            }
          }
          if (ps == 0 && (k & 1) == 0) {
#pragma unroll
            for (int s = 0; s < 4; s++) {
              A[c][s][0] = hsub2(A[c][s][0], m0); A[c][s][1] = hsub2(A[c][s][1], m1);
              A[c][s][2] = hsub2(A[c][s][2], m0); A[c][s][3] = hsub2(A[c][s][3], m1);
            }
            wg_fence();
          }
          UNIT_PRE(u);
          wgmma_rs_n128(acc, A[c][(k & 1) * 2], dg + UOFF(u), k != 0 ? 1 : (ps ? rz : 0));
          wgmma_rs_n128(acc, A[c][(k & 1) * 2 + 1], dg + UOFF(u) + 128, 1);
          UNIT_POST(u);
          if (ps == 0 && k == 7) TSTAMP(17);
        }
        wg_wait<0>();
        TSTAMP(22 + ps);
#pragma unroll
        for (int s = 0; s < 4; s++) {
          uint32_t (&hh)[4] = HH[4 + s];
          hh[0] = tg(pack2(acc[8 * s + 0] * acc[32 + 8 * s + 0], acc[8 * s + 1] * acc[32 + 8 * s + 1]), T);
          hh[1] = pack2(acc[8 * s + 2] * acc[32 + 8 * s + 2], acc[8 * s + 3] * acc[32 + 8 * s + 3]);
          hh[2] = pack2(acc[8 * s + 4] * acc[32 + 8 * s + 4], acc[8 * s + 5] * acc[32 + 8 * s + 5]);
          hh[3] = pack2(acc[8 * s + 6] * acc[32 + 8 * s + 6], acc[8 * s + 7] * acc[32 + 8 * s + 7]);
          st_rlx4(hhp + (4 * ps + s) * 128, hh[0], hh[1], hh[2], hh[3]);
        }
      }
      {
        float ag[24], au[24];
        const uint32_t* ph7 = reinterpret_cast<const uint32_t*>(&g_hh[rh3][jf ^ 1][7][wq][31]);
        uint32_t hv = 0;
        bar_sync(1 + wg, 128);
        wg_fence();
#pragma unroll
        for (int k = 0; k < 16; k++) {
          const int u = 32 + k, c = k >> 1;
          if (k == 6) {
#pragma unroll
            for (int s = 0; s < 4; s++) ld_rlx4(HH[s], hhp + s * 128);
          }
          if (k == 9) hv = ld_rlx1(ph7);
          if (k == 12) {
            int it = 0;
#pragma unroll 1
            while (((hv ^ T) & 1) && ++it < (1 << 18)) hv = ld_rlx1(ph7);
#pragma unroll
            for (int s = 0; s < 8; s++) ld_rlx4(PH[s], pp + s * 128);
          }
          UNIT_PRE(u);
          wgmma_rs_n48(ag, A[c][(k & 1) * 2], dg + UOFF(u), k != 0);
          wgmma_rs_n48(au, A[c][(k & 1) * 2], dg + UOFF(u) + 256, k != 0);
          wgmma_rs_n48(ag, A[c][(k & 1) * 2 + 1], dg + UOFF(u) + 128, 1);
          wgmma_rs_n48(au, A[c][(k & 1) * 2 + 1], dg + UOFF(u) + 256 + 128, 1);
          UNIT_POST(u);
        }
        wg_wait<0>();
        TSTAMP(13);
#pragma unroll
        for (int s = 0; s < 3; s++) {
          uint32_t (&hh)[4] = HH[8 + s];
          hh[0] = tg(pack2(ag[8 * s + 0] * au[8 * s + 0], ag[8 * s + 1] * au[8 * s + 1]), T);
          hh[1] = pack2(ag[8 * s + 2] * au[8 * s + 2], ag[8 * s + 3] * au[8 * s + 3]);
          hh[2] = pack2(ag[8 * s + 4] * au[8 * s + 4], ag[8 * s + 5] * au[8 * s + 5]);
          hh[3] = pack2(ag[8 * s + 6] * au[8 * s + 6], ag[8 * s + 7] * au[8 * s + 7]);
          st_rlx4(hhp + (8 + s) * 128, hh[0], hh[1], hh[2], hh[3]);
        }
      }
    }
    TSTAMP(14);

    {
      float ac[3][32], acc[32];
      uint32_t hr[4][4];
      const int m = jf >> 1, oc = (jf & 1) * 4 + m;
      const uint32_t* ph10 = reinterpret_cast<const uint32_t*>(&g_hh[rh3][jf ^ 1][10][wq][31]);
      uint32_t hv = 0;
      bar_arrive(8 + wg, 256);
      wg_fence();
#pragma unroll
      for (int k = 0; k < 3; k++) {
        mbar_wait(sb + SM_FULL + (ST_D + k) * 8);
        if (k == 1) hv = ld_rlx1(ph10);
#pragma unroll
        for (int s = 0; s < 11; s++) {
          if (k == 2 && s == 4) {
            int it = 0;
#pragma unroll 1
            while (((hv ^ T) & 1) && ++it < (1 << 18)) hv = ld_rlx1(ph10);
#pragma unroll
            for (int i = 8; i < 11; i++) ld_rlx4(PH[i], pp + i * 128);
          }
          wgmma_rs_n64(ac[k], HH[s], DESC(((ST_D + k) % NSLOT) * SLOT + s * 2048), s != 0);
        }
      }
      wg_commit();
      {
        int it = 0;
#pragma unroll 1
        while (__any_sync(0xffffffffu, bad4(PH[0][0], PH[1][0], PH[2][0], PH[3][0], T) | bad4(PH[4][0], PH[5][0], PH[6][0], PH[7][0], T) |
                                       bad4(PH[8][0], PH[9][0], PH[10][0], T, T))) {
#pragma unroll
          for (int s = 0; s < 11; s++) ld_rlx4(PH[s], pp + s * 128);
          if (++it > (1 << 18)) break;
        }
      }
      TSTAMP(20);
      uint4* outb = &g_part[rh3][(jf & 1) * 4][m][wq][0][lane];
#pragma unroll
      for (int k = 0; k < 4; k++) {
        mbar_wait(sb + SM_FULL + (ST_D + 3 + k) * 8);
        wg_fence();
#pragma unroll
        for (int s = 0; s < 11; s++) {
          if (k < 3) wgmma_rs_n64(ac[k], PH[s], DESC(((ST_D + 3 + k) % NSLOT) * SLOT + s * 2048), 1);
          else wgmma_rs_n64(acc, HH[s], DESC(((ST_D + 6) % NSLOT) * SLOT + s * 2048), s != 0);
        }
        wg_commit();
        if (k > 0) {
          wg_wait<1>();
          const float (&a)[32] = ac[k - 1];
          uint4* p = outb + ((m + k) & 3) * 2048;
#pragma unroll
          for (int s = 0; s < 4; s++)
            st_rlx4(p + s * 32, tg(pack2(a[8 * s + 0], a[8 * s + 1]), T), pack2(a[8 * s + 2], a[8 * s + 3]),
                    pack2(a[8 * s + 4], a[8 * s + 5]), pack2(a[8 * s + 6], a[8 * s + 7]));
        }
      }
      uint32_t in[3][4][4];
      const uint4* inb = &g_part[rh3][oc][0][wq][0][lane];
      const uint32_t* hint = reinterpret_cast<const uint32_t*>(&g_part[rh3][oc][(m - 1 - lane) & 3][wq][3][31]);
      ld_chunk(hr, &g_h[rh3][oc][wq][0][lane]);
      uint32_t hx = ld_rlx1(&g_hx[rh3][oc][wq][lane]);
      hv = ld_rlx1(hint);
      mbar_wait(sb + SM_FULL + (ST_D + 7) * 8);
      wg_fence();
#pragma unroll
      for (int s = 0; s < 11; s++) wgmma_rs_n64(acc, PH[s], DESC(((ST_D + 7) % NSLOT) * SLOT + s * 2048), 1);
      wg_commit();
      {
        int it = 0;
#pragma unroll
        for (int q = 0; q < 3; q++) {
#pragma unroll 1
          while (!((__ballot_sync(0xffffffffu, ((hv ^ T) & 1) == 0) >> q) & 1)) {
            hv = ld_rlx1(hint);
            if (++it > (1 << 18)) break;
          }
          ld_chunk(in[q], inb + ((m - 1 - q) & 3) * 512);
        }
#pragma unroll 1
        while (__any_sync(0xffffffffu, bad4(in[0][0][0], in[0][1][0], in[0][2][0], in[0][3][0], T) | bad4(in[1][0][0], in[1][1][0], in[1][2][0], in[1][3][0], T) |
                                       bad4(in[2][0][0], in[2][1][0], in[2][2][0], in[2][3][0], T) | ((hx ^ T) & 1))) {
#pragma unroll
          for (int q = 0; q < 3; q++) ld_chunk(in[q], inb + ((m - 1 - q) & 3) * 512);
          hx = ld_rlx1(&g_hx[rh3][oc][wq][lane]);
          if (++it > (1 << 18)) break;
        }
      }
      wg_wait<0>();
      TSTAMP(15);
#pragma unroll
      for (int s = 0; s < 4; s++) hr[s][0] = (hr[s][0] & 0xFFFFFFFEu) | ((hx >> (s + 1)) & 1u);
      add_frag(acc, in[0], IDF); add_frag(acc, in[1], IDF); add_frag(acc, in[2], IDF);
#pragma unroll
      for (int i = 0; i < 32; i++) acc[i] *= (i & 2) ? r1 : r0;
      add_frag(acc, hr, IDF);
      bar_sync(9 - wg, 256);
      const uint32_t ob = sb + ((ST_D - 1) % NSLOT) * SLOT + wg * 8192;
#pragma unroll
      for (int s = 0; s < 4; s++)
        stsm4(ob + lrow + (((2 * s + lhi) ^ lx) << 4), pack2(acc[8 * s + 0], acc[8 * s + 1]), pack2(acc[8 * s + 2], acc[8 * s + 3]),
              pack2(acc[8 * s + 4], acc[8 * s + 5]), pack2(acc[8 * s + 6], acc[8 * s + 7]));
      __syncwarp();
      {
        const int row = wq * 16 + (lane >> 3);
        __nv_bfloat16* op = out + (size_t)(rh3 * 64 + row) * 512 + oc * 64 + lx * 8;
#pragma unroll
        for (int i = 0; i < 4; i++) {
          uint4 v;
          asm volatile("ld.shared.v4.b32 {%0,%1,%2,%3}, [%4];" : "=r"(v.x), "=r"(v.y), "=r"(v.z), "=r"(v.w)
                       : "r"(ob + (row + i * 4) * 128 + ((lx ^ (((lane >> 3) + i * 4) & 7)) << 4)) : "memory");
          asm volatile("st.global.v4.b32 [%0], {%1,%2,%3,%4};" ::"l"(op + i * 2048), "r"(v.x), "r"(v.y), "r"(v.z), "r"(v.w) : "memory");
        }
      }
    }
    TSTAMP(16);
    asm volatile("barrier.cluster.arrive.relaxed.aligned;" ::: "memory");
    asm volatile("barrier.cluster.wait.aligned;" ::: "memory");
  } else {
    asm volatile("setmaxnreg.dec.sync.aligned.u32 24;");
    if (elect_one()) {
      if (warp == 8) {
#pragma unroll
        for (int k = 0; k < 9; k++) {
          const int s = k < 3 ? k : (k < 6 ? k + 3 : k - 3);
          const uint32_t bar = sb + SM_FULL + s * 8;
          mbar_init(bar, 1);
          mbar_expect_tx(bar, SLOT);
          if (s >= 3 && s < 6) tma2d(sb + s * SLOT, &maps.w, 512 + hg * 64, (s - 3) * 192, bar);
          else tma3d(sb + s * SLOT, &maps.x, 0, rb * 128 + (s >= 6 ? 64 : 0), 3 * (s % 3), bar);
        }
      } else if (warp == 9) {
        mbar_init(sb + SM_MISCB, 2);
        mbar_init(sb + SM_KVB, 1);
        mbar_expect_tx(sb + SM_KVB, 8704);
        mbar_expect_tx(sb + SM_MISCB, 2048);
        bulk_g2s(sb + SM_WPHI, wphi + hg * 1024, 2048, sb + SM_MISCB);
      } else if (warp == 10) {
        if ((sb & 0x3FFFF) != SM_BASE) __trap();
#pragma unroll 1
        for (int i = 0; i < 16; i++) {
          mbar_init(sb + SM_XF + i * 8, 1);
          mbar_expect_tx(sb + SM_XF + i * 8, (i == 8 || i == 12) ? 20480 : 16384);
          if (i < 12) mbar_init(sb + SM_XE + i * 8, 4);
        }
      } else {
        *reinterpret_cast<volatile unsigned*>(smem + SM_EPOCH) = atomicAdd(&g_start, 1u) / NCTA;
      }
      asm volatile("fence.mbarrier_init.release.cluster;" ::: "memory");
    }
    __syncwarp();
    if (warp != 11) bar_sync(0, 352);
    asm volatile("barrier.cluster.arrive.relaxed.aligned;" ::: "memory");
    if (warp == 8) {
      asm volatile("barrier.cluster.wait.aligned;" ::: "memory");
      if (elect_one()) {
        const CUtensorMap* mg = jf == 7 ? &maps.g7 : &maps.g;
        const CUtensorMap* mu = jf == 7 ? &maps.u7 : &maps.u;
        asm volatile("prefetch.tensormap [%0];" ::"l"(&maps.wo) : "memory");
        asm volatile("prefetch.tensormap [%0];" ::"l"(mg) : "memory");
        asm volatile("prefetch.tensormap [%0];" ::"l"(mu) : "memory");
        asm volatile("prefetch.tensormap [%0];" ::"l"(&maps.d) : "memory");
#pragma unroll 1
        for (int s = ST_WV; s < ST_XC; s++) {
          if (s == ST_SCR1) continue;
          mbar_wait(sb + SM_EMPTY + (s - 9) * 8);
          const uint32_t dst = sb + (s >= 18 ? s - 18 : s - 9) * SLOT, bar = sb + SM_FULL + s * 8;
          if (s < ST_WO) tma2d(dst, &maps.w, (s < ST_WQ ? 1024 : 0) + hg * 64, (s < ST_WQ ? s - ST_WV : s - ST_WQ) * 192, bar);
          else { mbar_wait(bar - 8); tma2d(dst, &maps.wo, hg * 64, (s - ST_WO) * 192, bar); }
        }
        const int jc = jf == 7 ? 0 : jf;
        int slot = (ST_GU + 1 - rank) % NSLOT;
#pragma unroll 1
        for (int s = ST_GU + 1 - rank; s < NSTAGE; s += 2) {
          mbar_wait(sb + SM_EMPTY + (s - 9) * 8);
          if (s > ST_GU && s < ST_GU + THR) mbar_wait(sb + SM_FULL + (s - 1) * 8);
          const uint32_t dst = sb + slot * SLOT, bar = sb + SM_FULL + s * 8;
          if (s < ST_D) {
#pragma unroll 1
            for (int i = 0; i < 3; i++) {
              const int u = (s - ST_GU) * 3 + i;
              tma3d_mc(dst + i * 8192, mg, (u >> 4) * 64, jc, (u & 15) * 32, bar);
              tma3d_mc(dst + i * 8192 + 4096, mu, (u >> 4) * 64, jc, (u & 15) * 32, bar);
            }
          } else {
            const int i = s - ST_D, k = i < 3 ? i : (i < 6 ? i - 3 : 3), pt = (i >= 3 && i != 6) ? 1 : 0;
            tma2d_mc(dst, &maps.d, ((jf & 1) * 4 + (((jf >> 1) + 1 + k) & 3)) * 64, (jf ^ pt) * 176, bar);
          }
          slot += 2; if (slot >= NSLOT) slot -= NSLOT;
        }
      }
      __syncwarp();
    } else {
      asm volatile("barrier.cluster.wait.aligned;" ::: "memory");
      if (warp == 11) {
#pragma unroll
        for (int i = 0; i < 4; i++)
          reinterpret_cast<uint4*>(smem + SM_ONES)[lane + 32 * i] = make_uint4(0x3F803F80u, 0x3F803F80u, 0x3F803F80u, 0x3F803F80u);
        fence_async_smem();
        __syncwarp();
        if (lane == 0) mbar_arrive(sb + SM_MISCB);
      }
      mbar_wait(sb + SM_MISCB);
      const unsigned epoch = *reinterpret_cast<volatile unsigned*>(smem + SM_EPOCH);
      const uint32_t T = (epoch & 1) ^ 1;
      if (warp == 11) {
        reinterpret_cast<float4*>(&g_kv[hg][rb * 136])[lane] = make_float4(0.f, 0.f, 0.f, 0.f);
        if (lane < 2) reinterpret_cast<float4*>(&g_kv[hg][rb * 136])[32 + lane] = make_float4(0.f, 0.f, 0.f, 0.f);
        __syncwarp();
        if (elect_one()) asm volatile("red.release.gpu.global.add.u32 [%0], 1;" ::"l"(&g_kvcnt[hg * 32 + 1]) : "memory");
        mbar_wait(sb + SM_FULL + (ST_WK + 2) * 8);
        if (elect_one()) {
          asm volatile("cp.async.bulk.prefetch.L2.global [%0], 4096;" ::"l"((const char*)wo + blockIdx.x * 4096) : "memory");
          asm volatile("cp.async.bulk.prefetch.L2.global [%0], 11008;" ::"l"((const char*)wg_ + blockIdx.x * 11008) : "memory");
          asm volatile("cp.async.bulk.prefetch.L2.global [%0], 11008;" ::"l"((const char*)wu_ + blockIdx.x * 11008) : "memory");
          asm volatile("cp.async.bulk.prefetch.L2.global [%0], 11008;" ::"l"((const char*)wd_ + blockIdx.x * 11008) : "memory");
          const unsigned target = (epoch + 1) * 16;
          unsigned v; int it = 0;
#pragma unroll 1
          do {
            asm volatile("ld.acquire.gpu.global.u32 %0, [%1];" : "=r"(v) : "l"(&g_kvcnt[hg * 32]) : "memory");
            if (++it > (1 << 18)) break;
          } while ((int)(v - target) < 0);
          TS2(0, 26);
          asm volatile("fence.proxy.async.global;" ::: "memory");
          bulk_g2s(sb + SM_KV32, &g_kv[hg][0], 8192, sb + SM_KVB);
          bulk_g2s(sb + SM_ONES, &g_kv[hg][2048], 512, sb + SM_KVB);
        }
        __syncwarp();
      } else {
        const int w = warp - 9;
        st_rlx4(reinterpret_cast<uint4*>(&g_st[2 * rb + w][hg][0]) + lane, T ^ 1, T ^ 1, T ^ 1, T ^ 1);
        if (lane < 8) st_rlx4(&g_o[2 * rb + w][hg][lane >> 1][3][30 + (lane & 1)], T ^ 1, T ^ 1, T ^ 1, T ^ 1);
        st_rlx4(&g_part[2 * rb3 + w][(jf & 1) * 4 + (lane >> 3)][jf >> 1][(lane >> 1) & 3][3][30 + (lane & 1)], T ^ 1, T ^ 1, T ^ 1, T ^ 1);
        if (lane < 16) st_rlx4(&g_hh[2 * rb3 + w][jf][7 + (lane >> 3) * 3][(lane >> 1) & 3][30 + (lane & 1)], T ^ 1, T ^ 1, T ^ 1, T ^ 1);
        if (w == 0) {
          mbar_wait(sb + SM_FULL + (ST_WQ + 2) * 8);
          unsigned v; int it = 0;
#pragma unroll 1
          do {
            asm volatile("ld.acquire.gpu.global.u32 %0, [%1];" : "=r"(v) : "l"(&g_kvcnt[hg * 32 + 1]) : "memory");
          } while ((int)(v - (epoch + 1) * 16) < 0 && ++it < (1 << 18));
          asm volatile("fence.proxy.async.global;" ::: "memory");
        }
        bar_sync(6, 320);
        if (w == 0 && elect_one()) {
          asm volatile("cp.reduce.async.bulk.global.shared::cta.bulk_group.add.f32 [%0], [%1], 8704;"
                       ::"l"(&g_kv[hg][0]), "r"(sb + 2 * SLOT) : "memory");
          asm volatile("cp.async.bulk.commit_group;" ::: "memory");
          asm volatile("cp.async.bulk.wait_group 0;" ::: "memory");
          asm volatile("red.relaxed.gpu.global.add.u32 [%0], 1;" ::"l"(&g_kvcnt[hg * 32]) : "memory");
          TS2(0, 25);
        }
        __syncwarp();
        mbar_wait(sb + SM_KVB);
        if (w == 0) { mbar_wait(sb + SM_EMPTY + 11 * 8); mbar_wait(sb + SM_EMPTY + 12 * 8); mbar_wait(sb + SM_EMPTY + 13 * 8); }
#pragma unroll 1
        for (int ph = 0; ph < 2; ph++) {
          const int use = 2 * ph + w, r = ph ? 2 * rb3 + w : 2 * rb + w;
          const uint32_t* pw = ph ? reinterpret_cast<const uint32_t*>(&g_st[r][lane >> 2][(lane & 3) * 16 + 15])
                                  : reinterpret_cast<const uint32_t*>(&g_o[r][lane >> 2][lane & 3][3][31]);
          const char* src = reinterpret_cast<const char*>(ph ? &g_h[r][0][0][0][0] : &g_o[r][0][0][0][0]);
          const uint32_t bf = sb + SM_XF + use * 32, be = sb + SM_XE + (use - 1) * 32;
          if (ph) mbar_wait(sb + SM_XE + w * 32 + 24);
          int it = 0;
#pragma unroll 1
          while (__any_sync(0xffffffffu, (ld_rlx1(pw) ^ T) & 1)) { if (++it > (1 << 18)) break; }
          if (elect_one()) {
            TS2(w, 27 + ph);
            if (use > 0) mbar_wait(be);
            if (ph) bulk_g2s(sb + SM_KV32 + w * 4096, &g_st[r][0][0], 4096, bf);
#pragma unroll
            for (int p = 0; p < 4; p++) {
              if (p > 0 && use > 0) mbar_wait(be + p * 8);
              bulk_g2s(sb + 2 * SLOT + p * 16384, src + p * 16384, 16384, bf + p * 8);
            }
          }
          __syncwarp();
        }
      }
    }
    asm volatile("barrier.cluster.arrive.relaxed.aligned;" ::: "memory");
    asm volatile("barrier.cluster.wait.aligned;" ::: "memory");
  }
}

typedef CUresult (*EncodeFn)(CUtensorMap*, CUtensorMapDataType, cuuint32_t, void*, const cuuint64_t*, const cuuint64_t*,
                             const cuuint32_t*, const cuuint32_t*, CUtensorMapInterleave, CUtensorMapSwizzle,
                             CUtensorMapL2promotion, CUtensorMapFloatOOBfill);

void encode(EncodeFn fn, CUtensorMap* m, const void* base, int rank, const cuuint64_t* dims, const cuuint64_t* strides,
            const cuuint32_t* box) {
  cuuint32_t es[3] = {1, 1, 1};
  fn(m, CU_TENSOR_MAP_DATA_TYPE_BFLOAT16, (cuuint32_t)rank, const_cast<void*>(base), dims, strides, box, es,
     CU_TENSOR_MAP_INTERLEAVE_NONE, CU_TENSOR_MAP_SWIZZLE_128B, CU_TENSOR_MAP_L2_PROMOTION_L2_256B,
     CU_TENSOR_MAP_FLOAT_OOB_FILL_NONE);
}

}

extern "C" void kernel_launch(void* const* d_in, const int* in_sizes, int n_in, void* d_out, int out_size) {
  (void)in_sizes; (void)n_in; (void)out_size;
  const __nv_bfloat16* x    = (const __nv_bfloat16*)d_in[0];
  const __nv_bfloat16* wqkv = (const __nv_bfloat16*)d_in[1];
  const __nv_bfloat16* wphi = (const __nv_bfloat16*)d_in[2];
  const __nv_bfloat16* wo   = (const __nv_bfloat16*)d_in[3];
  const __nv_bfloat16* wg   = (const __nv_bfloat16*)d_in[5];
  const __nv_bfloat16* wu   = (const __nv_bfloat16*)d_in[6];
  const __nv_bfloat16* wd   = (const __nv_bfloat16*)d_in[7];

  static EncodeFn fn = nullptr;
  if (!fn) {
    void* p = nullptr;
    cudaDriverEntryPointQueryResult qr;
    cudaGetDriverEntryPoint("cuTensorMapEncodeTiled", &p, cudaEnableDefault, &qr);
    fn = (EncodeFn)p;
    cudaFuncSetAttribute(fused_kernel, cudaFuncAttributeMaxDynamicSharedMemorySize, SM_TOTAL);
  }
  Maps maps;
  {
    cuuint64_t d[3] = {64, 2048, 8}, s[2] = {1024, 128}; cuuint32_t b[3] = {64, 64, 3};
    encode(fn, &maps.x, x, 3, d, s, b);
  }
  {
    cuuint64_t d[2] = {1536, 512}, s[1] = {3072}; cuuint32_t b[2] = {64, 192};
    encode(fn, &maps.w, wqkv, 2, d, s, b);
  }
  {
    cuuint64_t d[2] = {512, 512}, s[1] = {1024}; cuuint32_t b[2] = {64, 192};
    encode(fn, &maps.wo, wo, 2, d, s, b);
  }
  {
    cuuint64_t d[3] = {176, 7, 512}, d7[3] = {144, 1, 512}, s[2] = {352, 2752}; cuuint32_t b[3] = {64, 1, 32};
    encode(fn, &maps.g, wg, 3, d, s, b);
    encode(fn, &maps.u, wu, 3, d, s, b);
    encode(fn, &maps.g7, wg + 1232, 3, d7, s, b);
    encode(fn, &maps.u7, wu + 1232, 3, d7, s, b);
  }
  {
    cuuint64_t d[2] = {512, 1376}, s[1] = {1024}; cuuint32_t b[2] = {64, 176};
    encode(fn, &maps.d, wd, 2, d, s, b);
  }
  fused_kernel<<<NCTA, 384, SM_TOTAL>>>(maps, x, wphi, wo, wg, wu, wd, (__nv_bfloat16*)d_out);
}
```

```cpp
#include <cuda_runtime.h>
#include <cuda_bf16.h>
#include <cuda.h>
#include <stdint.h>

#define PROF 0

#define SAFE_WAIT 0
#define OPRIO 1
#define THR 6

namespace {

constexpr int NCTA   = 128;
constexpr int SLOT   = 24576;
constexpr int NSLOT  = 9;
constexpr int NSTAGE = 47;

constexpr int ST_X0   = 0;
constexpr int ST_WK   = 3;
constexpr int ST_X1   = 6;
constexpr int ST_SCR0 = 9;
constexpr int ST_WV   = 10;
constexpr int ST_SCR1 = 13;
constexpr int ST_WQ   = 14;
constexpr int ST_WO   = 17;
constexpr int ST_XC   = 20;
constexpr int ST_GU   = 23;
constexpr int ST_D    = 39;

__host__ __device__ constexpr int st_empty_cnt(int d) {
  return ((d < 3 || (d >= 6 && d < 9) || (d >= ST_XC && d < ST_GU)) ? 4 : (d == ST_SCR0 || d == ST_SCR1) ? 1 : 2) * (d + 9 >= ST_GU ? 2 : 1);
}

constexpr uint32_t SM_BASE = 1024;
constexpr int SM_ONES = NSLOT * SLOT;
constexpr int SM_WPHI = SM_ONES + 2048;
constexpr int SM_KVS  = SM_WPHI + 2048;
constexpr int SM_KV32 = 4 * SLOT + 16384;
constexpr int SM_BAR  = SM_KVS + 6144;
constexpr int SM_FULL  = SM_BAR;
constexpr int SM_EMPTY = SM_BAR + NSTAGE * 8;
constexpr int SM_MISCB = SM_BAR + 2 * NSTAGE * 8;
constexpr int SM_KVB   = SM_MISCB + 8;
constexpr int SM_EPOCH = SM_KVB + 8;
constexpr int SM_XF    = SM_EPOCH + 8;
constexpr int SM_XE    = SM_XF + 16 * 8;
constexpr int SM_KVR   = SM_XE + 12 * 8;
constexpr int SM_TOTAL = SM_BAR + 1024;

static_assert(SM_TOTAL == 232448 && SM_KVR + 8 <= SM_TOTAL, "smem budget");

struct Maps { CUtensorMap x, w, wo, g, u, g7, u7, d; };

__device__ uint4    g_o[32][8][4][4][32];
__device__ uint4    g_h[32][8][4][4][32];
__device__ uint32_t g_hx[32][8][4][32];
__device__ uint2    g_st[32][8][64];
__device__ uint4    g_hh[32][8][11][4][32];
__device__ uint4    g_part[32][8][4][4][4][32];
__device__ __align__(128) float g_kv[8][2048 + 128];
__device__ unsigned g_kvcnt[8 * 32];
__device__ unsigned g_start;

__device__ __forceinline__ uint32_t smem_u32(const void* p) { return (uint32_t)__cvta_generic_to_shared(p); }
__device__ __forceinline__ void mbar_init(uint32_t bar, int cnt) {
  asm volatile("mbarrier.init.shared::cta.b64 [%0], %1;" ::"r"(bar), "r"(cnt) : "memory");
}
__device__ __forceinline__ void mbar_expect_tx(uint32_t bar, uint32_t bytes) {
  asm volatile("mbarrier.arrive.expect_tx.shared::cta.b64 _, [%0], %1;" ::"r"(bar), "r"(bytes) : "memory");
}
__device__ __forceinline__ void mbar_arrive(uint32_t bar) {
  asm volatile("mbarrier.arrive.shared::cta.b64 _, [%0];" ::"r"(bar) : "memory");
}
__device__ __forceinline__ void mbar_arrive_cluster(uint32_t bar, uint32_t rank) {
  asm volatile("{\n.reg .b32 ra;\nmapa.shared::cluster.u32 ra, %0, %1;\n"
               "mbarrier.arrive.shared::cluster.b64 _, [ra];\n}" ::"r"(bar), "r"(rank) : "memory");
}
__device__ __forceinline__ void mbar_wait_p(uint32_t bar, uint32_t parity) {
  asm volatile("{\n.reg .pred p;\nW: mbarrier.try_wait.parity.shared::cta.b64 p, [%0], %1;\n@!p bra W;\n}" ::"r"(bar), "r"(parity) : "memory");
}
__device__ __forceinline__ void mbar_wait(uint32_t bar) { mbar_wait_p(bar, 0); }
__device__ __forceinline__ bool elect_one() {
  uint32_t p;
  asm volatile("{\n.reg .pred P;\nelect.sync _|P, 0xffffffff;\nselp.u32 %0, 1, 0, P;\n}" : "=r"(p));
  return p != 0;
}
__device__ __forceinline__ void bar_sync(int id, int n)   { asm volatile("bar.sync %0, %1;" ::"r"(id), "r"(n) : "memory"); }
__device__ __forceinline__ void bar_arrive(int id, int n) { asm volatile("bar.arrive %0, %1;" ::"r"(id), "r"(n) : "memory"); }
__device__ __forceinline__ void fence_async_smem() { asm volatile("fence.proxy.async.shared::cta;" ::: "memory"); }
__device__ __forceinline__ void wg_fence()  { asm volatile("wgmma.fence.sync.aligned;" ::: "memory"); }
__device__ __forceinline__ void wg_commit() { asm volatile("wgmma.commit_group.sync.aligned;" ::: "memory"); }
template <int N> __device__ __forceinline__ void wg_wait() { asm volatile("wgmma.wait_group.sync.aligned %0;" ::"n"(N) : "memory"); }
#define DESC(off) (db + ((uint32_t)(off) >> 4))
__device__ __forceinline__ void tma2d(uint32_t dst, const CUtensorMap* m, int c0, int c1, uint32_t bar) {
  asm volatile("cp.async.bulk.tensor.2d.shared::cluster.global.mbarrier::complete_tx::bytes [%0], [%1, {%3, %4}], [%2];"
               ::"r"(dst), "l"(m), "r"(bar), "r"(c0), "r"(c1) : "memory");
}
__device__ __forceinline__ void tma2d_mc(uint32_t dst, const CUtensorMap* m, int c0, int c1, uint32_t bar) {
  asm volatile("cp.async.bulk.tensor.2d.shared::cluster.global.mbarrier::complete_tx::bytes.multicast::cluster [%0], [%1, {%3, %4}], [%2], %5;"
               ::"r"(dst), "l"(m), "r"(bar), "r"(c0), "r"(c1), "h"((uint16_t)3) : "memory");
}
__device__ __forceinline__ void tma3d(uint32_t dst, const CUtensorMap* m, int c0, int c1, int c2, uint32_t bar) {
  asm volatile("cp.async.bulk.tensor.3d.shared::cluster.global.mbarrier::complete_tx::bytes [%0], [%1, {%3, %4, %5}], [%2];"
               ::"r"(dst), "l"(m), "r"(bar), "r"(c0), "r"(c1), "r"(c2) : "memory");
}
__device__ __forceinline__ void tma3d_mc(uint32_t dst, const CUtensorMap* m, int c0, int c1, int c2, uint32_t bar) {
  asm volatile("cp.async.bulk.tensor.3d.shared::cluster.global.mbarrier::complete_tx::bytes.multicast::cluster [%0], [%1, {%3, %4, %5}], [%2], %6;"
               ::"r"(dst), "l"(m), "r"(bar), "r"(c0), "r"(c1), "r"(c2), "h"((uint16_t)3) : "memory");
}
__device__ __forceinline__ void ldsm4(uint32_t (&r)[4], uint32_t addr) {
  asm volatile("ldmatrix.sync.aligned.m8n8.x4.shared.b16 {%0,%1,%2,%3}, [%4];"
               : "=r"(r[0]), "=r"(r[1]), "=r"(r[2]), "=r"(r[3]) : "r"(addr) : "memory");
}
__device__ __forceinline__ void ldsm4t(uint32_t (&r)[4], uint32_t addr) {
  asm volatile("ldmatrix.sync.aligned.m8n8.x4.trans.shared.b16 {%0,%1,%2,%3}, [%4];"
               : "=r"(r[0]), "=r"(r[1]), "=r"(r[2]), "=r"(r[3]) : "r"(addr) : "memory");
}
__device__ __forceinline__ void stsm4(uint32_t addr, uint32_t r0, uint32_t r1, uint32_t r2, uint32_t r3) {
  asm volatile("stmatrix.sync.aligned.m8n8.x4.shared.b16 [%0], {%1,%2,%3,%4};"
               ::"r"(addr), "r"(r0), "r"(r1), "r"(r2), "r"(r3) : "memory");
}
__device__ __forceinline__ void mma16816(float (&c)[4], const uint32_t (&a)[4], uint32_t b0, uint32_t b1) {
  asm volatile("mma.sync.aligned.m16n8k16.row.col.f32.bf16.bf16.f32 {%0,%1,%2,%3},{%4,%5,%6,%7},{%8,%9},{%0,%1,%2,%3};"
               : "+f"(c[0]), "+f"(c[1]), "+f"(c[2]), "+f"(c[3])
               : "r"(a[0]), "r"(a[1]), "r"(a[2]), "r"(a[3]), "r"(b0), "r"(b1));
}
__device__ __forceinline__ void add_frag(float (&c)[32], const uint32_t (&a)[4][4], uint32_t id) {
#pragma unroll
  for (int i = 0; i < 8; i++)
    asm volatile("mma.sync.aligned.m16n8k8.row.col.f32.bf16.bf16.f32 {%0,%1,%2,%3},{%4,%5},{%6},{%0,%1,%2,%3};"
                 : "+f"(c[4 * i]), "+f"(c[4 * i + 1]), "+f"(c[4 * i + 2]), "+f"(c[4 * i + 3])
                 : "r"(a[i >> 1][(i & 1) * 2]), "r"(a[i >> 1][(i & 1) * 2 + 1]), "r"(id));
}
__device__ __forceinline__ uint32_t pack2(float lo, float hi) {
  uint32_t r; asm("cvt.rn.bf16x2.f32 %0, %1, %2;" : "=r"(r) : "f"(hi), "f"(lo)); return r;
}
__device__ __forceinline__ float blo(uint32_t w) { return __uint_as_float(w << 16); }
__device__ __forceinline__ float bhi(uint32_t w) { return __uint_as_float(w & 0xFFFF0000u); }
__device__ __forceinline__ uint32_t hsub2(uint32_t a, uint32_t b) { uint32_t r; asm("sub.rn.bf16x2 %0, %1, %2;" : "=r"(r) : "r"(a), "r"(b)); return r; }
__device__ __forceinline__ uint32_t hmax2(uint32_t a, uint32_t b) { uint32_t r; asm("max.bf16x2 %0, %1, %2;" : "=r"(r) : "r"(a), "r"(b)); return r; }
__device__ __forceinline__ uint32_t hmin2(uint32_t a, uint32_t b) { uint32_t r; asm("min.bf16x2 %0, %1, %2;" : "=r"(r) : "r"(a), "r"(b)); return r; }
__device__ __forceinline__ float ex2(float x) { float r; asm("ex2.approx.ftz.f32 %0, %1;" : "=f"(r) : "f"(x)); return r; }
__device__ __forceinline__ float rcp(float x) { float r; asm("rcp.approx.ftz.f32 %0, %1;" : "=f"(r) : "f"(x)); return r; }
__device__ __forceinline__ void ld_rlx4(uint32_t (&r)[4], const uint4* p) {
  asm volatile("{\n.reg .b128 v;\nld.relaxed.gpu.global.b128 v, [%4];\nmov.b128 {%0,%1,%2,%3}, v;\n}"
               : "=r"(r[0]), "=r"(r[1]), "=r"(r[2]), "=r"(r[3]) : "l"(p) : "memory");
}
__device__ __forceinline__ void st_rlx4(uint4* p, uint32_t a, uint32_t b, uint32_t c, uint32_t d) {
  asm volatile("{\n.reg .b128 v;\nmov.b128 v, {%1,%2,%3,%4};\nst.relaxed.gpu.global.b128 [%0], v;\n}"
               ::"l"(p), "r"(a), "r"(b), "r"(c), "r"(d) : "memory");
}
__device__ __forceinline__ void st_rlx2(uint2* p, uint32_t a, uint32_t b) {
  asm volatile("{\n.reg .b64 v;\nmov.b64 v, {%1,%2};\nst.relaxed.gpu.global.b64 [%0], v;\n}" ::"l"(p), "r"(a), "r"(b) : "memory");
}
__device__ __forceinline__ uint32_t ld_rlx1(const uint32_t* p) {
  uint32_t r; asm volatile("ld.relaxed.gpu.global.b32 %0, [%1];" : "=r"(r) : "l"(p) : "memory"); return r;
}
__device__ __forceinline__ void st_rlx1(uint32_t* p, uint32_t a) {
  asm volatile("st.relaxed.gpu.global.b32 [%0], %1;" ::"l"(p), "r"(a) : "memory");
}
__device__ __forceinline__ void ld_rlx2(uint32_t& a, uint32_t& b, const uint2* p) {
  asm volatile("{\n.reg .b64 v;\nld.relaxed.gpu.b64 v, [%2];\nmov.b64 {%0,%1}, v;\n}" : "=r"(a), "=r"(b) : "l"(p) : "memory");
}
__device__ __forceinline__ void bulk_g2s(uint32_t dst, const void* src, uint32_t bytes, uint32_t bar) {
  asm volatile("cp.async.bulk.shared::cluster.global.mbarrier::complete_tx::bytes [%0], [%1], %2, [%3];"
               ::"r"(dst), "l"(src), "r"(bytes), "r"(bar) : "memory");
}
__device__ __forceinline__ uint32_t tg(uint32_t w, uint32_t T) { return (w & 0xFFFFFFFEu) | T; }
__device__ __forceinline__ uint32_t bad4(uint32_t a, uint32_t b, uint32_t c, uint32_t d, uint32_t T) {
  uint32_t u, v;
  asm("lop3.b32 %0, %1, %2, %3, 0x7E;" : "=r"(u) : "r"(a), "r"(b), "r"(T));
  asm("lop3.b32 %0, %1, %2, %3, 0x7E;" : "=r"(v) : "r"(c), "r"(d), "r"(T));
  asm("lop3.b32 %0, %1, %2, 1, 0xA8;" : "=r"(u) : "r"(u), "r"(v));
  return u;
}

__device__ __forceinline__ void ld_chunk(uint32_t (&a)[4][4], const uint4* p) {
#pragma unroll
  for (int s = 0; s < 4; s++) ld_rlx4(a[s], p + s * 32);
}
__device__ __forceinline__ void get_pair(uint32_t (&a)[4][4], uint32_t (&b)[4][4], const uint4* sp, const uint4* gp, uint32_t T) {
  int it = 0;
#pragma unroll 1
  do {
#pragma unroll
    for (int s = 0; s < 8; s++) {
      uint32_t (&r)[4] = s < 4 ? a[s & 3] : b[s & 3];
      asm volatile("{\n.reg .b128 v;\nld.relaxed.gpu.b128 v, [%4];\nmov.b128 {%0,%1,%2,%3}, v;\n}"
                   : "=r"(r[0]), "=r"(r[1]), "=r"(r[2]), "=r"(r[3]) : "l"(sp + (s >> 2) * 512 + (s & 3) * 32) : "memory");
    }
    sp = gp;
  } while (__any_sync(0xffffffffu, bad4(a[0][0], a[1][0], a[2][0], a[3][0], T) | bad4(b[0][0], b[1][0], b[2][0], b[3][0], T)) && ++it < (1 << 18));
}

__device__ __forceinline__ void wgmma_rs_n48(float (&d)[24], const uint32_t (&a)[4], uint32_t descB, int scaleD) {
  asm volatile("{\n.reg .pred p;\n.reg .b64 db;\nsetp.ne.b32 p, %29, 0;\nmov.b64 db, {%28, 0x40000040};\n"
    "wgmma.mma_async.sync.aligned.m64n48k16.f32.bf16.bf16 {%0,%1,%2,%3,%4,%5,%6,%7,%8,%9,%10,%11,%12,%13,%14,%15,%16,%17,%18,%19,%20,%21,%22,%23}, {%24,%25,%26,%27}, db, p, 1, 1, 1;\n}\n"
    : "+f"(d[0]),"+f"(d[1]),"+f"(d[2]),"+f"(d[3]),"+f"(d[4]),"+f"(d[5]),"+f"(d[6]),"+f"(d[7]),"+f"(d[8]),"+f"(d[9]),"+f"(d[10]),"+f"(d[11]),"+f"(d[12]),"+f"(d[13]),"+f"(d[14]),"+f"(d[15]),"+f"(d[16]),"+f"(d[17]),"+f"(d[18]),"+f"(d[19]),"+f"(d[20]),"+f"(d[21]),"+f"(d[22]),"+f"(d[23])
    : "r"(a[0]), "r"(a[1]), "r"(a[2]), "r"(a[3]), "r"(descB), "r"(scaleD));
}
__device__ __forceinline__ void wgmma_rs_n64(float (&d)[32], const uint32_t (&a)[4], uint32_t descB, int scaleD) {
  asm volatile("{\n.reg .pred p;\n.reg .b64 db;\nsetp.ne.b32 p, %37, 0;\nmov.b64 db, {%36, 0x40000040};\n"
    "wgmma.mma_async.sync.aligned.m64n64k16.f32.bf16.bf16 {%0,%1,%2,%3,%4,%5,%6,%7,%8,%9,%10,%11,%12,%13,%14,%15,%16,%17,%18,%19,%20,%21,%22,%23,%24,%25,%26,%27,%28,%29,%30,%31}, {%32,%33,%34,%35}, db, p, 1, 1, 1;\n}\n"
    : "+f"(d[0]),"+f"(d[1]),"+f"(d[2]),"+f"(d[3]),"+f"(d[4]),"+f"(d[5]),"+f"(d[6]),"+f"(d[7]),"+f"(d[8]),"+f"(d[9]),"+f"(d[10]),"+f"(d[11]),"+f"(d[12]),"+f"(d[13]),"+f"(d[14]),"+f"(d[15]),"+f"(d[16]),"+f"(d[17]),"+f"(d[18]),"+f"(d[19]),"+f"(d[20]),"+f"(d[21]),"+f"(d[22]),"+f"(d[23]),"+f"(d[24]),"+f"(d[25]),"+f"(d[26]),"+f"(d[27]),"+f"(d[28]),"+f"(d[29]),"+f"(d[30]),"+f"(d[31])
    : "r"(a[0]), "r"(a[1]), "r"(a[2]), "r"(a[3]), "r"(descB), "r"(scaleD));
}
__device__ __forceinline__ void wgmma_rs_n128(float (&d)[64], const uint32_t (&a)[4], uint32_t descB, int scaleD) {
  asm volatile("{\n.reg .pred p;\n.reg .b64 db;\nsetp.ne.b32 p, %69, 0;\nmov.b64 db, {%68, 0x40000040};\n"
    "wgmma.mma_async.sync.aligned.m64n128k16.f32.bf16.bf16 {%0,%1,%2,%3,%4,%5,%6,%7,%8,%9,%10,%11,%12,%13,%14,%15,%16,%17,%18,%19,%20,%21,%22,%23,%24,%25,%26,%27,%28,%29,%30,%31,%32,%33,%34,%35,%36,%37,%38,%39,%40,%41,%42,%43,%44,%45,%46,%47,%48,%49,%50,%51,%52,%53,%54,%55,%56,%57,%58,%59,%60,%61,%62,%63}, {%64,%65,%66,%67}, db, p, 1, 1, 1;\n}\n"
    : "+f"(d[0]),"+f"(d[1]),"+f"(d[2]),"+f"(d[3]),"+f"(d[4]),"+f"(d[5]),"+f"(d[6]),"+f"(d[7]),"+f"(d[8]),"+f"(d[9]),"+f"(d[10]),"+f"(d[11]),"+f"(d[12]),"+f"(d[13]),"+f"(d[14]),"+f"(d[15]),"+f"(d[16]),"+f"(d[17]),"+f"(d[18]),"+f"(d[19]),"+f"(d[20]),"+f"(d[21]),"+f"(d[22]),"+f"(d[23]),"+f"(d[24]),"+f"(d[25]),"+f"(d[26]),"+f"(d[27]),"+f"(d[28]),"+f"(d[29]),"+f"(d[30]),"+f"(d[31]),"+f"(d[32]),"+f"(d[33]),"+f"(d[34]),"+f"(d[35]),"+f"(d[36]),"+f"(d[37]),"+f"(d[38]),"+f"(d[39]),"+f"(d[40]),"+f"(d[41]),"+f"(d[42]),"+f"(d[43]),"+f"(d[44]),"+f"(d[45]),"+f"(d[46]),"+f"(d[47]),"+f"(d[48]),"+f"(d[49]),"+f"(d[50]),"+f"(d[51]),"+f"(d[52]),"+f"(d[53]),"+f"(d[54]),"+f"(d[55]),"+f"(d[56]),"+f"(d[57]),"+f"(d[58]),"+f"(d[59]),"+f"(d[60]),"+f"(d[61]),"+f"(d[62]),"+f"(d[63])
    : "r"(a[0]), "r"(a[1]), "r"(a[2]), "r"(a[3]), "r"(descB), "r"(scaleD));
}
__device__ __forceinline__ void wgmma_ss_n72_t11(float (&d)[36], uint32_t descA, uint32_t descB, int scaleD) {
  asm volatile("{\n.reg .pred p;\n.reg .b64 da, db;\nsetp.ne.b32 p, %38, 0;\nmov.b64 da, {%36, 0x40000040};\nmov.b64 db, {%37, 0x40000040};\n"
    "wgmma.mma_async.sync.aligned.m64n72k16.f32.bf16.bf16 {%0,%1,%2,%3,%4,%5,%6,%7,%8,%9,%10,%11,%12,%13,%14,%15,%16,%17,%18,%19,%20,%21,%22,%23,%24,%25,%26,%27,%28,%29,%30,%31,%32,%33,%34,%35}, da, db, p, 1, 1, 1, 1;\n}\n"
    : "+f"(d[0]),"+f"(d[1]),"+f"(d[2]),"+f"(d[3]),"+f"(d[4]),"+f"(d[5]),"+f"(d[6]),"+f"(d[7]),"+f"(d[8]),"+f"(d[9]),"+f"(d[10]),"+f"(d[11]),"+f"(d[12]),"+f"(d[13]),"+f"(d[14]),"+f"(d[15]),"+f"(d[16]),"+f"(d[17]),"+f"(d[18]),"+f"(d[19]),"+f"(d[20]),"+f"(d[21]),"+f"(d[22]),"+f"(d[23]),"+f"(d[24]),"+f"(d[25]),"+f"(d[26]),"+f"(d[27]),"+f"(d[28]),"+f"(d[29]),"+f"(d[30]),"+f"(d[31]),"+f"(d[32]),"+f"(d[33]),"+f"(d[34]),"+f"(d[35])
    : "r"(descA), "r"(descB), "r"(scaleD));
}

#define TSTAMP(i) do {} while (0)
#define TS2(w, i) do {} while (0)

constexpr float LOG2E = 1.4426950408889634f;

__device__ __forceinline__ void feat_exp(const uint32_t (&P)[4], float (&e)[16]) {
  uint32_t a = hmax2(P[0], P[2]), b = hmax2(P[1], P[3]);
  uint32_t mx = hmax2(__byte_perm(a, b, 0x5410), __byte_perm(a, b, 0x7632));
  a = hmin2(P[0], P[2]); b = hmin2(P[1], P[3]);
  uint32_t mn = hmin2(__byte_perm(a, b, 0x5410), __byte_perm(a, b, 0x7632));
  mx = hmax2(mx, __shfl_xor_sync(0xffffffffu, mx, 1));
  mn = hmin2(mn, __shfl_xor_sync(0xffffffffu, mn, 1));
  mx = hmax2(mx, __shfl_xor_sync(0xffffffffu, mx, 2));
  mn = hmin2(mn, __shfl_xor_sync(0xffffffffu, mn, 2));
  float mx0 = -blo(mx) * LOG2E, mx1 = -bhi(mx) * LOG2E, mn0 = blo(mn) * LOG2E, mn1 = bhi(mn) * LOG2E;
  float v[8] = {blo(P[0]), bhi(P[0]), blo(P[1]), bhi(P[1]), blo(P[2]), bhi(P[2]), blo(P[3]), bhi(P[3])};
#pragma unroll
  for (int i = 0; i < 8; i++) {
    bool r1 = (i >> 1) & 1;
    e[i]     = ex2(fmaf(v[i],  LOG2E, r1 ? mx1 : mx0));
    e[8 + i] = ex2(fmaf(v[i], -LOG2E, r1 ? mn1 : mn0));
  }
}

__global__ void __cluster_dims__(2, 1, 1) __launch_bounds__(384, 1)
fused_kernel(const __grid_constant__ Maps maps, const __nv_bfloat16* __restrict__ x, const __nv_bfloat16* __restrict__ wphi,
             const __nv_bfloat16* __restrict__ wo, const __nv_bfloat16* __restrict__ wg_, const __nv_bfloat16* __restrict__ wu_,
             const __nv_bfloat16* __restrict__ wd_, __nv_bfloat16* __restrict__ out) {
  extern __shared__ __align__(1024) unsigned char smem[];
  const uint32_t sb = smem_u32(smem);
  const int tid = threadIdx.x, lane = tid & 31;
  const int warp = __shfl_sync(0xffffffffu, tid >> 5, 0);
  const uint32_t rank = blockIdx.x & 1;
  const int cl = blockIdx.x >> 1;
  int quad, qi;
  if (cl < 4) { quad = 15; qi = cl; }
  else if (cl < 36) { quad = (cl - 4) & 7; qi = (cl - 4) >> 3; }
  else { qi = (cl - 36) / 7; quad = 8 + (cl - 36) - 7 * qi; }
  const int rb = quad, hg = 2 * qi + rank;
  const int rb3 = (quad & ~1) + rank, jf = 4 * (quad & 1) + qi;

  if (warp < 8) {
    asm volatile("setmaxnreg.inc.sync.aligned.u32 240;");
    if (elect_one()) {
#pragma unroll 1
      for (int d = warp; d + 9 < NSTAGE; d += 8) {
        mbar_init(sb + SM_EMPTY + d * 8, st_empty_cnt(d));
        {
          mbar_init(sb + SM_FULL + (d + 9) * 8, 1);
          mbar_expect_tx(sb + SM_FULL + (d + 9) * 8, d + 9 >= ST_D ? 22528 : SLOT);
        }
      }
      asm volatile("fence.mbarrier_init.release.cluster;" ::: "memory");
    }
    __syncwarp();
    bar_sync(0, 352);
    asm volatile("barrier.cluster.arrive.relaxed.aligned;" ::: "memory");
    const int wg = warp >> 2, wq = warp & 3, g = lane >> 2, t = lane & 3;
    const bool lead = (tid & 127) == 0;
    constexpr uint32_t db = (SM_BASE >> 4) | (512u << 16);
    auto release = [&](int d) {
      const int s = d + NSLOT;
      mbar_arrive_cluster(sb + SM_EMPTY + d * 8, s >= ST_GU ? (uint32_t)(s & 1) : rank);
    };
    const uint32_t lrow = (uint32_t)(wq * 16 + (lane & 7) + ((lane >> 3) & 1) * 8) * 128;
    const uint32_t lx = lane & 7, lhi = lane >> 4;
    if (wg == 1) bar_arrive(4, 256);

    float r0, r1;
    uint32_t E[4][8];
    uint32_t T = 0;
    {
      uint32_t A[32][4];
      const int sx = wg ? ST_X1 : ST_X0;
      {
        const uint32_t base = sb + sx * SLOT + lrow, baseb = sb + sx * SLOT + (wq * 16 + lx + lhi * 8) * 128;
        float cs[2][4], c0[2][4], c1[2][4];
#pragma unroll
        for (int i = 0; i < 4; i++) { cs[0][i] = cs[1][i] = c0[0][i] = c0[1][i] = c1[0][i] = c1[1][i] = 0.f; }
#pragma unroll
        for (int c = 0; c < 8; c++) {
          if (c % 3 == 0) mbar_wait(sb + SM_FULL + (sx + c / 3) * 8);
#pragma unroll
          for (int k = 0; k < 4; k++) ldsm4(A[4 * c + k], base + c * 8192 + (((2 * k + lhi) ^ lx) << 4));
#pragma unroll
          for (int k = 0; k < 4; k++) {
            const uint32_t (&f)[4] = A[4 * c + k];
            uint32_t bt[4];
            ldsm4(bt, baseb + c * 8192 + (((2 * k + ((lane >> 3) & 1)) ^ lx) << 4));
            mma16816(cs[k & 1], f, 0x3F803F80u, 0x3F803F80u);
            mma16816(c0[k & 1], f, bt[0], bt[1]);
            mma16816(c1[k & 1], f, bt[2], bt[3]);
          }
        }
        const float s0 = (cs[0][0] + cs[1][0]) * (1.f / 512.f), s1 = (cs[0][2] + cs[1][2]) * (1.f / 512.f);
        asm volatile("barrier.cluster.wait.aligned;" ::: "memory");
        if (lane < 3) release(sx + lane);
        const uint32_t m0 = pack2(s0, s0), m1 = pack2(s1, s1);
        float q0 = (g & 1) ? c0[0][1] + c0[1][1] : c0[0][0] + c0[1][0];
        float q1 = (g & 1) ? c1[0][3] + c1[1][3] : c1[0][2] + c1[1][2];
        q0 = __shfl_sync(0xffffffffu, q0, (lane & ~3) | (g >> 1));
        q1 = __shfl_sync(0xffffffffu, q1, (lane & ~3) | (g >> 1));
        r0 = rsqrtf(fmaxf(q0 * (1.f / 512.f) - s0 * s0, 0.f) + 1e-5f);
        r1 = rsqrtf(fmaxf(q1 * (1.f / 512.f) - s1 * s1, 0.f) + 1e-5f);
#pragma unroll
        for (int ks = 0; ks < 32; ks++) {
          A[ks][0] = hsub2(A[ks][0], m0); A[ks][1] = hsub2(A[ks][1], m1);
          A[ks][2] = hsub2(A[ks][2], m0); A[ks][3] = hsub2(A[ks][3], m1);
        }
      }
      TSTAMP(1);
      const uint32_t wpa = sb + SM_WPHI + ((lane & 7) + ((lane >> 3) & 1) * 8) * 32 + lhi * 16;
      const uint32_t scr = sb + (wg ? (ST_SCR1 % NSLOT) : (ST_SCR0 % NSLOT)) * SLOT;
#pragma unroll 1
      for (int ps = 0; ps < 3; ps++) {
        const int st0 = ps == 0 ? ST_WK : (ps == 1 ? ST_WV : ST_WQ);
        const uint32_t wdesc = DESC((ps == 0 ? ST_WK % NSLOT : (ps == 1 ? ST_WV % NSLOT : ST_WQ % NSLOT)) * SLOT);
        float acc[32];
        bar_sync(4 + wg, 256);
#pragma unroll
        for (int i = 0; i < 3; i++) {
          mbar_wait(sb + SM_FULL + (st0 + i) * 8);
          wg_fence();
#pragma unroll
          for (int kk = 0; kk < (i < 2 ? 12 : 8); kk++)
            wgmma_rs_n64(acc, A[12 * i + kk], wdesc + ((i * SLOT + kk * 2048) >> 4), (i | kk) != 0);
          wg_commit();
          if (i == 1) { wg_wait<1>(); if (lead) release(st0); }
        }
        if (ps == 1 && wg == 0) bar_arrive(5, 256);
        uint32_t a[4][4], b[4][4];
        mbar_wait(sb + SM_MISCB);
        T = (*reinterpret_cast<volatile unsigned*>(smem + SM_EPOCH) & 1) ^ 1;
#pragma unroll
        for (int h = 0; h < 4; h++) ldsm4t(b[h], wpa + h * 512);
        wg_wait<0>();
        if ((tid & 127) < 2) release(st0 + 1 + (tid & 1));
        TSTAMP(2 + 2 * ps);
#pragma unroll
        for (int h = 0; h < 4; h++) {
          a[h][0] = pack2(acc[8 * h + 0] * r0, acc[8 * h + 1] * r0); a[h][1] = pack2(acc[8 * h + 2] * r1, acc[8 * h + 3] * r1);
          a[h][2] = pack2(acc[8 * h + 4] * r0, acc[8 * h + 5] * r0); a[h][3] = pack2(acc[8 * h + 6] * r1, acc[8 * h + 7] * r1);
        }
        if (ps != 1) {
          {
            float pp[4][2][4];
#pragma unroll
            for (int h = 0; h < 4; h++) {
#pragma unroll
              for (int i = 0; i < 4; i++) { pp[h][0][i] = 0.f; pp[h][1][i] = 0.f; }
              mma16816(pp[h][0], a[h], b[h][0], b[h][1]);
              mma16816(pp[h][1], a[h], b[h][2], b[h][3]);
            }
#pragma unroll
            for (int h = 0; h < 4; h++) {
              a[h][0] = pack2(pp[h][0][0], pp[h][0][1]); a[h][1] = pack2(pp[h][0][2], pp[h][0][3]);
              a[h][2] = pack2(pp[h][1][0], pp[h][1][1]); a[h][3] = pack2(pp[h][1][2], pp[h][1][3]);
            }
          }
          if (ps == 0 || wg == 0) bar_arrive(4 + (wg ^ 1), 256);
          if (ps == 0) mbar_wait(sb + SM_EMPTY + (wg ? ST_SCR1 - NSLOT : ST_SCR0 - NSLOT) * 8);
#pragma unroll 1
          for (int hp = 0; hp < 2; hp++) {
            float e[2][16];
            feat_exp(a[0], e[0]);
            feat_exp(a[1], e[1]);
            if (ps == 0) {
#pragma unroll
              for (int h = 0; h < 2; h++) {
                const float (&f)[16] = e[h];
                float sp0 = (f[0] + f[1]) + (f[4] + f[5]), sp1 = (f[2] + f[3]) + (f[6] + f[7]);
                float sn0 = (f[8] + f[9]) + (f[12] + f[13]), sn1 = (f[10] + f[11]) + (f[14] + f[15]);
                sp0 += __shfl_xor_sync(0xffffffffu, sp0, 1); sp1 += __shfl_xor_sync(0xffffffffu, sp1, 1);
                sn0 += __shfl_xor_sync(0xffffffffu, sn0, 1); sn1 += __shfl_xor_sync(0xffffffffu, sn1, 1);
                sp0 += __shfl_xor_sync(0xffffffffu, sp0, 2); sp1 += __shfl_xor_sync(0xffffffffu, sp1, 2);
                sn0 += __shfl_xor_sync(0xffffffffu, sn0, 2); sn1 += __shfl_xor_sync(0xffffffffu, sn1, 2);
                sp0 = rcp(sp0); sp1 = rcp(sp1); sn0 = rcp(sn0); sn1 = rcp(sn1);
                const uint32_t dst = scr + hp * 8192 + lrow;
                stsm4(dst + (((h * 4 + lhi) ^ lx) << 4), pack2(f[0] * sp0, f[1] * sp0), pack2(f[2] * sp1, f[3] * sp1),
                      pack2(f[4] * sp0, f[5] * sp0), pack2(f[6] * sp1, f[7] * sp1));
                stsm4(dst + (((h * 4 + 2 + lhi) ^ lx) << 4), pack2(f[8] * sn0, f[9] * sn0), pack2(f[10] * sn1, f[11] * sn1),
                      pack2(f[12] * sn0, f[13] * sn0), pack2(f[14] * sn1, f[15] * sn1));
              }
            } else {
#pragma unroll
              for (int i = 0; i < 16; i++) {
                A[i >> 2][i & 3] = A[4 + (i >> 2)][i & 3];
                A[4 + (i >> 2)][i & 3] = pack2(e[i >> 3][2 * (i & 7)], e[i >> 3][2 * (i & 7) + 1]);
              }
            }
#pragma unroll
            for (int i = 0; i < 4; i++) { a[0][i] = a[2][i]; a[1][i] = a[3][i]; }
          }
        } else {
#pragma unroll
          for (int h = 0; h < 4; h++) stsm4(scr + 16384 + lrow + (((2 * h + lhi) ^ lx) << 4), a[h][0], a[h][1], a[h][2], a[h][3]);
          fence_async_smem();
          if (wg == 0) {
            bar_arrive(3, 256);
          } else {
            bar_sync(3, 256);
            float kv[2][36];
            wg_fence();
#pragma unroll
            for (int ks = 0; ks < 8; ks++) {
              const uint32_t sk = (ks < 4 ? (ST_SCR0 % NSLOT) : (ST_SCR1 % NSLOT)) * SLOT + (ks & 3) * 2048;
              const uint32_t dv = (DESC(sk + 16384) & 0xFFFFu) | (((SM_ONES - sk - 16384) >> 4) << 16);
              wgmma_ss_n72_t11(kv[0], DESC(sk), dv, ks != 0);
              wgmma_ss_n72_t11(kv[1], DESC(sk + 8192), dv, ks != 0);
            }
            wg_commit();
            bar_arrive(4, 256);
            wg_wait<0>();
            if (lead) { mbar_arrive(sb + SM_EMPTY + ST_SCR0 * 8); mbar_arrive(sb + SM_EMPTY + ST_SCR1 * 8); }
            const bool up = wq >= 2;
            float* kvp = reinterpret_cast<float*>(smem + 2 * SLOT) + (wq * 16 + g) * 16 + 2 * t;
#pragma unroll
            for (int b = 0; b < 2; b++) {
#pragma unroll
              for (int n = 0; n < 2; n++) {
                const int i0 = 16 * b + 4 * n;
                *reinterpret_cast<float2*>(kvp + b * 1024 + n * 8) = up ? make_float2(kv[b][i0 + 8], kv[b][i0 + 9]) : make_float2(kv[b][i0], kv[b][i0 + 1]);
                *reinterpret_cast<float2*>(kvp + b * 1024 + n * 8 + 128) = up ? make_float2(kv[b][i0 + 10], kv[b][i0 + 11]) : make_float2(kv[b][i0 + 2], kv[b][i0 + 3]);
              }
            }
            reinterpret_cast<float*>(smem + 2 * SLOT)[2048 + (t >> 1) * 64 + wq * 16 + g + (t & 1) * 8] =
                (t & 2) ? ((t & 1) ? kv[1][34] : kv[1][32]) : ((t & 1) ? kv[0][34] : kv[0][32]);
            fence_async_smem();
            bar_arrive(6, 192);
          }
        }
        TSTAMP(3 + 2 * ps);
      }
#pragma unroll
      for (int i = 0; i < 32; i++) E[i >> 3][i & 7] = A[i >> 2][i & 3];
    }
    const int rh = 2 * rb + wg;
#define IDF ((g >> 1) == t ? ((g & 1) ? 0x3F800000u : 0x00003F80u) : 0u)
    const uint4* xb = reinterpret_cast<const uint4*>(smem + 2 * SLOT) + wq * 128 + lane;
    mbar_wait(sb + SM_KVR);
    TSTAMP(8);
    {
      uint4* op = &g_o[rh][hg][wq][0][lane];
      if (wg == 1) bar_sync(5, 256);
#pragma unroll 1
      for (int hp = 0; hp < 2; hp++) {
#pragma unroll
      for (int h = 0; h < 2; h++) {
        uint32_t b0[4], b1[4], b2[4];
        const uint32_t kb = sb + SM_KVS + ((2 * hp + h) * 32 + lane) * 48;
        ldsm4t(b0, kb); ldsm4t(b1, kb + 16); ldsm4t(b2, kb + 32);
        const uint32_t ep[4] = {E[h][0], E[h][1], E[h][2], E[h][3]}, en[4] = {E[h][4], E[h][5], E[h][6], E[h][7]};
        float np0[4] = {0, 0, 0, 0}, np1[4] = {0, 0, 0, 0}, nn0[4] = {0, 0, 0, 0}, nn1[4] = {0, 0, 0, 0}, dp[4] = {0, 0, 0, 0}, dn[4] = {0, 0, 0, 0};
        mma16816(dp, ep, b2[0], b2[1]);  mma16816(dn, en, b2[2], b2[3]);
        mma16816(np0, ep, b0[0], b0[1]); mma16816(nn0, en, b0[2], b0[3]);
        mma16816(np1, ep, b1[0], b1[1]); mma16816(nn1, en, b1[2], b1[3]);
        const float i0 = rcp(fmaf(dp[0], dn[1], fmaf(dn[0], dp[1], 1e-6f * dp[1] * dn[1])));
        const float i1 = rcp(fmaf(dp[2], dn[3], fmaf(dn[2], dp[3], 1e-6f * dp[3] * dn[3])));
        const float cp0 = dn[1] * i0, cn0 = dp[1] * i0, cp1 = dn[3] * i1, cn1 = dp[3] * i1;
        st_rlx4(op + (2 * hp + h) * 32,
                tg(pack2(fmaf(np0[0], cp0, nn0[0] * cn0), fmaf(np0[1], cp0, nn0[1] * cn0)), T),
                pack2(fmaf(np0[2], cp1, nn0[2] * cn1), fmaf(np0[3], cp1, nn0[3] * cn1)),
                pack2(fmaf(np1[0], cp0, nn1[0] * cn0), fmaf(np1[1], cp0, nn1[1] * cn0)),
                pack2(fmaf(np1[2], cp1, nn1[2] * cn1), fmaf(np1[3], cp1, nn1[3] * cn1)));
      }
#pragma unroll
        for (int i = 0; i < 8; i++) { E[0][i] = E[2][i]; E[1][i] = E[3][i]; }
      }
    }
    if (wg == 0) bar_arrive(5, 256);
    TSTAMP(9);

    {
      uint32_t xr[4][4];
      {
        const uint32_t* xp = reinterpret_cast<const uint32_t*>(x + (size_t)(rh * 64 + wq * 16 + g) * 512 + hg * 64 + 2 * t);
#pragma unroll
        for (int i = 0; i < 8; i++) { xr[i >> 1][(i & 1) * 2] = __ldg(xp + 4 * i); xr[i >> 1][(i & 1) * 2 + 1] = __ldg(xp + 8 * 256 + 4 * i); }
      }
      uint32_t A[8][4][4];
      const uint4* op = &g_o[rh][0][wq][0][lane];
      float acc[32];
#pragma unroll
      for (int i = 0; i < 32; i++) acc[i] = 0.f;
      add_frag(acc, xr, IDF);
#pragma unroll
      for (int p = -1; p < 4; p++) {
        if (p < 3) {
          mbar_wait(sb + SM_XF + (wg * 4 + p + 1) * 8);
          if (p == -1) TSTAMP(18);
          get_pair(A[2 * p + 2], A[2 * p + 3], xb + (p + 1) * 1024, op + (p + 1) * 1024, T);
          if (lane == 0) mbar_arrive(sb + SM_XE + (wg * 4 + p + 1) * 8);
        }
        if (p == 0 && wg == 1) bar_sync(4, 256);
        if (p >= 0) {
          if (p != 2) mbar_wait(sb + SM_FULL + (ST_WO + (p + 1) / 2) * 8);
          wg_fence();
#pragma unroll
          for (int c = 2 * p; c < 2 * p + 2; c++)
#pragma unroll
            for (int s = 0; s < 4; s++)
              wgmma_rs_n64(acc, A[c][s], DESC(((ST_WO + c / 3) % NSLOT) * SLOT + ((c % 3) * 4 + s) * 2048), 1);
        }
      }
      wg_commit();
      if (wg == 0) bar_arrive(4, 256);
      wg_wait<0>();
      if ((tid & 127) < 3) release(ST_WO + (tid & 127));
      TSTAMP(10);
      uint4* hp_ = &g_h[rh][hg][wq][0][lane];
      uint32_t hx = T;
#pragma unroll
      for (int s = 0; s < 4; s++) {
        const uint32_t h0 = pack2(acc[8 * s], acc[8 * s + 1]);
        st_rlx4(hp_ + s * 32, tg(h0, T), pack2(acc[8 * s + 2], acc[8 * s + 3]), pack2(acc[8 * s + 4], acc[8 * s + 5]), pack2(acc[8 * s + 6], acc[8 * s + 7]));
        hx |= (h0 & 1u) << (s + 1);
      }
      float s0 = 0.f, s1 = 0.f, q0 = 0.f, q1 = 0.f, q2 = 0.f, q3 = 0.f;
#pragma unroll
      for (int i = 0; i < 8; i++) {
        s0 += acc[4 * i] + acc[4 * i + 1]; s1 += acc[4 * i + 2] + acc[4 * i + 3];
        q0 = fmaf(acc[4 * i], acc[4 * i], q0); q2 = fmaf(acc[4 * i + 1], acc[4 * i + 1], q2);
        q1 = fmaf(acc[4 * i + 2], acc[4 * i + 2], q1); q3 = fmaf(acc[4 * i + 3], acc[4 * i + 3], q3);
      }
      q0 += q2; q1 += q3;
      {
        const bool up = t & 2;
        float s = (up ? s1 : s0) + __shfl_xor_sync(0xffffffffu, up ? s0 : s1, 2);
        float q = (up ? q1 : q0) + __shfl_xor_sync(0xffffffffu, up ? q0 : q1, 2);
        s += __shfl_xor_sync(0xffffffffu, s, 1);
        q += __shfl_xor_sync(0xffffffffu, q, 1);
        if (!(t & 1)) st_rlx2(&g_st[rh][hg][wq * 16 + g + (t >> 1) * 8], tg(__float_as_uint(s), T), __float_as_uint(q));
      }
      st_rlx1(&g_hx[rh][hg][wq][lane], hx);
    }
    TSTAMP(11);

    const int rh3 = 2 * rb3 + wg;
    uint32_t HH[11][4], PH[11][4];
    const uint4* pp = &g_hh[rh3][jf ^ 1][0][wq][lane];
    {
      uint32_t A[8][4][4];
      const uint4* hp_ = &g_h[rh3][0][wq][0][lane];
      uint4* hhp = &g_hh[rh3][jf][0][wq][lane];
      const uint32_t dg = (db & 0xFFFFu) | (256u << 16);
      uint32_t m0, m1;
      mbar_wait(sb + SM_XF + ((2 + wg) * 4) * 8);
      TSTAMP(0);
      {
        const uint2* sp = reinterpret_cast<const uint2*>(smem + SM_KV32 + wg * 4096) + 2 * t * 64 + wq * 16 + g;
        uint2 a0, a1, b0, b1;
        int it = 0;
#pragma unroll 1
        do {
          ld_rlx2(a0.x, a0.y, sp); ld_rlx2(a1.x, a1.y, sp + 64); ld_rlx2(b0.x, b0.y, sp + 8); ld_rlx2(b1.x, b1.y, sp + 72);
          sp = &g_st[rh3][2 * t][wq * 16 + g];
        } while (__any_sync(0xffffffffu, bad4(a0.x, a1.x, b0.x, b1.x, T)) && ++it < (1 << 18));
        float s0 = __uint_as_float(a0.x) + __uint_as_float(a1.x), q0 = __uint_as_float(a0.y) + __uint_as_float(a1.y);
        float s1 = __uint_as_float(b0.x) + __uint_as_float(b1.x), q1 = __uint_as_float(b0.y) + __uint_as_float(b1.y);
        s0 += __shfl_xor_sync(0xffffffffu, s0, 1); s1 += __shfl_xor_sync(0xffffffffu, s1, 1);
        q0 += __shfl_xor_sync(0xffffffffu, q0, 1); q1 += __shfl_xor_sync(0xffffffffu, q1, 1);
        s0 += __shfl_xor_sync(0xffffffffu, s0, 2); s1 += __shfl_xor_sync(0xffffffffu, s1, 2);
        q0 += __shfl_xor_sync(0xffffffffu, q0, 2); q1 += __shfl_xor_sync(0xffffffffu, q1, 2);
        s0 *= (1.f / 512.f); s1 *= (1.f / 512.f);
        r0 = rcp(fmaxf(q0 * (1.f / 512.f) - s0 * s0, 0.f) + 1e-5f);
        r1 = rcp(fmaxf(q1 * (1.f / 512.f) - s1 * s1, 0.f) + 1e-5f);
        m0 = pack2(s0, s0); m1 = pack2(s1, s1);
      }
      TSTAMP(12);
#define UOFF(u) ((((ST_GU + (u) / 3) % NSLOT) * SLOT + ((u) % 3) * 8192) >> 4)
#define UNIT_PRE(u)  do { if ((u) % 3 == 0) mbar_wait(sb + SM_FULL + (ST_GU + (u) / 3) * 8); } while (0)
#define UNIT_POST(u) do { wg_commit(); if ((u) % 3 == 1 && (u) > 3) { wg_wait<2>(); if (lead) release(ST_GU + (u) / 3 - 1); } } while (0)
      float acc[64];
      const int rz = blockIdx.y;
#pragma unroll
      for (int ps = 0; ps < 2; ps++) {
        wg_fence();
#pragma unroll
        for (int k = 0; k < 16; k++) {
          const int u = 16 * ps + k, c = k >> 1;
          if (ps == 0 && (k == 0 || k == 4 || k == 8)) {
#pragma unroll
            for (int p = (k == 0 ? 0 : (k == 4 ? 1 : 3)); p < (k == 0 ? 1 : (k == 4 ? 3 : 4)); p++) {
              if (p > 0) mbar_wait(sb + SM_XF + ((2 + wg) * 4 + p) * 8);
              get_pair(A[2 * p], A[2 * p + 1], xb + p * 1024, hp_ + p * 1024, T);
              if (lane == 0) {
                if (wg == 0) mbar_arrive(sb + SM_XE + (8 + p) * 8);
                else if (p > 0) release(ST_XC + p - 1);
              }
            }
          }
          if (ps == 0 && (k & 1) == 0) {
#pragma unroll
            for (int s = 0; s < 4; s++) {
              A[c][s][0] = hsub2(A[c][s][0], m0); A[c][s][1] = hsub2(A[c][s][1], m1);
              A[c][s][2] = hsub2(A[c][s][2], m0); A[c][s][3] = hsub2(A[c][s][3], m1);
            }
            wg_fence();
          }
          UNIT_PRE(u);
          wgmma_rs_n128(acc, A[c][(k & 1) * 2], dg + UOFF(u), k != 0 ? 1 : (ps ? rz : 0));
          wgmma_rs_n128(acc, A[c][(k & 1) * 2 + 1], dg + UOFF(u) + 128, 1);
          UNIT_POST(u);
          if (ps == 0 && k == 7) TSTAMP(17);
        }
        wg_wait<0>();
        TSTAMP(22 + ps);
#pragma unroll
        for (int s = 0; s < 4; s++) {
          uint32_t (&hh)[4] = HH[4 + s];
          hh[0] = tg(pack2(acc[8 * s + 0] * acc[32 + 8 * s + 0], acc[8 * s + 1] * acc[32 + 8 * s + 1]), T);
          hh[1] = pack2(acc[8 * s + 2] * acc[32 + 8 * s + 2], acc[8 * s + 3] * acc[32 + 8 * s + 3]);
          hh[2] = pack2(acc[8 * s + 4] * acc[32 + 8 * s + 4], acc[8 * s + 5] * acc[32 + 8 * s + 5]);
          hh[3] = pack2(acc[8 * s + 6] * acc[32 + 8 * s + 6], acc[8 * s + 7] * acc[32 + 8 * s + 7]);
          st_rlx4(hhp + (4 * ps + s) * 128, hh[0], hh[1], hh[2], hh[3]);
        }
      }
      {
        float ag[24], au[24];
        const uint32_t* ph7 = reinterpret_cast<const uint32_t*>(&g_hh[rh3][jf ^ 1][7][wq][31]);
        uint32_t hv = 0;
        bar_sync(1 + wg, 128);
        wg_fence();
#pragma unroll
        for (int k = 0; k < 16; k++) {
          const int u = 32 + k, c = k >> 1;
          if (k == 6) {
#pragma unroll
            for (int s = 0; s < 4; s++) ld_rlx4(HH[s], hhp + s * 128);
          }
          if (k == 9) hv = ld_rlx1(ph7);
          if (k == 12) {
            int it = 0;
#pragma unroll 1
            while (((hv ^ T) & 1) && ++it < (1 << 18)) hv = ld_rlx1(ph7);
#pragma unroll
            for (int s = 0; s < 8; s++) ld_rlx4(PH[s], pp + s * 128);
          }
          UNIT_PRE(u);
          wgmma_rs_n48(ag, A[c][(k & 1) * 2], dg + UOFF(u), k != 0);
          wgmma_rs_n48(au, A[c][(k & 1) * 2], dg + UOFF(u) + 256, k != 0);
          wgmma_rs_n48(ag, A[c][(k & 1) * 2 + 1], dg + UOFF(u) + 128, 1);
          wgmma_rs_n48(au, A[c][(k & 1) * 2 + 1], dg + UOFF(u) + 256 + 128, 1);
          UNIT_POST(u);
        }
        wg_wait<0>();
        TSTAMP(13);
#pragma unroll
        for (int s = 0; s < 3; s++) {
          uint32_t (&hh)[4] = HH[8 + s];
          hh[0] = tg(pack2(ag[8 * s + 0] * au[8 * s + 0], ag[8 * s + 1] * au[8 * s + 1]), T);
          hh[1] = pack2(ag[8 * s + 2] * au[8 * s + 2], ag[8 * s + 3] * au[8 * s + 3]);
          hh[2] = pack2(ag[8 * s + 4] * au[8 * s + 4], ag[8 * s + 5] * au[8 * s + 5]);
          hh[3] = pack2(ag[8 * s + 6] * au[8 * s + 6], ag[8 * s + 7] * au[8 * s + 7]);
          st_rlx4(hhp + (8 + s) * 128, hh[0], hh[1], hh[2], hh[3]);
        }
      }
    }
    TSTAMP(14);

    {
      float ac[3][32], acc[32];
      uint32_t hr[4][4];
      const int m = jf >> 1, oc = (jf & 1) * 4 + m;
      const uint32_t* ph10 = reinterpret_cast<const uint32_t*>(&g_hh[rh3][jf ^ 1][10][wq][31]);
      uint32_t hv = 0;
      bar_arrive(8 + wg, 256);
      wg_fence();
#pragma unroll
      for (int k = 0; k < 3; k++) {
        mbar_wait(sb + SM_FULL + (ST_D + k) * 8);
        if (k == 1) hv = ld_rlx1(ph10);
#pragma unroll
        for (int s = 0; s < 11; s++) {
          if (k == 2 && s == 4) {
            int it = 0;
#pragma unroll 1
            while (((hv ^ T) & 1) && ++it < (1 << 18)) hv = ld_rlx1(ph10);
#pragma unroll
            for (int i = 8; i < 11; i++) ld_rlx4(PH[i], pp + i * 128);
          }
          wgmma_rs_n64(ac[k], HH[s], DESC(((ST_D + k) % NSLOT) * SLOT + s * 2048), s != 0);
        }
      }
      wg_commit();
      {
        int it = 0;
#pragma unroll 1
        while (__any_sync(0xffffffffu, bad4(PH[0][0], PH[1][0], PH[2][0], PH[3][0], T) | bad4(PH[4][0], PH[5][0], PH[6][0], PH[7][0], T) |
                                       bad4(PH[8][0], PH[9][0], PH[10][0], T, T))) {
#pragma unroll
          for (int s = 0; s < 11; s++) ld_rlx4(PH[s], pp + s * 128);
          if (++it > (1 << 18)) break;
        }
      }
      TSTAMP(20);
      uint4* outb = &g_part[rh3][(jf & 1) * 4][m][wq][0][lane];
#pragma unroll
      for (int k = 0; k < 4; k++) {
        mbar_wait(sb + SM_FULL + (ST_D + 3 + k) * 8);
        wg_fence();
#pragma unroll
        for (int s = 0; s < 11; s++) {
          if (k < 3) wgmma_rs_n64(ac[k], PH[s], DESC(((ST_D + 3 + k) % NSLOT) * SLOT + s * 2048), 1);
          else wgmma_rs_n64(acc, HH[s], DESC(((ST_D + 6) % NSLOT) * SLOT + s * 2048), s != 0);
        }
        wg_commit();
        if (k > 0) {
          wg_wait<1>();
          const float (&a)[32] = ac[k - 1];
          uint4* p = outb + ((m + k) & 3) * 2048;
#pragma unroll
          for (int s = 0; s < 4; s++)
            st_rlx4(p + s * 32, tg(pack2(a[8 * s + 0], a[8 * s + 1]), T), pack2(a[8 * s + 2], a[8 * s + 3]),
                    pack2(a[8 * s + 4], a[8 * s + 5]), pack2(a[8 * s + 6], a[8 * s + 7]));
        }
      }
      uint32_t in[3][4][4];
      const uint4* inb = &g_part[rh3][oc][0][wq][0][lane];
      const uint32_t* hint = reinterpret_cast<const uint32_t*>(&g_part[rh3][oc][(m - 1 - lane) & 3][wq][3][31]);
      ld_chunk(hr, &g_h[rh3][oc][wq][0][lane]);
      uint32_t hx = ld_rlx1(&g_hx[rh3][oc][wq][lane]);
      hv = ld_rlx1(hint);
      mbar_wait(sb + SM_FULL + (ST_D + 7) * 8);
      wg_fence();
#pragma unroll
      for (int s = 0; s < 11; s++) wgmma_rs_n64(acc, PH[s], DESC(((ST_D + 7) % NSLOT) * SLOT + s * 2048), 1);
      wg_commit();
      {
        int it = 0;
#pragma unroll
        for (int q = 0; q < 3; q++) {
#pragma unroll 1
          while (!((__ballot_sync(0xffffffffu, ((hv ^ T) & 1) == 0) >> q) & 1)) {
            hv = ld_rlx1(hint);
            if (++it > (1 << 18)) break;
          }
          ld_chunk(in[q], inb + ((m - 1 - q) & 3) * 512);
        }
#pragma unroll 1
        while (__any_sync(0xffffffffu, bad4(in[0][0][0], in[0][1][0], in[0][2][0], in[0][3][0], T) | bad4(in[1][0][0], in[1][1][0], in[1][2][0], in[1][3][0], T) |
                                       bad4(in[2][0][0], in[2][1][0], in[2][2][0], in[2][3][0], T) | ((hx ^ T) & 1))) {
#pragma unroll
          for (int q = 0; q < 3; q++) ld_chunk(in[q], inb + ((m - 1 - q) & 3) * 512);
          hx = ld_rlx1(&g_hx[rh3][oc][wq][lane]);
          if (++it > (1 << 18)) break;
        }
      }
      wg_wait<0>();
      TSTAMP(15);
#pragma unroll
      for (int s = 0; s < 4; s++) hr[s][0] = (hr[s][0] & 0xFFFFFFFEu) | ((hx >> (s + 1)) & 1u);
      add_frag(acc, in[0], IDF); add_frag(acc, in[1], IDF); add_frag(acc, in[2], IDF);
#pragma unroll
      for (int i = 0; i < 32; i++) acc[i] *= (i & 2) ? r1 : r0;
      add_frag(acc, hr, IDF);
      bar_sync(9 - wg, 256);
      const uint32_t ob = sb + ((ST_D - 1) % NSLOT) * SLOT + wg * 8192;
#pragma unroll
      for (int s = 0; s < 4; s++)
        stsm4(ob + lrow + (((2 * s + lhi) ^ lx) << 4), pack2(acc[8 * s + 0], acc[8 * s + 1]), pack2(acc[8 * s + 2], acc[8 * s + 3]),
              pack2(acc[8 * s + 4], acc[8 * s + 5]), pack2(acc[8 * s + 6], acc[8 * s + 7]));
      __syncwarp();
      {
        const int row = wq * 16 + (lane >> 3);
        __nv_bfloat16* op = out + (size_t)(rh3 * 64 + row) * 512 + oc * 64 + lx * 8;
#pragma unroll
        for (int i = 0; i < 4; i++) {
          uint4 v;
          asm volatile("ld.shared.v4.b32 {%0,%1,%2,%3}, [%4];" : "=r"(v.x), "=r"(v.y), "=r"(v.z), "=r"(v.w)
                       : "r"(ob + (row + i * 4) * 128 + ((lx ^ (((lane >> 3) + i * 4) & 7)) << 4)) : "memory");
          asm volatile("st.global.v4.b32 [%0], {%1,%2,%3,%4};" ::"l"(op + i * 2048), "r"(v.x), "r"(v.y), "r"(v.z), "r"(v.w) : "memory");
        }
      }
    }
    TSTAMP(16);
    asm volatile("barrier.cluster.arrive.relaxed.aligned;" ::: "memory");
    asm volatile("barrier.cluster.wait.aligned;" ::: "memory");
  } else {
    asm volatile("setmaxnreg.dec.sync.aligned.u32 24;");
    if (elect_one()) {
      if (warp == 8) {
#pragma unroll
        for (int k = 0; k < 9; k++) {
          const int s = k < 3 ? k : (k < 6 ? k + 3 : k - 3);
          const uint32_t bar = sb + SM_FULL + s * 8;
          mbar_init(bar, 1);
          mbar_expect_tx(bar, SLOT);
          if (s >= 3 && s < 6) tma2d(sb + s * SLOT, &maps.w, 512 + hg * 64, (s - 3) * 192, bar);
          else tma3d(sb + s * SLOT, &maps.x, 0, rb * 128 + (s >= 6 ? 64 : 0), 3 * (s % 3), bar);
        }
      } else if (warp == 9) {
        mbar_init(sb + SM_MISCB, 2);
        mbar_init(sb + SM_KVB, 1);
        mbar_init(sb + SM_KVR, 2);
        mbar_expect_tx(sb + SM_KVB, 8704);
        mbar_expect_tx(sb + SM_MISCB, 2048);
        bulk_g2s(sb + SM_WPHI, wphi + hg * 1024, 2048, sb + SM_MISCB);
      } else if (warp == 10) {
        if ((sb & 0x3FFFF) != SM_BASE) __trap();
#pragma unroll 1
        for (int i = 0; i < 16; i++) {
          mbar_init(sb + SM_XF + i * 8, 1);
          mbar_expect_tx(sb + SM_XF + i * 8, (i == 8 || i == 12) ? 20480 : 16384);
          if (i < 12) mbar_init(sb + SM_XE + i * 8, 4);
        }
      } else {
        *reinterpret_cast<volatile unsigned*>(smem + SM_EPOCH) = atomicAdd(&g_start, 1u) / NCTA;
      }
      asm volatile("fence.mbarrier_init.release.cluster;" ::: "memory");
    }
    __syncwarp();
    if (warp != 11) bar_sync(0, 352);
    asm volatile("barrier.cluster.arrive.relaxed.aligned;" ::: "memory");
    if (warp == 8) {
      asm volatile("barrier.cluster.wait.aligned;" ::: "memory");
      if (elect_one()) {
        const CUtensorMap* mg = jf == 7 ? &maps.g7 : &maps.g;
        const CUtensorMap* mu = jf == 7 ? &maps.u7 : &maps.u;
        asm volatile("prefetch.tensormap [%0];" ::"l"(&maps.wo) : "memory");
        asm volatile("prefetch.tensormap [%0];" ::"l"(mg) : "memory");
        asm volatile("prefetch.tensormap [%0];" ::"l"(mu) : "memory");
        asm volatile("prefetch.tensormap [%0];" ::"l"(&maps.d) : "memory");
#pragma unroll 1
        for (int s = ST_WV; s < ST_XC; s++) {
          if (s == ST_SCR1) continue;
          mbar_wait(sb + SM_EMPTY + (s - 9) * 8);
          const uint32_t dst = sb + (s >= 18 ? s - 18 : s - 9) * SLOT, bar = sb + SM_FULL + s * 8;
          if (s < ST_WO) tma2d(dst, &maps.w, (s < ST_WQ ? 1024 : 0) + hg * 64, (s < ST_WQ ? s - ST_WV : s - ST_WQ) * 192, bar);
          else { mbar_wait(bar - 8); tma2d(dst, &maps.wo, hg * 64, (s - ST_WO) * 192, bar); }
        }
        const int jc = jf == 7 ? 0 : jf;
        int slot = (ST_GU + 1 - rank) % NSLOT;
#pragma unroll 1
        for (int s = ST_GU + 1 - rank; s < NSTAGE; s += 2) {
          mbar_wait(sb + SM_EMPTY + (s - 9) * 8);
          if (s > ST_GU && s < ST_GU + THR) mbar_wait(sb + SM_FULL + (s - 1) * 8);
          const uint32_t dst = sb + slot * SLOT, bar = sb + SM_FULL + s * 8;
          if (s < ST_D) {
#pragma unroll 1
            for (int i = 0; i < 3; i++) {
              const int u = (s - ST_GU) * 3 + i;
              tma3d_mc(dst + i * 8192, mg, (u >> 4) * 64, jc, (u & 15) * 32, bar);
              tma3d_mc(dst + i * 8192 + 4096, mu, (u >> 4) * 64, jc, (u & 15) * 32, bar);
            }
          } else {
            const int i = s - ST_D, k = i < 3 ? i : (i < 6 ? i - 3 : 3), pt = (i >= 3 && i != 6) ? 1 : 0;
            tma2d_mc(dst, &maps.d, ((jf & 1) * 4 + (((jf >> 1) + 1 + k) & 3)) * 64, (jf ^ pt) * 176, bar);
          }
          slot += 2; if (slot >= NSLOT) slot -= NSLOT;
        }
      }
      __syncwarp();
    } else {
      asm volatile("barrier.cluster.wait.aligned;" ::: "memory");
      if (warp == 11) {
#pragma unroll
        for (int i = 0; i < 4; i++)
          reinterpret_cast<uint4*>(smem + SM_ONES)[lane + 32 * i] = make_uint4(0x3F803F80u, 0x3F803F80u, 0x3F803F80u, 0x3F803F80u);
        fence_async_smem();
        __syncwarp();
        if (lane == 0) mbar_arrive(sb + SM_MISCB);
      }
      mbar_wait(sb + SM_MISCB);
      const unsigned epoch = *reinterpret_cast<volatile unsigned*>(smem + SM_EPOCH);
      const uint32_t T = (epoch & 1) ^ 1;
      if (warp == 11) {
        reinterpret_cast<float4*>(&g_kv[hg][rb * 136])[lane] = make_float4(0.f, 0.f, 0.f, 0.f);
        if (lane < 2) reinterpret_cast<float4*>(&g_kv[hg][rb * 136])[32 + lane] = make_float4(0.f, 0.f, 0.f, 0.f);
        __syncwarp();
        if (elect_one()) asm volatile("red.release.gpu.global.add.u32 [%0], 1;" ::"l"(&g_kvcnt[hg * 32 + 1]) : "memory");
        mbar_wait(sb + SM_FULL + (ST_WK + 2) * 8);
        if (elect_one()) {
          asm volatile("cp.async.bulk.prefetch.L2.global [%0], 4096;" ::"l"((const char*)wo + blockIdx.x * 4096) : "memory");
          asm volatile("cp.async.bulk.prefetch.L2.global [%0], 11008;" ::"l"((const char*)wg_ + blockIdx.x * 11008) : "memory");
          asm volatile("cp.async.bulk.prefetch.L2.global [%0], 11008;" ::"l"((const char*)wu_ + blockIdx.x * 11008) : "memory");
          asm volatile("cp.async.bulk.prefetch.L2.global [%0], 11008;" ::"l"((const char*)wd_ + blockIdx.x * 11008) : "memory");
          const unsigned target = (epoch + 1) * 16;
          unsigned v; int it = 0;
#pragma unroll 1
          do {
            asm volatile("ld.acquire.gpu.global.u32 %0, [%1];" : "=r"(v) : "l"(&g_kvcnt[hg * 32]) : "memory");
            if (++it > (1 << 18)) break;
          } while ((int)(v - target) < 0);
          TS2(0, 26);
          asm volatile("fence.proxy.async.global;" ::: "memory");
          bulk_g2s(sb + SM_KV32, &g_kv[hg][0], 8192, sb + SM_KVB);
          bulk_g2s(sb + SM_ONES, &g_kv[hg][2048], 512, sb + SM_KVB);
        }
        __syncwarp();
      } else {
        const int w = warp - 9;
        st_rlx4(reinterpret_cast<uint4*>(&g_st[2 * rb + w][hg][0]) + lane, T ^ 1, T ^ 1, T ^ 1, T ^ 1);
        if (lane < 8) st_rlx4(&g_o[2 * rb + w][hg][lane >> 1][3][30 + (lane & 1)], T ^ 1, T ^ 1, T ^ 1, T ^ 1);
        st_rlx4(&g_part[2 * rb3 + w][(jf & 1) * 4 + (lane >> 3)][jf >> 1][(lane >> 1) & 3][3][30 + (lane & 1)], T ^ 1, T ^ 1, T ^ 1, T ^ 1);
        if (lane < 16) st_rlx4(&g_hh[2 * rb3 + w][jf][7 + (lane >> 3) * 3][(lane >> 1) & 3][30 + (lane & 1)], T ^ 1, T ^ 1, T ^ 1, T ^ 1);
        if (w == 0) {
          mbar_wait(sb + SM_FULL + (ST_WQ + 2) * 8);
          unsigned v; int it = 0;
#pragma unroll 1
          do {
            asm volatile("ld.acquire.gpu.global.u32 %0, [%1];" : "=r"(v) : "l"(&g_kvcnt[hg * 32 + 1]) : "memory");
          } while ((int)(v - (epoch + 1) * 16) < 0 && ++it < (1 << 18));
          asm volatile("fence.proxy.async.global;" ::: "memory");
        }
        bar_sync(6, 192);
        if (w == 0 && elect_one()) {
          asm volatile("cp.reduce.async.bulk.global.shared::cta.bulk_group.add.f32 [%0], [%1], 8704;"
                       ::"l"(&g_kv[hg][0]), "r"(sb + 2 * SLOT) : "memory");
          asm volatile("cp.async.bulk.commit_group;" ::: "memory");
          asm volatile("cp.async.bulk.wait_group 0;" ::: "memory");
          asm volatile("red.relaxed.gpu.global.add.u32 [%0], 1;" ::"l"(&g_kvcnt[hg * 32]) : "memory");
          TS2(0, 25);
        }
        __syncwarp();
        mbar_wait(sb + SM_KVB);
        {
          const int r = w * 32 + lane;
#pragma unroll
          for (int i = 0; i < 8; i++) {
            const float4 a = reinterpret_cast<const float4*>(smem + SM_KV32)[i * 64 + r];
            *reinterpret_cast<uint2*>(smem + SM_KVS + (i * 16 + (r >> 2)) * 48 + (r & 3) * 8) = make_uint2(pack2(a.x, a.y), pack2(a.z, a.w));
          }
#pragma unroll
          for (int i = 0; i < 2; i++) {
            const uint32_t zz = pack2(reinterpret_cast<const float*>(smem + SM_ONES)[i * 64 + r], 1.0f);
            *reinterpret_cast<uint4*>(smem + SM_KVS + (i * 64 + r) * 48 + 32) = make_uint4(zz, zz, zz, zz);
          }
          __syncwarp();
          if (lane == 0) mbar_arrive(sb + SM_KVR);
        }
        if (w == 0) { mbar_wait(sb + SM_EMPTY + 11 * 8); mbar_wait(sb + SM_EMPTY + 12 * 8); mbar_wait(sb + SM_EMPTY + 13 * 8); }
#pragma unroll 1
        for (int ph = 0; ph < 2; ph++) {
          const int use = 2 * ph + w, r = ph ? 2 * rb3 + w : 2 * rb + w;
          const uint32_t* pw = ph ? reinterpret_cast<const uint32_t*>(&g_st[r][lane >> 2][(lane & 3) * 16 + 15])
                                  : reinterpret_cast<const uint32_t*>(&g_o[r][lane >> 2][lane & 3][3][31]);
          const char* src = reinterpret_cast<const char*>(ph ? &g_h[r][0][0][0][0] : &g_o[r][0][0][0][0]);
          const uint32_t bf = sb + SM_XF + use * 32, be = sb + SM_XE + (use - 1) * 32;
          if (ph) mbar_wait(sb + SM_XE + w * 32 + 24);
          int it = 0;
#pragma unroll 1
          while (__any_sync(0xffffffffu, (ld_rlx1(pw) ^ T) & 1)) { if (++it > (1 << 18)) break; }
          if (elect_one()) {
            TS2(w, 27 + ph);
            if (use > 0) mbar_wait(be);
            if (ph) bulk_g2s(sb + SM_KV32 + w * 4096, &g_st[r][0][0], 4096, bf);
#pragma unroll
            for (int p = 0; p < 4; p++) {
              if (p > 0 && use > 0) mbar_wait(be + p * 8);
              bulk_g2s(sb + 2 * SLOT + p * 16384, src + p * 16384, 16384, bf + p * 8);
            }
          }
          __syncwarp();
        }
      }
    }
    asm volatile("barrier.cluster.arrive.relaxed.aligned;" ::: "memory");
    asm volatile("barrier.cluster.wait.aligned;" ::: "memory");
  }
}

typedef CUresult (*EncodeFn)(CUtensorMap*, CUtensorMapDataType, cuuint32_t, void*, const cuuint64_t*, const cuuint64_t*,
                             const cuuint32_t*, const cuuint32_t*, CUtensorMapInterleave, CUtensorMapSwizzle,
                             CUtensorMapL2promotion, CUtensorMapFloatOOBfill);

void encode(EncodeFn fn, CUtensorMap* m, const void* base, int rank, const cuuint64_t* dims, const cuuint64_t* strides,
            const cuuint32_t* box) {
  cuuint32_t es[3] = {1, 1, 1};
  fn(m, CU_TENSOR_MAP_DATA_TYPE_BFLOAT16, (cuuint32_t)rank, const_cast<void*>(base), dims, strides, box, es,
     CU_TENSOR_MAP_INTERLEAVE_NONE, CU_TENSOR_MAP_SWIZZLE_128B, CU_TENSOR_MAP_L2_PROMOTION_L2_256B,
     CU_TENSOR_MAP_FLOAT_OOB_FILL_NONE);
}

}

extern "C" void kernel_launch(void* const* d_in, const int* in_sizes, int n_in, void* d_out, int out_size) {
  (void)in_sizes; (void)n_in; (void)out_size;
  const __nv_bfloat16* x    = (const __nv_bfloat16*)d_in[0];
  const __nv_bfloat16* wqkv = (const __nv_bfloat16*)d_in[1];
  const __nv_bfloat16* wphi = (const __nv_bfloat16*)d_in[2];
  const __nv_bfloat16* wo   = (const __nv_bfloat16*)d_in[3];
  const __nv_bfloat16* wg   = (const __nv_bfloat16*)d_in[5];
  const __nv_bfloat16* wu   = (const __nv_bfloat16*)d_in[6];
  const __nv_bfloat16* wd   = (const __nv_bfloat16*)d_in[7];

  static EncodeFn fn = nullptr;
  if (!fn) {
    void* p = nullptr;
    cudaDriverEntryPointQueryResult qr;
    cudaGetDriverEntryPoint("cuTensorMapEncodeTiled", &p, cudaEnableDefault, &qr);
    fn = (EncodeFn)p;
    cudaFuncSetAttribute(fused_kernel, cudaFuncAttributeMaxDynamicSharedMemorySize, SM_TOTAL);
  }
  Maps maps;
  {
    cuuint64_t d[3] = {64, 2048, 8}, s[2] = {1024, 128}; cuuint32_t b[3] = {64, 64, 3};
    encode(fn, &maps.x, x, 3, d, s, b);
  }
  {
    cuuint64_t d[2] = {1536, 512}, s[1] = {3072}; cuuint32_t b[2] = {64, 192};
    encode(fn, &maps.w, wqkv, 2, d, s, b);
  }
  {
    cuuint64_t d[2] = {512, 512}, s[1] = {1024}; cuuint32_t b[2] = {64, 192};
    encode(fn, &maps.wo, wo, 2, d, s, b);
  }
  {
    cuuint64_t d[3] = {176, 7, 512}, d7[3] = {144, 1, 512}, s[2] = {352, 2752}; cuuint32_t b[3] = {64, 1, 32};
    encode(fn, &maps.g, wg, 3, d, s, b);
    encode(fn, &maps.u, wu, 3, d, s, b);
    encode(fn, &maps.g7, wg + 1232, 3, d7, s, b);
    encode(fn, &maps.u7, wu + 1232, 3, d7, s, b);
  }
  {
    cuuint64_t d[2] = {512, 1376}, s[1] = {1024}; cuuint32_t b[2] = {64, 176};
    encode(fn, &maps.d, wd, 2, d, s, b);
  }
  fused_kernel<<<NCTA, 384, SM_TOTAL>>>(maps, x, wphi, wo, wg, wu, wd, (__nv_bfloat16*)d_out);
}
```

```cpp
#include <cuda_runtime.h>
#include <cuda_bf16.h>
#include <cuda.h>
#include <stdint.h>

#define PROF 0

#define SAFE_WAIT 0
#define OPRIO 1
#define THR 6

namespace {

constexpr int NCTA   = 128;
constexpr int SLOT   = 24576;
constexpr int NSLOT  = 9;
constexpr int NSTAGE = 47;

constexpr int ST_X0   = 0;
constexpr int ST_WK   = 3;
constexpr int ST_X1   = 6;
constexpr int ST_SCR0 = 9;
constexpr int ST_WV   = 10;
constexpr int ST_SCR1 = 13;
constexpr int ST_WQ   = 14;
constexpr int ST_WO   = 17;
constexpr int ST_XC   = 20;
constexpr int ST_GU   = 23;
constexpr int ST_D    = 39;

__host__ __device__ constexpr int st_empty_cnt(int d) {
  return ((d < 3 || (d >= 6 && d < 9) || (d >= ST_XC && d < ST_GU)) ? 4 : 2) * (d + 9 >= ST_GU ? 2 : 1);
}

constexpr uint32_t SM_BASE = 1024;
constexpr int SM_ONES = NSLOT * SLOT;
constexpr int SM_WPHI = SM_ONES + 2048;
constexpr int SM_KVS  = SM_WPHI + 2048;
constexpr int SM_KV32 = 4 * SLOT + 16384;
constexpr int SM_BAR  = SM_KVS + 6144;
constexpr int SM_FULL  = SM_BAR;
constexpr int SM_EMPTY = SM_BAR + NSTAGE * 8;
constexpr int SM_MISCB = SM_BAR + 2 * NSTAGE * 8;
constexpr int SM_KVB   = SM_MISCB + 8;
constexpr int SM_EPOCH = SM_KVB + 8;
constexpr int SM_XF    = SM_EPOCH + 8;
constexpr int SM_XE    = SM_XF + 16 * 8;
constexpr int SM_TOTAL = SM_BAR + 1024;

static_assert(SM_TOTAL == 232448 && SM_XE + 12 * 8 <= SM_TOTAL, "smem budget");

struct Maps { CUtensorMap x, w, wo, g, u, g7, u7, d; };

__device__ uint4    g_o[32][8][4][4][32];
__device__ uint4    g_h[32][8][4][4][32];
__device__ uint32_t g_hx[32][8][4][32];
__device__ uint2    g_st[32][8][64];
__device__ uint4    g_hh[32][8][11][4][32];
__device__ uint4    g_part[32][8][4][4][4][32];
__device__ __align__(128) float g_kv[8][2048 + 128];
__device__ unsigned g_kvcnt[8 * 32];
__device__ unsigned g_start;

__device__ __forceinline__ uint32_t smem_u32(const void* p) { return (uint32_t)__cvta_generic_to_shared(p); }
__device__ __forceinline__ void mbar_init(uint32_t bar, int cnt) {
  asm volatile("mbarrier.init.shared::cta.b64 [%0], %1;" ::"r"(bar), "r"(cnt) : "memory");
}
__device__ __forceinline__ void mbar_expect_tx(uint32_t bar, uint32_t bytes) {
  asm volatile("mbarrier.arrive.expect_tx.shared::cta.b64 _, [%0], %1;" ::"r"(bar), "r"(bytes) : "memory");
}
__device__ __forceinline__ void mbar_arrive(uint32_t bar) {
  asm volatile("mbarrier.arrive.shared::cta.b64 _, [%0];" ::"r"(bar) : "memory");
}
__device__ __forceinline__ void mbar_arrive_cluster(uint32_t bar, uint32_t rank) {
  asm volatile("{\n.reg .b32 ra;\nmapa.shared::cluster.u32 ra, %0, %1;\n"
               "mbarrier.arrive.shared::cluster.b64 _, [ra];\n}" ::"r"(bar), "r"(rank) : "memory");
}
__device__ __forceinline__ void mbar_wait_p(uint32_t bar, uint32_t parity) {
  asm volatile("{\n.reg .pred p;\nW: mbarrier.try_wait.parity.shared::cta.b64 p, [%0], %1;\n@!p bra W;\n}" ::"r"(bar), "r"(parity) : "memory");
}
__device__ __forceinline__ void mbar_wait(uint32_t bar) { mbar_wait_p(bar, 0); }
__device__ __forceinline__ bool elect_one() {
  uint32_t p;
  asm volatile("{\n.reg .pred P;\nelect.sync _|P, 0xffffffff;\nselp.u32 %0, 1, 0, P;\n}" : "=r"(p));
  return p != 0;
}
__device__ __forceinline__ void bar_sync(int id, int n)   { asm volatile("bar.sync %0, %1;" ::"r"(id), "r"(n) : "memory"); }
__device__ __forceinline__ void bar_arrive(int id, int n) { asm volatile("bar.arrive %0, %1;" ::"r"(id), "r"(n) : "memory"); }
__device__ __forceinline__ void fence_async_smem() { asm volatile("fence.proxy.async.shared::cta;" ::: "memory"); }
__device__ __forceinline__ void wg_fence()  { asm volatile("wgmma.fence.sync.aligned;" ::: "memory"); }
__device__ __forceinline__ void wg_commit() { asm volatile("wgmma.commit_group.sync.aligned;" ::: "memory"); }
template <int N> __device__ __forceinline__ void wg_wait() { asm volatile("wgmma.wait_group.sync.aligned %0;" ::"n"(N) : "memory"); }
#define DESC(off) (db + ((uint32_t)(off) >> 4))
__device__ __forceinline__ void tma2d(uint32_t dst, const CUtensorMap* m, int c0, int c1, uint32_t bar) {
  asm volatile("cp.async.bulk.tensor.2d.shared::cluster.global.mbarrier::complete_tx::bytes [%0], [%1, {%3, %4}], [%2];"
               ::"r"(dst), "l"(m), "r"(bar), "r"(c0), "r"(c1) : "memory");
}
__device__ __forceinline__ void tma2d_mc(uint32_t dst, const CUtensorMap* m, int c0, int c1, uint32_t bar) {
  asm volatile("cp.async.bulk.tensor.2d.shared::cluster.global.mbarrier::complete_tx::bytes.multicast::cluster [%0], [%1, {%3, %4}], [%2], %5;"
               ::"r"(dst), "l"(m), "r"(bar), "r"(c0), "r"(c1), "h"((uint16_t)3) : "memory");
}
__device__ __forceinline__ void tma3d(uint32_t dst, const CUtensorMap* m, int c0, int c1, int c2, uint32_t bar) {
  asm volatile("cp.async.bulk.tensor.3d.shared::cluster.global.mbarrier::complete_tx::bytes [%0], [%1, {%3, %4, %5}], [%2];"
               ::"r"(dst), "l"(m), "r"(bar), "r"(c0), "r"(c1), "r"(c2) : "memory");
}
__device__ __forceinline__ void tma3d_mc(uint32_t dst, const CUtensorMap* m, int c0, int c1, int c2, uint32_t bar) {
  asm volatile("cp.async.bulk.tensor.3d.shared::cluster.global.mbarrier::complete_tx::bytes.multicast::cluster [%0], [%1, {%3, %4, %5}], [%2], %6;"
               ::"r"(dst), "l"(m), "r"(bar), "r"(c0), "r"(c1), "r"(c2), "h"((uint16_t)3) : "memory");
}
__device__ __forceinline__ void ldsm4(uint32_t (&r)[4], uint32_t addr) {
  asm volatile("ldmatrix.sync.aligned.m8n8.x4.shared.b16 {%0,%1,%2,%3}, [%4];"
               : "=r"(r[0]), "=r"(r[1]), "=r"(r[2]), "=r"(r[3]) : "r"(addr) : "memory");
}
__device__ __forceinline__ void ldsm4t(uint32_t (&r)[4], uint32_t addr) {
  asm volatile("ldmatrix.sync.aligned.m8n8.x4.trans.shared.b16 {%0,%1,%2,%3}, [%4];"
               : "=r"(r[0]), "=r"(r[1]), "=r"(r[2]), "=r"(r[3]) : "r"(addr) : "memory");
}
__device__ __forceinline__ void stsm4(uint32_t addr, uint32_t r0, uint32_t r1, uint32_t r2, uint32_t r3) {
  asm volatile("stmatrix.sync.aligned.m8n8.x4.shared.b16 [%0], {%1,%2,%3,%4};"
               ::"r"(addr), "r"(r0), "r"(r1), "r"(r2), "r"(r3) : "memory");
}
__device__ __forceinline__ void mma16816(float (&c)[4], const uint32_t (&a)[4], uint32_t b0, uint32_t b1) {
  asm volatile("mma.sync.aligned.m16n8k16.row.col.f32.bf16.bf16.f32 {%0,%1,%2,%3},{%4,%5,%6,%7},{%8,%9},{%0,%1,%2,%3};"
               : "+f"(c[0]), "+f"(c[1]), "+f"(c[2]), "+f"(c[3])
               : "r"(a[0]), "r"(a[1]), "r"(a[2]), "r"(a[3]), "r"(b0), "r"(b1));
}
__device__ __forceinline__ void add_frag(float (&c)[32], const uint32_t (&a)[4][4], uint32_t id) {
#pragma unroll
  for (int i = 0; i < 8; i++)
    asm volatile("mma.sync.aligned.m16n8k8.row.col.f32.bf16.bf16.f32 {%0,%1,%2,%3},{%4,%5},{%6},{%0,%1,%2,%3};"
                 : "+f"(c[4 * i]), "+f"(c[4 * i + 1]), "+f"(c[4 * i + 2]), "+f"(c[4 * i + 3])
                 : "r"(a[i >> 1][(i & 1) * 2]), "r"(a[i >> 1][(i & 1) * 2 + 1]), "r"(id));
}
__device__ __forceinline__ uint32_t pack2(float lo, float hi) {
  uint32_t r; asm("cvt.rn.bf16x2.f32 %0, %1, %2;" : "=r"(r) : "f"(hi), "f"(lo)); return r;
}
__device__ __forceinline__ float blo(uint32_t w) { return __uint_as_float(w << 16); }
__device__ __forceinline__ float bhi(uint32_t w) { return __uint_as_float(w & 0xFFFF0000u); }
__device__ __forceinline__ uint32_t hsub2(uint32_t a, uint32_t b) { uint32_t r; asm("sub.rn.bf16x2 %0, %1, %2;" : "=r"(r) : "r"(a), "r"(b)); return r; }
__device__ __forceinline__ uint32_t hmax2(uint32_t a, uint32_t b) { uint32_t r; asm("max.bf16x2 %0, %1, %2;" : "=r"(r) : "r"(a), "r"(b)); return r; }
__device__ __forceinline__ uint32_t hmin2(uint32_t a, uint32_t b) { uint32_t r; asm("min.bf16x2 %0, %1, %2;" : "=r"(r) : "r"(a), "r"(b)); return r; }
__device__ __forceinline__ float ex2(float x) { float r; asm("ex2.approx.ftz.f32 %0, %1;" : "=f"(r) : "f"(x)); return r; }
__device__ __forceinline__ float rcp(float x) { float r; asm("rcp.approx.ftz.f32 %0, %1;" : "=f"(r) : "f"(x)); return r; }
__device__ __forceinline__ void ld_rlx4(uint32_t (&r)[4], const uint4* p) {
  asm volatile("{\n.reg .b128 v;\nld.relaxed.gpu.global.b128 v, [%4];\nmov.b128 {%0,%1,%2,%3}, v;\n}"
               : "=r"(r[0]), "=r"(r[1]), "=r"(r[2]), "=r"(r[3]) : "l"(p) : "memory");
}
__device__ __forceinline__ void st_rlx4(uint4* p, uint32_t a, uint32_t b, uint32_t c, uint32_t d) {
  asm volatile("{\n.reg .b128 v;\nmov.b128 v, {%1,%2,%3,%4};\nst.relaxed.gpu.global.b128 [%0], v;\n}"
               ::"l"(p), "r"(a), "r"(b), "r"(c), "r"(d) : "memory");
}
__device__ __forceinline__ void st_rlx2(uint2* p, uint32_t a, uint32_t b) {
  asm volatile("{\n.reg .b64 v;\nmov.b64 v, {%1,%2};\nst.relaxed.gpu.global.b64 [%0], v;\n}" ::"l"(p), "r"(a), "r"(b) : "memory");
}
__device__ __forceinline__ uint32_t ld_rlx1(const uint32_t* p) {
  uint32_t r; asm volatile("ld.relaxed.gpu.global.b32 %0, [%1];" : "=r"(r) : "l"(p) : "memory"); return r;
}
__device__ __forceinline__ void st_rlx1(uint32_t* p, uint32_t a) {
  asm volatile("st.relaxed.gpu.global.b32 [%0], %1;" ::"l"(p), "r"(a) : "memory");
}
__device__ __forceinline__ void ld_rlx2(uint32_t& a, uint32_t& b, const uint2* p) {
  asm volatile("{\n.reg .b64 v;\nld.relaxed.gpu.b64 v, [%2];\nmov.b64 {%0,%1}, v;\n}" : "=r"(a), "=r"(b) : "l"(p) : "memory");
}
__device__ __forceinline__ void bulk_g2s(uint32_t dst, const void* src, uint32_t bytes, uint32_t bar) {
  asm volatile("cp.async.bulk.shared::cluster.global.mbarrier::complete_tx::bytes [%0], [%1], %2, [%3];"
               ::"r"(dst), "l"(src), "r"(bytes), "r"(bar) : "memory");
}
__device__ __forceinline__ uint32_t tg(uint32_t w, uint32_t T) { return (w & 0xFFFFFFFEu) | T; }
__device__ __forceinline__ uint32_t bad4(uint32_t a, uint32_t b, uint32_t c, uint32_t d, uint32_t T) {
  uint32_t u, v;
  asm("lop3.b32 %0, %1, %2, %3, 0x7E;" : "=r"(u) : "r"(a), "r"(b), "r"(T));
  asm("lop3.b32 %0, %1, %2, %3, 0x7E;" : "=r"(v) : "r"(c), "r"(d), "r"(T));
  asm("lop3.b32 %0, %1, %2, 1, 0xA8;" : "=r"(u) : "r"(u), "r"(v));
  return u;
}

__device__ __forceinline__ void ld_chunk(uint32_t (&a)[4][4], const uint4* p) {
#pragma unroll
  for (int s = 0; s < 4; s++) ld_rlx4(a[s], p + s * 32);
}
__device__ __forceinline__ void get_pair(uint32_t (&a)[4][4], uint32_t (&b)[4][4], const uint4* sp, const uint4* gp, uint32_t T) {
  int it = 0;
#pragma unroll 1
  do {
#pragma unroll
    for (int s = 0; s < 8; s++) {
      uint32_t (&r)[4] = s < 4 ? a[s & 3] : b[s & 3];
      asm volatile("{\n.reg .b128 v;\nld.relaxed.gpu.b128 v, [%4];\nmov.b128 {%0,%1,%2,%3}, v;\n}"
                   : "=r"(r[0]), "=r"(r[1]), "=r"(r[2]), "=r"(r[3]) : "l"(sp + (s >> 2) * 512 + (s & 3) * 32) : "memory");
    }
    sp = gp;
  } while (__any_sync(0xffffffffu, bad4(a[0][0], a[1][0], a[2][0], a[3][0], T) | bad4(b[0][0], b[1][0], b[2][0], b[3][0], T)) && ++it < (1 << 18));
}

__device__ __forceinline__ void wgmma_rs_n48(float (&d)[24], const uint32_t (&a)[4], uint32_t descB, int scaleD) {
  asm volatile("{\n.reg .pred p;\n.reg .b64 db;\nsetp.ne.b32 p, %29, 0;\nmov.b64 db, {%28, 0x40000040};\n"
    "wgmma.mma_async.sync.aligned.m64n48k16.f32.bf16.bf16 {%0,%1,%2,%3,%4,%5,%6,%7,%8,%9,%10,%11,%12,%13,%14,%15,%16,%17,%18,%19,%20,%21,%22,%23}, {%24,%25,%26,%27}, db, p, 1, 1, 1;\n}\n"
    : "+f"(d[0]),"+f"(d[1]),"+f"(d[2]),"+f"(d[3]),"+f"(d[4]),"+f"(d[5]),"+f"(d[6]),"+f"(d[7]),"+f"(d[8]),"+f"(d[9]),"+f"(d[10]),"+f"(d[11]),"+f"(d[12]),"+f"(d[13]),"+f"(d[14]),"+f"(d[15]),"+f"(d[16]),"+f"(d[17]),"+f"(d[18]),"+f"(d[19]),"+f"(d[20]),"+f"(d[21]),"+f"(d[22]),"+f"(d[23])
    : "r"(a[0]), "r"(a[1]), "r"(a[2]), "r"(a[3]), "r"(descB), "r"(scaleD));
}
__device__ __forceinline__ void wgmma_rs_n64(float (&d)[32], const uint32_t (&a)[4], uint32_t descB, int scaleD) {
  asm volatile("{\n.reg .pred p;\n.reg .b64 db;\nsetp.ne.b32 p, %37, 0;\nmov.b64 db, {%36, 0x40000040};\n"
    "wgmma.mma_async.sync.aligned.m64n64k16.f32.bf16.bf16 {%0,%1,%2,%3,%4,%5,%6,%7,%8,%9,%10,%11,%12,%13,%14,%15,%16,%17,%18,%19,%20,%21,%22,%23,%24,%25,%26,%27,%28,%29,%30,%31}, {%32,%33,%34,%35}, db, p, 1, 1, 1;\n}\n"
    : "+f"(d[0]),"+f"(d[1]),"+f"(d[2]),"+f"(d[3]),"+f"(d[4]),"+f"(d[5]),"+f"(d[6]),"+f"(d[7]),"+f"(d[8]),"+f"(d[9]),"+f"(d[10]),"+f"(d[11]),"+f"(d[12]),"+f"(d[13]),"+f"(d[14]),"+f"(d[15]),"+f"(d[16]),"+f"(d[17]),"+f"(d[18]),"+f"(d[19]),"+f"(d[20]),"+f"(d[21]),"+f"(d[22]),"+f"(d[23]),"+f"(d[24]),"+f"(d[25]),"+f"(d[26]),"+f"(d[27]),"+f"(d[28]),"+f"(d[29]),"+f"(d[30]),"+f"(d[31])
    : "r"(a[0]), "r"(a[1]), "r"(a[2]), "r"(a[3]), "r"(descB), "r"(scaleD));
}
__device__ __forceinline__ void wgmma_rs_n128(float (&d)[64], const uint32_t (&a)[4], uint32_t descB, int scaleD) {
  asm volatile("{\n.reg .pred p;\n.reg .b64 db;\nsetp.ne.b32 p, %69, 0;\nmov.b64 db, {%68, 0x40000040};\n"
    "wgmma.mma_async.sync.aligned.m64n128k16.f32.bf16.bf16 {%0,%1,%2,%3,%4,%5,%6,%7,%8,%9,%10,%11,%12,%13,%14,%15,%16,%17,%18,%19,%20,%21,%22,%23,%24,%25,%26,%27,%28,%29,%30,%31,%32,%33,%34,%35,%36,%37,%38,%39,%40,%41,%42,%43,%44,%45,%46,%47,%48,%49,%50,%51,%52,%53,%54,%55,%56,%57,%58,%59,%60,%61,%62,%63}, {%64,%65,%66,%67}, db, p, 1, 1, 1;\n}\n"
    : "+f"(d[0]),"+f"(d[1]),"+f"(d[2]),"+f"(d[3]),"+f"(d[4]),"+f"(d[5]),"+f"(d[6]),"+f"(d[7]),"+f"(d[8]),"+f"(d[9]),"+f"(d[10]),"+f"(d[11]),"+f"(d[12]),"+f"(d[13]),"+f"(d[14]),"+f"(d[15]),"+f"(d[16]),"+f"(d[17]),"+f"(d[18]),"+f"(d[19]),"+f"(d[20]),"+f"(d[21]),"+f"(d[22]),"+f"(d[23]),"+f"(d[24]),"+f"(d[25]),"+f"(d[26]),"+f"(d[27]),"+f"(d[28]),"+f"(d[29]),"+f"(d[30]),"+f"(d[31]),"+f"(d[32]),"+f"(d[33]),"+f"(d[34]),"+f"(d[35]),"+f"(d[36]),"+f"(d[37]),"+f"(d[38]),"+f"(d[39]),"+f"(d[40]),"+f"(d[41]),"+f"(d[42]),"+f"(d[43]),"+f"(d[44]),"+f"(d[45]),"+f"(d[46]),"+f"(d[47]),"+f"(d[48]),"+f"(d[49]),"+f"(d[50]),"+f"(d[51]),"+f"(d[52]),"+f"(d[53]),"+f"(d[54]),"+f"(d[55]),"+f"(d[56]),"+f"(d[57]),"+f"(d[58]),"+f"(d[59]),"+f"(d[60]),"+f"(d[61]),"+f"(d[62]),"+f"(d[63])
    : "r"(a[0]), "r"(a[1]), "r"(a[2]), "r"(a[3]), "r"(descB), "r"(scaleD));
}
__device__ __forceinline__ void wgmma_ss_n72_t11(float (&d)[36], uint32_t descA, uint32_t descB, int scaleD) {
  asm volatile("{\n.reg .pred p;\n.reg .b64 da, db;\nsetp.ne.b32 p, %38, 0;\nmov.b64 da, {%36, 0x40000040};\nmov.b64 db, {%37, 0x40000040};\n"
    "wgmma.mma_async.sync.aligned.m64n72k16.f32.bf16.bf16 {%0,%1,%2,%3,%4,%5,%6,%7,%8,%9,%10,%11,%12,%13,%14,%15,%16,%17,%18,%19,%20,%21,%22,%23,%24,%25,%26,%27,%28,%29,%30,%31,%32,%33,%34,%35}, da, db, p, 1, 1, 1, 1;\n}\n"
    : "+f"(d[0]),"+f"(d[1]),"+f"(d[2]),"+f"(d[3]),"+f"(d[4]),"+f"(d[5]),"+f"(d[6]),"+f"(d[7]),"+f"(d[8]),"+f"(d[9]),"+f"(d[10]),"+f"(d[11]),"+f"(d[12]),"+f"(d[13]),"+f"(d[14]),"+f"(d[15]),"+f"(d[16]),"+f"(d[17]),"+f"(d[18]),"+f"(d[19]),"+f"(d[20]),"+f"(d[21]),"+f"(d[22]),"+f"(d[23]),"+f"(d[24]),"+f"(d[25]),"+f"(d[26]),"+f"(d[27]),"+f"(d[28]),"+f"(d[29]),"+f"(d[30]),"+f"(d[31]),"+f"(d[32]),"+f"(d[33]),"+f"(d[34]),"+f"(d[35])
    : "r"(descA), "r"(descB), "r"(scaleD));
}

#define TSTAMP(i) do {} while (0)
#define TS2(w, i) do {} while (0)

constexpr float LOG2E = 1.4426950408889634f;

__device__ __forceinline__ void feat_exp(const uint32_t (&P)[4], float (&e)[16]) {
  uint32_t a = hmax2(P[0], P[2]), b = hmax2(P[1], P[3]);
  uint32_t mx = hmax2(__byte_perm(a, b, 0x5410), __byte_perm(a, b, 0x7632));
  a = hmin2(P[0], P[2]); b = hmin2(P[1], P[3]);
  uint32_t mn = hmin2(__byte_perm(a, b, 0x5410), __byte_perm(a, b, 0x7632));
  mx = hmax2(mx, __shfl_xor_sync(0xffffffffu, mx, 1));
  mn = hmin2(mn, __shfl_xor_sync(0xffffffffu, mn, 1));
  mx = hmax2(mx, __shfl_xor_sync(0xffffffffu, mx, 2));
  mn = hmin2(mn, __shfl_xor_sync(0xffffffffu, mn, 2));
  float mx0 = -blo(mx) * LOG2E, mx1 = -bhi(mx) * LOG2E, mn0 = blo(mn) * LOG2E, mn1 = bhi(mn) * LOG2E;
  float v[8] = {blo(P[0]), bhi(P[0]), blo(P[1]), bhi(P[1]), blo(P[2]), bhi(P[2]), blo(P[3]), bhi(P[3])};
#pragma unroll
  for (int i = 0; i < 8; i++) {
    bool r1 = (i >> 1) & 1;
    e[i]     = ex2(fmaf(v[i],  LOG2E, r1 ? mx1 : mx0));
    e[8 + i] = ex2(fmaf(v[i], -LOG2E, r1 ? mn1 : mn0));
  }
}

__global__ void __cluster_dims__(2, 1, 1) __launch_bounds__(384, 1)
fused_kernel(const __grid_constant__ Maps maps, const __nv_bfloat16* __restrict__ x, const __nv_bfloat16* __restrict__ wphi,
             const __nv_bfloat16* __restrict__ wo, const __nv_bfloat16* __restrict__ wg_, const __nv_bfloat16* __restrict__ wu_,
             const __nv_bfloat16* __restrict__ wd_, __nv_bfloat16* __restrict__ out) {
  extern __shared__ __align__(1024) unsigned char smem[];
  const uint32_t sb = smem_u32(smem);
  const int tid = threadIdx.x, lane = tid & 31;
  const int warp = __shfl_sync(0xffffffffu, tid >> 5, 0);
  const uint32_t rank = blockIdx.x & 1;
  const int cl = blockIdx.x >> 1;
  int quad, qi;
  if (cl < 4) { quad = 15; qi = cl; }
  else if (cl < 36) { quad = (cl - 4) & 7; qi = (cl - 4) >> 3; }
  else { qi = (cl - 36) / 7; quad = 8 + (cl - 36) - 7 * qi; }
  const int rb = quad, hg = 2 * qi + rank;
  const int rb3 = (quad & ~1) + rank, jf = 4 * (quad & 1) + qi;

  if (warp < 8) {
    asm volatile("setmaxnreg.inc.sync.aligned.u32 240;");
    if (elect_one()) {
#pragma unroll 1
      for (int d = warp; d + 9 < NSTAGE; d += 8) {
        mbar_init(sb + SM_EMPTY + d * 8, st_empty_cnt(d));
        {
          mbar_init(sb + SM_FULL + (d + 9) * 8, 1);
          mbar_expect_tx(sb + SM_FULL + (d + 9) * 8, d + 9 >= ST_D ? 22528 : SLOT);
        }
      }
      asm volatile("fence.mbarrier_init.release.cluster;" ::: "memory");
    }
    __syncwarp();
    bar_sync(0, 352);
    asm volatile("barrier.cluster.arrive.relaxed.aligned;" ::: "memory");
    const int wg = warp >> 2, wq = warp & 3, g = lane >> 2, t = lane & 3;
    const bool lead = (tid & 127) == 0;
    constexpr uint32_t db = (SM_BASE >> 4) | (512u << 16);
    auto release = [&](int d) {
      const int s = d + NSLOT;
      mbar_arrive_cluster(sb + SM_EMPTY + d * 8, s >= ST_GU ? (uint32_t)(s & 1) : rank);
    };
    const uint32_t lrow = (uint32_t)(wq * 16 + (lane & 7) + ((lane >> 3) & 1) * 8) * 128;
    const uint32_t lx = lane & 7, lhi = lane >> 4;
    if (wg == 1) bar_arrive(4, 256);

    float r0, r1;
    uint32_t E[4][8];
    uint32_t T = 0;
    {
      uint32_t A[32][4];
      const int sx = wg ? ST_X1 : ST_X0;
      {
        const uint32_t base = sb + sx * SLOT + lrow, baseb = sb + sx * SLOT + (wq * 16 + lx + lhi * 8) * 128;
        float cs[2][4], c0[2][4], c1[2][4];
#pragma unroll
        for (int i = 0; i < 4; i++) { cs[0][i] = cs[1][i] = c0[0][i] = c0[1][i] = c1[0][i] = c1[1][i] = 0.f; }
        uint32_t bt[2][4][4];
#pragma unroll
        for (int c = -1; c < 8; c++) {
          if (c < 7) {
            const int n = c + 1;
            if (n % 3 == 0) mbar_wait(sb + SM_FULL + (sx + n / 3) * 8);
#pragma unroll
            for (int k = 0; k < 4; k++) {
              ldsm4(A[4 * n + k], base + n * 8192 + (((2 * k + lhi) ^ lx) << 4));
              ldsm4(bt[n & 1][k], baseb + n * 8192 + (((2 * k + ((lane >> 3) & 1)) ^ lx) << 4));
            }
          }
          if (c >= 0) {
#pragma unroll
            for (int k = 0; k < 4; k++) {
              const uint32_t (&f)[4] = A[4 * c + k];
              mma16816(cs[k & 1], f, 0x3F803F80u, 0x3F803F80u);
              mma16816(c0[k & 1], f, bt[c & 1][k][0], bt[c & 1][k][1]);
              mma16816(c1[k & 1], f, bt[c & 1][k][2], bt[c & 1][k][3]);
            }
          }
        }
        const float s0 = (cs[0][0] + cs[1][0]) * (1.f / 512.f), s1 = (cs[0][2] + cs[1][2]) * (1.f / 512.f);
        asm volatile("barrier.cluster.wait.aligned;" ::: "memory");
        if (lane < 3) release(sx + lane);
        const uint32_t m0 = pack2(s0, s0), m1 = pack2(s1, s1);
        float q0 = (g & 1) ? c0[0][1] + c0[1][1] : c0[0][0] + c0[1][0];
        float q1 = (g & 1) ? c1[0][3] + c1[1][3] : c1[0][2] + c1[1][2];
        q0 = __shfl_sync(0xffffffffu, q0, (lane & ~3) | (g >> 1));
        q1 = __shfl_sync(0xffffffffu, q1, (lane & ~3) | (g >> 1));
        r0 = rsqrtf(fmaxf(q0 * (1.f / 512.f) - s0 * s0, 0.f) + 1e-5f);
        r1 = rsqrtf(fmaxf(q1 * (1.f / 512.f) - s1 * s1, 0.f) + 1e-5f);
#pragma unroll
        for (int ks = 0; ks < 32; ks++) {
          A[ks][0] = hsub2(A[ks][0], m0); A[ks][1] = hsub2(A[ks][1], m1);
          A[ks][2] = hsub2(A[ks][2], m0); A[ks][3] = hsub2(A[ks][3], m1);
        }
      }
      TSTAMP(1);
      const uint32_t wpa = sb + SM_WPHI + ((lane & 7) + ((lane >> 3) & 1) * 8) * 32 + lhi * 16;
      const uint32_t scr = sb + (wg ? (ST_SCR1 % NSLOT) : (ST_SCR0 % NSLOT)) * SLOT;
#pragma unroll 1
      for (int ps = 0; ps < 3; ps++) {
        const int st0 = ps == 0 ? ST_WK : (ps == 1 ? ST_WV : ST_WQ);
        const uint32_t wdesc = DESC((ps == 0 ? ST_WK % NSLOT : (ps == 1 ? ST_WV % NSLOT : ST_WQ % NSLOT)) * SLOT);
        float acc[32];
        bar_sync(4 + wg, 256);
#pragma unroll
        for (int i = 0; i < 3; i++) {
          mbar_wait(sb + SM_FULL + (st0 + i) * 8);
          wg_fence();
#pragma unroll
          for (int kk = 0; kk < (i < 2 ? 12 : 8); kk++)
            wgmma_rs_n64(acc, A[12 * i + kk], wdesc + ((i * SLOT + kk * 2048) >> 4), (i | kk) != 0);
          wg_commit();
          if (i == 1) { wg_wait<1>(); if (lead) release(st0); }
        }
        if (ps == 1 && wg == 0) bar_arrive(5, 256);
        uint32_t a[4][4], b[4][4];
        mbar_wait(sb + SM_MISCB);
        T = (*reinterpret_cast<volatile unsigned*>(smem + SM_EPOCH) & 1) ^ 1;
#pragma unroll
        for (int h = 0; h < 4; h++) ldsm4t(b[h], wpa + h * 512);
        wg_wait<0>();
        if ((tid & 127) < 2) release(st0 + 1 + (tid & 1));
        TSTAMP(2 + 2 * ps);
#pragma unroll
        for (int h = 0; h < 4; h++) {
          a[h][0] = pack2(acc[8 * h + 0] * r0, acc[8 * h + 1] * r0); a[h][1] = pack2(acc[8 * h + 2] * r1, acc[8 * h + 3] * r1);
          a[h][2] = pack2(acc[8 * h + 4] * r0, acc[8 * h + 5] * r0); a[h][3] = pack2(acc[8 * h + 6] * r1, acc[8 * h + 7] * r1);
        }
        if (ps != 1) {
          {
            float pp[4][2][4];
#pragma unroll
            for (int h = 0; h < 4; h++) {
#pragma unroll
              for (int i = 0; i < 4; i++) { pp[h][0][i] = 0.f; pp[h][1][i] = 0.f; }
              mma16816(pp[h][0], a[h], b[h][0], b[h][1]);
              mma16816(pp[h][1], a[h], b[h][2], b[h][3]);
            }
#pragma unroll
            for (int h = 0; h < 4; h++) {
              a[h][0] = pack2(pp[h][0][0], pp[h][0][1]); a[h][1] = pack2(pp[h][0][2], pp[h][0][3]);
              a[h][2] = pack2(pp[h][1][0], pp[h][1][1]); a[h][3] = pack2(pp[h][1][2], pp[h][1][3]);
            }
          }
          if (ps == 0 || wg == 0) bar_arrive(4 + (wg ^ 1), 256);
          if (ps == 0) mbar_wait(sb + SM_EMPTY + (wg ? ST_SCR1 - NSLOT : ST_SCR0 - NSLOT) * 8);
#pragma unroll 1
          for (int hp = 0; hp < 2; hp++) {
            float e[2][16];
            feat_exp(a[0], e[0]);
            feat_exp(a[1], e[1]);
            if (ps == 0) {
#pragma unroll
              for (int h = 0; h < 2; h++) {
                const float (&f)[16] = e[h];
                float sp0 = (f[0] + f[1]) + (f[4] + f[5]), sp1 = (f[2] + f[3]) + (f[6] + f[7]);
                float sn0 = (f[8] + f[9]) + (f[12] + f[13]), sn1 = (f[10] + f[11]) + (f[14] + f[15]);
                sp0 += __shfl_xor_sync(0xffffffffu, sp0, 1); sp1 += __shfl_xor_sync(0xffffffffu, sp1, 1);
                sn0 += __shfl_xor_sync(0xffffffffu, sn0, 1); sn1 += __shfl_xor_sync(0xffffffffu, sn1, 1);
                sp0 += __shfl_xor_sync(0xffffffffu, sp0, 2); sp1 += __shfl_xor_sync(0xffffffffu, sp1, 2);
                sn0 += __shfl_xor_sync(0xffffffffu, sn0, 2); sn1 += __shfl_xor_sync(0xffffffffu, sn1, 2);
                sp0 = rcp(sp0); sp1 = rcp(sp1); sn0 = rcp(sn0); sn1 = rcp(sn1);
                const uint32_t dst = scr + hp * 8192 + lrow;
                stsm4(dst + (((h * 4 + lhi) ^ lx) << 4), pack2(f[0] * sp0, f[1] * sp0), pack2(f[2] * sp1, f[3] * sp1),
                      pack2(f[4] * sp0, f[5] * sp0), pack2(f[6] * sp1, f[7] * sp1));
                stsm4(dst + (((h * 4 + 2 + lhi) ^ lx) << 4), pack2(f[8] * sn0, f[9] * sn0), pack2(f[10] * sn1, f[11] * sn1),
                      pack2(f[12] * sn0, f[13] * sn0), pack2(f[14] * sn1, f[15] * sn1));
              }
            } else {
#pragma unroll
              for (int i = 0; i < 16; i++) {
                A[i >> 2][i & 3] = A[4 + (i >> 2)][i & 3];
                A[4 + (i >> 2)][i & 3] = pack2(e[i >> 3][2 * (i & 7)], e[i >> 3][2 * (i & 7) + 1]);
              }
            }
#pragma unroll
            for (int i = 0; i < 4; i++) { a[0][i] = a[2][i]; a[1][i] = a[3][i]; }
          }
        } else {
#pragma unroll
          for (int h = 0; h < 4; h++) stsm4(scr + 16384 + lrow + (((2 * h + lhi) ^ lx) << 4), a[h][0], a[h][1], a[h][2], a[h][3]);
          fence_async_smem();
          bar_sync(3, 256);
          float kv[36];
          wg_fence();
#pragma unroll
          for (int ks = 0; ks < 8; ks++) {
            const uint32_t sk = (ks < 4 ? (ST_SCR0 % NSLOT) : (ST_SCR1 % NSLOT)) * SLOT + (ks & 3) * 2048;
            const uint32_t dv = (DESC(sk + 16384) & 0xFFFFu) | (((SM_ONES - sk - 16384) >> 4) << 16);
            wgmma_ss_n72_t11(kv, DESC(sk) + wg * 512, dv, ks != 0);
          }
          wg_commit();
          if (wg == 1) bar_arrive(4, 256);
          wg_wait<0>();
          if (lead) { mbar_arrive(sb + SM_EMPTY + ST_SCR0 * 8); mbar_arrive(sb + SM_EMPTY + ST_SCR1 * 8); }
          const int hl = 2 * wg + (wq >> 1), f = (wq & 1) * 16 + g;
          float* kvp = reinterpret_cast<float*>(smem + 2 * SLOT) + (hl * 32 + f) * 16 + 2 * t;
          float c[8];
#pragma unroll
          for (int i = 0; i < 8; i++) c[i] = hl >= 2 ? (hl == 3 ? kv[24 + i] : kv[16 + i]) : (hl == 1 ? kv[8 + i] : kv[i]);
#pragma unroll
          for (int n = 0; n < 2; n++) {
            *reinterpret_cast<float2*>(kvp + n * 8) = make_float2(c[4 * n], c[4 * n + 1]);
            *reinterpret_cast<float2*>(kvp + n * 8 + 128) = make_float2(c[4 * n + 2], c[4 * n + 3]);
          }
          if (t < 2) reinterpret_cast<float*>(smem + 2 * SLOT)[2048 + hl * 32 + f + t * 8] = t ? kv[34] : kv[32];
          fence_async_smem();
          bar_sync(6, 320);
        }
        TSTAMP(3 + 2 * ps);
      }
#pragma unroll
      for (int i = 0; i < 32; i++) E[i >> 3][i & 7] = A[i >> 2][i & 3];
    }
    const int rh = 2 * rb + wg;
#define IDF ((g >> 1) == t ? ((g & 1) ? 0x3F800000u : 0x00003F80u) : 0u)
    const uint4* xb = reinterpret_cast<const uint4*>(smem + 2 * SLOT) + wq * 128 + lane;
    mbar_wait(sb + SM_KVB);
    {
      const int r = tid & 127;
      const float4* src = reinterpret_cast<const float4*>(smem + SM_KV32) + r;
#pragma unroll
      for (int i = 0; i < 4; i++) {
        const float4 a = src[i * 128];
        *reinterpret_cast<uint2*>(smem + SM_KVS + (i * 32 + (r >> 2)) * 48 + (r & 3) * 8) = make_uint2(pack2(a.x, a.y), pack2(a.z, a.w));
      }
      const uint32_t zz = pack2(reinterpret_cast<const float*>(smem + SM_ONES)[r], 1.0f);
      *reinterpret_cast<uint4*>(smem + SM_KVS + r * 48 + 32) = make_uint4(zz, zz, zz, zz);
      bar_sync(1 + wg, 128);
    }
    TSTAMP(8);
    {
      uint4* op = &g_o[rh][hg][wq][0][lane];
      if (wg == 1) bar_sync(5, 256);
#pragma unroll 1
      for (int hp = 0; hp < 2; hp++) {
#pragma unroll
      for (int h = 0; h < 2; h++) {
        uint32_t b0[4], b1[4], b2[4];
        const uint32_t kb = sb + SM_KVS + ((2 * hp + h) * 32 + lane) * 48;
        ldsm4t(b0, kb); ldsm4t(b1, kb + 16); ldsm4t(b2, kb + 32);
        const uint32_t ep[4] = {E[h][0], E[h][1], E[h][2], E[h][3]}, en[4] = {E[h][4], E[h][5], E[h][6], E[h][7]};
        float np0[4] = {0, 0, 0, 0}, np1[4] = {0, 0, 0, 0}, nn0[4] = {0, 0, 0, 0}, nn1[4] = {0, 0, 0, 0}, dp[4] = {0, 0, 0, 0}, dn[4] = {0, 0, 0, 0};
        mma16816(dp, ep, b2[0], b2[1]);  mma16816(dn, en, b2[2], b2[3]);
        mma16816(np0, ep, b0[0], b0[1]); mma16816(nn0, en, b0[2], b0[3]);
        mma16816(np1, ep, b1[0], b1[1]); mma16816(nn1, en, b1[2], b1[3]);
        const float i0 = rcp(fmaf(dp[0], dn[1], fmaf(dn[0], dp[1], 1e-6f * dp[1] * dn[1])));
        const float i1 = rcp(fmaf(dp[2], dn[3], fmaf(dn[2], dp[3], 1e-6f * dp[3] * dn[3])));
        const float cp0 = dn[1] * i0, cn0 = dp[1] * i0, cp1 = dn[3] * i1, cn1 = dp[3] * i1;
        st_rlx4(op + (2 * hp + h) * 32,
                tg(pack2(fmaf(np0[0], cp0, nn0[0] * cn0), fmaf(np0[1], cp0, nn0[1] * cn0)), T),
                pack2(fmaf(np0[2], cp1, nn0[2] * cn1), fmaf(np0[3], cp1, nn0[3] * cn1)),
                pack2(fmaf(np1[0], cp0, nn1[0] * cn0), fmaf(np1[1], cp0, nn1[1] * cn0)),
                pack2(fmaf(np1[2], cp1, nn1[2] * cn1), fmaf(np1[3], cp1, nn1[3] * cn1)));
      }
#pragma unroll
        for (int i = 0; i < 8; i++) { E[0][i] = E[2][i]; E[1][i] = E[3][i]; }
      }
    }
    if (wg == 0) bar_arrive(5, 256);
    bar_arrive(10 + wg, 160);
    TSTAMP(9);

    {
      uint32_t xr[4][4];
      {
        const uint32_t* xp = reinterpret_cast<const uint32_t*>(x + (size_t)(rh * 64 + wq * 16 + g) * 512 + hg * 64 + 2 * t);
#pragma unroll
        for (int i = 0; i < 8; i++) { xr[i >> 1][(i & 1) * 2] = __ldg(xp + 4 * i); xr[i >> 1][(i & 1) * 2 + 1] = __ldg(xp + 8 * 256 + 4 * i); }
      }
      uint32_t A[8][4][4];
      const uint4* op = &g_o[rh][0][wq][0][lane];
      float acc[32];
#pragma unroll
      for (int i = 0; i < 32; i++) acc[i] = 0.f;
      add_frag(acc, xr, IDF);
#pragma unroll
      for (int p = -1; p < 4; p++) {
        if (p < 3) {
          mbar_wait(sb + SM_XF + (wg * 4 + p + 1) * 8);
          if (p == -1) TSTAMP(18);
          get_pair(A[2 * p + 2], A[2 * p + 3], xb + (p + 1) * 1024, op + (p + 1) * 1024, T);
          if (lane == 0) mbar_arrive(sb + SM_XE + (wg * 4 + p + 1) * 8);
        }
        if (p == 0 && wg == 1) bar_sync(4, 256);
        if (p >= 0) {
          if (p != 2) mbar_wait(sb + SM_FULL + (ST_WO + (p + 1) / 2) * 8);
          wg_fence();
#pragma unroll
          for (int c = 2 * p; c < 2 * p + 2; c++)
#pragma unroll
            for (int s = 0; s < 4; s++)
              wgmma_rs_n64(acc, A[c][s], DESC(((ST_WO + c / 3) % NSLOT) * SLOT + ((c % 3) * 4 + s) * 2048), 1);
        }
      }
      wg_commit();
      if (wg == 0) bar_arrive(4, 256);
      wg_wait<0>();
      if ((tid & 127) < 3) release(ST_WO + (tid & 127));
      TSTAMP(10);
      uint4* hp_ = &g_h[rh][hg][wq][0][lane];
      uint32_t hx = T;
#pragma unroll
      for (int s = 0; s < 4; s++) {
        const uint32_t h0 = pack2(acc[8 * s], acc[8 * s + 1]);
        st_rlx4(hp_ + s * 32, tg(h0, T), pack2(acc[8 * s + 2], acc[8 * s + 3]), pack2(acc[8 * s + 4], acc[8 * s + 5]), pack2(acc[8 * s + 6], acc[8 * s + 7]));
        hx |= (h0 & 1u) << (s + 1);
      }
      float s0 = 0.f, s1 = 0.f, q0 = 0.f, q1 = 0.f, q2 = 0.f, q3 = 0.f;
#pragma unroll
      for (int i = 0; i < 8; i++) {
        s0 += acc[4 * i] + acc[4 * i + 1]; s1 += acc[4 * i + 2] + acc[4 * i + 3];
        q0 = fmaf(acc[4 * i], acc[4 * i], q0); q2 = fmaf(acc[4 * i + 1], acc[4 * i + 1], q2);
        q1 = fmaf(acc[4 * i + 2], acc[4 * i + 2], q1); q3 = fmaf(acc[4 * i + 3], acc[4 * i + 3], q3);
      }
      q0 += q2; q1 += q3;
      {
        const bool up = t & 2;
        float s = (up ? s1 : s0) + __shfl_xor_sync(0xffffffffu, up ? s0 : s1, 2);
        float q = (up ? q1 : q0) + __shfl_xor_sync(0xffffffffu, up ? q0 : q1, 2);
        s += __shfl_xor_sync(0xffffffffu, s, 1);
        q += __shfl_xor_sync(0xffffffffu, q, 1);
        if (!(t & 1)) st_rlx2(&g_st[rh][hg][wq * 16 + g + (t >> 1) * 8], tg(__float_as_uint(s), T), __float_as_uint(q));
      }
      st_rlx1(&g_hx[rh][hg][wq][lane], hx);
    }
    bar_arrive(10 + wg, 160);
    TSTAMP(11);

    const int rh3 = 2 * rb3 + wg;
    uint32_t HH[11][4], PH[11][4];
    const uint4* pp = &g_hh[rh3][jf ^ 1][0][wq][lane];
    {
      uint32_t A[8][4][4];
      const uint4* hp_ = &g_h[rh3][0][wq][0][lane];
      uint4* hhp = &g_hh[rh3][jf][0][wq][lane];
      const uint32_t dg = (db & 0xFFFFu) | (256u << 16);
      uint32_t m0, m1;
      mbar_wait(sb + SM_XF + ((2 + wg) * 4) * 8);
      TSTAMP(0);
      {
        const uint2* sp = reinterpret_cast<const uint2*>(smem + SM_KV32 + wg * 4096) + 2 * t * 64 + wq * 16 + g;
        uint2 a0, a1, b0, b1;
        int it = 0;
#pragma unroll 1
        do {
          ld_rlx2(a0.x, a0.y, sp); ld_rlx2(a1.x, a1.y, sp + 64); ld_rlx2(b0.x, b0.y, sp + 8); ld_rlx2(b1.x, b1.y, sp + 72);
          sp = &g_st[rh3][2 * t][wq * 16 + g];
        } while (__any_sync(0xffffffffu, bad4(a0.x, a1.x, b0.x, b1.x, T)) && ++it < (1 << 18));
        float s0 = __uint_as_float(a0.x) + __uint_as_float(a1.x), q0 = __uint_as_float(a0.y) + __uint_as_float(a1.y);
        float s1 = __uint_as_float(b0.x) + __uint_as_float(b1.x), q1 = __uint_as_float(b0.y) + __uint_as_float(b1.y);
        s0 += __shfl_xor_sync(0xffffffffu, s0, 1); s1 += __shfl_xor_sync(0xffffffffu, s1, 1);
        q0 += __shfl_xor_sync(0xffffffffu, q0, 1); q1 += __shfl_xor_sync(0xffffffffu, q1, 1);
        s0 += __shfl_xor_sync(0xffffffffu, s0, 2); s1 += __shfl_xor_sync(0xffffffffu, s1, 2);
        q0 += __shfl_xor_sync(0xffffffffu, q0, 2); q1 += __shfl_xor_sync(0xffffffffu, q1, 2);
        s0 *= (1.f / 512.f); s1 *= (1.f / 512.f);
        r0 = rcp(fmaxf(q0 * (1.f / 512.f) - s0 * s0, 0.f) + 1e-5f);
        r1 = rcp(fmaxf(q1 * (1.f / 512.f) - s1 * s1, 0.f) + 1e-5f);
        m0 = pack2(s0, s0); m1 = pack2(s1, s1);
      }
      TSTAMP(12);
#define UOFF(u) ((((ST_GU + (u) / 3) % NSLOT) * SLOT + ((u) % 3) * 8192) >> 4)
#define UNIT_PRE(u)  do { if ((u) % 3 == 0) mbar_wait(sb + SM_FULL + (ST_GU + (u) / 3) * 8); } while (0)
#define UNIT_POST(u) do { wg_commit(); if ((u) % 3 == 1 && (u) > 3) { wg_wait<2>(); if (lead) release(ST_GU + (u) / 3 - 1); } } while (0)
      float acc[64];
      const int rz = blockIdx.y;
#pragma unroll
      for (int ps = 0; ps < 2; ps++) {
        wg_fence();
#pragma unroll
        for (int k = 0; k < 16; k++) {
          const int u = 16 * ps + k, c = k >> 1;
          if (ps == 0 && (k == 0 || k == 4 || k == 8)) {
#pragma unroll
            for (int p = (k == 0 ? 0 : (k == 4 ? 1 : 3)); p < (k == 0 ? 1 : (k == 4 ? 3 : 4)); p++) {
              if (p > 0) mbar_wait(sb + SM_XF + ((2 + wg) * 4 + p) * 8);
              get_pair(A[2 * p], A[2 * p + 1], xb + p * 1024, hp_ + p * 1024, T);
              if (lane == 0) {
                if (wg == 0) mbar_arrive(sb + SM_XE + (8 + p) * 8);
                else if (p > 0) release(ST_XC + p - 1);
              }
            }
          }
          if (ps == 0 && (k & 1) == 0) {
#pragma unroll
            for (int s = 0; s < 4; s++) {
              A[c][s][0] = hsub2(A[c][s][0], m0); A[c][s][1] = hsub2(A[c][s][1], m1);
              A[c][s][2] = hsub2(A[c][s][2], m0); A[c][s][3] = hsub2(A[c][s][3], m1);
            }
            wg_fence();
          }
          UNIT_PRE(u);
          wgmma_rs_n128(acc, A[c][(k & 1) * 2], dg + UOFF(u), k != 0 ? 1 : (ps ? rz : 0));
          wgmma_rs_n128(acc, A[c][(k & 1) * 2 + 1], dg + UOFF(u) + 128, 1);
          UNIT_POST(u);
          if (ps == 0 && k == 7) TSTAMP(17);
        }
        wg_wait<0>();
        TSTAMP(22 + ps);
#pragma unroll
        for (int s = 0; s < 4; s++) {
          uint32_t (&hh)[4] = HH[4 + s];
          hh[0] = tg(pack2(acc[8 * s + 0] * acc[32 + 8 * s + 0], acc[8 * s + 1] * acc[32 + 8 * s + 1]), T);
          hh[1] = pack2(acc[8 * s + 2] * acc[32 + 8 * s + 2], acc[8 * s + 3] * acc[32 + 8 * s + 3]);
          hh[2] = pack2(acc[8 * s + 4] * acc[32 + 8 * s + 4], acc[8 * s + 5] * acc[32 + 8 * s + 5]);
          hh[3] = pack2(acc[8 * s + 6] * acc[32 + 8 * s + 6], acc[8 * s + 7] * acc[32 + 8 * s + 7]);
          st_rlx4(hhp + (4 * ps + s) * 128, hh[0], hh[1], hh[2], hh[3]);
        }
      }
      {
        float ag[24], au[24];
        const uint32_t* ph7 = reinterpret_cast<const uint32_t*>(&g_hh[rh3][jf ^ 1][7][wq][31]);
        uint32_t hv = 0;
        bar_sync(1 + wg, 128);
        wg_fence();
#pragma unroll
        for (int k = 0; k < 16; k++) {
          const int u = 32 + k, c = k >> 1;
          if (k == 6) {
#pragma unroll
            for (int s = 0; s < 4; s++) ld_rlx4(HH[s], hhp + s * 128);
          }
          if (k == 9) hv = ld_rlx1(ph7);
          if (k == 12) {
            int it = 0;
#pragma unroll 1
            while (((hv ^ T) & 1) && ++it < (1 << 18)) hv = ld_rlx1(ph7);
#pragma unroll
            for (int s = 0; s < 8; s++) ld_rlx4(PH[s], pp + s * 128);
          }
          UNIT_PRE(u);
          wgmma_rs_n48(ag, A[c][(k & 1) * 2], dg + UOFF(u), k != 0);
          wgmma_rs_n48(au, A[c][(k & 1) * 2], dg + UOFF(u) + 256, k != 0);
          wgmma_rs_n48(ag, A[c][(k & 1) * 2 + 1], dg + UOFF(u) + 128, 1);
          wgmma_rs_n48(au, A[c][(k & 1) * 2 + 1], dg + UOFF(u) + 256 + 128, 1);
          UNIT_POST(u);
        }
        wg_wait<0>();
        TSTAMP(13);
#pragma unroll
        for (int s = 0; s < 3; s++) {
          uint32_t (&hh)[4] = HH[8 + s];
          hh[0] = tg(pack2(ag[8 * s + 0] * au[8 * s + 0], ag[8 * s + 1] * au[8 * s + 1]), T);
          hh[1] = pack2(ag[8 * s + 2] * au[8 * s + 2], ag[8 * s + 3] * au[8 * s + 3]);
          hh[2] = pack2(ag[8 * s + 4] * au[8 * s + 4], ag[8 * s + 5] * au[8 * s + 5]);
          hh[3] = pack2(ag[8 * s + 6] * au[8 * s + 6], ag[8 * s + 7] * au[8 * s + 7]);
          st_rlx4(hhp + (8 + s) * 128, hh[0], hh[1], hh[2], hh[3]);
        }
      }
    }
    TSTAMP(14);

    {
      float ac[3][32], acc[32];
      uint32_t hr[4][4];
      const int m = jf >> 1, oc = (jf & 1) * 4 + m;
      const uint32_t* ph10 = reinterpret_cast<const uint32_t*>(&g_hh[rh3][jf ^ 1][10][wq][31]);
      uint32_t hv = 0;
      bar_arrive(8 + wg, 256);
      wg_fence();
#pragma unroll
      for (int k = 0; k < 3; k++) {
        mbar_wait(sb + SM_FULL + (ST_D + k) * 8);
        if (k == 1) hv = ld_rlx1(ph10);
#pragma unroll
        for (int s = 0; s < 11; s++) {
          if (k == 2 && s == 4) {
            int it = 0;
#pragma unroll 1
            while (((hv ^ T) & 1) && ++it < (1 << 18)) hv = ld_rlx1(ph10);
#pragma unroll
            for (int i = 8; i < 11; i++) ld_rlx4(PH[i], pp + i * 128);
          }
          wgmma_rs_n64(ac[k], HH[s], DESC(((ST_D + k) % NSLOT) * SLOT + s * 2048), s != 0);
        }
      }
      wg_commit();
      {
        int it = 0;
#pragma unroll 1
        while (__any_sync(0xffffffffu, bad4(PH[0][0], PH[1][0], PH[2][0], PH[3][0], T) | bad4(PH[4][0], PH[5][0], PH[6][0], PH[7][0], T) |
                                       bad4(PH[8][0], PH[9][0], PH[10][0], T, T))) {
#pragma unroll
          for (int s = 0; s < 11; s++) ld_rlx4(PH[s], pp + s * 128);
          if (++it > (1 << 18)) break;
        }
      }
      TSTAMP(20);
      uint4* outb = &g_part[rh3][(jf & 1) * 4][m][wq][0][lane];
#pragma unroll
      for (int k = 0; k < 4; k++) {
        mbar_wait(sb + SM_FULL + (ST_D + 3 + k) * 8);
        wg_fence();
#pragma unroll
        for (int s = 0; s < 11; s++) {
          if (k < 3) wgmma_rs_n64(ac[k], PH[s], DESC(((ST_D + 3 + k) % NSLOT) * SLOT + s * 2048), 1);
          else wgmma_rs_n64(acc, HH[s], DESC(((ST_D + 6) % NSLOT) * SLOT + s * 2048), s != 0);
        }
        wg_commit();
        if (k > 0) {
          wg_wait<1>();
          if (k == 1) bar_arrive(12, 320);
          const float (&a)[32] = ac[k - 1];
          uint4* p = outb + ((m + k) & 3) * 2048;
#pragma unroll
          for (int s = 0; s < 4; s++)
            st_rlx4(p + s * 32, tg(pack2(a[8 * s + 0], a[8 * s + 1]), T), pack2(a[8 * s + 2], a[8 * s + 3]),
                    pack2(a[8 * s + 4], a[8 * s + 5]), pack2(a[8 * s + 6], a[8 * s + 7]));
        }
      }
      ld_chunk(hr, &g_h[rh3][oc][wq][0][lane]);
      uint32_t hx = ld_rlx1(&g_hx[rh3][oc][wq][lane]);
      mbar_wait(sb + SM_FULL + (ST_D + 7) * 8);
      wg_fence();
#pragma unroll
      for (int s = 0; s < 11; s++) wgmma_rs_n64(acc, PH[s], DESC(((ST_D + 7) % NSLOT) * SLOT + s * 2048), 1);
      wg_commit();
      wg_wait<0>();
      TSTAMP(15);
#pragma unroll 1
      for (int q = 0; q < 3; q++) {
        uint32_t in[4][4];
        const uint4* sp = reinterpret_cast<const uint4*>(smem + ((ST_D % NSLOT) + wg) * SLOT) + q * 512 + wq * 128 + lane;
        mbar_wait_p(sb + SM_XF + (wg * 4 + q) * 8, 1);
        int it = 0;
#pragma unroll 1
        do {
#pragma unroll
          for (int s = 0; s < 4; s++)
            asm volatile("{\n.reg .b128 v;\nld.relaxed.gpu.b128 v, [%4];\nmov.b128 {%0,%1,%2,%3}, v;\n}"
                         : "=r"(in[s][0]), "=r"(in[s][1]), "=r"(in[s][2]), "=r"(in[s][3]) : "l"(sp + s * 32) : "memory");
          sp = &g_part[rh3][oc][(m - 1 - q) & 3][wq][0][lane];
        } while (__any_sync(0xffffffffu, bad4(in[0][0], in[1][0], in[2][0], in[3][0], T)) && ++it < (1 << 18));
        add_frag(acc, in, IDF);
      }
      {
        int it = 0;
#pragma unroll 1
        while (__any_sync(0xffffffffu, (hx ^ T) & 1) && ++it < (1 << 18)) hx = ld_rlx1(&g_hx[rh3][oc][wq][lane]);
      }
#pragma unroll
      for (int s = 0; s < 4; s++) hr[s][0] = (hr[s][0] & 0xFFFFFFFEu) | ((hx >> (s + 1)) & 1u);
#pragma unroll
      for (int i = 0; i < 32; i++) acc[i] *= (i & 2) ? r1 : r0;
      add_frag(acc, hr, IDF);
      bar_sync(9 - wg, 256);
      const uint32_t ob = sb + ((ST_D - 1) % NSLOT) * SLOT + wg * 8192;
#pragma unroll
      for (int s = 0; s < 4; s++)
        stsm4(ob + lrow + (((2 * s + lhi) ^ lx) << 4), pack2(acc[8 * s + 0], acc[8 * s + 1]), pack2(acc[8 * s + 2], acc[8 * s + 3]),
              pack2(acc[8 * s + 4], acc[8 * s + 5]), pack2(acc[8 * s + 6], acc[8 * s + 7]));
      __syncwarp();
      {
        const int row = wq * 16 + (lane >> 3);
        __nv_bfloat16* op = out + (size_t)(rh3 * 64 + row) * 512 + oc * 64 + lx * 8;
#pragma unroll
        for (int i = 0; i < 4; i++) {
          uint4 v;
          asm volatile("ld.shared.v4.b32 {%0,%1,%2,%3}, [%4];" : "=r"(v.x), "=r"(v.y), "=r"(v.z), "=r"(v.w)
                       : "r"(ob + (row + i * 4) * 128 + ((lx ^ (((lane >> 3) + i * 4) & 7)) << 4)) : "memory");
          asm volatile("st.global.v4.b32 [%0], {%1,%2,%3,%4};" ::"l"(op + i * 2048), "r"(v.x), "r"(v.y), "r"(v.z), "r"(v.w) : "memory");
        }
      }
    }
    TSTAMP(16);
    asm volatile("barrier.cluster.arrive.relaxed.aligned;" ::: "memory");
    asm volatile("barrier.cluster.wait.aligned;" ::: "memory");
  } else {
    asm volatile("setmaxnreg.dec.sync.aligned.u32 24;");
    if (elect_one()) {
      if (warp == 8) {
#pragma unroll
        for (int k = 0; k < 9; k++) {
          const int s = k < 3 ? k : (k < 6 ? k + 3 : k - 3);
          const uint32_t bar = sb + SM_FULL + s * 8;
          mbar_init(bar, 1);
          mbar_expect_tx(bar, SLOT);
          if (s >= 3 && s < 6) tma2d(sb + s * SLOT, &maps.w, 512 + hg * 64, (s - 3) * 192, bar);
          else tma3d(sb + s * SLOT, &maps.x, 0, rb * 128 + (s >= 6 ? 64 : 0), 3 * (s % 3), bar);
        }
      } else if (warp == 9) {
        mbar_init(sb + SM_MISCB, 2);
        mbar_init(sb + SM_KVB, 1);
        mbar_expect_tx(sb + SM_KVB, 8704);
        mbar_expect_tx(sb + SM_MISCB, 2048);
        bulk_g2s(sb + SM_WPHI, wphi + hg * 1024, 2048, sb + SM_MISCB);
      } else if (warp == 10) {
        if ((sb & 0x3FFFF) != SM_BASE) __trap();
#pragma unroll 1
        for (int i = 0; i < 16; i++) {
          mbar_init(sb + SM_XF + i * 8, 1);
          mbar_expect_tx(sb + SM_XF + i * 8, (i == 8 || i == 12) ? 20480 : 16384);
          if (i < 12) mbar_init(sb + SM_XE + i * 8, 4);
        }
      } else {
        *reinterpret_cast<volatile unsigned*>(smem + SM_EPOCH) = atomicAdd(&g_start, 1u) / NCTA;
      }
      asm volatile("fence.mbarrier_init.release.cluster;" ::: "memory");
    }
    __syncwarp();
    if (warp != 11) bar_sync(0, 352);
    asm volatile("barrier.cluster.arrive.relaxed.aligned;" ::: "memory");
    if (warp == 8) {
      asm volatile("barrier.cluster.wait.aligned;" ::: "memory");
      if (elect_one()) {
        const CUtensorMap* mg = jf == 7 ? &maps.g7 : &maps.g;
        const CUtensorMap* mu = jf == 7 ? &maps.u7 : &maps.u;
        asm volatile("prefetch.tensormap [%0];" ::"l"(&maps.wo) : "memory");
        asm volatile("prefetch.tensormap [%0];" ::"l"(mg) : "memory");
        asm volatile("prefetch.tensormap [%0];" ::"l"(mu) : "memory");
        asm volatile("prefetch.tensormap [%0];" ::"l"(&maps.d) : "memory");
#pragma unroll 1
        for (int s = ST_WV; s < ST_XC; s++) {
          if (s == ST_SCR1) continue;
          mbar_wait(sb + SM_EMPTY + (s - 9) * 8);
          const uint32_t dst = sb + (s >= 18 ? s - 18 : s - 9) * SLOT, bar = sb + SM_FULL + s * 8;
          if (s < ST_WO) tma2d(dst, &maps.w, (s < ST_WQ ? 1024 : 0) + hg * 64, (s < ST_WQ ? s - ST_WV : s - ST_WQ) * 192, bar);
          else { mbar_wait(bar - 8); tma2d(dst, &maps.wo, hg * 64, (s - ST_WO) * 192, bar); }
        }
        const int jc = jf == 7 ? 0 : jf;
        int slot = (ST_GU + 1 - rank) % NSLOT;
#pragma unroll 1
        for (int s = ST_GU + 1 - rank; s < NSTAGE; s += 2) {
          mbar_wait(sb + SM_EMPTY + (s - 9) * 8);
          if (s > ST_GU && s < ST_GU + THR) mbar_wait(sb + SM_FULL + (s - 1) * 8);
          const uint32_t dst = sb + slot * SLOT, bar = sb + SM_FULL + s * 8;
          if (s < ST_D) {
#pragma unroll 1
            for (int i = 0; i < 3; i++) {
              const int u = (s - ST_GU) * 3 + i;
              tma3d_mc(dst + i * 8192, mg, (u >> 4) * 64, jc, (u & 15) * 32, bar);
              tma3d_mc(dst + i * 8192 + 4096, mu, (u >> 4) * 64, jc, (u & 15) * 32, bar);
            }
          } else {
            const int i = s - ST_D, k = i < 3 ? i : (i < 6 ? i - 3 : 3), pt = (i >= 3 && i != 6) ? 1 : 0;
            tma2d_mc(dst, &maps.d, ((jf & 1) * 4 + (((jf >> 1) + 1 + k) & 3)) * 64, (jf ^ pt) * 176, bar);
          }
          slot += 2; if (slot >= NSLOT) slot -= NSLOT;
        }
      }
      __syncwarp();
    } else {
      asm volatile("barrier.cluster.wait.aligned;" ::: "memory");
      if (warp == 11) {
#pragma unroll
        for (int i = 0; i < 4; i++)
          reinterpret_cast<uint4*>(smem + SM_ONES)[lane + 32 * i] = make_uint4(0x3F803F80u, 0x3F803F80u, 0x3F803F80u, 0x3F803F80u);
        fence_async_smem();
        __syncwarp();
        if (lane == 0) mbar_arrive(sb + SM_MISCB);
      }
      mbar_wait(sb + SM_MISCB);
      const unsigned epoch = *reinterpret_cast<volatile unsigned*>(smem + SM_EPOCH);
      const uint32_t T = (epoch & 1) ^ 1;
      if (warp == 11) {
        reinterpret_cast<float4*>(&g_kv[hg][rb * 136])[lane] = make_float4(0.f, 0.f, 0.f, 0.f);
        if (lane < 2) reinterpret_cast<float4*>(&g_kv[hg][rb * 136])[32 + lane] = make_float4(0.f, 0.f, 0.f, 0.f);
        __syncwarp();
        if (elect_one()) asm volatile("red.release.gpu.global.add.u32 [%0], 1;" ::"l"(&g_kvcnt[hg * 32 + 1]) : "memory");
        mbar_wait(sb + SM_FULL + (ST_WK + 2) * 8);
        if (elect_one()) {
          asm volatile("cp.async.bulk.prefetch.L2.global [%0], 4096;" ::"l"((const char*)wo + blockIdx.x * 4096) : "memory");
          asm volatile("cp.async.bulk.prefetch.L2.global [%0], 11008;" ::"l"((const char*)wg_ + blockIdx.x * 11008) : "memory");
          asm volatile("cp.async.bulk.prefetch.L2.global [%0], 11008;" ::"l"((const char*)wu_ + blockIdx.x * 11008) : "memory");
          asm volatile("cp.async.bulk.prefetch.L2.global [%0], 11008;" ::"l"((const char*)wd_ + blockIdx.x * 11008) : "memory");
          mbar_wait(sb + SM_EMPTY + ST_SCR0 * 8);
          const unsigned target = (epoch + 1) * 16;
          unsigned v; int it = 0;
#pragma unroll 1
          do {
            asm volatile("ld.acquire.gpu.global.u32 %0, [%1];" : "=r"(v) : "l"(&g_kvcnt[hg * 32]) : "memory");
            if (++it > (1 << 18)) break;
          } while ((int)(v - target) < 0);
          TS2(0, 26);
          asm volatile("fence.proxy.async.global;" ::: "memory");
          bulk_g2s(sb + SM_KV32, &g_kv[hg][0], 8192, sb + SM_KVB);
          bulk_g2s(sb + SM_ONES, &g_kv[hg][2048], 512, sb + SM_KVB);
        }
        __syncwarp();
      } else {
        const int w = warp - 9;
        st_rlx4(reinterpret_cast<uint4*>(&g_st[2 * rb + w][hg][0]) + lane, T ^ 1, T ^ 1, T ^ 1, T ^ 1);
        if (lane < 8) st_rlx4(&g_o[2 * rb + w][hg][lane >> 1][3][30 + (lane & 1)], T ^ 1, T ^ 1, T ^ 1, T ^ 1);
        st_rlx4(&g_part[2 * rb3 + w][(jf & 1) * 4 + (lane >> 3)][jf >> 1][(lane >> 1) & 3][3][30 + (lane & 1)], T ^ 1, T ^ 1, T ^ 1, T ^ 1);
        if (lane < 16) st_rlx4(&g_hh[2 * rb3 + w][jf][7 + (lane >> 3) * 3][(lane >> 1) & 3][30 + (lane & 1)], T ^ 1, T ^ 1, T ^ 1, T ^ 1);
        if (w == 0) {
          mbar_wait(sb + SM_FULL + (ST_WQ + 2) * 8);
          unsigned v; int it = 0;
#pragma unroll 1
          do {
            asm volatile("ld.acquire.gpu.global.u32 %0, [%1];" : "=r"(v) : "l"(&g_kvcnt[hg * 32 + 1]) : "memory");
          } while ((int)(v - (epoch + 1) * 16) < 0 && ++it < (1 << 18));
          asm volatile("fence.proxy.async.global;" ::: "memory");
        }
        bar_sync(6, 320);
        if (w == 0 && elect_one()) {
          asm volatile("cp.reduce.async.bulk.global.shared::cta.bulk_group.add.f32 [%0], [%1], 8704;"
                       ::"l"(&g_kv[hg][0]), "r"(sb + 2 * SLOT) : "memory");
          asm volatile("cp.async.bulk.commit_group;" ::: "memory");
          asm volatile("cp.async.bulk.wait_group 0;" ::: "memory");
          asm volatile("red.relaxed.gpu.global.add.u32 [%0], 1;" ::"l"(&g_kvcnt[hg * 32]) : "memory");
          TS2(0, 25);
        }
        __syncwarp();
        mbar_wait(sb + SM_KVB);
        if (w == 0) { mbar_wait(sb + SM_EMPTY + 11 * 8); mbar_wait(sb + SM_EMPTY + 12 * 8); mbar_wait(sb + SM_EMPTY + 13 * 8); }
#pragma unroll 1
        for (int ph = 0; ph < 2; ph++) {
          const int use = 2 * ph + w, r = ph ? 2 * rb3 + w : 2 * rb + w;
          const uint32_t* pw = ph ? reinterpret_cast<const uint32_t*>(&g_st[r][lane >> 2][(lane & 3) * 16 + 15])
                                  : reinterpret_cast<const uint32_t*>(&g_o[r][lane >> 2][lane & 3][3][31]);
          const char* src = reinterpret_cast<const char*>(ph ? &g_h[r][0][0][0][0] : &g_o[r][0][0][0][0]);
          const uint32_t bf = sb + SM_XF + use * 32, be = sb + SM_XE + (use - 1) * 32;
          bar_sync(10 + w, 160);
          int it = 0;
#pragma unroll 1
          for (bool miss = true; __any_sync(0xffffffffu, miss) && ++it < (1 << 18);) { if (miss) miss = (ld_rlx1(pw) ^ T) & 1; }
          if (elect_one()) {
            TS2(w, 27 + ph);
            if (use > 0) mbar_wait(be);
            if (ph) bulk_g2s(sb + SM_KV32 + w * 4096, &g_st[r][0][0], 4096, bf);
#pragma unroll
            for (int p = 0; p < 4; p++) {
              if (p > 0 && use > 0) mbar_wait(be + p * 8);
              bulk_g2s(sb + 2 * SLOT + p * 16384, src + p * 16384, 16384, bf + p * 8);
            }
          }
          __syncwarp();
        }
        {
          const int m = jf >> 1, oc = (jf & 1) * 4 + m;
          const uint32_t* pw = reinterpret_cast<const uint32_t*>(&g_part[2 * rb3 + w][oc][(m - 1 - (lane >> 2)) & 3][lane & 3][3][31]);
          bar_sync(12, 320);
          bool miss = lane < 12; int it = 0;
#pragma unroll 1
          for (int q = 0; q < 3; q++) {
#pragma unroll 1
            while ((__ballot_sync(0xffffffffu, miss) >> (4 * q) & 15) && ++it < (1 << 18)) { if (miss && (lane >> 2) <= q + 1) miss = (ld_rlx1(pw) ^ T) & 1; }
            if (elect_one()) {
              const uint32_t bar = sb + SM_XF + (w * 4 + q) * 8;
              mbar_expect_tx(bar, 8192);
              bulk_g2s(sb + ((ST_D % NSLOT) + w) * SLOT + q * 8192, &g_part[2 * rb3 + w][oc][(m - 1 - q) & 3][0][0][0], 8192, bar);
            }
            __syncwarp();
          }
        }
      }
    }
    asm volatile("barrier.cluster.arrive.relaxed.aligned;" ::: "memory");
    asm volatile("barrier.cluster.wait.aligned;" ::: "memory");
  }
}

typedef CUresult (*EncodeFn)(CUtensorMap*, CUtensorMapDataType, cuuint32_t, void*, const cuuint64_t*, const cuuint64_t*,
                             const cuuint32_t*, const cuuint32_t*, CUtensorMapInterleave, CUtensorMapSwizzle,
                             CUtensorMapL2promotion, CUtensorMapFloatOOBfill);

void encode(EncodeFn fn, CUtensorMap* m, const void* base, int rank, const cuuint64_t* dims, const cuuint64_t* strides,
            const cuuint32_t* box) {
  cuuint32_t es[3] = {1, 1, 1};
  fn(m, CU_TENSOR_MAP_DATA_TYPE_BFLOAT16, (cuuint32_t)rank, const_cast<void*>(base), dims, strides, box, es,
     CU_TENSOR_MAP_INTERLEAVE_NONE, CU_TENSOR_MAP_SWIZZLE_128B, CU_TENSOR_MAP_L2_PROMOTION_L2_256B,
     CU_TENSOR_MAP_FLOAT_OOB_FILL_NONE);
}

}

extern "C" void kernel_launch(void* const* d_in, const int* in_sizes, int n_in, void* d_out, int out_size) {
  (void)in_sizes; (void)n_in; (void)out_size;
  const __nv_bfloat16* x    = (const __nv_bfloat16*)d_in[0];
  const __nv_bfloat16* wqkv = (const __nv_bfloat16*)d_in[1];
  const __nv_bfloat16* wphi = (const __nv_bfloat16*)d_in[2];
  const __nv_bfloat16* wo   = (const __nv_bfloat16*)d_in[3];
  const __nv_bfloat16* wg   = (const __nv_bfloat16*)d_in[5];
  const __nv_bfloat16* wu   = (const __nv_bfloat16*)d_in[6];
  const __nv_bfloat16* wd   = (const __nv_bfloat16*)d_in[7];

  static EncodeFn fn = nullptr;
  if (!fn) {
    void* p = nullptr;
    cudaDriverEntryPointQueryResult qr;
    cudaGetDriverEntryPoint("cuTensorMapEncodeTiled", &p, cudaEnableDefault, &qr);
    fn = (EncodeFn)p;
    cudaFuncSetAttribute(fused_kernel, cudaFuncAttributeMaxDynamicSharedMemorySize, SM_TOTAL);
  }
  Maps maps;
  {
    cuuint64_t d[3] = {64, 2048, 8}, s[2] = {1024, 128}; cuuint32_t b[3] = {64, 64, 3};
    encode(fn, &maps.x, x, 3, d, s, b);
  }
  {
    cuuint64_t d[2] = {1536, 512}, s[1] = {3072}; cuuint32_t b[2] = {64, 192};
    encode(fn, &maps.w, wqkv, 2, d, s, b);
  }
  {
    cuuint64_t d[2] = {512, 512}, s[1] = {1024}; cuuint32_t b[2] = {64, 192};
    encode(fn, &maps.wo, wo, 2, d, s, b);
  }
  {
    cuuint64_t d[3] = {176, 7, 512}, d7[3] = {144, 1, 512}, s[2] = {352, 2752}; cuuint32_t b[3] = {64, 1, 32};
    encode(fn, &maps.g, wg, 3, d, s, b);
    encode(fn, &maps.u, wu, 3, d, s, b);
    encode(fn, &maps.g7, wg + 1232, 3, d7, s, b);
    encode(fn, &maps.u7, wu + 1232, 3, d7, s, b);
  }
  {
    cuuint64_t d[2] = {512, 1376}, s[1] = {1024}; cuuint32_t b[2] = {64, 176};
    encode(fn, &maps.d, wd, 2, d, s, b);
  }
  fused_kernel<<<NCTA, 384, SM_TOTAL>>>(maps, x, wphi, wo, wg, wu, wd, (__nv_bfloat16*)d_out);
}
```

```cpp
#include <cuda_runtime.h>
#include <cuda_bf16.h>
#include <cuda.h>
#include <stdint.h>

#define PROF 0

#define SAFE_WAIT 0
#define OPRIO 1
#define THR 6

namespace {

constexpr int NCTA   = 128;
constexpr int SLOT   = 24576;
constexpr int NSLOT  = 9;
constexpr int NSTAGE = 47;

constexpr int ST_X0   = 0;
constexpr int ST_WK   = 3;
constexpr int ST_X1   = 6;
constexpr int ST_SCR0 = 9;
constexpr int ST_WV   = 10;
constexpr int ST_SCR1 = 13;
constexpr int ST_WQ   = 14;
constexpr int ST_WO   = 17;
constexpr int ST_XC   = 20;
constexpr int ST_GU   = 23;
constexpr int ST_D    = 39;

__host__ __device__ constexpr int st_empty_cnt(int d) {
  return ((d < 3 || (d >= 6 && d < 9) || (d >= ST_XC && d < ST_GU)) ? 4 : 2) * (d + 9 >= ST_GU ? 2 : 1);
}

constexpr uint32_t SM_BASE = 1024;
constexpr int SM_ONES = NSLOT * SLOT;
constexpr int SM_WPHI = SM_ONES + 2048;
constexpr int SM_KVS  = SM_WPHI + 2048;
constexpr int SM_KV32 = 4 * SLOT + 16384;
constexpr int SM_BAR  = SM_KVS + 6144;
constexpr int SM_FULL  = SM_BAR;
constexpr int SM_EMPTY = SM_BAR + NSTAGE * 8;
constexpr int SM_MISCB = SM_BAR + 2 * NSTAGE * 8;
constexpr int SM_KVB   = SM_MISCB + 8;
constexpr int SM_EPOCH = SM_KVB + 8;
constexpr int SM_XF    = SM_EPOCH + 8;
constexpr int SM_XE    = SM_XF + 16 * 8;
constexpr int SM_TOTAL = SM_BAR + 1024;

static_assert(SM_TOTAL == 232448 && SM_XE + 12 * 8 <= SM_TOTAL, "smem budget");

struct Maps { CUtensorMap x, w, wo, g, u, g7, u7, d; };

__device__ uint4    g_o[32][8][4][4][32];
__device__ uint4    g_h[32][8][4][4][32];
__device__ uint32_t g_hx[32][8][4][32];
__device__ uint2    g_st[32][8][64];
__device__ uint4    g_hh[32][8][11][4][32];
__device__ uint4    g_part[32][8][4][4][4][32];
__device__ __align__(128) float g_kv[8][2048 + 128];
__device__ unsigned g_kvcnt[8 * 32];
__device__ unsigned g_start;

__device__ __forceinline__ uint32_t smem_u32(const void* p) { return (uint32_t)__cvta_generic_to_shared(p); }
__device__ __forceinline__ void mbar_init(uint32_t bar, int cnt) {
  asm volatile("mbarrier.init.shared::cta.b64 [%0], %1;" ::"r"(bar), "r"(cnt) : "memory");
}
__device__ __forceinline__ void mbar_expect_tx(uint32_t bar, uint32_t bytes) {
  asm volatile("mbarrier.arrive.expect_tx.shared::cta.b64 _, [%0], %1;" ::"r"(bar), "r"(bytes) : "memory");
}
__device__ __forceinline__ void mbar_arrive(uint32_t bar) {
  asm volatile("mbarrier.arrive.shared::cta.b64 _, [%0];" ::"r"(bar) : "memory");
}
__device__ __forceinline__ void mbar_arrive_cluster(uint32_t bar, uint32_t rank) {
  asm volatile("{\n.reg .b32 ra;\nmapa.shared::cluster.u32 ra, %0, %1;\n"
               "mbarrier.arrive.shared::cluster.b64 _, [ra];\n}" ::"r"(bar), "r"(rank) : "memory");
}
__device__ __forceinline__ void mbar_wait_p(uint32_t bar, uint32_t parity) {
  asm volatile("{\n.reg .pred p;\nW: mbarrier.try_wait.parity.shared::cta.b64 p, [%0], %1;\n@!p bra W;\n}" ::"r"(bar), "r"(parity) : "memory");
}
__device__ __forceinline__ void mbar_wait(uint32_t bar) { mbar_wait_p(bar, 0); }
__device__ __forceinline__ bool elect_one() {
  uint32_t p;
  asm volatile("{\n.reg .pred P;\nelect.sync _|P, 0xffffffff;\nselp.u32 %0, 1, 0, P;\n}" : "=r"(p));
  return p != 0;
}
__device__ __forceinline__ void bar_sync(int id, int n)   { asm volatile("bar.sync %0, %1;" ::"r"(id), "r"(n) : "memory"); }
__device__ __forceinline__ void bar_arrive(int id, int n) { asm volatile("bar.arrive %0, %1;" ::"r"(id), "r"(n) : "memory"); }
__device__ __forceinline__ void fence_async_smem() { asm volatile("fence.proxy.async.shared::cta;" ::: "memory"); }
__device__ __forceinline__ void wg_fence()  { asm volatile("wgmma.fence.sync.aligned;" ::: "memory"); }
__device__ __forceinline__ void wg_commit() { asm volatile("wgmma.commit_group.sync.aligned;" ::: "memory"); }
template <int N> __device__ __forceinline__ void wg_wait() { asm volatile("wgmma.wait_group.sync.aligned %0;" ::"n"(N) : "memory"); }
#define DESC(off) (db + ((uint32_t)(off) >> 4))
__device__ __forceinline__ void tma2d(uint32_t dst, const CUtensorMap* m, int c0, int c1, uint32_t bar) {
  asm volatile("cp.async.bulk.tensor.2d.shared::cluster.global.mbarrier::complete_tx::bytes [%0], [%1, {%3, %4}], [%2];"
               ::"r"(dst), "l"(m), "r"(bar), "r"(c0), "r"(c1) : "memory");
}
__device__ __forceinline__ void tma2d_mc(uint32_t dst, const CUtensorMap* m, int c0, int c1, uint32_t bar) {
  asm volatile("cp.async.bulk.tensor.2d.shared::cluster.global.mbarrier::complete_tx::bytes.multicast::cluster [%0], [%1, {%3, %4}], [%2], %5;"
               ::"r"(dst), "l"(m), "r"(bar), "r"(c0), "r"(c1), "h"((uint16_t)3) : "memory");
}
__device__ __forceinline__ void tma3d(uint32_t dst, const CUtensorMap* m, int c0, int c1, int c2, uint32_t bar) {
  asm volatile("cp.async.bulk.tensor.3d.shared::cluster.global.mbarrier::complete_tx::bytes [%0], [%1, {%3, %4, %5}], [%2];"
               ::"r"(dst), "l"(m), "r"(bar), "r"(c0), "r"(c1), "r"(c2) : "memory");
}
__device__ __forceinline__ void tma3d_mc(uint32_t dst, const CUtensorMap* m, int c0, int c1, int c2, uint32_t bar) {
  asm volatile("cp.async.bulk.tensor.3d.shared::cluster.global.mbarrier::complete_tx::bytes.multicast::cluster [%0], [%1, {%3, %4, %5}], [%2], %6;"
               ::"r"(dst), "l"(m), "r"(bar), "r"(c0), "r"(c1), "r"(c2), "h"((uint16_t)3) : "memory");
}
__device__ __forceinline__ void ldsm4(uint32_t (&r)[4], uint32_t addr) {
  asm volatile("ldmatrix.sync.aligned.m8n8.x4.shared.b16 {%0,%1,%2,%3}, [%4];"
               : "=r"(r[0]), "=r"(r[1]), "=r"(r[2]), "=r"(r[3]) : "r"(addr) : "memory");
}
__device__ __forceinline__ void ldsm4t(uint32_t (&r)[4], uint32_t addr) {
  asm volatile("ldmatrix.sync.aligned.m8n8.x4.trans.shared.b16 {%0,%1,%2,%3}, [%4];"
               : "=r"(r[0]), "=r"(r[1]), "=r"(r[2]), "=r"(r[3]) : "r"(addr) : "memory");
}
__device__ __forceinline__ void stsm4(uint32_t addr, uint32_t r0, uint32_t r1, uint32_t r2, uint32_t r3) {
  asm volatile("stmatrix.sync.aligned.m8n8.x4.shared.b16 [%0], {%1,%2,%3,%4};"
               ::"r"(addr), "r"(r0), "r"(r1), "r"(r2), "r"(r3) : "memory");
}
__device__ __forceinline__ void mma16816(float (&c)[4], const uint32_t (&a)[4], uint32_t b0, uint32_t b1) {
  asm volatile("mma.sync.aligned.m16n8k16.row.col.f32.bf16.bf16.f32 {%0,%1,%2,%3},{%4,%5,%6,%7},{%8,%9},{%0,%1,%2,%3};"
               : "+f"(c[0]), "+f"(c[1]), "+f"(c[2]), "+f"(c[3])
               : "r"(a[0]), "r"(a[1]), "r"(a[2]), "r"(a[3]), "r"(b0), "r"(b1));
}
__device__ __forceinline__ void add_frag(float (&c)[32], const uint32_t (&a)[4][4], uint32_t id) {
#pragma unroll
  for (int i = 0; i < 8; i++)
    asm volatile("mma.sync.aligned.m16n8k8.row.col.f32.bf16.bf16.f32 {%0,%1,%2,%3},{%4,%5},{%6},{%0,%1,%2,%3};"
                 : "+f"(c[4 * i]), "+f"(c[4 * i + 1]), "+f"(c[4 * i + 2]), "+f"(c[4 * i + 3])
                 : "r"(a[i >> 1][(i & 1) * 2]), "r"(a[i >> 1][(i & 1) * 2 + 1]), "r"(id));
}
__device__ __forceinline__ uint32_t pack2(float lo, float hi) {
  uint32_t r; asm("cvt.rn.bf16x2.f32 %0, %1, %2;" : "=r"(r) : "f"(hi), "f"(lo)); return r;
}
__device__ __forceinline__ float blo(uint32_t w) { return __uint_as_float(w << 16); }
__device__ __forceinline__ float bhi(uint32_t w) { return __uint_as_float(w & 0xFFFF0000u); }
__device__ __forceinline__ uint32_t hsub2(uint32_t a, uint32_t b) { uint32_t r; asm("sub.rn.bf16x2 %0, %1, %2;" : "=r"(r) : "r"(a), "r"(b)); return r; }
__device__ __forceinline__ uint32_t hmax2(uint32_t a, uint32_t b) { uint32_t r; asm("max.bf16x2 %0, %1, %2;" : "=r"(r) : "r"(a), "r"(b)); return r; }
__device__ __forceinline__ uint32_t hmin2(uint32_t a, uint32_t b) { uint32_t r; asm("min.bf16x2 %0, %1, %2;" : "=r"(r) : "r"(a), "r"(b)); return r; }
__device__ __forceinline__ float ex2(float x) { float r; asm("ex2.approx.ftz.f32 %0, %1;" : "=f"(r) : "f"(x)); return r; }
__device__ __forceinline__ float rcp(float x) { float r; asm("rcp.approx.ftz.f32 %0, %1;" : "=f"(r) : "f"(x)); return r; }
__device__ __forceinline__ void ld_rlx4(uint32_t (&r)[4], const uint4* p) {
  asm volatile("{\n.reg .b128 v;\nld.relaxed.gpu.global.b128 v, [%4];\nmov.b128 {%0,%1,%2,%3}, v;\n}"
               : "=r"(r[0]), "=r"(r[1]), "=r"(r[2]), "=r"(r[3]) : "l"(p) : "memory");
}
__device__ __forceinline__ void st_rlx4(uint4* p, uint32_t a, uint32_t b, uint32_t c, uint32_t d) {
  asm volatile("{\n.reg .b128 v;\nmov.b128 v, {%1,%2,%3,%4};\nst.relaxed.gpu.global.b128 [%0], v;\n}"
               ::"l"(p), "r"(a), "r"(b), "r"(c), "r"(d) : "memory");
}
__device__ __forceinline__ void st_rlx2(uint2* p, uint32_t a, uint32_t b) {
  asm volatile("{\n.reg .b64 v;\nmov.b64 v, {%1,%2};\nst.relaxed.gpu.global.b64 [%0], v;\n}" ::"l"(p), "r"(a), "r"(b) : "memory");
}
__device__ __forceinline__ uint32_t ld_rlx1(const uint32_t* p) {
  uint32_t r; asm volatile("ld.relaxed.gpu.global.b32 %0, [%1];" : "=r"(r) : "l"(p) : "memory"); return r;
}
__device__ __forceinline__ void st_rlx1(uint32_t* p, uint32_t a) {
  asm volatile("st.relaxed.gpu.global.b32 [%0], %1;" ::"l"(p), "r"(a) : "memory");
}
__device__ __forceinline__ void ld_rlx2(uint32_t& a, uint32_t& b, const uint2* p) {
  asm volatile("{\n.reg .b64 v;\nld.relaxed.gpu.b64 v, [%2];\nmov.b64 {%0,%1}, v;\n}" : "=r"(a), "=r"(b) : "l"(p) : "memory");
}
__device__ __forceinline__ void bulk_g2s(uint32_t dst, const void* src, uint32_t bytes, uint32_t bar) {
  asm volatile("cp.async.bulk.shared::cluster.global.mbarrier::complete_tx::bytes [%0], [%1], %2, [%3];"
               ::"r"(dst), "l"(src), "r"(bytes), "r"(bar) : "memory");
}
__device__ __forceinline__ uint32_t tg(uint32_t w, uint32_t T) { return (w & 0xFFFFFFFEu) | T; }
__device__ __forceinline__ uint32_t bad4(uint32_t a, uint32_t b, uint32_t c, uint32_t d, uint32_t T) {
  uint32_t u, v;
  asm("lop3.b32 %0, %1, %2, %3, 0x7E;" : "=r"(u) : "r"(a), "r"(b), "r"(T));
  asm("lop3.b32 %0, %1, %2, %3, 0x7E;" : "=r"(v) : "r"(c), "r"(d), "r"(T));
  asm("lop3.b32 %0, %1, %2, 1, 0xA8;" : "=r"(u) : "r"(u), "r"(v));
  return u;
}

__device__ __forceinline__ void ld_chunk(uint32_t (&a)[4][4], const uint4* p) {
#pragma unroll
  for (int s = 0; s < 4; s++) ld_rlx4(a[s], p + s * 32);
}
__device__ __forceinline__ void get_pair(uint32_t (&a)[4][4], uint32_t (&b)[4][4], const uint4* sp, const uint4* gp, uint32_t T) {
  int it = 0;
#pragma unroll 1
  do {
#pragma unroll
    for (int s = 0; s < 8; s++) {
      uint32_t (&r)[4] = s < 4 ? a[s & 3] : b[s & 3];
      asm volatile("{\n.reg .b128 v;\nld.relaxed.gpu.b128 v, [%4];\nmov.b128 {%0,%1,%2,%3}, v;\n}"
                   : "=r"(r[0]), "=r"(r[1]), "=r"(r[2]), "=r"(r[3]) : "l"(sp + (s >> 2) * 512 + (s & 3) * 32) : "memory");
    }
    sp = gp;
  } while (__any_sync(0xffffffffu, bad4(a[0][0], a[1][0], a[2][0], a[3][0], T) | bad4(b[0][0], b[1][0], b[2][0], b[3][0], T)) && ++it < (1 << 18));
}

__device__ __forceinline__ void wgmma_rs_n48(float (&d)[24], const uint32_t (&a)[4], uint32_t descB, int scaleD) {
  asm volatile("{\n.reg .pred p;\n.reg .b64 db;\nsetp.ne.b32 p, %29, 0;\nmov.b64 db, {%28, 0x40000040};\n"
    "wgmma.mma_async.sync.aligned.m64n48k16.f32.bf16.bf16 {%0,%1,%2,%3,%4,%5,%6,%7,%8,%9,%10,%11,%12,%13,%14,%15,%16,%17,%18,%19,%20,%21,%22,%23}, {%24,%25,%26,%27}, db, p, 1, 1, 1;\n}\n"
    : "+f"(d[0]),"+f"(d[1]),"+f"(d[2]),"+f"(d[3]),"+f"(d[4]),"+f"(d[5]),"+f"(d[6]),"+f"(d[7]),"+f"(d[8]),"+f"(d[9]),"+f"(d[10]),"+f"(d[11]),"+f"(d[12]),"+f"(d[13]),"+f"(d[14]),"+f"(d[15]),"+f"(d[16]),"+f"(d[17]),"+f"(d[18]),"+f"(d[19]),"+f"(d[20]),"+f"(d[21]),"+f"(d[22]),"+f"(d[23])
    : "r"(a[0]), "r"(a[1]), "r"(a[2]), "r"(a[3]), "r"(descB), "r"(scaleD));
}
__device__ __forceinline__ void wgmma_rs_n64(float (&d)[32], const uint32_t (&a)[4], uint32_t descB, int scaleD) {
  asm volatile("{\n.reg .pred p;\n.reg .b64 db;\nsetp.ne.b32 p, %37, 0;\nmov.b64 db, {%36, 0x40000040};\n"
    "wgmma.mma_async.sync.aligned.m64n64k16.f32.bf16.bf16 {%0,%1,%2,%3,%4,%5,%6,%7,%8,%9,%10,%11,%12,%13,%14,%15,%16,%17,%18,%19,%20,%21,%22,%23,%24,%25,%26,%27,%28,%29,%30,%31}, {%32,%33,%34,%35}, db, p, 1, 1, 1;\n}\n"
    : "+f"(d[0]),"+f"(d[1]),"+f"(d[2]),"+f"(d[3]),"+f"(d[4]),"+f"(d[5]),"+f"(d[6]),"+f"(d[7]),"+f"(d[8]),"+f"(d[9]),"+f"(d[10]),"+f"(d[11]),"+f"(d[12]),"+f"(d[13]),"+f"(d[14]),"+f"(d[15]),"+f"(d[16]),"+f"(d[17]),"+f"(d[18]),"+f"(d[19]),"+f"(d[20]),"+f"(d[21]),"+f"(d[22]),"+f"(d[23]),"+f"(d[24]),"+f"(d[25]),"+f"(d[26]),"+f"(d[27]),"+f"(d[28]),"+f"(d[29]),"+f"(d[30]),"+f"(d[31])
    : "r"(a[0]), "r"(a[1]), "r"(a[2]), "r"(a[3]), "r"(descB), "r"(scaleD));
}
__device__ __forceinline__ void wgmma_rs_n128(float (&d)[64], const uint32_t (&a)[4], uint32_t descB, int scaleD) {
  asm volatile("{\n.reg .pred p;\n.reg .b64 db;\nsetp.ne.b32 p, %69, 0;\nmov.b64 db, {%68, 0x40000040};\n"
    "wgmma.mma_async.sync.aligned.m64n128k16.f32.bf16.bf16 {%0,%1,%2,%3,%4,%5,%6,%7,%8,%9,%10,%11,%12,%13,%14,%15,%16,%17,%18,%19,%20,%21,%22,%23,%24,%25,%26,%27,%28,%29,%30,%31,%32,%33,%34,%35,%36,%37,%38,%39,%40,%41,%42,%43,%44,%45,%46,%47,%48,%49,%50,%51,%52,%53,%54,%55,%56,%57,%58,%59,%60,%61,%62,%63}, {%64,%65,%66,%67}, db, p, 1, 1, 1;\n}\n"
    : "+f"(d[0]),"+f"(d[1]),"+f"(d[2]),"+f"(d[3]),"+f"(d[4]),"+f"(d[5]),"+f"(d[6]),"+f"(d[7]),"+f"(d[8]),"+f"(d[9]),"+f"(d[10]),"+f"(d[11]),"+f"(d[12]),"+f"(d[13]),"+f"(d[14]),"+f"(d[15]),"+f"(d[16]),"+f"(d[17]),"+f"(d[18]),"+f"(d[19]),"+f"(d[20]),"+f"(d[21]),"+f"(d[22]),"+f"(d[23]),"+f"(d[24]),"+f"(d[25]),"+f"(d[26]),"+f"(d[27]),"+f"(d[28]),"+f"(d[29]),"+f"(d[30]),"+f"(d[31]),"+f"(d[32]),"+f"(d[33]),"+f"(d[34]),"+f"(d[35]),"+f"(d[36]),"+f"(d[37]),"+f"(d[38]),"+f"(d[39]),"+f"(d[40]),"+f"(d[41]),"+f"(d[42]),"+f"(d[43]),"+f"(d[44]),"+f"(d[45]),"+f"(d[46]),"+f"(d[47]),"+f"(d[48]),"+f"(d[49]),"+f"(d[50]),"+f"(d[51]),"+f"(d[52]),"+f"(d[53]),"+f"(d[54]),"+f"(d[55]),"+f"(d[56]),"+f"(d[57]),"+f"(d[58]),"+f"(d[59]),"+f"(d[60]),"+f"(d[61]),"+f"(d[62]),"+f"(d[63])
    : "r"(a[0]), "r"(a[1]), "r"(a[2]), "r"(a[3]), "r"(descB), "r"(scaleD));
}
__device__ __forceinline__ void wgmma_ss_n72_t11(float (&d)[36], uint32_t descA, uint32_t descB, int scaleD) {
  asm volatile("{\n.reg .pred p;\n.reg .b64 da, db;\nsetp.ne.b32 p, %38, 0;\nmov.b64 da, {%36, 0x40000040};\nmov.b64 db, {%37, 0x40000040};\n"
    "wgmma.mma_async.sync.aligned.m64n72k16.f32.bf16.bf16 {%0,%1,%2,%3,%4,%5,%6,%7,%8,%9,%10,%11,%12,%13,%14,%15,%16,%17,%18,%19,%20,%21,%22,%23,%24,%25,%26,%27,%28,%29,%30,%31,%32,%33,%34,%35}, da, db, p, 1, 1, 1, 1;\n}\n"
    : "+f"(d[0]),"+f"(d[1]),"+f"(d[2]),"+f"(d[3]),"+f"(d[4]),"+f"(d[5]),"+f"(d[6]),"+f"(d[7]),"+f"(d[8]),"+f"(d[9]),"+f"(d[10]),"+f"(d[11]),"+f"(d[12]),"+f"(d[13]),"+f"(d[14]),"+f"(d[15]),"+f"(d[16]),"+f"(d[17]),"+f"(d[18]),"+f"(d[19]),"+f"(d[20]),"+f"(d[21]),"+f"(d[22]),"+f"(d[23]),"+f"(d[24]),"+f"(d[25]),"+f"(d[26]),"+f"(d[27]),"+f"(d[28]),"+f"(d[29]),"+f"(d[30]),"+f"(d[31]),"+f"(d[32]),"+f"(d[33]),"+f"(d[34]),"+f"(d[35])
    : "r"(descA), "r"(descB), "r"(scaleD));
}

#define TSTAMP(i) do {} while (0)
#define TS2(w, i) do {} while (0)

constexpr float LOG2E = 1.4426950408889634f;

__device__ __forceinline__ void feat_exp(const uint32_t (&P)[4], float (&e)[16]) {
  uint32_t a = hmax2(P[0], P[2]), b = hmax2(P[1], P[3]);
  uint32_t mx = hmax2(__byte_perm(a, b, 0x5410), __byte_perm(a, b, 0x7632));
  a = hmin2(P[0], P[2]); b = hmin2(P[1], P[3]);
  uint32_t mn = hmin2(__byte_perm(a, b, 0x5410), __byte_perm(a, b, 0x7632));
  mx = hmax2(mx, __shfl_xor_sync(0xffffffffu, mx, 1));
  mn = hmin2(mn, __shfl_xor_sync(0xffffffffu, mn, 1));
  mx = hmax2(mx, __shfl_xor_sync(0xffffffffu, mx, 2));
  mn = hmin2(mn, __shfl_xor_sync(0xffffffffu, mn, 2));
  float mx0 = -blo(mx) * LOG2E, mx1 = -bhi(mx) * LOG2E, mn0 = blo(mn) * LOG2E, mn1 = bhi(mn) * LOG2E;
  float v[8] = {blo(P[0]), bhi(P[0]), blo(P[1]), bhi(P[1]), blo(P[2]), bhi(P[2]), blo(P[3]), bhi(P[3])};
#pragma unroll
  for (int i = 0; i < 8; i++) {
    bool r1 = (i >> 1) & 1;
    e[i]     = ex2(fmaf(v[i],  LOG2E, r1 ? mx1 : mx0));
    e[8 + i] = ex2(fmaf(v[i], -LOG2E, r1 ? mn1 : mn0));
  }
}

__global__ void __cluster_dims__(2, 1, 1) __launch_bounds__(384, 1)
fused_kernel(const __grid_constant__ Maps maps, const __nv_bfloat16* __restrict__ x, const __nv_bfloat16* __restrict__ wphi,
             const __nv_bfloat16* __restrict__ wo, const __nv_bfloat16* __restrict__ wg_, const __nv_bfloat16* __restrict__ wu_,
             const __nv_bfloat16* __restrict__ wd_, __nv_bfloat16* __restrict__ out) {
  extern __shared__ __align__(1024) unsigned char smem[];
  const uint32_t sb = smem_u32(smem);
  const int tid = threadIdx.x, lane = tid & 31;
  const int warp = __shfl_sync(0xffffffffu, tid >> 5, 0);
  const uint32_t rank = blockIdx.x & 1;
  const int cl = blockIdx.x >> 1;
  int quad, qi;
  if (cl < 4) { quad = 15; qi = cl; }
  else if (cl < 36) { quad = (cl - 4) & 7; qi = (cl - 4) >> 3; }
  else { qi = (cl - 36) / 7; quad = 8 + (cl - 36) - 7 * qi; }
  const int rb = quad, hg = 2 * qi + rank;
  const int rb3 = (quad & ~1) + rank, jf = 4 * (quad & 1) + qi;

  if (warp < 8) {
    asm volatile("setmaxnreg.inc.sync.aligned.u32 240;");
    if (elect_one()) {
#pragma unroll 1
      for (int d = warp; d + 9 < NSTAGE; d += 8) {
        mbar_init(sb + SM_EMPTY + d * 8, st_empty_cnt(d));
        {
          mbar_init(sb + SM_FULL + (d + 9) * 8, 1);
          mbar_expect_tx(sb + SM_FULL + (d + 9) * 8, d + 9 >= ST_D ? 22528 : SLOT);
        }
      }
      asm volatile("fence.mbarrier_init.release.cluster;" ::: "memory");
    }
    __syncwarp();
    bar_sync(0, 352);
    asm volatile("barrier.cluster.arrive.relaxed.aligned;" ::: "memory");
    const int wg = warp >> 2, wq = warp & 3, g = lane >> 2, t = lane & 3;
    const bool lead = (tid & 127) == 0;
    constexpr uint32_t db = (SM_BASE >> 4) | (512u << 16);
    auto release = [&](int d) {
      const int s = d + NSLOT;
      mbar_arrive_cluster(sb + SM_EMPTY + d * 8, s >= ST_GU ? (uint32_t)(s & 1) : rank);
    };
    const uint32_t lrow = (uint32_t)(wq * 16 + (lane & 7) + ((lane >> 3) & 1) * 8) * 128;
    const uint32_t lx = lane & 7, lhi = lane >> 4;
    if (wg == 1) bar_arrive(4, 256);

    float r0, r1;
    uint32_t E[4][8];
    uint32_t T = 0;
    {
      uint32_t A[32][4];
      const int sx = wg ? ST_X1 : ST_X0;
      {
        const uint32_t base = sb + sx * SLOT + lrow, baseb = sb + sx * SLOT + (wq * 16 + lx + lhi * 8) * 128;
        float cs[2][4], c0[2][4], c1[2][4];
#pragma unroll
        for (int i = 0; i < 4; i++) { cs[0][i] = cs[1][i] = c0[0][i] = c0[1][i] = c1[0][i] = c1[1][i] = 0.f; }
        uint32_t bt[2][4][4];
#pragma unroll
        for (int c = -1; c < 8; c++) {
          if (c < 7) {
            const int n = c + 1;
            if (n % 3 == 0) mbar_wait(sb + SM_FULL + (sx + n / 3) * 8);
#pragma unroll
            for (int k = 0; k < 4; k++) {
              ldsm4(A[4 * n + k], base + n * 8192 + (((2 * k + lhi) ^ lx) << 4));
              ldsm4(bt[n & 1][k], baseb + n * 8192 + (((2 * k + ((lane >> 3) & 1)) ^ lx) << 4));
            }
          }
          if (c >= 0) {
#pragma unroll
            for (int k = 0; k < 4; k++) {
              const uint32_t (&f)[4] = A[4 * c + k];
              mma16816(cs[k & 1], f, 0x3F803F80u, 0x3F803F80u);
              mma16816(c0[k & 1], f, bt[c & 1][k][0], bt[c & 1][k][1]);
              mma16816(c1[k & 1], f, bt[c & 1][k][2], bt[c & 1][k][3]);
            }
          }
        }
        const float s0 = (cs[0][0] + cs[1][0]) * (1.f / 512.f), s1 = (cs[0][2] + cs[1][2]) * (1.f / 512.f);
        asm volatile("barrier.cluster.wait.aligned;" ::: "memory");
        if (lane < 3) release(sx + lane);
        const uint32_t m0 = pack2(s0, s0), m1 = pack2(s1, s1);
        float q0 = (g & 1) ? c0[0][1] + c0[1][1] : c0[0][0] + c0[1][0];
        float q1 = (g & 1) ? c1[0][3] + c1[1][3] : c1[0][2] + c1[1][2];
        q0 = __shfl_sync(0xffffffffu, q0, (lane & ~3) | (g >> 1));
        q1 = __shfl_sync(0xffffffffu, q1, (lane & ~3) | (g >> 1));
        r0 = rsqrtf(fmaxf(q0 * (1.f / 512.f) - s0 * s0, 0.f) + 1e-5f);
        r1 = rsqrtf(fmaxf(q1 * (1.f / 512.f) - s1 * s1, 0.f) + 1e-5f);
#pragma unroll
        for (int ks = 0; ks < 32; ks++) {
          A[ks][0] = hsub2(A[ks][0], m0); A[ks][1] = hsub2(A[ks][1], m1);
          A[ks][2] = hsub2(A[ks][2], m0); A[ks][3] = hsub2(A[ks][3], m1);
        }
      }
      TSTAMP(1);
      const uint32_t wpa = sb + SM_WPHI + ((lane & 7) + ((lane >> 3) & 1) * 8) * 32 + lhi * 16;
      const uint32_t scr = sb + (wg ? (ST_SCR1 % NSLOT) : (ST_SCR0 % NSLOT)) * SLOT;
#pragma unroll 1
      for (int ps = 0; ps < 3; ps++) {
        const int st0 = ps == 0 ? ST_WK : (ps == 1 ? ST_WV : ST_WQ);
        const uint32_t wdesc = DESC((ps == 0 ? ST_WK % NSLOT : (ps == 1 ? ST_WV % NSLOT : ST_WQ % NSLOT)) * SLOT);
        float acc[32];
        bar_sync(4 + wg, 256);
#pragma unroll
        for (int i = 0; i < 3; i++) {
          mbar_wait(sb + SM_FULL + (st0 + i) * 8);
          wg_fence();
#pragma unroll
          for (int kk = 0; kk < (i < 2 ? 12 : 8); kk++)
            wgmma_rs_n64(acc, A[12 * i + kk], wdesc + ((i * SLOT + kk * 2048) >> 4), (i | kk) != 0);
          wg_commit();
          if (i == 1) { wg_wait<1>(); if (lead) release(st0); }
        }
        if (ps == 1 && wg == 0) bar_arrive(5, 256);
        uint32_t a[4][4], b[4][4];
        mbar_wait(sb + SM_MISCB);
        T = (*reinterpret_cast<volatile unsigned*>(smem + SM_EPOCH) & 1) ^ 1;
#pragma unroll
        for (int h = 0; h < 4; h++) ldsm4t(b[h], wpa + h * 512);
        wg_wait<0>();
        if ((tid & 127) < 2) release(st0 + 1 + (tid & 1));
        TSTAMP(2 + 2 * ps);
#pragma unroll
        for (int h = 0; h < 4; h++) {
          a[h][0] = pack2(acc[8 * h + 0] * r0, acc[8 * h + 1] * r0); a[h][1] = pack2(acc[8 * h + 2] * r1, acc[8 * h + 3] * r1);
          a[h][2] = pack2(acc[8 * h + 4] * r0, acc[8 * h + 5] * r0); a[h][3] = pack2(acc[8 * h + 6] * r1, acc[8 * h + 7] * r1);
        }
        if (ps != 1) {
          {
            float pp[4][2][4];
#pragma unroll
            for (int h = 0; h < 4; h++) {
#pragma unroll
              for (int i = 0; i < 4; i++) { pp[h][0][i] = 0.f; pp[h][1][i] = 0.f; }
              mma16816(pp[h][0], a[h], b[h][0], b[h][1]);
              mma16816(pp[h][1], a[h], b[h][2], b[h][3]);
            }
#pragma unroll
            for (int h = 0; h < 4; h++) {
              a[h][0] = pack2(pp[h][0][0], pp[h][0][1]); a[h][1] = pack2(pp[h][0][2], pp[h][0][3]);
              a[h][2] = pack2(pp[h][1][0], pp[h][1][1]); a[h][3] = pack2(pp[h][1][2], pp[h][1][3]);
            }
          }
          if (ps == 0 || wg == 0) bar_arrive(4 + (wg ^ 1), 256);
          if (ps == 0) mbar_wait(sb + SM_EMPTY + (wg ? ST_SCR1 - NSLOT : ST_SCR0 - NSLOT) * 8);
#pragma unroll 1
          for (int hp = 0; hp < 2; hp++) {
            float e[2][16];
            feat_exp(a[0], e[0]);
            feat_exp(a[1], e[1]);
            if (ps == 0) {
#pragma unroll
              for (int h = 0; h < 2; h++) {
                const float (&f)[16] = e[h];
                float sp0 = (f[0] + f[1]) + (f[4] + f[5]), sp1 = (f[2] + f[3]) + (f[6] + f[7]);
                float sn0 = (f[8] + f[9]) + (f[12] + f[13]), sn1 = (f[10] + f[11]) + (f[14] + f[15]);
                sp0 += __shfl_xor_sync(0xffffffffu, sp0, 1); sp1 += __shfl_xor_sync(0xffffffffu, sp1, 1);
                sn0 += __shfl_xor_sync(0xffffffffu, sn0, 1); sn1 += __shfl_xor_sync(0xffffffffu, sn1, 1);
                sp0 += __shfl_xor_sync(0xffffffffu, sp0, 2); sp1 += __shfl_xor_sync(0xffffffffu, sp1, 2);
                sn0 += __shfl_xor_sync(0xffffffffu, sn0, 2); sn1 += __shfl_xor_sync(0xffffffffu, sn1, 2);
                sp0 = rcp(sp0); sp1 = rcp(sp1); sn0 = rcp(sn0); sn1 = rcp(sn1);
                const uint32_t dst = scr + hp * 8192 + lrow;
                stsm4(dst + (((h * 4 + lhi) ^ lx) << 4), pack2(f[0] * sp0, f[1] * sp0), pack2(f[2] * sp1, f[3] * sp1),
                      pack2(f[4] * sp0, f[5] * sp0), pack2(f[6] * sp1, f[7] * sp1));
                stsm4(dst + (((h * 4 + 2 + lhi) ^ lx) << 4), pack2(f[8] * sn0, f[9] * sn0), pack2(f[10] * sn1, f[11] * sn1),
                      pack2(f[12] * sn0, f[13] * sn0), pack2(f[14] * sn1, f[15] * sn1));
              }
            } else {
#pragma unroll
              for (int i = 0; i < 16; i++) {
                A[i >> 2][i & 3] = A[4 + (i >> 2)][i & 3];
                A[4 + (i >> 2)][i & 3] = pack2(e[i >> 3][2 * (i & 7)], e[i >> 3][2 * (i & 7) + 1]);
              }
            }
#pragma unroll
            for (int i = 0; i < 4; i++) { a[0][i] = a[2][i]; a[1][i] = a[3][i]; }
          }
        } else {
#pragma unroll
          for (int h = 0; h < 4; h++) stsm4(scr + 16384 + lrow + (((2 * h + lhi) ^ lx) << 4), a[h][0], a[h][1], a[h][2], a[h][3]);
          fence_async_smem();
          bar_sync(3, 256);
          float kv[36];
          wg_fence();
#pragma unroll
          for (int ks = 0; ks < 8; ks++) {
            const uint32_t sk = (ks < 4 ? (ST_SCR0 % NSLOT) : (ST_SCR1 % NSLOT)) * SLOT + (ks & 3) * 2048;
            const uint32_t dv = (DESC(sk + 16384) & 0xFFFFu) | (((SM_ONES - sk - 16384) >> 4) << 16);
            wgmma_ss_n72_t11(kv, DESC(sk) + wg * 512, dv, ks != 0);
          }
          wg_commit();
          if (wg == 1) bar_arrive(4, 256);
          wg_wait<0>();
          if (lead) { mbar_arrive(sb + SM_EMPTY + ST_SCR0 * 8); mbar_arrive(sb + SM_EMPTY + ST_SCR1 * 8); }
          const int hl = 2 * wg + (wq >> 1), f = (wq & 1) * 16 + g;
          float* kvp = reinterpret_cast<float*>(smem + 2 * SLOT) + (hl * 32 + f) * 16 + 2 * t;
          float c[8];
#pragma unroll
          for (int i = 0; i < 8; i++) c[i] = hl >= 2 ? (hl == 3 ? kv[24 + i] : kv[16 + i]) : (hl == 1 ? kv[8 + i] : kv[i]);
#pragma unroll
          for (int n = 0; n < 2; n++) {
            *reinterpret_cast<float2*>(kvp + n * 8) = make_float2(c[4 * n], c[4 * n + 1]);
            *reinterpret_cast<float2*>(kvp + n * 8 + 128) = make_float2(c[4 * n + 2], c[4 * n + 3]);
          }
          if (t < 2) reinterpret_cast<float*>(smem + 2 * SLOT)[2048 + hl * 32 + f + t * 8] = t ? kv[34] : kv[32];
          fence_async_smem();
          bar_sync(6, 320);
        }
        TSTAMP(3 + 2 * ps);
      }
#pragma unroll
      for (int i = 0; i < 32; i++) E[i >> 3][i & 7] = A[i >> 2][i & 3];
    }
    const int rh = 2 * rb + wg;
#define IDF ((g >> 1) == t ? ((g & 1) ? 0x3F800000u : 0x00003F80u) : 0u)
    const uint4* xb = reinterpret_cast<const uint4*>(smem + 2 * SLOT) + wq * 128 + lane;
    mbar_wait(sb + SM_KVB);
    {
      const int r = tid & 127;
      const float4* src = reinterpret_cast<const float4*>(smem + SM_KV32) + r;
#pragma unroll
      for (int i = 0; i < 4; i++) {
        const float4 a = src[i * 128];
        *reinterpret_cast<uint2*>(smem + SM_KVS + (i * 32 + (r >> 2)) * 48 + (r & 3) * 8) = make_uint2(pack2(a.x, a.y), pack2(a.z, a.w));
      }
      const uint32_t zz = pack2(reinterpret_cast<const float*>(smem + SM_ONES)[r], 1.0f);
      *reinterpret_cast<uint4*>(smem + SM_KVS + r * 48 + 32) = make_uint4(zz, zz, zz, zz);
      bar_sync(1 + wg, 128);
    }
    TSTAMP(8);
    {
      uint4* op = &g_o[rh][hg][wq][0][lane];
      if (wg == 1) bar_sync(5, 256);
#pragma unroll 1
      for (int hp = 0; hp < 2; hp++) {
#pragma unroll
      for (int h = 0; h < 2; h++) {
        uint32_t b0[4], b1[4], b2[4];
        const uint32_t kb = sb + SM_KVS + ((2 * hp + h) * 32 + lane) * 48;
        ldsm4t(b0, kb); ldsm4t(b1, kb + 16); ldsm4t(b2, kb + 32);
        const uint32_t ep[4] = {E[h][0], E[h][1], E[h][2], E[h][3]}, en[4] = {E[h][4], E[h][5], E[h][6], E[h][7]};
        float np0[4] = {0, 0, 0, 0}, np1[4] = {0, 0, 0, 0}, nn0[4] = {0, 0, 0, 0}, nn1[4] = {0, 0, 0, 0}, dp[4] = {0, 0, 0, 0}, dn[4] = {0, 0, 0, 0};
        mma16816(dp, ep, b2[0], b2[1]);  mma16816(dn, en, b2[2], b2[3]);
        mma16816(np0, ep, b0[0], b0[1]); mma16816(nn0, en, b0[2], b0[3]);
        mma16816(np1, ep, b1[0], b1[1]); mma16816(nn1, en, b1[2], b1[3]);
        const float i0 = rcp(fmaf(dp[0], dn[1], fmaf(dn[0], dp[1], 1e-6f * dp[1] * dn[1])));
        const float i1 = rcp(fmaf(dp[2], dn[3], fmaf(dn[2], dp[3], 1e-6f * dp[3] * dn[3])));
        const float cp0 = dn[1] * i0, cn0 = dp[1] * i0, cp1 = dn[3] * i1, cn1 = dp[3] * i1;
        st_rlx4(op + (2 * hp + h) * 32,
                tg(pack2(fmaf(np0[0], cp0, nn0[0] * cn0), fmaf(np0[1], cp0, nn0[1] * cn0)), T),
                pack2(fmaf(np0[2], cp1, nn0[2] * cn1), fmaf(np0[3], cp1, nn0[3] * cn1)),
                pack2(fmaf(np1[0], cp0, nn1[0] * cn0), fmaf(np1[1], cp0, nn1[1] * cn0)),
                pack2(fmaf(np1[2], cp1, nn1[2] * cn1), fmaf(np1[3], cp1, nn1[3] * cn1)));
      }
#pragma unroll
        for (int i = 0; i < 8; i++) { E[0][i] = E[2][i]; E[1][i] = E[3][i]; }
      }
    }
    if (wg == 0) bar_arrive(5, 256);
    bar_arrive(10 + wg, 160);
    TSTAMP(9);

    {
      uint32_t xr[4][4];
      {
        const uint32_t* xp = reinterpret_cast<const uint32_t*>(x + (size_t)(rh * 64 + wq * 16 + g) * 512 + hg * 64 + 2 * t);
#pragma unroll
        for (int i = 0; i < 8; i++) { xr[i >> 1][(i & 1) * 2] = __ldg(xp + 4 * i); xr[i >> 1][(i & 1) * 2 + 1] = __ldg(xp + 8 * 256 + 4 * i); }
      }
      uint32_t A[8][4][4];
      const uint4* op = &g_o[rh][0][wq][0][lane];
      float acc[32];
#pragma unroll
      for (int i = 0; i < 32; i++) acc[i] = 0.f;
      add_frag(acc, xr, IDF);
#pragma unroll
      for (int p = -1; p < 4; p++) {
        if (p < 3) {
          mbar_wait(sb + SM_XF + (wg * 4 + p + 1) * 8);
          get_pair(A[2 * p + 2], A[2 * p + 3], xb + (p + 1) * 1024, op + (p + 1) * 1024, T);
          if (lane == 0) mbar_arrive(sb + SM_XE + (wg * 4 + p + 1) * 8);
        }
        if (p == 0 && wg == 1) bar_sync(4, 256);
        if (p >= 0) {
          if (p != 2) mbar_wait(sb + SM_FULL + (ST_WO + (p + 1) / 2) * 8);
          wg_fence();
#pragma unroll
          for (int c = 2 * p; c < 2 * p + 2; c++)
#pragma unroll
            for (int s = 0; s < 4; s++)
              wgmma_rs_n64(acc, A[c][s], DESC(((ST_WO + c / 3) % NSLOT) * SLOT + ((c % 3) * 4 + s) * 2048), 1);
        }
      }
      wg_commit();
      if (wg == 0) bar_arrive(4, 256);
      wg_wait<0>();
      if ((tid & 127) < 3) release(ST_WO + (tid & 127));
      TSTAMP(10);
      uint4* hp_ = &g_h[rh][hg][wq][0][lane];
      uint32_t hx = T;
#pragma unroll
      for (int s = 0; s < 4; s++) {
        const uint32_t h0 = pack2(acc[8 * s], acc[8 * s + 1]);
        st_rlx4(hp_ + s * 32, tg(h0, T), pack2(acc[8 * s + 2], acc[8 * s + 3]), pack2(acc[8 * s + 4], acc[8 * s + 5]), pack2(acc[8 * s + 6], acc[8 * s + 7]));
        hx |= (h0 & 1u) << (s + 1);
      }
      float s0 = 0.f, s1 = 0.f, q0 = 0.f, q1 = 0.f, q2 = 0.f, q3 = 0.f;
#pragma unroll
      for (int i = 0; i < 8; i++) {
        s0 += acc[4 * i] + acc[4 * i + 1]; s1 += acc[4 * i + 2] + acc[4 * i + 3];
        q0 = fmaf(acc[4 * i], acc[4 * i], q0); q2 = fmaf(acc[4 * i + 1], acc[4 * i + 1], q2);
        q1 = fmaf(acc[4 * i + 2], acc[4 * i + 2], q1); q3 = fmaf(acc[4 * i + 3], acc[4 * i + 3], q3);
      }
      q0 += q2; q1 += q3;
      {
        const bool up = t & 2;
        float s = (up ? s1 : s0) + __shfl_xor_sync(0xffffffffu, up ? s0 : s1, 2);
        float q = (up ? q1 : q0) + __shfl_xor_sync(0xffffffffu, up ? q0 : q1, 2);
        s += __shfl_xor_sync(0xffffffffu, s, 1);
        q += __shfl_xor_sync(0xffffffffu, q, 1);
        if (!(t & 1)) st_rlx2(&g_st[rh][hg][wq * 16 + g + (t >> 1) * 8], tg(__float_as_uint(s), T), __float_as_uint(q));
      }
      st_rlx1(&g_hx[rh][hg][wq][lane], hx);
    }
    bar_arrive(10 + wg, 160);
    TSTAMP(11);

    const int rh3 = 2 * rb3 + wg;
    uint32_t HH[11][4], PH[11][4];
    const uint4* pp = &g_hh[rh3][jf ^ 1][0][wq][lane];
    {
      uint32_t A[8][4][4];
      const uint4* hp_ = &g_h[rh3][0][wq][0][lane];
      uint4* hhp = &g_hh[rh3][jf][0][wq][lane];
      const uint32_t dg = (db & 0xFFFFu) | (256u << 16);
      uint32_t m0, m1;
      mbar_wait(sb + SM_XF + ((2 + wg) * 4) * 8);
      TSTAMP(0);
      {
        const uint2* sp = reinterpret_cast<const uint2*>(smem + SM_KV32 + wg * 4096) + 2 * t * 64 + wq * 16 + g;
        uint2 a0, a1, b0, b1;
        int it = 0;
#pragma unroll 1
        do {
          ld_rlx2(a0.x, a0.y, sp); ld_rlx2(a1.x, a1.y, sp + 64); ld_rlx2(b0.x, b0.y, sp + 8); ld_rlx2(b1.x, b1.y, sp + 72);
          sp = &g_st[rh3][2 * t][wq * 16 + g];
        } while (__any_sync(0xffffffffu, bad4(a0.x, a1.x, b0.x, b1.x, T)) && ++it < (1 << 18));
        float s0 = __uint_as_float(a0.x) + __uint_as_float(a1.x), q0 = __uint_as_float(a0.y) + __uint_as_float(a1.y);
        float s1 = __uint_as_float(b0.x) + __uint_as_float(b1.x), q1 = __uint_as_float(b0.y) + __uint_as_float(b1.y);
        s0 += __shfl_xor_sync(0xffffffffu, s0, 1); s1 += __shfl_xor_sync(0xffffffffu, s1, 1);
        q0 += __shfl_xor_sync(0xffffffffu, q0, 1); q1 += __shfl_xor_sync(0xffffffffu, q1, 1);
        s0 += __shfl_xor_sync(0xffffffffu, s0, 2); s1 += __shfl_xor_sync(0xffffffffu, s1, 2);
        q0 += __shfl_xor_sync(0xffffffffu, q0, 2); q1 += __shfl_xor_sync(0xffffffffu, q1, 2);
        s0 *= (1.f / 512.f); s1 *= (1.f / 512.f);
        r0 = rcp(fmaxf(q0 * (1.f / 512.f) - s0 * s0, 0.f) + 1e-5f);
        r1 = rcp(fmaxf(q1 * (1.f / 512.f) - s1 * s1, 0.f) + 1e-5f);
        m0 = pack2(s0, s0); m1 = pack2(s1, s1);
      }
      TSTAMP(12);
#define UOFF(u) ((((ST_GU + (u) / 3) % NSLOT) * SLOT + ((u) % 3) * 8192) >> 4)
#define UNIT_PRE(u)  do { if ((u) % 3 == 0) mbar_wait(sb + SM_FULL + (ST_GU + (u) / 3) * 8); } while (0)
#define UNIT_POST(u) do { wg_commit(); if ((u) % 3 == 1 && (u) > 3) { wg_wait<2>(); if (lead) release(ST_GU + (u) / 3 - 1); } } while (0)
      float acc[64];
      const int rz = blockIdx.y;
#pragma unroll
      for (int ps = 0; ps < 2; ps++) {
        wg_fence();
#pragma unroll
        for (int k = 0; k < 16; k++) {
          const int u = 16 * ps + k, c = k >> 1;
          if (ps == 0 && (k == 0 || k == 4 || k == 8)) {
#pragma unroll
            for (int p = (k == 0 ? 0 : (k == 4 ? 1 : 3)); p < (k == 0 ? 1 : (k == 4 ? 3 : 4)); p++) {
              if (p > 0) mbar_wait(sb + SM_XF + ((2 + wg) * 4 + p) * 8);
              get_pair(A[2 * p], A[2 * p + 1], xb + p * 1024, hp_ + p * 1024, T);
              if (lane == 0) {
                if (wg == 0) mbar_arrive(sb + SM_XE + (8 + p) * 8);
                else if (p > 0) release(ST_XC + p - 1);
              }
            }
          }
          if (ps == 0 && (k & 1) == 0) {
#pragma unroll
            for (int s = 0; s < 4; s++) {
              A[c][s][0] = hsub2(A[c][s][0], m0); A[c][s][1] = hsub2(A[c][s][1], m1);
              A[c][s][2] = hsub2(A[c][s][2], m0); A[c][s][3] = hsub2(A[c][s][3], m1);
            }
            wg_fence();
          }
          UNIT_PRE(u);
          wgmma_rs_n128(acc, A[c][(k & 1) * 2], dg + UOFF(u), k != 0 ? 1 : (ps ? rz : 0));
          wgmma_rs_n128(acc, A[c][(k & 1) * 2 + 1], dg + UOFF(u) + 128, 1);
          UNIT_POST(u);
        }
        wg_wait<0>();
        TSTAMP(22 + ps);
#pragma unroll
        for (int s = 0; s < 4; s++) {
          uint32_t (&hh)[4] = HH[4 + s];
          hh[0] = tg(pack2(acc[8 * s + 0] * acc[32 + 8 * s + 0], acc[8 * s + 1] * acc[32 + 8 * s + 1]), T);
          hh[1] = pack2(acc[8 * s + 2] * acc[32 + 8 * s + 2], acc[8 * s + 3] * acc[32 + 8 * s + 3]);
          hh[2] = pack2(acc[8 * s + 4] * acc[32 + 8 * s + 4], acc[8 * s + 5] * acc[32 + 8 * s + 5]);
          hh[3] = pack2(acc[8 * s + 6] * acc[32 + 8 * s + 6], acc[8 * s + 7] * acc[32 + 8 * s + 7]);
          st_rlx4(hhp + (4 * ps + s) * 128, hh[0], hh[1], hh[2], hh[3]);
        }
      }
      {
        float ag[24], au[24];
        const uint32_t* ph7 = reinterpret_cast<const uint32_t*>(&g_hh[rh3][jf ^ 1][7][wq][31]);
        uint32_t hv = 0;
        bar_sync(1 + wg, 128);
        wg_fence();
#pragma unroll
        for (int k = 0; k < 16; k++) {
          const int u = 32 + k, c = k >> 1;
          if (k == 6) {
#pragma unroll
            for (int s = 0; s < 4; s++) ld_rlx4(HH[s], hhp + s * 128);
          }
          if (k == 9) hv = ld_rlx1(ph7);
          if (k == 12) {
            int it = 0;
#pragma unroll 1
            while (((hv ^ T) & 1) && ++it < (1 << 18)) hv = ld_rlx1(ph7);
#pragma unroll
            for (int s = 0; s < 8; s++) ld_rlx4(PH[s], pp + s * 128);
          }
          UNIT_PRE(u);
          wgmma_rs_n48(ag, A[c][(k & 1) * 2], dg + UOFF(u), k != 0);
          wgmma_rs_n48(au, A[c][(k & 1) * 2], dg + UOFF(u) + 256, k != 0);
          wgmma_rs_n48(ag, A[c][(k & 1) * 2 + 1], dg + UOFF(u) + 128, 1);
          wgmma_rs_n48(au, A[c][(k & 1) * 2 + 1], dg + UOFF(u) + 256 + 128, 1);
          UNIT_POST(u);
        }
        wg_wait<0>();
        TSTAMP(13);
#pragma unroll
        for (int s = 0; s < 3; s++) {
          uint32_t (&hh)[4] = HH[8 + s];
          hh[0] = tg(pack2(ag[8 * s + 0] * au[8 * s + 0], ag[8 * s + 1] * au[8 * s + 1]), T);
          hh[1] = pack2(ag[8 * s + 2] * au[8 * s + 2], ag[8 * s + 3] * au[8 * s + 3]);
          hh[2] = pack2(ag[8 * s + 4] * au[8 * s + 4], ag[8 * s + 5] * au[8 * s + 5]);
          hh[3] = pack2(ag[8 * s + 6] * au[8 * s + 6], ag[8 * s + 7] * au[8 * s + 7]);
          st_rlx4(hhp + (8 + s) * 128, hh[0], hh[1], hh[2], hh[3]);
        }
      }
    }
    TSTAMP(14);

    {
      float acc[32];
      uint32_t hr[4][4], hx = 0;
      const int m = jf >> 1, oc = (jf & 1) * 4 + m;
      const uint32_t* ph10 = reinterpret_cast<const uint32_t*>(&g_hh[rh3][jf ^ 1][10][wq][31]);
      uint4* outb = &g_part[rh3][(jf & 1) * 4][m][wq][0][lane];
      bar_arrive(8 + wg, 256);
      int s0 = ST_D % NSLOT;
#pragma unroll 1
      for (int k = 0; k < 4; k++) {
        const int s1 = s0 + 1 == NSLOT ? 0 : s0 + 1;
        const uint32_t d0 = db + s0 * (SLOT >> 4), d1 = db + s1 * (SLOT >> 4);
        uint32_t pk[16];
#pragma unroll
        for (int i = 0; i < 16; i++) pk[i] = pack2(acc[2 * i], acc[2 * i + 1]);
        mbar_wait(sb + SM_FULL + (ST_D + 2 * k) * 8);
        wg_fence();
#pragma unroll
        for (int s = 0; s < 4; s++) wgmma_rs_n64(acc, HH[s], d0 + s * 128, s != 0);
        if (k > 0) {
          uint4* p = outb + ((m + k) & 3) * 2048;
#pragma unroll
          for (int s = 0; s < 4; s++) st_rlx4(p + s * 32, tg(pk[4 * s], T), pk[4 * s + 1], pk[4 * s + 2], pk[4 * s + 3]);
        }
        if (k == 3) TSTAMP(18);
#pragma unroll
        for (int s = 4; s < 11; s++) wgmma_rs_n64(acc, HH[s], d0 + s * 128, 1);
        if (k == 0) {
          int it = 0;
#pragma unroll 1
          while (((ld_rlx1(ph10) ^ T) & 1) && ++it < (1 << 18)) {}
#pragma unroll 1
          for (int first = 1;; first = 0) {
            if (!first) {
#pragma unroll
              for (int s = 0; s < 8; s++) ld_rlx4(PH[s], pp + s * 128);
            }
#pragma unroll
            for (int s = 8; s < 11; s++) ld_rlx4(PH[s], pp + s * 128);
            if (!__any_sync(0xffffffffu, bad4(PH[0][0], PH[1][0], PH[2][0], PH[3][0], T) | bad4(PH[4][0], PH[5][0], PH[6][0], PH[7][0], T) |
                                         bad4(PH[8][0], PH[9][0], PH[10][0], T, T)) || ++it > (1 << 18)) break;
          }
          TSTAMP(20);
        }
        if (k == 2) {
          ld_chunk(hr, &g_h[rh3][oc][wq][0][lane]);
          hx = ld_rlx1(&g_hx[rh3][oc][wq][lane]);
        }
        mbar_wait(sb + SM_FULL + (ST_D + 2 * k + 1) * 8);
        wg_fence();
#pragma unroll
        for (int s = 0; s < 11; s++) wgmma_rs_n64(acc, PH[s], d1 + s * 128, 1);
        wg_commit();
        wg_wait<0>();
        if (k == 0) bar_arrive(12, 320);
        s0 = s1 + 1 == NSLOT ? 0 : s1 + 1;
      }
      TSTAMP(15);
#pragma unroll 1
      for (int q = 0; q < 3; q++) {
        uint32_t in[4][4];
        const uint4* sp = reinterpret_cast<const uint4*>(smem + ((ST_D % NSLOT) + wg) * SLOT) + q * 512 + wq * 128 + lane;
        mbar_wait_p(sb + SM_XF + (wg * 4 + q) * 8, 1);
        if (q == 0) TSTAMP(19); if (q == 1) TSTAMP(21); if (q == 2) TSTAMP(24);
        int it = 0;
#pragma unroll 1
        do {
#pragma unroll
          for (int s = 0; s < 4; s++)
            asm volatile("{\n.reg .b128 v;\nld.relaxed.gpu.b128 v, [%4];\nmov.b128 {%0,%1,%2,%3}, v;\n}"
                         : "=r"(in[s][0]), "=r"(in[s][1]), "=r"(in[s][2]), "=r"(in[s][3]) : "l"(sp + s * 32) : "memory");
          sp = &g_part[rh3][oc][(m - 1 - q) & 3][wq][0][lane];
        } while (__any_sync(0xffffffffu, bad4(in[0][0], in[1][0], in[2][0], in[3][0], T)) && ++it < (1 << 18));
        add_frag(acc, in, IDF);
      }
      {
        int it = 0;
#pragma unroll 1
        while (__any_sync(0xffffffffu, (hx ^ T) & 1) && ++it < (1 << 18)) hx = ld_rlx1(&g_hx[rh3][oc][wq][lane]);
      }
#pragma unroll
      for (int s = 0; s < 4; s++) hr[s][0] = (hr[s][0] & 0xFFFFFFFEu) | ((hx >> (s + 1)) & 1u);
#pragma unroll
      for (int i = 0; i < 32; i++) acc[i] *= (i & 2) ? r1 : r0;
      add_frag(acc, hr, IDF);
      bar_sync(9 - wg, 256);
      const uint32_t ob = sb + ((ST_D - 1) % NSLOT) * SLOT + wg * 8192;
#pragma unroll
      for (int s = 0; s < 4; s++)
        stsm4(ob + lrow + (((2 * s + lhi) ^ lx) << 4), pack2(acc[8 * s + 0], acc[8 * s + 1]), pack2(acc[8 * s + 2], acc[8 * s + 3]),
              pack2(acc[8 * s + 4], acc[8 * s + 5]), pack2(acc[8 * s + 6], acc[8 * s + 7]));
      __syncwarp();
      {
        const int row = wq * 16 + (lane >> 3);
        __nv_bfloat16* op = out + (size_t)(rh3 * 64 + row) * 512 + oc * 64 + lx * 8;
#pragma unroll
        for (int i = 0; i < 4; i++) {
          uint4 v;
          asm volatile("ld.shared.v4.b32 {%0,%1,%2,%3}, [%4];" : "=r"(v.x), "=r"(v.y), "=r"(v.z), "=r"(v.w)
                       : "r"(ob + (row + i * 4) * 128 + ((lx ^ (((lane >> 3) + i * 4) & 7)) << 4)) : "memory");
          asm volatile("st.global.v4.b32 [%0], {%1,%2,%3,%4};" ::"l"(op + i * 2048), "r"(v.x), "r"(v.y), "r"(v.z), "r"(v.w) : "memory");
        }
      }
    }
    TSTAMP(16);
    asm volatile("barrier.cluster.arrive.relaxed.aligned;" ::: "memory");
    asm volatile("barrier.cluster.wait.aligned;" ::: "memory");
  } else {
    asm volatile("setmaxnreg.dec.sync.aligned.u32 24;");
    if (elect_one()) {
      if (warp == 8) {
#pragma unroll
        for (int k = 0; k < 9; k++) {
          const int s = k < 3 ? k : (k < 6 ? k + 3 : k - 3);
          const uint32_t bar = sb + SM_FULL + s * 8;
          mbar_init(bar, 1);
          mbar_expect_tx(bar, SLOT);
          if (s >= 3 && s < 6) tma2d(sb + s * SLOT, &maps.w, 512 + hg * 64, (s - 3) * 192, bar);
          else tma3d(sb + s * SLOT, &maps.x, 0, rb * 128 + (s >= 6 ? 64 : 0), 3 * (s % 3), bar);
        }
      } else if (warp == 9) {
        mbar_init(sb + SM_MISCB, 2);
        mbar_init(sb + SM_KVB, 1);
        mbar_expect_tx(sb + SM_KVB, 8704);
        mbar_expect_tx(sb + SM_MISCB, 2048);
        bulk_g2s(sb + SM_WPHI, wphi + hg * 1024, 2048, sb + SM_MISCB);
      } else if (warp == 10) {
        if ((sb & 0x3FFFF) != SM_BASE) __trap();
#pragma unroll 1
        for (int i = 0; i < 16; i++) {
          mbar_init(sb + SM_XF + i * 8, 1);
          mbar_expect_tx(sb + SM_XF + i * 8, (i == 8 || i == 12) ? 20480 : 16384);
          if (i < 12) mbar_init(sb + SM_XE + i * 8, 4);
        }
      } else {
        *reinterpret_cast<volatile unsigned*>(smem + SM_EPOCH) = atomicAdd(&g_start, 1u) / NCTA;
      }
      asm volatile("fence.mbarrier_init.release.cluster;" ::: "memory");
    }
    __syncwarp();
    if (warp != 11) bar_sync(0, 352);
    asm volatile("barrier.cluster.arrive.relaxed.aligned;" ::: "memory");
    if (warp == 8) {
      asm volatile("barrier.cluster.wait.aligned;" ::: "memory");
      if (elect_one()) {
        const CUtensorMap* mg = jf == 7 ? &maps.g7 : &maps.g;
        const CUtensorMap* mu = jf == 7 ? &maps.u7 : &maps.u;
        asm volatile("prefetch.tensormap [%0];" ::"l"(&maps.wo) : "memory");
        asm volatile("prefetch.tensormap [%0];" ::"l"(mg) : "memory");
        asm volatile("prefetch.tensormap [%0];" ::"l"(mu) : "memory");
        asm volatile("prefetch.tensormap [%0];" ::"l"(&maps.d) : "memory");
#pragma unroll 1
        for (int s = ST_WV; s < ST_XC; s++) {
          if (s == ST_SCR1) continue;
          mbar_wait(sb + SM_EMPTY + (s - 9) * 8);
          const uint32_t dst = sb + (s >= 18 ? s - 18 : s - 9) * SLOT, bar = sb + SM_FULL + s * 8;
          if (s < ST_WO) tma2d(dst, &maps.w, (s < ST_WQ ? 1024 : 0) + hg * 64, (s < ST_WQ ? s - ST_WV : s - ST_WQ) * 192, bar);
          else { mbar_wait(bar - 8); tma2d(dst, &maps.wo, hg * 64, (s - ST_WO) * 192, bar); }
        }
        const int jc = jf == 7 ? 0 : jf;
        int slot = (ST_GU + 1 - rank) % NSLOT;
#pragma unroll 1
        for (int s = ST_GU + 1 - rank; s < NSTAGE; s += 2) {
          mbar_wait(sb + SM_EMPTY + (s - 9) * 8);
          if (s > ST_GU && s < ST_GU + THR) mbar_wait(sb + SM_FULL + (s - 1) * 8);
          const uint32_t dst = sb + slot * SLOT, bar = sb + SM_FULL + s * 8;
          if (s < ST_D) {
#pragma unroll 1
            for (int i = 0; i < 3; i++) {
              const int u = (s - ST_GU) * 3 + i;
              tma3d_mc(dst + i * 8192, mg, (u >> 4) * 64, jc, (u & 15) * 32, bar);
              tma3d_mc(dst + i * 8192 + 4096, mu, (u >> 4) * 64, jc, (u & 15) * 32, bar);
            }
          } else {
            const int i = s - ST_D;
            tma2d_mc(dst, &maps.d, ((jf & 1) * 4 + (((jf >> 1) + 1 + (i >> 1)) & 3)) * 64, (jf ^ (i & 1)) * 176, bar);
          }
          slot += 2; if (slot >= NSLOT) slot -= NSLOT;
        }
      }
      __syncwarp();
    } else {
      asm volatile("barrier.cluster.wait.aligned;" ::: "memory");
      if (warp == 11) {
#pragma unroll
        for (int i = 0; i < 4; i++)
          reinterpret_cast<uint4*>(smem + SM_ONES)[lane + 32 * i] = make_uint4(0x3F803F80u, 0x3F803F80u, 0x3F803F80u, 0x3F803F80u);
        fence_async_smem();
        __syncwarp();
        if (lane == 0) mbar_arrive(sb + SM_MISCB);
      }
      mbar_wait(sb + SM_MISCB);
      const unsigned epoch = *reinterpret_cast<volatile unsigned*>(smem + SM_EPOCH);
      const uint32_t T = (epoch & 1) ^ 1;
      if (warp == 11) {
        reinterpret_cast<float4*>(&g_kv[hg][rb * 136])[lane] = make_float4(0.f, 0.f, 0.f, 0.f);
        if (lane < 2) reinterpret_cast<float4*>(&g_kv[hg][rb * 136])[32 + lane] = make_float4(0.f, 0.f, 0.f, 0.f);
        __syncwarp();
        if (elect_one()) asm volatile("red.release.gpu.global.add.u32 [%0], 1;" ::"l"(&g_kvcnt[hg * 32 + 1]) : "memory");
        mbar_wait(sb + SM_FULL + (ST_WK + 2) * 8);
        if (elect_one()) {
          asm volatile("cp.async.bulk.prefetch.L2.global [%0], 4096;" ::"l"((const char*)wo + blockIdx.x * 4096) : "memory");
          asm volatile("cp.async.bulk.prefetch.L2.global [%0], 11008;" ::"l"((const char*)wg_ + blockIdx.x * 11008) : "memory");
          asm volatile("cp.async.bulk.prefetch.L2.global [%0], 11008;" ::"l"((const char*)wu_ + blockIdx.x * 11008) : "memory");
          asm volatile("cp.async.bulk.prefetch.L2.global [%0], 11008;" ::"l"((const char*)wd_ + blockIdx.x * 11008) : "memory");
          mbar_wait(sb + SM_EMPTY + ST_SCR0 * 8);
          const unsigned target = (epoch + 1) * 16;
          unsigned v; int it = 0;
#pragma unroll 1
          do {
            asm volatile("ld.acquire.gpu.global.u32 %0, [%1];" : "=r"(v) : "l"(&g_kvcnt[hg * 32]) : "memory");
            if (++it > (1 << 18)) break;
          } while ((int)(v - target) < 0);
          TS2(0, 26);
          asm volatile("fence.proxy.async.global;" ::: "memory");
          bulk_g2s(sb + SM_KV32, &g_kv[hg][0], 8192, sb + SM_KVB);
          bulk_g2s(sb + SM_ONES, &g_kv[hg][2048], 512, sb + SM_KVB);
        }
        __syncwarp();
      } else {
        const int w = warp - 9;
        st_rlx4(reinterpret_cast<uint4*>(&g_st[2 * rb + w][hg][0]) + lane, T ^ 1, T ^ 1, T ^ 1, T ^ 1);
        if (lane < 8) st_rlx4(&g_o[2 * rb + w][hg][lane >> 1][3][30 + (lane & 1)], T ^ 1, T ^ 1, T ^ 1, T ^ 1);
        st_rlx4(&g_part[2 * rb3 + w][(jf & 1) * 4 + (lane >> 3)][jf >> 1][(lane >> 1) & 3][3][30 + (lane & 1)], T ^ 1, T ^ 1, T ^ 1, T ^ 1);
        if (lane < 16) st_rlx4(&g_hh[2 * rb3 + w][jf][7 + (lane >> 3) * 3][(lane >> 1) & 3][30 + (lane & 1)], T ^ 1, T ^ 1, T ^ 1, T ^ 1);
        if (w == 0) {
          mbar_wait(sb + SM_FULL + (ST_WQ + 2) * 8);
          unsigned v; int it = 0;
#pragma unroll 1
          do {
            asm volatile("ld.acquire.gpu.global.u32 %0, [%1];" : "=r"(v) : "l"(&g_kvcnt[hg * 32 + 1]) : "memory");
          } while ((int)(v - (epoch + 1) * 16) < 0 && ++it < (1 << 18));
          asm volatile("fence.proxy.async.global;" ::: "memory");
        }
        bar_sync(6, 320);
        if (w == 0 && elect_one()) {
          asm volatile("cp.reduce.async.bulk.global.shared::cta.bulk_group.add.f32 [%0], [%1], 8704;"
                       ::"l"(&g_kv[hg][0]), "r"(sb + 2 * SLOT) : "memory");
          asm volatile("cp.async.bulk.commit_group;" ::: "memory");
          asm volatile("cp.async.bulk.wait_group 0;" ::: "memory");
          asm volatile("red.relaxed.gpu.global.add.u32 [%0], 1;" ::"l"(&g_kvcnt[hg * 32]) : "memory");
          TS2(0, 25);
        }
        __syncwarp();
        mbar_wait(sb + SM_KVB);
        if (w == 0) { mbar_wait(sb + SM_EMPTY + 11 * 8); mbar_wait(sb + SM_EMPTY + 12 * 8); mbar_wait(sb + SM_EMPTY + 13 * 8); }
#pragma unroll 1
        for (int ph = 0; ph < 2; ph++) {
          const int use = 2 * ph + w, r = ph ? 2 * rb3 + w : 2 * rb + w;
          const uint32_t* pw = ph ? reinterpret_cast<const uint32_t*>(&g_st[r][lane >> 2][(lane & 3) * 16 + 15])
                                  : reinterpret_cast<const uint32_t*>(&g_o[r][lane >> 2][lane & 3][3][31]);
          const char* src = reinterpret_cast<const char*>(ph ? &g_h[r][0][0][0][0] : &g_o[r][0][0][0][0]);
          const uint32_t bf = sb + SM_XF + use * 32, be = sb + SM_XE + (use - 1) * 32;
          bar_sync(10 + w, 160);
          int it = 0;
#pragma unroll 1
          for (bool miss = true; __any_sync(0xffffffffu, miss) && ++it < (1 << 18);) { if (miss) miss = (ld_rlx1(pw) ^ T) & 1; }
          if (elect_one()) {
            TS2(w, 27 + ph);
            if (use > 0) mbar_wait(be);
            if (ph) bulk_g2s(sb + SM_KV32 + w * 4096, &g_st[r][0][0], 4096, bf);
#pragma unroll
            for (int p = 0; p < 4; p++) {
              if (p > 0 && use > 0) mbar_wait(be + p * 8);
              bulk_g2s(sb + 2 * SLOT + p * 16384, src + p * 16384, 16384, bf + p * 8);
            }
          }
          __syncwarp();
        }
        {
          const int m = jf >> 1, oc = (jf & 1) * 4 + m;
          const uint32_t* pw = reinterpret_cast<const uint32_t*>(&g_part[2 * rb3 + w][oc][(m - 1 - (lane >> 2)) & 3][lane & 3][3][31]);
          bar_sync(12, 320);
          bool miss = lane < 12; int it = 0;
#pragma unroll 1
          for (int q = 0; q < 3; q++) {
#pragma unroll 1
            while ((__ballot_sync(0xffffffffu, miss) >> (4 * q) & 15) && ++it < (1 << 18)) { if (miss && (lane >> 2) <= q + 1) miss = (ld_rlx1(pw) ^ T) & 1; }
            if (elect_one()) {
              const uint32_t bar = sb + SM_XF + (w * 4 + q) * 8;
              mbar_expect_tx(bar, 8192);
              if (q == 2) TS2(w, 17);
              bulk_g2s(sb + ((ST_D % NSLOT) + w) * SLOT + q * 8192, &g_part[2 * rb3 + w][oc][(m - 1 - q) & 3][0][0][0], 8192, bar);
            }
            __syncwarp();
          }
        }
      }
    }
    asm volatile("barrier.cluster.arrive.relaxed.aligned;" ::: "memory");
    asm volatile("barrier.cluster.wait.aligned;" ::: "memory");
  }
}

typedef CUresult (*EncodeFn)(CUtensorMap*, CUtensorMapDataType, cuuint32_t, void*, const cuuint64_t*, const cuuint64_t*,
                             const cuuint32_t*, const cuuint32_t*, CUtensorMapInterleave, CUtensorMapSwizzle,
                             CUtensorMapL2promotion, CUtensorMapFloatOOBfill);

void encode(EncodeFn fn, CUtensorMap* m, const void* base, int rank, const cuuint64_t* dims, const cuuint64_t* strides,
            const cuuint32_t* box) {
  cuuint32_t es[3] = {1, 1, 1};
  fn(m, CU_TENSOR_MAP_DATA_TYPE_BFLOAT16, (cuuint32_t)rank, const_cast<void*>(base), dims, strides, box, es,
     CU_TENSOR_MAP_INTERLEAVE_NONE, CU_TENSOR_MAP_SWIZZLE_128B, CU_TENSOR_MAP_L2_PROMOTION_L2_256B,
     CU_TENSOR_MAP_FLOAT_OOB_FILL_NONE);
}

}

extern "C" void kernel_launch(void* const* d_in, const int* in_sizes, int n_in, void* d_out, int out_size) {
  (void)in_sizes; (void)n_in; (void)out_size;
  const __nv_bfloat16* x    = (const __nv_bfloat16*)d_in[0];
  const __nv_bfloat16* wqkv = (const __nv_bfloat16*)d_in[1];
  const __nv_bfloat16* wphi = (const __nv_bfloat16*)d_in[2];
  const __nv_bfloat16* wo   = (const __nv_bfloat16*)d_in[3];
  const __nv_bfloat16* wg   = (const __nv_bfloat16*)d_in[5];
  const __nv_bfloat16* wu   = (const __nv_bfloat16*)d_in[6];
  const __nv_bfloat16* wd   = (const __nv_bfloat16*)d_in[7];

  static EncodeFn fn = nullptr;
  if (!fn) {
    void* p = nullptr;
    cudaDriverEntryPointQueryResult qr;
    cudaGetDriverEntryPoint("cuTensorMapEncodeTiled", &p, cudaEnableDefault, &qr);
    fn = (EncodeFn)p;
    cudaFuncSetAttribute(fused_kernel, cudaFuncAttributeMaxDynamicSharedMemorySize, SM_TOTAL);
  }
  Maps maps;
  {
    cuuint64_t d[3] = {64, 2048, 8}, s[2] = {1024, 128}; cuuint32_t b[3] = {64, 64, 3};
    encode(fn, &maps.x, x, 3, d, s, b);
  }
  {
    cuuint64_t d[2] = {1536, 512}, s[1] = {3072}; cuuint32_t b[2] = {64, 192};
    encode(fn, &maps.w, wqkv, 2, d, s, b);
  }
  {
    cuuint64_t d[2] = {512, 512}, s[1] = {1024}; cuuint32_t b[2] = {64, 192};
    encode(fn, &maps.wo, wo, 2, d, s, b);
  }
  {
    cuuint64_t d[3] = {176, 7, 512}, d7[3] = {144, 1, 512}, s[2] = {352, 2752}; cuuint32_t b[3] = {64, 1, 32};
    encode(fn, &maps.g, wg, 3, d, s, b);
    encode(fn, &maps.u, wu, 3, d, s, b);
    encode(fn, &maps.g7, wg + 1232, 3, d7, s, b);
    encode(fn, &maps.u7, wu + 1232, 3, d7, s, b);
  }
  {
    cuuint64_t d[2] = {512, 1376}, s[1] = {1024}; cuuint32_t b[2] = {64, 176};
    encode(fn, &maps.d, wd, 2, d, s, b);
  }
  fused_kernel<<<NCTA, 384, SM_TOTAL>>>(maps, x, wphi, wo, wg, wu, wd, (__nv_bfloat16*)d_out);
}
```

```cpp
#include <cuda_runtime.h>
#include <cuda_bf16.h>
#include <cuda.h>
#include <stdint.h>

#define PROF 0

#define SAFE_WAIT 0
#define OPRIO 1
#define THR 6

namespace {

constexpr int NCTA   = 128;
constexpr int SLOT   = 24576;
constexpr int NSLOT  = 9;
constexpr int NSTAGE = 47;

constexpr int ST_X0   = 0;
constexpr int ST_WK   = 3;
constexpr int ST_X1   = 6;
constexpr int ST_SCR0 = 9;
constexpr int ST_WV   = 10;
constexpr int ST_SCR1 = 13;
constexpr int ST_WQ   = 14;
constexpr int ST_WO   = 17;
constexpr int ST_XC   = 20;
constexpr int ST_GU   = 23;
constexpr int ST_D    = 39;

__host__ __device__ constexpr int st_empty_cnt(int d) {
  return ((d < 3 || (d >= 6 && d < 9) || (d >= ST_XC && d < ST_GU)) ? 4 : 2) * (d + 9 >= ST_GU ? 2 : 1);
}

constexpr uint32_t SM_BASE = 1024;
constexpr int SM_ONES = NSLOT * SLOT;
constexpr int SM_WPHI = SM_ONES + 2048;
constexpr int SM_KVS  = SM_WPHI + 2048;
constexpr int SM_KV32 = 4 * SLOT + 16384;
constexpr int SM_BAR  = SM_KVS + 6144;
constexpr int SM_FULL  = SM_BAR;
constexpr int SM_EMPTY = SM_BAR + NSTAGE * 8;
constexpr int SM_MISCB = SM_BAR + 2 * NSTAGE * 8;
constexpr int SM_KVB   = SM_MISCB + 8;
constexpr int SM_EPOCH = SM_KVB + 8;
constexpr int SM_XF    = SM_EPOCH + 8;
constexpr int SM_XE    = SM_XF + 16 * 8;
constexpr int SM_TOTAL = SM_BAR + 1024;

static_assert(SM_TOTAL == 232448 && SM_XE + 12 * 8 <= SM_TOTAL, "smem budget");

struct Maps { CUtensorMap x, w, wo, g, u, g7, u7, d; };

__device__ uint4    g_o[32][8][4][4][32];
__device__ uint4    g_h[32][8][4][4][32];
__device__ uint32_t g_hx[32][8][4][32];
__device__ uint2    g_st[32][8][64];
__device__ uint4    g_hh[32][8][11][4][32];
__device__ uint4    g_part[32][8][4][4][4][32];
__device__ __align__(128) float g_kv[8][2048 + 128];
__device__ unsigned g_kvcnt[8 * 32];
__device__ unsigned g_start;

__device__ __forceinline__ uint32_t smem_u32(const void* p) { return (uint32_t)__cvta_generic_to_shared(p); }
__device__ __forceinline__ void mbar_init(uint32_t bar, int cnt) {
  asm volatile("mbarrier.init.shared::cta.b64 [%0], %1;" ::"r"(bar), "r"(cnt) : "memory");
}
__device__ __forceinline__ void mbar_expect_tx(uint32_t bar, uint32_t bytes) {
  asm volatile("mbarrier.arrive.expect_tx.shared::cta.b64 _, [%0], %1;" ::"r"(bar), "r"(bytes) : "memory");
}
__device__ __forceinline__ void mbar_arrive(uint32_t bar) {
  asm volatile("mbarrier.arrive.shared::cta.b64 _, [%0];" ::"r"(bar) : "memory");
}
__device__ __forceinline__ void mbar_arrive_cluster(uint32_t bar, uint32_t rank) {
  asm volatile("{\n.reg .b32 ra;\nmapa.shared::cluster.u32 ra, %0, %1;\n"
               "mbarrier.arrive.shared::cluster.b64 _, [ra];\n}" ::"r"(bar), "r"(rank) : "memory");
}
__device__ __forceinline__ void mbar_wait_p(uint32_t bar, uint32_t parity) {
  asm volatile("{\n.reg .pred p;\nW: mbarrier.try_wait.parity.shared::cta.b64 p, [%0], %1;\n@!p bra W;\n}" ::"r"(bar), "r"(parity) : "memory");
}
__device__ __forceinline__ void mbar_wait(uint32_t bar) { mbar_wait_p(bar, 0); }
__device__ __forceinline__ bool elect_one() {
  uint32_t p;
  asm volatile("{\n.reg .pred P;\nelect.sync _|P, 0xffffffff;\nselp.u32 %0, 1, 0, P;\n}" : "=r"(p));
  return p != 0;
}
__device__ __forceinline__ void bar_sync(int id, int n)   { asm volatile("bar.sync %0, %1;" ::"r"(id), "r"(n) : "memory"); }
__device__ __forceinline__ void bar_arrive(int id, int n) { asm volatile("bar.arrive %0, %1;" ::"r"(id), "r"(n) : "memory"); }
__device__ __forceinline__ void fence_async_smem() { asm volatile("fence.proxy.async.shared::cta;" ::: "memory"); }
__device__ __forceinline__ void wg_fence()  { asm volatile("wgmma.fence.sync.aligned;" ::: "memory"); }
__device__ __forceinline__ void wg_commit() { asm volatile("wgmma.commit_group.sync.aligned;" ::: "memory"); }
template <int N> __device__ __forceinline__ void wg_wait() { asm volatile("wgmma.wait_group.sync.aligned %0;" ::"n"(N) : "memory"); }
#define DESC(off) (db + ((uint32_t)(off) >> 4))
__device__ __forceinline__ void tma2d(uint32_t dst, const CUtensorMap* m, int c0, int c1, uint32_t bar) {
  asm volatile("cp.async.bulk.tensor.2d.shared::cluster.global.mbarrier::complete_tx::bytes [%0], [%1, {%3, %4}], [%2];"
               ::"r"(dst), "l"(m), "r"(bar), "r"(c0), "r"(c1) : "memory");
}
__device__ __forceinline__ void tma2d_mc(uint32_t dst, const CUtensorMap* m, int c0, int c1, uint32_t bar) {
  asm volatile("cp.async.bulk.tensor.2d.shared::cluster.global.mbarrier::complete_tx::bytes.multicast::cluster [%0], [%1, {%3, %4}], [%2], %5;"
               ::"r"(dst), "l"(m), "r"(bar), "r"(c0), "r"(c1), "h"((uint16_t)3) : "memory");
}
__device__ __forceinline__ void tma3d(uint32_t dst, const CUtensorMap* m, int c0, int c1, int c2, uint32_t bar) {
  asm volatile("cp.async.bulk.tensor.3d.shared::cluster.global.mbarrier::complete_tx::bytes [%0], [%1, {%3, %4, %5}], [%2];"
               ::"r"(dst), "l"(m), "r"(bar), "r"(c0), "r"(c1), "r"(c2) : "memory");
}
__device__ __forceinline__ void tma3d_mc(uint32_t dst, const CUtensorMap* m, int c0, int c1, int c2, uint32_t bar) {
  asm volatile("cp.async.bulk.tensor.3d.shared::cluster.global.mbarrier::complete_tx::bytes.multicast::cluster [%0], [%1, {%3, %4, %5}], [%2], %6;"
               ::"r"(dst), "l"(m), "r"(bar), "r"(c0), "r"(c1), "r"(c2), "h"((uint16_t)3) : "memory");
}
__device__ __forceinline__ void ldsm4(uint32_t (&r)[4], uint32_t addr) {
  asm volatile("ldmatrix.sync.aligned.m8n8.x4.shared.b16 {%0,%1,%2,%3}, [%4];"
               : "=r"(r[0]), "=r"(r[1]), "=r"(r[2]), "=r"(r[3]) : "r"(addr) : "memory");
}
__device__ __forceinline__ void ldsm4t(uint32_t (&r)[4], uint32_t addr) {
  asm volatile("ldmatrix.sync.aligned.m8n8.x4.trans.shared.b16 {%0,%1,%2,%3}, [%4];"
               : "=r"(r[0]), "=r"(r[1]), "=r"(r[2]), "=r"(r[3]) : "r"(addr) : "memory");
}
__device__ __forceinline__ void stsm4(uint32_t addr, uint32_t r0, uint32_t r1, uint32_t r2, uint32_t r3) {
  asm volatile("stmatrix.sync.aligned.m8n8.x4.shared.b16 [%0], {%1,%2,%3,%4};"
               ::"r"(addr), "r"(r0), "r"(r1), "r"(r2), "r"(r3) : "memory");
}
__device__ __forceinline__ void mma16816(float (&c)[4], const uint32_t (&a)[4], uint32_t b0, uint32_t b1) {
  asm volatile("mma.sync.aligned.m16n8k16.row.col.f32.bf16.bf16.f32 {%0,%1,%2,%3},{%4,%5,%6,%7},{%8,%9},{%0,%1,%2,%3};"
               : "+f"(c[0]), "+f"(c[1]), "+f"(c[2]), "+f"(c[3])
               : "r"(a[0]), "r"(a[1]), "r"(a[2]), "r"(a[3]), "r"(b0), "r"(b1));
}
__device__ __forceinline__ void add_frag(float (&c)[32], const uint32_t (&a)[4][4], uint32_t id) {
#pragma unroll
  for (int i = 0; i < 8; i++)
    asm volatile("mma.sync.aligned.m16n8k8.row.col.f32.bf16.bf16.f32 {%0,%1,%2,%3},{%4,%5},{%6},{%0,%1,%2,%3};"
                 : "+f"(c[4 * i]), "+f"(c[4 * i + 1]), "+f"(c[4 * i + 2]), "+f"(c[4 * i + 3])
                 : "r"(a[i >> 1][(i & 1) * 2]), "r"(a[i >> 1][(i & 1) * 2 + 1]), "r"(id));
}
__device__ __forceinline__ uint32_t pack2(float lo, float hi) {
  uint32_t r; asm("cvt.rn.bf16x2.f32 %0, %1, %2;" : "=r"(r) : "f"(hi), "f"(lo)); return r;
}
__device__ __forceinline__ float blo(uint32_t w) { return __uint_as_float(w << 16); }
__device__ __forceinline__ float bhi(uint32_t w) { return __uint_as_float(w & 0xFFFF0000u); }
__device__ __forceinline__ uint32_t hsub2(uint32_t a, uint32_t b) { uint32_t r; asm("sub.rn.bf16x2 %0, %1, %2;" : "=r"(r) : "r"(a), "r"(b)); return r; }
__device__ __forceinline__ uint32_t hmax2(uint32_t a, uint32_t b) { uint32_t r; asm("max.bf16x2 %0, %1, %2;" : "=r"(r) : "r"(a), "r"(b)); return r; }
__device__ __forceinline__ uint32_t hmin2(uint32_t a, uint32_t b) { uint32_t r; asm("min.bf16x2 %0, %1, %2;" : "=r"(r) : "r"(a), "r"(b)); return r; }
__device__ __forceinline__ float ex2(float x) { float r; asm("ex2.approx.ftz.f32 %0, %1;" : "=f"(r) : "f"(x)); return r; }
__device__ __forceinline__ float rcp(float x) { float r; asm("rcp.approx.ftz.f32 %0, %1;" : "=f"(r) : "f"(x)); return r; }
__device__ __forceinline__ void ld_rlx4(uint32_t (&r)[4], const uint4* p) {
  asm volatile("{\n.reg .b128 v;\nld.relaxed.gpu.global.b128 v, [%4];\nmov.b128 {%0,%1,%2,%3}, v;\n}"
               : "=r"(r[0]), "=r"(r[1]), "=r"(r[2]), "=r"(r[3]) : "l"(p) : "memory");
}
__device__ __forceinline__ void st_rlx4(uint4* p, uint32_t a, uint32_t b, uint32_t c, uint32_t d) {
  asm volatile("{\n.reg .b128 v;\nmov.b128 v, {%1,%2,%3,%4};\nst.relaxed.gpu.global.b128 [%0], v;\n}"
               ::"l"(p), "r"(a), "r"(b), "r"(c), "r"(d) : "memory");
}
__device__ __forceinline__ void st_rlx2(uint2* p, uint32_t a, uint32_t b) {
  asm volatile("{\n.reg .b64 v;\nmov.b64 v, {%1,%2};\nst.relaxed.gpu.global.b64 [%0], v;\n}" ::"l"(p), "r"(a), "r"(b) : "memory");
}
__device__ __forceinline__ uint32_t ld_rlx1(const uint32_t* p) {
  uint32_t r; asm volatile("ld.relaxed.gpu.global.b32 %0, [%1];" : "=r"(r) : "l"(p) : "memory"); return r;
}
__device__ __forceinline__ void st_rlx1(uint32_t* p, uint32_t a) {
  asm volatile("st.relaxed.gpu.global.b32 [%0], %1;" ::"l"(p), "r"(a) : "memory");
}
__device__ __forceinline__ void ld_rlx2(uint32_t& a, uint32_t& b, const uint2* p) {
  asm volatile("{\n.reg .b64 v;\nld.relaxed.gpu.b64 v, [%2];\nmov.b64 {%0,%1}, v;\n}" : "=r"(a), "=r"(b) : "l"(p) : "memory");
}
__device__ __forceinline__ void bulk_g2s(uint32_t dst, const void* src, uint32_t bytes, uint32_t bar) {
  asm volatile("cp.async.bulk.shared::cluster.global.mbarrier::complete_tx::bytes [%0], [%1], %2, [%3];"
               ::"r"(dst), "l"(src), "r"(bytes), "r"(bar) : "memory");
}
__device__ __forceinline__ uint32_t tg(uint32_t w, uint32_t T) { return (w & 0xFFFFFFFEu) | T; }
__device__ __forceinline__ uint32_t bad4(uint32_t a, uint32_t b, uint32_t c, uint32_t d, uint32_t T) {
  uint32_t u, v;
  asm("lop3.b32 %0, %1, %2, %3, 0x7E;" : "=r"(u) : "r"(a), "r"(b), "r"(T));
  asm("lop3.b32 %0, %1, %2, %3, 0x7E;" : "=r"(v) : "r"(c), "r"(d), "r"(T));
  asm("lop3.b32 %0, %1, %2, 1, 0xA8;" : "=r"(u) : "r"(u), "r"(v));
  return u;
}

__device__ __forceinline__ void ld_chunk(uint32_t (&a)[4][4], const uint4* p) {
#pragma unroll
  for (int s = 0; s < 4; s++) ld_rlx4(a[s], p + s * 32);
}
__device__ __forceinline__ void get_pair(uint32_t (&a)[4][4], uint32_t (&b)[4][4], const uint4* sp, const uint4* gp, uint32_t T) {
  int it = 0;
#pragma unroll 1
  do {
#pragma unroll
    for (int s = 0; s < 8; s++) {
      uint32_t (&r)[4] = s < 4 ? a[s & 3] : b[s & 3];
      asm volatile("{\n.reg .b128 v;\nld.relaxed.gpu.b128 v, [%4];\nmov.b128 {%0,%1,%2,%3}, v;\n}"
                   : "=r"(r[0]), "=r"(r[1]), "=r"(r[2]), "=r"(r[3]) : "l"(sp + (s >> 2) * 512 + (s & 3) * 32) : "memory");
    }
    sp = gp;
  } while (__any_sync(0xffffffffu, bad4(a[0][0], a[1][0], a[2][0], a[3][0], T) | bad4(b[0][0], b[1][0], b[2][0], b[3][0], T)) && ++it < (1 << 18));
}

__device__ __forceinline__ void wgmma_rs_n48(float (&d)[24], const uint32_t (&a)[4], uint32_t descB, int scaleD) {
  asm volatile("{\n.reg .pred p;\n.reg .b64 db;\nsetp.ne.b32 p, %29, 0;\nmov.b64 db, {%28, 0x40000040};\n"
    "wgmma.mma_async.sync.aligned.m64n48k16.f32.bf16.bf16 {%0,%1,%2,%3,%4,%5,%6,%7,%8,%9,%10,%11,%12,%13,%14,%15,%16,%17,%18,%19,%20,%21,%22,%23}, {%24,%25,%26,%27}, db, p, 1, 1, 1;\n}\n"
    : "+f"(d[0]),"+f"(d[1]),"+f"(d[2]),"+f"(d[3]),"+f"(d[4]),"+f"(d[5]),"+f"(d[6]),"+f"(d[7]),"+f"(d[8]),"+f"(d[9]),"+f"(d[10]),"+f"(d[11]),"+f"(d[12]),"+f"(d[13]),"+f"(d[14]),"+f"(d[15]),"+f"(d[16]),"+f"(d[17]),"+f"(d[18]),"+f"(d[19]),"+f"(d[20]),"+f"(d[21]),"+f"(d[22]),"+f"(d[23])
    : "r"(a[0]), "r"(a[1]), "r"(a[2]), "r"(a[3]), "r"(descB), "r"(scaleD));
}
__device__ __forceinline__ void wgmma_rs_n64(float (&d)[32], const uint32_t (&a)[4], uint32_t descB, int scaleD) {
  asm volatile("{\n.reg .pred p;\n.reg .b64 db;\nsetp.ne.b32 p, %37, 0;\nmov.b64 db, {%36, 0x40000040};\n"
    "wgmma.mma_async.sync.aligned.m64n64k16.f32.bf16.bf16 {%0,%1,%2,%3,%4,%5,%6,%7,%8,%9,%10,%11,%12,%13,%14,%15,%16,%17,%18,%19,%20,%21,%22,%23,%24,%25,%26,%27,%28,%29,%30,%31}, {%32,%33,%34,%35}, db, p, 1, 1, 1;\n}\n"
    : "+f"(d[0]),"+f"(d[1]),"+f"(d[2]),"+f"(d[3]),"+f"(d[4]),"+f"(d[5]),"+f"(d[6]),"+f"(d[7]),"+f"(d[8]),"+f"(d[9]),"+f"(d[10]),"+f"(d[11]),"+f"(d[12]),"+f"(d[13]),"+f"(d[14]),"+f"(d[15]),"+f"(d[16]),"+f"(d[17]),"+f"(d[18]),"+f"(d[19]),"+f"(d[20]),"+f"(d[21]),"+f"(d[22]),"+f"(d[23]),"+f"(d[24]),"+f"(d[25]),"+f"(d[26]),"+f"(d[27]),"+f"(d[28]),"+f"(d[29]),"+f"(d[30]),"+f"(d[31])
    : "r"(a[0]), "r"(a[1]), "r"(a[2]), "r"(a[3]), "r"(descB), "r"(scaleD));
}
__device__ __forceinline__ void wgmma_rs_n128(float (&d)[64], const uint32_t (&a)[4], uint32_t descB, int scaleD) {
  asm volatile("{\n.reg .pred p;\n.reg .b64 db;\nsetp.ne.b32 p, %69, 0;\nmov.b64 db, {%68, 0x40000040};\n"
    "wgmma.mma_async.sync.aligned.m64n128k16.f32.bf16.bf16 {%0,%1,%2,%3,%4,%5,%6,%7,%8,%9,%10,%11,%12,%13,%14,%15,%16,%17,%18,%19,%20,%21,%22,%23,%24,%25,%26,%27,%28,%29,%30,%31,%32,%33,%34,%35,%36,%37,%38,%39,%40,%41,%42,%43,%44,%45,%46,%47,%48,%49,%50,%51,%52,%53,%54,%55,%56,%57,%58,%59,%60,%61,%62,%63}, {%64,%65,%66,%67}, db, p, 1, 1, 1;\n}\n"
    : "+f"(d[0]),"+f"(d[1]),"+f"(d[2]),"+f"(d[3]),"+f"(d[4]),"+f"(d[5]),"+f"(d[6]),"+f"(d[7]),"+f"(d[8]),"+f"(d[9]),"+f"(d[10]),"+f"(d[11]),"+f"(d[12]),"+f"(d[13]),"+f"(d[14]),"+f"(d[15]),"+f"(d[16]),"+f"(d[17]),"+f"(d[18]),"+f"(d[19]),"+f"(d[20]),"+f"(d[21]),"+f"(d[22]),"+f"(d[23]),"+f"(d[24]),"+f"(d[25]),"+f"(d[26]),"+f"(d[27]),"+f"(d[28]),"+f"(d[29]),"+f"(d[30]),"+f"(d[31]),"+f"(d[32]),"+f"(d[33]),"+f"(d[34]),"+f"(d[35]),"+f"(d[36]),"+f"(d[37]),"+f"(d[38]),"+f"(d[39]),"+f"(d[40]),"+f"(d[41]),"+f"(d[42]),"+f"(d[43]),"+f"(d[44]),"+f"(d[45]),"+f"(d[46]),"+f"(d[47]),"+f"(d[48]),"+f"(d[49]),"+f"(d[50]),"+f"(d[51]),"+f"(d[52]),"+f"(d[53]),"+f"(d[54]),"+f"(d[55]),"+f"(d[56]),"+f"(d[57]),"+f"(d[58]),"+f"(d[59]),"+f"(d[60]),"+f"(d[61]),"+f"(d[62]),"+f"(d[63])
    : "r"(a[0]), "r"(a[1]), "r"(a[2]), "r"(a[3]), "r"(descB), "r"(scaleD));
}
__device__ __forceinline__ void wgmma_ss_n72_t11(float (&d)[36], uint32_t descA, uint32_t descB, int scaleD) {
  asm volatile("{\n.reg .pred p;\n.reg .b64 da, db;\nsetp.ne.b32 p, %38, 0;\nmov.b64 da, {%36, 0x40000040};\nmov.b64 db, {%37, 0x40000040};\n"
    "wgmma.mma_async.sync.aligned.m64n72k16.f32.bf16.bf16 {%0,%1,%2,%3,%4,%5,%6,%7,%8,%9,%10,%11,%12,%13,%14,%15,%16,%17,%18,%19,%20,%21,%22,%23,%24,%25,%26,%27,%28,%29,%30,%31,%32,%33,%34,%35}, da, db, p, 1, 1, 1, 1;\n}\n"
    : "+f"(d[0]),"+f"(d[1]),"+f"(d[2]),"+f"(d[3]),"+f"(d[4]),"+f"(d[5]),"+f"(d[6]),"+f"(d[7]),"+f"(d[8]),"+f"(d[9]),"+f"(d[10]),"+f"(d[11]),"+f"(d[12]),"+f"(d[13]),"+f"(d[14]),"+f"(d[15]),"+f"(d[16]),"+f"(d[17]),"+f"(d[18]),"+f"(d[19]),"+f"(d[20]),"+f"(d[21]),"+f"(d[22]),"+f"(d[23]),"+f"(d[24]),"+f"(d[25]),"+f"(d[26]),"+f"(d[27]),"+f"(d[28]),"+f"(d[29]),"+f"(d[30]),"+f"(d[31]),"+f"(d[32]),"+f"(d[33]),"+f"(d[34]),"+f"(d[35])
    : "r"(descA), "r"(descB), "r"(scaleD));
}

#define TSTAMP(i) do {} while (0)
#define TS2(w, i) do {} while (0)

constexpr float LOG2E = 1.4426950408889634f;

__device__ __forceinline__ void feat_exp(const uint32_t (&P)[4], float (&e)[16]) {
  uint32_t a = hmax2(P[0], P[2]), b = hmax2(P[1], P[3]);
  uint32_t mx = hmax2(__byte_perm(a, b, 0x5410), __byte_perm(a, b, 0x7632));
  a = hmin2(P[0], P[2]); b = hmin2(P[1], P[3]);
  uint32_t mn = hmin2(__byte_perm(a, b, 0x5410), __byte_perm(a, b, 0x7632));
  mx = hmax2(mx, __shfl_xor_sync(0xffffffffu, mx, 1));
  mn = hmin2(mn, __shfl_xor_sync(0xffffffffu, mn, 1));
  mx = hmax2(mx, __shfl_xor_sync(0xffffffffu, mx, 2));
  mn = hmin2(mn, __shfl_xor_sync(0xffffffffu, mn, 2));
  float mx0 = -blo(mx) * LOG2E, mx1 = -bhi(mx) * LOG2E, mn0 = blo(mn) * LOG2E, mn1 = bhi(mn) * LOG2E;
  float v[8] = {blo(P[0]), bhi(P[0]), blo(P[1]), bhi(P[1]), blo(P[2]), bhi(P[2]), blo(P[3]), bhi(P[3])};
#pragma unroll
  for (int i = 0; i < 8; i++) {
    bool r1 = (i >> 1) & 1;
    e[i]     = ex2(fmaf(v[i],  LOG2E, r1 ? mx1 : mx0));
    e[8 + i] = ex2(fmaf(v[i], -LOG2E, r1 ? mn1 : mn0));
  }
}

__global__ void __cluster_dims__(2, 1, 1) __launch_bounds__(384, 1)
fused_kernel(const __grid_constant__ Maps maps, const __nv_bfloat16* __restrict__ x, const __nv_bfloat16* __restrict__ wphi,
             const __nv_bfloat16* __restrict__ wo, const __nv_bfloat16* __restrict__ wg_, const __nv_bfloat16* __restrict__ wu_,
             const __nv_bfloat16* __restrict__ wd_, __nv_bfloat16* __restrict__ out) {
  extern __shared__ __align__(1024) unsigned char smem[];
  const uint32_t sb = smem_u32(smem);
  const int tid = threadIdx.x, lane = tid & 31;
  const int warp = __shfl_sync(0xffffffffu, tid >> 5, 0);
  const uint32_t rank = blockIdx.x & 1;
  const int cl = blockIdx.x >> 1;
  int quad, qi;
  if (cl < 4) { quad = 15; qi = cl; }
  else if (cl < 36) { quad = (cl - 4) & 7; qi = (cl - 4) >> 3; }
  else { qi = (cl - 36) / 7; quad = 8 + (cl - 36) - 7 * qi; }
  const int rb = quad, hg = 2 * qi + rank;
  const int rb3 = (quad & ~1) + rank, jf = 4 * (quad & 1) + qi;

  if (warp < 8) {
    asm volatile("setmaxnreg.inc.sync.aligned.u32 240;");
    if (elect_one()) {
#pragma unroll 1
      for (int d = warp; d + 9 < NSTAGE; d += 8) {
        mbar_init(sb + SM_EMPTY + d * 8, st_empty_cnt(d));
        {
          mbar_init(sb + SM_FULL + (d + 9) * 8, 1);
          mbar_expect_tx(sb + SM_FULL + (d + 9) * 8, d + 9 >= ST_D ? 22528 : SLOT);
        }
      }
      asm volatile("fence.mbarrier_init.release.cluster;" ::: "memory");
    }
    __syncwarp();
    bar_sync(0, 352);
    asm volatile("barrier.cluster.arrive.relaxed.aligned;" ::: "memory");
    const int wg = warp >> 2, wq = warp & 3, g = lane >> 2, t = lane & 3;
    const bool lead = (tid & 127) == 0;
    constexpr uint32_t db = (SM_BASE >> 4) | (512u << 16);
    auto release = [&](int d) {
      const int s = d + NSLOT;
      mbar_arrive_cluster(sb + SM_EMPTY + d * 8, s >= ST_GU ? (uint32_t)(s & 1) : rank);
    };
    const uint32_t lrow = (uint32_t)(wq * 16 + (lane & 7) + ((lane >> 3) & 1) * 8) * 128;
    const uint32_t lx = lane & 7, lhi = lane >> 4;
    if (wg == 1) bar_arrive(4, 256);

    float r0, r1;
    uint32_t E[4][8];
    uint32_t T = 0;
    {
      uint32_t A[32][4];
      const int sx = wg ? ST_X1 : ST_X0;
      {
        const uint32_t base = sb + sx * SLOT + lrow, baseb = sb + sx * SLOT + (wq * 16 + lx + lhi * 8) * 128;
        float cs[2][4], c0[2][4], c1[2][4];
#pragma unroll
        for (int i = 0; i < 4; i++) { cs[0][i] = cs[1][i] = c0[0][i] = c0[1][i] = c1[0][i] = c1[1][i] = 0.f; }
        uint32_t bt[2][4][4];
#pragma unroll
        for (int c = -1; c < 8; c++) {
          if (c < 7) {
            const int n = c + 1;
            if (n % 3 == 0) mbar_wait(sb + SM_FULL + (sx + n / 3) * 8);
#pragma unroll
            for (int k = 0; k < 4; k++) {
              ldsm4(A[4 * n + k], base + n * 8192 + (((2 * k + lhi) ^ lx) << 4));
              ldsm4(bt[n & 1][k], baseb + n * 8192 + (((2 * k + ((lane >> 3) & 1)) ^ lx) << 4));
            }
          }
          if (c >= 0) {
#pragma unroll
            for (int k = 0; k < 4; k++) {
              const uint32_t (&f)[4] = A[4 * c + k];
              mma16816(cs[k & 1], f, 0x3F803F80u, 0x3F803F80u);
              mma16816(c0[k & 1], f, bt[c & 1][k][0], bt[c & 1][k][1]);
              mma16816(c1[k & 1], f, bt[c & 1][k][2], bt[c & 1][k][3]);
            }
          }
        }
        const float s0 = (cs[0][0] + cs[1][0]) * (1.f / 512.f), s1 = (cs[0][2] + cs[1][2]) * (1.f / 512.f);
        asm volatile("barrier.cluster.wait.aligned;" ::: "memory");
        if (lane < 3) release(sx + lane);
        const uint32_t m0 = pack2(s0, s0), m1 = pack2(s1, s1);
        float q0 = (g & 1) ? c0[0][1] + c0[1][1] : c0[0][0] + c0[1][0];
        float q1 = (g & 1) ? c1[0][3] + c1[1][3] : c1[0][2] + c1[1][2];
        q0 = __shfl_sync(0xffffffffu, q0, (lane & ~3) | (g >> 1));
        q1 = __shfl_sync(0xffffffffu, q1, (lane & ~3) | (g >> 1));
        r0 = rsqrtf(fmaxf(q0 * (1.f / 512.f) - s0 * s0, 0.f) + 1e-5f);
        r1 = rsqrtf(fmaxf(q1 * (1.f / 512.f) - s1 * s1, 0.f) + 1e-5f);
#pragma unroll
        for (int ks = 0; ks < 32; ks++) {
          A[ks][0] = hsub2(A[ks][0], m0); A[ks][1] = hsub2(A[ks][1], m1);
          A[ks][2] = hsub2(A[ks][2], m0); A[ks][3] = hsub2(A[ks][3], m1);
        }
      }
      TSTAMP(1);
      const uint32_t wpa = sb + SM_WPHI + ((lane & 7) + ((lane >> 3) & 1) * 8) * 32 + lhi * 16;
      const uint32_t scr = sb + (wg ? (ST_SCR1 % NSLOT) : (ST_SCR0 % NSLOT)) * SLOT;
#pragma unroll 1
      for (int ps = 0; ps < 3; ps++) {
        const int st0 = ps == 0 ? ST_WK : (ps == 1 ? ST_WV : ST_WQ);
        const uint32_t wdesc = DESC((ps == 0 ? ST_WK % NSLOT : (ps == 1 ? ST_WV % NSLOT : ST_WQ % NSLOT)) * SLOT);
        float acc[32];
        bar_sync(4 + wg, 256);
#pragma unroll
        for (int i = 0; i < 3; i++) {
          mbar_wait(sb + SM_FULL + (st0 + i) * 8);
          wg_fence();
#pragma unroll
          for (int kk = 0; kk < (i < 2 ? 12 : 8); kk++)
            wgmma_rs_n64(acc, A[12 * i + kk], wdesc + ((i * SLOT + kk * 2048) >> 4), (i | kk) != 0);
          wg_commit();
          if (i == 1) { wg_wait<1>(); if (lead) release(st0); }
        }
        if (ps == 1 && wg == 0) bar_arrive(5, 256);
        uint32_t a[4][4], b[4][4];
        mbar_wait(sb + SM_MISCB);
        T = (*reinterpret_cast<volatile unsigned*>(smem + SM_EPOCH) & 1) ^ 1;
#pragma unroll
        for (int h = 0; h < 4; h++) ldsm4t(b[h], wpa + h * 512);
        wg_wait<0>();
        if ((tid & 127) < 2) release(st0 + 1 + (tid & 1));
        TSTAMP(2 + 2 * ps);
#pragma unroll
        for (int h = 0; h < 4; h++) {
          a[h][0] = pack2(acc[8 * h + 0] * r0, acc[8 * h + 1] * r0); a[h][1] = pack2(acc[8 * h + 2] * r1, acc[8 * h + 3] * r1);
          a[h][2] = pack2(acc[8 * h + 4] * r0, acc[8 * h + 5] * r0); a[h][3] = pack2(acc[8 * h + 6] * r1, acc[8 * h + 7] * r1);
        }
        if (ps != 1) {
          {
            float pp[4][2][4];
#pragma unroll
            for (int h = 0; h < 4; h++) {
#pragma unroll
              for (int i = 0; i < 4; i++) { pp[h][0][i] = 0.f; pp[h][1][i] = 0.f; }
              mma16816(pp[h][0], a[h], b[h][0], b[h][1]);
              mma16816(pp[h][1], a[h], b[h][2], b[h][3]);
            }
#pragma unroll
            for (int h = 0; h < 4; h++) {
              a[h][0] = pack2(pp[h][0][0], pp[h][0][1]); a[h][1] = pack2(pp[h][0][2], pp[h][0][3]);
              a[h][2] = pack2(pp[h][1][0], pp[h][1][1]); a[h][3] = pack2(pp[h][1][2], pp[h][1][3]);
            }
          }
          if (ps == 0 || wg == 0) bar_arrive(4 + (wg ^ 1), 256);
          if (ps == 0) mbar_wait(sb + SM_EMPTY + (wg ? ST_SCR1 - NSLOT : ST_SCR0 - NSLOT) * 8);
#pragma unroll 1
          for (int hp = 0; hp < 2; hp++) {
            float e[2][16];
            feat_exp(a[0], e[0]);
            feat_exp(a[1], e[1]);
            if (ps == 0) {
#pragma unroll
              for (int h = 0; h < 2; h++) {
                const float (&f)[16] = e[h];
                float sp0 = (f[0] + f[1]) + (f[4] + f[5]), sp1 = (f[2] + f[3]) + (f[6] + f[7]);
                float sn0 = (f[8] + f[9]) + (f[12] + f[13]), sn1 = (f[10] + f[11]) + (f[14] + f[15]);
                sp0 += __shfl_xor_sync(0xffffffffu, sp0, 1); sp1 += __shfl_xor_sync(0xffffffffu, sp1, 1);
                sn0 += __shfl_xor_sync(0xffffffffu, sn0, 1); sn1 += __shfl_xor_sync(0xffffffffu, sn1, 1);
                sp0 += __shfl_xor_sync(0xffffffffu, sp0, 2); sp1 += __shfl_xor_sync(0xffffffffu, sp1, 2);
                sn0 += __shfl_xor_sync(0xffffffffu, sn0, 2); sn1 += __shfl_xor_sync(0xffffffffu, sn1, 2);
                sp0 = rcp(sp0); sp1 = rcp(sp1); sn0 = rcp(sn0); sn1 = rcp(sn1);
                const uint32_t dst = scr + hp * 8192 + lrow;
                stsm4(dst + (((h * 4 + lhi) ^ lx) << 4), pack2(f[0] * sp0, f[1] * sp0), pack2(f[2] * sp1, f[3] * sp1),
                      pack2(f[4] * sp0, f[5] * sp0), pack2(f[6] * sp1, f[7] * sp1));
                stsm4(dst + (((h * 4 + 2 + lhi) ^ lx) << 4), pack2(f[8] * sn0, f[9] * sn0), pack2(f[10] * sn1, f[11] * sn1),
                      pack2(f[12] * sn0, f[13] * sn0), pack2(f[14] * sn1, f[15] * sn1));
              }
            } else {
#pragma unroll
              for (int i = 0; i < 16; i++) {
                A[i >> 2][i & 3] = A[4 + (i >> 2)][i & 3];
                A[4 + (i >> 2)][i & 3] = pack2(e[i >> 3][2 * (i & 7)], e[i >> 3][2 * (i & 7) + 1]);
              }
            }
#pragma unroll
            for (int i = 0; i < 4; i++) { a[0][i] = a[2][i]; a[1][i] = a[3][i]; }
          }
        } else {
#pragma unroll
          for (int h = 0; h < 4; h++) stsm4(scr + 16384 + lrow + (((2 * h + lhi) ^ lx) << 4), a[h][0], a[h][1], a[h][2], a[h][3]);
          fence_async_smem();
          bar_sync(3, 256);
          float kv[36];
          wg_fence();
#pragma unroll
          for (int ks = 0; ks < 8; ks++) {
            const uint32_t sk = (ks < 4 ? (ST_SCR0 % NSLOT) : (ST_SCR1 % NSLOT)) * SLOT + (ks & 3) * 2048;
            const uint32_t dv = (DESC(sk + 16384) & 0xFFFFu) | (((SM_ONES - sk - 16384) >> 4) << 16);
            wgmma_ss_n72_t11(kv, DESC(sk) + wg * 512, dv, ks != 0);
          }
          wg_commit();
          if (wg == 1) bar_arrive(4, 256);
          wg_wait<0>();
          if (lead) { mbar_arrive(sb + SM_EMPTY + ST_SCR0 * 8); mbar_arrive(sb + SM_EMPTY + ST_SCR1 * 8); }
          const int hl = 2 * wg + (wq >> 1), f = (wq & 1) * 16 + g;
          float* kvp = reinterpret_cast<float*>(smem + 2 * SLOT) + (hl * 32 + f) * 16 + 2 * t;
          float c[8];
#pragma unroll
          for (int i = 0; i < 8; i++) c[i] = hl >= 2 ? (hl == 3 ? kv[24 + i] : kv[16 + i]) : (hl == 1 ? kv[8 + i] : kv[i]);
#pragma unroll
          for (int n = 0; n < 2; n++) {
            *reinterpret_cast<float2*>(kvp + n * 8) = make_float2(c[4 * n], c[4 * n + 1]);
            *reinterpret_cast<float2*>(kvp + n * 8 + 128) = make_float2(c[4 * n + 2], c[4 * n + 3]);
          }
          if (t < 2) reinterpret_cast<float*>(smem + 2 * SLOT)[2048 + hl * 32 + f + t * 8] = t ? kv[34] : kv[32];
          fence_async_smem();
          bar_sync(6, 320);
        }
        TSTAMP(3 + 2 * ps);
      }
#pragma unroll
      for (int i = 0; i < 32; i++) E[i >> 3][i & 7] = A[i >> 2][i & 3];
    }
    const int rh = 2 * rb + wg;
#define IDF ((g >> 1) == t ? ((g & 1) ? 0x3F800000u : 0x00003F80u) : 0u)
    const uint4* xb = reinterpret_cast<const uint4*>(smem + 2 * SLOT) + wq * 128 + lane;
    mbar_wait(sb + SM_KVB);
    {
      const int r = tid & 127;
      const float4* src = reinterpret_cast<const float4*>(smem + SM_KV32) + r;
#pragma unroll
      for (int i = 0; i < 4; i++) {
        const float4 a = src[i * 128];
        *reinterpret_cast<uint2*>(smem + SM_KVS + (i * 32 + (r >> 2)) * 48 + (r & 3) * 8) = make_uint2(pack2(a.x, a.y), pack2(a.z, a.w));
      }
      const uint32_t zz = pack2(reinterpret_cast<const float*>(smem + SM_ONES)[r], 1.0f);
      *reinterpret_cast<uint4*>(smem + SM_KVS + r * 48 + 32) = make_uint4(zz, zz, zz, zz);
      bar_sync(1 + wg, 128);
    }
    TSTAMP(8);
    {
      uint4* op = &g_o[rh][hg][wq][0][lane];
      if (wg == 1) bar_sync(5, 256);
#pragma unroll 1
      for (int hp = 0; hp < 2; hp++) {
#pragma unroll
      for (int h = 0; h < 2; h++) {
        uint32_t b0[4], b1[4], b2[4];
        const uint32_t kb = sb + SM_KVS + ((2 * hp + h) * 32 + lane) * 48;
        ldsm4t(b0, kb); ldsm4t(b1, kb + 16); ldsm4t(b2, kb + 32);
        const uint32_t ep[4] = {E[h][0], E[h][1], E[h][2], E[h][3]}, en[4] = {E[h][4], E[h][5], E[h][6], E[h][7]};
        float np0[4] = {0, 0, 0, 0}, np1[4] = {0, 0, 0, 0}, nn0[4] = {0, 0, 0, 0}, nn1[4] = {0, 0, 0, 0}, dp[4] = {0, 0, 0, 0}, dn[4] = {0, 0, 0, 0};
        mma16816(dp, ep, b2[0], b2[1]);  mma16816(dn, en, b2[2], b2[3]);
        mma16816(np0, ep, b0[0], b0[1]); mma16816(nn0, en, b0[2], b0[3]);
        mma16816(np1, ep, b1[0], b1[1]); mma16816(nn1, en, b1[2], b1[3]);
        const float i0 = rcp(fmaf(dp[0], dn[1], fmaf(dn[0], dp[1], 1e-6f * dp[1] * dn[1])));
        const float i1 = rcp(fmaf(dp[2], dn[3], fmaf(dn[2], dp[3], 1e-6f * dp[3] * dn[3])));
        const float cp0 = dn[1] * i0, cn0 = dp[1] * i0, cp1 = dn[3] * i1, cn1 = dp[3] * i1;
        st_rlx4(op + (2 * hp + h) * 32,
                tg(pack2(fmaf(np0[0], cp0, nn0[0] * cn0), fmaf(np0[1], cp0, nn0[1] * cn0)), T),
                pack2(fmaf(np0[2], cp1, nn0[2] * cn1), fmaf(np0[3], cp1, nn0[3] * cn1)),
                pack2(fmaf(np1[0], cp0, nn1[0] * cn0), fmaf(np1[1], cp0, nn1[1] * cn0)),
                pack2(fmaf(np1[2], cp1, nn1[2] * cn1), fmaf(np1[3], cp1, nn1[3] * cn1)));
      }
#pragma unroll
        for (int i = 0; i < 8; i++) { E[0][i] = E[2][i]; E[1][i] = E[3][i]; }
      }
    }
    if (wg == 0) bar_arrive(5, 256);
    bar_arrive(10 + wg, 160);
    TSTAMP(9);

    {
      uint32_t xr[4][4];
      {
        const uint32_t* xp = reinterpret_cast<const uint32_t*>(x + (size_t)(rh * 64 + wq * 16 + g) * 512 + hg * 64 + 2 * t);
#pragma unroll
        for (int i = 0; i < 8; i++) { xr[i >> 1][(i & 1) * 2] = __ldg(xp + 4 * i); xr[i >> 1][(i & 1) * 2 + 1] = __ldg(xp + 8 * 256 + 4 * i); }
      }
      uint32_t A[8][4][4];
      const uint4* op = &g_o[rh][0][wq][0][lane];
      float acc[32];
#pragma unroll
      for (int i = 0; i < 32; i++) acc[i] = 0.f;
      add_frag(acc, xr, IDF);
#pragma unroll
      for (int p = -1; p < 4; p++) {
        if (p < 3) {
          mbar_wait(sb + SM_XF + (wg * 4 + p + 1) * 8);
          get_pair(A[2 * p + 2], A[2 * p + 3], xb + (p + 1) * 1024, op + (p + 1) * 1024, T);
          if (lane == 0) mbar_arrive(sb + SM_XE + (wg * 4 + p + 1) * 8);
        }
        if (p == 0 && wg == 1) bar_sync(4, 256);
        if (p >= 0) {
          if (p != 2) mbar_wait(sb + SM_FULL + (ST_WO + (p + 1) / 2) * 8);
          wg_fence();
#pragma unroll
          for (int c = 2 * p; c < 2 * p + 2; c++)
#pragma unroll
            for (int s = 0; s < 4; s++)
              wgmma_rs_n64(acc, A[c][s], DESC(((ST_WO + c / 3) % NSLOT) * SLOT + ((c % 3) * 4 + s) * 2048), 1);
        }
      }
      wg_commit();
      if (wg == 0) bar_arrive(4, 256);
      wg_wait<0>();
      if ((tid & 127) < 3) release(ST_WO + (tid & 127));
      TSTAMP(10);
      uint4* hp_ = &g_h[rh][hg][wq][0][lane];
      uint32_t hx = T;
#pragma unroll
      for (int s = 0; s < 4; s++) {
        const uint32_t h0 = pack2(acc[8 * s], acc[8 * s + 1]);
        st_rlx4(hp_ + s * 32, tg(h0, T), pack2(acc[8 * s + 2], acc[8 * s + 3]), pack2(acc[8 * s + 4], acc[8 * s + 5]), pack2(acc[8 * s + 6], acc[8 * s + 7]));
        hx |= (h0 & 1u) << (s + 1);
      }
      float s0 = 0.f, s1 = 0.f, q0 = 0.f, q1 = 0.f, q2 = 0.f, q3 = 0.f;
#pragma unroll
      for (int i = 0; i < 8; i++) {
        s0 += acc[4 * i] + acc[4 * i + 1]; s1 += acc[4 * i + 2] + acc[4 * i + 3];
        q0 = fmaf(acc[4 * i], acc[4 * i], q0); q2 = fmaf(acc[4 * i + 1], acc[4 * i + 1], q2);
        q1 = fmaf(acc[4 * i + 2], acc[4 * i + 2], q1); q3 = fmaf(acc[4 * i + 3], acc[4 * i + 3], q3);
      }
      q0 += q2; q1 += q3;
      {
        const bool up = t & 2;
        float s = (up ? s1 : s0) + __shfl_xor_sync(0xffffffffu, up ? s0 : s1, 2);
        float q = (up ? q1 : q0) + __shfl_xor_sync(0xffffffffu, up ? q0 : q1, 2);
        s += __shfl_xor_sync(0xffffffffu, s, 1);
        q += __shfl_xor_sync(0xffffffffu, q, 1);
        if (!(t & 1)) st_rlx2(&g_st[rh][hg][wq * 16 + g + (t >> 1) * 8], tg(__float_as_uint(s), T), __float_as_uint(q));
      }
      st_rlx1(&g_hx[rh][hg][wq][lane], hx);
    }
    bar_arrive(10 + wg, 160);
    TSTAMP(11);

    const int rh3 = 2 * rb3 + wg;
    uint32_t HH[11][4], PH[11][4];
    const uint4* pp = &g_hh[rh3][jf ^ 1][0][wq][lane];
    {
      uint32_t A[8][4][4];
      const uint4* hp_ = &g_h[rh3][0][wq][0][lane];
      uint4* hhp = &g_hh[rh3][jf][0][wq][lane];
      const uint32_t dg = (db & 0xFFFFu) | (256u << 16);
      uint32_t m0, m1;
      mbar_wait(sb + SM_XF + ((2 + wg) * 4) * 8);
      TSTAMP(0);
      {
        const uint2* sp = reinterpret_cast<const uint2*>(smem + SM_KV32 + wg * 4096) + 2 * t * 64 + wq * 16 + g;
        uint2 a0, a1, b0, b1;
        int it = 0;
#pragma unroll 1
        do {
          ld_rlx2(a0.x, a0.y, sp); ld_rlx2(a1.x, a1.y, sp + 64); ld_rlx2(b0.x, b0.y, sp + 8); ld_rlx2(b1.x, b1.y, sp + 72);
          sp = &g_st[rh3][2 * t][wq * 16 + g];
        } while (__any_sync(0xffffffffu, bad4(a0.x, a1.x, b0.x, b1.x, T)) && ++it < (1 << 18));
        float s0 = __uint_as_float(a0.x) + __uint_as_float(a1.x), q0 = __uint_as_float(a0.y) + __uint_as_float(a1.y);
        float s1 = __uint_as_float(b0.x) + __uint_as_float(b1.x), q1 = __uint_as_float(b0.y) + __uint_as_float(b1.y);
        s0 += __shfl_xor_sync(0xffffffffu, s0, 1); s1 += __shfl_xor_sync(0xffffffffu, s1, 1);
        q0 += __shfl_xor_sync(0xffffffffu, q0, 1); q1 += __shfl_xor_sync(0xffffffffu, q1, 1);
        s0 += __shfl_xor_sync(0xffffffffu, s0, 2); s1 += __shfl_xor_sync(0xffffffffu, s1, 2);
        q0 += __shfl_xor_sync(0xffffffffu, q0, 2); q1 += __shfl_xor_sync(0xffffffffu, q1, 2);
        s0 *= (1.f / 512.f); s1 *= (1.f / 512.f);
        r0 = rcp(fmaxf(q0 * (1.f / 512.f) - s0 * s0, 0.f) + 1e-5f);
        r1 = rcp(fmaxf(q1 * (1.f / 512.f) - s1 * s1, 0.f) + 1e-5f);
        m0 = pack2(s0, s0); m1 = pack2(s1, s1);
      }
      TSTAMP(12);
#define UOFF(u) ((((ST_GU + (u) / 3) % NSLOT) * SLOT + ((u) % 3) * 8192) >> 4)
#define UNIT_PRE(u)  do { if ((u) % 3 == 0) mbar_wait(sb + SM_FULL + (ST_GU + (u) / 3) * 8); } while (0)
#define UNIT_POST(u) do { wg_commit(); if ((u) % 3 == 1 && (u) > 3) { wg_wait<2>(); if (lead) release(ST_GU + (u) / 3 - 1); } } while (0)
      float acc[64];
      const int rz = blockIdx.y;
#pragma unroll
      for (int ps = 0; ps < 2; ps++) {
        wg_fence();
#pragma unroll
        for (int k = 0; k < 16; k++) {
          const int u = 16 * ps + k, c = k >> 1;
          if (ps == 0 && (k == 0 || k == 4 || k == 8)) {
#pragma unroll
            for (int p = (k == 0 ? 0 : (k == 4 ? 1 : 3)); p < (k == 0 ? 1 : (k == 4 ? 3 : 4)); p++) {
              if (p > 0) mbar_wait(sb + SM_XF + ((2 + wg) * 4 + p) * 8);
              get_pair(A[2 * p], A[2 * p + 1], xb + p * 1024, hp_ + p * 1024, T);
              if (lane == 0) {
                if (wg == 0) mbar_arrive(sb + SM_XE + (8 + p) * 8);
                else if (p > 0) release(ST_XC + p - 1);
              }
            }
          }
          if (ps == 0 && (k & 1) == 0) {
#pragma unroll
            for (int s = 0; s < 4; s++) {
              A[c][s][0] = hsub2(A[c][s][0], m0); A[c][s][1] = hsub2(A[c][s][1], m1);
              A[c][s][2] = hsub2(A[c][s][2], m0); A[c][s][3] = hsub2(A[c][s][3], m1);
            }
            wg_fence();
          }
          UNIT_PRE(u);
          wgmma_rs_n128(acc, A[c][(k & 1) * 2], dg + UOFF(u), k != 0 ? 1 : (ps ? rz : 0));
          wgmma_rs_n128(acc, A[c][(k & 1) * 2 + 1], dg + UOFF(u) + 128, 1);
          UNIT_POST(u);
        }
        wg_wait<0>();
        TSTAMP(22 + ps);
#pragma unroll
        for (int s = 0; s < 4; s++) {
          uint32_t (&hh)[4] = HH[4 + s];
          hh[0] = tg(pack2(acc[8 * s + 0] * acc[32 + 8 * s + 0], acc[8 * s + 1] * acc[32 + 8 * s + 1]), T);
          hh[1] = pack2(acc[8 * s + 2] * acc[32 + 8 * s + 2], acc[8 * s + 3] * acc[32 + 8 * s + 3]);
          hh[2] = pack2(acc[8 * s + 4] * acc[32 + 8 * s + 4], acc[8 * s + 5] * acc[32 + 8 * s + 5]);
          hh[3] = pack2(acc[8 * s + 6] * acc[32 + 8 * s + 6], acc[8 * s + 7] * acc[32 + 8 * s + 7]);
          st_rlx4(hhp + (4 * ps + s) * 128, hh[0], hh[1], hh[2], hh[3]);
        }
      }
      {
        float ag[24], au[24];
        const uint32_t* ph7 = reinterpret_cast<const uint32_t*>(&g_hh[rh3][jf ^ 1][7][wq][31]);
        uint32_t hv = 0;
        bar_sync(1 + wg, 128);
        wg_fence();
#pragma unroll
        for (int k = 0; k < 16; k++) {
          const int u = 32 + k, c = k >> 1;
          if (k == 6) {
#pragma unroll
            for (int s = 0; s < 4; s++) ld_rlx4(HH[s], hhp + s * 128);
          }
          if (k == 9) hv = ld_rlx1(ph7);
          if (k == 12) {
            int it = 0;
#pragma unroll 1
            while (((hv ^ T) & 1) && ++it < (1 << 18)) hv = ld_rlx1(ph7);
#pragma unroll
            for (int s = 0; s < 8; s++) ld_rlx4(PH[s], pp + s * 128);
          }
          UNIT_PRE(u);
          wgmma_rs_n48(ag, A[c][(k & 1) * 2], dg + UOFF(u), k != 0);
          wgmma_rs_n48(au, A[c][(k & 1) * 2], dg + UOFF(u) + 256, k != 0);
          wgmma_rs_n48(ag, A[c][(k & 1) * 2 + 1], dg + UOFF(u) + 128, 1);
          wgmma_rs_n48(au, A[c][(k & 1) * 2 + 1], dg + UOFF(u) + 256 + 128, 1);
          UNIT_POST(u);
        }
        wg_wait<0>();
        TSTAMP(13);
#pragma unroll
        for (int s = 0; s < 3; s++) {
          uint32_t (&hh)[4] = HH[8 + s];
          hh[0] = tg(pack2(ag[8 * s + 0] * au[8 * s + 0], ag[8 * s + 1] * au[8 * s + 1]), T);
          hh[1] = pack2(ag[8 * s + 2] * au[8 * s + 2], ag[8 * s + 3] * au[8 * s + 3]);
          hh[2] = pack2(ag[8 * s + 4] * au[8 * s + 4], ag[8 * s + 5] * au[8 * s + 5]);
          hh[3] = pack2(ag[8 * s + 6] * au[8 * s + 6], ag[8 * s + 7] * au[8 * s + 7]);
          st_rlx4(hhp + (8 + s) * 128, hh[0], hh[1], hh[2], hh[3]);
        }
      }
    }
    TSTAMP(14);

    {
      float acc[32], sum[32];
      uint32_t hr[4][4], hx = 0;
      const int m = jf >> 1, oc = (jf & 1) * 4 + m;
      uint4* outb = &g_part[rh3][(jf & 1) * 4][m][wq][0][lane];
      bar_arrive(8 + wg, 256);
#pragma unroll
      for (int i = 0; i < 32; i++) sum[i] = 0.f;
      int s0 = ST_D % NSLOT;
#pragma unroll 1
      for (int k = 0; k < 4; k++) {
        const int s1 = s0 + 1 == NSLOT ? 0 : s0 + 1;
        const uint32_t d0 = db + s0 * (SLOT >> 4), d1 = db + s1 * (SLOT >> 4);
        uint32_t pk[16];
        wg_wait<0>();
        if (k == 1) bar_arrive(12, 320);
#pragma unroll
        for (int i = 0; i < 16; i++) pk[i] = pack2(acc[2 * i], acc[2 * i + 1]);
        mbar_wait(sb + SM_FULL + (ST_D + 2 * k) * 8);
        wg_fence();
#pragma unroll
        for (int s = 0; s < 4; s++) wgmma_rs_n64(acc, HH[s], d0 + s * 128, s != 0);
        if (k > 0) {
          uint4* p = outb + ((m + k) & 3) * 2048;
#pragma unroll
          for (int s = 0; s < 4; s++) st_rlx4(p + s * 32, tg(pk[4 * s], T), pk[4 * s + 1], pk[4 * s + 2], pk[4 * s + 3]);
        }
        if (k == 3) TSTAMP(18);
#pragma unroll
        for (int s = 4; s < 11; s++) wgmma_rs_n64(acc, HH[s], d0 + s * 128, 1);
        if (k == 0) {
          int it = 0;
#pragma unroll 1
          while (__any_sync(0xffffffffu, bad4(PH[0][0], PH[1][0], PH[2][0], PH[3][0], T) | bad4(PH[4][0], PH[5][0], PH[6][0], PH[7][0], T)) && ++it < (1 << 18)) {
#pragma unroll
            for (int s = 0; s < 8; s++) ld_rlx4(PH[s], pp + s * 128);
          }
#pragma unroll
          for (int s = 8; s < 11; s++) ld_rlx4(PH[s], pp + s * 128);
        }
        if (k == 2) {
          ld_chunk(hr, &g_h[rh3][oc][wq][0][lane]);
          hx = ld_rlx1(&g_hx[rh3][oc][wq][lane]);
        }
        mbar_wait(sb + SM_FULL + (ST_D + 2 * k + 1) * 8);
        wg_fence();
#pragma unroll
        for (int s = 0; s < 8; s++) wgmma_rs_n64(acc, PH[s], d1 + s * 128, 1);
        if (k == 0) {
          int it = 0;
#pragma unroll 1
          while (__any_sync(0xffffffffu, bad4(PH[8][0], PH[9][0], PH[10][0], T, T)) && ++it < (1 << 18)) {
#pragma unroll
            for (int s = 8; s < 11; s++) ld_rlx4(PH[s], pp + s * 128);
          }
          TSTAMP(20);
        }
        wg_fence();
#pragma unroll
        for (int s = 8; s < 11; s++) wgmma_rs_n64(acc, PH[s], d1 + s * 128, 1);
        wg_commit();
        s0 = s1 + 1 == NSLOT ? 0 : s1 + 1;
      }
#pragma unroll 1
      for (int q = 0; q < 3; q++) {
        uint32_t in[4][4];
        const uint4* sp = reinterpret_cast<const uint4*>(smem + ((ST_D % NSLOT) + wg) * SLOT) + q * 512 + wq * 128 + lane;
        mbar_wait_p(sb + SM_XF + (wg * 4 + q) * 8, 1);
        if (q == 0) TSTAMP(19); if (q == 1) TSTAMP(21); if (q == 2) TSTAMP(24);
        int it = 0;
#pragma unroll 1
        do {
#pragma unroll
          for (int s = 0; s < 4; s++)
            asm volatile("{\n.reg .b128 v;\nld.relaxed.gpu.b128 v, [%4];\nmov.b128 {%0,%1,%2,%3}, v;\n}"
                         : "=r"(in[s][0]), "=r"(in[s][1]), "=r"(in[s][2]), "=r"(in[s][3]) : "l"(sp + s * 32) : "memory");
          sp = &g_part[rh3][oc][(m - 1 - q) & 3][wq][0][lane];
        } while (__any_sync(0xffffffffu, bad4(in[0][0], in[1][0], in[2][0], in[3][0], T)) && ++it < (1 << 18));
#pragma unroll
        for (int i = 0; i < 16; i++) { sum[2 * i] += blo(in[i >> 2][i & 3]); sum[2 * i + 1] += bhi(in[i >> 2][i & 3]); }
      }
      wg_wait<0>();
      TSTAMP(15);
      {
        int it = 0;
#pragma unroll 1
        while (__any_sync(0xffffffffu, (hx ^ T) & 1) && ++it < (1 << 18)) hx = ld_rlx1(&g_hx[rh3][oc][wq][lane]);
      }
#pragma unroll
      for (int s = 0; s < 4; s++) hr[s][0] = (hr[s][0] & 0xFFFFFFFEu) | ((hx >> (s + 1)) & 1u);
#pragma unroll
      for (int i = 0; i < 16; i++) {
        const float r = (i & 1) ? r1 : r0;
        acc[2 * i]     = fmaf(acc[2 * i] + sum[2 * i], r, blo(hr[i >> 2][i & 3]));
        acc[2 * i + 1] = fmaf(acc[2 * i + 1] + sum[2 * i + 1], r, bhi(hr[i >> 2][i & 3]));
      }
      bar_sync(9 - wg, 256);
      const uint32_t ob = sb + ((ST_D - 1) % NSLOT) * SLOT + wg * 8192;
#pragma unroll
      for (int s = 0; s < 4; s++)
        stsm4(ob + lrow + (((2 * s + lhi) ^ lx) << 4), pack2(acc[8 * s + 0], acc[8 * s + 1]), pack2(acc[8 * s + 2], acc[8 * s + 3]),
              pack2(acc[8 * s + 4], acc[8 * s + 5]), pack2(acc[8 * s + 6], acc[8 * s + 7]));
      __syncwarp();
      {
        const int row = wq * 16 + (lane >> 3);
        __nv_bfloat16* op = out + (size_t)(rh3 * 64 + row) * 512 + oc * 64 + lx * 8;
#pragma unroll
        for (int i = 0; i < 4; i++) {
          uint4 v;
          asm volatile("ld.shared.v4.b32 {%0,%1,%2,%3}, [%4];" : "=r"(v.x), "=r"(v.y), "=r"(v.z), "=r"(v.w)
                       : "r"(ob + (row + i * 4) * 128 + ((lx ^ (((lane >> 3) + i * 4) & 7)) << 4)) : "memory");
          asm volatile("st.global.v4.b32 [%0], {%1,%2,%3,%4};" ::"l"(op + i * 2048), "r"(v.x), "r"(v.y), "r"(v.z), "r"(v.w) : "memory");
        }
      }
    }
    TSTAMP(16);
    asm volatile("barrier.cluster.arrive.relaxed.aligned;" ::: "memory");
    asm volatile("barrier.cluster.wait.aligned;" ::: "memory");
  } else {
    asm volatile("setmaxnreg.dec.sync.aligned.u32 24;");
    if (elect_one()) {
      if (warp == 8) {
#pragma unroll
        for (int k = 0; k < 9; k++) {
          const int s = k < 3 ? k : (k < 6 ? k + 3 : k - 3);
          const uint32_t bar = sb + SM_FULL + s * 8;
          mbar_init(bar, 1);
          mbar_expect_tx(bar, SLOT);
          if (s >= 3 && s < 6) tma2d(sb + s * SLOT, &maps.w, 512 + hg * 64, (s - 3) * 192, bar);
          else tma3d(sb + s * SLOT, &maps.x, 0, rb * 128 + (s >= 6 ? 64 : 0), 3 * (s % 3), bar);
        }
      } else if (warp == 9) {
        mbar_init(sb + SM_MISCB, 2);
        mbar_init(sb + SM_KVB, 1);
        mbar_expect_tx(sb + SM_KVB, 8704);
        mbar_expect_tx(sb + SM_MISCB, 2048);
        bulk_g2s(sb + SM_WPHI, wphi + hg * 1024, 2048, sb + SM_MISCB);
      } else if (warp == 10) {
        if ((sb & 0x3FFFF) != SM_BASE) __trap();
#pragma unroll 1
        for (int i = 0; i < 16; i++) {
          mbar_init(sb + SM_XF + i * 8, 1);
          mbar_expect_tx(sb + SM_XF + i * 8, (i == 8 || i == 12) ? 20480 : 16384);
          if (i < 12) mbar_init(sb + SM_XE + i * 8, 4);
        }
      } else {
        *reinterpret_cast<volatile unsigned*>(smem + SM_EPOCH) = atomicAdd(&g_start, 1u) / NCTA;
      }
      asm volatile("fence.mbarrier_init.release.cluster;" ::: "memory");
    }
    __syncwarp();
    if (warp != 11) bar_sync(0, 352);
    asm volatile("barrier.cluster.arrive.relaxed.aligned;" ::: "memory");
    if (warp == 8) {
      asm volatile("barrier.cluster.wait.aligned;" ::: "memory");
      if (elect_one()) {
        const CUtensorMap* mg = jf == 7 ? &maps.g7 : &maps.g;
        const CUtensorMap* mu = jf == 7 ? &maps.u7 : &maps.u;
        asm volatile("prefetch.tensormap [%0];" ::"l"(&maps.wo) : "memory");
        asm volatile("prefetch.tensormap [%0];" ::"l"(mg) : "memory");
        asm volatile("prefetch.tensormap [%0];" ::"l"(mu) : "memory");
        asm volatile("prefetch.tensormap [%0];" ::"l"(&maps.d) : "memory");
#pragma unroll 1
        for (int s = ST_WV; s < ST_XC; s++) {
          if (s == ST_SCR1) continue;
          mbar_wait(sb + SM_EMPTY + (s - 9) * 8);
          const uint32_t dst = sb + (s >= 18 ? s - 18 : s - 9) * SLOT, bar = sb + SM_FULL + s * 8;
          if (s < ST_WO) tma2d(dst, &maps.w, (s < ST_WQ ? 1024 : 0) + hg * 64, (s < ST_WQ ? s - ST_WV : s - ST_WQ) * 192, bar);
          else { mbar_wait(bar - 8); tma2d(dst, &maps.wo, hg * 64, (s - ST_WO) * 192, bar); }
        }
        const int jc = jf == 7 ? 0 : jf;
        int slot = (ST_GU + 1 - rank) % NSLOT;
#pragma unroll 1
        for (int s = ST_GU + 1 - rank; s < NSTAGE; s += 2) {
          mbar_wait(sb + SM_EMPTY + (s - 9) * 8);
          if (s > ST_GU && s < ST_GU + THR) mbar_wait(sb + SM_FULL + (s - 1) * 8);
          const uint32_t dst = sb + slot * SLOT, bar = sb + SM_FULL + s * 8;
          if (s < ST_D) {
#pragma unroll 1
            for (int i = 0; i < 3; i++) {
              const int u = (s - ST_GU) * 3 + i;
              tma3d_mc(dst + i * 8192, mg, (u >> 4) * 64, jc, (u & 15) * 32, bar);
              tma3d_mc(dst + i * 8192 + 4096, mu, (u >> 4) * 64, jc, (u & 15) * 32, bar);
            }
          } else {
            const int i = s - ST_D;
            tma2d_mc(dst, &maps.d, ((jf & 1) * 4 + (((jf >> 1) + 1 + (i >> 1)) & 3)) * 64, (jf ^ (i & 1)) * 176, bar);
          }
          slot += 2; if (slot >= NSLOT) slot -= NSLOT;
        }
      }
      __syncwarp();
    } else {
      asm volatile("barrier.cluster.wait.aligned;" ::: "memory");
      if (warp == 11) {
#pragma unroll
        for (int i = 0; i < 4; i++)
          reinterpret_cast<uint4*>(smem + SM_ONES)[lane + 32 * i] = make_uint4(0x3F803F80u, 0x3F803F80u, 0x3F803F80u, 0x3F803F80u);
        fence_async_smem();
        __syncwarp();
        if (lane == 0) mbar_arrive(sb + SM_MISCB);
      }
      mbar_wait(sb + SM_MISCB);
      const unsigned epoch = *reinterpret_cast<volatile unsigned*>(smem + SM_EPOCH);
      const uint32_t T = (epoch & 1) ^ 1;
      if (warp == 11) {
        reinterpret_cast<float4*>(&g_kv[hg][rb * 136])[lane] = make_float4(0.f, 0.f, 0.f, 0.f);
        if (lane < 2) reinterpret_cast<float4*>(&g_kv[hg][rb * 136])[32 + lane] = make_float4(0.f, 0.f, 0.f, 0.f);
        __syncwarp();
        if (elect_one()) asm volatile("red.release.gpu.global.add.u32 [%0], 1;" ::"l"(&g_kvcnt[hg * 32 + 1]) : "memory");
        mbar_wait(sb + SM_FULL + (ST_WK + 2) * 8);
        if (elect_one()) {
          asm volatile("cp.async.bulk.prefetch.L2.global [%0], 4096;" ::"l"((const char*)wo + blockIdx.x * 4096) : "memory");
          asm volatile("cp.async.bulk.prefetch.L2.global [%0], 11008;" ::"l"((const char*)wg_ + blockIdx.x * 11008) : "memory");
          asm volatile("cp.async.bulk.prefetch.L2.global [%0], 11008;" ::"l"((const char*)wu_ + blockIdx.x * 11008) : "memory");
          asm volatile("cp.async.bulk.prefetch.L2.global [%0], 11008;" ::"l"((const char*)wd_ + blockIdx.x * 11008) : "memory");
          mbar_wait(sb + SM_EMPTY + ST_SCR0 * 8);
          const unsigned target = (epoch + 1) * 16;
          unsigned v; int it = 0;
#pragma unroll 1
          do {
            asm volatile("ld.acquire.gpu.global.u32 %0, [%1];" : "=r"(v) : "l"(&g_kvcnt[hg * 32]) : "memory");
            if (++it > (1 << 18)) break;
          } while ((int)(v - target) < 0);
          TS2(0, 26);
          asm volatile("fence.proxy.async.global;" ::: "memory");
          bulk_g2s(sb + SM_KV32, &g_kv[hg][0], 8192, sb + SM_KVB);
          bulk_g2s(sb + SM_ONES, &g_kv[hg][2048], 512, sb + SM_KVB);
        }
        __syncwarp();
      } else {
        const int w = warp - 9;
        st_rlx4(reinterpret_cast<uint4*>(&g_st[2 * rb + w][hg][0]) + lane, T ^ 1, T ^ 1, T ^ 1, T ^ 1);
        if (lane < 8) st_rlx4(&g_o[2 * rb + w][hg][lane >> 1][3][30 + (lane & 1)], T ^ 1, T ^ 1, T ^ 1, T ^ 1);
        st_rlx4(&g_part[2 * rb3 + w][(jf & 1) * 4 + (lane >> 3)][jf >> 1][(lane >> 1) & 3][3][30 + (lane & 1)], T ^ 1, T ^ 1, T ^ 1, T ^ 1);
        if (lane < 8) st_rlx4(&g_hh[2 * rb3 + w][jf][7][lane >> 1][30 + (lane & 1)], T ^ 1, T ^ 1, T ^ 1, T ^ 1);
#pragma unroll 1
        for (int i = 0; i < 12; i++) st_rlx4(&g_hh[2 * rb3 + w][jf][8][0][lane] + i * 32, T ^ 1, T ^ 1, T ^ 1, T ^ 1);
        if (w == 0) {
          mbar_wait(sb + SM_FULL + (ST_WQ + 2) * 8);
          unsigned v; int it = 0;
#pragma unroll 1
          do {
            asm volatile("ld.acquire.gpu.global.u32 %0, [%1];" : "=r"(v) : "l"(&g_kvcnt[hg * 32 + 1]) : "memory");
          } while ((int)(v - (epoch + 1) * 16) < 0 && ++it < (1 << 18));
          asm volatile("fence.proxy.async.global;" ::: "memory");
        }
        bar_sync(6, 320);
        if (w == 0 && elect_one()) {
          asm volatile("cp.reduce.async.bulk.global.shared::cta.bulk_group.add.f32 [%0], [%1], 8704;"
                       ::"l"(&g_kv[hg][0]), "r"(sb + 2 * SLOT) : "memory");
          asm volatile("cp.async.bulk.commit_group;" ::: "memory");
          asm volatile("cp.async.bulk.wait_group 0;" ::: "memory");
          asm volatile("red.relaxed.gpu.global.add.u32 [%0], 1;" ::"l"(&g_kvcnt[hg * 32]) : "memory");
          TS2(0, 25);
        }
        __syncwarp();
        mbar_wait(sb + SM_KVB);
        if (w == 0) { mbar_wait(sb + SM_EMPTY + 11 * 8); mbar_wait(sb + SM_EMPTY + 12 * 8); mbar_wait(sb + SM_EMPTY + 13 * 8); }
#pragma unroll 1
        for (int ph = 0; ph < 2; ph++) {
          const int use = 2 * ph + w, r = ph ? 2 * rb3 + w : 2 * rb + w;
          const uint32_t* pw = ph ? reinterpret_cast<const uint32_t*>(&g_st[r][lane >> 2][(lane & 3) * 16 + 15])
                                  : reinterpret_cast<const uint32_t*>(&g_o[r][lane >> 2][lane & 3][3][31]);
          const char* src = reinterpret_cast<const char*>(ph ? &g_h[r][0][0][0][0] : &g_o[r][0][0][0][0]);
          const uint32_t bf = sb + SM_XF + use * 32, be = sb + SM_XE + (use - 1) * 32;
          bar_sync(10 + w, 160);
          int it = 0;
#pragma unroll 1
          for (bool miss = true; __any_sync(0xffffffffu, miss) && ++it < (1 << 18);) { if (miss) miss = (ld_rlx1(pw) ^ T) & 1; }
          if (elect_one()) {
            TS2(w, 27 + ph);
            if (use > 0) mbar_wait(be);
            if (ph) bulk_g2s(sb + SM_KV32 + w * 4096, &g_st[r][0][0], 4096, bf);
#pragma unroll
            for (int p = 0; p < 4; p++) {
              if (p > 0 && use > 0) mbar_wait(be + p * 8);
              bulk_g2s(sb + 2 * SLOT + p * 16384, src + p * 16384, 16384, bf + p * 8);
            }
          }
          __syncwarp();
        }
        {
          const int m = jf >> 1, oc = (jf & 1) * 4 + m;
          const uint32_t* pw = reinterpret_cast<const uint32_t*>(&g_part[2 * rb3 + w][oc][(m - 1 - (lane >> 2)) & 3][lane & 3][3][31]);
          bar_sync(12, 320);
          bool miss = lane < 12; int it = 0;
#pragma unroll 1
          for (int q = 0; q < 3; q++) {
#pragma unroll 1
            while ((__ballot_sync(0xffffffffu, miss) >> (4 * q) & 15) && ++it < (1 << 18)) { if (miss && (lane >> 2) <= q + 1) miss = (ld_rlx1(pw) ^ T) & 1; }
            if (elect_one()) {
              const uint32_t bar = sb + SM_XF + (w * 4 + q) * 8;
              mbar_expect_tx(bar, 8192);
              if (q == 2) TS2(w, 17);
              bulk_g2s(sb + ((ST_D % NSLOT) + w) * SLOT + q * 8192, &g_part[2 * rb3 + w][oc][(m - 1 - q) & 3][0][0][0], 8192, bar);
            }
            __syncwarp();
          }
        }
      }
    }
    asm volatile("barrier.cluster.arrive.relaxed.aligned;" ::: "memory");
    asm volatile("barrier.cluster.wait.aligned;" ::: "memory");
  }
}

typedef CUresult (*EncodeFn)(CUtensorMap*, CUtensorMapDataType, cuuint32_t, void*, const cuuint64_t*, const cuuint64_t*,
                             const cuuint32_t*, const cuuint32_t*, CUtensorMapInterleave, CUtensorMapSwizzle,
                             CUtensorMapL2promotion, CUtensorMapFloatOOBfill);

void encode(EncodeFn fn, CUtensorMap* m, const void* base, int rank, const cuuint64_t* dims, const cuuint64_t* strides,
            const cuuint32_t* box) {
  cuuint32_t es[3] = {1, 1, 1};
  fn(m, CU_TENSOR_MAP_DATA_TYPE_BFLOAT16, (cuuint32_t)rank, const_cast<void*>(base), dims, strides, box, es,
     CU_TENSOR_MAP_INTERLEAVE_NONE, CU_TENSOR_MAP_SWIZZLE_128B, CU_TENSOR_MAP_L2_PROMOTION_L2_256B,
     CU_TENSOR_MAP_FLOAT_OOB_FILL_NONE);
}

}

extern "C" void kernel_launch(void* const* d_in, const int* in_sizes, int n_in, void* d_out, int out_size) {
  (void)in_sizes; (void)n_in; (void)out_size;
  const __nv_bfloat16* x    = (const __nv_bfloat16*)d_in[0];
  const __nv_bfloat16* wqkv = (const __nv_bfloat16*)d_in[1];
  const __nv_bfloat16* wphi = (const __nv_bfloat16*)d_in[2];
  const __nv_bfloat16* wo   = (const __nv_bfloat16*)d_in[3];
  const __nv_bfloat16* wg   = (const __nv_bfloat16*)d_in[5];
  const __nv_bfloat16* wu   = (const __nv_bfloat16*)d_in[6];
  const __nv_bfloat16* wd   = (const __nv_bfloat16*)d_in[7];

  static EncodeFn fn = nullptr;
  if (!fn) {
    void* p = nullptr;
    cudaDriverEntryPointQueryResult qr;
    cudaGetDriverEntryPoint("cuTensorMapEncodeTiled", &p, cudaEnableDefault, &qr);
    fn = (EncodeFn)p;
    cudaFuncSetAttribute(fused_kernel, cudaFuncAttributeMaxDynamicSharedMemorySize, SM_TOTAL);
  }
  Maps maps;
  {
    cuuint64_t d[3] = {64, 2048, 8}, s[2] = {1024, 128}; cuuint32_t b[3] = {64, 64, 3};
    encode(fn, &maps.x, x, 3, d, s, b);
  }
  {
    cuuint64_t d[2] = {1536, 512}, s[1] = {3072}; cuuint32_t b[2] = {64, 192};
    encode(fn, &maps.w, wqkv, 2, d, s, b);
  }
  {
    cuuint64_t d[2] = {512, 512}, s[1] = {1024}; cuuint32_t b[2] = {64, 192};
    encode(fn, &maps.wo, wo, 2, d, s, b);
  }
  {
    cuuint64_t d[3] = {176, 7, 512}, d7[3] = {144, 1, 512}, s[2] = {352, 2752}; cuuint32_t b[3] = {64, 1, 32};
    encode(fn, &maps.g, wg, 3, d, s, b);
    encode(fn, &maps.u, wu, 3, d, s, b);
    encode(fn, &maps.g7, wg + 1232, 3, d7, s, b);
    encode(fn, &maps.u7, wu + 1232, 3, d7, s, b);
  }
  {
    cuuint64_t d[2] = {512, 1376}, s[1] = {1024}; cuuint32_t b[2] = {64, 176};
    encode(fn, &maps.d, wd, 2, d, s, b);
  }
  fused_kernel<<<NCTA, 384, SM_TOTAL>>>(maps, x, wphi, wo, wg, wu, wd, (__nv_bfloat16*)d_out);
}
```

```cpp
#include <cuda_runtime.h>
#include <cuda_bf16.h>
#include <cuda.h>
#include <stdint.h>

#define PROF 0

#define SAFE_WAIT 0
#define OPRIO 1
#define THR 6

namespace {

constexpr int NCTA   = 128;
constexpr int SLOT   = 24576;
constexpr int NSLOT  = 9;
constexpr int NSTAGE = 47;

constexpr int ST_X0   = 0;
constexpr int ST_WK   = 3;
constexpr int ST_X1   = 6;
constexpr int ST_SCR0 = 9;
constexpr int ST_WV   = 10;
constexpr int ST_SCR1 = 13;
constexpr int ST_WQ   = 14;
constexpr int ST_WO   = 17;
constexpr int ST_XC   = 20;
constexpr int ST_GU   = 23;
constexpr int ST_D    = 39;

__host__ __device__ constexpr int st_empty_cnt(int d) {
  return ((d < 3 || (d >= 6 && d < 9) || (d >= ST_XC && d < ST_GU)) ? 4 : 2) * (d + 9 >= ST_GU ? 2 : 1);
}

constexpr uint32_t SM_BASE = 1024;
constexpr int SM_ONES = NSLOT * SLOT;
constexpr int SM_WPHI = SM_ONES + 2048;
constexpr int SM_KVS  = SM_WPHI + 2048;
constexpr int SM_KV32 = 4 * SLOT + 16384;
constexpr int SM_BAR  = SM_KVS + 6144;
constexpr int SM_FULL  = SM_BAR;
constexpr int SM_EMPTY = SM_BAR + NSTAGE * 8;
constexpr int SM_MISCB = SM_BAR + 2 * NSTAGE * 8;
constexpr int SM_KVB   = SM_MISCB + 8;
constexpr int SM_EPOCH = SM_KVB + 8;
constexpr int SM_XF    = SM_EPOCH + 8;
constexpr int SM_XE    = SM_XF + 16 * 8;
constexpr int SM_TOTAL = SM_BAR + 1024;

static_assert(SM_TOTAL == 232448 && SM_XE + 12 * 8 <= SM_TOTAL, "smem budget");

struct Maps { CUtensorMap x, w, wo, g, u, g7, u7, d; };

__device__ uint4    g_o[32][8][4][4][32];
__device__ uint4    g_h[32][8][4][4][32];
__device__ uint32_t g_hx[32][8][4][32];
__device__ uint2    g_st[32][8][64];
__device__ uint4    g_hh[32][8][11][4][32];
__device__ uint4    g_part[32][8][4][4][4][32];
__device__ __align__(128) float g_kv[8][2048 + 128];
__device__ unsigned g_kvcnt[8 * 32];
__device__ unsigned g_start;

__device__ __forceinline__ uint32_t smem_u32(const void* p) { return (uint32_t)__cvta_generic_to_shared(p); }
__device__ __forceinline__ void mbar_init(uint32_t bar, int cnt) {
  asm volatile("mbarrier.init.shared::cta.b64 [%0], %1;" ::"r"(bar), "r"(cnt) : "memory");
}
__device__ __forceinline__ void mbar_expect_tx(uint32_t bar, uint32_t bytes) {
  asm volatile("mbarrier.arrive.expect_tx.shared::cta.b64 _, [%0], %1;" ::"r"(bar), "r"(bytes) : "memory");
}
__device__ __forceinline__ void mbar_arrive(uint32_t bar) {
  asm volatile("mbarrier.arrive.shared::cta.b64 _, [%0];" ::"r"(bar) : "memory");
}
__device__ __forceinline__ void mbar_arrive_cluster(uint32_t bar, uint32_t rank) {
  asm volatile("{\n.reg .b32 ra;\nmapa.shared::cluster.u32 ra, %0, %1;\n"
               "mbarrier.arrive.shared::cluster.b64 _, [ra];\n}" ::"r"(bar), "r"(rank) : "memory");
}
__device__ __forceinline__ void mbar_wait_p(uint32_t bar, uint32_t parity) {
  asm volatile("{\n.reg .pred p;\nW: mbarrier.try_wait.parity.shared::cta.b64 p, [%0], %1;\n@!p bra W;\n}" ::"r"(bar), "r"(parity) : "memory");
}
__device__ __forceinline__ void mbar_wait(uint32_t bar) { mbar_wait_p(bar, 0); }
__device__ __forceinline__ bool elect_one() {
  uint32_t p;
  asm volatile("{\n.reg .pred P;\nelect.sync _|P, 0xffffffff;\nselp.u32 %0, 1, 0, P;\n}" : "=r"(p));
  return p != 0;
}
__device__ __forceinline__ void bar_sync(int id, int n)   { asm volatile("bar.sync %0, %1;" ::"r"(id), "r"(n) : "memory"); }
__device__ __forceinline__ void bar_arrive(int id, int n) { asm volatile("bar.arrive %0, %1;" ::"r"(id), "r"(n) : "memory"); }
__device__ __forceinline__ void fence_async_smem() { asm volatile("fence.proxy.async.shared::cta;" ::: "memory"); }
__device__ __forceinline__ void wg_fence()  { asm volatile("wgmma.fence.sync.aligned;" ::: "memory"); }
__device__ __forceinline__ void wg_commit() { asm volatile("wgmma.commit_group.sync.aligned;" ::: "memory"); }
template <int N> __device__ __forceinline__ void wg_wait() { asm volatile("wgmma.wait_group.sync.aligned %0;" ::"n"(N) : "memory"); }
#define DESC(off) (db + ((uint32_t)(off) >> 4))
__device__ __forceinline__ void tma2d(uint32_t dst, const CUtensorMap* m, int c0, int c1, uint32_t bar) {
  asm volatile("cp.async.bulk.tensor.2d.shared::cluster.global.mbarrier::complete_tx::bytes [%0], [%1, {%3, %4}], [%2];"
               ::"r"(dst), "l"(m), "r"(bar), "r"(c0), "r"(c1) : "memory");
}
__device__ __forceinline__ void tma2d_mc(uint32_t dst, const CUtensorMap* m, int c0, int c1, uint32_t bar) {
  asm volatile("cp.async.bulk.tensor.2d.shared::cluster.global.mbarrier::complete_tx::bytes.multicast::cluster [%0], [%1, {%3, %4}], [%2], %5;"
               ::"r"(dst), "l"(m), "r"(bar), "r"(c0), "r"(c1), "h"((uint16_t)3) : "memory");
}
__device__ __forceinline__ void tma3d(uint32_t dst, const CUtensorMap* m, int c0, int c1, int c2, uint32_t bar) {
  asm volatile("cp.async.bulk.tensor.3d.shared::cluster.global.mbarrier::complete_tx::bytes [%0], [%1, {%3, %4, %5}], [%2];"
               ::"r"(dst), "l"(m), "r"(bar), "r"(c0), "r"(c1), "r"(c2) : "memory");
}
__device__ __forceinline__ void tma3d_mc(uint32_t dst, const CUtensorMap* m, int c0, int c1, int c2, uint32_t bar) {
  asm volatile("cp.async.bulk.tensor.3d.shared::cluster.global.mbarrier::complete_tx::bytes.multicast::cluster [%0], [%1, {%3, %4, %5}], [%2], %6;"
               ::"r"(dst), "l"(m), "r"(bar), "r"(c0), "r"(c1), "r"(c2), "h"((uint16_t)3) : "memory");
}
__device__ __forceinline__ void ldsm4(uint32_t (&r)[4], uint32_t addr) {
  asm volatile("ldmatrix.sync.aligned.m8n8.x4.shared.b16 {%0,%1,%2,%3}, [%4];"
               : "=r"(r[0]), "=r"(r[1]), "=r"(r[2]), "=r"(r[3]) : "r"(addr) : "memory");
}
__device__ __forceinline__ void ldsm4t(uint32_t (&r)[4], uint32_t addr) {
  asm volatile("ldmatrix.sync.aligned.m8n8.x4.trans.shared.b16 {%0,%1,%2,%3}, [%4];"
               : "=r"(r[0]), "=r"(r[1]), "=r"(r[2]), "=r"(r[3]) : "r"(addr) : "memory");
}
__device__ __forceinline__ void stsm4(uint32_t addr, uint32_t r0, uint32_t r1, uint32_t r2, uint32_t r3) {
  asm volatile("stmatrix.sync.aligned.m8n8.x4.shared.b16 [%0], {%1,%2,%3,%4};"
               ::"r"(addr), "r"(r0), "r"(r1), "r"(r2), "r"(r3) : "memory");
}
__device__ __forceinline__ void mma16816(float (&c)[4], const uint32_t (&a)[4], uint32_t b0, uint32_t b1) {
  asm volatile("mma.sync.aligned.m16n8k16.row.col.f32.bf16.bf16.f32 {%0,%1,%2,%3},{%4,%5,%6,%7},{%8,%9},{%0,%1,%2,%3};"
               : "+f"(c[0]), "+f"(c[1]), "+f"(c[2]), "+f"(c[3])
               : "r"(a[0]), "r"(a[1]), "r"(a[2]), "r"(a[3]), "r"(b0), "r"(b1));
}
__device__ __forceinline__ void add_frag(float (&c)[32], const uint32_t (&a)[4][4], uint32_t id) {
#pragma unroll
  for (int i = 0; i < 8; i++)
    asm volatile("mma.sync.aligned.m16n8k8.row.col.f32.bf16.bf16.f32 {%0,%1,%2,%3},{%4,%5},{%6},{%0,%1,%2,%3};"
                 : "+f"(c[4 * i]), "+f"(c[4 * i + 1]), "+f"(c[4 * i + 2]), "+f"(c[4 * i + 3])
                 : "r"(a[i >> 1][(i & 1) * 2]), "r"(a[i >> 1][(i & 1) * 2 + 1]), "r"(id));
}
__device__ __forceinline__ uint32_t pack2(float lo, float hi) {
  uint32_t r; asm("cvt.rn.bf16x2.f32 %0, %1, %2;" : "=r"(r) : "f"(hi), "f"(lo)); return r;
}
__device__ __forceinline__ float blo(uint32_t w) { return __uint_as_float(w << 16); }
__device__ __forceinline__ float bhi(uint32_t w) { return __uint_as_float(w & 0xFFFF0000u); }
__device__ __forceinline__ uint32_t hsub2(uint32_t a, uint32_t b) { uint32_t r; asm("sub.rn.bf16x2 %0, %1, %2;" : "=r"(r) : "r"(a), "r"(b)); return r; }
__device__ __forceinline__ uint32_t hmax2(uint32_t a, uint32_t b) { uint32_t r; asm("max.bf16x2 %0, %1, %2;" : "=r"(r) : "r"(a), "r"(b)); return r; }
__device__ __forceinline__ uint32_t hmin2(uint32_t a, uint32_t b) { uint32_t r; asm("min.bf16x2 %0, %1, %2;" : "=r"(r) : "r"(a), "r"(b)); return r; }
__device__ __forceinline__ float ex2(float x) { float r; asm("ex2.approx.ftz.f32 %0, %1;" : "=f"(r) : "f"(x)); return r; }
__device__ __forceinline__ float rcp(float x) { float r; asm("rcp.approx.ftz.f32 %0, %1;" : "=f"(r) : "f"(x)); return r; }
__device__ __forceinline__ void ld_rlx4(uint32_t (&r)[4], const uint4* p) {
  asm volatile("{\n.reg .b128 v;\nld.relaxed.gpu.global.b128 v, [%4];\nmov.b128 {%0,%1,%2,%3}, v;\n}"
               : "=r"(r[0]), "=r"(r[1]), "=r"(r[2]), "=r"(r[3]) : "l"(p) : "memory");
}
__device__ __forceinline__ void st_rlx4(uint4* p, uint32_t a, uint32_t b, uint32_t c, uint32_t d) {
  asm volatile("st.relaxed.gpu.global.v4.b32 [%0], {%1,%2,%3,%4};" ::"l"(p), "r"(a), "r"(b), "r"(c), "r"(d) : "memory");
}
__device__ __forceinline__ void st_rlx2(uint2* p, uint32_t a, uint32_t b) {
  asm volatile("{\n.reg .b64 v;\nmov.b64 v, {%1,%2};\nst.relaxed.gpu.global.b64 [%0], v;\n}" ::"l"(p), "r"(a), "r"(b) : "memory");
}
__device__ __forceinline__ uint32_t ld_rlx1(const uint32_t* p) {
  uint32_t r; asm volatile("ld.relaxed.gpu.global.b32 %0, [%1];" : "=r"(r) : "l"(p) : "memory"); return r;
}
__device__ __forceinline__ void st_rlx1(uint32_t* p, uint32_t a) {
  asm volatile("st.relaxed.gpu.global.b32 [%0], %1;" ::"l"(p), "r"(a) : "memory");
}
__device__ __forceinline__ void ld_rlx2(uint32_t& a, uint32_t& b, const uint2* p) {
  asm volatile("{\n.reg .b64 v;\nld.relaxed.gpu.b64 v, [%2];\nmov.b64 {%0,%1}, v;\n}" : "=r"(a), "=r"(b) : "l"(p) : "memory");
}
__device__ __forceinline__ void bulk_g2s(uint32_t dst, const void* src, uint32_t bytes, uint32_t bar) {
  asm volatile("cp.async.bulk.shared::cluster.global.mbarrier::complete_tx::bytes [%0], [%1], %2, [%3];"
               ::"r"(dst), "l"(src), "r"(bytes), "r"(bar) : "memory");
}
__device__ __forceinline__ uint32_t tg(uint32_t w, uint32_t T) { return (w & 0xFFFFFFFEu) | T; }
__device__ __forceinline__ uint32_t bad4(uint32_t a, uint32_t b, uint32_t c, uint32_t d, uint32_t T) {
  uint32_t u, v;
  asm("lop3.b32 %0, %1, %2, %3, 0x7E;" : "=r"(u) : "r"(a), "r"(b), "r"(T));
  asm("lop3.b32 %0, %1, %2, %3, 0x7E;" : "=r"(v) : "r"(c), "r"(d), "r"(T));
  asm("lop3.b32 %0, %1, %2, 1, 0xA8;" : "=r"(u) : "r"(u), "r"(v));
  return u;
}

__device__ __forceinline__ void ld_chunk(uint32_t (&a)[4][4], const uint4* p) {
#pragma unroll
  for (int s = 0; s < 4; s++) ld_rlx4(a[s], p + s * 32);
}
__device__ __forceinline__ void get_pair(uint32_t (&a)[4][4], uint32_t (&b)[4][4], const uint4* sp, const uint4* gp, uint32_t T) {
  int it = 0;
#pragma unroll 1
  do {
#pragma unroll
    for (int s = 0; s < 8; s++) {
      uint32_t (&r)[4] = s < 4 ? a[s & 3] : b[s & 3];
      asm volatile("{\n.reg .b128 v;\nld.relaxed.gpu.b128 v, [%4];\nmov.b128 {%0,%1,%2,%3}, v;\n}"
                   : "=r"(r[0]), "=r"(r[1]), "=r"(r[2]), "=r"(r[3]) : "l"(sp + (s >> 2) * 512 + (s & 3) * 32) : "memory");
    }
    sp = gp;
  } while (__any_sync(0xffffffffu, bad4(a[0][0], a[1][0], a[2][0], a[3][0], T) | bad4(b[0][0], b[1][0], b[2][0], b[3][0], T)) && ++it < (1 << 18));
}

__device__ __forceinline__ void wgmma_rs_n48(float (&d)[24], const uint32_t (&a)[4], uint32_t descB, int scaleD) {
  asm volatile("{\n.reg .pred p;\n.reg .b64 db;\nsetp.ne.b32 p, %29, 0;\nmov.b64 db, {%28, 0x40000040};\n"
    "wgmma.mma_async.sync.aligned.m64n48k16.f32.bf16.bf16 {%0,%1,%2,%3,%4,%5,%6,%7,%8,%9,%10,%11,%12,%13,%14,%15,%16,%17,%18,%19,%20,%21,%22,%23}, {%24,%25,%26,%27}, db, p, 1, 1, 1;\n}\n"
    : "+f"(d[0]),"+f"(d[1]),"+f"(d[2]),"+f"(d[3]),"+f"(d[4]),"+f"(d[5]),"+f"(d[6]),"+f"(d[7]),"+f"(d[8]),"+f"(d[9]),"+f"(d[10]),"+f"(d[11]),"+f"(d[12]),"+f"(d[13]),"+f"(d[14]),"+f"(d[15]),"+f"(d[16]),"+f"(d[17]),"+f"(d[18]),"+f"(d[19]),"+f"(d[20]),"+f"(d[21]),"+f"(d[22]),"+f"(d[23])
    : "r"(a[0]), "r"(a[1]), "r"(a[2]), "r"(a[3]), "r"(descB), "r"(scaleD));
}
__device__ __forceinline__ void wgmma_rs_n64(float (&d)[32], const uint32_t (&a)[4], uint32_t descB, int scaleD) {
  asm volatile("{\n.reg .pred p;\n.reg .b64 db;\nsetp.ne.b32 p, %37, 0;\nmov.b64 db, {%36, 0x40000040};\n"
    "wgmma.mma_async.sync.aligned.m64n64k16.f32.bf16.bf16 {%0,%1,%2,%3,%4,%5,%6,%7,%8,%9,%10,%11,%12,%13,%14,%15,%16,%17,%18,%19,%20,%21,%22,%23,%24,%25,%26,%27,%28,%29,%30,%31}, {%32,%33,%34,%35}, db, p, 1, 1, 1;\n}\n"
    : "+f"(d[0]),"+f"(d[1]),"+f"(d[2]),"+f"(d[3]),"+f"(d[4]),"+f"(d[5]),"+f"(d[6]),"+f"(d[7]),"+f"(d[8]),"+f"(d[9]),"+f"(d[10]),"+f"(d[11]),"+f"(d[12]),"+f"(d[13]),"+f"(d[14]),"+f"(d[15]),"+f"(d[16]),"+f"(d[17]),"+f"(d[18]),"+f"(d[19]),"+f"(d[20]),"+f"(d[21]),"+f"(d[22]),"+f"(d[23]),"+f"(d[24]),"+f"(d[25]),"+f"(d[26]),"+f"(d[27]),"+f"(d[28]),"+f"(d[29]),"+f"(d[30]),"+f"(d[31])
    : "r"(a[0]), "r"(a[1]), "r"(a[2]), "r"(a[3]), "r"(descB), "r"(scaleD));
}
__device__ __forceinline__ void wgmma_rs_n128(float (&d)[64], const uint32_t (&a)[4], uint32_t descB, int scaleD) {
  asm volatile("{\n.reg .pred p;\n.reg .b64 db;\nsetp.ne.b32 p, %69, 0;\nmov.b64 db, {%68, 0x40000040};\n"
    "wgmma.mma_async.sync.aligned.m64n128k16.f32.bf16.bf16 {%0,%1,%2,%3,%4,%5,%6,%7,%8,%9,%10,%11,%12,%13,%14,%15,%16,%17,%18,%19,%20,%21,%22,%23,%24,%25,%26,%27,%28,%29,%30,%31,%32,%33,%34,%35,%36,%37,%38,%39,%40,%41,%42,%43,%44,%45,%46,%47,%48,%49,%50,%51,%52,%53,%54,%55,%56,%57,%58,%59,%60,%61,%62,%63}, {%64,%65,%66,%67}, db, p, 1, 1, 1;\n}\n"
    : "+f"(d[0]),"+f"(d[1]),"+f"(d[2]),"+f"(d[3]),"+f"(d[4]),"+f"(d[5]),"+f"(d[6]),"+f"(d[7]),"+f"(d[8]),"+f"(d[9]),"+f"(d[10]),"+f"(d[11]),"+f"(d[12]),"+f"(d[13]),"+f"(d[14]),"+f"(d[15]),"+f"(d[16]),"+f"(d[17]),"+f"(d[18]),"+f"(d[19]),"+f"(d[20]),"+f"(d[21]),"+f"(d[22]),"+f"(d[23]),"+f"(d[24]),"+f"(d[25]),"+f"(d[26]),"+f"(d[27]),"+f"(d[28]),"+f"(d[29]),"+f"(d[30]),"+f"(d[31]),"+f"(d[32]),"+f"(d[33]),"+f"(d[34]),"+f"(d[35]),"+f"(d[36]),"+f"(d[37]),"+f"(d[38]),"+f"(d[39]),"+f"(d[40]),"+f"(d[41]),"+f"(d[42]),"+f"(d[43]),"+f"(d[44]),"+f"(d[45]),"+f"(d[46]),"+f"(d[47]),"+f"(d[48]),"+f"(d[49]),"+f"(d[50]),"+f"(d[51]),"+f"(d[52]),"+f"(d[53]),"+f"(d[54]),"+f"(d[55]),"+f"(d[56]),"+f"(d[57]),"+f"(d[58]),"+f"(d[59]),"+f"(d[60]),"+f"(d[61]),"+f"(d[62]),"+f"(d[63])
    : "r"(a[0]), "r"(a[1]), "r"(a[2]), "r"(a[3]), "r"(descB), "r"(scaleD));
}
__device__ __forceinline__ void wgmma_ss_n72_t11(float (&d)[36], uint32_t descA, uint32_t descB, int scaleD) {
  asm volatile("{\n.reg .pred p;\n.reg .b64 da, db;\nsetp.ne.b32 p, %38, 0;\nmov.b64 da, {%36, 0x40000040};\nmov.b64 db, {%37, 0x40000040};\n"
    "wgmma.mma_async.sync.aligned.m64n72k16.f32.bf16.bf16 {%0,%1,%2,%3,%4,%5,%6,%7,%8,%9,%10,%11,%12,%13,%14,%15,%16,%17,%18,%19,%20,%21,%22,%23,%24,%25,%26,%27,%28,%29,%30,%31,%32,%33,%34,%35}, da, db, p, 1, 1, 1, 1;\n}\n"
    : "+f"(d[0]),"+f"(d[1]),"+f"(d[2]),"+f"(d[3]),"+f"(d[4]),"+f"(d[5]),"+f"(d[6]),"+f"(d[7]),"+f"(d[8]),"+f"(d[9]),"+f"(d[10]),"+f"(d[11]),"+f"(d[12]),"+f"(d[13]),"+f"(d[14]),"+f"(d[15]),"+f"(d[16]),"+f"(d[17]),"+f"(d[18]),"+f"(d[19]),"+f"(d[20]),"+f"(d[21]),"+f"(d[22]),"+f"(d[23]),"+f"(d[24]),"+f"(d[25]),"+f"(d[26]),"+f"(d[27]),"+f"(d[28]),"+f"(d[29]),"+f"(d[30]),"+f"(d[31]),"+f"(d[32]),"+f"(d[33]),"+f"(d[34]),"+f"(d[35])
    : "r"(descA), "r"(descB), "r"(scaleD));
}

#define TSTAMP(i) do {} while (0)
#define TS2(w, i) do {} while (0)

constexpr float LOG2E = 1.4426950408889634f;

__device__ __forceinline__ void feat_exp(const uint32_t (&P)[4], float (&e)[16]) {
  uint32_t a = hmax2(P[0], P[2]), b = hmax2(P[1], P[3]);
  uint32_t mx = hmax2(__byte_perm(a, b, 0x5410), __byte_perm(a, b, 0x7632));
  a = hmin2(P[0], P[2]); b = hmin2(P[1], P[3]);
  uint32_t mn = hmin2(__byte_perm(a, b, 0x5410), __byte_perm(a, b, 0x7632));
  mx = hmax2(mx, __shfl_xor_sync(0xffffffffu, mx, 1));
  mn = hmin2(mn, __shfl_xor_sync(0xffffffffu, mn, 1));
  mx = hmax2(mx, __shfl_xor_sync(0xffffffffu, mx, 2));
  mn = hmin2(mn, __shfl_xor_sync(0xffffffffu, mn, 2));
  float mx0 = -blo(mx) * LOG2E, mx1 = -bhi(mx) * LOG2E, mn0 = blo(mn) * LOG2E, mn1 = bhi(mn) * LOG2E;
  float v[8] = {blo(P[0]), bhi(P[0]), blo(P[1]), bhi(P[1]), blo(P[2]), bhi(P[2]), blo(P[3]), bhi(P[3])};
#pragma unroll
  for (int i = 0; i < 8; i++) {
    bool r1 = (i >> 1) & 1;
    e[i]     = ex2(fmaf(v[i],  LOG2E, r1 ? mx1 : mx0));
    e[8 + i] = ex2(fmaf(v[i], -LOG2E, r1 ? mn1 : mn0));
  }
}

__global__ void __cluster_dims__(2, 1, 1) __launch_bounds__(384, 1)
fused_kernel(const __grid_constant__ Maps maps, const __nv_bfloat16* __restrict__ x, const __nv_bfloat16* __restrict__ wphi,
             const __nv_bfloat16* __restrict__ wo, const __nv_bfloat16* __restrict__ wg_, const __nv_bfloat16* __restrict__ wu_,
             const __nv_bfloat16* __restrict__ wd_, __nv_bfloat16* __restrict__ out) {
  extern __shared__ __align__(1024) unsigned char smem[];
  const uint32_t sb = smem_u32(smem);
  const int tid = threadIdx.x, lane = tid & 31;
  const int warp = __shfl_sync(0xffffffffu, tid >> 5, 0);
  const uint32_t rank = blockIdx.x & 1;
  const int cl = blockIdx.x >> 1;
  int quad, qi;
  if (cl < 4) { quad = 15; qi = cl; }
  else if (cl < 36) { quad = (cl - 4) & 7; qi = (cl - 4) >> 3; }
  else { qi = (cl - 36) / 7; quad = 8 + (cl - 36) - 7 * qi; }
  const int rb = quad, hg = 2 * qi + rank;
  const int rb3 = (quad & ~1) + rank, jf = 4 * (quad & 1) + qi;

  if (warp < 8) {
    asm volatile("setmaxnreg.inc.sync.aligned.u32 240;");
    if (elect_one()) {
#pragma unroll 1
      for (int d = warp; d + 9 < NSTAGE; d += 8) {
        mbar_init(sb + SM_EMPTY + d * 8, st_empty_cnt(d));
        {
          mbar_init(sb + SM_FULL + (d + 9) * 8, 1);
          mbar_expect_tx(sb + SM_FULL + (d + 9) * 8, d + 9 >= ST_D ? 22528 : SLOT);
        }
      }
      asm volatile("fence.mbarrier_init.release.cluster;" ::: "memory");
    }
    __syncwarp();
    bar_sync(0, 352);
    asm volatile("barrier.cluster.arrive.relaxed.aligned;" ::: "memory");
    const int wg = warp >> 2, wq = warp & 3, g = lane >> 2, t = lane & 3;
    const bool lead = (tid & 127) == 0;
    constexpr uint32_t db = (SM_BASE >> 4) | (512u << 16);
    auto release = [&](int d) {
      const int s = d + NSLOT;
      mbar_arrive_cluster(sb + SM_EMPTY + d * 8, s >= ST_GU ? (uint32_t)(s & 1) : rank);
    };
    const uint32_t lrow = (uint32_t)(wq * 16 + (lane & 7) + ((lane >> 3) & 1) * 8) * 128;
    const uint32_t lx = lane & 7, lhi = lane >> 4;
    if (wg == 1) bar_arrive(4, 256);

    float r0, r1;
    uint32_t E[4][8];
    uint32_t T = 0;
    {
      uint32_t A[32][4];
      const int sx = wg ? ST_X1 : ST_X0;
      {
        const uint32_t base = sb + sx * SLOT + lrow, baseb = sb + sx * SLOT + (wq * 16 + lx + lhi * 8) * 128;
        float cs[2][4], c0[2][4], c1[2][4];
#pragma unroll
        for (int i = 0; i < 4; i++) { cs[0][i] = cs[1][i] = c0[0][i] = c0[1][i] = c1[0][i] = c1[1][i] = 0.f; }
        uint32_t bt[2][4][4];
#pragma unroll
        for (int c = -1; c < 8; c++) {
          if (c < 7) {
            const int n = c + 1;
            if (n % 3 == 0) mbar_wait(sb + SM_FULL + (sx + n / 3) * 8);
#pragma unroll
            for (int k = 0; k < 4; k++) {
              ldsm4(A[4 * n + k], base + n * 8192 + (((2 * k + lhi) ^ lx) << 4));
              ldsm4(bt[n & 1][k], baseb + n * 8192 + (((2 * k + ((lane >> 3) & 1)) ^ lx) << 4));
            }
          }
          if (c >= 0) {
#pragma unroll
            for (int k = 0; k < 4; k++) {
              const uint32_t (&f)[4] = A[4 * c + k];
              mma16816(cs[k & 1], f, 0x3F803F80u, 0x3F803F80u);
              mma16816(c0[k & 1], f, bt[c & 1][k][0], bt[c & 1][k][1]);
              mma16816(c1[k & 1], f, bt[c & 1][k][2], bt[c & 1][k][3]);
            }
          }
        }
        const float s0 = (cs[0][0] + cs[1][0]) * (1.f / 512.f), s1 = (cs[0][2] + cs[1][2]) * (1.f / 512.f);
        asm volatile("barrier.cluster.wait.aligned;" ::: "memory");
        if (lane < 3) release(sx + lane);
        const uint32_t m0 = pack2(s0, s0), m1 = pack2(s1, s1);
        float q0 = (g & 1) ? c0[0][1] + c0[1][1] : c0[0][0] + c0[1][0];
        float q1 = (g & 1) ? c1[0][3] + c1[1][3] : c1[0][2] + c1[1][2];
        q0 = __shfl_sync(0xffffffffu, q0, (lane & ~3) | (g >> 1));
        q1 = __shfl_sync(0xffffffffu, q1, (lane & ~3) | (g >> 1));
        r0 = rsqrtf(fmaxf(q0 * (1.f / 512.f) - s0 * s0, 0.f) + 1e-5f);
        r1 = rsqrtf(fmaxf(q1 * (1.f / 512.f) - s1 * s1, 0.f) + 1e-5f);
#pragma unroll
        for (int ks = 0; ks < 32; ks++) {
          A[ks][0] = hsub2(A[ks][0], m0); A[ks][1] = hsub2(A[ks][1], m1);
          A[ks][2] = hsub2(A[ks][2], m0); A[ks][3] = hsub2(A[ks][3], m1);
        }
      }
      TSTAMP(1);
      const uint32_t wpa = sb + SM_WPHI + ((lane & 7) + ((lane >> 3) & 1) * 8) * 32 + lhi * 16;
      const uint32_t scr = sb + (wg ? (ST_SCR1 % NSLOT) : (ST_SCR0 % NSLOT)) * SLOT;
#pragma unroll 1
      for (int ps = 0; ps < 3; ps++) {
        const int st0 = ps == 0 ? ST_WK : (ps == 1 ? ST_WV : ST_WQ);
        const uint32_t wdesc = DESC((ps == 0 ? ST_WK % NSLOT : (ps == 1 ? ST_WV % NSLOT : ST_WQ % NSLOT)) * SLOT);
        float acc[32];
        bar_sync(4 + wg, 256);
#pragma unroll
        for (int i = 0; i < 3; i++) {
          mbar_wait(sb + SM_FULL + (st0 + i) * 8);
          wg_fence();
#pragma unroll
          for (int kk = 0; kk < (i < 2 ? 12 : 8); kk++)
            wgmma_rs_n64(acc, A[12 * i + kk], wdesc + ((i * SLOT + kk * 2048) >> 4), (i | kk) != 0);
          wg_commit();
          if (i == 1) { wg_wait<1>(); if (lead) release(st0); }
        }
        if (ps == 1 && wg == 0) bar_arrive(5, 256);
        uint32_t a[4][4], b[4][4];
        mbar_wait(sb + SM_MISCB);
        T = (*reinterpret_cast<volatile unsigned*>(smem + SM_EPOCH) & 1) ^ 1;
#pragma unroll
        for (int h = 0; h < 4; h++) ldsm4t(b[h], wpa + h * 512);
        wg_wait<0>();
        if ((tid & 127) < 2) release(st0 + 1 + (tid & 1));
        TSTAMP(2 + 2 * ps);
#pragma unroll
        for (int h = 0; h < 4; h++) {
          a[h][0] = pack2(acc[8 * h + 0] * r0, acc[8 * h + 1] * r0); a[h][1] = pack2(acc[8 * h + 2] * r1, acc[8 * h + 3] * r1);
          a[h][2] = pack2(acc[8 * h + 4] * r0, acc[8 * h + 5] * r0); a[h][3] = pack2(acc[8 * h + 6] * r1, acc[8 * h + 7] * r1);
        }
        if (ps != 1) {
          {
            float pp[4][2][4];
#pragma unroll
            for (int h = 0; h < 4; h++) {
#pragma unroll
              for (int i = 0; i < 4; i++) { pp[h][0][i] = 0.f; pp[h][1][i] = 0.f; }
              mma16816(pp[h][0], a[h], b[h][0], b[h][1]);
              mma16816(pp[h][1], a[h], b[h][2], b[h][3]);
            }
#pragma unroll
            for (int h = 0; h < 4; h++) {
              a[h][0] = pack2(pp[h][0][0], pp[h][0][1]); a[h][1] = pack2(pp[h][0][2], pp[h][0][3]);
              a[h][2] = pack2(pp[h][1][0], pp[h][1][1]); a[h][3] = pack2(pp[h][1][2], pp[h][1][3]);
            }
          }
          if (ps == 0 || wg == 0) bar_arrive(4 + (wg ^ 1), 256);
          if (ps == 0) mbar_wait(sb + SM_EMPTY + (wg ? ST_SCR1 - NSLOT : ST_SCR0 - NSLOT) * 8);
#pragma unroll 1
          for (int hp = 0; hp < 2; hp++) {
            float e[2][16];
            feat_exp(a[0], e[0]);
            feat_exp(a[1], e[1]);
            if (ps == 0) {
#pragma unroll
              for (int h = 0; h < 2; h++) {
                const float (&f)[16] = e[h];
                float sp0 = (f[0] + f[1]) + (f[4] + f[5]), sp1 = (f[2] + f[3]) + (f[6] + f[7]);
                float sn0 = (f[8] + f[9]) + (f[12] + f[13]), sn1 = (f[10] + f[11]) + (f[14] + f[15]);
                sp0 += __shfl_xor_sync(0xffffffffu, sp0, 1); sp1 += __shfl_xor_sync(0xffffffffu, sp1, 1);
                sn0 += __shfl_xor_sync(0xffffffffu, sn0, 1); sn1 += __shfl_xor_sync(0xffffffffu, sn1, 1);
                sp0 += __shfl_xor_sync(0xffffffffu, sp0, 2); sp1 += __shfl_xor_sync(0xffffffffu, sp1, 2);
                sn0 += __shfl_xor_sync(0xffffffffu, sn0, 2); sn1 += __shfl_xor_sync(0xffffffffu, sn1, 2);
                sp0 = rcp(sp0); sp1 = rcp(sp1); sn0 = rcp(sn0); sn1 = rcp(sn1);
                const uint32_t dst = scr + hp * 8192 + lrow;
                stsm4(dst + (((h * 4 + lhi) ^ lx) << 4), pack2(f[0] * sp0, f[1] * sp0), pack2(f[2] * sp1, f[3] * sp1),
                      pack2(f[4] * sp0, f[5] * sp0), pack2(f[6] * sp1, f[7] * sp1));
                stsm4(dst + (((h * 4 + 2 + lhi) ^ lx) << 4), pack2(f[8] * sn0, f[9] * sn0), pack2(f[10] * sn1, f[11] * sn1),
                      pack2(f[12] * sn0, f[13] * sn0), pack2(f[14] * sn1, f[15] * sn1));
              }
            } else {
#pragma unroll
              for (int i = 0; i < 16; i++) {
                A[i >> 2][i & 3] = A[4 + (i >> 2)][i & 3];
                A[4 + (i >> 2)][i & 3] = pack2(e[i >> 3][2 * (i & 7)], e[i >> 3][2 * (i & 7) + 1]);
              }
            }
#pragma unroll
            for (int i = 0; i < 4; i++) { a[0][i] = a[2][i]; a[1][i] = a[3][i]; }
          }
        } else {
#pragma unroll
          for (int h = 0; h < 4; h++) stsm4(scr + 16384 + lrow + (((2 * h + lhi) ^ lx) << 4), a[h][0], a[h][1], a[h][2], a[h][3]);
          fence_async_smem();
          bar_sync(3, 256);
          float kv[36];
          wg_fence();
#pragma unroll
          for (int ks = 0; ks < 8; ks++) {
            const uint32_t sk = (ks < 4 ? (ST_SCR0 % NSLOT) : (ST_SCR1 % NSLOT)) * SLOT + (ks & 3) * 2048;
            const uint32_t dv = (DESC(sk + 16384) & 0xFFFFu) | (((SM_ONES - sk - 16384) >> 4) << 16);
            wgmma_ss_n72_t11(kv, DESC(sk) + wg * 512, dv, ks != 0);
          }
          wg_commit();
          if (wg == 1) bar_arrive(4, 256);
          wg_wait<0>();
          if (lead) { mbar_arrive(sb + SM_EMPTY + ST_SCR0 * 8); mbar_arrive(sb + SM_EMPTY + ST_SCR1 * 8); }
          const int hl = 2 * wg + (wq >> 1), f = (wq & 1) * 16 + g;
          float* kvp = reinterpret_cast<float*>(smem + 2 * SLOT) + (hl * 32 + f) * 16 + 2 * t;
          float c[8];
#pragma unroll
          for (int i = 0; i < 8; i++) c[i] = hl >= 2 ? (hl == 3 ? kv[24 + i] : kv[16 + i]) : (hl == 1 ? kv[8 + i] : kv[i]);
#pragma unroll
          for (int n = 0; n < 2; n++) {
            *reinterpret_cast<float2*>(kvp + n * 8) = make_float2(c[4 * n], c[4 * n + 1]);
            *reinterpret_cast<float2*>(kvp + n * 8 + 128) = make_float2(c[4 * n + 2], c[4 * n + 3]);
          }
          if (t < 2) reinterpret_cast<float*>(smem + 2 * SLOT)[2048 + hl * 32 + f + t * 8] = t ? kv[34] : kv[32];
          fence_async_smem();
          bar_sync(6, 320);
        }
        TSTAMP(3 + 2 * ps);
      }
#pragma unroll
      for (int i = 0; i < 32; i++) E[i >> 3][i & 7] = A[i >> 2][i & 3];
    }
    const int rh = 2 * rb + wg;
#define IDF ((g >> 1) == t ? ((g & 1) ? 0x3F800000u : 0x00003F80u) : 0u)
    const uint4* xb = reinterpret_cast<const uint4*>(smem + 2 * SLOT) + wq * 128 + lane;
    mbar_wait(sb + SM_KVB);
    {
      const int r = tid & 127;
      const float4* src = reinterpret_cast<const float4*>(smem + SM_KV32) + r;
#pragma unroll
      for (int i = 0; i < 4; i++) {
        const float4 a = src[i * 128];
        *reinterpret_cast<uint2*>(smem + SM_KVS + (i * 32 + (r >> 2)) * 48 + (r & 3) * 8) = make_uint2(pack2(a.x, a.y), pack2(a.z, a.w));
      }
      const uint32_t zz = pack2(reinterpret_cast<const float*>(smem + SM_ONES)[r], 1.0f);
      *reinterpret_cast<uint4*>(smem + SM_KVS + r * 48 + 32) = make_uint4(zz, zz, zz, zz);
      bar_sync(1 + wg, 128);
    }
    TSTAMP(8);
    {
      uint4* op = &g_o[rh][hg][wq][0][lane];
      if (wg == 1) bar_sync(5, 256);
#pragma unroll 1
      for (int hp = 0; hp < 2; hp++) {
#pragma unroll
      for (int h = 0; h < 2; h++) {
        uint32_t b0[4], b1[4], b2[4];
        const uint32_t kb = sb + SM_KVS + ((2 * hp + h) * 32 + lane) * 48;
        ldsm4t(b0, kb); ldsm4t(b1, kb + 16); ldsm4t(b2, kb + 32);
        const uint32_t ep[4] = {E[h][0], E[h][1], E[h][2], E[h][3]}, en[4] = {E[h][4], E[h][5], E[h][6], E[h][7]};
        float np0[4] = {0, 0, 0, 0}, np1[4] = {0, 0, 0, 0}, nn0[4] = {0, 0, 0, 0}, nn1[4] = {0, 0, 0, 0}, dp[4] = {0, 0, 0, 0}, dn[4] = {0, 0, 0, 0};
        mma16816(dp, ep, b2[0], b2[1]);  mma16816(dn, en, b2[2], b2[3]);
        mma16816(np0, ep, b0[0], b0[1]); mma16816(nn0, en, b0[2], b0[3]);
        mma16816(np1, ep, b1[0], b1[1]); mma16816(nn1, en, b1[2], b1[3]);
        const float i0 = rcp(fmaf(dp[0], dn[1], fmaf(dn[0], dp[1], 1e-6f * dp[1] * dn[1])));
        const float i1 = rcp(fmaf(dp[2], dn[3], fmaf(dn[2], dp[3], 1e-6f * dp[3] * dn[3])));
        const float cp0 = dn[1] * i0, cn0 = dp[1] * i0, cp1 = dn[3] * i1, cn1 = dp[3] * i1;
        st_rlx4(op + (2 * hp + h) * 32,
                tg(pack2(fmaf(np0[0], cp0, nn0[0] * cn0), fmaf(np0[1], cp0, nn0[1] * cn0)), T),
                pack2(fmaf(np0[2], cp1, nn0[2] * cn1), fmaf(np0[3], cp1, nn0[3] * cn1)),
                pack2(fmaf(np1[0], cp0, nn1[0] * cn0), fmaf(np1[1], cp0, nn1[1] * cn0)),
                pack2(fmaf(np1[2], cp1, nn1[2] * cn1), fmaf(np1[3], cp1, nn1[3] * cn1)));
      }
#pragma unroll
        for (int i = 0; i < 8; i++) { E[0][i] = E[2][i]; E[1][i] = E[3][i]; }
      }
    }
    if (wg == 0) bar_arrive(5, 256);
    bar_arrive(10 + wg, 160);
    TSTAMP(9);

    {
      uint32_t xr[4][4];
      {
        const uint32_t* xp = reinterpret_cast<const uint32_t*>(x + (size_t)(rh * 64 + wq * 16 + g) * 512 + hg * 64 + 2 * t);
#pragma unroll
        for (int i = 0; i < 8; i++) { xr[i >> 1][(i & 1) * 2] = __ldg(xp + 4 * i); xr[i >> 1][(i & 1) * 2 + 1] = __ldg(xp + 8 * 256 + 4 * i); }
      }
      uint32_t A[8][4][4];
      const uint4* op = &g_o[rh][0][wq][0][lane];
      float acc[32];
#pragma unroll
      for (int i = 0; i < 32; i++) acc[i] = 0.f;
      add_frag(acc, xr, IDF);
#pragma unroll
      for (int p = -1; p < 4; p++) {
        if (p < 3) {
          mbar_wait(sb + SM_XF + (wg * 4 + p + 1) * 8);
          get_pair(A[2 * p + 2], A[2 * p + 3], xb + (p + 1) * 1024, op + (p + 1) * 1024, T);
          if (lane == 0) mbar_arrive(sb + SM_XE + (wg * 4 + p + 1) * 8);
        }
        if (p == 0 && wg == 1) bar_sync(4, 256);
        if (p >= 0) {
          if (p != 2) mbar_wait(sb + SM_FULL + (ST_WO + (p + 1) / 2) * 8);
          wg_fence();
#pragma unroll
          for (int c = 2 * p; c < 2 * p + 2; c++)
#pragma unroll
            for (int s = 0; s < 4; s++)
              wgmma_rs_n64(acc, A[c][s], DESC(((ST_WO + c / 3) % NSLOT) * SLOT + ((c % 3) * 4 + s) * 2048), 1);
        }
      }
      wg_commit();
      if (wg == 0) bar_arrive(4, 256);
      wg_wait<0>();
      if ((tid & 127) < 3) release(ST_WO + (tid & 127));
      TSTAMP(10);
      uint4* hp_ = &g_h[rh][hg][wq][0][lane];
      uint32_t hx = T;
#pragma unroll
      for (int s = 0; s < 4; s++) {
        const uint32_t h0 = pack2(acc[8 * s], acc[8 * s + 1]);
        st_rlx4(hp_ + s * 32, tg(h0, T), pack2(acc[8 * s + 2], acc[8 * s + 3]), pack2(acc[8 * s + 4], acc[8 * s + 5]), pack2(acc[8 * s + 6], acc[8 * s + 7]));
        hx |= (h0 & 1u) << (s + 1);
      }
      float s0 = 0.f, s1 = 0.f, q0 = 0.f, q1 = 0.f, q2 = 0.f, q3 = 0.f;
#pragma unroll
      for (int i = 0; i < 8; i++) {
        s0 += acc[4 * i] + acc[4 * i + 1]; s1 += acc[4 * i + 2] + acc[4 * i + 3];
        q0 = fmaf(acc[4 * i], acc[4 * i], q0); q2 = fmaf(acc[4 * i + 1], acc[4 * i + 1], q2);
        q1 = fmaf(acc[4 * i + 2], acc[4 * i + 2], q1); q3 = fmaf(acc[4 * i + 3], acc[4 * i + 3], q3);
      }
      q0 += q2; q1 += q3;
      {
        const bool up = t & 2;
        float s = (up ? s1 : s0) + __shfl_xor_sync(0xffffffffu, up ? s0 : s1, 2);
        float q = (up ? q1 : q0) + __shfl_xor_sync(0xffffffffu, up ? q0 : q1, 2);
        s += __shfl_xor_sync(0xffffffffu, s, 1);
        q += __shfl_xor_sync(0xffffffffu, q, 1);
        if (!(t & 1)) st_rlx2(&g_st[rh][hg][wq * 16 + g + (t >> 1) * 8], tg(__float_as_uint(s), T), __float_as_uint(q));
      }
      st_rlx1(&g_hx[rh][hg][wq][lane], hx);
    }
    bar_arrive(10 + wg, 160);
    TSTAMP(11);

    const int rh3 = 2 * rb3 + wg;
    uint32_t HH[11][4], PH[11][4];
    const uint4* pp = &g_hh[rh3][jf ^ 1][0][wq][lane];
    {
      uint32_t A[8][4][4];
      const uint4* hp_ = &g_h[rh3][0][wq][0][lane];
      uint4* hhp = &g_hh[rh3][jf][0][wq][lane];
      const uint32_t dg = (db & 0xFFFFu) | (256u << 16);
      uint32_t m0, m1;
      mbar_wait(sb + SM_XF + ((2 + wg) * 4) * 8);
      TSTAMP(0);
      {
        const uint2* sp = reinterpret_cast<const uint2*>(smem + SM_KV32 + wg * 4096) + 2 * t * 64 + wq * 16 + g;
        uint2 a0, a1, b0, b1;
        int it = 0;
#pragma unroll 1
        do {
          ld_rlx2(a0.x, a0.y, sp); ld_rlx2(a1.x, a1.y, sp + 64); ld_rlx2(b0.x, b0.y, sp + 8); ld_rlx2(b1.x, b1.y, sp + 72);
          sp = &g_st[rh3][2 * t][wq * 16 + g];
        } while (__any_sync(0xffffffffu, bad4(a0.x, a1.x, b0.x, b1.x, T)) && ++it < (1 << 18));
        float s0 = __uint_as_float(a0.x) + __uint_as_float(a1.x), q0 = __uint_as_float(a0.y) + __uint_as_float(a1.y);
        float s1 = __uint_as_float(b0.x) + __uint_as_float(b1.x), q1 = __uint_as_float(b0.y) + __uint_as_float(b1.y);
        s0 += __shfl_xor_sync(0xffffffffu, s0, 1); s1 += __shfl_xor_sync(0xffffffffu, s1, 1);
        q0 += __shfl_xor_sync(0xffffffffu, q0, 1); q1 += __shfl_xor_sync(0xffffffffu, q1, 1);
        s0 += __shfl_xor_sync(0xffffffffu, s0, 2); s1 += __shfl_xor_sync(0xffffffffu, s1, 2);
        q0 += __shfl_xor_sync(0xffffffffu, q0, 2); q1 += __shfl_xor_sync(0xffffffffu, q1, 2);
        s0 *= (1.f / 512.f); s1 *= (1.f / 512.f);
        r0 = rcp(fmaxf(q0 * (1.f / 512.f) - s0 * s0, 0.f) + 1e-5f);
        r1 = rcp(fmaxf(q1 * (1.f / 512.f) - s1 * s1, 0.f) + 1e-5f);
        m0 = pack2(s0, s0); m1 = pack2(s1, s1);
      }
      TSTAMP(12);
#define UOFF(u) ((((ST_GU + (u) / 3) % NSLOT) * SLOT + ((u) % 3) * 8192) >> 4)
#define UNIT_PRE(u)  do { if ((u) % 3 == 0) mbar_wait(sb + SM_FULL + (ST_GU + (u) / 3) * 8); } while (0)
#define UNIT_POST(u) do { wg_commit(); if ((u) % 3 == 1 && (u) > 3) { wg_wait<2>(); if (lead) release(ST_GU + (u) / 3 - 1); } } while (0)
      float acc[64];
      const int rz = blockIdx.y;
#pragma unroll
      for (int ps = 0; ps < 2; ps++) {
        wg_fence();
#pragma unroll
        for (int k = 0; k < 16; k++) {
          const int u = 16 * ps + k, c = k >> 1;
          if (ps == 0 && (k == 0 || k == 4 || k == 8)) {
#pragma unroll
            for (int p = (k == 0 ? 0 : (k == 4 ? 1 : 3)); p < (k == 0 ? 1 : (k == 4 ? 3 : 4)); p++) {
              if (p > 0) mbar_wait(sb + SM_XF + ((2 + wg) * 4 + p) * 8);
              get_pair(A[2 * p], A[2 * p + 1], xb + p * 1024, hp_ + p * 1024, T);
              if (lane == 0) {
                if (wg == 0) mbar_arrive(sb + SM_XE + (8 + p) * 8);
                else if (p > 0) release(ST_XC + p - 1);
              }
            }
          }
          if (ps == 0 && (k & 1) == 0) {
#pragma unroll
            for (int s = 0; s < 4; s++) {
              A[c][s][0] = hsub2(A[c][s][0], m0); A[c][s][1] = hsub2(A[c][s][1], m1);
              A[c][s][2] = hsub2(A[c][s][2], m0); A[c][s][3] = hsub2(A[c][s][3], m1);
            }
            wg_fence();
          }
          UNIT_PRE(u);
          wgmma_rs_n128(acc, A[c][(k & 1) * 2], dg + UOFF(u), k != 0 ? 1 : (ps ? rz : 0));
          wgmma_rs_n128(acc, A[c][(k & 1) * 2 + 1], dg + UOFF(u) + 128, 1);
          UNIT_POST(u);
        }
        wg_wait<0>();
        TSTAMP(22 + ps);
#pragma unroll
        for (int s = 0; s < 4; s++) {
          uint32_t (&hh)[4] = HH[4 + s];
          hh[0] = tg(pack2(acc[8 * s + 0] * acc[32 + 8 * s + 0], acc[8 * s + 1] * acc[32 + 8 * s + 1]), T);
          hh[1] = pack2(acc[8 * s + 2] * acc[32 + 8 * s + 2], acc[8 * s + 3] * acc[32 + 8 * s + 3]);
          hh[2] = pack2(acc[8 * s + 4] * acc[32 + 8 * s + 4], acc[8 * s + 5] * acc[32 + 8 * s + 5]);
          hh[3] = pack2(acc[8 * s + 6] * acc[32 + 8 * s + 6], acc[8 * s + 7] * acc[32 + 8 * s + 7]);
          st_rlx4(hhp + (4 * ps + s) * 128, hh[0], hh[1], hh[2], hh[3]);
        }
      }
      {
        float ag[24], au[24];
        const uint32_t* ph7 = reinterpret_cast<const uint32_t*>(&g_hh[rh3][jf ^ 1][7][wq][31]);
        uint32_t hv = 0;
        bar_sync(1 + wg, 128);
        wg_fence();
#pragma unroll
        for (int k = 0; k < 16; k++) {
          const int u = 32 + k, c = k >> 1;
          if (k == 6) {
#pragma unroll
            for (int s = 0; s < 4; s++) ld_rlx4(HH[s], hhp + s * 128);
          }
          if (k == 9) hv = ld_rlx1(ph7);
          if (k == 12) {
            int it = 0;
#pragma unroll 1
            while (((hv ^ T) & 1) && ++it < (1 << 18)) hv = ld_rlx1(ph7);
#pragma unroll
            for (int s = 0; s < 8; s++) ld_rlx4(PH[s], pp + s * 128);
          }
          UNIT_PRE(u);
          wgmma_rs_n48(ag, A[c][(k & 1) * 2], dg + UOFF(u), k != 0);
          wgmma_rs_n48(au, A[c][(k & 1) * 2], dg + UOFF(u) + 256, k != 0);
          wgmma_rs_n48(ag, A[c][(k & 1) * 2 + 1], dg + UOFF(u) + 128, 1);
          wgmma_rs_n48(au, A[c][(k & 1) * 2 + 1], dg + UOFF(u) + 256 + 128, 1);
          UNIT_POST(u);
        }
        wg_wait<0>();
        TSTAMP(13);
#pragma unroll
        for (int s = 0; s < 3; s++) {
          uint32_t (&hh)[4] = HH[8 + s];
          hh[0] = tg(pack2(ag[8 * s + 0] * au[8 * s + 0], ag[8 * s + 1] * au[8 * s + 1]), T);
          hh[1] = pack2(ag[8 * s + 2] * au[8 * s + 2], ag[8 * s + 3] * au[8 * s + 3]);
          hh[2] = pack2(ag[8 * s + 4] * au[8 * s + 4], ag[8 * s + 5] * au[8 * s + 5]);
          hh[3] = pack2(ag[8 * s + 6] * au[8 * s + 6], ag[8 * s + 7] * au[8 * s + 7]);
          st_rlx4(hhp + (8 + s) * 128, hh[0], hh[1], hh[2], hh[3]);
        }
      }
    }
    TSTAMP(14);

    {
      float acc[32], sum[32];
      uint32_t hr[4][4], hx = 0;
      const int m = jf >> 1, oc = (jf & 1) * 4 + m;
      uint4* outb = &g_part[rh3][(jf & 1) * 4][m][wq][0][lane];
      bar_arrive(8 + wg, 256);
#pragma unroll
      for (int i = 0; i < 32; i++) sum[i] = 0.f;
      int s0 = ST_D % NSLOT;
#pragma unroll 1
      for (int k = 0; k < 4; k++) {
        const int s1 = s0 + 1 == NSLOT ? 0 : s0 + 1;
        const uint32_t d0 = db + s0 * (SLOT >> 4), d1 = db + s1 * (SLOT >> 4);
        wg_wait<0>();
        if (k > 0) {
          uint4* p = outb + ((m + k) & 3) * 2048;
#pragma unroll
          for (int s = 0; s < 4; s++)
            st_rlx4(p + s * 32, tg(pack2(acc[8 * s], acc[8 * s + 1]), T), pack2(acc[8 * s + 2], acc[8 * s + 3]),
                    pack2(acc[8 * s + 4], acc[8 * s + 5]), pack2(acc[8 * s + 6], acc[8 * s + 7]));
          if (k == 1) bar_arrive(12, 320);
        }
        if (k == 3) TSTAMP(18);
        mbar_wait(sb + SM_FULL + (ST_D + 2 * k) * 8);
        mbar_wait(sb + SM_FULL + (ST_D + 2 * k + 1) * 8);
        wg_fence();
#pragma unroll
        for (int s = 0; s < 11; s++) wgmma_rs_n64(acc, HH[s], d0 + s * 128, s != 0);
        if (k == 0) {
          int it = 0;
#pragma unroll 1
          while (__any_sync(0xffffffffu, bad4(PH[0][0], PH[1][0], PH[2][0], PH[3][0], T) | bad4(PH[4][0], PH[5][0], PH[6][0], PH[7][0], T)) && ++it < (1 << 18)) {
#pragma unroll
            for (int s = 0; s < 8; s++) ld_rlx4(PH[s], pp + s * 128);
          }
          wg_fence();
        }
#pragma unroll
        for (int s = 0; s < 8; s++) wgmma_rs_n64(acc, PH[s], d1 + s * 128, 1);
        if (k == 0) {
          int it = 0;
#pragma unroll 1
          do {
#pragma unroll
            for (int s = 8; s < 11; s++) ld_rlx4(PH[s], pp + s * 128);
          } while (__any_sync(0xffffffffu, bad4(PH[8][0], PH[9][0], PH[10][0], T, T)) && ++it < (1 << 18));
          TSTAMP(20);
          wg_fence();
        }
#pragma unroll
        for (int s = 8; s < 11; s++) wgmma_rs_n64(acc, PH[s], d1 + s * 128, 1);
        wg_commit();
        s0 = s1 + 1 == NSLOT ? 0 : s1 + 1;
      }
      ld_chunk(hr, &g_h[rh3][oc][wq][0][lane]);
      hx = ld_rlx1(&g_hx[rh3][oc][wq][lane]);
#pragma unroll 1
      for (int q = 0; q < 3; q++) {
        uint32_t in[4][4];
        const uint4* sp = reinterpret_cast<const uint4*>(smem + ((ST_D % NSLOT) + wg) * SLOT) + q * 512 + wq * 128 + lane;
        mbar_wait_p(sb + SM_XF + (wg * 4 + q) * 8, 1);
        if (q == 0) TSTAMP(19); if (q == 1) TSTAMP(21); if (q == 2) TSTAMP(24);
        int it = 0;
#pragma unroll 1
        do {
#pragma unroll
          for (int s = 0; s < 4; s++)
            asm volatile("{\n.reg .b128 v;\nld.relaxed.gpu.b128 v, [%4];\nmov.b128 {%0,%1,%2,%3}, v;\n}"
                         : "=r"(in[s][0]), "=r"(in[s][1]), "=r"(in[s][2]), "=r"(in[s][3]) : "l"(sp + s * 32) : "memory");
          sp = &g_part[rh3][oc][(m - 1 - q) & 3][wq][0][lane];
        } while (__any_sync(0xffffffffu, bad4(in[0][0], in[1][0], in[2][0], in[3][0], T)) && ++it < (1 << 18));
#pragma unroll
        for (int i = 0; i < 16; i++) { sum[2 * i] += blo(in[i >> 2][i & 3]); sum[2 * i + 1] += bhi(in[i >> 2][i & 3]); }
      }
      wg_wait<0>();
      TSTAMP(15);
      {
        int it = 0;
#pragma unroll 1
        while (__any_sync(0xffffffffu, (hx ^ T) & 1) && ++it < (1 << 18)) hx = ld_rlx1(&g_hx[rh3][oc][wq][lane]);
      }
#pragma unroll
      for (int s = 0; s < 4; s++) hr[s][0] = (hr[s][0] & 0xFFFFFFFEu) | ((hx >> (s + 1)) & 1u);
#pragma unroll
      for (int i = 0; i < 16; i++) {
        const float r = (i & 1) ? r1 : r0;
        acc[2 * i]     = fmaf(acc[2 * i] + sum[2 * i], r, blo(hr[i >> 2][i & 3]));
        acc[2 * i + 1] = fmaf(acc[2 * i + 1] + sum[2 * i + 1], r, bhi(hr[i >> 2][i & 3]));
      }
      bar_sync(9 - wg, 256);
      const uint32_t ob = sb + ((ST_D - 1) % NSLOT) * SLOT + wg * 8192;
#pragma unroll
      for (int s = 0; s < 4; s++)
        stsm4(ob + lrow + (((2 * s + lhi) ^ lx) << 4), pack2(acc[8 * s + 0], acc[8 * s + 1]), pack2(acc[8 * s + 2], acc[8 * s + 3]),
              pack2(acc[8 * s + 4], acc[8 * s + 5]), pack2(acc[8 * s + 6], acc[8 * s + 7]));
      __syncwarp();
      {
        const int row = wq * 16 + (lane >> 3);
        __nv_bfloat16* op = out + (size_t)(rh3 * 64 + row) * 512 + oc * 64 + lx * 8;
#pragma unroll
        for (int i = 0; i < 4; i++) {
          uint4 v;
          asm volatile("ld.shared.v4.b32 {%0,%1,%2,%3}, [%4];" : "=r"(v.x), "=r"(v.y), "=r"(v.z), "=r"(v.w)
                       : "r"(ob + (row + i * 4) * 128 + ((lx ^ (((lane >> 3) + i * 4) & 7)) << 4)) : "memory");
          asm volatile("st.global.v4.b32 [%0], {%1,%2,%3,%4};" ::"l"(op + i * 2048), "r"(v.x), "r"(v.y), "r"(v.z), "r"(v.w) : "memory");
        }
      }
    }
    TSTAMP(16);
    asm volatile("barrier.cluster.arrive.relaxed.aligned;" ::: "memory");
    asm volatile("barrier.cluster.wait.aligned;" ::: "memory");
  } else {
    asm volatile("setmaxnreg.dec.sync.aligned.u32 24;");
    if (elect_one()) {
      if (warp == 8) {
#pragma unroll
        for (int k = 0; k < 9; k++) {
          const int s = k < 3 ? k : (k < 6 ? k + 3 : k - 3);
          const uint32_t bar = sb + SM_FULL + s * 8;
          mbar_init(bar, 1);
          mbar_expect_tx(bar, SLOT);
          if (s >= 3 && s < 6) tma2d(sb + s * SLOT, &maps.w, 512 + hg * 64, (s - 3) * 192, bar);
          else tma3d(sb + s * SLOT, &maps.x, 0, rb * 128 + (s >= 6 ? 64 : 0), 3 * (s % 3), bar);
        }
      } else if (warp == 9) {
        mbar_init(sb + SM_MISCB, 2);
        mbar_init(sb + SM_KVB, 1);
        mbar_expect_tx(sb + SM_KVB, 8704);
        mbar_expect_tx(sb + SM_MISCB, 2048);
        bulk_g2s(sb + SM_WPHI, wphi + hg * 1024, 2048, sb + SM_MISCB);
      } else if (warp == 10) {
        if ((sb & 0x3FFFF) != SM_BASE) __trap();
#pragma unroll 1
        for (int i = 0; i < 16; i++) {
          mbar_init(sb + SM_XF + i * 8, 1);
          mbar_expect_tx(sb + SM_XF + i * 8, (i == 8 || i == 12) ? 20480 : 16384);
          if (i < 12) mbar_init(sb + SM_XE + i * 8, 4);
        }
      } else {
        *reinterpret_cast<volatile unsigned*>(smem + SM_EPOCH) = atomicAdd(&g_start, 1u) / NCTA;
      }
      asm volatile("fence.mbarrier_init.release.cluster;" ::: "memory");
    }
    __syncwarp();
    if (warp != 11) bar_sync(0, 352);
    asm volatile("barrier.cluster.arrive.relaxed.aligned;" ::: "memory");
    if (warp == 8) {
      asm volatile("barrier.cluster.wait.aligned;" ::: "memory");
      if (elect_one()) {
        const CUtensorMap* mg = jf == 7 ? &maps.g7 : &maps.g;
        const CUtensorMap* mu = jf == 7 ? &maps.u7 : &maps.u;
        asm volatile("prefetch.tensormap [%0];" ::"l"(&maps.wo) : "memory");
        asm volatile("prefetch.tensormap [%0];" ::"l"(mg) : "memory");
        asm volatile("prefetch.tensormap [%0];" ::"l"(mu) : "memory");
        asm volatile("prefetch.tensormap [%0];" ::"l"(&maps.d) : "memory");
#pragma unroll 1
        for (int s = ST_WV; s < ST_XC; s++) {
          if (s == ST_SCR1) continue;
          mbar_wait(sb + SM_EMPTY + (s - 9) * 8);
          const uint32_t dst = sb + (s >= 18 ? s - 18 : s - 9) * SLOT, bar = sb + SM_FULL + s * 8;
          if (s < ST_WO) tma2d(dst, &maps.w, (s < ST_WQ ? 1024 : 0) + hg * 64, (s < ST_WQ ? s - ST_WV : s - ST_WQ) * 192, bar);
          else { mbar_wait(bar - 8); tma2d(dst, &maps.wo, hg * 64, (s - ST_WO) * 192, bar); }
        }
        const int jc = jf == 7 ? 0 : jf;
        int slot = (ST_GU + 1 - rank) % NSLOT;
#pragma unroll 1
        for (int s = ST_GU + 1 - rank; s < NSTAGE; s += 2) {
          mbar_wait(sb + SM_EMPTY + (s - 9) * 8);
          if (s > ST_GU && s < ST_GU + THR) mbar_wait(sb + SM_FULL + (s - 1) * 8);
          const uint32_t dst = sb + slot * SLOT, bar = sb + SM_FULL + s * 8;
          if (s < ST_D) {
#pragma unroll 1
            for (int i = 0; i < 3; i++) {
              const int u = (s - ST_GU) * 3 + i;
              tma3d_mc(dst + i * 8192, mg, (u >> 4) * 64, jc, (u & 15) * 32, bar);
              tma3d_mc(dst + i * 8192 + 4096, mu, (u >> 4) * 64, jc, (u & 15) * 32, bar);
            }
          } else {
            const int i = s - ST_D;
            tma2d_mc(dst, &maps.d, ((jf & 1) * 4 + (((jf >> 1) + 1 + (i >> 1)) & 3)) * 64, (jf ^ (i & 1)) * 176, bar);
          }
          slot += 2; if (slot >= NSLOT) slot -= NSLOT;
        }
      }
      __syncwarp();
    } else {
      asm volatile("barrier.cluster.wait.aligned;" ::: "memory");
      if (warp == 11) {
#pragma unroll
        for (int i = 0; i < 4; i++)
          reinterpret_cast<uint4*>(smem + SM_ONES)[lane + 32 * i] = make_uint4(0x3F803F80u, 0x3F803F80u, 0x3F803F80u, 0x3F803F80u);
        fence_async_smem();
        __syncwarp();
        if (lane == 0) mbar_arrive(sb + SM_MISCB);
      }
      mbar_wait(sb + SM_MISCB);
      const unsigned epoch = *reinterpret_cast<volatile unsigned*>(smem + SM_EPOCH);
      const uint32_t T = (epoch & 1) ^ 1;
      if (warp == 11) {
        reinterpret_cast<float4*>(&g_kv[hg][rb * 136])[lane] = make_float4(0.f, 0.f, 0.f, 0.f);
        if (lane < 2) reinterpret_cast<float4*>(&g_kv[hg][rb * 136])[32 + lane] = make_float4(0.f, 0.f, 0.f, 0.f);
        __syncwarp();
        if (elect_one()) asm volatile("red.release.gpu.global.add.u32 [%0], 1;" ::"l"(&g_kvcnt[hg * 32 + 1]) : "memory");
        mbar_wait(sb + SM_FULL + (ST_WK + 2) * 8);
        if (elect_one()) {
          asm volatile("cp.async.bulk.prefetch.L2.global [%0], 4096;" ::"l"((const char*)wo + blockIdx.x * 4096) : "memory");
          asm volatile("cp.async.bulk.prefetch.L2.global [%0], 11008;" ::"l"((const char*)wg_ + blockIdx.x * 11008) : "memory");
          asm volatile("cp.async.bulk.prefetch.L2.global [%0], 11008;" ::"l"((const char*)wu_ + blockIdx.x * 11008) : "memory");
          asm volatile("cp.async.bulk.prefetch.L2.global [%0], 11008;" ::"l"((const char*)wd_ + blockIdx.x * 11008) : "memory");
          mbar_wait(sb + SM_EMPTY + ST_SCR0 * 8);
          const unsigned target = (epoch + 1) * 16;
          unsigned v; int it = 0;
#pragma unroll 1
          do {
            asm volatile("ld.acquire.gpu.global.u32 %0, [%1];" : "=r"(v) : "l"(&g_kvcnt[hg * 32]) : "memory");
            if (++it > (1 << 18)) break;
          } while ((int)(v - target) < 0);
          TS2(0, 26);
          asm volatile("fence.proxy.async.global;" ::: "memory");
          bulk_g2s(sb + SM_KV32, &g_kv[hg][0], 8192, sb + SM_KVB);
          bulk_g2s(sb + SM_ONES, &g_kv[hg][2048], 512, sb + SM_KVB);
        }
        __syncwarp();
      } else {
        const int w = warp - 9;
        st_rlx4(reinterpret_cast<uint4*>(&g_st[2 * rb + w][hg][0]) + lane, T ^ 1, T ^ 1, T ^ 1, T ^ 1);
        if (lane < 8) st_rlx4(&g_o[2 * rb + w][hg][lane >> 1][3][30 + (lane & 1)], T ^ 1, T ^ 1, T ^ 1, T ^ 1);
        st_rlx4(&g_part[2 * rb3 + w][(jf & 1) * 4 + (lane >> 3)][jf >> 1][(lane >> 1) & 3][3][30 + (lane & 1)], T ^ 1, T ^ 1, T ^ 1, T ^ 1);
        if (lane < 8) st_rlx4(&g_hh[2 * rb3 + w][jf][7][lane >> 1][30 + (lane & 1)], T ^ 1, T ^ 1, T ^ 1, T ^ 1);
#pragma unroll 1
        for (int i = 0; i < 12; i++) st_rlx4(&g_hh[2 * rb3 + w][jf][8][0][lane] + i * 32, T ^ 1, T ^ 1, T ^ 1, T ^ 1);
        if (w == 0) {
          mbar_wait(sb + SM_FULL + (ST_WQ + 2) * 8);
          unsigned v; int it = 0;
#pragma unroll 1
          do {
            asm volatile("ld.acquire.gpu.global.u32 %0, [%1];" : "=r"(v) : "l"(&g_kvcnt[hg * 32 + 1]) : "memory");
          } while ((int)(v - (epoch + 1) * 16) < 0 && ++it < (1 << 18));
          asm volatile("fence.proxy.async.global;" ::: "memory");
        }
        bar_sync(6, 320);
        if (w == 0 && elect_one()) {
          asm volatile("cp.reduce.async.bulk.global.shared::cta.bulk_group.add.f32 [%0], [%1], 8704;"
                       ::"l"(&g_kv[hg][0]), "r"(sb + 2 * SLOT) : "memory");
          asm volatile("cp.async.bulk.commit_group;" ::: "memory");
          asm volatile("cp.async.bulk.wait_group 0;" ::: "memory");
          asm volatile("red.relaxed.gpu.global.add.u32 [%0], 1;" ::"l"(&g_kvcnt[hg * 32]) : "memory");
          TS2(0, 25);
        }
        __syncwarp();
        mbar_wait(sb + SM_KVB);
        if (w == 0) { mbar_wait(sb + SM_EMPTY + 11 * 8); mbar_wait(sb + SM_EMPTY + 12 * 8); mbar_wait(sb + SM_EMPTY + 13 * 8); }
#pragma unroll 1
        for (int ph = 0; ph < 2; ph++) {
          const int use = 2 * ph + w, r = ph ? 2 * rb3 + w : 2 * rb + w;
          const uint32_t* pw = ph ? reinterpret_cast<const uint32_t*>(&g_st[r][lane >> 2][(lane & 3) * 16 + 15])
                                  : reinterpret_cast<const uint32_t*>(&g_o[r][lane >> 2][lane & 3][3][31]);
          const char* src = reinterpret_cast<const char*>(ph ? &g_h[r][0][0][0][0] : &g_o[r][0][0][0][0]);
          const uint32_t bf = sb + SM_XF + use * 32, be = sb + SM_XE + (use - 1) * 32;
          bar_sync(10 + w, 160);
          int it = 0;
#pragma unroll 1
          for (bool miss = true; __any_sync(0xffffffffu, miss) && ++it < (1 << 18);) { if (miss) miss = (ld_rlx1(pw) ^ T) & 1; }
          if (elect_one()) {
            TS2(w, 27 + ph);
            if (use > 0) mbar_wait(be);
            if (ph) bulk_g2s(sb + SM_KV32 + w * 4096, &g_st[r][0][0], 4096, bf);
#pragma unroll
            for (int p = 0; p < 4; p++) {
              if (p > 0 && use > 0) mbar_wait(be + p * 8);
              bulk_g2s(sb + 2 * SLOT + p * 16384, src + p * 16384, 16384, bf + p * 8);
            }
          }
          __syncwarp();
        }
        {
          const int m = jf >> 1, oc = (jf & 1) * 4 + m;
          const uint32_t* pw = reinterpret_cast<const uint32_t*>(&g_part[2 * rb3 + w][oc][(m - 1 - (lane >> 2)) & 3][lane & 3][3][31]);
          bar_sync(12, 320);
          bool miss = lane < 12; int it = 0;
#pragma unroll 1
          for (int q = 0; q < 3; q++) {
#pragma unroll 1
            while ((__ballot_sync(0xffffffffu, miss) >> (4 * q) & 15) && ++it < (1 << 18)) { if (miss && (lane >> 2) <= q + 1) miss = (ld_rlx1(pw) ^ T) & 1; }
            if (elect_one()) {
              const uint32_t bar = sb + SM_XF + (w * 4 + q) * 8;
              mbar_expect_tx(bar, 8192);
              if (q == 2) TS2(w, 17);
              bulk_g2s(sb + ((ST_D % NSLOT) + w) * SLOT + q * 8192, &g_part[2 * rb3 + w][oc][(m - 1 - q) & 3][0][0][0], 8192, bar);
            }
            __syncwarp();
          }
        }
      }
    }
    asm volatile("barrier.cluster.arrive.relaxed.aligned;" ::: "memory");
    asm volatile("barrier.cluster.wait.aligned;" ::: "memory");
  }
}

typedef CUresult (*EncodeFn)(CUtensorMap*, CUtensorMapDataType, cuuint32_t, void*, const cuuint64_t*, const cuuint64_t*,
                             const cuuint32_t*, const cuuint32_t*, CUtensorMapInterleave, CUtensorMapSwizzle,
                             CUtensorMapL2promotion, CUtensorMapFloatOOBfill);

void encode(EncodeFn fn, CUtensorMap* m, const void* base, int rank, const cuuint64_t* dims, const cuuint64_t* strides,
            const cuuint32_t* box) {
  cuuint32_t es[3] = {1, 1, 1};
  fn(m, CU_TENSOR_MAP_DATA_TYPE_BFLOAT16, (cuuint32_t)rank, const_cast<void*>(base), dims, strides, box, es,
     CU_TENSOR_MAP_INTERLEAVE_NONE, CU_TENSOR_MAP_SWIZZLE_128B, CU_TENSOR_MAP_L2_PROMOTION_L2_256B,
     CU_TENSOR_MAP_FLOAT_OOB_FILL_NONE);
}

}

extern "C" void kernel_launch(void* const* d_in, const int* in_sizes, int n_in, void* d_out, int out_size) {
  (void)in_sizes; (void)n_in; (void)out_size;
  const __nv_bfloat16* x    = (const __nv_bfloat16*)d_in[0];
  const __nv_bfloat16* wqkv = (const __nv_bfloat16*)d_in[1];
  const __nv_bfloat16* wphi = (const __nv_bfloat16*)d_in[2];
  const __nv_bfloat16* wo   = (const __nv_bfloat16*)d_in[3];
  const __nv_bfloat16* wg   = (const __nv_bfloat16*)d_in[5];
  const __nv_bfloat16* wu   = (const __nv_bfloat16*)d_in[6];
  const __nv_bfloat16* wd   = (const __nv_bfloat16*)d_in[7];

  static EncodeFn fn = nullptr;
  if (!fn) {
    void* p = nullptr;
    cudaDriverEntryPointQueryResult qr;
    cudaGetDriverEntryPoint("cuTensorMapEncodeTiled", &p, cudaEnableDefault, &qr);
    fn = (EncodeFn)p;
    cudaFuncSetAttribute(fused_kernel, cudaFuncAttributeMaxDynamicSharedMemorySize, SM_TOTAL);
  }
  Maps maps;
  {
    cuuint64_t d[3] = {64, 2048, 8}, s[2] = {1024, 128}; cuuint32_t b[3] = {64, 64, 3};
    encode(fn, &maps.x, x, 3, d, s, b);
  }
  {
    cuuint64_t d[2] = {1536, 512}, s[1] = {3072}; cuuint32_t b[2] = {64, 192};
    encode(fn, &maps.w, wqkv, 2, d, s, b);
  }
  {
    cuuint64_t d[2] = {512, 512}, s[1] = {1024}; cuuint32_t b[2] = {64, 192};
    encode(fn, &maps.wo, wo, 2, d, s, b);
  }
  {
    cuuint64_t d[3] = {176, 7, 512}, d7[3] = {144, 1, 512}, s[2] = {352, 2752}; cuuint32_t b[3] = {64, 1, 32};
    encode(fn, &maps.g, wg, 3, d, s, b);
    encode(fn, &maps.u, wu, 3, d, s, b);
    encode(fn, &maps.g7, wg + 1232, 3, d7, s, b);
    encode(fn, &maps.u7, wu + 1232, 3, d7, s, b);
  }
  {
    cuuint64_t d[2] = {512, 1376}, s[1] = {1024}; cuuint32_t b[2] = {64, 176};
    encode(fn, &maps.d, wd, 2, d, s, b);
  }
  fused_kernel<<<NCTA, 384, SM_TOTAL>>>(maps, x, wphi, wo, wg, wu, wd, (__nv_bfloat16*)d_out);
}
```

```cpp
#include <cuda_runtime.h>
#include <cuda_bf16.h>
#include <cuda.h>
#include <stdint.h>

#define PROF 0

#define SAFE_WAIT 0
#define OPRIO 1
#define THR 6

namespace {

constexpr int NCTA   = 128;
constexpr int SLOT   = 24576;
constexpr int NSLOT  = 9;
constexpr int NSTAGE = 47;

constexpr int ST_X0   = 0;
constexpr int ST_WK   = 3;
constexpr int ST_X1   = 6;
constexpr int ST_SCR0 = 9;
constexpr int ST_WV   = 10;
constexpr int ST_SCR1 = 13;
constexpr int ST_WQ   = 14;
constexpr int ST_WO   = 17;
constexpr int ST_XC   = 20;
constexpr int ST_GU   = 23;
constexpr int ST_D    = 39;

__host__ __device__ constexpr int st_empty_cnt(int d) {
  return ((d < 3 || (d >= 6 && d < 9) || (d >= ST_XC && d < ST_GU)) ? 4 : 2) * (d + 9 >= ST_GU ? 2 : 1);
}

constexpr uint32_t SM_BASE = 1024;
constexpr int SM_ONES = NSLOT * SLOT;
constexpr int SM_WPHI = SM_ONES + 2048;
constexpr int SM_KVS  = SM_WPHI + 2048;
constexpr int SM_KV32 = 4 * SLOT + 16384;
constexpr int SM_BAR  = SM_KVS + 6144;
constexpr int SM_FULL  = SM_BAR;
constexpr int SM_EMPTY = SM_BAR + NSTAGE * 8;
constexpr int SM_MISCB = SM_BAR + 2 * NSTAGE * 8;
constexpr int SM_KVB   = SM_MISCB + 8;
constexpr int SM_EPOCH = SM_KVB + 8;
constexpr int SM_XF    = SM_EPOCH + 8;
constexpr int SM_XE    = SM_XF + 16 * 8;
constexpr int SM_TOTAL = SM_BAR + 1024;

static_assert(SM_TOTAL == 232448 && SM_XE + 12 * 8 <= SM_TOTAL, "smem budget");

struct Maps { CUtensorMap x, w, wo, g, u, g7, u7, d; };

__device__ uint4    g_o[32][8][4][4][32];
__device__ uint4    g_h[32][8][4][4][32];
__device__ uint32_t g_hx[32][8][4][32];
__device__ uint2    g_st[32][8][64];
__device__ uint4    g_hh[32][8][11][4][32];
__device__ uint4    g_part[32][8][4][4][4][32];
__device__ __align__(128) float g_kv[8][2048 + 128];
__device__ unsigned g_kvcnt[8 * 32];
__device__ unsigned g_start;

__device__ __forceinline__ uint32_t smem_u32(const void* p) { return (uint32_t)__cvta_generic_to_shared(p); }
__device__ __forceinline__ void mbar_init(uint32_t bar, int cnt) {
  asm volatile("mbarrier.init.shared::cta.b64 [%0], %1;" ::"r"(bar), "r"(cnt) : "memory");
}
__device__ __forceinline__ void mbar_expect_tx(uint32_t bar, uint32_t bytes) {
  asm volatile("mbarrier.arrive.expect_tx.shared::cta.b64 _, [%0], %1;" ::"r"(bar), "r"(bytes) : "memory");
}
__device__ __forceinline__ void mbar_arrive(uint32_t bar) {
  asm volatile("mbarrier.arrive.shared::cta.b64 _, [%0];" ::"r"(bar) : "memory");
}
__device__ __forceinline__ void mbar_arrive_cluster(uint32_t bar, uint32_t rank) {
  asm volatile("{\n.reg .b32 ra;\nmapa.shared::cluster.u32 ra, %0, %1;\n"
               "mbarrier.arrive.shared::cluster.b64 _, [ra];\n}" ::"r"(bar), "r"(rank) : "memory");
}
__device__ __forceinline__ void mbar_wait_p(uint32_t bar, uint32_t parity) {
  asm volatile("{\n.reg .pred p;\nW: mbarrier.try_wait.parity.shared::cta.b64 p, [%0], %1;\n@!p bra W;\n}" ::"r"(bar), "r"(parity) : "memory");
}
__device__ __forceinline__ void mbar_wait(uint32_t bar) { mbar_wait_p(bar, 0); }
__device__ __forceinline__ bool elect_one() {
  uint32_t p;
  asm volatile("{\n.reg .pred P;\nelect.sync _|P, 0xffffffff;\nselp.u32 %0, 1, 0, P;\n}" : "=r"(p));
  return p != 0;
}
__device__ __forceinline__ void bar_sync(int id, int n)   { asm volatile("bar.sync %0, %1;" ::"r"(id), "r"(n) : "memory"); }
__device__ __forceinline__ void bar_arrive(int id, int n) { asm volatile("bar.arrive %0, %1;" ::"r"(id), "r"(n) : "memory"); }
__device__ __forceinline__ void fence_async_smem() { asm volatile("fence.proxy.async.shared::cta;" ::: "memory"); }
__device__ __forceinline__ void wg_fence()  { asm volatile("wgmma.fence.sync.aligned;" ::: "memory"); }
__device__ __forceinline__ void wg_commit() { asm volatile("wgmma.commit_group.sync.aligned;" ::: "memory"); }
template <int N> __device__ __forceinline__ void wg_wait() { asm volatile("wgmma.wait_group.sync.aligned %0;" ::"n"(N) : "memory"); }
#define DESC(off) (db + ((uint32_t)(off) >> 4))
__device__ __forceinline__ void tma2d(uint32_t dst, const CUtensorMap* m, int c0, int c1, uint32_t bar) {
  asm volatile("cp.async.bulk.tensor.2d.shared::cluster.global.mbarrier::complete_tx::bytes [%0], [%1, {%3, %4}], [%2];"
               ::"r"(dst), "l"(m), "r"(bar), "r"(c0), "r"(c1) : "memory");
}
__device__ __forceinline__ void tma2d_mc(uint32_t dst, const CUtensorMap* m, int c0, int c1, uint32_t bar) {
  asm volatile("cp.async.bulk.tensor.2d.shared::cluster.global.mbarrier::complete_tx::bytes.multicast::cluster [%0], [%1, {%3, %4}], [%2], %5;"
               ::"r"(dst), "l"(m), "r"(bar), "r"(c0), "r"(c1), "h"((uint16_t)3) : "memory");
}
__device__ __forceinline__ void tma3d(uint32_t dst, const CUtensorMap* m, int c0, int c1, int c2, uint32_t bar) {
  asm volatile("cp.async.bulk.tensor.3d.shared::cluster.global.mbarrier::complete_tx::bytes [%0], [%1, {%3, %4, %5}], [%2];"
               ::"r"(dst), "l"(m), "r"(bar), "r"(c0), "r"(c1), "r"(c2) : "memory");
}
__device__ __forceinline__ void tma3d_mc(uint32_t dst, const CUtensorMap* m, int c0, int c1, int c2, uint32_t bar) {
  asm volatile("cp.async.bulk.tensor.3d.shared::cluster.global.mbarrier::complete_tx::bytes.multicast::cluster [%0], [%1, {%3, %4, %5}], [%2], %6;"
               ::"r"(dst), "l"(m), "r"(bar), "r"(c0), "r"(c1), "r"(c2), "h"((uint16_t)3) : "memory");
}
__device__ __forceinline__ void ldsm4(uint32_t (&r)[4], uint32_t addr) {
  asm volatile("ldmatrix.sync.aligned.m8n8.x4.shared.b16 {%0,%1,%2,%3}, [%4];"
               : "=r"(r[0]), "=r"(r[1]), "=r"(r[2]), "=r"(r[3]) : "r"(addr) : "memory");
}
__device__ __forceinline__ void ldsm4t(uint32_t (&r)[4], uint32_t addr) {
  asm volatile("ldmatrix.sync.aligned.m8n8.x4.trans.shared.b16 {%0,%1,%2,%3}, [%4];"
               : "=r"(r[0]), "=r"(r[1]), "=r"(r[2]), "=r"(r[3]) : "r"(addr) : "memory");
}
__device__ __forceinline__ void stsm4(uint32_t addr, uint32_t r0, uint32_t r1, uint32_t r2, uint32_t r3) {
  asm volatile("stmatrix.sync.aligned.m8n8.x4.shared.b16 [%0], {%1,%2,%3,%4};"
               ::"r"(addr), "r"(r0), "r"(r1), "r"(r2), "r"(r3) : "memory");
}
__device__ __forceinline__ void mma16816(float (&c)[4], const uint32_t (&a)[4], uint32_t b0, uint32_t b1) {
  asm volatile("mma.sync.aligned.m16n8k16.row.col.f32.bf16.bf16.f32 {%0,%1,%2,%3},{%4,%5,%6,%7},{%8,%9},{%0,%1,%2,%3};"
               : "+f"(c[0]), "+f"(c[1]), "+f"(c[2]), "+f"(c[3])
               : "r"(a[0]), "r"(a[1]), "r"(a[2]), "r"(a[3]), "r"(b0), "r"(b1));
}
__device__ __forceinline__ void add_frag(float (&c)[32], const uint32_t (&a)[4][4], uint32_t id) {
#pragma unroll
  for (int i = 0; i < 8; i++)
    asm volatile("mma.sync.aligned.m16n8k8.row.col.f32.bf16.bf16.f32 {%0,%1,%2,%3},{%4,%5},{%6},{%0,%1,%2,%3};"
                 : "+f"(c[4 * i]), "+f"(c[4 * i + 1]), "+f"(c[4 * i + 2]), "+f"(c[4 * i + 3])
                 : "r"(a[i >> 1][(i & 1) * 2]), "r"(a[i >> 1][(i & 1) * 2 + 1]), "r"(id));
}
__device__ __forceinline__ uint32_t pack2(float lo, float hi) {
  uint32_t r; asm("cvt.rn.bf16x2.f32 %0, %1, %2;" : "=r"(r) : "f"(hi), "f"(lo)); return r;
}
__device__ __forceinline__ float blo(uint32_t w) { return __uint_as_float(w << 16); }
__device__ __forceinline__ float bhi(uint32_t w) { return __uint_as_float(w & 0xFFFF0000u); }
__device__ __forceinline__ uint32_t hsub2(uint32_t a, uint32_t b) { uint32_t r; asm("sub.rn.bf16x2 %0, %1, %2;" : "=r"(r) : "r"(a), "r"(b)); return r; }
__device__ __forceinline__ uint32_t hmax2(uint32_t a, uint32_t b) { uint32_t r; asm("max.bf16x2 %0, %1, %2;" : "=r"(r) : "r"(a), "r"(b)); return r; }
__device__ __forceinline__ uint32_t hmin2(uint32_t a, uint32_t b) { uint32_t r; asm("min.bf16x2 %0, %1, %2;" : "=r"(r) : "r"(a), "r"(b)); return r; }
__device__ __forceinline__ float ex2(float x) { float r; asm("ex2.approx.ftz.f32 %0, %1;" : "=f"(r) : "f"(x)); return r; }
__device__ __forceinline__ float rcp(float x) { float r; asm("rcp.approx.ftz.f32 %0, %1;" : "=f"(r) : "f"(x)); return r; }
__device__ __forceinline__ void ld_rlx4(uint32_t (&r)[4], const uint4* p) {
  asm volatile("{\n.reg .b128 v;\nld.relaxed.gpu.global.b128 v, [%4];\nmov.b128 {%0,%1,%2,%3}, v;\n}"
               : "=r"(r[0]), "=r"(r[1]), "=r"(r[2]), "=r"(r[3]) : "l"(p) : "memory");
}
__device__ __forceinline__ void st_rlx4(uint4* p, uint32_t a, uint32_t b, uint32_t c, uint32_t d) {
  asm volatile("st.relaxed.gpu.global.v4.b32 [%0], {%1,%2,%3,%4};" ::"l"(p), "r"(a), "r"(b), "r"(c), "r"(d) : "memory");
}
__device__ __forceinline__ void st_rlx2(uint2* p, uint32_t a, uint32_t b) {
  asm volatile("{\n.reg .b64 v;\nmov.b64 v, {%1,%2};\nst.relaxed.gpu.global.b64 [%0], v;\n}" ::"l"(p), "r"(a), "r"(b) : "memory");
}
__device__ __forceinline__ uint32_t ld_rlx1(const uint32_t* p) {
  uint32_t r; asm volatile("ld.relaxed.gpu.global.b32 %0, [%1];" : "=r"(r) : "l"(p) : "memory"); return r;
}
__device__ __forceinline__ void st_rlx1(uint32_t* p, uint32_t a) {
  asm volatile("st.relaxed.gpu.global.b32 [%0], %1;" ::"l"(p), "r"(a) : "memory");
}
__device__ __forceinline__ void ld_rlx2(uint32_t& a, uint32_t& b, const uint2* p) {
  asm volatile("{\n.reg .b64 v;\nld.relaxed.gpu.b64 v, [%2];\nmov.b64 {%0,%1}, v;\n}" : "=r"(a), "=r"(b) : "l"(p) : "memory");
}
__device__ __forceinline__ void bulk_g2s(uint32_t dst, const void* src, uint32_t bytes, uint32_t bar) {
  asm volatile("cp.async.bulk.shared::cluster.global.mbarrier::complete_tx::bytes [%0], [%1], %2, [%3];"
               ::"r"(dst), "l"(src), "r"(bytes), "r"(bar) : "memory");
}
__device__ __forceinline__ uint32_t tg(uint32_t w, uint32_t T) { return (w & 0xFFFFFFFEu) | T; }
__device__ __forceinline__ uint32_t bad4(uint32_t a, uint32_t b, uint32_t c, uint32_t d, uint32_t T) {
  uint32_t u, v;
  asm("lop3.b32 %0, %1, %2, %3, 0x7E;" : "=r"(u) : "r"(a), "r"(b), "r"(T));
  asm("lop3.b32 %0, %1, %2, %3, 0x7E;" : "=r"(v) : "r"(c), "r"(d), "r"(T));
  asm("lop3.b32 %0, %1, %2, 1, 0xA8;" : "=r"(u) : "r"(u), "r"(v));
  return u;
}

__device__ __forceinline__ void ld_chunk(uint32_t (&a)[4][4], const uint4* p) {
#pragma unroll
  for (int s = 0; s < 4; s++) ld_rlx4(a[s], p + s * 32);
}
__device__ __forceinline__ void get_pair(uint32_t (&a)[4][4], uint32_t (&b)[4][4], const uint4* sp, const uint4* gp, uint32_t T) {
  int it = 0;
#pragma unroll 1
  do {
#pragma unroll
    for (int s = 0; s < 8; s++) {
      uint32_t (&r)[4] = s < 4 ? a[s & 3] : b[s & 3];
      asm volatile("{\n.reg .b128 v;\nld.relaxed.gpu.b128 v, [%4];\nmov.b128 {%0,%1,%2,%3}, v;\n}"
                   : "=r"(r[0]), "=r"(r[1]), "=r"(r[2]), "=r"(r[3]) : "l"(sp + (s >> 2) * 512 + (s & 3) * 32) : "memory");
    }
    sp = gp;
  } while (__any_sync(0xffffffffu, bad4(a[0][0], a[1][0], a[2][0], a[3][0], T) | bad4(b[0][0], b[1][0], b[2][0], b[3][0], T)) && ++it < (1 << 18));
}

__device__ __forceinline__ void wgmma_rs_n48(float (&d)[24], const uint32_t (&a)[4], uint32_t descB, int scaleD) {
  asm volatile("{\n.reg .pred p;\n.reg .b64 db;\nsetp.ne.b32 p, %29, 0;\nmov.b64 db, {%28, 0x40000040};\n"
    "wgmma.mma_async.sync.aligned.m64n48k16.f32.bf16.bf16 {%0,%1,%2,%3,%4,%5,%6,%7,%8,%9,%10,%11,%12,%13,%14,%15,%16,%17,%18,%19,%20,%21,%22,%23}, {%24,%25,%26,%27}, db, p, 1, 1, 1;\n}\n"
    : "+f"(d[0]),"+f"(d[1]),"+f"(d[2]),"+f"(d[3]),"+f"(d[4]),"+f"(d[5]),"+f"(d[6]),"+f"(d[7]),"+f"(d[8]),"+f"(d[9]),"+f"(d[10]),"+f"(d[11]),"+f"(d[12]),"+f"(d[13]),"+f"(d[14]),"+f"(d[15]),"+f"(d[16]),"+f"(d[17]),"+f"(d[18]),"+f"(d[19]),"+f"(d[20]),"+f"(d[21]),"+f"(d[22]),"+f"(d[23])
    : "r"(a[0]), "r"(a[1]), "r"(a[2]), "r"(a[3]), "r"(descB), "r"(scaleD));
}
__device__ __forceinline__ void wgmma_rs_n64(float (&d)[32], const uint32_t (&a)[4], uint32_t descB, int scaleD) {
  asm volatile("{\n.reg .pred p;\n.reg .b64 db;\nsetp.ne.b32 p, %37, 0;\nmov.b64 db, {%36, 0x40000040};\n"
    "wgmma.mma_async.sync.aligned.m64n64k16.f32.bf16.bf16 {%0,%1,%2,%3,%4,%5,%6,%7,%8,%9,%10,%11,%12,%13,%14,%15,%16,%17,%18,%19,%20,%21,%22,%23,%24,%25,%26,%27,%28,%29,%30,%31}, {%32,%33,%34,%35}, db, p, 1, 1, 1;\n}\n"
    : "+f"(d[0]),"+f"(d[1]),"+f"(d[2]),"+f"(d[3]),"+f"(d[4]),"+f"(d[5]),"+f"(d[6]),"+f"(d[7]),"+f"(d[8]),"+f"(d[9]),"+f"(d[10]),"+f"(d[11]),"+f"(d[12]),"+f"(d[13]),"+f"(d[14]),"+f"(d[15]),"+f"(d[16]),"+f"(d[17]),"+f"(d[18]),"+f"(d[19]),"+f"(d[20]),"+f"(d[21]),"+f"(d[22]),"+f"(d[23]),"+f"(d[24]),"+f"(d[25]),"+f"(d[26]),"+f"(d[27]),"+f"(d[28]),"+f"(d[29]),"+f"(d[30]),"+f"(d[31])
    : "r"(a[0]), "r"(a[1]), "r"(a[2]), "r"(a[3]), "r"(descB), "r"(scaleD));
}
__device__ __forceinline__ void wgmma_rs_n128(float (&d)[64], const uint32_t (&a)[4], uint32_t descB, int scaleD) {
  asm volatile("{\n.reg .pred p;\n.reg .b64 db;\nsetp.ne.b32 p, %69, 0;\nmov.b64 db, {%68, 0x40000040};\n"
    "wgmma.mma_async.sync.aligned.m64n128k16.f32.bf16.bf16 {%0,%1,%2,%3,%4,%5,%6,%7,%8,%9,%10,%11,%12,%13,%14,%15,%16,%17,%18,%19,%20,%21,%22,%23,%24,%25,%26,%27,%28,%29,%30,%31,%32,%33,%34,%35,%36,%37,%38,%39,%40,%41,%42,%43,%44,%45,%46,%47,%48,%49,%50,%51,%52,%53,%54,%55,%56,%57,%58,%59,%60,%61,%62,%63}, {%64,%65,%66,%67}, db, p, 1, 1, 1;\n}\n"
    : "+f"(d[0]),"+f"(d[1]),"+f"(d[2]),"+f"(d[3]),"+f"(d[4]),"+f"(d[5]),"+f"(d[6]),"+f"(d[7]),"+f"(d[8]),"+f"(d[9]),"+f"(d[10]),"+f"(d[11]),"+f"(d[12]),"+f"(d[13]),"+f"(d[14]),"+f"(d[15]),"+f"(d[16]),"+f"(d[17]),"+f"(d[18]),"+f"(d[19]),"+f"(d[20]),"+f"(d[21]),"+f"(d[22]),"+f"(d[23]),"+f"(d[24]),"+f"(d[25]),"+f"(d[26]),"+f"(d[27]),"+f"(d[28]),"+f"(d[29]),"+f"(d[30]),"+f"(d[31]),"+f"(d[32]),"+f"(d[33]),"+f"(d[34]),"+f"(d[35]),"+f"(d[36]),"+f"(d[37]),"+f"(d[38]),"+f"(d[39]),"+f"(d[40]),"+f"(d[41]),"+f"(d[42]),"+f"(d[43]),"+f"(d[44]),"+f"(d[45]),"+f"(d[46]),"+f"(d[47]),"+f"(d[48]),"+f"(d[49]),"+f"(d[50]),"+f"(d[51]),"+f"(d[52]),"+f"(d[53]),"+f"(d[54]),"+f"(d[55]),"+f"(d[56]),"+f"(d[57]),"+f"(d[58]),"+f"(d[59]),"+f"(d[60]),"+f"(d[61]),"+f"(d[62]),"+f"(d[63])
    : "r"(a[0]), "r"(a[1]), "r"(a[2]), "r"(a[3]), "r"(descB), "r"(scaleD));
}
__device__ __forceinline__ void wgmma_ss_n72_t11(float (&d)[36], uint32_t descA, uint32_t descB, int scaleD) {
  asm volatile("{\n.reg .pred p;\n.reg .b64 da, db;\nsetp.ne.b32 p, %38, 0;\nmov.b64 da, {%36, 0x40000040};\nmov.b64 db, {%37, 0x40000040};\n"
    "wgmma.mma_async.sync.aligned.m64n72k16.f32.bf16.bf16 {%0,%1,%2,%3,%4,%5,%6,%7,%8,%9,%10,%11,%12,%13,%14,%15,%16,%17,%18,%19,%20,%21,%22,%23,%24,%25,%26,%27,%28,%29,%30,%31,%32,%33,%34,%35}, da, db, p, 1, 1, 1, 1;\n}\n"
    : "+f"(d[0]),"+f"(d[1]),"+f"(d[2]),"+f"(d[3]),"+f"(d[4]),"+f"(d[5]),"+f"(d[6]),"+f"(d[7]),"+f"(d[8]),"+f"(d[9]),"+f"(d[10]),"+f"(d[11]),"+f"(d[12]),"+f"(d[13]),"+f"(d[14]),"+f"(d[15]),"+f"(d[16]),"+f"(d[17]),"+f"(d[18]),"+f"(d[19]),"+f"(d[20]),"+f"(d[21]),"+f"(d[22]),"+f"(d[23]),"+f"(d[24]),"+f"(d[25]),"+f"(d[26]),"+f"(d[27]),"+f"(d[28]),"+f"(d[29]),"+f"(d[30]),"+f"(d[31]),"+f"(d[32]),"+f"(d[33]),"+f"(d[34]),"+f"(d[35])
    : "r"(descA), "r"(descB), "r"(scaleD));
}

#define TSTAMP(i) do {} while (0)
#define TS2(w, i) do {} while (0)

constexpr float LOG2E = 1.4426950408889634f;

__device__ __forceinline__ void feat_exp(const uint32_t (&P)[4], float (&e)[16]) {
  uint32_t a = hmax2(P[0], P[2]), b = hmax2(P[1], P[3]);
  uint32_t mx = hmax2(__byte_perm(a, b, 0x5410), __byte_perm(a, b, 0x7632));
  a = hmin2(P[0], P[2]); b = hmin2(P[1], P[3]);
  uint32_t mn = hmin2(__byte_perm(a, b, 0x5410), __byte_perm(a, b, 0x7632));
  mx = hmax2(mx, __shfl_xor_sync(0xffffffffu, mx, 1));
  mn = hmin2(mn, __shfl_xor_sync(0xffffffffu, mn, 1));
  mx = hmax2(mx, __shfl_xor_sync(0xffffffffu, mx, 2));
  mn = hmin2(mn, __shfl_xor_sync(0xffffffffu, mn, 2));
  float mx0 = -blo(mx) * LOG2E, mx1 = -bhi(mx) * LOG2E, mn0 = blo(mn) * LOG2E, mn1 = bhi(mn) * LOG2E;
  float v[8] = {blo(P[0]), bhi(P[0]), blo(P[1]), bhi(P[1]), blo(P[2]), bhi(P[2]), blo(P[3]), bhi(P[3])};
#pragma unroll
  for (int i = 0; i < 8; i++) {
    bool r1 = (i >> 1) & 1;
    e[i]     = ex2(fmaf(v[i],  LOG2E, r1 ? mx1 : mx0));
    e[8 + i] = ex2(fmaf(v[i], -LOG2E, r1 ? mn1 : mn0));
  }
}

__global__ void __cluster_dims__(2, 1, 1) __launch_bounds__(384, 1)
fused_kernel(const __grid_constant__ Maps maps, const __nv_bfloat16* __restrict__ x, const __nv_bfloat16* __restrict__ wphi,
             const __nv_bfloat16* __restrict__ wo, const __nv_bfloat16* __restrict__ wg_, const __nv_bfloat16* __restrict__ wu_,
             const __nv_bfloat16* __restrict__ wd_, __nv_bfloat16* __restrict__ out) {
  extern __shared__ __align__(1024) unsigned char smem[];
  const uint32_t sb = smem_u32(smem);
  const int tid = threadIdx.x, lane = tid & 31;
  const int warp = __shfl_sync(0xffffffffu, tid >> 5, 0);
  const uint32_t rank = blockIdx.x & 1;
  const int cl = blockIdx.x >> 1;
  int quad, qi;
  if (cl < 4) { quad = 15; qi = cl; }
  else if (cl < 36) { quad = (cl - 4) & 7; qi = (cl - 4) >> 3; }
  else { qi = (cl - 36) / 7; quad = 8 + (cl - 36) - 7 * qi; }
  const int rb = quad, hg = 2 * qi + rank;
  const int rb3 = (quad & ~1) + rank, jf = 4 * (quad & 1) + qi;

  if (warp < 8) {
    asm volatile("setmaxnreg.inc.sync.aligned.u32 240;");
    if (elect_one()) {
#pragma unroll 1
      for (int d = warp; d + 9 < NSTAGE; d += 8) {
        mbar_init(sb + SM_EMPTY + d * 8, st_empty_cnt(d));
        {
          mbar_init(sb + SM_FULL + (d + 9) * 8, 1);
          mbar_expect_tx(sb + SM_FULL + (d + 9) * 8, d + 9 >= ST_D ? 22528 : SLOT);
        }
      }
      asm volatile("fence.mbarrier_init.release.cluster;" ::: "memory");
    }
    __syncwarp();
    bar_sync(0, 352);
    asm volatile("barrier.cluster.arrive.relaxed.aligned;" ::: "memory");
    const int wg = warp >> 2, wq = warp & 3, g = lane >> 2, t = lane & 3;
    const bool lead = (tid & 127) == 0;
    constexpr uint32_t db = (SM_BASE >> 4) | (512u << 16);
    auto release = [&](int d) {
      const int s = d + NSLOT;
      mbar_arrive_cluster(sb + SM_EMPTY + d * 8, s >= ST_GU ? (uint32_t)(s & 1) : rank);
    };
    const uint32_t lrow = (uint32_t)(wq * 16 + (lane & 7) + ((lane >> 3) & 1) * 8) * 128;
    const uint32_t lx = lane & 7, lhi = lane >> 4;
    if (wg == 1) bar_arrive(4, 256);

    float r0, r1;
    uint32_t E[4][8];
    uint32_t T = 0;
    {
      uint32_t A[32][4];
      const int sx = wg ? ST_X1 : ST_X0;
      {
        const uint32_t base = sb + sx * SLOT + lrow, baseb = sb + sx * SLOT + (wq * 16 + lx + lhi * 8) * 128;
        float cs[2][4], c0[2][4], c1[2][4];
#pragma unroll
        for (int i = 0; i < 4; i++) { cs[0][i] = cs[1][i] = c0[0][i] = c0[1][i] = c1[0][i] = c1[1][i] = 0.f; }
        uint32_t bt[2][4][4];
#pragma unroll
        for (int c = -1; c < 8; c++) {
          if (c < 7) {
            const int n = c + 1;
            if (n % 3 == 0) mbar_wait(sb + SM_FULL + (sx + n / 3) * 8);
#pragma unroll
            for (int k = 0; k < 4; k++) {
              ldsm4(A[4 * n + k], base + n * 8192 + (((2 * k + lhi) ^ lx) << 4));
              ldsm4(bt[n & 1][k], baseb + n * 8192 + (((2 * k + ((lane >> 3) & 1)) ^ lx) << 4));
            }
          }
          if (c >= 0) {
#pragma unroll
            for (int k = 0; k < 4; k++) {
              const uint32_t (&f)[4] = A[4 * c + k];
              mma16816(cs[k & 1], f, 0x3F803F80u, 0x3F803F80u);
              mma16816(c0[k & 1], f, bt[c & 1][k][0], bt[c & 1][k][1]);
              mma16816(c1[k & 1], f, bt[c & 1][k][2], bt[c & 1][k][3]);
            }
          }
        }
        const float s0 = (cs[0][0] + cs[1][0]) * (1.f / 512.f), s1 = (cs[0][2] + cs[1][2]) * (1.f / 512.f);
        asm volatile("barrier.cluster.wait.aligned;" ::: "memory");
        if (lane < 3) release(sx + lane);
        const uint32_t m0 = pack2(s0, s0), m1 = pack2(s1, s1);
        float q0 = (g & 1) ? c0[0][1] + c0[1][1] : c0[0][0] + c0[1][0];
        float q1 = (g & 1) ? c1[0][3] + c1[1][3] : c1[0][2] + c1[1][2];
        q0 = __shfl_sync(0xffffffffu, q0, (lane & ~3) | (g >> 1));
        q1 = __shfl_sync(0xffffffffu, q1, (lane & ~3) | (g >> 1));
        r0 = rsqrtf(fmaxf(q0 * (1.f / 512.f) - s0 * s0, 0.f) + 1e-5f);
        r1 = rsqrtf(fmaxf(q1 * (1.f / 512.f) - s1 * s1, 0.f) + 1e-5f);
#pragma unroll
        for (int ks = 0; ks < 32; ks++) {
          A[ks][0] = hsub2(A[ks][0], m0); A[ks][1] = hsub2(A[ks][1], m1);
          A[ks][2] = hsub2(A[ks][2], m0); A[ks][3] = hsub2(A[ks][3], m1);
        }
      }
      TSTAMP(1);
      const uint32_t wpa = sb + SM_WPHI + ((lane & 7) + ((lane >> 3) & 1) * 8) * 32 + lhi * 16;
      const uint32_t scr = sb + (wg ? (ST_SCR1 % NSLOT) : (ST_SCR0 % NSLOT)) * SLOT;
#pragma unroll 1
      for (int ps = 0; ps < 3; ps++) {
        const int st0 = ps == 0 ? ST_WK : (ps == 1 ? ST_WV : ST_WQ);
        const uint32_t wdesc = DESC((ps == 0 ? ST_WK % NSLOT : (ps == 1 ? ST_WV % NSLOT : ST_WQ % NSLOT)) * SLOT);
        float acc[32];
        bar_sync(4 + wg, 256);
#pragma unroll
        for (int i = 0; i < 3; i++) {
          mbar_wait(sb + SM_FULL + (st0 + i) * 8);
          wg_fence();
#pragma unroll
          for (int kk = 0; kk < (i < 2 ? 12 : 8); kk++)
            wgmma_rs_n64(acc, A[12 * i + kk], wdesc + ((i * SLOT + kk * 2048) >> 4), (i | kk) != 0);
          wg_commit();
          if (i == 1) { wg_wait<1>(); if (lead) release(st0); }
        }
        if (ps == 1 && wg == 0) bar_arrive(5, 256);
        uint32_t a[4][4], b[4][4];
        mbar_wait(sb + SM_MISCB);
        T = (*reinterpret_cast<volatile unsigned*>(smem + SM_EPOCH) & 1) ^ 1;
#pragma unroll
        for (int h = 0; h < 4; h++) ldsm4t(b[h], wpa + h * 512);
        wg_wait<0>();
        if ((tid & 127) < 2) release(st0 + 1 + (tid & 1));
        TSTAMP(2 + 2 * ps);
#pragma unroll
        for (int h = 0; h < 4; h++) {
          a[h][0] = pack2(acc[8 * h + 0] * r0, acc[8 * h + 1] * r0); a[h][1] = pack2(acc[8 * h + 2] * r1, acc[8 * h + 3] * r1);
          a[h][2] = pack2(acc[8 * h + 4] * r0, acc[8 * h + 5] * r0); a[h][3] = pack2(acc[8 * h + 6] * r1, acc[8 * h + 7] * r1);
        }
        if (ps != 1) {
          {
            float pp[4][2][4];
#pragma unroll
            for (int h = 0; h < 4; h++) {
#pragma unroll
              for (int i = 0; i < 4; i++) { pp[h][0][i] = 0.f; pp[h][1][i] = 0.f; }
              mma16816(pp[h][0], a[h], b[h][0], b[h][1]);
              mma16816(pp[h][1], a[h], b[h][2], b[h][3]);
            }
#pragma unroll
            for (int h = 0; h < 4; h++) {
              a[h][0] = pack2(pp[h][0][0], pp[h][0][1]); a[h][1] = pack2(pp[h][0][2], pp[h][0][3]);
              a[h][2] = pack2(pp[h][1][0], pp[h][1][1]); a[h][3] = pack2(pp[h][1][2], pp[h][1][3]);
            }
          }
          if (ps == 0 || wg == 0) bar_arrive(4 + (wg ^ 1), 256);
          if (ps == 0) mbar_wait(sb + SM_EMPTY + (wg ? ST_SCR1 - NSLOT : ST_SCR0 - NSLOT) * 8);
#pragma unroll 1
          for (int hp = 0; hp < 2; hp++) {
            float e[2][16];
            feat_exp(a[0], e[0]);
            feat_exp(a[1], e[1]);
            if (ps == 0) {
#pragma unroll
              for (int h = 0; h < 2; h++) {
                const float (&f)[16] = e[h];
                float sp0 = (f[0] + f[1]) + (f[4] + f[5]), sp1 = (f[2] + f[3]) + (f[6] + f[7]);
                float sn0 = (f[8] + f[9]) + (f[12] + f[13]), sn1 = (f[10] + f[11]) + (f[14] + f[15]);
                sp0 += __shfl_xor_sync(0xffffffffu, sp0, 1); sp1 += __shfl_xor_sync(0xffffffffu, sp1, 1);
                sn0 += __shfl_xor_sync(0xffffffffu, sn0, 1); sn1 += __shfl_xor_sync(0xffffffffu, sn1, 1);
                sp0 += __shfl_xor_sync(0xffffffffu, sp0, 2); sp1 += __shfl_xor_sync(0xffffffffu, sp1, 2);
                sn0 += __shfl_xor_sync(0xffffffffu, sn0, 2); sn1 += __shfl_xor_sync(0xffffffffu, sn1, 2);
                sp0 = rcp(sp0); sp1 = rcp(sp1); sn0 = rcp(sn0); sn1 = rcp(sn1);
                const uint32_t dst = scr + hp * 8192 + lrow;
                stsm4(dst + (((h * 4 + lhi) ^ lx) << 4), pack2(f[0] * sp0, f[1] * sp0), pack2(f[2] * sp1, f[3] * sp1),
                      pack2(f[4] * sp0, f[5] * sp0), pack2(f[6] * sp1, f[7] * sp1));
                stsm4(dst + (((h * 4 + 2 + lhi) ^ lx) << 4), pack2(f[8] * sn0, f[9] * sn0), pack2(f[10] * sn1, f[11] * sn1),
                      pack2(f[12] * sn0, f[13] * sn0), pack2(f[14] * sn1, f[15] * sn1));
              }
            } else {
#pragma unroll
              for (int i = 0; i < 16; i++) {
                A[i >> 2][i & 3] = A[4 + (i >> 2)][i & 3];
                A[4 + (i >> 2)][i & 3] = pack2(e[i >> 3][2 * (i & 7)], e[i >> 3][2 * (i & 7) + 1]);
              }
            }
#pragma unroll
            for (int i = 0; i < 4; i++) { a[0][i] = a[2][i]; a[1][i] = a[3][i]; }
          }
        } else {
#pragma unroll
          for (int h = 0; h < 4; h++) stsm4(scr + 16384 + lrow + (((2 * h + lhi) ^ lx) << 4), a[h][0], a[h][1], a[h][2], a[h][3]);
          fence_async_smem();
          bar_sync(3, 256);
          float kv[36];
          wg_fence();
#pragma unroll
          for (int ks = 0; ks < 8; ks++) {
            const uint32_t sk = (ks < 4 ? (ST_SCR0 % NSLOT) : (ST_SCR1 % NSLOT)) * SLOT + (ks & 3) * 2048;
            const uint32_t dv = (DESC(sk + 16384) & 0xFFFFu) | (((SM_ONES - sk - 16384) >> 4) << 16);
            wgmma_ss_n72_t11(kv, DESC(sk) + wg * 512, dv, ks != 0);
          }
          wg_commit();
          if (wg == 1) bar_arrive(4, 256);
          wg_wait<0>();
          if (lead) { mbar_arrive(sb + SM_EMPTY + ST_SCR0 * 8); mbar_arrive(sb + SM_EMPTY + ST_SCR1 * 8); }
          const int hl = 2 * wg + (wq >> 1), f = (wq & 1) * 16 + g;
          float* kvp = reinterpret_cast<float*>(smem + 2 * SLOT) + (hl * 32 + f) * 16 + 2 * t;
          float c[8];
#pragma unroll
          for (int i = 0; i < 8; i++) c[i] = hl >= 2 ? (hl == 3 ? kv[24 + i] : kv[16 + i]) : (hl == 1 ? kv[8 + i] : kv[i]);
#pragma unroll
          for (int n = 0; n < 2; n++) {
            *reinterpret_cast<float2*>(kvp + n * 8) = make_float2(c[4 * n], c[4 * n + 1]);
            *reinterpret_cast<float2*>(kvp + n * 8 + 128) = make_float2(c[4 * n + 2], c[4 * n + 3]);
          }
          if (t < 2) reinterpret_cast<float*>(smem + 2 * SLOT)[2048 + hl * 32 + f + t * 8] = t ? kv[34] : kv[32];
          fence_async_smem();
          bar_sync(6, 320);
        }
        TSTAMP(3 + 2 * ps);
      }
#pragma unroll
      for (int i = 0; i < 32; i++) E[i >> 3][i & 7] = A[i >> 2][i & 3];
    }
    const int rh = 2 * rb + wg;
#define IDF ((g >> 1) == t ? ((g & 1) ? 0x3F800000u : 0x00003F80u) : 0u)
    const uint4* xb = reinterpret_cast<const uint4*>(smem + 2 * SLOT) + wq * 128 + lane;
    mbar_wait(sb + SM_KVB);
    {
      const int r = tid & 127;
      const float4* src = reinterpret_cast<const float4*>(smem + SM_KV32) + r;
#pragma unroll
      for (int i = 0; i < 4; i++) {
        const float4 a = src[i * 128];
        *reinterpret_cast<uint2*>(smem + SM_KVS + (i * 32 + (r >> 2)) * 48 + (r & 3) * 8) = make_uint2(pack2(a.x, a.y), pack2(a.z, a.w));
      }
      const uint32_t zz = pack2(reinterpret_cast<const float*>(smem + SM_ONES)[r], 1.0f);
      *reinterpret_cast<uint4*>(smem + SM_KVS + r * 48 + 32) = make_uint4(zz, zz, zz, zz);
      bar_sync(1 + wg, 128);
    }
    TSTAMP(8);
    {
      uint4* op = &g_o[rh][hg][wq][0][lane];
      if (wg == 1) bar_sync(5, 256);
#pragma unroll 1
      for (int hp = 0; hp < 2; hp++) {
#pragma unroll
      for (int h = 0; h < 2; h++) {
        uint32_t b0[4], b1[4], b2[4];
        const uint32_t kb = sb + SM_KVS + ((2 * hp + h) * 32 + lane) * 48;
        ldsm4t(b0, kb); ldsm4t(b1, kb + 16); ldsm4t(b2, kb + 32);
        const uint32_t ep[4] = {E[h][0], E[h][1], E[h][2], E[h][3]}, en[4] = {E[h][4], E[h][5], E[h][6], E[h][7]};
        float np0[4] = {0, 0, 0, 0}, np1[4] = {0, 0, 0, 0}, nn0[4] = {0, 0, 0, 0}, nn1[4] = {0, 0, 0, 0}, dp[4] = {0, 0, 0, 0}, dn[4] = {0, 0, 0, 0};
        mma16816(dp, ep, b2[0], b2[1]);  mma16816(dn, en, b2[2], b2[3]);
        mma16816(np0, ep, b0[0], b0[1]); mma16816(nn0, en, b0[2], b0[3]);
        mma16816(np1, ep, b1[0], b1[1]); mma16816(nn1, en, b1[2], b1[3]);
        const float i0 = rcp(fmaf(dp[0], dn[1], fmaf(dn[0], dp[1], 1e-6f * dp[1] * dn[1])));
        const float i1 = rcp(fmaf(dp[2], dn[3], fmaf(dn[2], dp[3], 1e-6f * dp[3] * dn[3])));
        const float cp0 = dn[1] * i0, cn0 = dp[1] * i0, cp1 = dn[3] * i1, cn1 = dp[3] * i1;
        st_rlx4(op + (2 * hp + h) * 32,
                tg(pack2(fmaf(np0[0], cp0, nn0[0] * cn0), fmaf(np0[1], cp0, nn0[1] * cn0)), T),
                pack2(fmaf(np0[2], cp1, nn0[2] * cn1), fmaf(np0[3], cp1, nn0[3] * cn1)),
                pack2(fmaf(np1[0], cp0, nn1[0] * cn0), fmaf(np1[1], cp0, nn1[1] * cn0)),
                pack2(fmaf(np1[2], cp1, nn1[2] * cn1), fmaf(np1[3], cp1, nn1[3] * cn1)));
      }
#pragma unroll
        for (int i = 0; i < 8; i++) { E[0][i] = E[2][i]; E[1][i] = E[3][i]; }
      }
    }
    if (wg == 0) bar_arrive(5, 256);
    bar_arrive(10 + wg, 160);
    TSTAMP(9);

    {
      uint32_t xr[4][4];
      {
        const uint32_t* xp = reinterpret_cast<const uint32_t*>(x + (size_t)(rh * 64 + wq * 16 + g) * 512 + hg * 64 + 2 * t);
#pragma unroll
        for (int i = 0; i < 8; i++) { xr[i >> 1][(i & 1) * 2] = __ldg(xp + 4 * i); xr[i >> 1][(i & 1) * 2 + 1] = __ldg(xp + 8 * 256 + 4 * i); }
      }
      uint32_t A[8][4][4];
      const uint4* op = &g_o[rh][0][wq][0][lane];
      float acc[32];
#pragma unroll
      for (int i = 0; i < 32; i++) acc[i] = 0.f;
      add_frag(acc, xr, IDF);
#pragma unroll
      for (int p = -1; p < 4; p++) {
        if (p < 3) {
          mbar_wait(sb + SM_XF + (wg * 4 + p + 1) * 8);
          get_pair(A[2 * p + 2], A[2 * p + 3], xb + (p + 1) * 1024, op + (p + 1) * 1024, T);
          if (lane == 0) mbar_arrive(sb + SM_XE + (wg * 4 + p + 1) * 8);
        }
        if (p == 0 && wg == 1) bar_sync(4, 256);
        if (p >= 0) {
          if (p != 2) mbar_wait(sb + SM_FULL + (ST_WO + (p + 1) / 2) * 8);
          wg_fence();
#pragma unroll
          for (int c = 2 * p; c < 2 * p + 2; c++)
#pragma unroll
            for (int s = 0; s < 4; s++)
              wgmma_rs_n64(acc, A[c][s], DESC(((ST_WO + c / 3) % NSLOT) * SLOT + ((c % 3) * 4 + s) * 2048), 1);
        }
      }
      wg_commit();
      if (wg == 0) bar_arrive(4, 256);
      wg_wait<0>();
      if ((tid & 127) < 3) release(ST_WO + (tid & 127));
      TSTAMP(10);
      uint4* hp_ = &g_h[rh][hg][wq][0][lane];
      uint32_t hx = T;
#pragma unroll
      for (int s = 0; s < 4; s++) {
        const uint32_t h0 = pack2(acc[8 * s], acc[8 * s + 1]);
        st_rlx4(hp_ + s * 32, tg(h0, T), pack2(acc[8 * s + 2], acc[8 * s + 3]), pack2(acc[8 * s + 4], acc[8 * s + 5]), pack2(acc[8 * s + 6], acc[8 * s + 7]));
        hx |= (h0 & 1u) << (s + 1);
      }
      float s0 = 0.f, s1 = 0.f, q0 = 0.f, q1 = 0.f, q2 = 0.f, q3 = 0.f;
#pragma unroll
      for (int i = 0; i < 8; i++) {
        s0 += acc[4 * i] + acc[4 * i + 1]; s1 += acc[4 * i + 2] + acc[4 * i + 3];
        q0 = fmaf(acc[4 * i], acc[4 * i], q0); q2 = fmaf(acc[4 * i + 1], acc[4 * i + 1], q2);
        q1 = fmaf(acc[4 * i + 2], acc[4 * i + 2], q1); q3 = fmaf(acc[4 * i + 3], acc[4 * i + 3], q3);
      }
      q0 += q2; q1 += q3;
      {
        const bool up = t & 2;
        float s = (up ? s1 : s0) + __shfl_xor_sync(0xffffffffu, up ? s0 : s1, 2);
        float q = (up ? q1 : q0) + __shfl_xor_sync(0xffffffffu, up ? q0 : q1, 2);
        s += __shfl_xor_sync(0xffffffffu, s, 1);
        q += __shfl_xor_sync(0xffffffffu, q, 1);
        if (!(t & 1)) st_rlx2(&g_st[rh][hg][wq * 16 + g + (t >> 1) * 8], tg(__float_as_uint(s), T), __float_as_uint(q));
      }
      st_rlx1(&g_hx[rh][hg][wq][lane], hx);
    }
    bar_arrive(10 + wg, 160);
    TSTAMP(11);

    const int rh3 = 2 * rb3 + wg;
    uint32_t HH[11][4], PH[11][4];
    const uint4* pp = &g_hh[rh3][jf ^ 1][0][wq][lane];
    {
      uint32_t A[8][4][4];
      const uint4* hp_ = &g_h[rh3][0][wq][0][lane];
      uint4* hhp = &g_hh[rh3][jf][0][wq][lane];
      const uint32_t dg = (db & 0xFFFFu) | (256u << 16);
      uint32_t m0, m1;
      mbar_wait(sb + SM_XF + ((2 + wg) * 4) * 8);
      TSTAMP(0);
      {
        const uint2* sp = reinterpret_cast<const uint2*>(smem + SM_KV32 + wg * 4096) + 2 * t * 64 + wq * 16 + g;
        uint2 a0, a1, b0, b1;
        int it = 0;
#pragma unroll 1
        do {
          ld_rlx2(a0.x, a0.y, sp); ld_rlx2(a1.x, a1.y, sp + 64); ld_rlx2(b0.x, b0.y, sp + 8); ld_rlx2(b1.x, b1.y, sp + 72);
          sp = &g_st[rh3][2 * t][wq * 16 + g];
        } while (__any_sync(0xffffffffu, bad4(a0.x, a1.x, b0.x, b1.x, T)) && ++it < (1 << 18));
        float s0 = __uint_as_float(a0.x) + __uint_as_float(a1.x), q0 = __uint_as_float(a0.y) + __uint_as_float(a1.y);
        float s1 = __uint_as_float(b0.x) + __uint_as_float(b1.x), q1 = __uint_as_float(b0.y) + __uint_as_float(b1.y);
        s0 += __shfl_xor_sync(0xffffffffu, s0, 1); s1 += __shfl_xor_sync(0xffffffffu, s1, 1);
        q0 += __shfl_xor_sync(0xffffffffu, q0, 1); q1 += __shfl_xor_sync(0xffffffffu, q1, 1);
        s0 += __shfl_xor_sync(0xffffffffu, s0, 2); s1 += __shfl_xor_sync(0xffffffffu, s1, 2);
        q0 += __shfl_xor_sync(0xffffffffu, q0, 2); q1 += __shfl_xor_sync(0xffffffffu, q1, 2);
        s0 *= (1.f / 512.f); s1 *= (1.f / 512.f);
        r0 = rcp(fmaxf(q0 * (1.f / 512.f) - s0 * s0, 0.f) + 1e-5f);
        r1 = rcp(fmaxf(q1 * (1.f / 512.f) - s1 * s1, 0.f) + 1e-5f);
        m0 = pack2(s0, s0); m1 = pack2(s1, s1);
      }
      TSTAMP(12);
#define UOFF(u) ((((ST_GU + (u) / 3) % NSLOT) * SLOT + ((u) % 3) * 8192) >> 4)
#define UNIT_PRE(u)  do { if ((u) % 3 == 0) mbar_wait(sb + SM_FULL + (ST_GU + (u) / 3) * 8); } while (0)
#define UNIT_POST(u) do { wg_commit(); if ((u) % 3 == 1 && (u) > 3) { wg_wait<2>(); if (lead) release(ST_GU + (u) / 3 - 1); } } while (0)
      float acc[64];
      const int rz = blockIdx.y;
#pragma unroll
      for (int ps = 0; ps < 2; ps++) {
        wg_fence();
#pragma unroll
        for (int k = 0; k < 16; k++) {
          const int u = 16 * ps + k, c = k >> 1;
          if (ps == 0 && (k == 0 || k == 4 || k == 8)) {
#pragma unroll
            for (int p = (k == 0 ? 0 : (k == 4 ? 1 : 3)); p < (k == 0 ? 1 : (k == 4 ? 3 : 4)); p++) {
              if (p > 0) mbar_wait(sb + SM_XF + ((2 + wg) * 4 + p) * 8);
              get_pair(A[2 * p], A[2 * p + 1], xb + p * 1024, hp_ + p * 1024, T);
              if (lane == 0) {
                if (wg == 0) mbar_arrive(sb + SM_XE + (8 + p) * 8);
                else if (p > 0) release(ST_XC + p - 1);
              }
            }
          }
          if (ps == 0 && (k & 1) == 0) {
#pragma unroll
            for (int s = 0; s < 4; s++) {
              A[c][s][0] = hsub2(A[c][s][0], m0); A[c][s][1] = hsub2(A[c][s][1], m1);
              A[c][s][2] = hsub2(A[c][s][2], m0); A[c][s][3] = hsub2(A[c][s][3], m1);
            }
            wg_fence();
          }
          UNIT_PRE(u);
          wgmma_rs_n128(acc, A[c][(k & 1) * 2], dg + UOFF(u), k != 0 ? 1 : (ps ? rz : 0));
          wgmma_rs_n128(acc, A[c][(k & 1) * 2 + 1], dg + UOFF(u) + 128, 1);
          UNIT_POST(u);
        }
        wg_wait<0>();
        TSTAMP(22 + ps);
#pragma unroll
        for (int s = 0; s < 4; s++) {
          uint32_t (&hh)[4] = HH[4 + s];
          hh[0] = tg(pack2(acc[8 * s + 0] * acc[32 + 8 * s + 0], acc[8 * s + 1] * acc[32 + 8 * s + 1]), T);
          hh[1] = pack2(acc[8 * s + 2] * acc[32 + 8 * s + 2], acc[8 * s + 3] * acc[32 + 8 * s + 3]);
          hh[2] = pack2(acc[8 * s + 4] * acc[32 + 8 * s + 4], acc[8 * s + 5] * acc[32 + 8 * s + 5]);
          hh[3] = pack2(acc[8 * s + 6] * acc[32 + 8 * s + 6], acc[8 * s + 7] * acc[32 + 8 * s + 7]);
          st_rlx4(hhp + (4 * ps + s) * 128, hh[0], hh[1], hh[2], hh[3]);
        }
      }
      {
        float ag[24], au[24];
        const uint32_t* ph7 = reinterpret_cast<const uint32_t*>(&g_hh[rh3][jf ^ 1][7][wq][31]);
        uint32_t hv = 0;
        bar_sync(1 + wg, 128);
        wg_fence();
#pragma unroll
        for (int k = 0; k < 16; k++) {
          const int u = 32 + k, c = k >> 1;
          if (k == 6) {
#pragma unroll
            for (int s = 0; s < 4; s++) ld_rlx4(HH[s], hhp + s * 128);
          }
          if (k == 9) hv = ld_rlx1(ph7);
          if (k == 12) {
            int it = 0;
#pragma unroll 1
            while (((hv ^ T) & 1) && ++it < (1 << 18)) hv = ld_rlx1(ph7);
#pragma unroll
            for (int s = 0; s < 8; s++) ld_rlx4(PH[s], pp + s * 128);
          }
          UNIT_PRE(u);
          wgmma_rs_n48(ag, A[c][(k & 1) * 2], dg + UOFF(u), k != 0);
          wgmma_rs_n48(au, A[c][(k & 1) * 2], dg + UOFF(u) + 256, k != 0);
          wgmma_rs_n48(ag, A[c][(k & 1) * 2 + 1], dg + UOFF(u) + 128, 1);
          wgmma_rs_n48(au, A[c][(k & 1) * 2 + 1], dg + UOFF(u) + 256 + 128, 1);
          UNIT_POST(u);
        }
        wg_wait<0>();
        TSTAMP(13);
#pragma unroll
        for (int s = 0; s < 3; s++) {
          uint32_t (&hh)[4] = HH[8 + s];
          hh[0] = tg(pack2(ag[8 * s + 0] * au[8 * s + 0], ag[8 * s + 1] * au[8 * s + 1]), T);
          hh[1] = pack2(ag[8 * s + 2] * au[8 * s + 2], ag[8 * s + 3] * au[8 * s + 3]);
          hh[2] = pack2(ag[8 * s + 4] * au[8 * s + 4], ag[8 * s + 5] * au[8 * s + 5]);
          hh[3] = pack2(ag[8 * s + 6] * au[8 * s + 6], ag[8 * s + 7] * au[8 * s + 7]);
          st_rlx4(hhp + (8 + s) * 128, hh[0], hh[1], hh[2], hh[3]);
        }
      }
    }
    TSTAMP(14);

    {
      float acc[32], sum[32];
      uint32_t hr[4][4], hx = 0;
      const int m = jf >> 1, oc = (jf & 1) * 4 + m;
      uint4* outb = &g_part[rh3][(jf & 1) * 4][m][wq][0][lane];
      bar_arrive(8 + wg, 256);
#pragma unroll
      for (int i = 0; i < 32; i++) sum[i] = 0.f;
      int s0 = ST_D % NSLOT;
#pragma unroll 1
      for (int k = 0; k < 5; k++) {
        wg_wait<0>();
        if (k < 4) {
          const int s1 = s0 + 1 == NSLOT ? 0 : s0 + 1;
          const uint32_t d0 = db + s0 * (SLOT >> 4), d1 = db + s1 * (SLOT >> 4);
          if (k > 0) {
            uint4* p = outb + ((m + k) & 3) * 2048;
#pragma unroll
            for (int s = 0; s < 4; s++)
              st_rlx4(p + s * 32, tg(pack2(acc[8 * s], acc[8 * s + 1]), T), pack2(acc[8 * s + 2], acc[8 * s + 3]),
                      pack2(acc[8 * s + 4], acc[8 * s + 5]), pack2(acc[8 * s + 6], acc[8 * s + 7]));
            if (k == 1) bar_arrive(12, 320);
          }
          if (k == 3) TSTAMP(18);
          mbar_wait(sb + SM_FULL + (ST_D + 2 * k) * 8);
          mbar_wait(sb + SM_FULL + (ST_D + 2 * k + 1) * 8);
          wg_fence();
#pragma unroll
          for (int s = 0; s < 11; s++) wgmma_rs_n64(acc, HH[s], d0 + s * 128, s != 0);
          if (k == 0) {
            int it = 0;
#pragma unroll 1
            while (__any_sync(0xffffffffu, bad4(PH[0][0], PH[1][0], PH[2][0], PH[3][0], T) | bad4(PH[4][0], PH[5][0], PH[6][0], PH[7][0], T)) && ++it < (1 << 18)) {
#pragma unroll
              for (int s = 0; s < 8; s++) ld_rlx4(PH[s], pp + s * 128);
            }
            wg_fence();
          }
#pragma unroll
          for (int s = 0; s < 8; s++) wgmma_rs_n64(acc, PH[s], d1 + s * 128, 1);
          if (k == 0) {
            int it = 0;
            ld_chunk(hr, &g_h[rh3][oc][wq][0][lane]);
#pragma unroll 1
            do {
              hx = ld_rlx1(&g_hx[rh3][oc][wq][lane]);
#pragma unroll
              for (int s = 8; s < 11; s++) ld_rlx4(PH[s], pp + s * 128);
            } while (__any_sync(0xffffffffu, bad4(PH[8][0], PH[9][0], PH[10][0], hx, T)) && ++it < (1 << 18));
            TSTAMP(20);
            wg_fence();
          }
#pragma unroll
          for (int s = 8; s < 11; s++) wgmma_rs_n64(acc, PH[s], d1 + s * 128, 1);
          wg_commit();
          s0 = s1 + 1 == NSLOT ? 0 : s1 + 1;
        }
        if (k >= 2) {
          uint32_t in[4][4];
          const uint4* sp = reinterpret_cast<const uint4*>(smem + ((ST_D % NSLOT) + wg) * SLOT) + (k - 2) * 512 + wq * 128 + lane;
          mbar_wait_p(sb + SM_XF + (wg * 4 + k - 2) * 8, 1);
          if (k == 2) TSTAMP(19); if (k == 3) TSTAMP(21); if (k == 4) TSTAMP(24);
          int it = 0;
#pragma unroll 1
          do {
#pragma unroll
            for (int s = 0; s < 4; s++)
              asm volatile("{\n.reg .b128 v;\nld.relaxed.gpu.b128 v, [%4];\nmov.b128 {%0,%1,%2,%3}, v;\n}"
                           : "=r"(in[s][0]), "=r"(in[s][1]), "=r"(in[s][2]), "=r"(in[s][3]) : "l"(sp + s * 32) : "memory");
            sp = &g_part[rh3][oc][(m + 1 - k) & 3][wq][0][lane];
          } while (__any_sync(0xffffffffu, bad4(in[0][0], in[1][0], in[2][0], in[3][0], T)) && ++it < (1 << 18));
#pragma unroll
          for (int i = 0; i < 16; i++) { sum[2 * i] += blo(in[i >> 2][i & 3]); sum[2 * i + 1] += bhi(in[i >> 2][i & 3]); }
        }
      }
      wg_wait<0>();
      TSTAMP(15);
#pragma unroll
      for (int s = 0; s < 4; s++) hr[s][0] = (hr[s][0] & 0xFFFFFFFEu) | ((hx >> (s + 1)) & 1u);
#pragma unroll
      for (int i = 0; i < 16; i++) {
        const float r = (i & 1) ? r1 : r0;
        acc[2 * i]     = fmaf(acc[2 * i] + sum[2 * i], r, blo(hr[i >> 2][i & 3]));
        acc[2 * i + 1] = fmaf(acc[2 * i + 1] + sum[2 * i + 1], r, bhi(hr[i >> 2][i & 3]));
      }
      bar_sync(9 - wg, 256);
      const uint32_t ob = sb + ((ST_D - 1) % NSLOT) * SLOT + wg * 8192;
#pragma unroll
      for (int s = 0; s < 4; s++)
        stsm4(ob + lrow + (((2 * s + lhi) ^ lx) << 4), pack2(acc[8 * s + 0], acc[8 * s + 1]), pack2(acc[8 * s + 2], acc[8 * s + 3]),
              pack2(acc[8 * s + 4], acc[8 * s + 5]), pack2(acc[8 * s + 6], acc[8 * s + 7]));
      __syncwarp();
      {
        const int row = wq * 16 + (lane >> 3);
        __nv_bfloat16* op = out + (size_t)(rh3 * 64 + row) * 512 + oc * 64 + lx * 8;
#pragma unroll
        for (int i = 0; i < 4; i++) {
          uint4 v;
          asm volatile("ld.shared.v4.b32 {%0,%1,%2,%3}, [%4];" : "=r"(v.x), "=r"(v.y), "=r"(v.z), "=r"(v.w)
                       : "r"(ob + (row + i * 4) * 128 + ((lx ^ (((lane >> 3) + i * 4) & 7)) << 4)) : "memory");
          asm volatile("st.global.v4.b32 [%0], {%1,%2,%3,%4};" ::"l"(op + i * 2048), "r"(v.x), "r"(v.y), "r"(v.z), "r"(v.w) : "memory");
        }
      }
    }
    TSTAMP(16);
    asm volatile("barrier.cluster.arrive.relaxed.aligned;" ::: "memory");
    asm volatile("barrier.cluster.wait.aligned;" ::: "memory");
  } else {
    asm volatile("setmaxnreg.dec.sync.aligned.u32 24;");
    if (elect_one()) {
      if (warp == 8) {
#pragma unroll
        for (int k = 0; k < 9; k++) {
          const int s = k < 3 ? k : (k < 6 ? k + 3 : k - 3);
          const uint32_t bar = sb + SM_FULL + s * 8;
          mbar_init(bar, 1);
          mbar_expect_tx(bar, SLOT);
          if (s >= 3 && s < 6) tma2d(sb + s * SLOT, &maps.w, 512 + hg * 64, (s - 3) * 192, bar);
          else tma3d(sb + s * SLOT, &maps.x, 0, rb * 128 + (s >= 6 ? 64 : 0), 3 * (s % 3), bar);
        }
      } else if (warp == 9) {
        mbar_init(sb + SM_MISCB, 2);
        mbar_init(sb + SM_KVB, 1);
        mbar_expect_tx(sb + SM_KVB, 8704);
        mbar_expect_tx(sb + SM_MISCB, 2048);
        bulk_g2s(sb + SM_WPHI, wphi + hg * 1024, 2048, sb + SM_MISCB);
      } else if (warp == 10) {
        if ((sb & 0x3FFFF) != SM_BASE) __trap();
#pragma unroll 1
        for (int i = 0; i < 16; i++) {
          mbar_init(sb + SM_XF + i * 8, 1);
          mbar_expect_tx(sb + SM_XF + i * 8, (i == 8 || i == 12) ? 20480 : 16384);
          if (i < 12) mbar_init(sb + SM_XE + i * 8, 4);
        }
      } else {
        *reinterpret_cast<volatile unsigned*>(smem + SM_EPOCH) = atomicAdd(&g_start, 1u) / NCTA;
      }
      asm volatile("fence.mbarrier_init.release.cluster;" ::: "memory");
    }
    __syncwarp();
    if (warp != 11) bar_sync(0, 352);
    asm volatile("barrier.cluster.arrive.relaxed.aligned;" ::: "memory");
    if (warp == 8) {
      asm volatile("barrier.cluster.wait.aligned;" ::: "memory");
      if (elect_one()) {
        const CUtensorMap* mg = jf == 7 ? &maps.g7 : &maps.g;
        const CUtensorMap* mu = jf == 7 ? &maps.u7 : &maps.u;
        asm volatile("prefetch.tensormap [%0];" ::"l"(&maps.wo) : "memory");
        asm volatile("prefetch.tensormap [%0];" ::"l"(mg) : "memory");
        asm volatile("prefetch.tensormap [%0];" ::"l"(mu) : "memory");
        asm volatile("prefetch.tensormap [%0];" ::"l"(&maps.d) : "memory");
#pragma unroll 1
        for (int s = ST_WV; s < ST_XC; s++) {
          if (s == ST_SCR1) continue;
          mbar_wait(sb + SM_EMPTY + (s - 9) * 8);
          const uint32_t dst = sb + (s >= 18 ? s - 18 : s - 9) * SLOT, bar = sb + SM_FULL + s * 8;
          if (s < ST_WO) tma2d(dst, &maps.w, (s < ST_WQ ? 1024 : 0) + hg * 64, (s < ST_WQ ? s - ST_WV : s - ST_WQ) * 192, bar);
          else { mbar_wait(bar - 8); tma2d(dst, &maps.wo, hg * 64, (s - ST_WO) * 192, bar); }
        }
        const int jc = jf == 7 ? 0 : jf;
        int slot = (ST_GU + 1 - rank) % NSLOT;
#pragma unroll 1
        for (int s = ST_GU + 1 - rank; s < NSTAGE; s += 2) {
          mbar_wait(sb + SM_EMPTY + (s - 9) * 8);
          if (s > ST_GU && s < ST_GU + THR) mbar_wait(sb + SM_FULL + (s - 1) * 8);
          const uint32_t dst = sb + slot * SLOT, bar = sb + SM_FULL + s * 8;
          if (s < ST_D) {
#pragma unroll 1
            for (int i = 0; i < 3; i++) {
              const int u = (s - ST_GU) * 3 + i;
              tma3d_mc(dst + i * 8192, mg, (u >> 4) * 64, jc, (u & 15) * 32, bar);
              tma3d_mc(dst + i * 8192 + 4096, mu, (u >> 4) * 64, jc, (u & 15) * 32, bar);
            }
          } else {
            const int i = s - ST_D;
            tma2d_mc(dst, &maps.d, ((jf & 1) * 4 + (((jf >> 1) + 1 + (i >> 1)) & 3)) * 64, (jf ^ (i & 1)) * 176, bar);
          }
          slot += 2; if (slot >= NSLOT) slot -= NSLOT;
        }
      }
      __syncwarp();
    } else {
      asm volatile("barrier.cluster.wait.aligned;" ::: "memory");
      if (warp == 11) {
#pragma unroll
        for (int i = 0; i < 4; i++)
          reinterpret_cast<uint4*>(smem + SM_ONES)[lane + 32 * i] = make_uint4(0x3F803F80u, 0x3F803F80u, 0x3F803F80u, 0x3F803F80u);
        fence_async_smem();
        __syncwarp();
        if (lane == 0) mbar_arrive(sb + SM_MISCB);
      }
      mbar_wait(sb + SM_MISCB);
      const unsigned epoch = *reinterpret_cast<volatile unsigned*>(smem + SM_EPOCH);
      const uint32_t T = (epoch & 1) ^ 1;
      if (warp == 11) {
        reinterpret_cast<float4*>(&g_kv[hg][rb * 136])[lane] = make_float4(0.f, 0.f, 0.f, 0.f);
        if (lane < 2) reinterpret_cast<float4*>(&g_kv[hg][rb * 136])[32 + lane] = make_float4(0.f, 0.f, 0.f, 0.f);
        __syncwarp();
        if (elect_one()) asm volatile("red.release.gpu.global.add.u32 [%0], 1;" ::"l"(&g_kvcnt[hg * 32 + 1]) : "memory");
        mbar_wait(sb + SM_FULL + (ST_WK + 2) * 8);
        if (elect_one()) {
          asm volatile("cp.async.bulk.prefetch.L2.global [%0], 4096;" ::"l"((const char*)wo + blockIdx.x * 4096) : "memory");
          asm volatile("cp.async.bulk.prefetch.L2.global [%0], 11008;" ::"l"((const char*)wg_ + blockIdx.x * 11008) : "memory");
          asm volatile("cp.async.bulk.prefetch.L2.global [%0], 11008;" ::"l"((const char*)wu_ + blockIdx.x * 11008) : "memory");
          asm volatile("cp.async.bulk.prefetch.L2.global [%0], 11008;" ::"l"((const char*)wd_ + blockIdx.x * 11008) : "memory");
          mbar_wait(sb + SM_EMPTY + ST_SCR0 * 8);
          const unsigned target = (epoch + 1) * 16;
          unsigned v; int it = 0;
#pragma unroll 1
          do {
            asm volatile("ld.acquire.gpu.global.u32 %0, [%1];" : "=r"(v) : "l"(&g_kvcnt[hg * 32]) : "memory");
            if (++it > (1 << 18)) break;
          } while ((int)(v - target) < 0);
          TS2(0, 26);
          asm volatile("fence.proxy.async.global;" ::: "memory");
          bulk_g2s(sb + SM_KV32, &g_kv[hg][0], 8192, sb + SM_KVB);
          bulk_g2s(sb + SM_ONES, &g_kv[hg][2048], 512, sb + SM_KVB);
        }
        __syncwarp();
      } else {
        const int w = warp - 9;
        st_rlx4(reinterpret_cast<uint4*>(&g_st[2 * rb + w][hg][0]) + lane, T ^ 1, T ^ 1, T ^ 1, T ^ 1);
        if (lane < 8) st_rlx4(&g_o[2 * rb + w][hg][lane >> 1][3][30 + (lane & 1)], T ^ 1, T ^ 1, T ^ 1, T ^ 1);
        st_rlx4(&g_part[2 * rb3 + w][(jf & 1) * 4 + (lane >> 3)][jf >> 1][(lane >> 1) & 3][3][30 + (lane & 1)], T ^ 1, T ^ 1, T ^ 1, T ^ 1);
        if (lane < 8) st_rlx4(&g_hh[2 * rb3 + w][jf][7][lane >> 1][30 + (lane & 1)], T ^ 1, T ^ 1, T ^ 1, T ^ 1);
#pragma unroll 1
        for (int i = 0; i < 12; i++) st_rlx4(&g_hh[2 * rb3 + w][jf][8][0][lane] + i * 32, T ^ 1, T ^ 1, T ^ 1, T ^ 1);
        if (w == 0) {
          mbar_wait(sb + SM_FULL + (ST_WQ + 2) * 8);
          unsigned v; int it = 0;
#pragma unroll 1
          do {
            asm volatile("ld.acquire.gpu.global.u32 %0, [%1];" : "=r"(v) : "l"(&g_kvcnt[hg * 32 + 1]) : "memory");
          } while ((int)(v - (epoch + 1) * 16) < 0 && ++it < (1 << 18));
          asm volatile("fence.proxy.async.global;" ::: "memory");
        }
        bar_sync(6, 320);
        if (w == 0 && elect_one()) {
          asm volatile("cp.reduce.async.bulk.global.shared::cta.bulk_group.add.f32 [%0], [%1], 8704;"
                       ::"l"(&g_kv[hg][0]), "r"(sb + 2 * SLOT) : "memory");
          asm volatile("cp.async.bulk.commit_group;" ::: "memory");
          asm volatile("cp.async.bulk.wait_group 0;" ::: "memory");
          asm volatile("red.relaxed.gpu.global.add.u32 [%0], 1;" ::"l"(&g_kvcnt[hg * 32]) : "memory");
          TS2(0, 25);
        }
        __syncwarp();
        mbar_wait(sb + SM_KVB);
        if (w == 0) { mbar_wait(sb + SM_EMPTY + 11 * 8); mbar_wait(sb + SM_EMPTY + 12 * 8); mbar_wait(sb + SM_EMPTY + 13 * 8); }
#pragma unroll 1
        for (int ph = 0; ph < 2; ph++) {
          const int use = 2 * ph + w, r = ph ? 2 * rb3 + w : 2 * rb + w;
          const uint32_t* pw = ph ? reinterpret_cast<const uint32_t*>(&g_st[r][lane >> 2][(lane & 3) * 16 + 15])
                                  : reinterpret_cast<const uint32_t*>(&g_o[r][lane >> 2][lane & 3][3][31]);
          const char* src = reinterpret_cast<const char*>(ph ? &g_h[r][0][0][0][0] : &g_o[r][0][0][0][0]);
          const uint32_t bf = sb + SM_XF + use * 32, be = sb + SM_XE + (use - 1) * 32;
          bar_sync(10 + w, 160);
          int it = 0;
#pragma unroll 1
          for (bool miss = true; __any_sync(0xffffffffu, miss) && ++it < (1 << 18);) { if (miss) miss = (ld_rlx1(pw) ^ T) & 1; }
          if (elect_one()) {
            TS2(w, 27 + ph);
            if (use > 0) mbar_wait(be);
            if (ph) bulk_g2s(sb + SM_KV32 + w * 4096, &g_st[r][0][0], 4096, bf);
#pragma unroll
            for (int p = 0; p < 4; p++) {
              if (p > 0 && use > 0) mbar_wait(be + p * 8);
              bulk_g2s(sb + 2 * SLOT + p * 16384, src + p * 16384, 16384, bf + p * 8);
            }
          }
          __syncwarp();
        }
        {
          const int m = jf >> 1, oc = (jf & 1) * 4 + m;
          const uint32_t* pw = reinterpret_cast<const uint32_t*>(&g_part[2 * rb3 + w][oc][(m - 1 - (lane >> 2)) & 3][lane & 3][3][31]);
          bar_sync(12, 320);
          bool miss = lane < 12; int it = 0;
#pragma unroll 1
          for (int q = 0; q < 3; q++) {
#pragma unroll 1
            while ((__ballot_sync(0xffffffffu, miss) >> (4 * q) & 15) && ++it < (1 << 18)) { if (miss && (lane >> 2) <= q + 1) miss = (ld_rlx1(pw) ^ T) & 1; }
            if (elect_one()) {
              const uint32_t bar = sb + SM_XF + (w * 4 + q) * 8;
              mbar_expect_tx(bar, 8192);
              if (q == 2) TS2(w, 17);
              bulk_g2s(sb + ((ST_D % NSLOT) + w) * SLOT + q * 8192, &g_part[2 * rb3 + w][oc][(m - 1 - q) & 3][0][0][0], 8192, bar);
            }
            __syncwarp();
          }
        }
      }
    }
    asm volatile("barrier.cluster.arrive.relaxed.aligned;" ::: "memory");
    asm volatile("barrier.cluster.wait.aligned;" ::: "memory");
  }
}

typedef CUresult (*EncodeFn)(CUtensorMap*, CUtensorMapDataType, cuuint32_t, void*, const cuuint64_t*, const cuuint64_t*,
                             const cuuint32_t*, const cuuint32_t*, CUtensorMapInterleave, CUtensorMapSwizzle,
                             CUtensorMapL2promotion, CUtensorMapFloatOOBfill);

void encode(EncodeFn fn, CUtensorMap* m, const void* base, int rank, const cuuint64_t* dims, const cuuint64_t* strides,
            const cuuint32_t* box) {
  cuuint32_t es[3] = {1, 1, 1};
  fn(m, CU_TENSOR_MAP_DATA_TYPE_BFLOAT16, (cuuint32_t)rank, const_cast<void*>(base), dims, strides, box, es,
     CU_TENSOR_MAP_INTERLEAVE_NONE, CU_TENSOR_MAP_SWIZZLE_128B, CU_TENSOR_MAP_L2_PROMOTION_L2_256B,
     CU_TENSOR_MAP_FLOAT_OOB_FILL_NONE);
}

}

extern "C" void kernel_launch(void* const* d_in, const int* in_sizes, int n_in, void* d_out, int out_size) {
  (void)in_sizes; (void)n_in; (void)out_size;
  const __nv_bfloat16* x    = (const __nv_bfloat16*)d_in[0];
  const __nv_bfloat16* wqkv = (const __nv_bfloat16*)d_in[1];
  const __nv_bfloat16* wphi = (const __nv_bfloat16*)d_in[2];
  const __nv_bfloat16* wo   = (const __nv_bfloat16*)d_in[3];
  const __nv_bfloat16* wg   = (const __nv_bfloat16*)d_in[5];
  const __nv_bfloat16* wu   = (const __nv_bfloat16*)d_in[6];
  const __nv_bfloat16* wd   = (const __nv_bfloat16*)d_in[7];

  static EncodeFn fn = nullptr;
  if (!fn) {
    void* p = nullptr;
    cudaDriverEntryPointQueryResult qr;
    cudaGetDriverEntryPoint("cuTensorMapEncodeTiled", &p, cudaEnableDefault, &qr);
    fn = (EncodeFn)p;
    cudaFuncSetAttribute(fused_kernel, cudaFuncAttributeMaxDynamicSharedMemorySize, SM_TOTAL);
  }
  Maps maps;
  {
    cuuint64_t d[3] = {64, 2048, 8}, s[2] = {1024, 128}; cuuint32_t b[3] = {64, 64, 3};
    encode(fn, &maps.x, x, 3, d, s, b);
  }
  {
    cuuint64_t d[2] = {1536, 512}, s[1] = {3072}; cuuint32_t b[2] = {64, 192};
    encode(fn, &maps.w, wqkv, 2, d, s, b);
  }
  {
    cuuint64_t d[2] = {512, 512}, s[1] = {1024}; cuuint32_t b[2] = {64, 192};
    encode(fn, &maps.wo, wo, 2, d, s, b);
  }
  {
    cuuint64_t d[3] = {176, 7, 512}, d7[3] = {144, 1, 512}, s[2] = {352, 2752}; cuuint32_t b[3] = {64, 1, 32};
    encode(fn, &maps.g, wg, 3, d, s, b);
    encode(fn, &maps.u, wu, 3, d, s, b);
    encode(fn, &maps.g7, wg + 1232, 3, d7, s, b);
    encode(fn, &maps.u7, wu + 1232, 3, d7, s, b);
  }
  {
    cuuint64_t d[2] = {512, 1376}, s[1] = {1024}; cuuint32_t b[2] = {64, 176};
    encode(fn, &maps.d, wd, 2, d, s, b);
  }
  fused_kernel<<<NCTA, 384, SM_TOTAL>>>(maps, x, wphi, wo, wg, wu, wd, (__nv_bfloat16*)d_out);
}
```

```cpp
#include <cuda_runtime.h>
#include <cuda_bf16.h>
#include <cuda.h>
#include <stdint.h>

#define SAFE_WAIT 0

namespace {

constexpr int NCTA   = 128;
constexpr int SLOT   = 24576;
constexpr int NSLOT  = 9;
constexpr int NSTAGE = 47;

constexpr int ST_X0   = 0;
constexpr int ST_WK   = 3;
constexpr int ST_X1   = 6;
constexpr int ST_SCR0 = 9;
constexpr int ST_WV   = 10;
constexpr int ST_SCR1 = 13;
constexpr int ST_WQ   = 14;
constexpr int ST_WO   = 17;
constexpr int ST_XC   = 20;
constexpr int ST_GU   = 23;
constexpr int ST_D    = 39;

__host__ __device__ constexpr int st_empty_cnt(int d) {
  return ((d < 3 || (d >= 6 && d < 9) || (d >= ST_XC && d < ST_GU)) ? 4 : 2) * (d + 9 >= ST_GU ? 2 : 1);
}

constexpr uint32_t SM_BASE = 1024;
constexpr int SM_ONES = NSLOT * SLOT;
constexpr int SM_WPHI = SM_ONES + 2048;
constexpr int SM_KVS  = SM_WPHI + 2048;
constexpr int SM_KV32 = 4 * SLOT + 16384;
constexpr int SM_BAR  = SM_KVS + 6144;
constexpr int SM_FULL  = SM_BAR;
constexpr int SM_EMPTY = SM_BAR + NSTAGE * 8;
constexpr int SM_MISCB = SM_BAR + 2 * NSTAGE * 8;
constexpr int SM_KVB   = SM_MISCB + 8;
constexpr int SM_EPOCH = SM_KVB + 8;
constexpr int SM_XF    = SM_EPOCH + 8;
constexpr int SM_XE    = SM_XF + 16 * 8;
constexpr int SM_TOTAL = SM_BAR + 1024;

static_assert(SM_TOTAL == 232448 && SM_XE + 12 * 8 <= SM_TOTAL, "smem budget");

struct Maps { CUtensorMap x, w, wo, g, u, g7, u7, d; };

__device__ __align__(128) uint4    g_o[32][8][4][4][32];
__device__ __align__(128) uint4    g_h[32][8][4][4][32];
__device__ __align__(128) uint32_t g_hx[32][8][4][32];
__device__ __align__(128) uint2    g_st[32][8][64];
__device__ __align__(128) uint4    g_hh[32][8][11][4][32];
__device__ __align__(128) uint4    g_part[32][8][4][4][4][32];
__device__ __align__(128) float g_kv[8][2048 + 128];
__device__ __align__(128) unsigned g_kvcnt[8 * 32];
__device__ unsigned g_start;

__device__ __forceinline__ uint32_t smem_u32(const void* p) { return (uint32_t)__cvta_generic_to_shared(p); }
__device__ __forceinline__ void mbar_init(uint32_t bar, int cnt) {
  asm volatile("mbarrier.init.shared::cta.b64 [%0], %1;" ::"r"(bar), "r"(cnt) : "memory");
}
__device__ __forceinline__ void mbar_expect_tx(uint32_t bar, uint32_t bytes) {
  asm volatile("mbarrier.arrive.expect_tx.shared::cta.b64 _, [%0], %1;" ::"r"(bar), "r"(bytes) : "memory");
}
__device__ __forceinline__ void mbar_arrive(uint32_t bar) {
  asm volatile("mbarrier.arrive.shared::cta.b64 _, [%0];" ::"r"(bar) : "memory");
}
__device__ __forceinline__ void mbar_arrive_cluster(uint32_t bar, uint32_t rank) {
  asm volatile("{\n.reg .b32 ra;\nmapa.shared::cluster.u32 ra, %0, %1;\n"
               "mbarrier.arrive.shared::cluster.b64 _, [ra];\n}" ::"r"(bar), "r"(rank) : "memory");
}
__device__ __forceinline__ void mbar_wait_p(uint32_t bar, uint32_t parity) {
  asm volatile("{\n.reg .pred p;\nW: mbarrier.try_wait.parity.shared::cta.b64 p, [%0], %1;\n@!p bra W;\n}" ::"r"(bar), "r"(parity) : "memory");
}
__device__ __forceinline__ void mbar_wait(uint32_t bar) { mbar_wait_p(bar, 0); }
__device__ __forceinline__ bool elect_one() {
  uint32_t p;
  asm volatile("{\n.reg .pred P;\nelect.sync _|P, 0xffffffff;\nselp.u32 %0, 1, 0, P;\n}" : "=r"(p));
  return p != 0;
}
__device__ __forceinline__ void bar_sync(int id, int n)   { asm volatile("bar.sync %0, %1;" ::"r"(id), "r"(n) : "memory"); }
__device__ __forceinline__ void bar_arrive(int id, int n) { asm volatile("bar.arrive %0, %1;" ::"r"(id), "r"(n) : "memory"); }
__device__ __forceinline__ void fence_async_smem() { asm volatile("fence.proxy.async.shared::cta;" ::: "memory"); }
__device__ __forceinline__ void wg_fence()  { asm volatile("wgmma.fence.sync.aligned;" ::: "memory"); }
__device__ __forceinline__ void wg_commit() { asm volatile("wgmma.commit_group.sync.aligned;" ::: "memory"); }
template <int N> __device__ __forceinline__ void wg_wait() { asm volatile("wgmma.wait_group.sync.aligned %0;" ::"n"(N) : "memory"); }
#define DESC(off) (db + ((uint32_t)(off) >> 4))
__device__ __forceinline__ void tma2d(uint32_t dst, const CUtensorMap* m, int c0, int c1, uint32_t bar) {
  asm volatile("cp.async.bulk.tensor.2d.shared::cluster.global.mbarrier::complete_tx::bytes [%0], [%1, {%3, %4}], [%2];"
               ::"r"(dst), "l"(m), "r"(bar), "r"(c0), "r"(c1) : "memory");
}
__device__ __forceinline__ void tma2d_mc(uint32_t dst, const CUtensorMap* m, int c0, int c1, uint32_t bar) {
  asm volatile("cp.async.bulk.tensor.2d.shared::cluster.global.mbarrier::complete_tx::bytes.multicast::cluster [%0], [%1, {%3, %4}], [%2], %5;"
               ::"r"(dst), "l"(m), "r"(bar), "r"(c0), "r"(c1), "h"((uint16_t)3) : "memory");
}
__device__ __forceinline__ void tma3d(uint32_t dst, const CUtensorMap* m, int c0, int c1, int c2, uint32_t bar) {
  asm volatile("cp.async.bulk.tensor.3d.shared::cluster.global.mbarrier::complete_tx::bytes [%0], [%1, {%3, %4, %5}], [%2];"
               ::"r"(dst), "l"(m), "r"(bar), "r"(c0), "r"(c1), "r"(c2) : "memory");
}
__device__ __forceinline__ void tma3d_mc(uint32_t dst, const CUtensorMap* m, int c0, int c1, int c2, uint32_t bar) {
  asm volatile("cp.async.bulk.tensor.3d.shared::cluster.global.mbarrier::complete_tx::bytes.multicast::cluster [%0], [%1, {%3, %4, %5}], [%2], %6;"
               ::"r"(dst), "l"(m), "r"(bar), "r"(c0), "r"(c1), "r"(c2), "h"((uint16_t)3) : "memory");
}
__device__ __forceinline__ void ldsm4(uint32_t (&r)[4], uint32_t addr) {
  asm volatile("ldmatrix.sync.aligned.m8n8.x4.shared.b16 {%0,%1,%2,%3}, [%4];"
               : "=r"(r[0]), "=r"(r[1]), "=r"(r[2]), "=r"(r[3]) : "r"(addr) : "memory");
}
__device__ __forceinline__ void ldsm4t(uint32_t (&r)[4], uint32_t addr) {
  asm volatile("ldmatrix.sync.aligned.m8n8.x4.trans.shared.b16 {%0,%1,%2,%3}, [%4];"
               : "=r"(r[0]), "=r"(r[1]), "=r"(r[2]), "=r"(r[3]) : "r"(addr) : "memory");
}
__device__ __forceinline__ void stsm4(uint32_t addr, uint32_t r0, uint32_t r1, uint32_t r2, uint32_t r3) {
  asm volatile("stmatrix.sync.aligned.m8n8.x4.shared.b16 [%0], {%1,%2,%3,%4};"
               ::"r"(addr), "r"(r0), "r"(r1), "r"(r2), "r"(r3) : "memory");
}
__device__ __forceinline__ void mma16816(float (&c)[4], const uint32_t (&a)[4], uint32_t b0, uint32_t b1) {
  asm volatile("mma.sync.aligned.m16n8k16.row.col.f32.bf16.bf16.f32 {%0,%1,%2,%3},{%4,%5,%6,%7},{%8,%9},{%0,%1,%2,%3};"
               : "+f"(c[0]), "+f"(c[1]), "+f"(c[2]), "+f"(c[3])
               : "r"(a[0]), "r"(a[1]), "r"(a[2]), "r"(a[3]), "r"(b0), "r"(b1));
}
__device__ __forceinline__ void add_frag(float (&c)[32], const uint32_t (&a)[4][4], uint32_t id) {
#pragma unroll
  for (int i = 0; i < 8; i++)
    asm volatile("mma.sync.aligned.m16n8k8.row.col.f32.bf16.bf16.f32 {%0,%1,%2,%3},{%4,%5},{%6},{%0,%1,%2,%3};"
                 : "+f"(c[4 * i]), "+f"(c[4 * i + 1]), "+f"(c[4 * i + 2]), "+f"(c[4 * i + 3])
                 : "r"(a[i >> 1][(i & 1) * 2]), "r"(a[i >> 1][(i & 1) * 2 + 1]), "r"(id));
}
__device__ __forceinline__ uint32_t pack2(float lo, float hi) {
  uint32_t r; asm("cvt.rn.bf16x2.f32 %0, %1, %2;" : "=r"(r) : "f"(hi), "f"(lo)); return r;
}
__device__ __forceinline__ float blo(uint32_t w) { return __uint_as_float(w << 16); }
__device__ __forceinline__ float bhi(uint32_t w) { return __uint_as_float(w & 0xFFFF0000u); }
__device__ __forceinline__ uint32_t hsub2(uint32_t a, uint32_t b) { uint32_t r; asm("sub.rn.bf16x2 %0, %1, %2;" : "=r"(r) : "r"(a), "r"(b)); return r; }
__device__ __forceinline__ uint32_t hmax2(uint32_t a, uint32_t b) { uint32_t r; asm("max.bf16x2 %0, %1, %2;" : "=r"(r) : "r"(a), "r"(b)); return r; }
__device__ __forceinline__ uint32_t hmin2(uint32_t a, uint32_t b) { uint32_t r; asm("min.bf16x2 %0, %1, %2;" : "=r"(r) : "r"(a), "r"(b)); return r; }
__device__ __forceinline__ float ex2(float x) { float r; asm("ex2.approx.ftz.f32 %0, %1;" : "=f"(r) : "f"(x)); return r; }
__device__ __forceinline__ float rcp(float x) { float r; asm("rcp.approx.ftz.f32 %0, %1;" : "=f"(r) : "f"(x)); return r; }
__device__ __forceinline__ void ld_rlx4(uint32_t (&r)[4], const uint4* p) {
  asm volatile("{\n.reg .b128 v;\nld.relaxed.gpu.global.b128 v, [%4];\nmov.b128 {%0,%1,%2,%3}, v;\n}"
               : "=r"(r[0]), "=r"(r[1]), "=r"(r[2]), "=r"(r[3]) : "l"(p) : "memory");
}
__device__ __forceinline__ void st_rlx4(uint4* p, uint32_t a, uint32_t b, uint32_t c, uint32_t d) {
  asm volatile("st.relaxed.gpu.global.v4.b32 [%0], {%1,%2,%3,%4};" ::"l"(p), "r"(a), "r"(b), "r"(c), "r"(d) : "memory");
}
__device__ __forceinline__ void st_rlx2(uint2* p, uint32_t a, uint32_t b) {
  asm volatile("{\n.reg .b64 v;\nmov.b64 v, {%1,%2};\nst.relaxed.gpu.global.b64 [%0], v;\n}" ::"l"(p), "r"(a), "r"(b) : "memory");
}
__device__ __forceinline__ uint32_t ld_rlx1(const uint32_t* p) {
  uint32_t r; asm volatile("ld.relaxed.gpu.global.b32 %0, [%1];" : "=r"(r) : "l"(p) : "memory"); return r;
}
__device__ __forceinline__ void st_rlx1(uint32_t* p, uint32_t a) {
  asm volatile("st.relaxed.gpu.global.b32 [%0], %1;" ::"l"(p), "r"(a) : "memory");
}
__device__ __forceinline__ void ld_rlx2(uint32_t& a, uint32_t& b, const uint2* p) {
  asm volatile("{\n.reg .b64 v;\nld.relaxed.gpu.b64 v, [%2];\nmov.b64 {%0,%1}, v;\n}" : "=r"(a), "=r"(b) : "l"(p) : "memory");
}
__device__ __forceinline__ void bulk_g2s(uint32_t dst, const void* src, uint32_t bytes, uint32_t bar) {
  asm volatile("cp.async.bulk.shared::cluster.global.mbarrier::complete_tx::bytes [%0], [%1], %2, [%3];"
               ::"r"(dst), "l"(src), "r"(bytes), "r"(bar) : "memory");
}
__device__ __forceinline__ uint32_t tg(uint32_t w, uint32_t T) { return (w & 0xFFFFFFFEu) | T; }
__device__ __forceinline__ uint32_t bad4(uint32_t a, uint32_t b, uint32_t c, uint32_t d, uint32_t T) {
  uint32_t u, v;
  asm("lop3.b32 %0, %1, %2, %3, 0x7E;" : "=r"(u) : "r"(a), "r"(b), "r"(T));
  asm("lop3.b32 %0, %1, %2, %3, 0x7E;" : "=r"(v) : "r"(c), "r"(d), "r"(T));
  asm("lop3.b32 %0, %1, %2, 1, 0xA8;" : "=r"(u) : "r"(u), "r"(v));
  return u;
}

__device__ __forceinline__ void ld_chunk(uint32_t (&a)[4][4], const uint4* p) {
#pragma unroll
  for (int s = 0; s < 4; s++) ld_rlx4(a[s], p + s * 32);
}
__device__ __forceinline__ void get_pair(uint32_t (&a)[4][4], uint32_t (&b)[4][4], const uint4* sp, const uint4* gp, uint32_t T) {
  int it = 0;
#pragma unroll 1
  do {
#pragma unroll
    for (int s = 0; s < 8; s++) {
      uint32_t (&r)[4] = s < 4 ? a[s & 3] : b[s & 3];
      asm volatile("{\n.reg .b128 v;\nld.relaxed.gpu.b128 v, [%4];\nmov.b128 {%0,%1,%2,%3}, v;\n}"
                   : "=r"(r[0]), "=r"(r[1]), "=r"(r[2]), "=r"(r[3]) : "l"(sp + (s >> 2) * 512 + (s & 3) * 32) : "memory");
    }
    sp = gp;
  } while (__any_sync(0xffffffffu, bad4(a[0][0], a[1][0], a[2][0], a[3][0], T) | bad4(b[0][0], b[1][0], b[2][0], b[3][0], T)) && ++it < (1 << 18));
}

__device__ __forceinline__ void wgmma_rs_n48(float (&d)[24], const uint32_t (&a)[4], uint32_t descB, int scaleD) {
  asm volatile("{\n.reg .pred p;\n.reg .b64 db;\nsetp.ne.b32 p, %29, 0;\nmov.b64 db, {%28, 0x40000040};\n"
    "wgmma.mma_async.sync.aligned.m64n48k16.f32.bf16.bf16 {%0,%1,%2,%3,%4,%5,%6,%7,%8,%9,%10,%11,%12,%13,%14,%15,%16,%17,%18,%19,%20,%21,%22,%23}, {%24,%25,%26,%27}, db, p, 1, 1, 1;\n}\n"
    : "+f"(d[0]),"+f"(d[1]),"+f"(d[2]),"+f"(d[3]),"+f"(d[4]),"+f"(d[5]),"+f"(d[6]),"+f"(d[7]),"+f"(d[8]),"+f"(d[9]),"+f"(d[10]),"+f"(d[11]),"+f"(d[12]),"+f"(d[13]),"+f"(d[14]),"+f"(d[15]),"+f"(d[16]),"+f"(d[17]),"+f"(d[18]),"+f"(d[19]),"+f"(d[20]),"+f"(d[21]),"+f"(d[22]),"+f"(d[23])
    : "r"(a[0]), "r"(a[1]), "r"(a[2]), "r"(a[3]), "r"(descB), "r"(scaleD));
}
__device__ __forceinline__ void wgmma_rs_n64(float (&d)[32], const uint32_t (&a)[4], uint32_t descB, int scaleD) {
  asm volatile("{\n.reg .pred p;\n.reg .b64 db;\nsetp.ne.b32 p, %37, 0;\nmov.b64 db, {%36, 0x40000040};\n"
    "wgmma.mma_async.sync.aligned.m64n64k16.f32.bf16.bf16 {%0,%1,%2,%3,%4,%5,%6,%7,%8,%9,%10,%11,%12,%13,%14,%15,%16,%17,%18,%19,%20,%21,%22,%23,%24,%25,%26,%27,%28,%29,%30,%31}, {%32,%33,%34,%35}, db, p, 1, 1, 1;\n}\n"
    : "+f"(d[0]),"+f"(d[1]),"+f"(d[2]),"+f"(d[3]),"+f"(d[4]),"+f"(d[5]),"+f"(d[6]),"+f"(d[7]),"+f"(d[8]),"+f"(d[9]),"+f"(d[10]),"+f"(d[11]),"+f"(d[12]),"+f"(d[13]),"+f"(d[14]),"+f"(d[15]),"+f"(d[16]),"+f"(d[17]),"+f"(d[18]),"+f"(d[19]),"+f"(d[20]),"+f"(d[21]),"+f"(d[22]),"+f"(d[23]),"+f"(d[24]),"+f"(d[25]),"+f"(d[26]),"+f"(d[27]),"+f"(d[28]),"+f"(d[29]),"+f"(d[30]),"+f"(d[31])
    : "r"(a[0]), "r"(a[1]), "r"(a[2]), "r"(a[3]), "r"(descB), "r"(scaleD));
}
__device__ __forceinline__ void wgmma_rs_n128(float (&d)[64], const uint32_t (&a)[4], uint32_t descB, int scaleD) {
  asm volatile("{\n.reg .pred p;\n.reg .b64 db;\nsetp.ne.b32 p, %69, 0;\nmov.b64 db, {%68, 0x40000040};\n"
    "wgmma.mma_async.sync.aligned.m64n128k16.f32.bf16.bf16 {%0,%1,%2,%3,%4,%5,%6,%7,%8,%9,%10,%11,%12,%13,%14,%15,%16,%17,%18,%19,%20,%21,%22,%23,%24,%25,%26,%27,%28,%29,%30,%31,%32,%33,%34,%35,%36,%37,%38,%39,%40,%41,%42,%43,%44,%45,%46,%47,%48,%49,%50,%51,%52,%53,%54,%55,%56,%57,%58,%59,%60,%61,%62,%63}, {%64,%65,%66,%67}, db, p, 1, 1, 1;\n}\n"
    : "+f"(d[0]),"+f"(d[1]),"+f"(d[2]),"+f"(d[3]),"+f"(d[4]),"+f"(d[5]),"+f"(d[6]),"+f"(d[7]),"+f"(d[8]),"+f"(d[9]),"+f"(d[10]),"+f"(d[11]),"+f"(d[12]),"+f"(d[13]),"+f"(d[14]),"+f"(d[15]),"+f"(d[16]),"+f"(d[17]),"+f"(d[18]),"+f"(d[19]),"+f"(d[20]),"+f"(d[21]),"+f"(d[22]),"+f"(d[23]),"+f"(d[24]),"+f"(d[25]),"+f"(d[26]),"+f"(d[27]),"+f"(d[28]),"+f"(d[29]),"+f"(d[30]),"+f"(d[31]),"+f"(d[32]),"+f"(d[33]),"+f"(d[34]),"+f"(d[35]),"+f"(d[36]),"+f"(d[37]),"+f"(d[38]),"+f"(d[39]),"+f"(d[40]),"+f"(d[41]),"+f"(d[42]),"+f"(d[43]),"+f"(d[44]),"+f"(d[45]),"+f"(d[46]),"+f"(d[47]),"+f"(d[48]),"+f"(d[49]),"+f"(d[50]),"+f"(d[51]),"+f"(d[52]),"+f"(d[53]),"+f"(d[54]),"+f"(d[55]),"+f"(d[56]),"+f"(d[57]),"+f"(d[58]),"+f"(d[59]),"+f"(d[60]),"+f"(d[61]),"+f"(d[62]),"+f"(d[63])
    : "r"(a[0]), "r"(a[1]), "r"(a[2]), "r"(a[3]), "r"(descB), "r"(scaleD));
}
__device__ __forceinline__ void wgmma_ss_n72_t11(float (&d)[36], uint32_t descA, uint32_t descB, int scaleD) {
  asm volatile("{\n.reg .pred p;\n.reg .b64 da, db;\nsetp.ne.b32 p, %38, 0;\nmov.b64 da, {%36, 0x40000040};\nmov.b64 db, {%37, 0x40000040};\n"
    "wgmma.mma_async.sync.aligned.m64n72k16.f32.bf16.bf16 {%0,%1,%2,%3,%4,%5,%6,%7,%8,%9,%10,%11,%12,%13,%14,%15,%16,%17,%18,%19,%20,%21,%22,%23,%24,%25,%26,%27,%28,%29,%30,%31,%32,%33,%34,%35}, da, db, p, 1, 1, 1, 1;\n}\n"
    : "+f"(d[0]),"+f"(d[1]),"+f"(d[2]),"+f"(d[3]),"+f"(d[4]),"+f"(d[5]),"+f"(d[6]),"+f"(d[7]),"+f"(d[8]),"+f"(d[9]),"+f"(d[10]),"+f"(d[11]),"+f"(d[12]),"+f"(d[13]),"+f"(d[14]),"+f"(d[15]),"+f"(d[16]),"+f"(d[17]),"+f"(d[18]),"+f"(d[19]),"+f"(d[20]),"+f"(d[21]),"+f"(d[22]),"+f"(d[23]),"+f"(d[24]),"+f"(d[25]),"+f"(d[26]),"+f"(d[27]),"+f"(d[28]),"+f"(d[29]),"+f"(d[30]),"+f"(d[31]),"+f"(d[32]),"+f"(d[33]),"+f"(d[34]),"+f"(d[35])
    : "r"(descA), "r"(descB), "r"(scaleD));
}

constexpr float LOG2E = 1.4426950408889634f;

__device__ __forceinline__ void feat_exp(const uint32_t (&P)[4], float (&e)[16]) {
  uint32_t a = hmax2(P[0], P[2]), b = hmax2(P[1], P[3]);
  uint32_t mx = hmax2(__byte_perm(a, b, 0x5410), __byte_perm(a, b, 0x7632));
  a = hmin2(P[0], P[2]); b = hmin2(P[1], P[3]);
  uint32_t mn = hmin2(__byte_perm(a, b, 0x5410), __byte_perm(a, b, 0x7632));
  mx = hmax2(mx, __shfl_xor_sync(0xffffffffu, mx, 1));
  mn = hmin2(mn, __shfl_xor_sync(0xffffffffu, mn, 1));
  mx = hmax2(mx, __shfl_xor_sync(0xffffffffu, mx, 2));
  mn = hmin2(mn, __shfl_xor_sync(0xffffffffu, mn, 2));
  float mx0 = -blo(mx) * LOG2E, mx1 = -bhi(mx) * LOG2E, mn0 = blo(mn) * LOG2E, mn1 = bhi(mn) * LOG2E;
  float v[8] = {blo(P[0]), bhi(P[0]), blo(P[1]), bhi(P[1]), blo(P[2]), bhi(P[2]), blo(P[3]), bhi(P[3])};
#pragma unroll
  for (int i = 0; i < 8; i++) {
    bool r1 = (i >> 1) & 1;
    e[i]     = ex2(fmaf(v[i],  LOG2E, r1 ? mx1 : mx0));
    e[8 + i] = ex2(fmaf(v[i], -LOG2E, r1 ? mn1 : mn0));
  }
}

__global__ void __cluster_dims__(2, 1, 1) __launch_bounds__(384, 1)
fused_kernel(const __grid_constant__ Maps maps, const __nv_bfloat16* __restrict__ x, const __nv_bfloat16* __restrict__ wphi,
             const __nv_bfloat16* __restrict__ wo, const __nv_bfloat16* __restrict__ wg_, const __nv_bfloat16* __restrict__ wu_,
             const __nv_bfloat16* __restrict__ wd_, __nv_bfloat16* __restrict__ out) {
  extern __shared__ __align__(1024) unsigned char smem[];
  const uint32_t sb = smem_u32(smem);
  const int tid = threadIdx.x, lane = tid & 31;
  const int warp = __shfl_sync(0xffffffffu, tid >> 5, 0);
  const uint32_t rank = blockIdx.x & 1;
  const int cl = blockIdx.x >> 1;
  int quad, qi;
  if (cl < 4) { quad = 15; qi = cl; }
  else if (cl < 36) { quad = (cl - 4) & 7; qi = (cl - 4) >> 3; }
  else { qi = (cl - 36) / 7; quad = 8 + (cl - 36) - 7 * qi; }
  const int rb = quad, hg = 2 * qi + rank;
  const int rb3 = (quad & ~1) + rank, jf = 4 * (quad & 1) + qi;

  if (warp < 8) {
    asm volatile("setmaxnreg.inc.sync.aligned.u32 240;");
    if (elect_one()) {
#pragma unroll 1
      for (int d = warp; d + 9 < NSTAGE; d += 8) {
        mbar_init(sb + SM_EMPTY + d * 8, st_empty_cnt(d));
        mbar_init(sb + SM_FULL + (d + 9) * 8, 1);
        mbar_expect_tx(sb + SM_FULL + (d + 9) * 8, d + 9 >= ST_D ? 22528 : SLOT);
      }
      asm volatile("fence.mbarrier_init.release.cluster;" ::: "memory");
    }
    __syncwarp();
    bar_sync(0, 352);
    asm volatile("barrier.cluster.arrive.relaxed.aligned;" ::: "memory");
    const int wg = warp >> 2, wq = warp & 3, g = lane >> 2, t = lane & 3;
    const bool lead = (tid & 127) == 0;
    constexpr uint32_t db = (SM_BASE >> 4) | (512u << 16);
    auto release = [&](int d) {
      const int s = d + NSLOT;
      mbar_arrive_cluster(sb + SM_EMPTY + d * 8, s >= ST_GU ? (uint32_t)(s & 1) : rank);
    };
    const uint32_t lrow = (uint32_t)(wq * 16 + (lane & 7) + ((lane >> 3) & 1) * 8) * 128;
    const uint32_t lx = lane & 7, lhi = lane >> 4;
    if (wg == 1) bar_arrive(4, 256);

    float r0, r1;
    uint32_t E[4][8];
    uint32_t T = 0;
    {
      uint32_t A[32][4];
      const int sx = wg ? ST_X1 : ST_X0;
      {
        const uint32_t base = sb + sx * SLOT + lrow, baseb = sb + sx * SLOT + (wq * 16 + lx + lhi * 8) * 128;
        float cs[2][4], c0[2][4], c1[2][4];
#pragma unroll
        for (int i = 0; i < 4; i++) { cs[0][i] = cs[1][i] = c0[0][i] = c0[1][i] = c1[0][i] = c1[1][i] = 0.f; }
        uint32_t bt[2][4][4];
        if (wg == 1) bar_sync(13, 256);
#pragma unroll
        for (int c = -1; c < 8; c++) {
          if (c < 7) {
            const int n = c + 1;
            if (n % 3 == 0) mbar_wait(sb + SM_FULL + (sx + n / 3) * 8);
#pragma unroll
            for (int k = 0; k < 4; k++) {
              ldsm4(A[4 * n + k], base + n * 8192 + (((2 * k + lhi) ^ lx) << 4));
              ldsm4(bt[n & 1][k], baseb + n * 8192 + (((2 * k + ((lane >> 3) & 1)) ^ lx) << 4));
            }
          }
          if (c >= 0) {
#pragma unroll
            for (int k = 0; k < 4; k++) {
              const uint32_t (&f)[4] = A[4 * c + k];
              mma16816(cs[k & 1], f, 0x3F803F80u, 0x3F803F80u);
              mma16816(c0[k & 1], f, bt[c & 1][k][0], bt[c & 1][k][1]);
              mma16816(c1[k & 1], f, bt[c & 1][k][2], bt[c & 1][k][3]);
            }
          }
        }
        if (wg == 0) bar_arrive(13, 256);
        const float s0 = (cs[0][0] + cs[1][0]) * (1.f / 512.f), s1 = (cs[0][2] + cs[1][2]) * (1.f / 512.f);
        asm volatile("barrier.cluster.wait.aligned;" ::: "memory");
        if (lane < 3) release(sx + lane);
        const uint32_t m0 = pack2(s0, s0), m1 = pack2(s1, s1);
        float q0 = (g & 1) ? c0[0][1] + c0[1][1] : c0[0][0] + c0[1][0];
        float q1 = (g & 1) ? c1[0][3] + c1[1][3] : c1[0][2] + c1[1][2];
        q0 = __shfl_sync(0xffffffffu, q0, (lane & ~3) | (g >> 1));
        q1 = __shfl_sync(0xffffffffu, q1, (lane & ~3) | (g >> 1));
        r0 = rsqrtf(fmaxf(q0 * (1.f / 512.f) - s0 * s0, 0.f) + 1e-5f);
        r1 = rsqrtf(fmaxf(q1 * (1.f / 512.f) - s1 * s1, 0.f) + 1e-5f);
#pragma unroll
        for (int ks = 0; ks < 32; ks++) {
          A[ks][0] = hsub2(A[ks][0], m0); A[ks][1] = hsub2(A[ks][1], m1);
          A[ks][2] = hsub2(A[ks][2], m0); A[ks][3] = hsub2(A[ks][3], m1);
        }
      }
      const uint32_t wpa = sb + SM_WPHI + ((lane & 7) + ((lane >> 3) & 1) * 8) * 32 + lhi * 16;
      const uint32_t scr = sb + (wg ? (ST_SCR1 % NSLOT) : (ST_SCR0 % NSLOT)) * SLOT;
#pragma unroll 1
      for (int ps = 0; ps < 3; ps++) {
        const int st0 = ps == 0 ? ST_WK : (ps == 1 ? ST_WV : ST_WQ);
        const uint32_t wdesc = DESC((ps == 0 ? ST_WK % NSLOT : (ps == 1 ? ST_WV % NSLOT : ST_WQ % NSLOT)) * SLOT);
        float acc[32];
        bar_sync(4 + wg, 256);
#pragma unroll
        for (int i = 0; i < 3; i++) {
          mbar_wait(sb + SM_FULL + (st0 + i) * 8);
          wg_fence();
#pragma unroll
          for (int kk = 0; kk < (i < 2 ? 12 : 8); kk++)
            wgmma_rs_n64(acc, A[12 * i + kk], wdesc + ((i * SLOT + kk * 2048) >> 4), (i | kk) != 0);
          wg_commit();
          if (i == 1) { wg_wait<1>(); if (lead) release(st0); }
        }
        if (ps == 1 && wg == 0) bar_arrive(5, 256);
        uint32_t a[4][4], b[4][4];
        mbar_wait(sb + SM_MISCB);
        T = (*reinterpret_cast<volatile unsigned*>(smem + SM_EPOCH) & 1) ^ 1;
#pragma unroll
        for (int h = 0; h < 4; h++) ldsm4t(b[h], wpa + h * 512);
        wg_wait<0>();
        if ((tid & 127) < 2) release(st0 + 1 + (tid & 1));
#pragma unroll
        for (int h = 0; h < 4; h++) {
          a[h][0] = pack2(acc[8 * h + 0] * r0, acc[8 * h + 1] * r0); a[h][1] = pack2(acc[8 * h + 2] * r1, acc[8 * h + 3] * r1);
          a[h][2] = pack2(acc[8 * h + 4] * r0, acc[8 * h + 5] * r0); a[h][3] = pack2(acc[8 * h + 6] * r1, acc[8 * h + 7] * r1);
        }
        if (ps != 1) {
          {
            float pp[4][2][4];
#pragma unroll
            for (int h = 0; h < 4; h++) {
#pragma unroll
              for (int i = 0; i < 4; i++) { pp[h][0][i] = 0.f; pp[h][1][i] = 0.f; }
              mma16816(pp[h][0], a[h], b[h][0], b[h][1]);
              mma16816(pp[h][1], a[h], b[h][2], b[h][3]);
            }
#pragma unroll
            for (int h = 0; h < 4; h++) {
              a[h][0] = pack2(pp[h][0][0], pp[h][0][1]); a[h][1] = pack2(pp[h][0][2], pp[h][0][3]);
              a[h][2] = pack2(pp[h][1][0], pp[h][1][1]); a[h][3] = pack2(pp[h][1][2], pp[h][1][3]);
            }
          }
          if (ps == 0 || wg == 0) bar_arrive(4 + (wg ^ 1), 256);
          if (ps == 0) mbar_wait(sb + SM_EMPTY + (wg ? ST_SCR1 - NSLOT : ST_SCR0 - NSLOT) * 8);
#pragma unroll 1
          for (int hp = 0; hp < 2; hp++) {
            float e[2][16];
            feat_exp(a[0], e[0]);
            feat_exp(a[1], e[1]);
            if (ps == 0) {
#pragma unroll
              for (int h = 0; h < 2; h++) {
                const float (&f)[16] = e[h];
                float sp0 = (f[0] + f[1]) + (f[4] + f[5]), sp1 = (f[2] + f[3]) + (f[6] + f[7]);
                float sn0 = (f[8] + f[9]) + (f[12] + f[13]), sn1 = (f[10] + f[11]) + (f[14] + f[15]);
                sp0 += __shfl_xor_sync(0xffffffffu, sp0, 1); sp1 += __shfl_xor_sync(0xffffffffu, sp1, 1);
                sn0 += __shfl_xor_sync(0xffffffffu, sn0, 1); sn1 += __shfl_xor_sync(0xffffffffu, sn1, 1);
                sp0 += __shfl_xor_sync(0xffffffffu, sp0, 2); sp1 += __shfl_xor_sync(0xffffffffu, sp1, 2);
                sn0 += __shfl_xor_sync(0xffffffffu, sn0, 2); sn1 += __shfl_xor_sync(0xffffffffu, sn1, 2);
                sp0 = rcp(sp0); sp1 = rcp(sp1); sn0 = rcp(sn0); sn1 = rcp(sn1);
                const uint32_t dst = scr + hp * 8192 + lrow;
                stsm4(dst + (((h * 4 + lhi) ^ lx) << 4), pack2(f[0] * sp0, f[1] * sp0), pack2(f[2] * sp1, f[3] * sp1),
                      pack2(f[4] * sp0, f[5] * sp0), pack2(f[6] * sp1, f[7] * sp1));
                stsm4(dst + (((h * 4 + 2 + lhi) ^ lx) << 4), pack2(f[8] * sn0, f[9] * sn0), pack2(f[10] * sn1, f[11] * sn1),
                      pack2(f[12] * sn0, f[13] * sn0), pack2(f[14] * sn1, f[15] * sn1));
              }
            } else {
#pragma unroll
              for (int i = 0; i < 16; i++) {
                A[i >> 2][i & 3] = A[4 + (i >> 2)][i & 3];
                A[4 + (i >> 2)][i & 3] = pack2(e[i >> 3][2 * (i & 7)], e[i >> 3][2 * (i & 7) + 1]);
              }
            }
#pragma unroll
            for (int i = 0; i < 4; i++) { a[0][i] = a[2][i]; a[1][i] = a[3][i]; }
          }
        } else {
#pragma unroll
          for (int h = 0; h < 4; h++) stsm4(scr + 16384 + lrow + (((2 * h + lhi) ^ lx) << 4), a[h][0], a[h][1], a[h][2], a[h][3]);
          fence_async_smem();
          bar_sync(3, 256);
          float kv[36];
          wg_fence();
#pragma unroll
          for (int ks = 0; ks < 8; ks++) {
            const uint32_t sk = (ks < 4 ? (ST_SCR0 % NSLOT) : (ST_SCR1 % NSLOT)) * SLOT + (ks & 3) * 2048;
            const uint32_t dv = (DESC(sk + 16384) & 0xFFFFu) | (((SM_ONES - sk - 16384) >> 4) << 16);
            wgmma_ss_n72_t11(kv, DESC(sk) + wg * 512, dv, ks != 0);
          }
          wg_commit();
          if (wg == 1) bar_arrive(4, 256);
          wg_wait<0>();
          if (lead) { mbar_arrive(sb + SM_EMPTY + ST_SCR0 * 8); mbar_arrive(sb + SM_EMPTY + ST_SCR1 * 8); }
          const int hl = 2 * wg + (wq >> 1), f = (wq & 1) * 16 + g;
          float* kvp = reinterpret_cast<float*>(smem + 2 * SLOT) + (hl * 32 + f) * 16 + 2 * t;
          float c[8];
#pragma unroll
          for (int i = 0; i < 8; i++) c[i] = hl >= 2 ? (hl == 3 ? kv[24 + i] : kv[16 + i]) : (hl == 1 ? kv[8 + i] : kv[i]);
#pragma unroll
          for (int n = 0; n < 2; n++) {
            *reinterpret_cast<float2*>(kvp + n * 8) = make_float2(c[4 * n], c[4 * n + 1]);
            *reinterpret_cast<float2*>(kvp + n * 8 + 128) = make_float2(c[4 * n + 2], c[4 * n + 3]);
          }
          if (t < 2) reinterpret_cast<float*>(smem + 2 * SLOT)[2048 + hl * 32 + f + t * 8] = t ? kv[34] : kv[32];
          fence_async_smem();
          bar_sync(6, 320);
        }
      }
#pragma unroll
      for (int i = 0; i < 32; i++) E[i >> 3][i & 7] = A[i >> 2][i & 3];
    }
    const int rh = 2 * rb + wg;
#define IDF ((g >> 1) == t ? ((g & 1) ? 0x3F800000u : 0x00003F80u) : 0u)
    const uint4* xb = reinterpret_cast<const uint4*>(smem + 2 * SLOT) + wq * 128 + lane;
    mbar_wait(sb + SM_KVB);
    {
      const int r = tid & 127;
      const float4* src = reinterpret_cast<const float4*>(smem + SM_KV32) + r;
#pragma unroll
      for (int i = 0; i < 4; i++) {
        const float4 a = src[i * 128];
        *reinterpret_cast<uint2*>(smem + SM_KVS + (i * 32 + (r >> 2)) * 48 + (r & 3) * 8) = make_uint2(pack2(a.x, a.y), pack2(a.z, a.w));
      }
      const uint32_t zz = pack2(reinterpret_cast<const float*>(smem + SM_ONES)[r], 1.0f);
      *reinterpret_cast<uint4*>(smem + SM_KVS + r * 48 + 32) = make_uint4(zz, zz, zz, zz);
      bar_sync(1 + wg, 128);
    }
    {
      uint4* op = &g_o[rh][hg][wq][0][lane];
      if (wg == 1) bar_sync(5, 256);
#pragma unroll 1
      for (int hp = 0; hp < 2; hp++) {
#pragma unroll
      for (int h = 0; h < 2; h++) {
        uint32_t b0[4], b1[4], b2[4];
        const uint32_t kb = sb + SM_KVS + ((2 * hp + h) * 32 + lane) * 48;
        ldsm4t(b0, kb); ldsm4t(b1, kb + 16); ldsm4t(b2, kb + 32);
        const uint32_t ep[4] = {E[h][0], E[h][1], E[h][2], E[h][3]}, en[4] = {E[h][4], E[h][5], E[h][6], E[h][7]};
        float np0[4] = {0, 0, 0, 0}, np1[4] = {0, 0, 0, 0}, nn0[4] = {0, 0, 0, 0}, nn1[4] = {0, 0, 0, 0}, dp[4] = {0, 0, 0, 0}, dn[4] = {0, 0, 0, 0};
        mma16816(dp, ep, b2[0], b2[1]);  mma16816(dn, en, b2[2], b2[3]);
        mma16816(np0, ep, b0[0], b0[1]); mma16816(nn0, en, b0[2], b0[3]);
        mma16816(np1, ep, b1[0], b1[1]); mma16816(nn1, en, b1[2], b1[3]);
        const float i0 = rcp(fmaf(dp[0], dn[1], fmaf(dn[0], dp[1], 1e-6f * dp[1] * dn[1])));
        const float i1 = rcp(fmaf(dp[2], dn[3], fmaf(dn[2], dp[3], 1e-6f * dp[3] * dn[3])));
        const float cp0 = dn[1] * i0, cn0 = dp[1] * i0, cp1 = dn[3] * i1, cn1 = dp[3] * i1;
        st_rlx4(op + (2 * hp + h) * 32,
                tg(pack2(fmaf(np0[0], cp0, nn0[0] * cn0), fmaf(np0[1], cp0, nn0[1] * cn0)), T),
                pack2(fmaf(np0[2], cp1, nn0[2] * cn1), fmaf(np0[3], cp1, nn0[3] * cn1)),
                pack2(fmaf(np1[0], cp0, nn1[0] * cn0), fmaf(np1[1], cp0, nn1[1] * cn0)),
                pack2(fmaf(np1[2], cp1, nn1[2] * cn1), fmaf(np1[3], cp1, nn1[3] * cn1)));
      }
#pragma unroll
        for (int i = 0; i < 8; i++) { E[0][i] = E[2][i]; E[1][i] = E[3][i]; }
      }
    }
    if (wg == 0) bar_arrive(5, 256);
    bar_arrive(10 + wg, 160);

    {
      uint32_t xr[4][4];
      {
        const uint32_t* xp = reinterpret_cast<const uint32_t*>(x + (size_t)(rh * 64 + wq * 16 + g) * 512 + hg * 64 + 2 * t);
#pragma unroll
        for (int i = 0; i < 8; i++) { xr[i >> 1][(i & 1) * 2] = __ldg(xp + 4 * i); xr[i >> 1][(i & 1) * 2 + 1] = __ldg(xp + 8 * 256 + 4 * i); }
      }
      uint32_t A[8][4][4];
      const uint4* op = &g_o[rh][0][wq][0][lane];
      float acc[32];
#pragma unroll
      for (int i = 0; i < 32; i++) acc[i] = 0.f;
      add_frag(acc, xr, IDF);
#pragma unroll
      for (int p = -1; p < 4; p++) {
        if (p < 3) {
          mbar_wait(sb + SM_XF + (wg * 4 + p + 1) * 8);
          get_pair(A[2 * p + 2], A[2 * p + 3], xb + (p + 1) * 1024, op + (p + 1) * 1024, T);
          if (lane == 0) mbar_arrive(sb + SM_XE + (wg * 4 + p + 1) * 8);
        }
        if (p == 0 && wg == 1) bar_sync(4, 256);
        if (p >= 0) {
          if (p != 2) mbar_wait(sb + SM_FULL + (ST_WO + (p + 1) / 2) * 8);
          wg_fence();
#pragma unroll
          for (int c = 2 * p; c < 2 * p + 2; c++)
#pragma unroll
            for (int s = 0; s < 4; s++)
              wgmma_rs_n64(acc, A[c][s], DESC(((ST_WO + c / 3) % NSLOT) * SLOT + ((c % 3) * 4 + s) * 2048), 1);
        }
      }
      wg_commit();
      if (wg == 0) bar_arrive(4, 256);
      wg_wait<0>();
      if ((tid & 127) < 3) release(ST_WO + (tid & 127));
      uint4* hp_ = &g_h[rh][hg][wq][0][lane];
      uint32_t hx = T;
#pragma unroll
      for (int s = 0; s < 4; s++) {
        const uint32_t h0 = pack2(acc[8 * s], acc[8 * s + 1]);
        st_rlx4(hp_ + s * 32, tg(h0, T), pack2(acc[8 * s + 2], acc[8 * s + 3]), pack2(acc[8 * s + 4], acc[8 * s + 5]), pack2(acc[8 * s + 6], acc[8 * s + 7]));
        hx |= (h0 & 1u) << (s + 1);
      }
      float s0 = 0.f, s1 = 0.f, q0 = 0.f, q1 = 0.f, q2 = 0.f, q3 = 0.f;
#pragma unroll
      for (int i = 0; i < 8; i++) {
        s0 += acc[4 * i] + acc[4 * i + 1]; s1 += acc[4 * i + 2] + acc[4 * i + 3];
        q0 = fmaf(acc[4 * i], acc[4 * i], q0); q2 = fmaf(acc[4 * i + 1], acc[4 * i + 1], q2);
        q1 = fmaf(acc[4 * i + 2], acc[4 * i + 2], q1); q3 = fmaf(acc[4 * i + 3], acc[4 * i + 3], q3);
      }
      q0 += q2; q1 += q3;
      {
        const bool up = t & 2;
        float s = (up ? s1 : s0) + __shfl_xor_sync(0xffffffffu, up ? s0 : s1, 2);
        float q = (up ? q1 : q0) + __shfl_xor_sync(0xffffffffu, up ? q0 : q1, 2);
        s += __shfl_xor_sync(0xffffffffu, s, 1);
        q += __shfl_xor_sync(0xffffffffu, q, 1);
        if (!(t & 1)) st_rlx2(&g_st[rh][hg][wq * 16 + g + (t >> 1) * 8], tg(__float_as_uint(s), T), __float_as_uint(q));
      }
      st_rlx1(&g_hx[rh][hg][wq][lane], hx);
    }
    bar_arrive(10 + wg, 160);

    const int rh3 = 2 * rb3 + wg;
    uint32_t HH[11][4], PH[11][4];
    const uint4* pp = &g_hh[rh3][jf ^ 1][0][wq][lane];
    {
      uint32_t A[8][4][4];
      const uint4* hp_ = &g_h[rh3][0][wq][0][lane];
      uint4* hhp = &g_hh[rh3][jf][0][wq][lane];
      const uint32_t dg = (db & 0xFFFFu) | (256u << 16);
      uint32_t m0, m1;
      mbar_wait(sb + SM_XF + ((2 + wg) * 4) * 8);
      {
        const uint2* sp = reinterpret_cast<const uint2*>(smem + SM_KV32 + wg * 4096) + 2 * t * 64 + wq * 16 + g;
        uint2 a0, a1, b0, b1;
        int it = 0;
#pragma unroll 1
        do {
          ld_rlx2(a0.x, a0.y, sp); ld_rlx2(a1.x, a1.y, sp + 64); ld_rlx2(b0.x, b0.y, sp + 8); ld_rlx2(b1.x, b1.y, sp + 72);
          sp = &g_st[rh3][2 * t][wq * 16 + g];
        } while (__any_sync(0xffffffffu, bad4(a0.x, a1.x, b0.x, b1.x, T)) && ++it < (1 << 18));
        float s0 = __uint_as_float(a0.x) + __uint_as_float(a1.x), q0 = __uint_as_float(a0.y) + __uint_as_float(a1.y);
        float s1 = __uint_as_float(b0.x) + __uint_as_float(b1.x), q1 = __uint_as_float(b0.y) + __uint_as_float(b1.y);
        s0 += __shfl_xor_sync(0xffffffffu, s0, 1); s1 += __shfl_xor_sync(0xffffffffu, s1, 1);
        q0 += __shfl_xor_sync(0xffffffffu, q0, 1); q1 += __shfl_xor_sync(0xffffffffu, q1, 1);
        s0 += __shfl_xor_sync(0xffffffffu, s0, 2); s1 += __shfl_xor_sync(0xffffffffu, s1, 2);
        q0 += __shfl_xor_sync(0xffffffffu, q0, 2); q1 += __shfl_xor_sync(0xffffffffu, q1, 2);
        s0 *= (1.f / 512.f); s1 *= (1.f / 512.f);
        r0 = rcp(fmaxf(q0 * (1.f / 512.f) - s0 * s0, 0.f) + 1e-5f);
        r1 = rcp(fmaxf(q1 * (1.f / 512.f) - s1 * s1, 0.f) + 1e-5f);
        m0 = pack2(s0, s0); m1 = pack2(s1, s1);
      }
#define UOFF(u) ((((ST_GU + (u) / 3) % NSLOT) * SLOT + ((u) % 3) * 8192) >> 4)
#define UNIT_PRE(u)  do { if ((u) % 3 == 0) mbar_wait(sb + SM_FULL + (ST_GU + (u) / 3) * 8); } while (0)
#define UNIT_POST(u) do { wg_commit(); if ((u) % 3 == 1 && (u) > 3) { wg_wait<2>(); if (lead) release(ST_GU + (u) / 3 - 1); } } while (0)
      float acc[64];
      const int rz = blockIdx.y;
#pragma unroll
      for (int ps = 0; ps < 2; ps++) {
        wg_fence();
#pragma unroll
        for (int k = 0; k < 16; k++) {
          const int u = 16 * ps + k, c = k >> 1;
          if (ps == 0 && (k == 0 || k == 4 || k == 8)) {
#pragma unroll
            for (int p = (k == 0 ? 0 : (k == 4 ? 1 : 3)); p < (k == 0 ? 1 : (k == 4 ? 3 : 4)); p++) {
              if (p > 0) mbar_wait(sb + SM_XF + ((2 + wg) * 4 + p) * 8);
              get_pair(A[2 * p], A[2 * p + 1], xb + p * 1024, hp_ + p * 1024, T);
              if (lane == 0) {
                if (wg == 0) mbar_arrive(sb + SM_XE + (8 + p) * 8);
                else if (p > 0) release(ST_XC + p - 1);
              }
            }
          }
          if (ps == 0 && (k & 1) == 0) {
#pragma unroll
            for (int s = 0; s < 4; s++) {
              A[c][s][0] = hsub2(A[c][s][0], m0); A[c][s][1] = hsub2(A[c][s][1], m1);
              A[c][s][2] = hsub2(A[c][s][2], m0); A[c][s][3] = hsub2(A[c][s][3], m1);
            }
            wg_fence();
          }
          UNIT_PRE(u);
          wgmma_rs_n128(acc, A[c][(k & 1) * 2], dg + UOFF(u), k != 0 ? 1 : (ps ? rz : 0));
          wgmma_rs_n128(acc, A[c][(k & 1) * 2 + 1], dg + UOFF(u) + 128, 1);
          UNIT_POST(u);
        }
        wg_wait<0>();
#pragma unroll
        for (int s = 0; s < 4; s++) {
          uint32_t (&hh)[4] = HH[4 + s];
          hh[0] = tg(pack2(acc[8 * s + 0] * acc[32 + 8 * s + 0], acc[8 * s + 1] * acc[32 + 8 * s + 1]), T);
          hh[1] = pack2(acc[8 * s + 2] * acc[32 + 8 * s + 2], acc[8 * s + 3] * acc[32 + 8 * s + 3]);
          hh[2] = pack2(acc[8 * s + 4] * acc[32 + 8 * s + 4], acc[8 * s + 5] * acc[32 + 8 * s + 5]);
          hh[3] = pack2(acc[8 * s + 6] * acc[32 + 8 * s + 6], acc[8 * s + 7] * acc[32 + 8 * s + 7]);
          st_rlx4(hhp + (4 * ps + s) * 128, hh[0], hh[1], hh[2], hh[3]);
        }
      }
      {
        float ag[24], au[24];
        const uint32_t* ph7 = reinterpret_cast<const uint32_t*>(&g_hh[rh3][jf ^ 1][7][wq][31]);
        uint32_t hv = 0;
        bar_sync(1 + wg, 128);
        wg_fence();
#pragma unroll
        for (int k = 0; k < 16; k++) {
          const int u = 32 + k, c = k >> 1;
          if (k == 6) {
#pragma unroll
            for (int s = 0; s < 4; s++) ld_rlx4(HH[s], hhp + s * 128);
          }
          if (k == 9) hv = ld_rlx1(ph7);
          if (k == 12) {
            int it = 0;
#pragma unroll 1
            while (((hv ^ T) & 1) && ++it < (1 << 18)) hv = ld_rlx1(ph7);
#pragma unroll
            for (int s = 0; s < 8; s++) ld_rlx4(PH[s], pp + s * 128);
          }
          UNIT_PRE(u);
          wgmma_rs_n48(ag, A[c][(k & 1) * 2], dg + UOFF(u), k != 0);
          wgmma_rs_n48(au, A[c][(k & 1) * 2], dg + UOFF(u) + 256, k != 0);
          wgmma_rs_n48(ag, A[c][(k & 1) * 2 + 1], dg + UOFF(u) + 128, 1);
          wgmma_rs_n48(au, A[c][(k & 1) * 2 + 1], dg + UOFF(u) + 256 + 128, 1);
          UNIT_POST(u);
        }
        wg_wait<0>();
#pragma unroll
        for (int s = 0; s < 3; s++) {
          uint32_t (&hh)[4] = HH[8 + s];
          hh[0] = tg(pack2(ag[8 * s + 0] * au[8 * s + 0], ag[8 * s + 1] * au[8 * s + 1]), T);
          hh[1] = pack2(ag[8 * s + 2] * au[8 * s + 2], ag[8 * s + 3] * au[8 * s + 3]);
          hh[2] = pack2(ag[8 * s + 4] * au[8 * s + 4], ag[8 * s + 5] * au[8 * s + 5]);
          hh[3] = pack2(ag[8 * s + 6] * au[8 * s + 6], ag[8 * s + 7] * au[8 * s + 7]);
          st_rlx4(hhp + (8 + s) * 128, hh[0], hh[1], hh[2], hh[3]);
        }
      }
    }

    {
      float ac[3][32], acc[32];
      uint32_t hr[4][4];
      const int m = jf >> 1, oc = (jf & 1) * 4 + m;
      const uint32_t* ph10 = reinterpret_cast<const uint32_t*>(&g_hh[rh3][jf ^ 1][10][wq][31]);
      uint32_t hv = 0;
      bar_arrive(8 + wg, 256);
      wg_fence();
#pragma unroll
      for (int k = 0; k < 3; k++) {
        mbar_wait(sb + SM_FULL + (ST_D + k) * 8);
        if (k == 1) hv = ld_rlx1(ph10);
#pragma unroll
        for (int s = 0; s < 11; s++) {
          if (k == 2 && s == 4) {
            int it = 0;
#pragma unroll 1
            while (((hv ^ T) & 1) && ++it < (1 << 18)) hv = ld_rlx1(ph10);
#pragma unroll
            for (int i = 8; i < 11; i++) ld_rlx4(PH[i], pp + i * 128);
          }
          wgmma_rs_n64(ac[k], HH[s], DESC(((ST_D + k) % NSLOT) * SLOT + s * 2048), s != 0);
        }
      }
      wg_commit();
      {
        int it = 0;
#pragma unroll 1
        while (__any_sync(0xffffffffu, bad4(PH[0][0], PH[1][0], PH[2][0], PH[3][0], T) | bad4(PH[4][0], PH[5][0], PH[6][0], PH[7][0], T) |
                                       bad4(PH[8][0], PH[9][0], PH[10][0], T, T))) {
#pragma unroll
          for (int s = 0; s < 11; s++) ld_rlx4(PH[s], pp + s * 128);
          if (++it > (1 << 18)) break;
        }
      }
      uint4* outb = &g_part[rh3][(jf & 1) * 4][m][wq][0][lane];
#pragma unroll
      for (int k = 0; k < 4; k++) {
        mbar_wait(sb + SM_FULL + (ST_D + 3 + k) * 8);
        wg_fence();
#pragma unroll
        for (int s = 0; s < 11; s++) {
          if (k < 3) wgmma_rs_n64(ac[k], PH[s], DESC(((ST_D + 3 + k) % NSLOT) * SLOT + s * 2048), 1);
          else wgmma_rs_n64(acc, HH[s], DESC(((ST_D + 6) % NSLOT) * SLOT + s * 2048), s != 0);
          if (s == 6 && k > 0) {
            wg_commit();
            wg_wait<1>();
            if (k == 1) bar_arrive(12, 320);
            const float (&a)[32] = ac[k - 1];
            uint4* p = outb + ((m + k) & 3) * 2048;
#pragma unroll
            for (int i = 0; i < 4; i++)
              st_rlx4(p + i * 32, tg(pack2(a[8 * i + 0], a[8 * i + 1]), T), pack2(a[8 * i + 2], a[8 * i + 3]),
                      pack2(a[8 * i + 4], a[8 * i + 5]), pack2(a[8 * i + 6], a[8 * i + 7]));
          }
        }
        wg_commit();
      }
      ld_chunk(hr, &g_h[rh3][oc][wq][0][lane]);
      uint32_t hx = ld_rlx1(&g_hx[rh3][oc][wq][lane]);
      mbar_wait(sb + SM_FULL + (ST_D + 7) * 8);
      wg_fence();
#pragma unroll
      for (int s = 0; s < 11; s++) wgmma_rs_n64(acc, PH[s], DESC(((ST_D + 7) % NSLOT) * SLOT + s * 2048), 1);
      wg_commit();
      wg_wait<0>();
#pragma unroll 1
      for (int q = 0; q < 3; q++) {
        uint32_t in[4][4];
        const uint4* sp = reinterpret_cast<const uint4*>(smem + ((ST_D % NSLOT) + wg) * SLOT) + q * 512 + wq * 128 + lane;
        mbar_wait_p(sb + SM_XF + (wg * 4 + q) * 8, 1);
        int it = 0;
#pragma unroll 1
        do {
#pragma unroll
          for (int s = 0; s < 4; s++)
            asm volatile("{\n.reg .b128 v;\nld.relaxed.gpu.b128 v, [%4];\nmov.b128 {%0,%1,%2,%3}, v;\n}"
                         : "=r"(in[s][0]), "=r"(in[s][1]), "=r"(in[s][2]), "=r"(in[s][3]) : "l"(sp + s * 32) : "memory");
          sp = &g_part[rh3][oc][(m - 1 - q) & 3][wq][0][lane];
        } while (__any_sync(0xffffffffu, bad4(in[0][0], in[1][0], in[2][0], in[3][0], T)) && ++it < (1 << 18));
        add_frag(acc, in, IDF);
      }
      {
        int it = 0;
#pragma unroll 1
        while (__any_sync(0xffffffffu, (hx ^ T) & 1) && ++it < (1 << 18)) hx = ld_rlx1(&g_hx[rh3][oc][wq][lane]);
      }
#pragma unroll
      for (int s = 0; s < 4; s++) hr[s][0] = (hr[s][0] & 0xFFFFFFFEu) | ((hx >> (s + 1)) & 1u);
#pragma unroll
      for (int i = 0; i < 32; i++) acc[i] *= (i & 2) ? r1 : r0;
      add_frag(acc, hr, IDF);
      bar_sync(9 - wg, 256);
      const uint32_t ob = sb + ((ST_D - 1) % NSLOT) * SLOT + wg * 8192;
#pragma unroll
      for (int s = 0; s < 4; s++)
        stsm4(ob + lrow + (((2 * s + lhi) ^ lx) << 4), pack2(acc[8 * s + 0], acc[8 * s + 1]), pack2(acc[8 * s + 2], acc[8 * s + 3]),
              pack2(acc[8 * s + 4], acc[8 * s + 5]), pack2(acc[8 * s + 6], acc[8 * s + 7]));
      __syncwarp();
      {
        const int row = wq * 16 + (lane >> 3);
        __nv_bfloat16* op = out + (size_t)(rh3 * 64 + row) * 512 + oc * 64 + lx * 8;
#pragma unroll
        for (int i = 0; i < 4; i++) {
          uint4 v;
          asm volatile("ld.shared.v4.b32 {%0,%1,%2,%3}, [%4];" : "=r"(v.x), "=r"(v.y), "=r"(v.z), "=r"(v.w)
                       : "r"(ob + (row + i * 4) * 128 + ((lx ^ (((lane >> 3) + i * 4) & 7)) << 4)) : "memory");
          asm volatile("st.global.v4.b32 [%0], {%1,%2,%3,%4};" ::"l"(op + i * 2048), "r"(v.x), "r"(v.y), "r"(v.z), "r"(v.w) : "memory");
        }
      }
    }
    asm volatile("barrier.cluster.arrive.relaxed.aligned;" ::: "memory");
    asm volatile("barrier.cluster.wait.aligned;" ::: "memory");
  } else {
    asm volatile("setmaxnreg.dec.sync.aligned.u32 24;");
    if (elect_one()) {
      if (warp == 8) {
#pragma unroll
        for (int k = 0; k < 9; k++) {
          const int s = k < 3 ? k : (k < 6 ? k + 3 : k - 3);
          const uint32_t bar = sb + SM_FULL + s * 8;
          mbar_init(bar, 1);
          mbar_expect_tx(bar, SLOT);
          if (s >= 3 && s < 6) tma2d(sb + s * SLOT, &maps.w, 512 + hg * 64, (s - 3) * 192, bar);
          else tma3d(sb + s * SLOT, &maps.x, 0, rb * 128 + (s >= 6 ? 64 : 0), 3 * (s % 3), bar);
        }
      } else if (warp == 9) {
        mbar_init(sb + SM_MISCB, 2);
        mbar_init(sb + SM_KVB, 1);
        mbar_expect_tx(sb + SM_KVB, 8704);
        mbar_expect_tx(sb + SM_MISCB, 2048);
        bulk_g2s(sb + SM_WPHI, wphi + hg * 1024, 2048, sb + SM_MISCB);
      } else if (warp == 10) {
        if ((sb & 0x3FFFF) != SM_BASE) __trap();
#pragma unroll 1
        for (int i = 0; i < 16; i++) {
          mbar_init(sb + SM_XF + i * 8, 1);
          mbar_expect_tx(sb + SM_XF + i * 8, (i == 8 || i == 12) ? 20480 : 16384);
          if (i < 12) mbar_init(sb + SM_XE + i * 8, 4);
        }
      } else {
        *reinterpret_cast<volatile unsigned*>(smem + SM_EPOCH) = atomicAdd(&g_start, 1u) / NCTA;
      }
      asm volatile("fence.mbarrier_init.release.cluster;" ::: "memory");
    }
    __syncwarp();
    if (warp != 11) bar_sync(0, 352);
    asm volatile("barrier.cluster.arrive.relaxed.aligned;" ::: "memory");
    if (warp == 8) {
      asm volatile("barrier.cluster.wait.aligned;" ::: "memory");
      if (elect_one()) {
        const CUtensorMap* mg = jf == 7 ? &maps.g7 : &maps.g;
        const CUtensorMap* mu = jf == 7 ? &maps.u7 : &maps.u;
        asm volatile("prefetch.tensormap [%0];" ::"l"(&maps.wo) : "memory");
        asm volatile("prefetch.tensormap [%0];" ::"l"(mg) : "memory");
        asm volatile("prefetch.tensormap [%0];" ::"l"(mu) : "memory");
        asm volatile("prefetch.tensormap [%0];" ::"l"(&maps.d) : "memory");
#pragma unroll 1
        for (int s = ST_WV; s < ST_XC; s++) {
          if (s == ST_SCR1) continue;
          mbar_wait(sb + SM_EMPTY + (s - 9) * 8);
          const uint32_t dst = sb + (s >= 18 ? s - 18 : s - 9) * SLOT, bar = sb + SM_FULL + s * 8;
          if (s < ST_WO) tma2d(dst, &maps.w, (s < ST_WQ ? 1024 : 0) + hg * 64, (s < ST_WQ ? s - ST_WV : s - ST_WQ) * 192, bar);
          else { mbar_wait(bar - 8); tma2d(dst, &maps.wo, hg * 64, (s - ST_WO) * 192, bar); }
        }
        const int jc = jf == 7 ? 0 : jf;
        int slot = (ST_GU + 1 - rank) % NSLOT;
#pragma unroll 1
        for (int s = ST_GU + 1 - rank; s < NSTAGE; s += 2) {
          mbar_wait(sb + SM_EMPTY + (s - 9) * 8);
          if (s > ST_GU && s < ST_GU + 6) mbar_wait(sb + SM_FULL + (s - 1) * 8);
          const uint32_t dst = sb + slot * SLOT, bar = sb + SM_FULL + s * 8;
          if (s < ST_D) {
#pragma unroll 1
            for (int i = 0; i < 3; i++) {
              const int u = (s - ST_GU) * 3 + i;
              tma3d_mc(dst + i * 8192, mg, (u >> 4) * 64, jc, (u & 15) * 32, bar);
              tma3d_mc(dst + i * 8192 + 4096, mu, (u >> 4) * 64, jc, (u & 15) * 32, bar);
            }
          } else {
            const int i = s - ST_D, k = i < 3 ? i : (i < 6 ? i - 3 : 3), pt = (i >= 3 && i != 6) ? 1 : 0;
            tma2d_mc(dst, &maps.d, ((jf & 1) * 4 + (((jf >> 1) + 1 + k) & 3)) * 64, (jf ^ pt) * 176, bar);
          }
          slot += 2; if (slot >= NSLOT) slot -= NSLOT;
        }
      }
      __syncwarp();
    } else {
      asm volatile("barrier.cluster.wait.aligned;" ::: "memory");
      if (warp == 11) {
#pragma unroll
        for (int i = 0; i < 4; i++)
          reinterpret_cast<uint4*>(smem + SM_ONES)[lane + 32 * i] = make_uint4(0x3F803F80u, 0x3F803F80u, 0x3F803F80u, 0x3F803F80u);
        fence_async_smem();
        __syncwarp();
        if (lane == 0) mbar_arrive(sb + SM_MISCB);
      }
      mbar_wait(sb + SM_MISCB);
      const unsigned epoch = *reinterpret_cast<volatile unsigned*>(smem + SM_EPOCH);
      const uint32_t T = (epoch & 1) ^ 1;
      if (warp == 11) {
        reinterpret_cast<float4*>(&g_kv[hg][rb * 136])[lane] = make_float4(0.f, 0.f, 0.f, 0.f);
        if (lane < 2) reinterpret_cast<float4*>(&g_kv[hg][rb * 136])[32 + lane] = make_float4(0.f, 0.f, 0.f, 0.f);
        __syncwarp();
        if (elect_one()) asm volatile("red.release.gpu.global.add.u32 [%0], 8;" ::"l"(&g_kvcnt[hg * 32 + 1]) : "memory");
        mbar_wait(sb + SM_FULL + (ST_WK + 2) * 8);
        if (elect_one()) {
          asm volatile("cp.async.bulk.prefetch.L2.global [%0], 4096;" ::"l"((const char*)wo + blockIdx.x * 4096) : "memory");
          asm volatile("cp.async.bulk.prefetch.L2.global [%0], 11008;" ::"l"((const char*)wg_ + blockIdx.x * 11008) : "memory");
          asm volatile("cp.async.bulk.prefetch.L2.global [%0], 11008;" ::"l"((const char*)wu_ + blockIdx.x * 11008) : "memory");
          asm volatile("cp.async.bulk.prefetch.L2.global [%0], 11008;" ::"l"((const char*)wd_ + blockIdx.x * 11008) : "memory");
          mbar_wait(sb + SM_EMPTY + ST_SCR0 * 8);
          const unsigned target = (epoch + 1) * 128;
          unsigned v; int it = 0;
#pragma unroll 1
          do {
            asm volatile("ld.acquire.gpu.global.u32 %0, [%1];" : "=r"(v) : "l"(&g_kvcnt[hg * 32]) : "memory");
            if (++it > (1 << 18)) break;
          } while ((int)(v - target) < 0);
          asm volatile("fence.proxy.async.global;" ::: "memory");
          bulk_g2s(sb + SM_KV32, &g_kv[hg][0], 8192, sb + SM_KVB);
          bulk_g2s(sb + SM_ONES, &g_kv[hg][2048], 512, sb + SM_KVB);
        }
        __syncwarp();
      } else {
        const int w = warp - 9;
        st_rlx4(reinterpret_cast<uint4*>(&g_st[2 * rb + w][hg][0]) + lane, T ^ 1, T ^ 1, T ^ 1, T ^ 1);
        if (lane < 8) st_rlx4(&g_o[2 * rb + w][hg][lane >> 1][3][30 + (lane & 1)], T ^ 1, T ^ 1, T ^ 1, T ^ 1);
        st_rlx4(&g_part[2 * rb3 + w][(jf & 1) * 4 + (lane >> 3)][jf >> 1][(lane >> 1) & 3][3][30 + (lane & 1)], T ^ 1, T ^ 1, T ^ 1, T ^ 1);
        if (lane < 16) st_rlx4(&g_hh[2 * rb3 + w][jf][7 + (lane >> 3) * 3][(lane >> 1) & 3][30 + (lane & 1)], T ^ 1, T ^ 1, T ^ 1, T ^ 1);
        if (w == 0) {
          mbar_wait(sb + SM_FULL + (ST_WQ + 2) * 8);
          unsigned v; int it = 0;
#pragma unroll 1
          do {
            asm volatile("ld.acquire.gpu.global.u32 %0, [%1];" : "=r"(v) : "l"(&g_kvcnt[hg * 32 + 1]) : "memory");
          } while ((int)(v - (epoch + 1) * 128) < 0 && ++it < (1 << 18));
          asm volatile("fence.proxy.async.global;" ::: "memory");
        }
        bar_sync(6, 320);
        if (w == 0 && elect_one()) {
          asm volatile("cp.reduce.async.bulk.global.shared::cta.bulk_group.add.f32 [%0], [%1], 8704;"
                       ::"l"(&g_kv[hg][0]), "r"(sb + 2 * SLOT) : "memory");
          asm volatile("cp.async.bulk.commit_group;" ::: "memory");
          asm volatile("cp.async.bulk.wait_group 0;" ::: "memory");
          asm volatile("red.relaxed.gpu.global.add.u32 [%0], 8;" ::"l"(&g_kvcnt[hg * 32]) : "memory");
        }
        __syncwarp();
        mbar_wait(sb + SM_KVB);
        if (w == 0) { mbar_wait(sb + SM_EMPTY + 11 * 8); mbar_wait(sb + SM_EMPTY + 12 * 8); mbar_wait(sb + SM_EMPTY + 13 * 8); }
#pragma unroll 1
        for (int ph = 0; ph < 2; ph++) {
          const int use = 2 * ph + w, r = ph ? 2 * rb3 + w : 2 * rb + w;
          const uint32_t* pw = ph ? reinterpret_cast<const uint32_t*>(&g_st[r][lane >> 2][(lane & 3) * 16 + 15])
                                  : reinterpret_cast<const uint32_t*>(&g_o[r][lane >> 2][lane & 3][3][31]);
          const char* src = reinterpret_cast<const char*>(ph ? &g_h[r][0][0][0][0] : &g_o[r][0][0][0][0]);
          const uint32_t bf = sb + SM_XF + use * 32, be = sb + SM_XE + (use - 1) * 32;
          bar_sync(10 + w, 160);
          int it = 0;
#pragma unroll 1
          for (bool miss = true; __any_sync(0xffffffffu, miss) && ++it < (1 << 18);) { if (miss) miss = (ld_rlx1(pw) ^ T) & 1; }
          if (elect_one()) {
            if (use > 0) mbar_wait(be);
            if (ph) bulk_g2s(sb + SM_KV32 + w * 4096, &g_st[r][0][0], 4096, bf);
#pragma unroll
            for (int p = 0; p < 4; p++) {
              if (p > 0 && use > 0) mbar_wait(be + p * 8);
              bulk_g2s(sb + 2 * SLOT + p * 16384, src + p * 16384, 16384, bf + p * 8);
            }
          }
          __syncwarp();
        }
        {
          const int m = jf >> 1, oc = (jf & 1) * 4 + m;
          const uint32_t* pw = reinterpret_cast<const uint32_t*>(&g_part[2 * rb3 + w][oc][(m - 1 - (lane >> 2)) & 3][lane & 3][3][31]);
          bar_sync(12, 320);
          bool miss = lane < 12; int it = 0;
#pragma unroll 1
          for (int q = 0; q < 3; q++) {
#pragma unroll 1
            while ((__ballot_sync(0xffffffffu, miss) >> (4 * q) & 15) && ++it < (1 << 18)) { if (miss && (lane >> 2) <= q + 1) miss = (ld_rlx1(pw) ^ T) & 1; }
            if (elect_one()) {
              const uint32_t bar = sb + SM_XF + (w * 4 + q) * 8;
              mbar_expect_tx(bar, 8192);
              bulk_g2s(sb + ((ST_D % NSLOT) + w) * SLOT + q * 8192, &g_part[2 * rb3 + w][oc][(m - 1 - q) & 3][0][0][0], 8192, bar);
            }
            __syncwarp();
          }
        }
      }
    }
    asm volatile("barrier.cluster.arrive.relaxed.aligned;" ::: "memory");
    asm volatile("barrier.cluster.wait.aligned;" ::: "memory");
  }
}

typedef CUresult (*EncodeFn)(CUtensorMap*, CUtensorMapDataType, cuuint32_t, void*, const cuuint64_t*, const cuuint64_t*,
                             const cuuint32_t*, const cuuint32_t*, CUtensorMapInterleave, CUtensorMapSwizzle,
                             CUtensorMapL2promotion, CUtensorMapFloatOOBfill);

void encode(EncodeFn fn, CUtensorMap* m, const void* base, int rank, const cuuint64_t* dims, const cuuint64_t* strides,
            const cuuint32_t* box) {
  cuuint32_t es[3] = {1, 1, 1};
  fn(m, CU_TENSOR_MAP_DATA_TYPE_BFLOAT16, (cuuint32_t)rank, const_cast<void*>(base), dims, strides, box, es,
     CU_TENSOR_MAP_INTERLEAVE_NONE, CU_TENSOR_MAP_SWIZZLE_128B, CU_TENSOR_MAP_L2_PROMOTION_L2_256B,
     CU_TENSOR_MAP_FLOAT_OOB_FILL_NONE);
}

}

extern "C" void kernel_launch(void* const* d_in, const int* in_sizes, int n_in, void* d_out, int out_size) {
  (void)in_sizes; (void)n_in; (void)out_size;
  const __nv_bfloat16* x    = (const __nv_bfloat16*)d_in[0];
  const __nv_bfloat16* wqkv = (const __nv_bfloat16*)d_in[1];
  const __nv_bfloat16* wphi = (const __nv_bfloat16*)d_in[2];
  const __nv_bfloat16* wo   = (const __nv_bfloat16*)d_in[3];
  const __nv_bfloat16* wg   = (const __nv_bfloat16*)d_in[5];
  const __nv_bfloat16* wu   = (const __nv_bfloat16*)d_in[6];
  const __nv_bfloat16* wd   = (const __nv_bfloat16*)d_in[7];

  static EncodeFn fn = nullptr;
  if (!fn) {
    void* p = nullptr;
    cudaDriverEntryPointQueryResult qr;
    cudaGetDriverEntryPoint("cuTensorMapEncodeTiled", &p, cudaEnableDefault, &qr);
    fn = (EncodeFn)p;
    cudaFuncSetAttribute(fused_kernel, cudaFuncAttributeMaxDynamicSharedMemorySize, SM_TOTAL);
  }
  Maps maps;
  {
    cuuint64_t d[3] = {64, 2048, 8}, s[2] = {1024, 128}; cuuint32_t b[3] = {64, 64, 3};
    encode(fn, &maps.x, x, 3, d, s, b);
  }
  {
    cuuint64_t d[2] = {1536, 512}, s[1] = {3072}; cuuint32_t b[2] = {64, 192};
    encode(fn, &maps.w, wqkv, 2, d, s, b);
  }
  {
    cuuint64_t d[2] = {512, 512}, s[1] = {1024}; cuuint32_t b[2] = {64, 192};
    encode(fn, &maps.wo, wo, 2, d, s, b);
  }
  {
    cuuint64_t d[3] = {176, 7, 512}, d7[3] = {144, 1, 512}, s[2] = {352, 2752}; cuuint32_t b[3] = {64, 1, 32};
    encode(fn, &maps.g, wg, 3, d, s, b);
    encode(fn, &maps.u, wu, 3, d, s, b);
    encode(fn, &maps.g7, wg + 1232, 3, d7, s, b);
    encode(fn, &maps.u7, wu + 1232, 3, d7, s, b);
  }
  {
    cuuint64_t d[2] = {512, 1376}, s[1] = {1024}; cuuint32_t b[2] = {64, 176};
    encode(fn, &maps.d, wd, 2, d, s, b);
  }
  fused_kernel<<<NCTA, 384, SM_TOTAL>>>(maps, x, wphi, wo, wg, wu, wd, (__nv_bfloat16*)d_out);
}
```

```cpp
#include <cuda_runtime.h>
#include <cuda_bf16.h>
#include <cuda.h>
#include <stdint.h>

#define SAFE_WAIT 0

namespace {

constexpr int NCTA   = 128;
constexpr int SLOT   = 24576;
constexpr int NSLOT  = 9;
constexpr int NSTAGE = 47;

constexpr int ST_X0   = 0;
constexpr int ST_WK   = 3;
constexpr int ST_X1   = 6;
constexpr int ST_SCR0 = 9;
constexpr int ST_WV   = 10;
constexpr int ST_SCR1 = 13;
constexpr int ST_WQ   = 14;
constexpr int ST_WO   = 17;
constexpr int ST_XC   = 20;
constexpr int ST_GU   = 23;
constexpr int ST_D    = 39;

__host__ __device__ constexpr int st_empty_cnt(int d) {
  return ((d < 3 || (d >= 6 && d < 9) || (d >= ST_XC && d < ST_GU)) ? 4 : 2) * (d + 9 >= ST_GU ? 2 : 1);
}

constexpr uint32_t SM_BASE = 1024;
constexpr int SM_ONES = NSLOT * SLOT;
constexpr int SM_WPHI = SM_ONES + 2048;
constexpr int SM_KVS  = SM_WPHI + 2048;
constexpr int SM_KV32 = 4 * SLOT + 16384;
constexpr int SM_BAR  = SM_KVS + 6144;
constexpr int SM_FULL  = SM_BAR;
constexpr int SM_EMPTY = SM_BAR + NSTAGE * 8;
constexpr int SM_MISCB = SM_BAR + 2 * NSTAGE * 8;
constexpr int SM_KVB   = SM_MISCB + 8;
constexpr int SM_EPOCH = SM_KVB + 8;
constexpr int SM_XF    = SM_EPOCH + 8;
constexpr int SM_XE    = SM_XF + 16 * 8;
constexpr int SM_TOTAL = SM_BAR + 1024;

static_assert(SM_TOTAL == 232448 && SM_XE + 12 * 8 <= SM_TOTAL, "smem budget");

struct Maps { CUtensorMap x, w, wo, g, u, g7, u7, d; };

__device__ __align__(128) uint4    g_o[32][8][4][4][32];
__device__ __align__(128) uint4    g_h[32][8][4][4][32];
__device__ __align__(128) uint32_t g_hx[32][8][4][32];
__device__ __align__(128) uint2    g_st[32][8][64];
__device__ __align__(128) uint4    g_hh[32][8][11][4][32];
__device__ __align__(128) uint4    g_part[32][8][4][4][4][32];
__device__ __align__(128) float4 g_kv[8][128][6];
__device__ __align__(128) unsigned g_kvcnt[8 * 32];
__device__ unsigned g_start;

__device__ __forceinline__ uint32_t smem_u32(const void* p) { return (uint32_t)__cvta_generic_to_shared(p); }
__device__ __forceinline__ void mbar_init(uint32_t bar, int cnt) {
  asm volatile("mbarrier.init.shared::cta.b64 [%0], %1;" ::"r"(bar), "r"(cnt) : "memory");
}
__device__ __forceinline__ void mbar_expect_tx(uint32_t bar, uint32_t bytes) {
  asm volatile("mbarrier.arrive.expect_tx.shared::cta.b64 _, [%0], %1;" ::"r"(bar), "r"(bytes) : "memory");
}
__device__ __forceinline__ void mbar_arrive(uint32_t bar) {
  asm volatile("mbarrier.arrive.shared::cta.b64 _, [%0];" ::"r"(bar) : "memory");
}
__device__ __forceinline__ void mbar_arrive_cluster(uint32_t bar, uint32_t rank) {
  asm volatile("{\n.reg .b32 ra;\nmapa.shared::cluster.u32 ra, %0, %1;\n"
               "mbarrier.arrive.shared::cluster.b64 _, [ra];\n}" ::"r"(bar), "r"(rank) : "memory");
}
__device__ __forceinline__ void mbar_wait_p(uint32_t bar, uint32_t parity) {
  asm volatile("{\n.reg .pred p;\nW: mbarrier.try_wait.parity.shared::cta.b64 p, [%0], %1;\n@!p bra W;\n}" ::"r"(bar), "r"(parity) : "memory");
}
__device__ __forceinline__ void mbar_wait(uint32_t bar) { mbar_wait_p(bar, 0); }
__device__ __forceinline__ bool elect_one() {
  uint32_t p;
  asm volatile("{\n.reg .pred P;\nelect.sync _|P, 0xffffffff;\nselp.u32 %0, 1, 0, P;\n}" : "=r"(p));
  return p != 0;
}
__device__ __forceinline__ void bar_sync(int id, int n)   { asm volatile("bar.sync %0, %1;" ::"r"(id), "r"(n) : "memory"); }
__device__ __forceinline__ void bar_arrive(int id, int n) { asm volatile("bar.arrive %0, %1;" ::"r"(id), "r"(n) : "memory"); }
__device__ __forceinline__ void fence_async_smem() { asm volatile("fence.proxy.async.shared::cta;" ::: "memory"); }
__device__ __forceinline__ void wg_fence()  { asm volatile("wgmma.fence.sync.aligned;" ::: "memory"); }
__device__ __forceinline__ void wg_commit() { asm volatile("wgmma.commit_group.sync.aligned;" ::: "memory"); }
template <int N> __device__ __forceinline__ void wg_wait() { asm volatile("wgmma.wait_group.sync.aligned %0;" ::"n"(N) : "memory"); }
#define DESC(off) (db + ((uint32_t)(off) >> 4))
__device__ __forceinline__ void tma2d(uint32_t dst, const CUtensorMap* m, int c0, int c1, uint32_t bar) {
  asm volatile("cp.async.bulk.tensor.2d.shared::cluster.global.mbarrier::complete_tx::bytes [%0], [%1, {%3, %4}], [%2];"
               ::"r"(dst), "l"(m), "r"(bar), "r"(c0), "r"(c1) : "memory");
}
__device__ __forceinline__ void tma2d_mc(uint32_t dst, const CUtensorMap* m, int c0, int c1, uint32_t bar) {
  asm volatile("cp.async.bulk.tensor.2d.shared::cluster.global.mbarrier::complete_tx::bytes.multicast::cluster [%0], [%1, {%3, %4}], [%2], %5;"
               ::"r"(dst), "l"(m), "r"(bar), "r"(c0), "r"(c1), "h"((uint16_t)3) : "memory");
}
__device__ __forceinline__ void tma3d(uint32_t dst, const CUtensorMap* m, int c0, int c1, int c2, uint32_t bar) {
  asm volatile("cp.async.bulk.tensor.3d.shared::cluster.global.mbarrier::complete_tx::bytes [%0], [%1, {%3, %4, %5}], [%2];"
               ::"r"(dst), "l"(m), "r"(bar), "r"(c0), "r"(c1), "r"(c2) : "memory");
}
__device__ __forceinline__ void tma3d_mc(uint32_t dst, const CUtensorMap* m, int c0, int c1, int c2, uint32_t bar) {
  asm volatile("cp.async.bulk.tensor.3d.shared::cluster.global.mbarrier::complete_tx::bytes.multicast::cluster [%0], [%1, {%3, %4, %5}], [%2], %6;"
               ::"r"(dst), "l"(m), "r"(bar), "r"(c0), "r"(c1), "r"(c2), "h"((uint16_t)3) : "memory");
}
__device__ __forceinline__ void ldsm4(uint32_t (&r)[4], uint32_t addr) {
  asm volatile("ldmatrix.sync.aligned.m8n8.x4.shared.b16 {%0,%1,%2,%3}, [%4];"
               : "=r"(r[0]), "=r"(r[1]), "=r"(r[2]), "=r"(r[3]) : "r"(addr) : "memory");
}
__device__ __forceinline__ void ldsm4t(uint32_t (&r)[4], uint32_t addr) {
  asm volatile("ldmatrix.sync.aligned.m8n8.x4.trans.shared.b16 {%0,%1,%2,%3}, [%4];"
               : "=r"(r[0]), "=r"(r[1]), "=r"(r[2]), "=r"(r[3]) : "r"(addr) : "memory");
}
__device__ __forceinline__ void stsm4(uint32_t addr, uint32_t r0, uint32_t r1, uint32_t r2, uint32_t r3) {
  asm volatile("stmatrix.sync.aligned.m8n8.x4.shared.b16 [%0], {%1,%2,%3,%4};"
               ::"r"(addr), "r"(r0), "r"(r1), "r"(r2), "r"(r3) : "memory");
}
__device__ __forceinline__ void mma16816(float (&c)[4], const uint32_t (&a)[4], uint32_t b0, uint32_t b1) {
  asm volatile("mma.sync.aligned.m16n8k16.row.col.f32.bf16.bf16.f32 {%0,%1,%2,%3},{%4,%5,%6,%7},{%8,%9},{%0,%1,%2,%3};"
               : "+f"(c[0]), "+f"(c[1]), "+f"(c[2]), "+f"(c[3])
               : "r"(a[0]), "r"(a[1]), "r"(a[2]), "r"(a[3]), "r"(b0), "r"(b1));
}
__device__ __forceinline__ void add_frag(float (&c)[32], const uint32_t (&a)[4][4], uint32_t id) {
#pragma unroll
  for (int i = 0; i < 8; i++)
    asm volatile("mma.sync.aligned.m16n8k8.row.col.f32.bf16.bf16.f32 {%0,%1,%2,%3},{%4,%5},{%6},{%0,%1,%2,%3};"
                 : "+f"(c[4 * i]), "+f"(c[4 * i + 1]), "+f"(c[4 * i + 2]), "+f"(c[4 * i + 3])
                 : "r"(a[i >> 1][(i & 1) * 2]), "r"(a[i >> 1][(i & 1) * 2 + 1]), "r"(id));
}
__device__ __forceinline__ uint32_t pack2(float lo, float hi) {
  uint32_t r; asm("cvt.rn.bf16x2.f32 %0, %1, %2;" : "=r"(r) : "f"(hi), "f"(lo)); return r;
}
__device__ __forceinline__ float blo(uint32_t w) { return __uint_as_float(w << 16); }
__device__ __forceinline__ float bhi(uint32_t w) { return __uint_as_float(w & 0xFFFF0000u); }
__device__ __forceinline__ uint32_t hsub2(uint32_t a, uint32_t b) { uint32_t r; asm("sub.rn.bf16x2 %0, %1, %2;" : "=r"(r) : "r"(a), "r"(b)); return r; }
__device__ __forceinline__ uint32_t hmax2(uint32_t a, uint32_t b) { uint32_t r; asm("max.bf16x2 %0, %1, %2;" : "=r"(r) : "r"(a), "r"(b)); return r; }
__device__ __forceinline__ uint32_t hmin2(uint32_t a, uint32_t b) { uint32_t r; asm("min.bf16x2 %0, %1, %2;" : "=r"(r) : "r"(a), "r"(b)); return r; }
__device__ __forceinline__ float ex2(float x) { float r; asm("ex2.approx.ftz.f32 %0, %1;" : "=f"(r) : "f"(x)); return r; }
__device__ __forceinline__ float rcp(float x) { float r; asm("rcp.approx.ftz.f32 %0, %1;" : "=f"(r) : "f"(x)); return r; }
__device__ __forceinline__ void ld_rlx4(uint32_t (&r)[4], const uint4* p) {
  asm volatile("{\n.reg .b128 v;\nld.relaxed.gpu.global.b128 v, [%4];\nmov.b128 {%0,%1,%2,%3}, v;\n}"
               : "=r"(r[0]), "=r"(r[1]), "=r"(r[2]), "=r"(r[3]) : "l"(p) : "memory");
}
__device__ __forceinline__ void st_rlx4(uint4* p, uint32_t a, uint32_t b, uint32_t c, uint32_t d) {
  asm volatile("st.relaxed.gpu.global.v4.b32 [%0], {%1,%2,%3,%4};" ::"l"(p), "r"(a), "r"(b), "r"(c), "r"(d) : "memory");
}
__device__ __forceinline__ void st_rlx2(uint2* p, uint32_t a, uint32_t b) {
  asm volatile("{\n.reg .b64 v;\nmov.b64 v, {%1,%2};\nst.relaxed.gpu.global.b64 [%0], v;\n}" ::"l"(p), "r"(a), "r"(b) : "memory");
}
__device__ __forceinline__ uint32_t ld_rlx1(const uint32_t* p) {
  uint32_t r; asm volatile("ld.relaxed.gpu.global.b32 %0, [%1];" : "=r"(r) : "l"(p) : "memory"); return r;
}
__device__ __forceinline__ void st_rlx1(uint32_t* p, uint32_t a) {
  asm volatile("st.relaxed.gpu.global.b32 [%0], %1;" ::"l"(p), "r"(a) : "memory");
}
__device__ __forceinline__ void ld_rlx2(uint32_t& a, uint32_t& b, const uint2* p) {
  asm volatile("{\n.reg .b64 v;\nld.relaxed.gpu.b64 v, [%2];\nmov.b64 {%0,%1}, v;\n}" : "=r"(a), "=r"(b) : "l"(p) : "memory");
}
__device__ __forceinline__ void bulk_g2s(uint32_t dst, const void* src, uint32_t bytes, uint32_t bar) {
  asm volatile("cp.async.bulk.shared::cluster.global.mbarrier::complete_tx::bytes [%0], [%1], %2, [%3];"
               ::"r"(dst), "l"(src), "r"(bytes), "r"(bar) : "memory");
}
__device__ __forceinline__ uint32_t tg(uint32_t w, uint32_t T) { return (w & 0xFFFFFFFEu) | T; }
__device__ __forceinline__ uint32_t bad4(uint32_t a, uint32_t b, uint32_t c, uint32_t d, uint32_t T) {
  uint32_t u, v;
  asm("lop3.b32 %0, %1, %2, %3, 0x7E;" : "=r"(u) : "r"(a), "r"(b), "r"(T));
  asm("lop3.b32 %0, %1, %2, %3, 0x7E;" : "=r"(v) : "r"(c), "r"(d), "r"(T));
  asm("lop3.b32 %0, %1, %2, 1, 0xA8;" : "=r"(u) : "r"(u), "r"(v));
  return u;
}

__device__ __forceinline__ void ld_chunk(uint32_t (&a)[4][4], const uint4* p) {
#pragma unroll
  for (int s = 0; s < 4; s++) ld_rlx4(a[s], p + s * 32);
}
__device__ __forceinline__ void get_pair(uint32_t (&a)[4][4], uint32_t (&b)[4][4], const uint4* sp, const uint4* gp, uint32_t T) {
  int it = 0;
#pragma unroll 1
  do {
#pragma unroll
    for (int s = 0; s < 8; s++) {
      uint32_t (&r)[4] = s < 4 ? a[s & 3] : b[s & 3];
      asm volatile("{\n.reg .b128 v;\nld.relaxed.gpu.b128 v, [%4];\nmov.b128 {%0,%1,%2,%3}, v;\n}"
                   : "=r"(r[0]), "=r"(r[1]), "=r"(r[2]), "=r"(r[3]) : "l"(sp + (s >> 2) * 512 + (s & 3) * 32) : "memory");
    }
    sp = gp;
  } while (__any_sync(0xffffffffu, bad4(a[0][0], a[1][0], a[2][0], a[3][0], T) | bad4(b[0][0], b[1][0], b[2][0], b[3][0], T)) && ++it < (1 << 18));
}

__device__ __forceinline__ void wgmma_rs_n48(float (&d)[24], const uint32_t (&a)[4], uint32_t descB, int scaleD) {
  asm volatile("{\n.reg .pred p;\n.reg .b64 db;\nsetp.ne.b32 p, %29, 0;\nmov.b64 db, {%28, 0x40000040};\n"
    "wgmma.mma_async.sync.aligned.m64n48k16.f32.bf16.bf16 {%0,%1,%2,%3,%4,%5,%6,%7,%8,%9,%10,%11,%12,%13,%14,%15,%16,%17,%18,%19,%20,%21,%22,%23}, {%24,%25,%26,%27}, db, p, 1, 1, 1;\n}\n"
    : "+f"(d[0]),"+f"(d[1]),"+f"(d[2]),"+f"(d[3]),"+f"(d[4]),"+f"(d[5]),"+f"(d[6]),"+f"(d[7]),"+f"(d[8]),"+f"(d[9]),"+f"(d[10]),"+f"(d[11]),"+f"(d[12]),"+f"(d[13]),"+f"(d[14]),"+f"(d[15]),"+f"(d[16]),"+f"(d[17]),"+f"(d[18]),"+f"(d[19]),"+f"(d[20]),"+f"(d[21]),"+f"(d[22]),"+f"(d[23])
    : "r"(a[0]), "r"(a[1]), "r"(a[2]), "r"(a[3]), "r"(descB), "r"(scaleD));
}
__device__ __forceinline__ void wgmma_rs_n64(float (&d)[32], const uint32_t (&a)[4], uint32_t descB, int scaleD) {
  asm volatile("{\n.reg .pred p;\n.reg .b64 db;\nsetp.ne.b32 p, %37, 0;\nmov.b64 db, {%36, 0x40000040};\n"
    "wgmma.mma_async.sync.aligned.m64n64k16.f32.bf16.bf16 {%0,%1,%2,%3,%4,%5,%6,%7,%8,%9,%10,%11,%12,%13,%14,%15,%16,%17,%18,%19,%20,%21,%22,%23,%24,%25,%26,%27,%28,%29,%30,%31}, {%32,%33,%34,%35}, db, p, 1, 1, 1;\n}\n"
    : "+f"(d[0]),"+f"(d[1]),"+f"(d[2]),"+f"(d[3]),"+f"(d[4]),"+f"(d[5]),"+f"(d[6]),"+f"(d[7]),"+f"(d[8]),"+f"(d[9]),"+f"(d[10]),"+f"(d[11]),"+f"(d[12]),"+f"(d[13]),"+f"(d[14]),"+f"(d[15]),"+f"(d[16]),"+f"(d[17]),"+f"(d[18]),"+f"(d[19]),"+f"(d[20]),"+f"(d[21]),"+f"(d[22]),"+f"(d[23]),"+f"(d[24]),"+f"(d[25]),"+f"(d[26]),"+f"(d[27]),"+f"(d[28]),"+f"(d[29]),"+f"(d[30]),"+f"(d[31])
    : "r"(a[0]), "r"(a[1]), "r"(a[2]), "r"(a[3]), "r"(descB), "r"(scaleD));
}
__device__ __forceinline__ void wgmma_rs_n128(float (&d)[64], const uint32_t (&a)[4], uint32_t descB, int scaleD) {
  asm volatile("{\n.reg .pred p;\n.reg .b64 db;\nsetp.ne.b32 p, %69, 0;\nmov.b64 db, {%68, 0x40000040};\n"
    "wgmma.mma_async.sync.aligned.m64n128k16.f32.bf16.bf16 {%0,%1,%2,%3,%4,%5,%6,%7,%8,%9,%10,%11,%12,%13,%14,%15,%16,%17,%18,%19,%20,%21,%22,%23,%24,%25,%26,%27,%28,%29,%30,%31,%32,%33,%34,%35,%36,%37,%38,%39,%40,%41,%42,%43,%44,%45,%46,%47,%48,%49,%50,%51,%52,%53,%54,%55,%56,%57,%58,%59,%60,%61,%62,%63}, {%64,%65,%66,%67}, db, p, 1, 1, 1;\n}\n"
    : "+f"(d[0]),"+f"(d[1]),"+f"(d[2]),"+f"(d[3]),"+f"(d[4]),"+f"(d[5]),"+f"(d[6]),"+f"(d[7]),"+f"(d[8]),"+f"(d[9]),"+f"(d[10]),"+f"(d[11]),"+f"(d[12]),"+f"(d[13]),"+f"(d[14]),"+f"(d[15]),"+f"(d[16]),"+f"(d[17]),"+f"(d[18]),"+f"(d[19]),"+f"(d[20]),"+f"(d[21]),"+f"(d[22]),"+f"(d[23]),"+f"(d[24]),"+f"(d[25]),"+f"(d[26]),"+f"(d[27]),"+f"(d[28]),"+f"(d[29]),"+f"(d[30]),"+f"(d[31]),"+f"(d[32]),"+f"(d[33]),"+f"(d[34]),"+f"(d[35]),"+f"(d[36]),"+f"(d[37]),"+f"(d[38]),"+f"(d[39]),"+f"(d[40]),"+f"(d[41]),"+f"(d[42]),"+f"(d[43]),"+f"(d[44]),"+f"(d[45]),"+f"(d[46]),"+f"(d[47]),"+f"(d[48]),"+f"(d[49]),"+f"(d[50]),"+f"(d[51]),"+f"(d[52]),"+f"(d[53]),"+f"(d[54]),"+f"(d[55]),"+f"(d[56]),"+f"(d[57]),"+f"(d[58]),"+f"(d[59]),"+f"(d[60]),"+f"(d[61]),"+f"(d[62]),"+f"(d[63])
    : "r"(a[0]), "r"(a[1]), "r"(a[2]), "r"(a[3]), "r"(descB), "r"(scaleD));
}
__device__ __forceinline__ void wgmma_ss_n72_t11(float (&d)[36], uint32_t descA, uint32_t descB, int scaleD) {
  asm volatile("{\n.reg .pred p;\n.reg .b64 da, db;\nsetp.ne.b32 p, %38, 0;\nmov.b64 da, {%36, 0x40000040};\nmov.b64 db, {%37, 0x40000040};\n"
    "wgmma.mma_async.sync.aligned.m64n72k16.f32.bf16.bf16 {%0,%1,%2,%3,%4,%5,%6,%7,%8,%9,%10,%11,%12,%13,%14,%15,%16,%17,%18,%19,%20,%21,%22,%23,%24,%25,%26,%27,%28,%29,%30,%31,%32,%33,%34,%35}, da, db, p, 1, 1, 1, 1;\n}\n"
    : "+f"(d[0]),"+f"(d[1]),"+f"(d[2]),"+f"(d[3]),"+f"(d[4]),"+f"(d[5]),"+f"(d[6]),"+f"(d[7]),"+f"(d[8]),"+f"(d[9]),"+f"(d[10]),"+f"(d[11]),"+f"(d[12]),"+f"(d[13]),"+f"(d[14]),"+f"(d[15]),"+f"(d[16]),"+f"(d[17]),"+f"(d[18]),"+f"(d[19]),"+f"(d[20]),"+f"(d[21]),"+f"(d[22]),"+f"(d[23]),"+f"(d[24]),"+f"(d[25]),"+f"(d[26]),"+f"(d[27]),"+f"(d[28]),"+f"(d[29]),"+f"(d[30]),"+f"(d[31]),"+f"(d[32]),"+f"(d[33]),"+f"(d[34]),"+f"(d[35])
    : "r"(descA), "r"(descB), "r"(scaleD));
}

constexpr float LOG2E = 1.4426950408889634f;

__device__ __forceinline__ void feat_exp(const uint32_t (&P)[4], float (&e)[16]) {
  uint32_t a = hmax2(P[0], P[2]), b = hmax2(P[1], P[3]);
  uint32_t mx = hmax2(__byte_perm(a, b, 0x5410), __byte_perm(a, b, 0x7632));
  a = hmin2(P[0], P[2]); b = hmin2(P[1], P[3]);
  uint32_t mn = hmin2(__byte_perm(a, b, 0x5410), __byte_perm(a, b, 0x7632));
  mx = hmax2(mx, __shfl_xor_sync(0xffffffffu, mx, 1));
  mn = hmin2(mn, __shfl_xor_sync(0xffffffffu, mn, 1));
  mx = hmax2(mx, __shfl_xor_sync(0xffffffffu, mx, 2));
  mn = hmin2(mn, __shfl_xor_sync(0xffffffffu, mn, 2));
  float mx0 = -blo(mx) * LOG2E, mx1 = -bhi(mx) * LOG2E, mn0 = blo(mn) * LOG2E, mn1 = bhi(mn) * LOG2E;
  float v[8] = {blo(P[0]), bhi(P[0]), blo(P[1]), bhi(P[1]), blo(P[2]), bhi(P[2]), blo(P[3]), bhi(P[3])};
#pragma unroll
  for (int i = 0; i < 8; i++) {
    bool r1 = (i >> 1) & 1;
    e[i]     = ex2(fmaf(v[i],  LOG2E, r1 ? mx1 : mx0));
    e[8 + i] = ex2(fmaf(v[i], -LOG2E, r1 ? mn1 : mn0));
  }
}

__global__ void __cluster_dims__(2, 1, 1) __launch_bounds__(384, 1)
fused_kernel(const __grid_constant__ Maps maps, const __nv_bfloat16* __restrict__ x, const __nv_bfloat16* __restrict__ wphi,
             const __nv_bfloat16* __restrict__ wo, const __nv_bfloat16* __restrict__ wg_, const __nv_bfloat16* __restrict__ wu_,
             const __nv_bfloat16* __restrict__ wd_, __nv_bfloat16* __restrict__ out) {
  extern __shared__ __align__(1024) unsigned char smem[];
  const uint32_t sb = smem_u32(smem);
  const int tid = threadIdx.x, lane = tid & 31;
  const int warp = __shfl_sync(0xffffffffu, tid >> 5, 0);
  const uint32_t rank = blockIdx.x & 1;
  const int cl = blockIdx.x >> 1;
  int quad, qi;
  if (cl < 4) { quad = 15; qi = cl; }
  else if (cl < 36) { quad = (cl - 4) & 7; qi = (cl - 4) >> 3; }
  else { qi = (cl - 36) / 7; quad = 8 + (cl - 36) - 7 * qi; }
  const int rb = quad, hg = 2 * qi + rank;
  const int rb3 = (quad & ~1) + rank, jf = 4 * (quad & 1) + qi;

  if (warp < 8) {
    asm volatile("setmaxnreg.inc.sync.aligned.u32 240;");
    if (elect_one()) {
#pragma unroll 1
      for (int d = warp; d + 9 < NSTAGE; d += 8) {
        mbar_init(sb + SM_EMPTY + d * 8, st_empty_cnt(d));
        mbar_init(sb + SM_FULL + (d + 9) * 8, 1);
        mbar_expect_tx(sb + SM_FULL + (d + 9) * 8, d + 9 >= ST_D ? 22528 : SLOT);
      }
      asm volatile("fence.mbarrier_init.release.cluster;" ::: "memory");
    }
    __syncwarp();
    bar_sync(0, 352);
    asm volatile("barrier.cluster.arrive.relaxed.aligned;" ::: "memory");
    const int wg = warp >> 2, wq = warp & 3, g = lane >> 2, t = lane & 3;
    const bool lead = (tid & 127) == 0;
    constexpr uint32_t db = (SM_BASE >> 4) | (512u << 16);
    auto release = [&](int d) {
      const int s = d + NSLOT;
      mbar_arrive_cluster(sb + SM_EMPTY + d * 8, s >= ST_GU ? (uint32_t)(s & 1) : rank);
    };
    const uint32_t lrow = (uint32_t)(wq * 16 + (lane & 7) + ((lane >> 3) & 1) * 8) * 128;
    const uint32_t lx = lane & 7, lhi = lane >> 4;
    if (wg == 1) bar_arrive(4, 256);

    float r0, r1;
    uint32_t E[4][8];
    uint32_t T = 0;
    {
      uint32_t A[32][4];
      const int sx = wg ? ST_X1 : ST_X0;
      {
        const uint32_t base = sb + sx * SLOT + lrow, baseb = sb + sx * SLOT + (wq * 16 + lx + lhi * 8) * 128;
        float cs[2][4], c0[2][4], c1[2][4];
#pragma unroll
        for (int i = 0; i < 4; i++) { cs[0][i] = cs[1][i] = c0[0][i] = c0[1][i] = c1[0][i] = c1[1][i] = 0.f; }
        uint32_t bt[2][4][4];
        if (wg == 1) bar_sync(13, 256);
#pragma unroll
        for (int c = -1; c < 8; c++) {
          if (c < 7) {
            const int n = c + 1;
            if (n % 3 == 0) mbar_wait(sb + SM_FULL + (sx + n / 3) * 8);
#pragma unroll
            for (int k = 0; k < 4; k++) {
              ldsm4(A[4 * n + k], base + n * 8192 + (((2 * k + lhi) ^ lx) << 4));
              ldsm4(bt[n & 1][k], baseb + n * 8192 + (((2 * k + ((lane >> 3) & 1)) ^ lx) << 4));
            }
          }
          if (c >= 0) {
#pragma unroll
            for (int k = 0; k < 4; k++) {
              const uint32_t (&f)[4] = A[4 * c + k];
              mma16816(cs[k & 1], f, 0x3F803F80u, 0x3F803F80u);
              mma16816(c0[k & 1], f, bt[c & 1][k][0], bt[c & 1][k][1]);
              mma16816(c1[k & 1], f, bt[c & 1][k][2], bt[c & 1][k][3]);
            }
          }
        }
        if (wg == 0) bar_arrive(13, 256);
        const float s0 = (cs[0][0] + cs[1][0]) * (1.f / 512.f), s1 = (cs[0][2] + cs[1][2]) * (1.f / 512.f);
        asm volatile("barrier.cluster.wait.aligned;" ::: "memory");
        if (lane < 3) release(sx + lane);
        const uint32_t m0 = pack2(s0, s0), m1 = pack2(s1, s1);
        float q0 = (g & 1) ? c0[0][1] + c0[1][1] : c0[0][0] + c0[1][0];
        float q1 = (g & 1) ? c1[0][3] + c1[1][3] : c1[0][2] + c1[1][2];
        q0 = __shfl_sync(0xffffffffu, q0, (lane & ~3) | (g >> 1));
        q1 = __shfl_sync(0xffffffffu, q1, (lane & ~3) | (g >> 1));
        r0 = rsqrtf(fmaxf(q0 * (1.f / 512.f) - s0 * s0, 0.f) + 1e-5f);
        r1 = rsqrtf(fmaxf(q1 * (1.f / 512.f) - s1 * s1, 0.f) + 1e-5f);
#pragma unroll
        for (int ks = 0; ks < 32; ks++) {
          A[ks][0] = hsub2(A[ks][0], m0); A[ks][1] = hsub2(A[ks][1], m1);
          A[ks][2] = hsub2(A[ks][2], m0); A[ks][3] = hsub2(A[ks][3], m1);
        }
      }
      const uint32_t wpa = sb + SM_WPHI + ((lane & 7) + ((lane >> 3) & 1) * 8) * 32 + lhi * 16;
      const uint32_t scr = sb + (wg ? (ST_SCR1 % NSLOT) : (ST_SCR0 % NSLOT)) * SLOT;
#pragma unroll 1
      for (int ps = 0; ps < 3; ps++) {
        const int st0 = ps == 0 ? ST_WK : (ps == 1 ? ST_WV : ST_WQ);
        const uint32_t wdesc = DESC((ps == 0 ? ST_WK % NSLOT : (ps == 1 ? ST_WV % NSLOT : ST_WQ % NSLOT)) * SLOT);
        float acc[32];
        bar_sync(4 + wg, 256);
#pragma unroll
        for (int i = 0; i < 3; i++) {
          mbar_wait(sb + SM_FULL + (st0 + i) * 8);
          wg_fence();
#pragma unroll
          for (int kk = 0; kk < (i < 2 ? 12 : 8); kk++)
            wgmma_rs_n64(acc, A[12 * i + kk], wdesc + ((i * SLOT + kk * 2048) >> 4), (i | kk) != 0);
          wg_commit();
          if (i == 1) { wg_wait<1>(); if (lead) release(st0); }
        }
        if (ps == 1 && wg == 0) bar_arrive(5, 256);
        uint32_t a[4][4], b[4][4];
        mbar_wait(sb + SM_MISCB);
        T = (*reinterpret_cast<volatile unsigned*>(smem + SM_EPOCH) & 1) ^ 1;
#pragma unroll
        for (int h = 0; h < 4; h++) ldsm4t(b[h], wpa + h * 512);
        wg_wait<0>();
        if ((tid & 127) < 2) release(st0 + 1 + (tid & 1));
#pragma unroll
        for (int h = 0; h < 4; h++) {
          a[h][0] = pack2(acc[8 * h + 0] * r0, acc[8 * h + 1] * r0); a[h][1] = pack2(acc[8 * h + 2] * r1, acc[8 * h + 3] * r1);
          a[h][2] = pack2(acc[8 * h + 4] * r0, acc[8 * h + 5] * r0); a[h][3] = pack2(acc[8 * h + 6] * r1, acc[8 * h + 7] * r1);
        }
        if (ps != 1) {
          {
            float pp[4][2][4];
#pragma unroll
            for (int h = 0; h < 4; h++) {
#pragma unroll
              for (int i = 0; i < 4; i++) { pp[h][0][i] = 0.f; pp[h][1][i] = 0.f; }
              mma16816(pp[h][0], a[h], b[h][0], b[h][1]);
              mma16816(pp[h][1], a[h], b[h][2], b[h][3]);
            }
#pragma unroll
            for (int h = 0; h < 4; h++) {
              a[h][0] = pack2(pp[h][0][0], pp[h][0][1]); a[h][1] = pack2(pp[h][0][2], pp[h][0][3]);
              a[h][2] = pack2(pp[h][1][0], pp[h][1][1]); a[h][3] = pack2(pp[h][1][2], pp[h][1][3]);
            }
          }
          if (ps == 0 || wg == 0) bar_arrive(4 + (wg ^ 1), 256);
          if (ps == 0) mbar_wait(sb + SM_EMPTY + (wg ? ST_SCR1 - NSLOT : ST_SCR0 - NSLOT) * 8);
#pragma unroll 1
          for (int hp = 0; hp < 2; hp++) {
            float e[2][16];
            feat_exp(a[0], e[0]);
            feat_exp(a[1], e[1]);
            if (ps == 0) {
#pragma unroll
              for (int h = 0; h < 2; h++) {
                const float (&f)[16] = e[h];
                float sp0 = (f[0] + f[1]) + (f[4] + f[5]), sp1 = (f[2] + f[3]) + (f[6] + f[7]);
                float sn0 = (f[8] + f[9]) + (f[12] + f[13]), sn1 = (f[10] + f[11]) + (f[14] + f[15]);
                sp0 += __shfl_xor_sync(0xffffffffu, sp0, 1); sp1 += __shfl_xor_sync(0xffffffffu, sp1, 1);
                sn0 += __shfl_xor_sync(0xffffffffu, sn0, 1); sn1 += __shfl_xor_sync(0xffffffffu, sn1, 1);
                sp0 += __shfl_xor_sync(0xffffffffu, sp0, 2); sp1 += __shfl_xor_sync(0xffffffffu, sp1, 2);
                sn0 += __shfl_xor_sync(0xffffffffu, sn0, 2); sn1 += __shfl_xor_sync(0xffffffffu, sn1, 2);
                sp0 = rcp(sp0); sp1 = rcp(sp1); sn0 = rcp(sn0); sn1 = rcp(sn1);
                const uint32_t dst = scr + hp * 8192 + lrow;
                stsm4(dst + (((h * 4 + lhi) ^ lx) << 4), pack2(f[0] * sp0, f[1] * sp0), pack2(f[2] * sp1, f[3] * sp1),
                      pack2(f[4] * sp0, f[5] * sp0), pack2(f[6] * sp1, f[7] * sp1));
                stsm4(dst + (((h * 4 + 2 + lhi) ^ lx) << 4), pack2(f[8] * sn0, f[9] * sn0), pack2(f[10] * sn1, f[11] * sn1),
                      pack2(f[12] * sn0, f[13] * sn0), pack2(f[14] * sn1, f[15] * sn1));
              }
            } else {
#pragma unroll
              for (int i = 0; i < 16; i++) {
                A[i >> 2][i & 3] = A[4 + (i >> 2)][i & 3];
                A[4 + (i >> 2)][i & 3] = pack2(e[i >> 3][2 * (i & 7)], e[i >> 3][2 * (i & 7) + 1]);
              }
            }
#pragma unroll
            for (int i = 0; i < 4; i++) { a[0][i] = a[2][i]; a[1][i] = a[3][i]; }
          }
        } else {
#pragma unroll
          for (int h = 0; h < 4; h++) stsm4(scr + 16384 + lrow + (((2 * h + lhi) ^ lx) << 4), a[h][0], a[h][1], a[h][2], a[h][3]);
          fence_async_smem();
          bar_sync(3, 256);
          float kv[36];
          wg_fence();
#pragma unroll
          for (int ks = 0; ks < 8; ks++) {
            const uint32_t sk = (ks < 4 ? (ST_SCR0 % NSLOT) : (ST_SCR1 % NSLOT)) * SLOT + (ks & 3) * 2048;
            const uint32_t dv = (DESC(sk + 16384) & 0xFFFFu) | (((SM_ONES - sk - 16384) >> 4) << 16);
            wgmma_ss_n72_t11(kv, DESC(sk) + wg * 512, dv, ks != 0);
          }
          wg_commit();
          if (wg == 1) bar_arrive(4, 256);
          wg_wait<0>();
          if (lead) { mbar_arrive(sb + SM_EMPTY + ST_SCR0 * 8); mbar_arrive(sb + SM_EMPTY + ST_SCR1 * 8); }
          const int hl = 2 * wg + (wq >> 1), f = (wq & 1) * 16 + g;
          float* kvp = reinterpret_cast<float*>(smem + 2 * SLOT) + (hl * 32 + f) * 24;
          float c[8];
#pragma unroll
          for (int i = 0; i < 8; i++) c[i] = hl >= 2 ? (hl == 3 ? kv[24 + i] : kv[16 + i]) : (hl == 1 ? kv[8 + i] : kv[i]);
#pragma unroll
          for (int i = 0; i < 4; i++) {
            const int d = (i >> 1) * 8 + 2 * t + (i & 1), pos = d + ((d * 11) >> 5);
            kvp[pos] = c[(i >> 1) * 4 + (i & 1)];
            kvp[pos + 8 * 24] = c[(i >> 1) * 4 + (i & 1) + 2];
          }
          {
            float* cp = kvp + (t >> 1) * 8 * 24 + (t & 1) * 12;
            cp[3] = 1.f; cp[7] = 1.f; cp[11] = 1.f;
            if (t & 1) { cp[9] = (t >> 1) ? kv[34] : kv[32]; cp[10] = 0.f; }
          }
          fence_async_smem();
          bar_sync(6, 320);
        }
      }
#pragma unroll
      for (int i = 0; i < 32; i++) E[i >> 3][i & 7] = A[i >> 2][i & 3];
    }
    const int rh = 2 * rb + wg;
#define IDF ((g >> 1) == t ? ((g & 1) ? 0x3F800000u : 0x00003F80u) : 0u)
    const uint4* xb = reinterpret_cast<const uint4*>(smem + 2 * SLOT) + wq * 128 + lane;
    if (wg == 0) {
      mbar_wait(sb + SM_KVB);
      const uint4* sp = reinterpret_cast<const uint4*>(smem + 3 * SLOT) + tid * 6;
      uint32_t v[6][4];
      int it = 0;
#pragma unroll 1
      do {
#pragma unroll
        for (int i = 0; i < 6; i++)
          asm volatile("{\n.reg .b128 v;\nld.relaxed.gpu.b128 v, [%4];\nmov.b128 {%0,%1,%2,%3}, v;\n}"
                       : "=r"(v[i][0]), "=r"(v[i][1]), "=r"(v[i][2]), "=r"(v[i][3]) : "l"(sp + i) : "memory");
        sp = reinterpret_cast<const uint4*>(&g_kv[hg][tid][0]);
      } while (min(min(min(v[0][3], v[1][3]), min(v[2][3], v[3][3])), min(v[4][3], v[5][3])) != 0x41800000u && ++it < (1 << 18));
#define KVF(d) __uint_as_float(v[(d) / 3][(d) % 3])
      uint4* dst = reinterpret_cast<uint4*>(smem + SM_KVS + tid * 48);
      const uint32_t zz = pack2(KVF(16), 1.0f);
      dst[0] = make_uint4(pack2(KVF(0), KVF(1)), pack2(KVF(2), KVF(3)), pack2(KVF(4), KVF(5)), pack2(KVF(6), KVF(7)));
      dst[1] = make_uint4(pack2(KVF(8), KVF(9)), pack2(KVF(10), KVF(11)), pack2(KVF(12), KVF(13)), pack2(KVF(14), KVF(15)));
      dst[2] = make_uint4(zz, zz, zz, zz);
      __syncwarp();
      bar_sync(1, 128);
    }
    {
      uint4* op = &g_o[rh][hg][wq][0][lane];
      if (wg == 1) bar_sync(5, 256);
#pragma unroll 1
      for (int hp = 0; hp < 2; hp++) {
#pragma unroll
      for (int h = 0; h < 2; h++) {
        uint32_t b0[4], b1[4], b2[4];
        const uint32_t kb = sb + SM_KVS + ((2 * hp + h) * 32 + lane) * 48;
        ldsm4t(b0, kb); ldsm4t(b1, kb + 16); ldsm4t(b2, kb + 32);
        const uint32_t ep[4] = {E[h][0], E[h][1], E[h][2], E[h][3]}, en[4] = {E[h][4], E[h][5], E[h][6], E[h][7]};
        float np0[4] = {0, 0, 0, 0}, np1[4] = {0, 0, 0, 0}, nn0[4] = {0, 0, 0, 0}, nn1[4] = {0, 0, 0, 0}, dp[4] = {0, 0, 0, 0}, dn[4] = {0, 0, 0, 0};
        mma16816(dp, ep, b2[0], b2[1]);  mma16816(dn, en, b2[2], b2[3]);
        mma16816(np0, ep, b0[0], b0[1]); mma16816(nn0, en, b0[2], b0[3]);
        mma16816(np1, ep, b1[0], b1[1]); mma16816(nn1, en, b1[2], b1[3]);
        const float i0 = rcp(fmaf(dp[0], dn[1], fmaf(dn[0], dp[1], 1e-6f * dp[1] * dn[1])));
        const float i1 = rcp(fmaf(dp[2], dn[3], fmaf(dn[2], dp[3], 1e-6f * dp[3] * dn[3])));
        const float cp0 = dn[1] * i0, cn0 = dp[1] * i0, cp1 = dn[3] * i1, cn1 = dp[3] * i1;
        st_rlx4(op + (2 * hp + h) * 32,
                tg(pack2(fmaf(np0[0], cp0, nn0[0] * cn0), fmaf(np0[1], cp0, nn0[1] * cn0)), T),
                pack2(fmaf(np0[2], cp1, nn0[2] * cn1), fmaf(np0[3], cp1, nn0[3] * cn1)),
                pack2(fmaf(np1[0], cp0, nn1[0] * cn0), fmaf(np1[1], cp0, nn1[1] * cn0)),
                pack2(fmaf(np1[2], cp1, nn1[2] * cn1), fmaf(np1[3], cp1, nn1[3] * cn1)));
      }
#pragma unroll
        for (int i = 0; i < 8; i++) { E[0][i] = E[2][i]; E[1][i] = E[3][i]; }
      }
    }
    if (wg == 0) bar_arrive(5, 256);
    bar_arrive(10 + wg, 160);

    {
      uint32_t xr[4][4];
      {
        const uint32_t* xp = reinterpret_cast<const uint32_t*>(x + (size_t)(rh * 64 + wq * 16 + g) * 512 + hg * 64 + 2 * t);
#pragma unroll
        for (int i = 0; i < 8; i++) { xr[i >> 1][(i & 1) * 2] = __ldg(xp + 4 * i); xr[i >> 1][(i & 1) * 2 + 1] = __ldg(xp + 8 * 256 + 4 * i); }
      }
      uint32_t A[8][4][4];
      const uint4* op = &g_o[rh][0][wq][0][lane];
      float acc[32];
#pragma unroll
      for (int i = 0; i < 32; i++) acc[i] = 0.f;
      add_frag(acc, xr, IDF);
#pragma unroll
      for (int p = -1; p < 4; p++) {
        if (p < 3) {
          mbar_wait(sb + SM_XF + (wg * 4 + p + 1) * 8);
          get_pair(A[2 * p + 2], A[2 * p + 3], xb + (p + 1) * 1024, op + (p + 1) * 1024, T);
          if (lane == 0) mbar_arrive(sb + SM_XE + (wg * 4 + p + 1) * 8);
        }
        if (p == 0 && wg == 1) bar_sync(4, 256);
        if (p >= 0) {
          if (p != 2) mbar_wait(sb + SM_FULL + (ST_WO + (p + 1) / 2) * 8);
          wg_fence();
#pragma unroll
          for (int c = 2 * p; c < 2 * p + 2; c++)
#pragma unroll
            for (int s = 0; s < 4; s++)
              wgmma_rs_n64(acc, A[c][s], DESC(((ST_WO + c / 3) % NSLOT) * SLOT + ((c % 3) * 4 + s) * 2048), 1);
        }
      }
      wg_commit();
      if (wg == 0) bar_arrive(4, 256);
      wg_wait<0>();
      if ((tid & 127) < 3) release(ST_WO + (tid & 127));
      uint4* hp_ = &g_h[rh][hg][wq][0][lane];
      uint32_t hx = T;
#pragma unroll
      for (int s = 0; s < 4; s++) {
        const uint32_t h0 = pack2(acc[8 * s], acc[8 * s + 1]);
        st_rlx4(hp_ + s * 32, tg(h0, T), pack2(acc[8 * s + 2], acc[8 * s + 3]), pack2(acc[8 * s + 4], acc[8 * s + 5]), pack2(acc[8 * s + 6], acc[8 * s + 7]));
        hx |= (h0 & 1u) << (s + 1);
      }
      float s0 = 0.f, s1 = 0.f, q0 = 0.f, q1 = 0.f, q2 = 0.f, q3 = 0.f;
#pragma unroll
      for (int i = 0; i < 8; i++) {
        s0 += acc[4 * i] + acc[4 * i + 1]; s1 += acc[4 * i + 2] + acc[4 * i + 3];
        q0 = fmaf(acc[4 * i], acc[4 * i], q0); q2 = fmaf(acc[4 * i + 1], acc[4 * i + 1], q2);
        q1 = fmaf(acc[4 * i + 2], acc[4 * i + 2], q1); q3 = fmaf(acc[4 * i + 3], acc[4 * i + 3], q3);
      }
      q0 += q2; q1 += q3;
      {
        const bool up = t & 2;
        float s = (up ? s1 : s0) + __shfl_xor_sync(0xffffffffu, up ? s0 : s1, 2);
        float q = (up ? q1 : q0) + __shfl_xor_sync(0xffffffffu, up ? q0 : q1, 2);
        s += __shfl_xor_sync(0xffffffffu, s, 1);
        q += __shfl_xor_sync(0xffffffffu, q, 1);
        if (!(t & 1)) st_rlx2(&g_st[rh][hg][wq * 16 + g + (t >> 1) * 8], tg(__float_as_uint(s), T), __float_as_uint(q));
      }
      st_rlx1(&g_hx[rh][hg][wq][lane], hx);
    }
    bar_arrive(10 + wg, 160);

    const int rh3 = 2 * rb3 + wg;
    uint32_t HH[11][4], PH[11][4];
    const uint4* pp = &g_hh[rh3][jf ^ 1][0][wq][lane];
    {
      uint32_t A[8][4][4];
      const uint4* hp_ = &g_h[rh3][0][wq][0][lane];
      uint4* hhp = &g_hh[rh3][jf][0][wq][lane];
      const uint32_t dg = (db & 0xFFFFu) | (256u << 16);
      uint32_t m0, m1;
      mbar_wait(sb + SM_XF + ((2 + wg) * 4) * 8);
      {
        const uint2* sp = reinterpret_cast<const uint2*>(smem + SM_KV32 + wg * 4096) + 2 * t * 64 + wq * 16 + g;
        uint2 a0, a1, b0, b1;
        int it = 0;
#pragma unroll 1
        do {
          ld_rlx2(a0.x, a0.y, sp); ld_rlx2(a1.x, a1.y, sp + 64); ld_rlx2(b0.x, b0.y, sp + 8); ld_rlx2(b1.x, b1.y, sp + 72);
          sp = &g_st[rh3][2 * t][wq * 16 + g];
        } while (__any_sync(0xffffffffu, bad4(a0.x, a1.x, b0.x, b1.x, T)) && ++it < (1 << 18));
        float s0 = __uint_as_float(a0.x) + __uint_as_float(a1.x), q0 = __uint_as_float(a0.y) + __uint_as_float(a1.y);
        float s1 = __uint_as_float(b0.x) + __uint_as_float(b1.x), q1 = __uint_as_float(b0.y) + __uint_as_float(b1.y);
        s0 += __shfl_xor_sync(0xffffffffu, s0, 1); s1 += __shfl_xor_sync(0xffffffffu, s1, 1);
        q0 += __shfl_xor_sync(0xffffffffu, q0, 1); q1 += __shfl_xor_sync(0xffffffffu, q1, 1);
        s0 += __shfl_xor_sync(0xffffffffu, s0, 2); s1 += __shfl_xor_sync(0xffffffffu, s1, 2);
        q0 += __shfl_xor_sync(0xffffffffu, q0, 2); q1 += __shfl_xor_sync(0xffffffffu, q1, 2);
        s0 *= (1.f / 512.f); s1 *= (1.f / 512.f);
        r0 = rcp(fmaxf(q0 * (1.f / 512.f) - s0 * s0, 0.f) + 1e-5f);
        r1 = rcp(fmaxf(q1 * (1.f / 512.f) - s1 * s1, 0.f) + 1e-5f);
        m0 = pack2(s0, s0); m1 = pack2(s1, s1);
      }
#define UOFF(u) ((((ST_GU + (u) / 3) % NSLOT) * SLOT + ((u) % 3) * 8192) >> 4)
#define UNIT_PRE(u)  do { if ((u) % 3 == 0) mbar_wait(sb + SM_FULL + (ST_GU + (u) / 3) * 8); } while (0)
#define UNIT_POST(u) do { wg_commit(); if ((u) % 3 == 1 && (u) > 3) { wg_wait<2>(); if (lead) release(ST_GU + (u) / 3 - 1); } } while (0)
      float acc[64];
      const int rz = blockIdx.y;
#pragma unroll
      for (int ps = 0; ps < 2; ps++) {
        wg_fence();
#pragma unroll
        for (int k = 0; k < 16; k++) {
          const int u = 16 * ps + k, c = k >> 1;
          if (ps == 0 && (k == 0 || k == 4 || k == 8)) {
#pragma unroll
            for (int p = (k == 0 ? 0 : (k == 4 ? 1 : 3)); p < (k == 0 ? 1 : (k == 4 ? 3 : 4)); p++) {
              if (p > 0) mbar_wait(sb + SM_XF + ((2 + wg) * 4 + p) * 8);
              get_pair(A[2 * p], A[2 * p + 1], xb + p * 1024, hp_ + p * 1024, T);
              if (lane == 0) {
                if (wg == 0) mbar_arrive(sb + SM_XE + (8 + p) * 8);
                else if (p > 0) release(ST_XC + p - 1);
              }
            }
          }
          if (ps == 0 && (k & 1) == 0) {
#pragma unroll
            for (int s = 0; s < 4; s++) {
              A[c][s][0] = hsub2(A[c][s][0], m0); A[c][s][1] = hsub2(A[c][s][1], m1);
              A[c][s][2] = hsub2(A[c][s][2], m0); A[c][s][3] = hsub2(A[c][s][3], m1);
            }
            wg_fence();
          }
          UNIT_PRE(u);
          wgmma_rs_n128(acc, A[c][(k & 1) * 2], dg + UOFF(u), k != 0 ? 1 : (ps ? rz : 0));
          wgmma_rs_n128(acc, A[c][(k & 1) * 2 + 1], dg + UOFF(u) + 128, 1);
          UNIT_POST(u);
        }
        wg_wait<0>();
#pragma unroll
        for (int s = 0; s < 4; s++) {
          uint32_t (&hh)[4] = HH[4 + s];
          hh[0] = tg(pack2(acc[8 * s + 0] * acc[32 + 8 * s + 0], acc[8 * s + 1] * acc[32 + 8 * s + 1]), T);
          hh[1] = pack2(acc[8 * s + 2] * acc[32 + 8 * s + 2], acc[8 * s + 3] * acc[32 + 8 * s + 3]);
          hh[2] = pack2(acc[8 * s + 4] * acc[32 + 8 * s + 4], acc[8 * s + 5] * acc[32 + 8 * s + 5]);
          hh[3] = pack2(acc[8 * s + 6] * acc[32 + 8 * s + 6], acc[8 * s + 7] * acc[32 + 8 * s + 7]);
          st_rlx4(hhp + (4 * ps + s) * 128, hh[0], hh[1], hh[2], hh[3]);
        }
      }
      {
        float ag[24], au[24];
        const uint32_t* ph7 = reinterpret_cast<const uint32_t*>(&g_hh[rh3][jf ^ 1][7][wq][31]);
        uint32_t hv = 0;
        bar_sync(1 + wg, 128);
        wg_fence();
#pragma unroll
        for (int k = 0; k < 16; k++) {
          const int u = 32 + k, c = k >> 1;
          if (k == 6) {
#pragma unroll
            for (int s = 0; s < 4; s++) ld_rlx4(HH[s], hhp + s * 128);
          }
          if (k == 9) hv = ld_rlx1(ph7);
          if (k == 12) {
            int it = 0;
#pragma unroll 1
            while (((hv ^ T) & 1) && ++it < (1 << 18)) hv = ld_rlx1(ph7);
#pragma unroll
            for (int s = 0; s < 8; s++) ld_rlx4(PH[s], pp + s * 128);
          }
          UNIT_PRE(u);
          wgmma_rs_n48(ag, A[c][(k & 1) * 2], dg + UOFF(u), k != 0);
          wgmma_rs_n48(au, A[c][(k & 1) * 2], dg + UOFF(u) + 256, k != 0);
          wgmma_rs_n48(ag, A[c][(k & 1) * 2 + 1], dg + UOFF(u) + 128, 1);
          wgmma_rs_n48(au, A[c][(k & 1) * 2 + 1], dg + UOFF(u) + 256 + 128, 1);
          UNIT_POST(u);
        }
        wg_wait<0>();
#pragma unroll
        for (int s = 0; s < 3; s++) {
          uint32_t (&hh)[4] = HH[8 + s];
          hh[0] = tg(pack2(ag[8 * s + 0] * au[8 * s + 0], ag[8 * s + 1] * au[8 * s + 1]), T);
          hh[1] = pack2(ag[8 * s + 2] * au[8 * s + 2], ag[8 * s + 3] * au[8 * s + 3]);
          hh[2] = pack2(ag[8 * s + 4] * au[8 * s + 4], ag[8 * s + 5] * au[8 * s + 5]);
          hh[3] = pack2(ag[8 * s + 6] * au[8 * s + 6], ag[8 * s + 7] * au[8 * s + 7]);
          st_rlx4(hhp + (8 + s) * 128, hh[0], hh[1], hh[2], hh[3]);
        }
      }
    }

    {
      float ac[3][32], acc[32];
      uint32_t hr[4][4];
      const int m = jf >> 1, oc = (jf & 1) * 4 + m;
      const uint32_t* ph10 = reinterpret_cast<const uint32_t*>(&g_hh[rh3][jf ^ 1][10][wq][31]);
      uint32_t hv = 0;
      bar_arrive(8 + wg, 256);
      wg_fence();
#pragma unroll
      for (int k = 0; k < 3; k++) {
        mbar_wait(sb + SM_FULL + (ST_D + k) * 8);
        if (k == 1) hv = ld_rlx1(ph10);
#pragma unroll
        for (int s = 0; s < 11; s++) {
          if (k == 2 && s == 4) {
            int it = 0;
#pragma unroll 1
            while (((hv ^ T) & 1) && ++it < (1 << 18)) hv = ld_rlx1(ph10);
#pragma unroll
            for (int i = 8; i < 11; i++) ld_rlx4(PH[i], pp + i * 128);
          }
          wgmma_rs_n64(ac[k], HH[s], DESC(((ST_D + k) % NSLOT) * SLOT + s * 2048), s != 0);
        }
      }
      wg_commit();
      {
        int it = 0;
#pragma unroll 1
        while (__any_sync(0xffffffffu, bad4(PH[0][0], PH[1][0], PH[2][0], PH[3][0], T) | bad4(PH[4][0], PH[5][0], PH[6][0], PH[7][0], T) |
                                       bad4(PH[8][0], PH[9][0], PH[10][0], T, T))) {
#pragma unroll
          for (int s = 0; s < 11; s++) ld_rlx4(PH[s], pp + s * 128);
          if (++it > (1 << 18)) break;
        }
      }
      uint4* outb = &g_part[rh3][(jf & 1) * 4][m][wq][0][lane];
#pragma unroll
      for (int k = 0; k < 4; k++) {
        mbar_wait(sb + SM_FULL + (ST_D + 3 + k) * 8);
        wg_fence();
#pragma unroll
        for (int s = 0; s < 11; s++) {
          if (k < 3) wgmma_rs_n64(ac[k], PH[s], DESC(((ST_D + 3 + k) % NSLOT) * SLOT + s * 2048), 1);
          else wgmma_rs_n64(acc, HH[s], DESC(((ST_D + 6) % NSLOT) * SLOT + s * 2048), s != 0);
          if (s == 6 && k > 0) {
            wg_commit();
            wg_wait<1>();
            if (k == 1) bar_arrive(12, 320);
            const float (&a)[32] = ac[k - 1];
            uint4* p = outb + ((m + k) & 3) * 2048;
#pragma unroll
            for (int i = 0; i < 4; i++)
              st_rlx4(p + i * 32, tg(pack2(a[8 * i + 0], a[8 * i + 1]), T), pack2(a[8 * i + 2], a[8 * i + 3]),
                      pack2(a[8 * i + 4], a[8 * i + 5]), pack2(a[8 * i + 6], a[8 * i + 7]));
          }
        }
        wg_commit();
      }
      ld_chunk(hr, &g_h[rh3][oc][wq][0][lane]);
      uint32_t hx = ld_rlx1(&g_hx[rh3][oc][wq][lane]);
      mbar_wait(sb + SM_FULL + (ST_D + 7) * 8);
      wg_fence();
#pragma unroll
      for (int s = 0; s < 11; s++) wgmma_rs_n64(acc, PH[s], DESC(((ST_D + 7) % NSLOT) * SLOT + s * 2048), 1);
      wg_commit();
      wg_wait<0>();
#pragma unroll 1
      for (int q = 0; q < 3; q++) {
        uint32_t in[4][4];
        const uint4* sp = reinterpret_cast<const uint4*>(smem + ((ST_D % NSLOT) + wg) * SLOT) + q * 512 + wq * 128 + lane;
        mbar_wait_p(sb + SM_XF + (wg * 4 + q) * 8, 1);
        int it = 0;
#pragma unroll 1
        do {
#pragma unroll
          for (int s = 0; s < 4; s++)
            asm volatile("{\n.reg .b128 v;\nld.relaxed.gpu.b128 v, [%4];\nmov.b128 {%0,%1,%2,%3}, v;\n}"
                         : "=r"(in[s][0]), "=r"(in[s][1]), "=r"(in[s][2]), "=r"(in[s][3]) : "l"(sp + s * 32) : "memory");
          sp = &g_part[rh3][oc][(m - 1 - q) & 3][wq][0][lane];
        } while (__any_sync(0xffffffffu, bad4(in[0][0], in[1][0], in[2][0], in[3][0], T)) && ++it < (1 << 18));
        add_frag(acc, in, IDF);
      }
      {
        int it = 0;
#pragma unroll 1
        while (__any_sync(0xffffffffu, (hx ^ T) & 1) && ++it < (1 << 18)) hx = ld_rlx1(&g_hx[rh3][oc][wq][lane]);
      }
#pragma unroll
      for (int s = 0; s < 4; s++) hr[s][0] = (hr[s][0] & 0xFFFFFFFEu) | ((hx >> (s + 1)) & 1u);
#pragma unroll
      for (int i = 0; i < 32; i++) acc[i] *= (i & 2) ? r1 : r0;
      add_frag(acc, hr, IDF);
      bar_sync(9 - wg, 256);
      const uint32_t ob = sb + ((ST_D - 1) % NSLOT) * SLOT + wg * 8192;
#pragma unroll
      for (int s = 0; s < 4; s++)
        stsm4(ob + lrow + (((2 * s + lhi) ^ lx) << 4), pack2(acc[8 * s + 0], acc[8 * s + 1]), pack2(acc[8 * s + 2], acc[8 * s + 3]),
              pack2(acc[8 * s + 4], acc[8 * s + 5]), pack2(acc[8 * s + 6], acc[8 * s + 7]));
      __syncwarp();
      {
        const int row = wq * 16 + (lane >> 3);
        __nv_bfloat16* op = out + (size_t)(rh3 * 64 + row) * 512 + oc * 64 + lx * 8;
#pragma unroll
        for (int i = 0; i < 4; i++) {
          uint4 v;
          asm volatile("ld.shared.v4.b32 {%0,%1,%2,%3}, [%4];" : "=r"(v.x), "=r"(v.y), "=r"(v.z), "=r"(v.w)
                       : "r"(ob + (row + i * 4) * 128 + ((lx ^ (((lane >> 3) + i * 4) & 7)) << 4)) : "memory");
          asm volatile("st.global.v4.b32 [%0], {%1,%2,%3,%4};" ::"l"(op + i * 2048), "r"(v.x), "r"(v.y), "r"(v.z), "r"(v.w) : "memory");
        }
      }
    }
    asm volatile("barrier.cluster.arrive.relaxed.aligned;" ::: "memory");
    asm volatile("barrier.cluster.wait.aligned;" ::: "memory");
  } else {
    asm volatile("setmaxnreg.dec.sync.aligned.u32 24;");
    if (elect_one()) {
      if (warp == 8) {
#pragma unroll
        for (int k = 0; k < 9; k++) {
          const int s = k < 3 ? k : (k < 6 ? k + 3 : k - 3);
          const uint32_t bar = sb + SM_FULL + s * 8;
          mbar_init(bar, 1);
          mbar_expect_tx(bar, SLOT);
          if (s >= 3 && s < 6) tma2d(sb + s * SLOT, &maps.w, 512 + hg * 64, (s - 3) * 192, bar);
          else tma3d(sb + s * SLOT, &maps.x, 0, rb * 128 + (s >= 6 ? 64 : 0), 3 * (s % 3), bar);
        }
      } else if (warp == 9) {
        mbar_init(sb + SM_MISCB, 2);
        mbar_init(sb + SM_KVB, 1);
        mbar_expect_tx(sb + SM_KVB, 12288);
        mbar_expect_tx(sb + SM_MISCB, 2048);
        bulk_g2s(sb + SM_WPHI, wphi + hg * 1024, 2048, sb + SM_MISCB);
      } else if (warp == 10) {
        if ((sb & 0x3FFFF) != SM_BASE) __trap();
#pragma unroll 1
        for (int i = 0; i < 16; i++) {
          mbar_init(sb + SM_XF + i * 8, 1);
          mbar_expect_tx(sb + SM_XF + i * 8, (i == 8 || i == 12) ? 20480 : 16384);
          if (i < 12) mbar_init(sb + SM_XE + i * 8, 4);
        }
      } else {
        *reinterpret_cast<volatile unsigned*>(smem + SM_EPOCH) = atomicAdd(&g_start, 1u) / NCTA;
      }
      asm volatile("fence.mbarrier_init.release.cluster;" ::: "memory");
    }
    __syncwarp();
    if (warp != 11) bar_sync(0, 352);
    asm volatile("barrier.cluster.arrive.relaxed.aligned;" ::: "memory");
    if (warp == 8) {
      asm volatile("barrier.cluster.wait.aligned;" ::: "memory");
      if (elect_one()) {
        const CUtensorMap* mg = jf == 7 ? &maps.g7 : &maps.g;
        const CUtensorMap* mu = jf == 7 ? &maps.u7 : &maps.u;
        asm volatile("prefetch.tensormap [%0];" ::"l"(&maps.wo) : "memory");
        asm volatile("prefetch.tensormap [%0];" ::"l"(mg) : "memory");
        asm volatile("prefetch.tensormap [%0];" ::"l"(mu) : "memory");
        asm volatile("prefetch.tensormap [%0];" ::"l"(&maps.d) : "memory");
#pragma unroll 1
        for (int s = ST_WV; s < ST_XC; s++) {
          if (s == ST_SCR1) continue;
          mbar_wait(sb + SM_EMPTY + (s - 9) * 8);
          const uint32_t dst = sb + (s >= 18 ? s - 18 : s - 9) * SLOT, bar = sb + SM_FULL + s * 8;
          if (s < ST_WO) tma2d(dst, &maps.w, (s < ST_WQ ? 1024 : 0) + hg * 64, (s < ST_WQ ? s - ST_WV : s - ST_WQ) * 192, bar);
          else { mbar_wait(bar - 8); tma2d(dst, &maps.wo, hg * 64, (s - ST_WO) * 192, bar); }
        }
        const int jc = jf == 7 ? 0 : jf;
        int slot = (ST_GU + 1 - rank) % NSLOT;
#pragma unroll 1
        for (int s = ST_GU + 1 - rank; s < NSTAGE; s += 2) {
          mbar_wait(sb + SM_EMPTY + (s - 9) * 8);
          if (s > ST_GU && s < ST_GU + 6) mbar_wait(sb + SM_FULL + (s - 1) * 8);
          const uint32_t dst = sb + slot * SLOT, bar = sb + SM_FULL + s * 8;
          if (s < ST_D) {
#pragma unroll 1
            for (int i = 0; i < 3; i++) {
              const int u = (s - ST_GU) * 3 + i;
              tma3d_mc(dst + i * 8192, mg, (u >> 4) * 64, jc, (u & 15) * 32, bar);
              tma3d_mc(dst + i * 8192 + 4096, mu, (u >> 4) * 64, jc, (u & 15) * 32, bar);
            }
          } else {
            const int i = s - ST_D, k = i < 3 ? i : (i < 6 ? i - 3 : 3), pt = (i >= 3 && i != 6) ? 1 : 0;
            tma2d_mc(dst, &maps.d, ((jf & 1) * 4 + (((jf >> 1) + 1 + k) & 3)) * 64, (jf ^ pt) * 176, bar);
          }
          slot += 2; if (slot >= NSLOT) slot -= NSLOT;
        }
      }
      __syncwarp();
    } else {
      asm volatile("barrier.cluster.wait.aligned;" ::: "memory");
      if (warp == 11) {
#pragma unroll
        for (int i = 0; i < 4; i++)
          reinterpret_cast<uint4*>(smem + SM_ONES)[lane + 32 * i] = make_uint4(0x3F803F80u, 0x3F803F80u, 0x3F803F80u, 0x3F803F80u);
        fence_async_smem();
        __syncwarp();
        if (lane == 0) mbar_arrive(sb + SM_MISCB);
      }
      mbar_wait(sb + SM_MISCB);
      const unsigned epoch = *reinterpret_cast<volatile unsigned*>(smem + SM_EPOCH);
      const uint32_t T = (epoch & 1) ^ 1;
      if (warp == 11) {
        (&g_kv[hg][rb * 8][0])[lane] = make_float4(0.f, 0.f, 0.f, 0.f);
        if (lane < 16) (&g_kv[hg][rb * 8][0])[32 + lane] = make_float4(0.f, 0.f, 0.f, 0.f);
        __syncwarp();
        if (elect_one()) asm volatile("red.release.gpu.global.add.u32 [%0], 8;" ::"l"(&g_kvcnt[hg * 32 + 1]) : "memory");
        mbar_wait(sb + SM_FULL + (ST_WK + 2) * 8);
        if (elect_one()) {
          asm volatile("cp.async.bulk.prefetch.L2.global [%0], 4096;" ::"l"((const char*)wo + blockIdx.x * 4096) : "memory");
          asm volatile("cp.async.bulk.prefetch.L2.global [%0], 11008;" ::"l"((const char*)wg_ + blockIdx.x * 11008) : "memory");
          asm volatile("cp.async.bulk.prefetch.L2.global [%0], 11008;" ::"l"((const char*)wu_ + blockIdx.x * 11008) : "memory");
          asm volatile("cp.async.bulk.prefetch.L2.global [%0], 11008;" ::"l"((const char*)wd_ + blockIdx.x * 11008) : "memory");
          mbar_wait(sb + SM_EMPTY + ST_SCR0 * 8);
          const unsigned target = (epoch + 1) * 128;
          unsigned v; int it = 0;
#pragma unroll 1
          do {
            asm volatile("ld.acquire.gpu.global.u32 %0, [%1];" : "=r"(v) : "l"(&g_kvcnt[hg * 32]) : "memory");
            if (++it > (1 << 18)) break;
          } while ((int)(v - target) < 0);
          asm volatile("fence.proxy.async.global;" ::: "memory");
          bulk_g2s(sb + 3 * SLOT, &g_kv[hg][0][0], 12288, sb + SM_KVB);
        }
        __syncwarp();
      } else {
        const int w = warp - 9;
        st_rlx4(reinterpret_cast<uint4*>(&g_st[2 * rb + w][hg][0]) + lane, T ^ 1, T ^ 1, T ^ 1, T ^ 1);
        if (lane < 8) st_rlx4(&g_o[2 * rb + w][hg][lane >> 1][3][30 + (lane & 1)], T ^ 1, T ^ 1, T ^ 1, T ^ 1);
        st_rlx4(&g_part[2 * rb3 + w][(jf & 1) * 4 + (lane >> 3)][jf >> 1][(lane >> 1) & 3][3][30 + (lane & 1)], T ^ 1, T ^ 1, T ^ 1, T ^ 1);
        if (lane < 16) st_rlx4(&g_hh[2 * rb3 + w][jf][7 + (lane >> 3) * 3][(lane >> 1) & 3][30 + (lane & 1)], T ^ 1, T ^ 1, T ^ 1, T ^ 1);
        if (w == 0) {
          mbar_wait(sb + SM_FULL + (ST_WQ + 2) * 8);
          unsigned v; int it = 0;
#pragma unroll 1
          do {
            asm volatile("ld.acquire.gpu.global.u32 %0, [%1];" : "=r"(v) : "l"(&g_kvcnt[hg * 32 + 1]) : "memory");
          } while ((int)(v - (epoch + 1) * 128) < 0 && ++it < (1 << 18));
          asm volatile("fence.proxy.async.global;" ::: "memory");
        }
        bar_sync(6, 320);
        if (w == 0 && elect_one()) {
          asm volatile("cp.reduce.async.bulk.global.shared::cta.bulk_group.add.f32 [%0], [%1], 12288;"
                       ::"l"(&g_kv[hg][0][0]), "r"(sb + 2 * SLOT) : "memory");
          asm volatile("cp.async.bulk.commit_group;" ::: "memory");
          asm volatile("cp.async.bulk.wait_group 0;" ::: "memory");
          asm volatile("red.relaxed.gpu.global.add.u32 [%0], 8;" ::"l"(&g_kvcnt[hg * 32]) : "memory");
        }
        __syncwarp();
        mbar_wait(sb + SM_KVB);
        if (w == 0) { mbar_wait(sb + SM_EMPTY + 11 * 8); mbar_wait(sb + SM_EMPTY + 12 * 8); mbar_wait(sb + SM_EMPTY + 13 * 8); }
#pragma unroll 1
        for (int ph = 0; ph < 2; ph++) {
          const int use = 2 * ph + w, r = ph ? 2 * rb3 + w : 2 * rb + w;
          const uint32_t* pw = ph ? reinterpret_cast<const uint32_t*>(&g_st[r][lane >> 2][(lane & 3) * 16 + 15])
                                  : reinterpret_cast<const uint32_t*>(&g_o[r][lane >> 2][lane & 3][3][31]);
          const char* src = reinterpret_cast<const char*>(ph ? &g_h[r][0][0][0][0] : &g_o[r][0][0][0][0]);
          const uint32_t bf = sb + SM_XF + use * 32, be = sb + SM_XE + (use - 1) * 32;
          bar_sync(10 + w, 160);
          int it = 0;
#pragma unroll 1
          for (bool miss = true; __any_sync(0xffffffffu, miss) && ++it < (1 << 18);) { if (miss) miss = (ld_rlx1(pw) ^ T) & 1; }
          if (elect_one()) {
            if (use > 0) mbar_wait(be);
            if (ph) bulk_g2s(sb + SM_KV32 + w * 4096, &g_st[r][0][0], 4096, bf);
#pragma unroll
            for (int p = 0; p < 4; p++) {
              if (p > 0 && use > 0) mbar_wait(be + p * 8);
              bulk_g2s(sb + 2 * SLOT + p * 16384, src + p * 16384, 16384, bf + p * 8);
            }
          }
          __syncwarp();
        }
        {
          const int m = jf >> 1, oc = (jf & 1) * 4 + m;
          const uint32_t* pw = reinterpret_cast<const uint32_t*>(&g_part[2 * rb3 + w][oc][(m - 1 - (lane >> 2)) & 3][lane & 3][3][31]);
          bar_sync(12, 320);
          bool miss = lane < 12; int it = 0;
#pragma unroll 1
          for (int q = 0; q < 3; q++) {
#pragma unroll 1
            while ((__ballot_sync(0xffffffffu, miss) >> (4 * q) & 15) && ++it < (1 << 18)) { if (miss && (lane >> 2) <= q + 1) miss = (ld_rlx1(pw) ^ T) & 1; }
            if (elect_one()) {
              const uint32_t bar = sb + SM_XF + (w * 4 + q) * 8;
              mbar_expect_tx(bar, 8192);
              bulk_g2s(sb + ((ST_D % NSLOT) + w) * SLOT + q * 8192, &g_part[2 * rb3 + w][oc][(m - 1 - q) & 3][0][0][0], 8192, bar);
            }
            __syncwarp();
          }
        }
      }
    }
    asm volatile("barrier.cluster.arrive.relaxed.aligned;" ::: "memory");
    asm volatile("barrier.cluster.wait.aligned;" ::: "memory");
  }
}

typedef CUresult (*EncodeFn)(CUtensorMap*, CUtensorMapDataType, cuuint32_t, void*, const cuuint64_t*, const cuuint64_t*,
                             const cuuint32_t*, const cuuint32_t*, CUtensorMapInterleave, CUtensorMapSwizzle,
                             CUtensorMapL2promotion, CUtensorMapFloatOOBfill);

void encode(EncodeFn fn, CUtensorMap* m, const void* base, int rank, const cuuint64_t* dims, const cuuint64_t* strides,
            const cuuint32_t* box) {
  cuuint32_t es[3] = {1, 1, 1};
  fn(m, CU_TENSOR_MAP_DATA_TYPE_BFLOAT16, (cuuint32_t)rank, const_cast<void*>(base), dims, strides, box, es,
     CU_TENSOR_MAP_INTERLEAVE_NONE, CU_TENSOR_MAP_SWIZZLE_128B, CU_TENSOR_MAP_L2_PROMOTION_L2_256B,
     CU_TENSOR_MAP_FLOAT_OOB_FILL_NONE);
}

}

extern "C" void kernel_launch(void* const* d_in, const int* in_sizes, int n_in, void* d_out, int out_size) {
  (void)in_sizes; (void)n_in; (void)out_size;
  const __nv_bfloat16* x    = (const __nv_bfloat16*)d_in[0];
  const __nv_bfloat16* wqkv = (const __nv_bfloat16*)d_in[1];
  const __nv_bfloat16* wphi = (const __nv_bfloat16*)d_in[2];
  const __nv_bfloat16* wo   = (const __nv_bfloat16*)d_in[3];
  const __nv_bfloat16* wg   = (const __nv_bfloat16*)d_in[5];
  const __nv_bfloat16* wu   = (const __nv_bfloat16*)d_in[6];
  const __nv_bfloat16* wd   = (const __nv_bfloat16*)d_in[7];

  static EncodeFn fn = nullptr;
  if (!fn) {
    void* p = nullptr;
    cudaDriverEntryPointQueryResult qr;
    cudaGetDriverEntryPoint("cuTensorMapEncodeTiled", &p, cudaEnableDefault, &qr);
    fn = (EncodeFn)p;
    cudaFuncSetAttribute(fused_kernel, cudaFuncAttributeMaxDynamicSharedMemorySize, SM_TOTAL);
  }
  Maps maps;
  {
    cuuint64_t d[3] = {64, 2048, 8}, s[2] = {1024, 128}; cuuint32_t b[3] = {64, 64, 3};
    encode(fn, &maps.x, x, 3, d, s, b);
  }
  {
    cuuint64_t d[2] = {1536, 512}, s[1] = {3072}; cuuint32_t b[2] = {64, 192};
    encode(fn, &maps.w, wqkv, 2, d, s, b);
  }
  {
    cuuint64_t d[2] = {512, 512}, s[1] = {1024}; cuuint32_t b[2] = {64, 192};
    encode(fn, &maps.wo, wo, 2, d, s, b);
  }
  {
    cuuint64_t d[3] = {176, 7, 512}, d7[3] = {144, 1, 512}, s[2] = {352, 2752}; cuuint32_t b[3] = {64, 1, 32};
    encode(fn, &maps.g, wg, 3, d, s, b);
    encode(fn, &maps.u, wu, 3, d, s, b);
    encode(fn, &maps.g7, wg + 1232, 3, d7, s, b);
    encode(fn, &maps.u7, wu + 1232, 3, d7, s, b);
  }
  {
    cuuint64_t d[2] = {512, 1376}, s[1] = {1024}; cuuint32_t b[2] = {64, 176};
    encode(fn, &maps.d, wd, 2, d, s, b);
  }
  fused_kernel<<<NCTA, 384, SM_TOTAL>>>(maps, x, wphi, wo, wg, wu, wd, (__nv_bfloat16*)d_out);
}
```

```cpp
#include <cuda_runtime.h>
#include <cuda_bf16.h>
#include <cuda.h>
#include <stdint.h>

#define SAFE_WAIT 0

namespace {

constexpr int NCTA   = 128;
constexpr int SLOT   = 24576;
constexpr int NSLOT  = 9;
constexpr int NSTAGE = 47;

constexpr int ST_X0   = 0;
constexpr int ST_WK   = 3;
constexpr int ST_X1   = 6;
constexpr int ST_SCR0 = 9;
constexpr int ST_WV   = 10;
constexpr int ST_SCR1 = 13;
constexpr int ST_WQ   = 14;
constexpr int ST_WO   = 17;
constexpr int ST_XC   = 20;
constexpr int ST_GU   = 23;
constexpr int ST_D    = 39;

__host__ __device__ constexpr int st_empty_cnt(int d) {
  return ((d < 3 || (d >= 6 && d < 9) || (d >= ST_XC && d < ST_GU)) ? 4 : 2) * (d + 9 >= ST_GU ? 2 : 1);
}

constexpr uint32_t SM_BASE = 1024;
constexpr int SM_ONES = NSLOT * SLOT;
constexpr int SM_WPHI = SM_ONES + 2048;
constexpr int SM_KVS  = SM_WPHI + 2048;
constexpr int SM_KV32 = 4 * SLOT + 16384;
constexpr int SM_BAR  = SM_KVS + 6144;
constexpr int SM_FULL  = SM_BAR;
constexpr int SM_EMPTY = SM_BAR + NSTAGE * 8;
constexpr int SM_MISCB = SM_BAR + 2 * NSTAGE * 8;
constexpr int SM_KVB   = SM_MISCB + 8;
constexpr int SM_EPOCH = SM_KVB + 8;
constexpr int SM_XF    = SM_EPOCH + 8;
constexpr int SM_XE    = SM_XF + 16 * 8;
constexpr int SM_TOTAL = SM_BAR + 1024;

static_assert(SM_TOTAL == 232448 && SM_XE + 12 * 8 <= SM_TOTAL, "smem budget");

struct Maps { CUtensorMap x, w, wo, g, u, g7, u7, d; };

__device__ __align__(128) uint4    g_o[32][8][4][4][32];
__device__ __align__(128) uint4    g_h[32][8][4][4][32];
__device__ __align__(128) uint32_t g_hx[32][8][4][32];
__device__ __align__(128) uint2    g_st[32][8][64];
__device__ __align__(128) uint4    g_hh[32][8][11][4][32];
__device__ __align__(128) uint4    g_part[32][8][4][4][4][32];
__device__ __align__(128) float g_kv[8][2048 + 128];
__device__ __align__(128) unsigned g_kvcnt[8 * 32];
__device__ unsigned g_start;

__device__ __forceinline__ uint32_t smem_u32(const void* p) { return (uint32_t)__cvta_generic_to_shared(p); }
__device__ __forceinline__ void mbar_init(uint32_t bar, int cnt) {
  asm volatile("mbarrier.init.shared::cta.b64 [%0], %1;" ::"r"(bar), "r"(cnt) : "memory");
}
__device__ __forceinline__ void mbar_expect_tx(uint32_t bar, uint32_t bytes) {
  asm volatile("mbarrier.arrive.expect_tx.shared::cta.b64 _, [%0], %1;" ::"r"(bar), "r"(bytes) : "memory");
}
__device__ __forceinline__ void mbar_arrive(uint32_t bar) {
  asm volatile("mbarrier.arrive.shared::cta.b64 _, [%0];" ::"r"(bar) : "memory");
}
__device__ __forceinline__ void mbar_arrive_cluster(uint32_t bar, uint32_t rank) {
  asm volatile("{\n.reg .b32 ra;\nmapa.shared::cluster.u32 ra, %0, %1;\n"
               "mbarrier.arrive.shared::cluster.b64 _, [ra];\n}" ::"r"(bar), "r"(rank) : "memory");
}
__device__ __forceinline__ void mbar_wait_p(uint32_t bar, uint32_t parity) {
  asm volatile("{\n.reg .pred p;\nW: mbarrier.try_wait.parity.shared::cta.b64 p, [%0], %1;\n@!p bra W;\n}" ::"r"(bar), "r"(parity) : "memory");
}
__device__ __forceinline__ void mbar_wait(uint32_t bar) { mbar_wait_p(bar, 0); }
__device__ __forceinline__ bool elect_one() {
  uint32_t p;
  asm volatile("{\n.reg .pred P;\nelect.sync _|P, 0xffffffff;\nselp.u32 %0, 1, 0, P;\n}" : "=r"(p));
  return p != 0;
}
__device__ __forceinline__ void bar_sync(int id, int n)   { asm volatile("bar.sync %0, %1;" ::"r"(id), "r"(n) : "memory"); }
__device__ __forceinline__ void bar_arrive(int id, int n) { asm volatile("bar.arrive %0, %1;" ::"r"(id), "r"(n) : "memory"); }
__device__ __forceinline__ void fence_async_smem() { asm volatile("fence.proxy.async.shared::cta;" ::: "memory"); }
__device__ __forceinline__ void wg_fence()  { asm volatile("wgmma.fence.sync.aligned;" ::: "memory"); }
__device__ __forceinline__ void wg_commit() { asm volatile("wgmma.commit_group.sync.aligned;" ::: "memory"); }
template <int N> __device__ __forceinline__ void wg_wait() { asm volatile("wgmma.wait_group.sync.aligned %0;" ::"n"(N) : "memory"); }
#define DESC(off) (db + ((uint32_t)(off) >> 4))
__device__ __forceinline__ void tma2d(uint32_t dst, const CUtensorMap* m, int c0, int c1, uint32_t bar) {
  asm volatile("cp.async.bulk.tensor.2d.shared::cluster.global.mbarrier::complete_tx::bytes [%0], [%1, {%3, %4}], [%2];"
               ::"r"(dst), "l"(m), "r"(bar), "r"(c0), "r"(c1) : "memory");
}
__device__ __forceinline__ void tma2d_mc(uint32_t dst, const CUtensorMap* m, int c0, int c1, uint32_t bar) {
  asm volatile("cp.async.bulk.tensor.2d.shared::cluster.global.mbarrier::complete_tx::bytes.multicast::cluster [%0], [%1, {%3, %4}], [%2], %5;"
               ::"r"(dst), "l"(m), "r"(bar), "r"(c0), "r"(c1), "h"((uint16_t)3) : "memory");
}
__device__ __forceinline__ void tma3d(uint32_t dst, const CUtensorMap* m, int c0, int c1, int c2, uint32_t bar) {
  asm volatile("cp.async.bulk.tensor.3d.shared::cluster.global.mbarrier::complete_tx::bytes [%0], [%1, {%3, %4, %5}], [%2];"
               ::"r"(dst), "l"(m), "r"(bar), "r"(c0), "r"(c1), "r"(c2) : "memory");
}
__device__ __forceinline__ void tma3d_mc(uint32_t dst, const CUtensorMap* m, int c0, int c1, int c2, uint32_t bar) {
  asm volatile("cp.async.bulk.tensor.3d.shared::cluster.global.mbarrier::complete_tx::bytes.multicast::cluster [%0], [%1, {%3, %4, %5}], [%2], %6;"
               ::"r"(dst), "l"(m), "r"(bar), "r"(c0), "r"(c1), "r"(c2), "h"((uint16_t)3) : "memory");
}
__device__ __forceinline__ void ldsm4(uint32_t (&r)[4], uint32_t addr) {
  asm volatile("ldmatrix.sync.aligned.m8n8.x4.shared.b16 {%0,%1,%2,%3}, [%4];"
               : "=r"(r[0]), "=r"(r[1]), "=r"(r[2]), "=r"(r[3]) : "r"(addr) : "memory");
}
__device__ __forceinline__ void ldsm4t(uint32_t (&r)[4], uint32_t addr) {
  asm volatile("ldmatrix.sync.aligned.m8n8.x4.trans.shared.b16 {%0,%1,%2,%3}, [%4];"
               : "=r"(r[0]), "=r"(r[1]), "=r"(r[2]), "=r"(r[3]) : "r"(addr) : "memory");
}
__device__ __forceinline__ void stsm4(uint32_t addr, uint32_t r0, uint32_t r1, uint32_t r2, uint32_t r3) {
  asm volatile("stmatrix.sync.aligned.m8n8.x4.shared.b16 [%0], {%1,%2,%3,%4};"
               ::"r"(addr), "r"(r0), "r"(r1), "r"(r2), "r"(r3) : "memory");
}
__device__ __forceinline__ void mma16816(float (&c)[4], const uint32_t (&a)[4], uint32_t b0, uint32_t b1) {
  asm volatile("mma.sync.aligned.m16n8k16.row.col.f32.bf16.bf16.f32 {%0,%1,%2,%3},{%4,%5,%6,%7},{%8,%9},{%0,%1,%2,%3};"
               : "+f"(c[0]), "+f"(c[1]), "+f"(c[2]), "+f"(c[3])
               : "r"(a[0]), "r"(a[1]), "r"(a[2]), "r"(a[3]), "r"(b0), "r"(b1));
}
__device__ __forceinline__ void add_frag(float (&c)[32], const uint32_t (&a)[4][4], uint32_t id) {
#pragma unroll
  for (int i = 0; i < 8; i++)
    asm volatile("mma.sync.aligned.m16n8k8.row.col.f32.bf16.bf16.f32 {%0,%1,%2,%3},{%4,%5},{%6},{%0,%1,%2,%3};"
                 : "+f"(c[4 * i]), "+f"(c[4 * i + 1]), "+f"(c[4 * i + 2]), "+f"(c[4 * i + 3])
                 : "r"(a[i >> 1][(i & 1) * 2]), "r"(a[i >> 1][(i & 1) * 2 + 1]), "r"(id));
}
__device__ __forceinline__ uint32_t pack2(float lo, float hi) {
  uint32_t r; asm("cvt.rn.bf16x2.f32 %0, %1, %2;" : "=r"(r) : "f"(hi), "f"(lo)); return r;
}
__device__ __forceinline__ float blo(uint32_t w) { return __uint_as_float(w << 16); }
__device__ __forceinline__ float bhi(uint32_t w) { return __uint_as_float(w & 0xFFFF0000u); }
__device__ __forceinline__ uint32_t hsub2(uint32_t a, uint32_t b) { uint32_t r; asm("sub.rn.bf16x2 %0, %1, %2;" : "=r"(r) : "r"(a), "r"(b)); return r; }
__device__ __forceinline__ uint32_t hmax2(uint32_t a, uint32_t b) { uint32_t r; asm("max.bf16x2 %0, %1, %2;" : "=r"(r) : "r"(a), "r"(b)); return r; }
__device__ __forceinline__ uint32_t hmin2(uint32_t a, uint32_t b) { uint32_t r; asm("min.bf16x2 %0, %1, %2;" : "=r"(r) : "r"(a), "r"(b)); return r; }
__device__ __forceinline__ float ex2(float x) { float r; asm("ex2.approx.ftz.f32 %0, %1;" : "=f"(r) : "f"(x)); return r; }
__device__ __forceinline__ float rcp(float x) { float r; asm("rcp.approx.ftz.f32 %0, %1;" : "=f"(r) : "f"(x)); return r; }
__device__ __forceinline__ void ld_rlx4(uint32_t (&r)[4], const uint4* p) {
  asm volatile("{\n.reg .b128 v;\nld.relaxed.gpu.global.b128 v, [%4];\nmov.b128 {%0,%1,%2,%3}, v;\n}"
               : "=r"(r[0]), "=r"(r[1]), "=r"(r[2]), "=r"(r[3]) : "l"(p) : "memory");
}
__device__ __forceinline__ void st_rlx4(uint4* p, uint32_t a, uint32_t b, uint32_t c, uint32_t d) {
  asm volatile("st.relaxed.gpu.global.v4.b32 [%0], {%1,%2,%3,%4};" ::"l"(p), "r"(a), "r"(b), "r"(c), "r"(d) : "memory");
}
__device__ __forceinline__ void st_rlx2(uint2* p, uint32_t a, uint32_t b) {
  asm volatile("{\n.reg .b64 v;\nmov.b64 v, {%1,%2};\nst.relaxed.gpu.global.b64 [%0], v;\n}" ::"l"(p), "r"(a), "r"(b) : "memory");
}
__device__ __forceinline__ uint32_t ld_rlx1(const uint32_t* p) {
  uint32_t r; asm volatile("ld.relaxed.gpu.global.b32 %0, [%1];" : "=r"(r) : "l"(p) : "memory"); return r;
}
__device__ __forceinline__ void st_rlx1(uint32_t* p, uint32_t a) {
  asm volatile("st.relaxed.gpu.global.b32 [%0], %1;" ::"l"(p), "r"(a) : "memory");
}
__device__ __forceinline__ void ld_rlx2(uint32_t& a, uint32_t& b, const uint2* p) {
  asm volatile("{\n.reg .b64 v;\nld.relaxed.gpu.b64 v, [%2];\nmov.b64 {%0,%1}, v;\n}" : "=r"(a), "=r"(b) : "l"(p) : "memory");
}
__device__ __forceinline__ void bulk_g2s(uint32_t dst, const void* src, uint32_t bytes, uint32_t bar) {
  asm volatile("cp.async.bulk.shared::cluster.global.mbarrier::complete_tx::bytes [%0], [%1], %2, [%3];"
               ::"r"(dst), "l"(src), "r"(bytes), "r"(bar) : "memory");
}
__device__ __forceinline__ uint32_t tg(uint32_t w, uint32_t T) { return (w & 0xFFFFFFFEu) | T; }
__device__ __forceinline__ uint32_t bad4(uint32_t a, uint32_t b, uint32_t c, uint32_t d, uint32_t T) {
  uint32_t u, v;
  asm("lop3.b32 %0, %1, %2, %3, 0x7E;" : "=r"(u) : "r"(a), "r"(b), "r"(T));
  asm("lop3.b32 %0, %1, %2, %3, 0x7E;" : "=r"(v) : "r"(c), "r"(d), "r"(T));
  asm("lop3.b32 %0, %1, %2, 1, 0xA8;" : "=r"(u) : "r"(u), "r"(v));
  return u;
}

__device__ __forceinline__ void ld_chunk(uint32_t (&a)[4][4], const uint4* p) {
#pragma unroll
  for (int s = 0; s < 4; s++) ld_rlx4(a[s], p + s * 32);
}
__device__ __forceinline__ void get_pair(uint32_t (&a)[4][4], uint32_t (&b)[4][4], const uint4* sp, const uint4* gp, uint32_t T) {
  int it = 0;
#pragma unroll 1
  do {
#pragma unroll
    for (int s = 0; s < 8; s++) {
      uint32_t (&r)[4] = s < 4 ? a[s & 3] : b[s & 3];
      asm volatile("{\n.reg .b128 v;\nld.relaxed.gpu.b128 v, [%4];\nmov.b128 {%0,%1,%2,%3}, v;\n}"
                   : "=r"(r[0]), "=r"(r[1]), "=r"(r[2]), "=r"(r[3]) : "l"(sp + (s >> 2) * 512 + (s & 3) * 32) : "memory");
    }
    sp = gp;
  } while (__any_sync(0xffffffffu, bad4(a[0][0], a[1][0], a[2][0], a[3][0], T) | bad4(b[0][0], b[1][0], b[2][0], b[3][0], T)) && ++it < (1 << 18));
}

__device__ __forceinline__ void wgmma_rs_n48(float (&d)[24], const uint32_t (&a)[4], uint32_t descB, int scaleD) {
  asm volatile("{\n.reg .pred p;\n.reg .b64 db;\nsetp.ne.b32 p, %29, 0;\nmov.b64 db, {%28, 0x40000040};\n"
    "wgmma.mma_async.sync.aligned.m64n48k16.f32.bf16.bf16 {%0,%1,%2,%3,%4,%5,%6,%7,%8,%9,%10,%11,%12,%13,%14,%15,%16,%17,%18,%19,%20,%21,%22,%23}, {%24,%25,%26,%27}, db, p, 1, 1, 1;\n}\n"
    : "+f"(d[0]),"+f"(d[1]),"+f"(d[2]),"+f"(d[3]),"+f"(d[4]),"+f"(d[5]),"+f"(d[6]),"+f"(d[7]),"+f"(d[8]),"+f"(d[9]),"+f"(d[10]),"+f"(d[11]),"+f"(d[12]),"+f"(d[13]),"+f"(d[14]),"+f"(d[15]),"+f"(d[16]),"+f"(d[17]),"+f"(d[18]),"+f"(d[19]),"+f"(d[20]),"+f"(d[21]),"+f"(d[22]),"+f"(d[23])
    : "r"(a[0]), "r"(a[1]), "r"(a[2]), "r"(a[3]), "r"(descB), "r"(scaleD));
}
__device__ __forceinline__ void wgmma_rs_n64(float (&d)[32], const uint32_t (&a)[4], uint32_t descB, int scaleD) {
  asm volatile("{\n.reg .pred p;\n.reg .b64 db;\nsetp.ne.b32 p, %37, 0;\nmov.b64 db, {%36, 0x40000040};\n"
    "wgmma.mma_async.sync.aligned.m64n64k16.f32.bf16.bf16 {%0,%1,%2,%3,%4,%5,%6,%7,%8,%9,%10,%11,%12,%13,%14,%15,%16,%17,%18,%19,%20,%21,%22,%23,%24,%25,%26,%27,%28,%29,%30,%31}, {%32,%33,%34,%35}, db, p, 1, 1, 1;\n}\n"
    : "+f"(d[0]),"+f"(d[1]),"+f"(d[2]),"+f"(d[3]),"+f"(d[4]),"+f"(d[5]),"+f"(d[6]),"+f"(d[7]),"+f"(d[8]),"+f"(d[9]),"+f"(d[10]),"+f"(d[11]),"+f"(d[12]),"+f"(d[13]),"+f"(d[14]),"+f"(d[15]),"+f"(d[16]),"+f"(d[17]),"+f"(d[18]),"+f"(d[19]),"+f"(d[20]),"+f"(d[21]),"+f"(d[22]),"+f"(d[23]),"+f"(d[24]),"+f"(d[25]),"+f"(d[26]),"+f"(d[27]),"+f"(d[28]),"+f"(d[29]),"+f"(d[30]),"+f"(d[31])
    : "r"(a[0]), "r"(a[1]), "r"(a[2]), "r"(a[3]), "r"(descB), "r"(scaleD));
}
__device__ __forceinline__ void wgmma_rs_n128(float (&d)[64], const uint32_t (&a)[4], uint32_t descB, int scaleD) {
  asm volatile("{\n.reg .pred p;\n.reg .b64 db;\nsetp.ne.b32 p, %69, 0;\nmov.b64 db, {%68, 0x40000040};\n"
    "wgmma.mma_async.sync.aligned.m64n128k16.f32.bf16.bf16 {%0,%1,%2,%3,%4,%5,%6,%7,%8,%9,%10,%11,%12,%13,%14,%15,%16,%17,%18,%19,%20,%21,%22,%23,%24,%25,%26,%27,%28,%29,%30,%31,%32,%33,%34,%35,%36,%37,%38,%39,%40,%41,%42,%43,%44,%45,%46,%47,%48,%49,%50,%51,%52,%53,%54,%55,%56,%57,%58,%59,%60,%61,%62,%63}, {%64,%65,%66,%67}, db, p, 1, 1, 1;\n}\n"
    : "+f"(d[0]),"+f"(d[1]),"+f"(d[2]),"+f"(d[3]),"+f"(d[4]),"+f"(d[5]),"+f"(d[6]),"+f"(d[7]),"+f"(d[8]),"+f"(d[9]),"+f"(d[10]),"+f"(d[11]),"+f"(d[12]),"+f"(d[13]),"+f"(d[14]),"+f"(d[15]),"+f"(d[16]),"+f"(d[17]),"+f"(d[18]),"+f"(d[19]),"+f"(d[20]),"+f"(d[21]),"+f"(d[22]),"+f"(d[23]),"+f"(d[24]),"+f"(d[25]),"+f"(d[26]),"+f"(d[27]),"+f"(d[28]),"+f"(d[29]),"+f"(d[30]),"+f"(d[31]),"+f"(d[32]),"+f"(d[33]),"+f"(d[34]),"+f"(d[35]),"+f"(d[36]),"+f"(d[37]),"+f"(d[38]),"+f"(d[39]),"+f"(d[40]),"+f"(d[41]),"+f"(d[42]),"+f"(d[43]),"+f"(d[44]),"+f"(d[45]),"+f"(d[46]),"+f"(d[47]),"+f"(d[48]),"+f"(d[49]),"+f"(d[50]),"+f"(d[51]),"+f"(d[52]),"+f"(d[53]),"+f"(d[54]),"+f"(d[55]),"+f"(d[56]),"+f"(d[57]),"+f"(d[58]),"+f"(d[59]),"+f"(d[60]),"+f"(d[61]),"+f"(d[62]),"+f"(d[63])
    : "r"(a[0]), "r"(a[1]), "r"(a[2]), "r"(a[3]), "r"(descB), "r"(scaleD));
}
__device__ __forceinline__ void wgmma_ss_n72_t11(float (&d)[36], uint32_t descA, uint32_t descB, int scaleD) {
  asm volatile("{\n.reg .pred p;\n.reg .b64 da, db;\nsetp.ne.b32 p, %38, 0;\nmov.b64 da, {%36, 0x40000040};\nmov.b64 db, {%37, 0x40000040};\n"
    "wgmma.mma_async.sync.aligned.m64n72k16.f32.bf16.bf16 {%0,%1,%2,%3,%4,%5,%6,%7,%8,%9,%10,%11,%12,%13,%14,%15,%16,%17,%18,%19,%20,%21,%22,%23,%24,%25,%26,%27,%28,%29,%30,%31,%32,%33,%34,%35}, da, db, p, 1, 1, 1, 1;\n}\n"
    : "+f"(d[0]),"+f"(d[1]),"+f"(d[2]),"+f"(d[3]),"+f"(d[4]),"+f"(d[5]),"+f"(d[6]),"+f"(d[7]),"+f"(d[8]),"+f"(d[9]),"+f"(d[10]),"+f"(d[11]),"+f"(d[12]),"+f"(d[13]),"+f"(d[14]),"+f"(d[15]),"+f"(d[16]),"+f"(d[17]),"+f"(d[18]),"+f"(d[19]),"+f"(d[20]),"+f"(d[21]),"+f"(d[22]),"+f"(d[23]),"+f"(d[24]),"+f"(d[25]),"+f"(d[26]),"+f"(d[27]),"+f"(d[28]),"+f"(d[29]),"+f"(d[30]),"+f"(d[31]),"+f"(d[32]),"+f"(d[33]),"+f"(d[34]),"+f"(d[35])
    : "r"(descA), "r"(descB), "r"(scaleD));
}

constexpr float LOG2E = 1.4426950408889634f;

__device__ __forceinline__ void feat_exp(const uint32_t (&P)[4], float (&e)[16]) {
  uint32_t a = hmax2(P[0], P[2]), b = hmax2(P[1], P[3]);
  uint32_t mx = hmax2(__byte_perm(a, b, 0x5410), __byte_perm(a, b, 0x7632));
  a = hmin2(P[0], P[2]); b = hmin2(P[1], P[3]);
  uint32_t mn = hmin2(__byte_perm(a, b, 0x5410), __byte_perm(a, b, 0x7632));
  mx = hmax2(mx, __shfl_xor_sync(0xffffffffu, mx, 1));
  mn = hmin2(mn, __shfl_xor_sync(0xffffffffu, mn, 1));
  mx = hmax2(mx, __shfl_xor_sync(0xffffffffu, mx, 2));
  mn = hmin2(mn, __shfl_xor_sync(0xffffffffu, mn, 2));
  float mx0 = -blo(mx) * LOG2E, mx1 = -bhi(mx) * LOG2E, mn0 = blo(mn) * LOG2E, mn1 = bhi(mn) * LOG2E;
  float v[8] = {blo(P[0]), bhi(P[0]), blo(P[1]), bhi(P[1]), blo(P[2]), bhi(P[2]), blo(P[3]), bhi(P[3])};
#pragma unroll
  for (int i = 0; i < 8; i++) {
    bool r1 = (i >> 1) & 1;
    e[i]     = ex2(fmaf(v[i],  LOG2E, r1 ? mx1 : mx0));
    e[8 + i] = ex2(fmaf(v[i], -LOG2E, r1 ? mn1 : mn0));
  }
}

__global__ void __cluster_dims__(2, 1, 1) __launch_bounds__(384, 1)
fused_kernel(const __grid_constant__ Maps maps, const __nv_bfloat16* __restrict__ x, const __nv_bfloat16* __restrict__ wphi,
             const __nv_bfloat16* __restrict__ wo, const __nv_bfloat16* __restrict__ wg_, const __nv_bfloat16* __restrict__ wu_,
             const __nv_bfloat16* __restrict__ wd_, __nv_bfloat16* __restrict__ out) {
  extern __shared__ __align__(1024) unsigned char smem[];
  const uint32_t sb = smem_u32(smem);
  const int tid = threadIdx.x, lane = tid & 31;
  const int warp = __shfl_sync(0xffffffffu, tid >> 5, 0);
  const uint32_t rank = blockIdx.x & 1;
  const int cl = blockIdx.x >> 1;
  int quad, qi;
  if (cl < 4) { quad = 15; qi = cl; }
  else if (cl < 36) { quad = (cl - 4) & 7; qi = (cl - 4) >> 3; }
  else { qi = (cl - 36) / 7; quad = 8 + (cl - 36) - 7 * qi; }
  const int rb = quad, hg = 2 * qi + rank;
  const int rb3 = (quad & ~1) + rank, jf = 4 * (quad & 1) + qi;

  if (warp < 8) {
    asm volatile("setmaxnreg.inc.sync.aligned.u32 240;");
    if (elect_one()) {
#pragma unroll 1
      for (int d = warp; d + 9 < NSTAGE; d += 8) {
        mbar_init(sb + SM_EMPTY + d * 8, st_empty_cnt(d));
        mbar_init(sb + SM_FULL + (d + 9) * 8, 1);
        mbar_expect_tx(sb + SM_FULL + (d + 9) * 8, d + 9 >= ST_D ? 22528 : SLOT);
      }
      asm volatile("fence.mbarrier_init.release.cluster;" ::: "memory");
    }
    __syncwarp();
    bar_sync(0, 352);
    asm volatile("barrier.cluster.arrive.relaxed.aligned;" ::: "memory");
    const int wg = warp >> 2, wq = warp & 3, g = lane >> 2, t = lane & 3;
    const bool lead = (tid & 127) == 0;
    constexpr uint32_t db = (SM_BASE >> 4) | (512u << 16);
    auto release = [&](int d) {
      const int s = d + NSLOT;
      mbar_arrive_cluster(sb + SM_EMPTY + d * 8, s >= ST_GU ? (uint32_t)(s & 1) : rank);
    };
    const uint32_t lrow = (uint32_t)(wq * 16 + (lane & 7) + ((lane >> 3) & 1) * 8) * 128;
    const uint32_t lx = lane & 7, lhi = lane >> 4;
    if (wg == 1) bar_arrive(4, 256);

    float r0, r1;
    uint32_t E[4][8];
    uint32_t T = 0;
    {
      uint32_t A[32][4];
      const int sx = wg ? ST_X1 : ST_X0;
      {
        const uint32_t base = sb + sx * SLOT + lrow, baseb = sb + sx * SLOT + (wq * 16 + lx + lhi * 8) * 128;
        float cs[2][4], c0[2][4], c1[2][4];
#pragma unroll
        for (int i = 0; i < 4; i++) { cs[0][i] = cs[1][i] = c0[0][i] = c0[1][i] = c1[0][i] = c1[1][i] = 0.f; }
        uint32_t bt[2][4][4];
        if (wg == 1) bar_sync(13, 256);
#pragma unroll
        for (int c = -1; c < 8; c++) {
          if (c < 7) {
            const int n = c + 1;
            if (n % 3 == 0) mbar_wait(sb + SM_FULL + (sx + n / 3) * 8);
#pragma unroll
            for (int k = 0; k < 4; k++) {
              ldsm4(A[4 * n + k], base + n * 8192 + (((2 * k + lhi) ^ lx) << 4));
              ldsm4(bt[n & 1][k], baseb + n * 8192 + (((2 * k + ((lane >> 3) & 1)) ^ lx) << 4));
            }
          }
          if (c >= 0) {
#pragma unroll
            for (int k = 0; k < 4; k++) {
              const uint32_t (&f)[4] = A[4 * c + k];
              mma16816(cs[k & 1], f, 0x3F803F80u, 0x3F803F80u);
              mma16816(c0[k & 1], f, bt[c & 1][k][0], bt[c & 1][k][1]);
              mma16816(c1[k & 1], f, bt[c & 1][k][2], bt[c & 1][k][3]);
            }
          }
        }
        if (wg == 0) bar_arrive(13, 256);
        const float s0 = (cs[0][0] + cs[1][0]) * (1.f / 512.f), s1 = (cs[0][2] + cs[1][2]) * (1.f / 512.f);
        asm volatile("barrier.cluster.wait.aligned;" ::: "memory");
        if (lane < 3) release(sx + lane);
        const uint32_t m0 = pack2(s0, s0), m1 = pack2(s1, s1);
        float q0 = (g & 1) ? c0[0][1] + c0[1][1] : c0[0][0] + c0[1][0];
        float q1 = (g & 1) ? c1[0][3] + c1[1][3] : c1[0][2] + c1[1][2];
        q0 = __shfl_sync(0xffffffffu, q0, (lane & ~3) | (g >> 1));
        q1 = __shfl_sync(0xffffffffu, q1, (lane & ~3) | (g >> 1));
        r0 = rsqrtf(fmaxf(q0 * (1.f / 512.f) - s0 * s0, 0.f) + 1e-5f);
        r1 = rsqrtf(fmaxf(q1 * (1.f / 512.f) - s1 * s1, 0.f) + 1e-5f);
#pragma unroll
        for (int ks = 0; ks < 32; ks++) {
          A[ks][0] = hsub2(A[ks][0], m0); A[ks][1] = hsub2(A[ks][1], m1);
          A[ks][2] = hsub2(A[ks][2], m0); A[ks][3] = hsub2(A[ks][3], m1);
        }
      }
      const uint32_t wpa = sb + SM_WPHI + ((lane & 7) + ((lane >> 3) & 1) * 8) * 32 + lhi * 16;
      const uint32_t scr = sb + (wg ? (ST_SCR1 % NSLOT) : (ST_SCR0 % NSLOT)) * SLOT;
#pragma unroll 1
      for (int ps = 0; ps < 2; ps++) {
        const int st0 = ps == 0 ? ST_WK : ST_WQ;
        const uint32_t wdesc = DESC((ps == 0 ? ST_WK % NSLOT : ST_WQ % NSLOT) * SLOT);
        float acc[32];
        bar_sync(4 + wg, 256);
#pragma unroll
        for (int i = 0; i < 3; i++) {
          mbar_wait(sb + SM_FULL + (st0 + i) * 8);
          wg_fence();
#pragma unroll
          for (int kk = 0; kk < (i < 2 ? 12 : 8); kk++)
            wgmma_rs_n64(acc, A[12 * i + kk], wdesc + ((i * SLOT + kk * 2048) >> 4), (i | kk) != 0);
          wg_commit();
          if (i == 1) { wg_wait<1>(); if (lead) release(st0); }
        }
        uint32_t a[4][4], b[4][4];
        mbar_wait(sb + SM_MISCB);
        T = (*reinterpret_cast<volatile unsigned*>(smem + SM_EPOCH) & 1) ^ 1;
#pragma unroll
        for (int h = 0; h < 4; h++) ldsm4t(b[h], wpa + h * 512);
        wg_wait<0>();
        if ((tid & 127) < 2) release(st0 + 1 + (tid & 1));
#pragma unroll
        for (int h = 0; h < 4; h++) {
          a[h][0] = pack2(acc[8 * h + 0] * r0, acc[8 * h + 1] * r0); a[h][1] = pack2(acc[8 * h + 2] * r1, acc[8 * h + 3] * r1);
          a[h][2] = pack2(acc[8 * h + 4] * r0, acc[8 * h + 5] * r0); a[h][3] = pack2(acc[8 * h + 6] * r1, acc[8 * h + 7] * r1);
        }
        {
          float pp[4][2][4];
#pragma unroll
          for (int h = 0; h < 4; h++) {
#pragma unroll
            for (int i = 0; i < 4; i++) { pp[h][0][i] = 0.f; pp[h][1][i] = 0.f; }
            mma16816(pp[h][0], a[h], b[h][0], b[h][1]);
            mma16816(pp[h][1], a[h], b[h][2], b[h][3]);
          }
#pragma unroll
          for (int h = 0; h < 4; h++) {
            a[h][0] = pack2(pp[h][0][0], pp[h][0][1]); a[h][1] = pack2(pp[h][0][2], pp[h][0][3]);
            a[h][2] = pack2(pp[h][1][0], pp[h][1][1]); a[h][3] = pack2(pp[h][1][2], pp[h][1][3]);
          }
        }
        if (wg == 0) bar_arrive(5, 256);
        if (ps == 0) mbar_wait(sb + SM_EMPTY + (wg ? ST_SCR1 - NSLOT : ST_SCR0 - NSLOT) * 8);
        auto vgroup = [&](int c) {
          mbar_wait(sb + SM_FULL + (ST_WV + (8 * c + 7) / 12) * 8);
          wg_fence();
#pragma unroll
          for (int ks = 8 * c; ks < 8 * c + 8; ks++) wgmma_rs_n64(acc, A[ks], DESC((ST_WV % NSLOT) * SLOT + ks * 2048), ks != 0);
        };
#pragma unroll 1
        for (int hp = 0; hp < 2; hp++) {
          float e[2][16];
          if (ps == 0) { if (hp == 0) vgroup(0); else vgroup(2); }
          feat_exp(a[0], e[0]);
          feat_exp(a[1], e[1]);
          if (ps == 0) {
            if (hp == 0) vgroup(1); else vgroup(3);
#pragma unroll
              for (int h = 0; h < 2; h++) {
                const float (&f)[16] = e[h];
                float sp0 = (f[0] + f[1]) + (f[4] + f[5]), sp1 = (f[2] + f[3]) + (f[6] + f[7]);
                float sn0 = (f[8] + f[9]) + (f[12] + f[13]), sn1 = (f[10] + f[11]) + (f[14] + f[15]);
                sp0 += __shfl_xor_sync(0xffffffffu, sp0, 1); sp1 += __shfl_xor_sync(0xffffffffu, sp1, 1);
                sn0 += __shfl_xor_sync(0xffffffffu, sn0, 1); sn1 += __shfl_xor_sync(0xffffffffu, sn1, 1);
                sp0 += __shfl_xor_sync(0xffffffffu, sp0, 2); sp1 += __shfl_xor_sync(0xffffffffu, sp1, 2);
                sn0 += __shfl_xor_sync(0xffffffffu, sn0, 2); sn1 += __shfl_xor_sync(0xffffffffu, sn1, 2);
                sp0 = rcp(sp0); sp1 = rcp(sp1); sn0 = rcp(sn0); sn1 = rcp(sn1);
                const uint32_t dst = scr + hp * 8192 + lrow;
                stsm4(dst + (((h * 4 + lhi) ^ lx) << 4), pack2(f[0] * sp0, f[1] * sp0), pack2(f[2] * sp1, f[3] * sp1),
                      pack2(f[4] * sp0, f[5] * sp0), pack2(f[6] * sp1, f[7] * sp1));
                stsm4(dst + (((h * 4 + 2 + lhi) ^ lx) << 4), pack2(f[8] * sn0, f[9] * sn0), pack2(f[10] * sn1, f[11] * sn1),
                      pack2(f[12] * sn0, f[13] * sn0), pack2(f[14] * sn1, f[15] * sn1));
              }
          } else {
#pragma unroll
            for (int i = 0; i < 16; i++) {
              A[i >> 2][i & 3] = A[4 + (i >> 2)][i & 3];
              A[4 + (i >> 2)][i & 3] = pack2(e[i >> 3][2 * (i & 7)], e[i >> 3][2 * (i & 7) + 1]);
            }
          }
#pragma unroll
          for (int i = 0; i < 4; i++) { a[0][i] = a[2][i]; a[1][i] = a[3][i]; }
        }
        wg_commit();
        wg_wait<0>();
        if (ps == 0) {
          if ((tid & 127) < 3) release(ST_WV + (tid & 127));
#pragma unroll
          for (int h = 0; h < 4; h++)
            stsm4(scr + 16384 + lrow + (((2 * h + lhi) ^ lx) << 4), pack2(acc[8 * h + 0] * r0, acc[8 * h + 1] * r0), pack2(acc[8 * h + 2] * r1, acc[8 * h + 3] * r1),
                  pack2(acc[8 * h + 4] * r0, acc[8 * h + 5] * r0), pack2(acc[8 * h + 6] * r1, acc[8 * h + 7] * r1));
          fence_async_smem();
          bar_sync(3, 256);
          float kv[36];
          wg_fence();
#pragma unroll
          for (int ks = 0; ks < 8; ks++) {
            const uint32_t sk = (ks < 4 ? (ST_SCR0 % NSLOT) : (ST_SCR1 % NSLOT)) * SLOT + (ks & 3) * 2048;
            const uint32_t dv = (DESC(sk + 16384) & 0xFFFFu) | (((SM_ONES - sk - 16384) >> 4) << 16);
            wgmma_ss_n72_t11(kv, DESC(sk) + wg * 512, dv, ks != 0);
          }
          wg_commit();
          if (wg == 1) bar_arrive(4, 256);
          wg_wait<0>();
          if (lead) { mbar_arrive(sb + SM_EMPTY + ST_SCR0 * 8); mbar_arrive(sb + SM_EMPTY + ST_SCR1 * 8); }
          const int hl = 2 * wg + (wq >> 1), f = (wq & 1) * 16 + g;
          float* kvp = reinterpret_cast<float*>(smem + 2 * SLOT) + (hl * 32 + f) * 16 + 2 * t;
          float c[8];
#pragma unroll
          for (int i = 0; i < 8; i++) c[i] = hl >= 2 ? (hl == 3 ? kv[24 + i] : kv[16 + i]) : (hl == 1 ? kv[8 + i] : kv[i]);
#pragma unroll
          for (int n = 0; n < 2; n++) {
            *reinterpret_cast<float2*>(kvp + n * 8) = make_float2(c[4 * n], c[4 * n + 1]);
            *reinterpret_cast<float2*>(kvp + n * 8 + 128) = make_float2(c[4 * n + 2], c[4 * n + 3]);
          }
          if (t < 2) reinterpret_cast<float*>(smem + 2 * SLOT)[2048 + hl * 32 + f + t * 8] = t ? kv[34] : kv[32];
          fence_async_smem();
          bar_sync(6, 320);
        }
      }
#pragma unroll
      for (int i = 0; i < 32; i++) E[i >> 3][i & 7] = A[i >> 2][i & 3];
    }
    const int rh = 2 * rb + wg;
#define IDF ((g >> 1) == t ? ((g & 1) ? 0x3F800000u : 0x00003F80u) : 0u)
    const uint4* xb = reinterpret_cast<const uint4*>(smem + 2 * SLOT) + wq * 128 + lane;
    mbar_wait(sb + SM_KVB);
    {
      const int r = tid & 127;
      const float4* src = reinterpret_cast<const float4*>(smem + SM_KV32) + r;
#pragma unroll
      for (int i = 0; i < 4; i++) {
        const float4 a = src[i * 128];
        *reinterpret_cast<uint2*>(smem + SM_KVS + (i * 32 + (r >> 2)) * 48 + (r & 3) * 8) = make_uint2(pack2(a.x, a.y), pack2(a.z, a.w));
      }
      const uint32_t zz = pack2(reinterpret_cast<const float*>(smem + SM_ONES)[r], 1.0f);
      *reinterpret_cast<uint4*>(smem + SM_KVS + r * 48 + 32) = make_uint4(zz, zz, zz, zz);
      bar_sync(1 + wg, 128);
    }
    {
      uint4* op = &g_o[rh][hg][wq][0][lane];
      if (wg == 1) bar_sync(5, 256);
#pragma unroll 1
      for (int hp = 0; hp < 2; hp++) {
#pragma unroll
      for (int h = 0; h < 2; h++) {
        uint32_t b0[4], b1[4], b2[4];
        const uint32_t kb = sb + SM_KVS + ((2 * hp + h) * 32 + lane) * 48;
        ldsm4t(b0, kb); ldsm4t(b1, kb + 16); ldsm4t(b2, kb + 32);
        const uint32_t ep[4] = {E[h][0], E[h][1], E[h][2], E[h][3]}, en[4] = {E[h][4], E[h][5], E[h][6], E[h][7]};
        float np0[4] = {0, 0, 0, 0}, np1[4] = {0, 0, 0, 0}, nn0[4] = {0, 0, 0, 0}, nn1[4] = {0, 0, 0, 0}, dp[4] = {0, 0, 0, 0}, dn[4] = {0, 0, 0, 0};
        mma16816(dp, ep, b2[0], b2[1]);  mma16816(dn, en, b2[2], b2[3]);
        mma16816(np0, ep, b0[0], b0[1]); mma16816(nn0, en, b0[2], b0[3]);
        mma16816(np1, ep, b1[0], b1[1]); mma16816(nn1, en, b1[2], b1[3]);
        const float i0 = rcp(fmaf(dp[0], dn[1], fmaf(dn[0], dp[1], 1e-6f * dp[1] * dn[1])));
        const float i1 = rcp(fmaf(dp[2], dn[3], fmaf(dn[2], dp[3], 1e-6f * dp[3] * dn[3])));
        const float cp0 = dn[1] * i0, cn0 = dp[1] * i0, cp1 = dn[3] * i1, cn1 = dp[3] * i1;
        st_rlx4(op + (2 * hp + h) * 32,
                tg(pack2(fmaf(np0[0], cp0, nn0[0] * cn0), fmaf(np0[1], cp0, nn0[1] * cn0)), T),
                pack2(fmaf(np0[2], cp1, nn0[2] * cn1), fmaf(np0[3], cp1, nn0[3] * cn1)),
                pack2(fmaf(np1[0], cp0, nn1[0] * cn0), fmaf(np1[1], cp0, nn1[1] * cn0)),
                pack2(fmaf(np1[2], cp1, nn1[2] * cn1), fmaf(np1[3], cp1, nn1[3] * cn1)));
      }
#pragma unroll
        for (int i = 0; i < 8; i++) { E[0][i] = E[2][i]; E[1][i] = E[3][i]; }
      }
    }
    if (wg == 0) bar_arrive(5, 256);
    bar_arrive(10 + wg, 160);

    {
      uint32_t xr[4][4];
      {
        const uint32_t* xp = reinterpret_cast<const uint32_t*>(x + (size_t)(rh * 64 + wq * 16 + g) * 512 + hg * 64 + 2 * t);
#pragma unroll
        for (int i = 0; i < 8; i++) { xr[i >> 1][(i & 1) * 2] = __ldg(xp + 4 * i); xr[i >> 1][(i & 1) * 2 + 1] = __ldg(xp + 8 * 256 + 4 * i); }
      }
      uint32_t A[8][4][4];
      const uint4* op = &g_o[rh][0][wq][0][lane];
      float acc[32];
#pragma unroll
      for (int i = 0; i < 32; i++) acc[i] = 0.f;
      add_frag(acc, xr, IDF);
#pragma unroll
      for (int p = -1; p < 4; p++) {
        if (p < 3) {
          mbar_wait(sb + SM_XF + (wg * 4 + p + 1) * 8);
          get_pair(A[2 * p + 2], A[2 * p + 3], xb + (p + 1) * 1024, op + (p + 1) * 1024, T);
          if (lane == 0) mbar_arrive(sb + SM_XE + (wg * 4 + p + 1) * 8);
        }
        if (p == 0 && wg == 1) bar_sync(4, 256);
        if (p >= 0) {
          if (p != 2) mbar_wait(sb + SM_FULL + (ST_WO + (p + 1) / 2) * 8);
          wg_fence();
#pragma unroll
          for (int c = 2 * p; c < 2 * p + 2; c++)
#pragma unroll
            for (int s = 0; s < 4; s++)
              wgmma_rs_n64(acc, A[c][s], DESC(((ST_WO + c / 3) % NSLOT) * SLOT + ((c % 3) * 4 + s) * 2048), 1);
        }
      }
      wg_commit();
      if (wg == 0) bar_arrive(4, 256);
      wg_wait<0>();
      if ((tid & 127) < 3) release(ST_WO + (tid & 127));
      uint4* hp_ = &g_h[rh][hg][wq][0][lane];
      uint32_t hx = T;
#pragma unroll
      for (int s = 0; s < 4; s++) {
        const uint32_t h0 = pack2(acc[8 * s], acc[8 * s + 1]);
        st_rlx4(hp_ + s * 32, tg(h0, T), pack2(acc[8 * s + 2], acc[8 * s + 3]), pack2(acc[8 * s + 4], acc[8 * s + 5]), pack2(acc[8 * s + 6], acc[8 * s + 7]));
        hx |= (h0 & 1u) << (s + 1);
      }
      float s0 = 0.f, s1 = 0.f, q0 = 0.f, q1 = 0.f, q2 = 0.f, q3 = 0.f;
#pragma unroll
      for (int i = 0; i < 8; i++) {
        s0 += acc[4 * i] + acc[4 * i + 1]; s1 += acc[4 * i + 2] + acc[4 * i + 3];
        q0 = fmaf(acc[4 * i], acc[4 * i], q0); q2 = fmaf(acc[4 * i + 1], acc[4 * i + 1], q2);
        q1 = fmaf(acc[4 * i + 2], acc[4 * i + 2], q1); q3 = fmaf(acc[4 * i + 3], acc[4 * i + 3], q3);
      }
      q0 += q2; q1 += q3;
      {
        const bool up = t & 2;
        float s = (up ? s1 : s0) + __shfl_xor_sync(0xffffffffu, up ? s0 : s1, 2);
        float q = (up ? q1 : q0) + __shfl_xor_sync(0xffffffffu, up ? q0 : q1, 2);
        s += __shfl_xor_sync(0xffffffffu, s, 1);
        q += __shfl_xor_sync(0xffffffffu, q, 1);
        if (!(t & 1)) st_rlx2(&g_st[rh][hg][wq * 16 + g + (t >> 1) * 8], tg(__float_as_uint(s), T), __float_as_uint(q));
      }
      st_rlx1(&g_hx[rh][hg][wq][lane], hx);
    }
    bar_arrive(10 + wg, 160);

    const int rh3 = 2 * rb3 + wg;
    uint32_t HH[11][4], PH[11][4];
    const uint4* pp = &g_hh[rh3][jf ^ 1][0][wq][lane];
    {
      uint32_t A[8][4][4];
      const uint4* hp_ = &g_h[rh3][0][wq][0][lane];
      uint4* hhp = &g_hh[rh3][jf][0][wq][lane];
      const uint32_t dg = (db & 0xFFFFu) | (256u << 16);
      uint32_t m0, m1;
      mbar_wait(sb + SM_XF + ((2 + wg) * 4) * 8);
      {
        const uint2* sp = reinterpret_cast<const uint2*>(smem + SM_KV32 + wg * 4096) + 2 * t * 64 + wq * 16 + g;
        uint2 a0, a1, b0, b1;
        int it = 0;
#pragma unroll 1
        do {
          ld_rlx2(a0.x, a0.y, sp); ld_rlx2(a1.x, a1.y, sp + 64); ld_rlx2(b0.x, b0.y, sp + 8); ld_rlx2(b1.x, b1.y, sp + 72);
          sp = &g_st[rh3][2 * t][wq * 16 + g];
        } while (__any_sync(0xffffffffu, bad4(a0.x, a1.x, b0.x, b1.x, T)) && ++it < (1 << 18));
        float s0 = __uint_as_float(a0.x) + __uint_as_float(a1.x), q0 = __uint_as_float(a0.y) + __uint_as_float(a1.y);
        float s1 = __uint_as_float(b0.x) + __uint_as_float(b1.x), q1 = __uint_as_float(b0.y) + __uint_as_float(b1.y);
        s0 += __shfl_xor_sync(0xffffffffu, s0, 1); s1 += __shfl_xor_sync(0xffffffffu, s1, 1);
        q0 += __shfl_xor_sync(0xffffffffu, q0, 1); q1 += __shfl_xor_sync(0xffffffffu, q1, 1);
        s0 += __shfl_xor_sync(0xffffffffu, s0, 2); s1 += __shfl_xor_sync(0xffffffffu, s1, 2);
        q0 += __shfl_xor_sync(0xffffffffu, q0, 2); q1 += __shfl_xor_sync(0xffffffffu, q1, 2);
        s0 *= (1.f / 512.f); s1 *= (1.f / 512.f);
        r0 = rcp(fmaxf(q0 * (1.f / 512.f) - s0 * s0, 0.f) + 1e-5f);
        r1 = rcp(fmaxf(q1 * (1.f / 512.f) - s1 * s1, 0.f) + 1e-5f);
        m0 = pack2(s0, s0); m1 = pack2(s1, s1);
      }
#define UOFF(u) ((((ST_GU + (u) / 3) % NSLOT) * SLOT + ((u) % 3) * 8192) >> 4)
#define UNIT_PRE(u)  do { if ((u) % 3 == 0) mbar_wait(sb + SM_FULL + (ST_GU + (u) / 3) * 8); } while (0)
#define UNIT_POST(u) do { wg_commit(); if ((u) % 3 == 1 && (u) > 3) { wg_wait<2>(); if (lead) release(ST_GU + (u) / 3 - 1); } } while (0)
      float acc[64];
      const int rz = blockIdx.y;
#pragma unroll
      for (int ps = 0; ps < 2; ps++) {
        wg_fence();
#pragma unroll
        for (int k = 0; k < 16; k++) {
          const int u = 16 * ps + k, c = k >> 1;
          if (ps == 0 && (k == 0 || k == 4 || k == 8)) {
#pragma unroll
            for (int p = (k == 0 ? 0 : (k == 4 ? 1 : 3)); p < (k == 0 ? 1 : (k == 4 ? 3 : 4)); p++) {
              if (p > 0) mbar_wait(sb + SM_XF + ((2 + wg) * 4 + p) * 8);
              get_pair(A[2 * p], A[2 * p + 1], xb + p * 1024, hp_ + p * 1024, T);
              if (lane == 0) {
                if (wg == 0) mbar_arrive(sb + SM_XE + (8 + p) * 8);
                else if (p > 0) release(ST_XC + p - 1);
              }
            }
          }
          if (ps == 0 && (k & 1) == 0) {
#pragma unroll
            for (int s = 0; s < 4; s++) {
              A[c][s][0] = hsub2(A[c][s][0], m0); A[c][s][1] = hsub2(A[c][s][1], m1);
              A[c][s][2] = hsub2(A[c][s][2], m0); A[c][s][3] = hsub2(A[c][s][3], m1);
            }
            wg_fence();
          }
          UNIT_PRE(u);
          wgmma_rs_n128(acc, A[c][(k & 1) * 2], dg + UOFF(u), k != 0 ? 1 : (ps ? rz : 0));
          wgmma_rs_n128(acc, A[c][(k & 1) * 2 + 1], dg + UOFF(u) + 128, 1);
          UNIT_POST(u);
        }
        wg_wait<0>();
#pragma unroll
        for (int s = 0; s < 4; s++) {
          uint32_t (&hh)[4] = HH[4 + s];
          hh[0] = tg(pack2(acc[8 * s + 0] * acc[32 + 8 * s + 0], acc[8 * s + 1] * acc[32 + 8 * s + 1]), T);
          hh[1] = pack2(acc[8 * s + 2] * acc[32 + 8 * s + 2], acc[8 * s + 3] * acc[32 + 8 * s + 3]);
          hh[2] = pack2(acc[8 * s + 4] * acc[32 + 8 * s + 4], acc[8 * s + 5] * acc[32 + 8 * s + 5]);
          hh[3] = pack2(acc[8 * s + 6] * acc[32 + 8 * s + 6], acc[8 * s + 7] * acc[32 + 8 * s + 7]);
          st_rlx4(hhp + (4 * ps + s) * 128, hh[0], hh[1], hh[2], hh[3]);
        }
      }
      {
        float ag[24], au[24];
        const uint32_t* ph7 = reinterpret_cast<const uint32_t*>(&g_hh[rh3][jf ^ 1][7][wq][31]);
        uint32_t hv = 0;
        bar_sync(1 + wg, 128);
        wg_fence();
#pragma unroll
        for (int k = 0; k < 16; k++) {
          const int u = 32 + k, c = k >> 1;
          if (k == 6) {
#pragma unroll
            for (int s = 0; s < 4; s++) ld_rlx4(HH[s], hhp + s * 128);
          }
          if (k == 9) hv = ld_rlx1(ph7);
          if (k == 12) {
            int it = 0;
#pragma unroll 1
            while (((hv ^ T) & 1) && ++it < (1 << 18)) hv = ld_rlx1(ph7);
#pragma unroll
            for (int s = 0; s < 8; s++) ld_rlx4(PH[s], pp + s * 128);
          }
          UNIT_PRE(u);
          wgmma_rs_n48(ag, A[c][(k & 1) * 2], dg + UOFF(u), k != 0);
          wgmma_rs_n48(au, A[c][(k & 1) * 2], dg + UOFF(u) + 256, k != 0);
          wgmma_rs_n48(ag, A[c][(k & 1) * 2 + 1], dg + UOFF(u) + 128, 1);
          wgmma_rs_n48(au, A[c][(k & 1) * 2 + 1], dg + UOFF(u) + 256 + 128, 1);
          UNIT_POST(u);
        }
        wg_wait<0>();
#pragma unroll
        for (int s = 0; s < 3; s++) {
          uint32_t (&hh)[4] = HH[8 + s];
          hh[0] = tg(pack2(ag[8 * s + 0] * au[8 * s + 0], ag[8 * s + 1] * au[8 * s + 1]), T);
          hh[1] = pack2(ag[8 * s + 2] * au[8 * s + 2], ag[8 * s + 3] * au[8 * s + 3]);
          hh[2] = pack2(ag[8 * s + 4] * au[8 * s + 4], ag[8 * s + 5] * au[8 * s + 5]);
          hh[3] = pack2(ag[8 * s + 6] * au[8 * s + 6], ag[8 * s + 7] * au[8 * s + 7]);
          st_rlx4(hhp + (8 + s) * 128, hh[0], hh[1], hh[2], hh[3]);
        }
      }
    }

    {
      float ac[3][32], acc[32];
      uint32_t hr[4][4];
      const int m = jf >> 1, oc = (jf & 1) * 4 + m;
      const uint32_t* ph10 = reinterpret_cast<const uint32_t*>(&g_hh[rh3][jf ^ 1][10][wq][31]);
      uint32_t hv = 0;
      bar_arrive(8 + wg, 256);
      wg_fence();
#pragma unroll
      for (int k = 0; k < 3; k++) {
        mbar_wait(sb + SM_FULL + (ST_D + k) * 8);
        if (k == 1) hv = ld_rlx1(ph10);
#pragma unroll
        for (int s = 0; s < 11; s++) {
          if (k == 2 && s == 4) {
            int it = 0;
#pragma unroll 1
            while (((hv ^ T) & 1) && ++it < (1 << 18)) hv = ld_rlx1(ph10);
#pragma unroll
            for (int i = 8; i < 11; i++) ld_rlx4(PH[i], pp + i * 128);
          }
          wgmma_rs_n64(ac[k], HH[s], DESC(((ST_D + k) % NSLOT) * SLOT + s * 2048), s != 0);
        }
      }
      wg_commit();
      {
        int it = 0;
#pragma unroll 1
        while (__any_sync(0xffffffffu, bad4(PH[0][0], PH[1][0], PH[2][0], PH[3][0], T) | bad4(PH[4][0], PH[5][0], PH[6][0], PH[7][0], T) |
                                       bad4(PH[8][0], PH[9][0], PH[10][0], T, T))) {
#pragma unroll
          for (int s = 0; s < 11; s++) ld_rlx4(PH[s], pp + s * 128);
          if (++it > (1 << 18)) break;
        }
      }
      uint4* outb = &g_part[rh3][(jf & 1) * 4][m][wq][0][lane];
#pragma unroll
      for (int k = 0; k < 4; k++) {
        mbar_wait(sb + SM_FULL + (ST_D + 3 + k) * 8);
        wg_fence();
#pragma unroll
        for (int s = 0; s < 11; s++) {
          if (k < 3) wgmma_rs_n64(ac[k], PH[s], DESC(((ST_D + 3 + k) % NSLOT) * SLOT + s * 2048), 1);
          else wgmma_rs_n64(acc, HH[s], DESC(((ST_D + 6) % NSLOT) * SLOT + s * 2048), s != 0);
          if (s == 6 && k > 0) {
            wg_commit();
            wg_wait<1>();
            if (k == 1) bar_arrive(12, 320);
            const float (&a)[32] = ac[k - 1];
            uint4* p = outb + ((m + k) & 3) * 2048;
#pragma unroll
            for (int i = 0; i < 4; i++)
              st_rlx4(p + i * 32, tg(pack2(a[8 * i + 0], a[8 * i + 1]), T), pack2(a[8 * i + 2], a[8 * i + 3]),
                      pack2(a[8 * i + 4], a[8 * i + 5]), pack2(a[8 * i + 6], a[8 * i + 7]));
          }
        }
        wg_commit();
      }
      ld_chunk(hr, &g_h[rh3][oc][wq][0][lane]);
      uint32_t hx = ld_rlx1(&g_hx[rh3][oc][wq][lane]);
      mbar_wait(sb + SM_FULL + (ST_D + 7) * 8);
      wg_fence();
#pragma unroll
      for (int s = 0; s < 11; s++) wgmma_rs_n64(acc, PH[s], DESC(((ST_D + 7) % NSLOT) * SLOT + s * 2048), 1);
      wg_commit();
      wg_wait<0>();
#pragma unroll 1
      for (int q = 0; q < 3; q++) {
        uint32_t in[4][4];
        const uint4* sp = reinterpret_cast<const uint4*>(smem + ((ST_D % NSLOT) + wg) * SLOT) + q * 512 + wq * 128 + lane;
        mbar_wait_p(sb + SM_XF + (wg * 4 + q) * 8, 1);
        int it = 0;
#pragma unroll 1
        do {
#pragma unroll
          for (int s = 0; s < 4; s++)
            asm volatile("{\n.reg .b128 v;\nld.relaxed.gpu.b128 v, [%4];\nmov.b128 {%0,%1,%2,%3}, v;\n}"
                         : "=r"(in[s][0]), "=r"(in[s][1]), "=r"(in[s][2]), "=r"(in[s][3]) : "l"(sp + s * 32) : "memory");
          sp = &g_part[rh3][oc][(m - 1 - q) & 3][wq][0][lane];
        } while (__any_sync(0xffffffffu, bad4(in[0][0], in[1][0], in[2][0], in[3][0], T)) && ++it < (1 << 18));
        add_frag(acc, in, IDF);
      }
      {
        int it = 0;
#pragma unroll 1
        while (__any_sync(0xffffffffu, (hx ^ T) & 1) && ++it < (1 << 18)) hx = ld_rlx1(&g_hx[rh3][oc][wq][lane]);
      }
#pragma unroll
      for (int s = 0; s < 4; s++) hr[s][0] = (hr[s][0] & 0xFFFFFFFEu) | ((hx >> (s + 1)) & 1u);
#pragma unroll
      for (int i = 0; i < 32; i++) acc[i] *= (i & 2) ? r1 : r0;
      add_frag(acc, hr, IDF);
      bar_sync(9 - wg, 256);
      const uint32_t ob = sb + ((ST_D - 1) % NSLOT) * SLOT + wg * 8192;
#pragma unroll
      for (int s = 0; s < 4; s++)
        stsm4(ob + lrow + (((2 * s + lhi) ^ lx) << 4), pack2(acc[8 * s + 0], acc[8 * s + 1]), pack2(acc[8 * s + 2], acc[8 * s + 3]),
              pack2(acc[8 * s + 4], acc[8 * s + 5]), pack2(acc[8 * s + 6], acc[8 * s + 7]));
      __syncwarp();
      {
        const int row = wq * 16 + (lane >> 3);
        __nv_bfloat16* op = out + (size_t)(rh3 * 64 + row) * 512 + oc * 64 + lx * 8;
#pragma unroll
        for (int i = 0; i < 4; i++) {
          uint4 v;
          asm volatile("ld.shared.v4.b32 {%0,%1,%2,%3}, [%4];" : "=r"(v.x), "=r"(v.y), "=r"(v.z), "=r"(v.w)
                       : "r"(ob + (row + i * 4) * 128 + ((lx ^ (((lane >> 3) + i * 4) & 7)) << 4)) : "memory");
          asm volatile("st.global.v4.b32 [%0], {%1,%2,%3,%4};" ::"l"(op + i * 2048), "r"(v.x), "r"(v.y), "r"(v.z), "r"(v.w) : "memory");
        }
      }
    }
    asm volatile("barrier.cluster.arrive.relaxed.aligned;" ::: "memory");
    asm volatile("barrier.cluster.wait.aligned;" ::: "memory");
  } else {
    asm volatile("setmaxnreg.dec.sync.aligned.u32 24;");
    if (elect_one()) {
      if (warp == 8) {
#pragma unroll
        for (int k = 0; k < 9; k++) {
          const int s = k < 3 ? k : (k < 6 ? k + 3 : k - 3);
          const uint32_t bar = sb + SM_FULL + s * 8;
          mbar_init(bar, 1);
          mbar_expect_tx(bar, SLOT);
          if (s >= 3 && s < 6) tma2d(sb + s * SLOT, &maps.w, 512 + hg * 64, (s - 3) * 192, bar);
          else tma3d(sb + s * SLOT, &maps.x, 0, rb * 128 + (s >= 6 ? 64 : 0), 3 * (s % 3), bar);
        }
      } else if (warp == 9) {
        mbar_init(sb + SM_MISCB, 2);
        mbar_init(sb + SM_KVB, 1);
        mbar_expect_tx(sb + SM_KVB, 8704);
        mbar_expect_tx(sb + SM_MISCB, 2048);
        bulk_g2s(sb + SM_WPHI, wphi + hg * 1024, 2048, sb + SM_MISCB);
      } else if (warp == 10) {
        if ((sb & 0x3FFFF) != SM_BASE) __trap();
#pragma unroll 1
        for (int i = 0; i < 16; i++) {
          mbar_init(sb + SM_XF + i * 8, 1);
          mbar_expect_tx(sb + SM_XF + i * 8, (i == 8 || i == 12) ? 20480 : 16384);
          if (i < 12) mbar_init(sb + SM_XE + i * 8, 4);
        }
      } else {
        *reinterpret_cast<volatile unsigned*>(smem + SM_EPOCH) = atomicAdd(&g_start, 1u) / NCTA;
      }
      asm volatile("fence.mbarrier_init.release.cluster;" ::: "memory");
    }
    __syncwarp();
    if (warp != 11) bar_sync(0, 352);
    asm volatile("barrier.cluster.arrive.relaxed.aligned;" ::: "memory");
    if (warp == 8) {
      asm volatile("barrier.cluster.wait.aligned;" ::: "memory");
      if (elect_one()) {
        const CUtensorMap* mg = jf == 7 ? &maps.g7 : &maps.g;
        const CUtensorMap* mu = jf == 7 ? &maps.u7 : &maps.u;
        asm volatile("prefetch.tensormap [%0];" ::"l"(&maps.wo) : "memory");
        asm volatile("prefetch.tensormap [%0];" ::"l"(mg) : "memory");
        asm volatile("prefetch.tensormap [%0];" ::"l"(mu) : "memory");
        asm volatile("prefetch.tensormap [%0];" ::"l"(&maps.d) : "memory");
#pragma unroll 1
        for (int s = ST_WV; s < ST_XC; s++) {
          if (s == ST_SCR1) continue;
          mbar_wait(sb + SM_EMPTY + (s - 9) * 8);
          const uint32_t dst = sb + (s >= 18 ? s - 18 : s - 9) * SLOT, bar = sb + SM_FULL + s * 8;
          if (s < ST_WO) tma2d(dst, &maps.w, (s < ST_WQ ? 1024 : 0) + hg * 64, (s < ST_WQ ? s - ST_WV : s - ST_WQ) * 192, bar);
          else { mbar_wait(bar - 8); tma2d(dst, &maps.wo, hg * 64, (s - ST_WO) * 192, bar); }
        }
        const int jc = jf == 7 ? 0 : jf;
        int slot = (ST_GU + 1 - rank) % NSLOT;
#pragma unroll 1
        for (int s = ST_GU + 1 - rank; s < NSTAGE; s += 2) {
          mbar_wait(sb + SM_EMPTY + (s - 9) * 8);
          if (s > ST_GU && s < ST_GU + 6) mbar_wait(sb + SM_FULL + (s - 1) * 8);
          const uint32_t dst = sb + slot * SLOT, bar = sb + SM_FULL + s * 8;
          if (s < ST_D) {
#pragma unroll 1
            for (int i = 0; i < 3; i++) {
              const int u = (s - ST_GU) * 3 + i;
              tma3d_mc(dst + i * 8192, mg, (u >> 4) * 64, jc, (u & 15) * 32, bar);
              tma3d_mc(dst + i * 8192 + 4096, mu, (u >> 4) * 64, jc, (u & 15) * 32, bar);
            }
          } else {
            const int i = s - ST_D, k = i < 3 ? i : (i < 6 ? i - 3 : 3), pt = (i >= 3 && i != 6) ? 1 : 0;
            tma2d_mc(dst, &maps.d, ((jf & 1) * 4 + (((jf >> 1) + 1 + k) & 3)) * 64, (jf ^ pt) * 176, bar);
          }
          slot += 2; if (slot >= NSLOT) slot -= NSLOT;
        }
      }
      __syncwarp();
    } else {
      asm volatile("barrier.cluster.wait.aligned;" ::: "memory");
      if (warp == 11) {
#pragma unroll
        for (int i = 0; i < 4; i++)
          reinterpret_cast<uint4*>(smem + SM_ONES)[lane + 32 * i] = make_uint4(0x3F803F80u, 0x3F803F80u, 0x3F803F80u, 0x3F803F80u);
        fence_async_smem();
        __syncwarp();
        if (lane == 0) mbar_arrive(sb + SM_MISCB);
      }
      mbar_wait(sb + SM_MISCB);
      const unsigned epoch = *reinterpret_cast<volatile unsigned*>(smem + SM_EPOCH);
      const uint32_t T = (epoch & 1) ^ 1;
      if (warp == 11) {
        reinterpret_cast<float4*>(&g_kv[hg][rb * 136])[lane] = make_float4(0.f, 0.f, 0.f, 0.f);
        if (lane < 2) reinterpret_cast<float4*>(&g_kv[hg][rb * 136])[32 + lane] = make_float4(0.f, 0.f, 0.f, 0.f);
        __syncwarp();
        if (elect_one()) asm volatile("red.release.gpu.global.add.u32 [%0], 8;" ::"l"(&g_kvcnt[hg * 32 + 1]) : "memory");
        mbar_wait(sb + SM_FULL + (ST_WK + 2) * 8);
        if (elect_one()) {
          asm volatile("cp.async.bulk.prefetch.L2.global [%0], 4096;" ::"l"((const char*)wo + blockIdx.x * 4096) : "memory");
          asm volatile("cp.async.bulk.prefetch.L2.global [%0], 11008;" ::"l"((const char*)wg_ + blockIdx.x * 11008) : "memory");
          asm volatile("cp.async.bulk.prefetch.L2.global [%0], 11008;" ::"l"((const char*)wu_ + blockIdx.x * 11008) : "memory");
          asm volatile("cp.async.bulk.prefetch.L2.global [%0], 11008;" ::"l"((const char*)wd_ + blockIdx.x * 11008) : "memory");
          mbar_wait(sb + SM_EMPTY + ST_SCR0 * 8);
          const unsigned target = (epoch + 1) * 128;
          unsigned v; int it = 0;
#pragma unroll 1
          do {
            asm volatile("ld.acquire.gpu.global.u32 %0, [%1];" : "=r"(v) : "l"(&g_kvcnt[hg * 32]) : "memory");
            if (++it > (1 << 18)) break;
          } while ((int)(v - target) < 0);
          asm volatile("fence.proxy.async.global;" ::: "memory");
          bulk_g2s(sb + SM_KV32, &g_kv[hg][0], 8192, sb + SM_KVB);
          bulk_g2s(sb + SM_ONES, &g_kv[hg][2048], 512, sb + SM_KVB);
        }
        __syncwarp();
      } else {
        const int w = warp - 9;
        st_rlx4(reinterpret_cast<uint4*>(&g_st[2 * rb + w][hg][0]) + lane, T ^ 1, T ^ 1, T ^ 1, T ^ 1);
        if (lane < 8) st_rlx4(&g_o[2 * rb + w][hg][lane >> 1][3][30 + (lane & 1)], T ^ 1, T ^ 1, T ^ 1, T ^ 1);
        st_rlx4(&g_part[2 * rb3 + w][(jf & 1) * 4 + (lane >> 3)][jf >> 1][(lane >> 1) & 3][3][30 + (lane & 1)], T ^ 1, T ^ 1, T ^ 1, T ^ 1);
        if (lane < 16) st_rlx4(&g_hh[2 * rb3 + w][jf][7 + (lane >> 3) * 3][(lane >> 1) & 3][30 + (lane & 1)], T ^ 1, T ^ 1, T ^ 1, T ^ 1);
        if (w == 0) {
          mbar_wait(sb + SM_FULL + (ST_WQ + 2) * 8);
          unsigned v; int it = 0;
#pragma unroll 1
          do {
            asm volatile("ld.acquire.gpu.global.u32 %0, [%1];" : "=r"(v) : "l"(&g_kvcnt[hg * 32 + 1]) : "memory");
          } while ((int)(v - (epoch + 1) * 128) < 0 && ++it < (1 << 18));
          asm volatile("fence.proxy.async.global;" ::: "memory");
        }
        bar_sync(6, 320);
        if (w == 0 && elect_one()) {
          asm volatile("cp.reduce.async.bulk.global.shared::cta.bulk_group.add.f32 [%0], [%1], 8704;"
                       ::"l"(&g_kv[hg][0]), "r"(sb + 2 * SLOT) : "memory");
          asm volatile("cp.async.bulk.commit_group;" ::: "memory");
          asm volatile("cp.async.bulk.wait_group 0;" ::: "memory");
          asm volatile("red.release.gpu.global.add.u32 [%0], 8;" ::"l"(&g_kvcnt[hg * 32]) : "memory");
        }
        __syncwarp();
        mbar_wait(sb + SM_KVB);
        if (w == 0) { mbar_wait(sb + SM_EMPTY + 11 * 8); mbar_wait(sb + SM_EMPTY + 12 * 8); mbar_wait(sb + SM_EMPTY + 13 * 8); }
#pragma unroll 1
        for (int ph = 0; ph < 2; ph++) {
          const int use = 2 * ph + w, r = ph ? 2 * rb3 + w : 2 * rb + w;
          const uint32_t* pw = ph ? reinterpret_cast<const uint32_t*>(&g_st[r][lane >> 2][(lane & 3) * 16 + 15])
                                  : reinterpret_cast<const uint32_t*>(&g_o[r][lane >> 2][lane & 3][3][31]);
          const char* src = reinterpret_cast<const char*>(ph ? &g_h[r][0][0][0][0] : &g_o[r][0][0][0][0]);
          const uint32_t bf = sb + SM_XF + use * 32, be = sb + SM_XE + (use - 1) * 32;
          bar_sync(10 + w, 160);
          int it = 0;
#pragma unroll 1
          for (bool miss = true; __any_sync(0xffffffffu, miss) && ++it < (1 << 18);) { if (miss) miss = (ld_rlx1(pw) ^ T) & 1; }
          if (elect_one()) {
            if (use > 0) mbar_wait(be);
            if (ph) bulk_g2s(sb + SM_KV32 + w * 4096, &g_st[r][0][0], 4096, bf);
#pragma unroll
            for (int p = 0; p < 4; p++) {
              if (p > 0 && use > 0) mbar_wait(be + p * 8);
              bulk_g2s(sb + 2 * SLOT + p * 16384, src + p * 16384, 16384, bf + p * 8);
            }
          }
          __syncwarp();
        }
        {
          const int m = jf >> 1, oc = (jf & 1) * 4 + m;
          const uint32_t* pw = reinterpret_cast<const uint32_t*>(&g_part[2 * rb3 + w][oc][(m - 1 - (lane >> 2)) & 3][lane & 3][3][31]);
          bar_sync(12, 320);
          bool miss = lane < 12; int it = 0;
#pragma unroll 1
          for (int q = 0; q < 3; q++) {
#pragma unroll 1
            while ((__ballot_sync(0xffffffffu, miss) >> (4 * q) & 15) && ++it < (1 << 18)) { if (miss && (lane >> 2) <= q + 1) miss = (ld_rlx1(pw) ^ T) & 1; }
            if (elect_one()) {
              const uint32_t bar = sb + SM_XF + (w * 4 + q) * 8;
              mbar_expect_tx(bar, 8192);
              bulk_g2s(sb + ((ST_D % NSLOT) + w) * SLOT + q * 8192, &g_part[2 * rb3 + w][oc][(m - 1 - q) & 3][0][0][0], 8192, bar);
            }
            __syncwarp();
          }
        }
      }
    }
    asm volatile("barrier.cluster.arrive.relaxed.aligned;" ::: "memory");
    asm volatile("barrier.cluster.wait.aligned;" ::: "memory");
  }
}

typedef CUresult (*EncodeFn)(CUtensorMap*, CUtensorMapDataType, cuuint32_t, void*, const cuuint64_t*, const cuuint64_t*,
                             const cuuint32_t*, const cuuint32_t*, CUtensorMapInterleave, CUtensorMapSwizzle,
                             CUtensorMapL2promotion, CUtensorMapFloatOOBfill);

void encode(EncodeFn fn, CUtensorMap* m, const void* base, int rank, const cuuint64_t* dims, const cuuint64_t* strides,
            const cuuint32_t* box) {
  cuuint32_t es[3] = {1, 1, 1};
  fn(m, CU_TENSOR_MAP_DATA_TYPE_BFLOAT16, (cuuint32_t)rank, const_cast<void*>(base), dims, strides, box, es,
     CU_TENSOR_MAP_INTERLEAVE_NONE, CU_TENSOR_MAP_SWIZZLE_128B, CU_TENSOR_MAP_L2_PROMOTION_L2_256B,
     CU_TENSOR_MAP_FLOAT_OOB_FILL_NONE);
}

}

extern "C" void kernel_launch(void* const* d_in, const int* in_sizes, int n_in, void* d_out, int out_size) {
  (void)in_sizes; (void)n_in; (void)out_size;
  const __nv_bfloat16* x    = (const __nv_bfloat16*)d_in[0];
  const __nv_bfloat16* wqkv = (const __nv_bfloat16*)d_in[1];
  const __nv_bfloat16* wphi = (const __nv_bfloat16*)d_in[2];
  const __nv_bfloat16* wo   = (const __nv_bfloat16*)d_in[3];
  const __nv_bfloat16* wg   = (const __nv_bfloat16*)d_in[5];
  const __nv_bfloat16* wu   = (const __nv_bfloat16*)d_in[6];
  const __nv_bfloat16* wd   = (const __nv_bfloat16*)d_in[7];

  static EncodeFn fn = nullptr;
  if (!fn) {
    void* p = nullptr;
    cudaDriverEntryPointQueryResult qr;
    cudaGetDriverEntryPoint("cuTensorMapEncodeTiled", &p, cudaEnableDefault, &qr);
    fn = (EncodeFn)p;
    cudaFuncSetAttribute(fused_kernel, cudaFuncAttributeMaxDynamicSharedMemorySize, SM_TOTAL);
  }
  Maps maps;
  {
    cuuint64_t d[3] = {64, 2048, 8}, s[2] = {1024, 128}; cuuint32_t b[3] = {64, 64, 3};
    encode(fn, &maps.x, x, 3, d, s, b);
  }
  {
    cuuint64_t d[2] = {1536, 512}, s[1] = {3072}; cuuint32_t b[2] = {64, 192};
    encode(fn, &maps.w, wqkv, 2, d, s, b);
  }
  {
    cuuint64_t d[2] = {512, 512}, s[1] = {1024}; cuuint32_t b[2] = {64, 192};
    encode(fn, &maps.wo, wo, 2, d, s, b);
  }
  {
    cuuint64_t d[3] = {176, 7, 512}, d7[3] = {144, 1, 512}, s[2] = {352, 2752}; cuuint32_t b[3] = {64, 1, 32};
    encode(fn, &maps.g, wg, 3, d, s, b);
    encode(fn, &maps.u, wu, 3, d, s, b);
    encode(fn, &maps.g7, wg + 1232, 3, d7, s, b);
    encode(fn, &maps.u7, wu + 1232, 3, d7, s, b);
  }
  {
    cuuint64_t d[2] = {512, 1376}, s[1] = {1024}; cuuint32_t b[2] = {64, 176};
    encode(fn, &maps.d, wd, 2, d, s, b);
  }
  fused_kernel<<<NCTA, 384, SM_TOTAL>>>(maps, x, wphi, wo, wg, wu, wd, (__nv_bfloat16*)d_out);
}
```

```cpp
#include <cuda_runtime.h>
#include <cuda_bf16.h>
#include <cuda.h>
#include <stdint.h>

#define SAFE_WAIT 0

namespace {

constexpr int NCTA   = 128;
constexpr int SLOT   = 24576;
constexpr int NSLOT  = 9;
constexpr int NSTAGE = 47;

constexpr int ST_X0   = 0;
constexpr int ST_WK   = 3;
constexpr int ST_X1   = 6;
constexpr int ST_SCR0 = 9;
constexpr int ST_WV   = 10;
constexpr int ST_SCR1 = 13;
constexpr int ST_WQ   = 14;
constexpr int ST_WO   = 17;
constexpr int ST_XC   = 20;
constexpr int ST_GU   = 23;
constexpr int ST_D    = 39;

__host__ __device__ constexpr int st_empty_cnt(int d) {
  return ((d < 3 || (d >= 6 && d < 9) || (d >= ST_XC && d < ST_GU)) ? 4 : 2) * (d + 9 >= ST_GU ? 2 : 1);
}

constexpr uint32_t SM_BASE = 1024;
constexpr int SM_ONES = NSLOT * SLOT;
constexpr int SM_WPHI = SM_ONES + 2048;
constexpr int SM_KVS  = SM_WPHI + 2048;
constexpr int SM_KV32 = 4 * SLOT + 16384;
constexpr int SM_BAR  = SM_KVS + 6144;
constexpr int SM_FULL  = SM_BAR;
constexpr int SM_EMPTY = SM_BAR + NSTAGE * 8;
constexpr int SM_MISCB = SM_BAR + 2 * NSTAGE * 8;
constexpr int SM_KVB   = SM_MISCB + 8;
constexpr int SM_EPOCH = SM_KVB + 8;
constexpr int SM_XF    = SM_EPOCH + 8;
constexpr int SM_XE    = SM_XF + 16 * 8;
constexpr int SM_TOTAL = SM_BAR + 1024;

static_assert(SM_TOTAL == 232448 && SM_XE + 12 * 8 <= SM_TOTAL, "smem budget");

struct Maps { CUtensorMap x, w, wo, g, u, g7, u7, d; };

__device__ __align__(128) uint4    g_o[32][8][4][4][32];
__device__ __align__(128) uint4    g_h[32][8][4][4][32];
__device__ __align__(128) uint32_t g_hx[32][8][4][32];
__device__ __align__(128) uint2    g_st[32][8][64];
__device__ __align__(128) uint4    g_hh[32][8][11][4][32];
__device__ __align__(128) uint4    g_part[32][8][4][4][4][32];
__device__ __align__(128) float g_kv[8][2048 + 128];
__device__ __align__(128) unsigned g_kvcnt[8 * 32];
__device__ unsigned g_start;

__device__ __forceinline__ uint32_t smem_u32(const void* p) { return (uint32_t)__cvta_generic_to_shared(p); }
__device__ __forceinline__ void mbar_init(uint32_t bar, int cnt) {
  asm volatile("mbarrier.init.shared::cta.b64 [%0], %1;" ::"r"(bar), "r"(cnt) : "memory");
}
__device__ __forceinline__ void mbar_expect_tx(uint32_t bar, uint32_t bytes) {
  asm volatile("mbarrier.arrive.expect_tx.shared::cta.b64 _, [%0], %1;" ::"r"(bar), "r"(bytes) : "memory");
}
__device__ __forceinline__ void mbar_arrive(uint32_t bar) {
  asm volatile("mbarrier.arrive.shared::cta.b64 _, [%0];" ::"r"(bar) : "memory");
}
__device__ __forceinline__ void mbar_arrive_cluster(uint32_t bar, uint32_t rank) {
  asm volatile("{\n.reg .b32 ra;\nmapa.shared::cluster.u32 ra, %0, %1;\n"
               "mbarrier.arrive.shared::cluster.b64 _, [ra];\n}" ::"r"(bar), "r"(rank) : "memory");
}
__device__ __forceinline__ void mbar_wait_p(uint32_t bar, uint32_t parity) {
  asm volatile("{\n.reg .pred p;\nW: mbarrier.try_wait.parity.shared::cta.b64 p, [%0], %1;\n@!p bra W;\n}" ::"r"(bar), "r"(parity) : "memory");
}
__device__ __forceinline__ void mbar_wait(uint32_t bar) { mbar_wait_p(bar, 0); }
__device__ __forceinline__ bool elect_one() {
  uint32_t p;
  asm volatile("{\n.reg .pred P;\nelect.sync _|P, 0xffffffff;\nselp.u32 %0, 1, 0, P;\n}" : "=r"(p));
  return p != 0;
}
__device__ __forceinline__ void bar_sync(int id, int n)   { asm volatile("bar.sync %0, %1;" ::"r"(id), "r"(n) : "memory"); }
__device__ __forceinline__ void bar_arrive(int id, int n) { asm volatile("bar.arrive %0, %1;" ::"r"(id), "r"(n) : "memory"); }
__device__ __forceinline__ void fence_async_smem() { asm volatile("fence.proxy.async.shared::cta;" ::: "memory"); }
__device__ __forceinline__ void wg_fence()  { asm volatile("wgmma.fence.sync.aligned;" ::: "memory"); }
__device__ __forceinline__ void wg_commit() { asm volatile("wgmma.commit_group.sync.aligned;" ::: "memory"); }
template <int N> __device__ __forceinline__ void wg_wait() { asm volatile("wgmma.wait_group.sync.aligned %0;" ::"n"(N) : "memory"); }
#define DESC(off) (db + ((uint32_t)(off) >> 4))
__device__ __forceinline__ void tma2d(uint32_t dst, const CUtensorMap* m, int c0, int c1, uint32_t bar) {
  asm volatile("cp.async.bulk.tensor.2d.shared::cluster.global.mbarrier::complete_tx::bytes [%0], [%1, {%3, %4}], [%2];"
               ::"r"(dst), "l"(m), "r"(bar), "r"(c0), "r"(c1) : "memory");
}
__device__ __forceinline__ void tma2d_mc(uint32_t dst, const CUtensorMap* m, int c0, int c1, uint32_t bar) {
  asm volatile("cp.async.bulk.tensor.2d.shared::cluster.global.mbarrier::complete_tx::bytes.multicast::cluster [%0], [%1, {%3, %4}], [%2], %5;"
               ::"r"(dst), "l"(m), "r"(bar), "r"(c0), "r"(c1), "h"((uint16_t)3) : "memory");
}
__device__ __forceinline__ void tma3d(uint32_t dst, const CUtensorMap* m, int c0, int c1, int c2, uint32_t bar) {
  asm volatile("cp.async.bulk.tensor.3d.shared::cluster.global.mbarrier::complete_tx::bytes [%0], [%1, {%3, %4, %5}], [%2];"
               ::"r"(dst), "l"(m), "r"(bar), "r"(c0), "r"(c1), "r"(c2) : "memory");
}
__device__ __forceinline__ void tma3d_mc(uint32_t dst, const CUtensorMap* m, int c0, int c1, int c2, uint32_t bar) {
  asm volatile("cp.async.bulk.tensor.3d.shared::cluster.global.mbarrier::complete_tx::bytes.multicast::cluster [%0], [%1, {%3, %4, %5}], [%2], %6;"
               ::"r"(dst), "l"(m), "r"(bar), "r"(c0), "r"(c1), "r"(c2), "h"((uint16_t)3) : "memory");
}
__device__ __forceinline__ void ldsm4(uint32_t (&r)[4], uint32_t addr) {
  asm volatile("ldmatrix.sync.aligned.m8n8.x4.shared.b16 {%0,%1,%2,%3}, [%4];"
               : "=r"(r[0]), "=r"(r[1]), "=r"(r[2]), "=r"(r[3]) : "r"(addr) : "memory");
}
__device__ __forceinline__ void ldsm4t(uint32_t (&r)[4], uint32_t addr) {
  asm volatile("ldmatrix.sync.aligned.m8n8.x4.trans.shared.b16 {%0,%1,%2,%3}, [%4];"
               : "=r"(r[0]), "=r"(r[1]), "=r"(r[2]), "=r"(r[3]) : "r"(addr) : "memory");
}
__device__ __forceinline__ void stsm4(uint32_t addr, uint32_t r0, uint32_t r1, uint32_t r2, uint32_t r3) {
  asm volatile("stmatrix.sync.aligned.m8n8.x4.shared.b16 [%0], {%1,%2,%3,%4};"
               ::"r"(addr), "r"(r0), "r"(r1), "r"(r2), "r"(r3) : "memory");
}
__device__ __forceinline__ void mma16816(float (&c)[4], const uint32_t (&a)[4], uint32_t b0, uint32_t b1) {
  asm volatile("mma.sync.aligned.m16n8k16.row.col.f32.bf16.bf16.f32 {%0,%1,%2,%3},{%4,%5,%6,%7},{%8,%9},{%0,%1,%2,%3};"
               : "+f"(c[0]), "+f"(c[1]), "+f"(c[2]), "+f"(c[3])
               : "r"(a[0]), "r"(a[1]), "r"(a[2]), "r"(a[3]), "r"(b0), "r"(b1));
}
__device__ __forceinline__ void add_frag(float (&c)[32], const uint32_t (&a)[4][4], uint32_t id) {
#pragma unroll
  for (int i = 0; i < 8; i++)
    asm volatile("mma.sync.aligned.m16n8k8.row.col.f32.bf16.bf16.f32 {%0,%1,%2,%3},{%4,%5},{%6},{%0,%1,%2,%3};"
                 : "+f"(c[4 * i]), "+f"(c[4 * i + 1]), "+f"(c[4 * i + 2]), "+f"(c[4 * i + 3])
                 : "r"(a[i >> 1][(i & 1) * 2]), "r"(a[i >> 1][(i & 1) * 2 + 1]), "r"(id));
}
__device__ __forceinline__ uint32_t pack2(float lo, float hi) {
  uint32_t r; asm("cvt.rn.bf16x2.f32 %0, %1, %2;" : "=r"(r) : "f"(hi), "f"(lo)); return r;
}
__device__ __forceinline__ float blo(uint32_t w) { return __uint_as_float(w << 16); }
__device__ __forceinline__ float bhi(uint32_t w) { return __uint_as_float(w & 0xFFFF0000u); }
__device__ __forceinline__ uint32_t hsub2(uint32_t a, uint32_t b) { uint32_t r; asm("sub.rn.bf16x2 %0, %1, %2;" : "=r"(r) : "r"(a), "r"(b)); return r; }
__device__ __forceinline__ uint32_t hmax2(uint32_t a, uint32_t b) { uint32_t r; asm("max.bf16x2 %0, %1, %2;" : "=r"(r) : "r"(a), "r"(b)); return r; }
__device__ __forceinline__ uint32_t hmin2(uint32_t a, uint32_t b) { uint32_t r; asm("min.bf16x2 %0, %1, %2;" : "=r"(r) : "r"(a), "r"(b)); return r; }
__device__ __forceinline__ float ex2(float x) { float r; asm("ex2.approx.ftz.f32 %0, %1;" : "=f"(r) : "f"(x)); return r; }
__device__ __forceinline__ float rcp(float x) { float r; asm("rcp.approx.ftz.f32 %0, %1;" : "=f"(r) : "f"(x)); return r; }
__device__ __forceinline__ void ld_rlx4(uint32_t (&r)[4], const uint4* p) {
  asm volatile("{\n.reg .b128 v;\nld.relaxed.gpu.global.b128 v, [%4];\nmov.b128 {%0,%1,%2,%3}, v;\n}"
               : "=r"(r[0]), "=r"(r[1]), "=r"(r[2]), "=r"(r[3]) : "l"(p) : "memory");
}
__device__ __forceinline__ void st_rlx4(uint4* p, uint32_t a, uint32_t b, uint32_t c, uint32_t d) {
  asm volatile("st.relaxed.gpu.global.v4.b32 [%0], {%1,%2,%3,%4};" ::"l"(p), "r"(a), "r"(b), "r"(c), "r"(d) : "memory");
}
__device__ __forceinline__ void st_rlx2(uint2* p, uint32_t a, uint32_t b) {
  asm volatile("{\n.reg .b64 v;\nmov.b64 v, {%1,%2};\nst.relaxed.gpu.global.b64 [%0], v;\n}" ::"l"(p), "r"(a), "r"(b) : "memory");
}
__device__ __forceinline__ uint32_t ld_rlx1(const uint32_t* p) {
  uint32_t r; asm volatile("ld.relaxed.gpu.global.b32 %0, [%1];" : "=r"(r) : "l"(p) : "memory"); return r;
}
__device__ __forceinline__ void st_rlx1(uint32_t* p, uint32_t a) {
  asm volatile("st.relaxed.gpu.global.b32 [%0], %1;" ::"l"(p), "r"(a) : "memory");
}
__device__ __forceinline__ void ld_rlx2(uint32_t& a, uint32_t& b, const uint2* p) {
  asm volatile("{\n.reg .b64 v;\nld.relaxed.gpu.b64 v, [%2];\nmov.b64 {%0,%1}, v;\n}" : "=r"(a), "=r"(b) : "l"(p) : "memory");
}
__device__ __forceinline__ void bulk_g2s(uint32_t dst, const void* src, uint32_t bytes, uint32_t bar) {
  asm volatile("cp.async.bulk.shared::cluster.global.mbarrier::complete_tx::bytes [%0], [%1], %2, [%3];"
               ::"r"(dst), "l"(src), "r"(bytes), "r"(bar) : "memory");
}
__device__ __forceinline__ uint32_t tg(uint32_t w, uint32_t T) { return (w & 0xFFFFFFFEu) | T; }
__device__ __forceinline__ uint32_t bad4(uint32_t a, uint32_t b, uint32_t c, uint32_t d, uint32_t T) {
  uint32_t u, v;
  asm("lop3.b32 %0, %1, %2, %3, 0x7E;" : "=r"(u) : "r"(a), "r"(b), "r"(T));
  asm("lop3.b32 %0, %1, %2, %3, 0x7E;" : "=r"(v) : "r"(c), "r"(d), "r"(T));
  asm("lop3.b32 %0, %1, %2, 1, 0xA8;" : "=r"(u) : "r"(u), "r"(v));
  return u;
}

__device__ __forceinline__ void ld_chunk(uint32_t (&a)[4][4], const uint4* p) {
#pragma unroll
  for (int s = 0; s < 4; s++) ld_rlx4(a[s], p + s * 32);
}
__device__ __forceinline__ void get_pair(uint32_t (&a)[4][4], uint32_t (&b)[4][4], const uint4* sp, const uint4* gp, uint32_t T) {
  int it = 0;
#pragma unroll 1
  do {
#pragma unroll
    for (int s = 0; s < 8; s++) {
      uint32_t (&r)[4] = s < 4 ? a[s & 3] : b[s & 3];
      asm volatile("{\n.reg .b128 v;\nld.relaxed.gpu.b128 v, [%4];\nmov.b128 {%0,%1,%2,%3}, v;\n}"
                   : "=r"(r[0]), "=r"(r[1]), "=r"(r[2]), "=r"(r[3]) : "l"(sp + (s >> 2) * 512 + (s & 3) * 32) : "memory");
    }
    sp = gp;
  } while (__any_sync(0xffffffffu, bad4(a[0][0], a[1][0], a[2][0], a[3][0], T) | bad4(b[0][0], b[1][0], b[2][0], b[3][0], T)) && ++it < (1 << 18));
}

__device__ __forceinline__ void wgmma_rs_n48(float (&d)[24], const uint32_t (&a)[4], uint32_t descB, int scaleD) {
  asm volatile("{\n.reg .pred p;\n.reg .b64 db;\nsetp.ne.b32 p, %29, 0;\nmov.b64 db, {%28, 0x40000040};\n"
    "wgmma.mma_async.sync.aligned.m64n48k16.f32.bf16.bf16 {%0,%1,%2,%3,%4,%5,%6,%7,%8,%9,%10,%11,%12,%13,%14,%15,%16,%17,%18,%19,%20,%21,%22,%23}, {%24,%25,%26,%27}, db, p, 1, 1, 1;\n}\n"
    : "+f"(d[0]),"+f"(d[1]),"+f"(d[2]),"+f"(d[3]),"+f"(d[4]),"+f"(d[5]),"+f"(d[6]),"+f"(d[7]),"+f"(d[8]),"+f"(d[9]),"+f"(d[10]),"+f"(d[11]),"+f"(d[12]),"+f"(d[13]),"+f"(d[14]),"+f"(d[15]),"+f"(d[16]),"+f"(d[17]),"+f"(d[18]),"+f"(d[19]),"+f"(d[20]),"+f"(d[21]),"+f"(d[22]),"+f"(d[23])
    : "r"(a[0]), "r"(a[1]), "r"(a[2]), "r"(a[3]), "r"(descB), "r"(scaleD));
}
__device__ __forceinline__ void wgmma_rs_n64(float (&d)[32], const uint32_t (&a)[4], uint32_t descB, int scaleD) {
  asm volatile("{\n.reg .pred p;\n.reg .b64 db;\nsetp.ne.b32 p, %37, 0;\nmov.b64 db, {%36, 0x40000040};\n"
    "wgmma.mma_async.sync.aligned.m64n64k16.f32.bf16.bf16 {%0,%1,%2,%3,%4,%5,%6,%7,%8,%9,%10,%11,%12,%13,%14,%15,%16,%17,%18,%19,%20,%21,%22,%23,%24,%25,%26,%27,%28,%29,%30,%31}, {%32,%33,%34,%35}, db, p, 1, 1, 1;\n}\n"
    : "+f"(d[0]),"+f"(d[1]),"+f"(d[2]),"+f"(d[3]),"+f"(d[4]),"+f"(d[5]),"+f"(d[6]),"+f"(d[7]),"+f"(d[8]),"+f"(d[9]),"+f"(d[10]),"+f"(d[11]),"+f"(d[12]),"+f"(d[13]),"+f"(d[14]),"+f"(d[15]),"+f"(d[16]),"+f"(d[17]),"+f"(d[18]),"+f"(d[19]),"+f"(d[20]),"+f"(d[21]),"+f"(d[22]),"+f"(d[23]),"+f"(d[24]),"+f"(d[25]),"+f"(d[26]),"+f"(d[27]),"+f"(d[28]),"+f"(d[29]),"+f"(d[30]),"+f"(d[31])
    : "r"(a[0]), "r"(a[1]), "r"(a[2]), "r"(a[3]), "r"(descB), "r"(scaleD));
}
__device__ __forceinline__ void wgmma_rs_n128(float (&d)[64], const uint32_t (&a)[4], uint32_t descB, int scaleD) {
  asm volatile("{\n.reg .pred p;\n.reg .b64 db;\nsetp.ne.b32 p, %69, 0;\nmov.b64 db, {%68, 0x40000040};\n"
    "wgmma.mma_async.sync.aligned.m64n128k16.f32.bf16.bf16 {%0,%1,%2,%3,%4,%5,%6,%7,%8,%9,%10,%11,%12,%13,%14,%15,%16,%17,%18,%19,%20,%21,%22,%23,%24,%25,%26,%27,%28,%29,%30,%31,%32,%33,%34,%35,%36,%37,%38,%39,%40,%41,%42,%43,%44,%45,%46,%47,%48,%49,%50,%51,%52,%53,%54,%55,%56,%57,%58,%59,%60,%61,%62,%63}, {%64,%65,%66,%67}, db, p, 1, 1, 1;\n}\n"
    : "+f"(d[0]),"+f"(d[1]),"+f"(d[2]),"+f"(d[3]),"+f"(d[4]),"+f"(d[5]),"+f"(d[6]),"+f"(d[7]),"+f"(d[8]),"+f"(d[9]),"+f"(d[10]),"+f"(d[11]),"+f"(d[12]),"+f"(d[13]),"+f"(d[14]),"+f"(d[15]),"+f"(d[16]),"+f"(d[17]),"+f"(d[18]),"+f"(d[19]),"+f"(d[20]),"+f"(d[21]),"+f"(d[22]),"+f"(d[23]),"+f"(d[24]),"+f"(d[25]),"+f"(d[26]),"+f"(d[27]),"+f"(d[28]),"+f"(d[29]),"+f"(d[30]),"+f"(d[31]),"+f"(d[32]),"+f"(d[33]),"+f"(d[34]),"+f"(d[35]),"+f"(d[36]),"+f"(d[37]),"+f"(d[38]),"+f"(d[39]),"+f"(d[40]),"+f"(d[41]),"+f"(d[42]),"+f"(d[43]),"+f"(d[44]),"+f"(d[45]),"+f"(d[46]),"+f"(d[47]),"+f"(d[48]),"+f"(d[49]),"+f"(d[50]),"+f"(d[51]),"+f"(d[52]),"+f"(d[53]),"+f"(d[54]),"+f"(d[55]),"+f"(d[56]),"+f"(d[57]),"+f"(d[58]),"+f"(d[59]),"+f"(d[60]),"+f"(d[61]),"+f"(d[62]),"+f"(d[63])
    : "r"(a[0]), "r"(a[1]), "r"(a[2]), "r"(a[3]), "r"(descB), "r"(scaleD));
}
__device__ __forceinline__ void wgmma_ss_n72_t11(float (&d)[36], uint32_t descA, uint32_t descB, int scaleD) {
  asm volatile("{\n.reg .pred p;\n.reg .b64 da, db;\nsetp.ne.b32 p, %38, 0;\nmov.b64 da, {%36, 0x40000040};\nmov.b64 db, {%37, 0x40000040};\n"
    "wgmma.mma_async.sync.aligned.m64n72k16.f32.bf16.bf16 {%0,%1,%2,%3,%4,%5,%6,%7,%8,%9,%10,%11,%12,%13,%14,%15,%16,%17,%18,%19,%20,%21,%22,%23,%24,%25,%26,%27,%28,%29,%30,%31,%32,%33,%34,%35}, da, db, p, 1, 1, 1, 1;\n}\n"
    : "+f"(d[0]),"+f"(d[1]),"+f"(d[2]),"+f"(d[3]),"+f"(d[4]),"+f"(d[5]),"+f"(d[6]),"+f"(d[7]),"+f"(d[8]),"+f"(d[9]),"+f"(d[10]),"+f"(d[11]),"+f"(d[12]),"+f"(d[13]),"+f"(d[14]),"+f"(d[15]),"+f"(d[16]),"+f"(d[17]),"+f"(d[18]),"+f"(d[19]),"+f"(d[20]),"+f"(d[21]),"+f"(d[22]),"+f"(d[23]),"+f"(d[24]),"+f"(d[25]),"+f"(d[26]),"+f"(d[27]),"+f"(d[28]),"+f"(d[29]),"+f"(d[30]),"+f"(d[31]),"+f"(d[32]),"+f"(d[33]),"+f"(d[34]),"+f"(d[35])
    : "r"(descA), "r"(descB), "r"(scaleD));
}

constexpr float LOG2E = 1.4426950408889634f;

__device__ __forceinline__ void feat_exp(const uint32_t (&P)[4], float (&e)[16]) {
  uint32_t a = hmax2(P[0], P[2]), b = hmax2(P[1], P[3]);
  uint32_t mx = hmax2(__byte_perm(a, b, 0x5410), __byte_perm(a, b, 0x7632));
  a = hmin2(P[0], P[2]); b = hmin2(P[1], P[3]);
  uint32_t mn = hmin2(__byte_perm(a, b, 0x5410), __byte_perm(a, b, 0x7632));
  mx = hmax2(mx, __shfl_xor_sync(0xffffffffu, mx, 1));
  mn = hmin2(mn, __shfl_xor_sync(0xffffffffu, mn, 1));
  mx = hmax2(mx, __shfl_xor_sync(0xffffffffu, mx, 2));
  mn = hmin2(mn, __shfl_xor_sync(0xffffffffu, mn, 2));
  float mx0 = -blo(mx) * LOG2E, mx1 = -bhi(mx) * LOG2E, mn0 = blo(mn) * LOG2E, mn1 = bhi(mn) * LOG2E;
  float v[8] = {blo(P[0]), bhi(P[0]), blo(P[1]), bhi(P[1]), blo(P[2]), bhi(P[2]), blo(P[3]), bhi(P[3])};
#pragma unroll
  for (int i = 0; i < 8; i++) {
    bool r1 = (i >> 1) & 1;
    e[i]     = ex2(fmaf(v[i],  LOG2E, r1 ? mx1 : mx0));
    e[8 + i] = ex2(fmaf(v[i], -LOG2E, r1 ? mn1 : mn0));
  }
}

__global__ void __cluster_dims__(2, 1, 1) __launch_bounds__(384, 1)
fused_kernel(const __grid_constant__ Maps maps, const __nv_bfloat16* __restrict__ x, const __nv_bfloat16* __restrict__ wphi,
             const __nv_bfloat16* __restrict__ wo, const __nv_bfloat16* __restrict__ wg_, const __nv_bfloat16* __restrict__ wu_,
             const __nv_bfloat16* __restrict__ wd_, __nv_bfloat16* __restrict__ out) {
  extern __shared__ __align__(1024) unsigned char smem[];
  const uint32_t sb = smem_u32(smem);
  const int tid = threadIdx.x, lane = tid & 31;
  const int warp = __shfl_sync(0xffffffffu, tid >> 5, 0);
  const uint32_t rank = blockIdx.x & 1;
  const int cl = blockIdx.x >> 1;
  int quad, qi;
  if (cl < 4) { quad = 15; qi = cl; }
  else if (cl < 36) { quad = (cl - 4) & 7; qi = (cl - 4) >> 3; }
  else { qi = (cl - 36) / 7; quad = 8 + (cl - 36) - 7 * qi; }
  const int rb = quad, hg = 2 * qi + rank;
  const int rb3 = (quad & ~1) + rank, jf = 4 * (quad & 1) + qi;

  if (warp < 8) {
    asm volatile("setmaxnreg.inc.sync.aligned.u32 240;");
    if (elect_one()) {
#pragma unroll 1
      for (int d = warp; d + 9 < NSTAGE; d += 8) {
        mbar_init(sb + SM_EMPTY + d * 8, st_empty_cnt(d));
        mbar_init(sb + SM_FULL + (d + 9) * 8, 1);
        mbar_expect_tx(sb + SM_FULL + (d + 9) * 8, d + 9 >= ST_D ? 22528 : SLOT);
      }
      asm volatile("fence.mbarrier_init.release.cluster;" ::: "memory");
    }
    __syncwarp();
    bar_sync(0, 352);
    asm volatile("barrier.cluster.arrive.relaxed.aligned;" ::: "memory");
    const int wg = warp >> 2, wq = warp & 3, g = lane >> 2, t = lane & 3;
    const bool lead = (tid & 127) == 0;
    constexpr uint32_t db = (SM_BASE >> 4) | (512u << 16);
    auto release = [&](int d) {
      const int s = d + NSLOT;
      mbar_arrive_cluster(sb + SM_EMPTY + d * 8, s >= ST_GU ? (uint32_t)(s & 1) : rank);
    };
    const uint32_t lrow = (uint32_t)(wq * 16 + (lane & 7) + ((lane >> 3) & 1) * 8) * 128;
    const uint32_t lx = lane & 7, lhi = lane >> 4;
    if (wg == 1) bar_arrive(4, 256);

    float r0, r1;
    uint32_t E[4][8];
    uint32_t T = 0;
    {
      uint32_t A[32][4];
      const int sx = wg ? ST_X1 : ST_X0;
      {
        const uint32_t base = sb + sx * SLOT + lrow, baseb = sb + sx * SLOT + (wq * 16 + lx + lhi * 8) * 128;
        float cs[2][4], c0[2][4], c1[2][4];
#pragma unroll
        for (int i = 0; i < 4; i++) { cs[0][i] = cs[1][i] = c0[0][i] = c0[1][i] = c1[0][i] = c1[1][i] = 0.f; }
        uint32_t bt[2][4][4];
        if (wg == 1) bar_sync(13, 256);
#pragma unroll
        for (int c = -1; c < 8; c++) {
          if (c < 7) {
            const int n = c + 1;
            if (n % 3 == 0) mbar_wait(sb + SM_FULL + (sx + n / 3) * 8);
#pragma unroll
            for (int k = 0; k < 4; k++) {
              ldsm4(A[4 * n + k], base + n * 8192 + (((2 * k + lhi) ^ lx) << 4));
              ldsm4(bt[n & 1][k], baseb + n * 8192 + (((2 * k + ((lane >> 3) & 1)) ^ lx) << 4));
            }
          }
          if (c >= 0) {
#pragma unroll
            for (int k = 0; k < 4; k++) {
              const uint32_t (&f)[4] = A[4 * c + k];
              mma16816(cs[k & 1], f, 0x3F803F80u, 0x3F803F80u);
              mma16816(c0[k & 1], f, bt[c & 1][k][0], bt[c & 1][k][1]);
              mma16816(c1[k & 1], f, bt[c & 1][k][2], bt[c & 1][k][3]);
            }
          }
        }
        if (wg == 0) bar_arrive(13, 256);
        const float s0 = (cs[0][0] + cs[1][0]) * (1.f / 512.f), s1 = (cs[0][2] + cs[1][2]) * (1.f / 512.f);
        asm volatile("barrier.cluster.wait.aligned;" ::: "memory");
        if (lane < 3) release(sx + lane);
        const uint32_t m0 = pack2(s0, s0), m1 = pack2(s1, s1);
        float q0 = (g & 1) ? c0[0][1] + c0[1][1] : c0[0][0] + c0[1][0];
        float q1 = (g & 1) ? c1[0][3] + c1[1][3] : c1[0][2] + c1[1][2];
        q0 = __shfl_sync(0xffffffffu, q0, (lane & ~3) | (g >> 1));
        q1 = __shfl_sync(0xffffffffu, q1, (lane & ~3) | (g >> 1));
        r0 = rsqrtf(fmaxf(q0 * (1.f / 512.f) - s0 * s0, 0.f) + 1e-5f);
        r1 = rsqrtf(fmaxf(q1 * (1.f / 512.f) - s1 * s1, 0.f) + 1e-5f);
#pragma unroll
        for (int ks = 0; ks < 32; ks++) {
          A[ks][0] = hsub2(A[ks][0], m0); A[ks][1] = hsub2(A[ks][1], m1);
          A[ks][2] = hsub2(A[ks][2], m0); A[ks][3] = hsub2(A[ks][3], m1);
        }
      }
      const uint32_t wpa = sb + SM_WPHI + ((lane & 7) + ((lane >> 3) & 1) * 8) * 32 + lhi * 16;
      const uint32_t scr = sb + (wg ? (ST_SCR1 % NSLOT) : (ST_SCR0 % NSLOT)) * SLOT;
#pragma unroll 1
      for (int ps = 0; ps < 3; ps++) {
        const int st0 = ps == 0 ? ST_WK : (ps == 1 ? ST_WV : ST_WQ);
        const uint32_t wdesc = DESC((ps == 0 ? ST_WK % NSLOT : (ps == 1 ? ST_WV % NSLOT : ST_WQ % NSLOT)) * SLOT);
        float acc[32];
        bar_sync(4 + wg, 256);
#pragma unroll
        for (int i = 0; i < 3; i++) {
          mbar_wait(sb + SM_FULL + (st0 + i) * 8);
          wg_fence();
#pragma unroll
          for (int kk = 0; kk < (i < 2 ? 12 : 8); kk++)
            wgmma_rs_n64(acc, A[12 * i + kk], wdesc + ((i * SLOT + kk * 2048) >> 4), (i | kk) != 0);
          wg_commit();
          if (i == 1) { wg_wait<1>(); if (lead) release(st0); }
        }
        if (ps == 1 && wg == 0) bar_arrive(5, 256);
        uint32_t a[4][4], b[4][4];
        mbar_wait(sb + SM_MISCB);
        T = (*reinterpret_cast<volatile unsigned*>(smem + SM_EPOCH) & 1) ^ 1;
#pragma unroll
        for (int h = 0; h < 4; h++) ldsm4t(b[h], wpa + h * 512);
        wg_wait<0>();
        if ((tid & 127) < 2) release(st0 + 1 + (tid & 1));
#pragma unroll
        for (int h = 0; h < 4; h++) {
          a[h][0] = pack2(acc[8 * h + 0] * r0, acc[8 * h + 1] * r0); a[h][1] = pack2(acc[8 * h + 2] * r1, acc[8 * h + 3] * r1);
          a[h][2] = pack2(acc[8 * h + 4] * r0, acc[8 * h + 5] * r0); a[h][3] = pack2(acc[8 * h + 6] * r1, acc[8 * h + 7] * r1);
        }
        if (ps != 1) {
          {
            float pp[4][2][4];
#pragma unroll
            for (int h = 0; h < 4; h++) {
#pragma unroll
              for (int i = 0; i < 4; i++) { pp[h][0][i] = 0.f; pp[h][1][i] = 0.f; }
              mma16816(pp[h][0], a[h], b[h][0], b[h][1]);
              mma16816(pp[h][1], a[h], b[h][2], b[h][3]);
            }
#pragma unroll
            for (int h = 0; h < 4; h++) {
              a[h][0] = pack2(pp[h][0][0], pp[h][0][1]); a[h][1] = pack2(pp[h][0][2], pp[h][0][3]);
              a[h][2] = pack2(pp[h][1][0], pp[h][1][1]); a[h][3] = pack2(pp[h][1][2], pp[h][1][3]);
            }
          }
          if (ps == 0 || wg == 0) bar_arrive(4 + (wg ^ 1), 256);
          if (ps == 0) mbar_wait(sb + SM_EMPTY + (wg ? ST_SCR1 - NSLOT : ST_SCR0 - NSLOT) * 8);
#pragma unroll 1
          for (int hp = 0; hp < 2; hp++) {
            float e[2][16];
            feat_exp(a[0], e[0]);
            feat_exp(a[1], e[1]);
            if (ps == 0) {
#pragma unroll
              for (int h = 0; h < 2; h++) {
                const float (&f)[16] = e[h];
                float sp0 = (f[0] + f[1]) + (f[4] + f[5]), sp1 = (f[2] + f[3]) + (f[6] + f[7]);
                float sn0 = (f[8] + f[9]) + (f[12] + f[13]), sn1 = (f[10] + f[11]) + (f[14] + f[15]);
                sp0 += __shfl_xor_sync(0xffffffffu, sp0, 1); sp1 += __shfl_xor_sync(0xffffffffu, sp1, 1);
                sn0 += __shfl_xor_sync(0xffffffffu, sn0, 1); sn1 += __shfl_xor_sync(0xffffffffu, sn1, 1);
                sp0 += __shfl_xor_sync(0xffffffffu, sp0, 2); sp1 += __shfl_xor_sync(0xffffffffu, sp1, 2);
                sn0 += __shfl_xor_sync(0xffffffffu, sn0, 2); sn1 += __shfl_xor_sync(0xffffffffu, sn1, 2);
                sp0 = rcp(sp0); sp1 = rcp(sp1); sn0 = rcp(sn0); sn1 = rcp(sn1);
                const uint32_t dst = scr + hp * 8192 + lrow;
                stsm4(dst + (((h * 4 + lhi) ^ lx) << 4), pack2(f[0] * sp0, f[1] * sp0), pack2(f[2] * sp1, f[3] * sp1),
                      pack2(f[4] * sp0, f[5] * sp0), pack2(f[6] * sp1, f[7] * sp1));
                stsm4(dst + (((h * 4 + 2 + lhi) ^ lx) << 4), pack2(f[8] * sn0, f[9] * sn0), pack2(f[10] * sn1, f[11] * sn1),
                      pack2(f[12] * sn0, f[13] * sn0), pack2(f[14] * sn1, f[15] * sn1));
              }
            } else {
#pragma unroll
              for (int i = 0; i < 16; i++) {
                A[i >> 2][i & 3] = A[4 + (i >> 2)][i & 3];
                A[4 + (i >> 2)][i & 3] = pack2(e[i >> 3][2 * (i & 7)], e[i >> 3][2 * (i & 7) + 1]);
              }
            }
#pragma unroll
            for (int i = 0; i < 4; i++) { a[0][i] = a[2][i]; a[1][i] = a[3][i]; }
          }
        } else {
#pragma unroll
          for (int h = 0; h < 4; h++) stsm4(scr + 16384 + lrow + (((2 * h + lhi) ^ lx) << 4), a[h][0], a[h][1], a[h][2], a[h][3]);
          fence_async_smem();
          bar_sync(3, 256);
          float kv[36];
          wg_fence();
#pragma unroll
          for (int ks = 0; ks < 8; ks++) {
            const uint32_t sk = (ks < 4 ? (ST_SCR0 % NSLOT) : (ST_SCR1 % NSLOT)) * SLOT + (ks & 3) * 2048;
            const uint32_t dv = (DESC(sk + 16384) & 0xFFFFu) | (((SM_ONES - sk - 16384) >> 4) << 16);
            wgmma_ss_n72_t11(kv, DESC(sk) + wg * 512, dv, ks != 0);
          }
          wg_commit();
          if (wg == 1) bar_arrive(4, 256);
          wg_wait<0>();
          if (lead) { mbar_arrive(sb + SM_EMPTY + ST_SCR0 * 8); mbar_arrive(sb + SM_EMPTY + ST_SCR1 * 8); }
          const int hl = 2 * wg + (wq >> 1), f = (wq & 1) * 16 + g;
          float* kvp = reinterpret_cast<float*>(smem + 2 * SLOT) + (hl * 32 + f) * 16 + 2 * t;
          float c[8];
#pragma unroll
          for (int i = 0; i < 8; i++) c[i] = hl >= 2 ? (hl == 3 ? kv[24 + i] : kv[16 + i]) : (hl == 1 ? kv[8 + i] : kv[i]);
#pragma unroll
          for (int n = 0; n < 2; n++) {
            *reinterpret_cast<float2*>(kvp + n * 8) = make_float2(c[4 * n], c[4 * n + 1]);
            *reinterpret_cast<float2*>(kvp + n * 8 + 128) = make_float2(c[4 * n + 2], c[4 * n + 3]);
          }
          if (t < 2) reinterpret_cast<float*>(smem + 2 * SLOT)[2048 + hl * 32 + f + t * 8] = t ? kv[34] : kv[32];
          fence_async_smem();
          bar_sync(6, 320);
        }
      }
#pragma unroll
      for (int i = 0; i < 32; i++) E[i >> 3][i & 7] = A[i >> 2][i & 3];
    }
    const int rh = 2 * rb + wg;
#define IDF ((g >> 1) == t ? ((g & 1) ? 0x3F800000u : 0x00003F80u) : 0u)
    const uint4* xb = reinterpret_cast<const uint4*>(smem + 2 * SLOT) + wq * 128 + lane;
    if (wg == 0) {
      mbar_wait(sb + SM_KVB);
      const int r = tid;
      const float4* src = reinterpret_cast<const float4*>(smem + SM_KV32) + r;
#pragma unroll
      for (int i = 0; i < 4; i++) {
        const float4 a = src[i * 128];
        *reinterpret_cast<uint2*>(smem + SM_KVS + (i * 32 + (r >> 2)) * 48 + (r & 3) * 8) = make_uint2(pack2(a.x, a.y), pack2(a.z, a.w));
      }
      const uint32_t zz = pack2(reinterpret_cast<const float*>(smem + SM_ONES)[r], 1.0f);
      *reinterpret_cast<uint4*>(smem + SM_KVS + r * 48 + 32) = make_uint4(zz, zz, zz, zz);
      bar_sync(1, 128);
    }
    {
      uint4* op = &g_o[rh][hg][wq][0][lane];
      if (wg == 1) bar_sync(7, 256);
#pragma unroll 1
      for (int hp = 0; hp < 2; hp++) {
#pragma unroll
      for (int h = 0; h < 2; h++) {
        uint32_t b0[4], b1[4], b2[4];
        const uint32_t kb = sb + SM_KVS + ((2 * hp + h) * 32 + lane) * 48;
        ldsm4t(b0, kb); ldsm4t(b1, kb + 16); ldsm4t(b2, kb + 32);
        const uint32_t ep[4] = {E[h][0], E[h][1], E[h][2], E[h][3]}, en[4] = {E[h][4], E[h][5], E[h][6], E[h][7]};
        float np0[4] = {0, 0, 0, 0}, np1[4] = {0, 0, 0, 0}, nn0[4] = {0, 0, 0, 0}, nn1[4] = {0, 0, 0, 0}, dp[4] = {0, 0, 0, 0}, dn[4] = {0, 0, 0, 0};
        mma16816(dp, ep, b2[0], b2[1]);  mma16816(dn, en, b2[2], b2[3]);
        mma16816(np0, ep, b0[0], b0[1]); mma16816(nn0, en, b0[2], b0[3]);
        mma16816(np1, ep, b1[0], b1[1]); mma16816(nn1, en, b1[2], b1[3]);
        const float i0 = rcp(fmaf(dp[0], dn[1], fmaf(dn[0], dp[1], 1e-6f * dp[1] * dn[1])));
        const float i1 = rcp(fmaf(dp[2], dn[3], fmaf(dn[2], dp[3], 1e-6f * dp[3] * dn[3])));
        const float cp0 = dn[1] * i0, cn0 = dp[1] * i0, cp1 = dn[3] * i1, cn1 = dp[3] * i1;
        st_rlx4(op + (2 * hp + h) * 32,
                tg(pack2(fmaf(np0[0], cp0, nn0[0] * cn0), fmaf(np0[1], cp0, nn0[1] * cn0)), T),
                pack2(fmaf(np0[2], cp1, nn0[2] * cn1), fmaf(np0[3], cp1, nn0[3] * cn1)),
                pack2(fmaf(np1[0], cp0, nn1[0] * cn0), fmaf(np1[1], cp0, nn1[1] * cn0)),
                pack2(fmaf(np1[2], cp1, nn1[2] * cn1), fmaf(np1[3], cp1, nn1[3] * cn1)));
      }
#pragma unroll
        for (int i = 0; i < 8; i++) { E[0][i] = E[2][i]; E[1][i] = E[3][i]; }
      }
    }
    if (wg == 0) bar_arrive(7, 256);
    bar_arrive(10 + wg, 160);

    {
      uint32_t xr[4][4];
      {
        const uint32_t* xp = reinterpret_cast<const uint32_t*>(x + (size_t)(rh * 64 + wq * 16 + g) * 512 + hg * 64 + 2 * t);
#pragma unroll
        for (int i = 0; i < 8; i++) { xr[i >> 1][(i & 1) * 2] = __ldg(xp + 4 * i); xr[i >> 1][(i & 1) * 2 + 1] = __ldg(xp + 8 * 256 + 4 * i); }
      }
      uint32_t A[8][4][4];
      const uint4* op = &g_o[rh][0][wq][0][lane];
      float acc[32];
#pragma unroll
      for (int i = 0; i < 32; i++) acc[i] = 0.f;
      add_frag(acc, xr, IDF);
#pragma unroll
      for (int p = -1; p < 4; p++) {
        if (p < 3) {
          mbar_wait(sb + SM_XF + (wg * 4 + p + 1) * 8);
          get_pair(A[2 * p + 2], A[2 * p + 3], xb + (p + 1) * 1024, op + (p + 1) * 1024, T);
          if (lane == 0) mbar_arrive(sb + SM_XE + (wg * 4 + p + 1) * 8);
        }
        if (p == 0 && wg == 1) bar_sync(14, 256);
        if (p >= 0) {
          if (p != 2) mbar_wait(sb + SM_FULL + (ST_WO + (p + 1) / 2) * 8);
          wg_fence();
#pragma unroll
          for (int c = 2 * p; c < 2 * p + 2; c++)
#pragma unroll
            for (int s = 0; s < 4; s++)
              wgmma_rs_n64(acc, A[c][s], DESC(((ST_WO + c / 3) % NSLOT) * SLOT + ((c % 3) * 4 + s) * 2048), 1);
        }
      }
      wg_commit();
      if (wg == 0) bar_arrive(14, 256);
      wg_wait<0>();
      if ((tid & 127) < 3) release(ST_WO + (tid & 127));
      uint4* hp_ = &g_h[rh][hg][wq][0][lane];
      uint32_t hx = T;
#pragma unroll
      for (int s = 0; s < 4; s++) {
        const uint32_t h0 = pack2(acc[8 * s], acc[8 * s + 1]);
        st_rlx4(hp_ + s * 32, tg(h0, T), pack2(acc[8 * s + 2], acc[8 * s + 3]), pack2(acc[8 * s + 4], acc[8 * s + 5]), pack2(acc[8 * s + 6], acc[8 * s + 7]));
        hx |= (h0 & 1u) << (s + 1);
      }
      float s0 = 0.f, s1 = 0.f, q0 = 0.f, q1 = 0.f, q2 = 0.f, q3 = 0.f;
#pragma unroll
      for (int i = 0; i < 8; i++) {
        s0 += acc[4 * i] + acc[4 * i + 1]; s1 += acc[4 * i + 2] + acc[4 * i + 3];
        q0 = fmaf(acc[4 * i], acc[4 * i], q0); q2 = fmaf(acc[4 * i + 1], acc[4 * i + 1], q2);
        q1 = fmaf(acc[4 * i + 2], acc[4 * i + 2], q1); q3 = fmaf(acc[4 * i + 3], acc[4 * i + 3], q3);
      }
      q0 += q2; q1 += q3;
      {
        const bool up = t & 2;
        float s = (up ? s1 : s0) + __shfl_xor_sync(0xffffffffu, up ? s0 : s1, 2);
        float q = (up ? q1 : q0) + __shfl_xor_sync(0xffffffffu, up ? q0 : q1, 2);
        s += __shfl_xor_sync(0xffffffffu, s, 1);
        q += __shfl_xor_sync(0xffffffffu, q, 1);
        if (!(t & 1)) st_rlx2(&g_st[rh][hg][wq * 16 + g + (t >> 1) * 8], tg(__float_as_uint(s), T), __float_as_uint(q));
      }
      st_rlx1(&g_hx[rh][hg][wq][lane], hx);
    }
    bar_arrive(10 + wg, 160);

    const int rh3 = 2 * rb3 + wg;
    uint32_t HH[11][4], PH[11][4];
    const uint4* pp = &g_hh[rh3][jf ^ 1][0][wq][lane];
    {
      uint32_t A[8][4][4];
      const uint4* hp_ = &g_h[rh3][0][wq][0][lane];
      uint4* hhp = &g_hh[rh3][jf][0][wq][lane];
      const uint32_t dg = (db & 0xFFFFu) | (256u << 16);
      uint32_t m0, m1;
      mbar_wait(sb + SM_XF + ((2 + wg) * 4) * 8);
      {
        const uint2* sp = reinterpret_cast<const uint2*>(smem + SM_KV32 + wg * 4096) + 2 * t * 64 + wq * 16 + g;
        uint2 a0, a1, b0, b1;
        int it = 0;
#pragma unroll 1
        do {
          ld_rlx2(a0.x, a0.y, sp); ld_rlx2(a1.x, a1.y, sp + 64); ld_rlx2(b0.x, b0.y, sp + 8); ld_rlx2(b1.x, b1.y, sp + 72);
          sp = &g_st[rh3][2 * t][wq * 16 + g];
        } while (__any_sync(0xffffffffu, bad4(a0.x, a1.x, b0.x, b1.x, T)) && ++it < (1 << 18));
        float s0 = __uint_as_float(a0.x) + __uint_as_float(a1.x), q0 = __uint_as_float(a0.y) + __uint_as_float(a1.y);
        float s1 = __uint_as_float(b0.x) + __uint_as_float(b1.x), q1 = __uint_as_float(b0.y) + __uint_as_float(b1.y);
        s0 += __shfl_xor_sync(0xffffffffu, s0, 1); s1 += __shfl_xor_sync(0xffffffffu, s1, 1);
        q0 += __shfl_xor_sync(0xffffffffu, q0, 1); q1 += __shfl_xor_sync(0xffffffffu, q1, 1);
        s0 += __shfl_xor_sync(0xffffffffu, s0, 2); s1 += __shfl_xor_sync(0xffffffffu, s1, 2);
        q0 += __shfl_xor_sync(0xffffffffu, q0, 2); q1 += __shfl_xor_sync(0xffffffffu, q1, 2);
        s0 *= (1.f / 512.f); s1 *= (1.f / 512.f);
        r0 = rcp(fmaxf(q0 * (1.f / 512.f) - s0 * s0, 0.f) + 1e-5f);
        r1 = rcp(fmaxf(q1 * (1.f / 512.f) - s1 * s1, 0.f) + 1e-5f);
        m0 = pack2(s0, s0); m1 = pack2(s1, s1);
      }
#define UOFF(u) ((((ST_GU + (u) / 3) % NSLOT) * SLOT + ((u) % 3) * 8192) >> 4)
#define UNIT_PRE(u)  do { if ((u) % 3 == 0) mbar_wait(sb + SM_FULL + (ST_GU + (u) / 3) * 8); } while (0)
#define UNIT_POST(u) do { wg_commit(); if ((u) % 3 == 1 && (u) > 3) { wg_wait<2>(); if (lead) release(ST_GU + (u) / 3 - 1); } } while (0)
      float acc[64];
      const int rz = blockIdx.y;
#pragma unroll
      for (int ps = 0; ps < 2; ps++) {
        wg_fence();
#pragma unroll
        for (int k = 0; k < 16; k++) {
          const int u = 16 * ps + k, c = k >> 1;
          if (ps == 0 && (k == 0 || k == 4 || k == 8)) {
#pragma unroll
            for (int p = (k == 0 ? 0 : (k == 4 ? 1 : 3)); p < (k == 0 ? 1 : (k == 4 ? 3 : 4)); p++) {
              if (p > 0) mbar_wait(sb + SM_XF + ((2 + wg) * 4 + p) * 8);
              get_pair(A[2 * p], A[2 * p + 1], xb + p * 1024, hp_ + p * 1024, T);
              if (lane == 0) {
                if (wg == 0) mbar_arrive(sb + SM_XE + (8 + p) * 8);
                else if (p > 0) release(ST_XC + p - 1);
              }
            }
          }
          if (ps == 0 && (k & 1) == 0) {
#pragma unroll
            for (int s = 0; s < 4; s++) {
              A[c][s][0] = hsub2(A[c][s][0], m0); A[c][s][1] = hsub2(A[c][s][1], m1);
              A[c][s][2] = hsub2(A[c][s][2], m0); A[c][s][3] = hsub2(A[c][s][3], m1);
            }
            wg_fence();
          }
          UNIT_PRE(u);
          wgmma_rs_n128(acc, A[c][(k & 1) * 2], dg + UOFF(u), k != 0 ? 1 : (ps ? rz : 0));
          wgmma_rs_n128(acc, A[c][(k & 1) * 2 + 1], dg + UOFF(u) + 128, 1);
          UNIT_POST(u);
        }
        wg_wait<0>();
#pragma unroll
        for (int s = 0; s < 4; s++) {
          uint32_t (&hh)[4] = HH[4 + s];
          hh[0] = tg(pack2(acc[8 * s + 0] * acc[32 + 8 * s + 0], acc[8 * s + 1] * acc[32 + 8 * s + 1]), T);
          hh[1] = pack2(acc[8 * s + 2] * acc[32 + 8 * s + 2], acc[8 * s + 3] * acc[32 + 8 * s + 3]);
          hh[2] = pack2(acc[8 * s + 4] * acc[32 + 8 * s + 4], acc[8 * s + 5] * acc[32 + 8 * s + 5]);
          hh[3] = pack2(acc[8 * s + 6] * acc[32 + 8 * s + 6], acc[8 * s + 7] * acc[32 + 8 * s + 7]);
          st_rlx4(hhp + (4 * ps + s) * 128, hh[0], hh[1], hh[2], hh[3]);
        }
      }
      {
        float ag[24], au[24];
        const uint32_t* ph7 = reinterpret_cast<const uint32_t*>(&g_hh[rh3][jf ^ 1][7][wq][31]);
        uint32_t hv = 0;
        bar_sync(1 + wg, 128);
        wg_fence();
#pragma unroll
        for (int k = 0; k < 16; k++) {
          const int u = 32 + k, c = k >> 1;
          if (k == 6) {
#pragma unroll
            for (int s = 0; s < 4; s++) ld_rlx4(HH[s], hhp + s * 128);
          }
          if (k == 9) hv = ld_rlx1(ph7);
          if (k == 12) {
            int it = 0;
#pragma unroll 1
            while (((hv ^ T) & 1) && ++it < (1 << 18)) hv = ld_rlx1(ph7);
#pragma unroll
            for (int s = 0; s < 8; s++) ld_rlx4(PH[s], pp + s * 128);
          }
          UNIT_PRE(u);
          wgmma_rs_n48(ag, A[c][(k & 1) * 2], dg + UOFF(u), k != 0);
          wgmma_rs_n48(au, A[c][(k & 1) * 2], dg + UOFF(u) + 256, k != 0);
          wgmma_rs_n48(ag, A[c][(k & 1) * 2 + 1], dg + UOFF(u) + 128, 1);
          wgmma_rs_n48(au, A[c][(k & 1) * 2 + 1], dg + UOFF(u) + 256 + 128, 1);
          UNIT_POST(u);
        }
        wg_wait<0>();
#pragma unroll
        for (int s = 0; s < 3; s++) {
          uint32_t (&hh)[4] = HH[8 + s];
          hh[0] = tg(pack2(ag[8 * s + 0] * au[8 * s + 0], ag[8 * s + 1] * au[8 * s + 1]), T);
          hh[1] = pack2(ag[8 * s + 2] * au[8 * s + 2], ag[8 * s + 3] * au[8 * s + 3]);
          hh[2] = pack2(ag[8 * s + 4] * au[8 * s + 4], ag[8 * s + 5] * au[8 * s + 5]);
          hh[3] = pack2(ag[8 * s + 6] * au[8 * s + 6], ag[8 * s + 7] * au[8 * s + 7]);
          st_rlx4(hhp + (8 + s) * 128, hh[0], hh[1], hh[2], hh[3]);
        }
      }
    }

    {
      float ac[3][32], acc[32];
      uint32_t hr[4][4];
      const int m = jf >> 1, oc = (jf & 1) * 4 + m;
      const uint32_t* ph10 = reinterpret_cast<const uint32_t*>(&g_hh[rh3][jf ^ 1][10][wq][31]);
      uint32_t hv = 0;
      bar_arrive(8 + wg, 256);
      wg_fence();
#pragma unroll
      for (int k = 0; k < 3; k++) {
        mbar_wait(sb + SM_FULL + (ST_D + k) * 8);
        if (k == 1) hv = ld_rlx1(ph10);
#pragma unroll
        for (int s = 0; s < 11; s++) {
          if (k == 2 && s == 4) {
            int it = 0;
#pragma unroll 1
            while (((hv ^ T) & 1) && ++it < (1 << 18)) hv = ld_rlx1(ph10);
#pragma unroll
            for (int i = 8; i < 11; i++) ld_rlx4(PH[i], pp + i * 128);
          }
          wgmma_rs_n64(ac[k], HH[s], DESC(((ST_D + k) % NSLOT) * SLOT + s * 2048), s != 0);
        }
      }
      wg_commit();
      {
        int it = 0;
#pragma unroll 1
        while (__any_sync(0xffffffffu, bad4(PH[0][0], PH[1][0], PH[2][0], PH[3][0], T) | bad4(PH[4][0], PH[5][0], PH[6][0], PH[7][0], T) |
                                       bad4(PH[8][0], PH[9][0], PH[10][0], T, T))) {
#pragma unroll
          for (int s = 0; s < 11; s++) ld_rlx4(PH[s], pp + s * 128);
          if (++it > (1 << 18)) break;
        }
      }
      uint4* outb = &g_part[rh3][(jf & 1) * 4][m][wq][0][lane];
#pragma unroll
      for (int k = 0; k < 4; k++) {
        mbar_wait(sb + SM_FULL + (ST_D + 3 + k) * 8);
        wg_fence();
#pragma unroll
        for (int s = 0; s < 11; s++) {
          if (k < 3) wgmma_rs_n64(ac[k], PH[s], DESC(((ST_D + 3 + k) % NSLOT) * SLOT + s * 2048), 1);
          else wgmma_rs_n64(acc, HH[s], DESC(((ST_D + 6) % NSLOT) * SLOT + s * 2048), s != 0);
          if (s == 6 && k > 0) {
            wg_commit();
            wg_wait<1>();
            if (k == 1) bar_arrive(12, 320);
            const float (&a)[32] = ac[k - 1];
            uint4* p = outb + ((m + k) & 3) * 2048;
#pragma unroll
            for (int i = 0; i < 4; i++)
              st_rlx4(p + i * 32, tg(pack2(a[8 * i + 0], a[8 * i + 1]), T), pack2(a[8 * i + 2], a[8 * i + 3]),
                      pack2(a[8 * i + 4], a[8 * i + 5]), pack2(a[8 * i + 6], a[8 * i + 7]));
          }
        }
        wg_commit();
      }
      ld_chunk(hr, &g_h[rh3][oc][wq][0][lane]);
      uint32_t hx = ld_rlx1(&g_hx[rh3][oc][wq][lane]);
      mbar_wait(sb + SM_FULL + (ST_D + 7) * 8);
      wg_fence();
#pragma unroll
      for (int s = 0; s < 11; s++) wgmma_rs_n64(acc, PH[s], DESC(((ST_D + 7) % NSLOT) * SLOT + s * 2048), 1);
      wg_commit();
      wg_wait<0>();
#pragma unroll 1
      for (int q = 0; q < 3; q++) {
        uint32_t in[4][4];
        const uint4* sp = reinterpret_cast<const uint4*>(smem + ((ST_D % NSLOT) + wg) * SLOT) + q * 512 + wq * 128 + lane;
        mbar_wait_p(sb + SM_XF + (wg * 4 + q) * 8, 1);
        int it = 0;
#pragma unroll 1
        do {
#pragma unroll
          for (int s = 0; s < 4; s++)
            asm volatile("{\n.reg .b128 v;\nld.relaxed.gpu.b128 v, [%4];\nmov.b128 {%0,%1,%2,%3}, v;\n}"
                         : "=r"(in[s][0]), "=r"(in[s][1]), "=r"(in[s][2]), "=r"(in[s][3]) : "l"(sp + s * 32) : "memory");
          sp = &g_part[rh3][oc][(m - 1 - q) & 3][wq][0][lane];
        } while (__any_sync(0xffffffffu, bad4(in[0][0], in[1][0], in[2][0], in[3][0], T)) && ++it < (1 << 18));
        add_frag(acc, in, IDF);
      }
      {
        int it = 0;
#pragma unroll 1
        while (__any_sync(0xffffffffu, (hx ^ T) & 1) && ++it < (1 << 18)) hx = ld_rlx1(&g_hx[rh3][oc][wq][lane]);
      }
#pragma unroll
      for (int s = 0; s < 4; s++) hr[s][0] = (hr[s][0] & 0xFFFFFFFEu) | ((hx >> (s + 1)) & 1u);
#pragma unroll
      for (int i = 0; i < 32; i++) acc[i] *= (i & 2) ? r1 : r0;
      add_frag(acc, hr, IDF);
      bar_sync(9 - wg, 256);
      const uint32_t ob = sb + ((ST_D - 1) % NSLOT) * SLOT + wg * 8192;
#pragma unroll
      for (int s = 0; s < 4; s++)
        stsm4(ob + lrow + (((2 * s + lhi) ^ lx) << 4), pack2(acc[8 * s + 0], acc[8 * s + 1]), pack2(acc[8 * s + 2], acc[8 * s + 3]),
              pack2(acc[8 * s + 4], acc[8 * s + 5]), pack2(acc[8 * s + 6], acc[8 * s + 7]));
      __syncwarp();
      {
        const int row = wq * 16 + (lane >> 3);
        __nv_bfloat16* op = out + (size_t)(rh3 * 64 + row) * 512 + oc * 64 + lx * 8;
#pragma unroll
        for (int i = 0; i < 4; i++) {
          uint4 v;
          asm volatile("ld.shared.v4.b32 {%0,%1,%2,%3}, [%4];" : "=r"(v.x), "=r"(v.y), "=r"(v.z), "=r"(v.w)
                       : "r"(ob + (row + i * 4) * 128 + ((lx ^ (((lane >> 3) + i * 4) & 7)) << 4)) : "memory");
          asm volatile("st.global.v4.b32 [%0], {%1,%2,%3,%4};" ::"l"(op + i * 2048), "r"(v.x), "r"(v.y), "r"(v.z), "r"(v.w) : "memory");
        }
      }
    }
    asm volatile("barrier.cluster.arrive.relaxed.aligned;" ::: "memory");
    asm volatile("barrier.cluster.wait.aligned;" ::: "memory");
  } else {
    asm volatile("setmaxnreg.dec.sync.aligned.u32 24;");
    if (elect_one()) {
      if (warp == 8) {
#pragma unroll
        for (int k = 0; k < 9; k++) {
          const int s = k < 3 ? k : (k < 6 ? k + 3 : k - 3);
          const uint32_t bar = sb + SM_FULL + s * 8;
          mbar_init(bar, 1);
          mbar_expect_tx(bar, SLOT);
          if (s >= 3 && s < 6) tma2d(sb + s * SLOT, &maps.w, 512 + hg * 64, (s - 3) * 192, bar);
          else tma3d(sb + s * SLOT, &maps.x, 0, rb * 128 + (s >= 6 ? 64 : 0), 3 * (s % 3), bar);
        }
      } else if (warp == 9) {
        mbar_init(sb + SM_MISCB, 2);
        mbar_init(sb + SM_KVB, 1);
        mbar_expect_tx(sb + SM_KVB, 8704);
        mbar_expect_tx(sb + SM_MISCB, 2048);
        bulk_g2s(sb + SM_WPHI, wphi + hg * 1024, 2048, sb + SM_MISCB);
      } else if (warp == 10) {
        if ((sb & 0x3FFFF) != SM_BASE) __trap();
#pragma unroll 1
        for (int i = 0; i < 16; i++) {
          mbar_init(sb + SM_XF + i * 8, 1);
          mbar_expect_tx(sb + SM_XF + i * 8, (i == 8 || i == 12) ? 20480 : 16384);
          if (i < 12) mbar_init(sb + SM_XE + i * 8, 4);
        }
      } else {
        *reinterpret_cast<volatile unsigned*>(smem + SM_EPOCH) = atomicAdd(&g_start, 1u) / NCTA;
      }
      asm volatile("fence.mbarrier_init.release.cluster;" ::: "memory");
    }
    __syncwarp();
    if (warp != 11) bar_sync(0, 352);
    asm volatile("barrier.cluster.arrive.relaxed.aligned;" ::: "memory");
    if (warp == 8) {
      asm volatile("barrier.cluster.wait.aligned;" ::: "memory");
      if (elect_one()) {
        const CUtensorMap* mg = jf == 7 ? &maps.g7 : &maps.g;
        const CUtensorMap* mu = jf == 7 ? &maps.u7 : &maps.u;
        asm volatile("prefetch.tensormap [%0];" ::"l"(&maps.wo) : "memory");
        asm volatile("prefetch.tensormap [%0];" ::"l"(mg) : "memory");
        asm volatile("prefetch.tensormap [%0];" ::"l"(mu) : "memory");
        asm volatile("prefetch.tensormap [%0];" ::"l"(&maps.d) : "memory");
#pragma unroll 1
        for (int s = ST_WV; s < ST_XC; s++) {
          if (s == ST_SCR1) continue;
          mbar_wait(sb + SM_EMPTY + (s - 9) * 8);
          const uint32_t dst = sb + (s >= 18 ? s - 18 : s - 9) * SLOT, bar = sb + SM_FULL + s * 8;
          if (s < ST_WO) tma2d(dst, &maps.w, (s < ST_WQ ? 1024 : 0) + hg * 64, (s < ST_WQ ? s - ST_WV : s - ST_WQ) * 192, bar);
          else { mbar_wait(bar - 8); tma2d(dst, &maps.wo, hg * 64, (s - ST_WO) * 192, bar); }
        }
        const int jc = jf == 7 ? 0 : jf;
        int slot = (ST_GU + 1 - rank) % NSLOT;
#pragma unroll 1
        for (int s = ST_GU + 1 - rank; s < NSTAGE; s += 2) {
          mbar_wait(sb + SM_EMPTY + (s - 9) * 8);
          if (s > ST_GU && s < ST_GU + 6) mbar_wait(sb + SM_FULL + (s - 1) * 8);
          const uint32_t dst = sb + slot * SLOT, bar = sb + SM_FULL + s * 8;
          if (s < ST_D) {
#pragma unroll 1
            for (int i = 0; i < 3; i++) {
              const int u = (s - ST_GU) * 3 + i;
              tma3d_mc(dst + i * 8192, mg, (u >> 4) * 64, jc, (u & 15) * 32, bar);
              tma3d_mc(dst + i * 8192 + 4096, mu, (u >> 4) * 64, jc, (u & 15) * 32, bar);
            }
          } else {
            const int i = s - ST_D, k = i < 3 ? i : (i < 6 ? i - 3 : 3), pt = (i >= 3 && i != 6) ? 1 : 0;
            tma2d_mc(dst, &maps.d, ((jf & 1) * 4 + (((jf >> 1) + 1 + k) & 3)) * 64, (jf ^ pt) * 176, bar);
          }
          slot += 2; if (slot >= NSLOT) slot -= NSLOT;
        }
      }
      __syncwarp();
    } else {
      asm volatile("barrier.cluster.wait.aligned;" ::: "memory");
      if (warp == 11) {
#pragma unroll
        for (int i = 0; i < 4; i++)
          reinterpret_cast<uint4*>(smem + SM_ONES)[lane + 32 * i] = make_uint4(0x3F803F80u, 0x3F803F80u, 0x3F803F80u, 0x3F803F80u);
        fence_async_smem();
        __syncwarp();
        if (lane == 0) mbar_arrive(sb + SM_MISCB);
      }
      mbar_wait(sb + SM_MISCB);
      const unsigned epoch = *reinterpret_cast<volatile unsigned*>(smem + SM_EPOCH);
      const uint32_t T = (epoch & 1) ^ 1;
      if (warp == 11) {
        reinterpret_cast<float4*>(&g_kv[hg][rb * 136])[lane] = make_float4(0.f, 0.f, 0.f, 0.f);
        if (lane < 2) reinterpret_cast<float4*>(&g_kv[hg][rb * 136])[32 + lane] = make_float4(0.f, 0.f, 0.f, 0.f);
        __syncwarp();
        if (elect_one()) asm volatile("red.release.gpu.global.add.u32 [%0], 8;" ::"l"(&g_kvcnt[hg * 32 + 1]) : "memory");
        mbar_wait(sb + SM_FULL + (ST_WK + 2) * 8);
        if (elect_one()) {
          asm volatile("cp.async.bulk.prefetch.L2.global [%0], 4096;" ::"l"((const char*)wo + blockIdx.x * 4096) : "memory");
          asm volatile("cp.async.bulk.prefetch.L2.global [%0], 11008;" ::"l"((const char*)wg_ + blockIdx.x * 11008) : "memory");
          asm volatile("cp.async.bulk.prefetch.L2.global [%0], 11008;" ::"l"((const char*)wu_ + blockIdx.x * 11008) : "memory");
          asm volatile("cp.async.bulk.prefetch.L2.global [%0], 11008;" ::"l"((const char*)wd_ + blockIdx.x * 11008) : "memory");
          mbar_wait(sb + SM_EMPTY + ST_SCR0 * 8);
          const unsigned target = (epoch + 1) * 128;
          unsigned v; int it = 0;
#pragma unroll 1
          do {
            asm volatile("ld.acquire.gpu.global.u32 %0, [%1];" : "=r"(v) : "l"(&g_kvcnt[hg * 32]) : "memory");
            if (++it > (1 << 18)) break;
          } while ((int)(v - target) < 0);
          asm volatile("fence.proxy.async.global;" ::: "memory");
          bulk_g2s(sb + SM_KV32, &g_kv[hg][0], 8192, sb + SM_KVB);
          bulk_g2s(sb + SM_ONES, &g_kv[hg][2048], 512, sb + SM_KVB);
        }
        __syncwarp();
      } else {
        const int w = warp - 9;
        st_rlx4(reinterpret_cast<uint4*>(&g_st[2 * rb + w][hg][0]) + lane, T ^ 1, T ^ 1, T ^ 1, T ^ 1);
        if (lane < 8) st_rlx4(&g_o[2 * rb + w][hg][lane >> 1][3][30 + (lane & 1)], T ^ 1, T ^ 1, T ^ 1, T ^ 1);
        st_rlx4(&g_part[2 * rb3 + w][(jf & 1) * 4 + (lane >> 3)][jf >> 1][(lane >> 1) & 3][3][30 + (lane & 1)], T ^ 1, T ^ 1, T ^ 1, T ^ 1);
        if (lane < 16) st_rlx4(&g_hh[2 * rb3 + w][jf][7 + (lane >> 3) * 3][(lane >> 1) & 3][30 + (lane & 1)], T ^ 1, T ^ 1, T ^ 1, T ^ 1);
        if (w == 0) {
          mbar_wait(sb + SM_FULL + (ST_WQ + 2) * 8);
          unsigned v; int it = 0;
#pragma unroll 1
          do {
            asm volatile("ld.acquire.gpu.global.u32 %0, [%1];" : "=r"(v) : "l"(&g_kvcnt[hg * 32 + 1]) : "memory");
          } while ((int)(v - (epoch + 1) * 128) < 0 && ++it < (1 << 18));
          asm volatile("fence.proxy.async.global;" ::: "memory");
        }
        bar_sync(6, 320);
        if (w == 0 && elect_one()) {
          asm volatile("cp.reduce.async.bulk.global.shared::cta.bulk_group.add.f32 [%0], [%1], 8704;"
                       ::"l"(&g_kv[hg][0]), "r"(sb + 2 * SLOT) : "memory");
          asm volatile("cp.async.bulk.commit_group;" ::: "memory");
          asm volatile("cp.async.bulk.wait_group 0;" ::: "memory");
          asm volatile("red.release.gpu.global.add.u32 [%0], 8;" ::"l"(&g_kvcnt[hg * 32]) : "memory");
        }
        __syncwarp();
        mbar_wait(sb + SM_KVB);
        if (w == 0) { mbar_wait(sb + SM_EMPTY + 11 * 8); mbar_wait(sb + SM_EMPTY + 12 * 8); mbar_wait(sb + SM_EMPTY + 13 * 8); }
#pragma unroll 1
        for (int ph = 0; ph < 2; ph++) {
          const int use = 2 * ph + w, r = ph ? 2 * rb3 + w : 2 * rb + w;
          const uint32_t* pw = ph ? reinterpret_cast<const uint32_t*>(&g_st[r][lane >> 2][(lane & 3) * 16 + 15])
                                  : reinterpret_cast<const uint32_t*>(&g_o[r][lane >> 2][lane & 3][3][31]);
          const char* src = reinterpret_cast<const char*>(ph ? &g_h[r][0][0][0][0] : &g_o[r][0][0][0][0]);
          const uint32_t bf = sb + SM_XF + use * 32, be = sb + SM_XE + (use - 1) * 32;
          bar_sync(10 + w, 160);
          int it = 0;
#pragma unroll 1
          for (bool miss = true; __any_sync(0xffffffffu, miss) && ++it < (1 << 18);) { if (miss) miss = (ld_rlx1(pw) ^ T) & 1; }
          if (elect_one()) {
            if (use > 0) mbar_wait(be);
            if (ph) bulk_g2s(sb + SM_KV32 + w * 4096, &g_st[r][0][0], 4096, bf);
#pragma unroll
            for (int p = 0; p < 4; p++) {
              if (p > 0 && use > 0) mbar_wait(be + p * 8);
              bulk_g2s(sb + 2 * SLOT + p * 16384, src + p * 16384, 16384, bf + p * 8);
            }
          }
          __syncwarp();
        }
        {
          const int m = jf >> 1, oc = (jf & 1) * 4 + m;
          const uint32_t* pw = reinterpret_cast<const uint32_t*>(&g_part[2 * rb3 + w][oc][(m - 1 - (lane >> 2)) & 3][lane & 3][3][31]);
          bar_sync(12, 320);
          bool miss = lane < 12; int it = 0;
#pragma unroll 1
          for (int q = 0; q < 3; q++) {
#pragma unroll 1
            while ((__ballot_sync(0xffffffffu, miss) >> (4 * q) & 15) && ++it < (1 << 18)) { if (miss && (lane >> 2) <= q + 1) miss = (ld_rlx1(pw) ^ T) & 1; }
            if (elect_one()) {
              const uint32_t bar = sb + SM_XF + (w * 4 + q) * 8;
              mbar_expect_tx(bar, 8192);
              bulk_g2s(sb + ((ST_D % NSLOT) + w) * SLOT + q * 8192, &g_part[2 * rb3 + w][oc][(m - 1 - q) & 3][0][0][0], 8192, bar);
            }
            __syncwarp();
          }
        }
      }
    }
    asm volatile("barrier.cluster.arrive.relaxed.aligned;" ::: "memory");
    asm volatile("barrier.cluster.wait.aligned;" ::: "memory");
  }
}

typedef CUresult (*EncodeFn)(CUtensorMap*, CUtensorMapDataType, cuuint32_t, void*, const cuuint64_t*, const cuuint64_t*,
                             const cuuint32_t*, const cuuint32_t*, CUtensorMapInterleave, CUtensorMapSwizzle,
                             CUtensorMapL2promotion, CUtensorMapFloatOOBfill);

void encode(EncodeFn fn, CUtensorMap* m, const void* base, int rank, const cuuint64_t* dims, const cuuint64_t* strides,
            const cuuint32_t* box) {
  cuuint32_t es[3] = {1, 1, 1};
  fn(m, CU_TENSOR_MAP_DATA_TYPE_BFLOAT16, (cuuint32_t)rank, const_cast<void*>(base), dims, strides, box, es,
     CU_TENSOR_MAP_INTERLEAVE_NONE, CU_TENSOR_MAP_SWIZZLE_128B, CU_TENSOR_MAP_L2_PROMOTION_L2_256B,
     CU_TENSOR_MAP_FLOAT_OOB_FILL_NONE);
}

}

extern "C" void kernel_launch(void* const* d_in, const int* in_sizes, int n_in, void* d_out, int out_size) {
  (void)in_sizes; (void)n_in; (void)out_size;
  const __nv_bfloat16* x    = (const __nv_bfloat16*)d_in[0];
  const __nv_bfloat16* wqkv = (const __nv_bfloat16*)d_in[1];
  const __nv_bfloat16* wphi = (const __nv_bfloat16*)d_in[2];
  const __nv_bfloat16* wo   = (const __nv_bfloat16*)d_in[3];
  const __nv_bfloat16* wg   = (const __nv_bfloat16*)d_in[5];
  const __nv_bfloat16* wu   = (const __nv_bfloat16*)d_in[6];
  const __nv_bfloat16* wd   = (const __nv_bfloat16*)d_in[7];

  static EncodeFn fn = nullptr;
  if (!fn) {
    void* p = nullptr;
    cudaDriverEntryPointQueryResult qr;
    cudaGetDriverEntryPoint("cuTensorMapEncodeTiled", &p, cudaEnableDefault, &qr);
    fn = (EncodeFn)p;
    cudaFuncSetAttribute(fused_kernel, cudaFuncAttributeMaxDynamicSharedMemorySize, SM_TOTAL);
  }
  Maps maps;
  {
    cuuint64_t d[3] = {64, 2048, 8}, s[2] = {1024, 128}; cuuint32_t b[3] = {64, 64, 3};
    encode(fn, &maps.x, x, 3, d, s, b);
  }
  {
    cuuint64_t d[2] = {1536, 512}, s[1] = {3072}; cuuint32_t b[2] = {64, 192};
    encode(fn, &maps.w, wqkv, 2, d, s, b);
  }
  {
    cuuint64_t d[2] = {512, 512}, s[1] = {1024}; cuuint32_t b[2] = {64, 192};
    encode(fn, &maps.wo, wo, 2, d, s, b);
  }
  {
    cuuint64_t d[3] = {176, 7, 512}, d7[3] = {144, 1, 512}, s[2] = {352, 2752}; cuuint32_t b[3] = {64, 1, 32};
    encode(fn, &maps.g, wg, 3, d, s, b);
    encode(fn, &maps.u, wu, 3, d, s, b);
    encode(fn, &maps.g7, wg + 1232, 3, d7, s, b);
    encode(fn, &maps.u7, wu + 1232, 3, d7, s, b);
  }
  {
    cuuint64_t d[2] = {512, 1376}, s[1] = {1024}; cuuint32_t b[2] = {64, 176};
    encode(fn, &maps.d, wd, 2, d, s, b);
  }
  fused_kernel<<<NCTA, 384, SM_TOTAL>>>(maps, x, wphi, wo, wg, wu, wd, (__nv_bfloat16*)d_out);
}
```

```cpp
#include <cuda_runtime.h>
#include <cuda_bf16.h>
#include <cuda.h>
#include <stdint.h>

#define SAFE_WAIT 0

namespace {

constexpr int NCTA   = 128;
constexpr int SLOT   = 24576;
constexpr int NSLOT  = 9;
constexpr int NSTAGE = 47;

constexpr int ST_X0   = 0;
constexpr int ST_WK   = 3;
constexpr int ST_X1   = 6;
constexpr int ST_SCR0 = 9;
constexpr int ST_WV   = 10;
constexpr int ST_SCR1 = 13;
constexpr int ST_WQ   = 14;
constexpr int ST_WO   = 17;
constexpr int ST_XC   = 20;
constexpr int ST_GU   = 23;
constexpr int ST_D    = 39;

__host__ __device__ constexpr int st_empty_cnt(int d) {
  return ((d < 3 || (d >= 6 && d < 9) || (d >= ST_XC && d < ST_GU)) ? 4 : 2) * (d + 9 >= ST_GU ? 2 : 1);
}

constexpr uint32_t SM_BASE = 1024;
constexpr int SM_ONES = NSLOT * SLOT;
constexpr int SM_WPHI = SM_ONES + 2048;
constexpr int SM_KVS  = SM_WPHI + 2048;
constexpr int SM_KV32 = 4 * SLOT + 16384;
constexpr int SM_BAR  = SM_KVS + 6144;
constexpr int SM_FULL  = SM_BAR;
constexpr int SM_EMPTY = SM_BAR + NSTAGE * 8;
constexpr int SM_MISCB = SM_BAR + 2 * NSTAGE * 8;
constexpr int SM_KVB   = SM_MISCB + 8;
constexpr int SM_EPOCH = SM_KVB + 8;
constexpr int SM_XF    = SM_EPOCH + 8;
constexpr int SM_XE    = SM_XF + 16 * 8;
constexpr int SM_TOTAL = SM_BAR + 1024;

static_assert(SM_TOTAL == 232448 && SM_XE + 12 * 8 <= SM_TOTAL, "smem budget");

struct Maps { CUtensorMap x, w, wo, g, u, g7, u7, d; };

__device__ __align__(128) uint4    g_o[32][8][4][4][32];
__device__ __align__(128) uint4    g_h[32][8][4][4][32];
__device__ __align__(128) uint32_t g_hx[32][8][4][32];
__device__ __align__(128) uint2    g_st[32][8][64];
__device__ __align__(128) uint4    g_hh[32][8][11][4][32];
__device__ __align__(128) uint4    g_part[32][8][4][4][4][32];
__device__ __align__(128) float g_kv[8][2048 + 128];
__device__ __align__(128) unsigned g_kvcnt[8 * 32];
__device__ unsigned g_start;

__device__ __forceinline__ uint32_t smem_u32(const void* p) { return (uint32_t)__cvta_generic_to_shared(p); }
__device__ __forceinline__ void mbar_init(uint32_t bar, int cnt) {
  asm volatile("mbarrier.init.shared::cta.b64 [%0], %1;" ::"r"(bar), "r"(cnt) : "memory");
}
__device__ __forceinline__ void mbar_expect_tx(uint32_t bar, uint32_t bytes) {
  asm volatile("mbarrier.arrive.expect_tx.shared::cta.b64 _, [%0], %1;" ::"r"(bar), "r"(bytes) : "memory");
}
__device__ __forceinline__ void mbar_arrive(uint32_t bar) {
  asm volatile("mbarrier.arrive.shared::cta.b64 _, [%0];" ::"r"(bar) : "memory");
}
__device__ __forceinline__ void mbar_arrive_cluster(uint32_t bar, uint32_t rank) {
  asm volatile("{\n.reg .b32 ra;\nmapa.shared::cluster.u32 ra, %0, %1;\n"
               "mbarrier.arrive.shared::cluster.b64 _, [ra];\n}" ::"r"(bar), "r"(rank) : "memory");
}
__device__ __forceinline__ void mbar_wait_p(uint32_t bar, uint32_t parity) {
  asm volatile("{\n.reg .pred p;\nW: mbarrier.try_wait.parity.shared::cta.b64 p, [%0], %1;\n@!p bra W;\n}" ::"r"(bar), "r"(parity) : "memory");
}
__device__ __forceinline__ void mbar_wait(uint32_t bar) { mbar_wait_p(bar, 0); }
__device__ __forceinline__ bool elect_one() {
  uint32_t p;
  asm volatile("{\n.reg .pred P;\nelect.sync _|P, 0xffffffff;\nselp.u32 %0, 1, 0, P;\n}" : "=r"(p));
  return p != 0;
}
__device__ __forceinline__ void bar_sync(int id, int n)   { asm volatile("bar.sync %0, %1;" ::"r"(id), "r"(n) : "memory"); }
__device__ __forceinline__ void bar_arrive(int id, int n) { asm volatile("bar.arrive %0, %1;" ::"r"(id), "r"(n) : "memory"); }
__device__ __forceinline__ void fence_async_smem() { asm volatile("fence.proxy.async.shared::cta;" ::: "memory"); }
__device__ __forceinline__ void wg_fence()  { asm volatile("wgmma.fence.sync.aligned;" ::: "memory"); }
__device__ __forceinline__ void wg_commit() { asm volatile("wgmma.commit_group.sync.aligned;" ::: "memory"); }
template <int N> __device__ __forceinline__ void wg_wait() { asm volatile("wgmma.wait_group.sync.aligned %0;" ::"n"(N) : "memory"); }
#define DESC(off) (db + ((uint32_t)(off) >> 4))
__device__ __forceinline__ void tma2d(uint32_t dst, const CUtensorMap* m, int c0, int c1, uint32_t bar) {
  asm volatile("cp.async.bulk.tensor.2d.shared::cluster.global.mbarrier::complete_tx::bytes [%0], [%1, {%3, %4}], [%2];"
               ::"r"(dst), "l"(m), "r"(bar), "r"(c0), "r"(c1) : "memory");
}
__device__ __forceinline__ void tma2d_mc(uint32_t dst, const CUtensorMap* m, int c0, int c1, uint32_t bar) {
  asm volatile("cp.async.bulk.tensor.2d.shared::cluster.global.mbarrier::complete_tx::bytes.multicast::cluster [%0], [%1, {%3, %4}], [%2], %5;"
               ::"r"(dst), "l"(m), "r"(bar), "r"(c0), "r"(c1), "h"((uint16_t)3) : "memory");
}
__device__ __forceinline__ void tma3d(uint32_t dst, const CUtensorMap* m, int c0, int c1, int c2, uint32_t bar) {
  asm volatile("cp.async.bulk.tensor.3d.shared::cluster.global.mbarrier::complete_tx::bytes [%0], [%1, {%3, %4, %5}], [%2];"
               ::"r"(dst), "l"(m), "r"(bar), "r"(c0), "r"(c1), "r"(c2) : "memory");
}
__device__ __forceinline__ void tma3d_mc(uint32_t dst, const CUtensorMap* m, int c0, int c1, int c2, uint32_t bar) {
  asm volatile("cp.async.bulk.tensor.3d.shared::cluster.global.mbarrier::complete_tx::bytes.multicast::cluster [%0], [%1, {%3, %4, %5}], [%2], %6;"
               ::"r"(dst), "l"(m), "r"(bar), "r"(c0), "r"(c1), "r"(c2), "h"((uint16_t)3) : "memory");
}
__device__ __forceinline__ void ldsm4(uint32_t (&r)[4], uint32_t addr) {
  asm volatile("ldmatrix.sync.aligned.m8n8.x4.shared.b16 {%0,%1,%2,%3}, [%4];"
               : "=r"(r[0]), "=r"(r[1]), "=r"(r[2]), "=r"(r[3]) : "r"(addr) : "memory");
}
__device__ __forceinline__ void ldsm4t(uint32_t (&r)[4], uint32_t addr) {
  asm volatile("ldmatrix.sync.aligned.m8n8.x4.trans.shared.b16 {%0,%1,%2,%3}, [%4];"
               : "=r"(r[0]), "=r"(r[1]), "=r"(r[2]), "=r"(r[3]) : "r"(addr) : "memory");
}
__device__ __forceinline__ void stsm4(uint32_t addr, uint32_t r0, uint32_t r1, uint32_t r2, uint32_t r3) {
  asm volatile("stmatrix.sync.aligned.m8n8.x4.shared.b16 [%0], {%1,%2,%3,%4};"
               ::"r"(addr), "r"(r0), "r"(r1), "r"(r2), "r"(r3) : "memory");
}
__device__ __forceinline__ void mma16816(float (&c)[4], const uint32_t (&a)[4], uint32_t b0, uint32_t b1) {
  asm volatile("mma.sync.aligned.m16n8k16.row.col.f32.bf16.bf16.f32 {%0,%1,%2,%3},{%4,%5,%6,%7},{%8,%9},{%0,%1,%2,%3};"
               : "+f"(c[0]), "+f"(c[1]), "+f"(c[2]), "+f"(c[3])
               : "r"(a[0]), "r"(a[1]), "r"(a[2]), "r"(a[3]), "r"(b0), "r"(b1));
}
__device__ __forceinline__ void add_frag(float (&c)[32], const uint32_t (&a)[4][4], uint32_t id) {
#pragma unroll
  for (int i = 0; i < 8; i++)
    asm volatile("mma.sync.aligned.m16n8k8.row.col.f32.bf16.bf16.f32 {%0,%1,%2,%3},{%4,%5},{%6},{%0,%1,%2,%3};"
                 : "+f"(c[4 * i]), "+f"(c[4 * i + 1]), "+f"(c[4 * i + 2]), "+f"(c[4 * i + 3])
                 : "r"(a[i >> 1][(i & 1) * 2]), "r"(a[i >> 1][(i & 1) * 2 + 1]), "r"(id));
}
__device__ __forceinline__ uint32_t pack2(float lo, float hi) {
  uint32_t r; asm("cvt.rn.bf16x2.f32 %0, %1, %2;" : "=r"(r) : "f"(hi), "f"(lo)); return r;
}
__device__ __forceinline__ float blo(uint32_t w) { return __uint_as_float(w << 16); }
__device__ __forceinline__ float bhi(uint32_t w) { return __uint_as_float(w & 0xFFFF0000u); }
__device__ __forceinline__ uint32_t hsub2(uint32_t a, uint32_t b) { uint32_t r; asm("sub.rn.bf16x2 %0, %1, %2;" : "=r"(r) : "r"(a), "r"(b)); return r; }
__device__ __forceinline__ uint32_t hmax2(uint32_t a, uint32_t b) { uint32_t r; asm("max.bf16x2 %0, %1, %2;" : "=r"(r) : "r"(a), "r"(b)); return r; }
__device__ __forceinline__ uint32_t hmin2(uint32_t a, uint32_t b) { uint32_t r; asm("min.bf16x2 %0, %1, %2;" : "=r"(r) : "r"(a), "r"(b)); return r; }
__device__ __forceinline__ float ex2(float x) { float r; asm("ex2.approx.ftz.f32 %0, %1;" : "=f"(r) : "f"(x)); return r; }
__device__ __forceinline__ float rcp(float x) { float r; asm("rcp.approx.ftz.f32 %0, %1;" : "=f"(r) : "f"(x)); return r; }
__device__ __forceinline__ void ld_rlx4(uint32_t (&r)[4], const uint4* p) {
  asm volatile("{\n.reg .b128 v;\nld.relaxed.gpu.global.b128 v, [%4];\nmov.b128 {%0,%1,%2,%3}, v;\n}"
               : "=r"(r[0]), "=r"(r[1]), "=r"(r[2]), "=r"(r[3]) : "l"(p) : "memory");
}
__device__ __forceinline__ void st_rlx4(uint4* p, uint32_t a, uint32_t b, uint32_t c, uint32_t d) {
  asm volatile("st.relaxed.gpu.global.v4.b32 [%0], {%1,%2,%3,%4};" ::"l"(p), "r"(a), "r"(b), "r"(c), "r"(d) : "memory");
}
__device__ __forceinline__ void st_rlx2(uint2* p, uint32_t a, uint32_t b) {
  asm volatile("{\n.reg .b64 v;\nmov.b64 v, {%1,%2};\nst.relaxed.gpu.global.b64 [%0], v;\n}" ::"l"(p), "r"(a), "r"(b) : "memory");
}
__device__ __forceinline__ uint32_t ld_rlx1(const uint32_t* p) {
  uint32_t r; asm volatile("ld.relaxed.gpu.global.b32 %0, [%1];" : "=r"(r) : "l"(p) : "memory"); return r;
}
__device__ __forceinline__ void st_rlx1(uint32_t* p, uint32_t a) {
  asm volatile("st.relaxed.gpu.global.b32 [%0], %1;" ::"l"(p), "r"(a) : "memory");
}
__device__ __forceinline__ void ld_rlx2(uint32_t& a, uint32_t& b, const uint2* p) {
  asm volatile("{\n.reg .b64 v;\nld.relaxed.gpu.b64 v, [%2];\nmov.b64 {%0,%1}, v;\n}" : "=r"(a), "=r"(b) : "l"(p) : "memory");
}
__device__ __forceinline__ void bulk_g2s(uint32_t dst, const void* src, uint32_t bytes, uint32_t bar) {
  asm volatile("cp.async.bulk.shared::cluster.global.mbarrier::complete_tx::bytes [%0], [%1], %2, [%3];"
               ::"r"(dst), "l"(src), "r"(bytes), "r"(bar) : "memory");
}
__device__ __forceinline__ uint32_t tg(uint32_t w, uint32_t T) { return (w & 0xFFFFFFFEu) | T; }
__device__ __forceinline__ uint32_t bad4(uint32_t a, uint32_t b, uint32_t c, uint32_t d, uint32_t T) {
  uint32_t u, v;
  asm("lop3.b32 %0, %1, %2, %3, 0x7E;" : "=r"(u) : "r"(a), "r"(b), "r"(T));
  asm("lop3.b32 %0, %1, %2, %3, 0x7E;" : "=r"(v) : "r"(c), "r"(d), "r"(T));
  asm("lop3.b32 %0, %1, %2, 1, 0xA8;" : "=r"(u) : "r"(u), "r"(v));
  return u;
}

__device__ __forceinline__ void ld_chunk(uint32_t (&a)[4][4], const uint4* p) {
#pragma unroll
  for (int s = 0; s < 4; s++) ld_rlx4(a[s], p + s * 32);
}
__device__ __forceinline__ void get_pair(uint32_t (&a)[4][4], uint32_t (&b)[4][4], const uint4* sp, const uint4* gp, uint32_t T) {
  int it = 0;
#pragma unroll 1
  do {
#pragma unroll
    for (int s = 0; s < 8; s++) {
      uint32_t (&r)[4] = s < 4 ? a[s & 3] : b[s & 3];
      asm volatile("{\n.reg .b128 v;\nld.relaxed.gpu.b128 v, [%4];\nmov.b128 {%0,%1,%2,%3}, v;\n}"
                   : "=r"(r[0]), "=r"(r[1]), "=r"(r[2]), "=r"(r[3]) : "l"(sp + (s >> 2) * 512 + (s & 3) * 32) : "memory");
    }
    sp = gp;
  } while (__any_sync(0xffffffffu, bad4(a[0][0], a[1][0], a[2][0], a[3][0], T) | bad4(b[0][0], b[1][0], b[2][0], b[3][0], T)) && ++it < (1 << 18));
}

__device__ __forceinline__ void wgmma_rs_n48(float (&d)[24], const uint32_t (&a)[4], uint32_t descB, int scaleD) {
  asm volatile("{\n.reg .pred p;\n.reg .b64 db;\nsetp.ne.b32 p, %29, 0;\nmov.b64 db, {%28, 0x40000040};\n"
    "wgmma.mma_async.sync.aligned.m64n48k16.f32.bf16.bf16 {%0,%1,%2,%3,%4,%5,%6,%7,%8,%9,%10,%11,%12,%13,%14,%15,%16,%17,%18,%19,%20,%21,%22,%23}, {%24,%25,%26,%27}, db, p, 1, 1, 1;\n}\n"
    : "+f"(d[0]),"+f"(d[1]),"+f"(d[2]),"+f"(d[3]),"+f"(d[4]),"+f"(d[5]),"+f"(d[6]),"+f"(d[7]),"+f"(d[8]),"+f"(d[9]),"+f"(d[10]),"+f"(d[11]),"+f"(d[12]),"+f"(d[13]),"+f"(d[14]),"+f"(d[15]),"+f"(d[16]),"+f"(d[17]),"+f"(d[18]),"+f"(d[19]),"+f"(d[20]),"+f"(d[21]),"+f"(d[22]),"+f"(d[23])
    : "r"(a[0]), "r"(a[1]), "r"(a[2]), "r"(a[3]), "r"(descB), "r"(scaleD));
}
__device__ __forceinline__ void wgmma_rs_n64(float (&d)[32], const uint32_t (&a)[4], uint32_t descB, int scaleD) {
  asm volatile("{\n.reg .pred p;\n.reg .b64 db;\nsetp.ne.b32 p, %37, 0;\nmov.b64 db, {%36, 0x40000040};\n"
    "wgmma.mma_async.sync.aligned.m64n64k16.f32.bf16.bf16 {%0,%1,%2,%3,%4,%5,%6,%7,%8,%9,%10,%11,%12,%13,%14,%15,%16,%17,%18,%19,%20,%21,%22,%23,%24,%25,%26,%27,%28,%29,%30,%31}, {%32,%33,%34,%35}, db, p, 1, 1, 1;\n}\n"
    : "+f"(d[0]),"+f"(d[1]),"+f"(d[2]),"+f"(d[3]),"+f"(d[4]),"+f"(d[5]),"+f"(d[6]),"+f"(d[7]),"+f"(d[8]),"+f"(d[9]),"+f"(d[10]),"+f"(d[11]),"+f"(d[12]),"+f"(d[13]),"+f"(d[14]),"+f"(d[15]),"+f"(d[16]),"+f"(d[17]),"+f"(d[18]),"+f"(d[19]),"+f"(d[20]),"+f"(d[21]),"+f"(d[22]),"+f"(d[23]),"+f"(d[24]),"+f"(d[25]),"+f"(d[26]),"+f"(d[27]),"+f"(d[28]),"+f"(d[29]),"+f"(d[30]),"+f"(d[31])
    : "r"(a[0]), "r"(a[1]), "r"(a[2]), "r"(a[3]), "r"(descB), "r"(scaleD));
}
__device__ __forceinline__ void wgmma_rs_n128(float (&d)[64], const uint32_t (&a)[4], uint32_t descB, int scaleD) {
  asm volatile("{\n.reg .pred p;\n.reg .b64 db;\nsetp.ne.b32 p, %69, 0;\nmov.b64 db, {%68, 0x40000040};\n"
    "wgmma.mma_async.sync.aligned.m64n128k16.f32.bf16.bf16 {%0,%1,%2,%3,%4,%5,%6,%7,%8,%9,%10,%11,%12,%13,%14,%15,%16,%17,%18,%19,%20,%21,%22,%23,%24,%25,%26,%27,%28,%29,%30,%31,%32,%33,%34,%35,%36,%37,%38,%39,%40,%41,%42,%43,%44,%45,%46,%47,%48,%49,%50,%51,%52,%53,%54,%55,%56,%57,%58,%59,%60,%61,%62,%63}, {%64,%65,%66,%67}, db, p, 1, 1, 1;\n}\n"
    : "+f"(d[0]),"+f"(d[1]),"+f"(d[2]),"+f"(d[3]),"+f"(d[4]),"+f"(d[5]),"+f"(d[6]),"+f"(d[7]),"+f"(d[8]),"+f"(d[9]),"+f"(d[10]),"+f"(d[11]),"+f"(d[12]),"+f"(d[13]),"+f"(d[14]),"+f"(d[15]),"+f"(d[16]),"+f"(d[17]),"+f"(d[18]),"+f"(d[19]),"+f"(d[20]),"+f"(d[21]),"+f"(d[22]),"+f"(d[23]),"+f"(d[24]),"+f"(d[25]),"+f"(d[26]),"+f"(d[27]),"+f"(d[28]),"+f"(d[29]),"+f"(d[30]),"+f"(d[31]),"+f"(d[32]),"+f"(d[33]),"+f"(d[34]),"+f"(d[35]),"+f"(d[36]),"+f"(d[37]),"+f"(d[38]),"+f"(d[39]),"+f"(d[40]),"+f"(d[41]),"+f"(d[42]),"+f"(d[43]),"+f"(d[44]),"+f"(d[45]),"+f"(d[46]),"+f"(d[47]),"+f"(d[48]),"+f"(d[49]),"+f"(d[50]),"+f"(d[51]),"+f"(d[52]),"+f"(d[53]),"+f"(d[54]),"+f"(d[55]),"+f"(d[56]),"+f"(d[57]),"+f"(d[58]),"+f"(d[59]),"+f"(d[60]),"+f"(d[61]),"+f"(d[62]),"+f"(d[63])
    : "r"(a[0]), "r"(a[1]), "r"(a[2]), "r"(a[3]), "r"(descB), "r"(scaleD));
}
__device__ __forceinline__ void wgmma_ss_n72_t11(float (&d)[36], uint32_t descA, uint32_t descB, int scaleD) {
  asm volatile("{\n.reg .pred p;\n.reg .b64 da, db;\nsetp.ne.b32 p, %38, 0;\nmov.b64 da, {%36, 0x40000040};\nmov.b64 db, {%37, 0x40000040};\n"
    "wgmma.mma_async.sync.aligned.m64n72k16.f32.bf16.bf16 {%0,%1,%2,%3,%4,%5,%6,%7,%8,%9,%10,%11,%12,%13,%14,%15,%16,%17,%18,%19,%20,%21,%22,%23,%24,%25,%26,%27,%28,%29,%30,%31,%32,%33,%34,%35}, da, db, p, 1, 1, 1, 1;\n}\n"
    : "+f"(d[0]),"+f"(d[1]),"+f"(d[2]),"+f"(d[3]),"+f"(d[4]),"+f"(d[5]),"+f"(d[6]),"+f"(d[7]),"+f"(d[8]),"+f"(d[9]),"+f"(d[10]),"+f"(d[11]),"+f"(d[12]),"+f"(d[13]),"+f"(d[14]),"+f"(d[15]),"+f"(d[16]),"+f"(d[17]),"+f"(d[18]),"+f"(d[19]),"+f"(d[20]),"+f"(d[21]),"+f"(d[22]),"+f"(d[23]),"+f"(d[24]),"+f"(d[25]),"+f"(d[26]),"+f"(d[27]),"+f"(d[28]),"+f"(d[29]),"+f"(d[30]),"+f"(d[31]),"+f"(d[32]),"+f"(d[33]),"+f"(d[34]),"+f"(d[35])
    : "r"(descA), "r"(descB), "r"(scaleD));
}

constexpr float LOG2E = 1.4426950408889634f;

__device__ __forceinline__ void feat_exp(const uint32_t (&P)[4], float (&e)[16]) {
  uint32_t a = hmax2(P[0], P[2]), b = hmax2(P[1], P[3]);
  uint32_t mx = hmax2(__byte_perm(a, b, 0x5410), __byte_perm(a, b, 0x7632));
  a = hmin2(P[0], P[2]); b = hmin2(P[1], P[3]);
  uint32_t mn = hmin2(__byte_perm(a, b, 0x5410), __byte_perm(a, b, 0x7632));
  mx = hmax2(mx, __shfl_xor_sync(0xffffffffu, mx, 1));
  mn = hmin2(mn, __shfl_xor_sync(0xffffffffu, mn, 1));
  mx = hmax2(mx, __shfl_xor_sync(0xffffffffu, mx, 2));
  mn = hmin2(mn, __shfl_xor_sync(0xffffffffu, mn, 2));
  float mx0 = -blo(mx) * LOG2E, mx1 = -bhi(mx) * LOG2E, mn0 = blo(mn) * LOG2E, mn1 = bhi(mn) * LOG2E;
  float v[8] = {blo(P[0]), bhi(P[0]), blo(P[1]), bhi(P[1]), blo(P[2]), bhi(P[2]), blo(P[3]), bhi(P[3])};
#pragma unroll
  for (int i = 0; i < 8; i++) {
    bool r1 = (i >> 1) & 1;
    e[i]     = ex2(fmaf(v[i],  LOG2E, r1 ? mx1 : mx0));
    e[8 + i] = ex2(fmaf(v[i], -LOG2E, r1 ? mn1 : mn0));
  }
}

__global__ void __cluster_dims__(2, 1, 1) __launch_bounds__(384, 1)
fused_kernel(const __grid_constant__ Maps maps, const __nv_bfloat16* __restrict__ x, const __nv_bfloat16* __restrict__ wphi,
             const __nv_bfloat16* __restrict__ wo, const __nv_bfloat16* __restrict__ wg_, const __nv_bfloat16* __restrict__ wu_,
             const __nv_bfloat16* __restrict__ wd_, __nv_bfloat16* __restrict__ out) {
  extern __shared__ __align__(1024) unsigned char smem[];
  const uint32_t sb = smem_u32(smem);
  const int tid = threadIdx.x, lane = tid & 31;
  const int warp = __shfl_sync(0xffffffffu, tid >> 5, 0);
  const uint32_t rank = blockIdx.x & 1;
  const int cl = blockIdx.x >> 1;
  int quad, qi;
  if (cl < 4) { quad = 15; qi = cl; }
  else if (cl < 36) { quad = (cl - 4) & 7; qi = (cl - 4) >> 3; }
  else { qi = (cl - 36) / 7; quad = 8 + (cl - 36) - 7 * qi; }
  const int rb = quad, hg = 2 * qi + rank;
  const int rb3 = (quad & ~1) + rank, jf = 4 * (quad & 1) + qi;

  if (warp < 8) {
    asm volatile("setmaxnreg.inc.sync.aligned.u32 240;");
    if (elect_one()) {
#pragma unroll 1
      for (int d = warp; d + 9 < NSTAGE; d += 8) {
        mbar_init(sb + SM_EMPTY + d * 8, st_empty_cnt(d));
        mbar_init(sb + SM_FULL + (d + 9) * 8, 1);
        mbar_expect_tx(sb + SM_FULL + (d + 9) * 8, d + 9 >= ST_D ? 22528 : (d + 9 == ST_SCR0 || d + 9 == ST_SCR1) ? 256 : SLOT);
      }
      asm volatile("fence.mbarrier_init.release.cluster;" ::: "memory");
    }
    __syncwarp();
    bar_sync(0, 352);
    asm volatile("barrier.cluster.arrive.relaxed.aligned;" ::: "memory");
    const int wg = warp >> 2, wq = warp & 3, g = lane >> 2, t = lane & 3;
    const bool lead = (tid & 127) == 0;
    constexpr uint32_t db = (SM_BASE >> 4) | (512u << 16);
    auto release = [&](int d) {
      const int s = d + NSLOT;
      mbar_arrive_cluster(sb + SM_EMPTY + d * 8, s >= ST_GU ? (uint32_t)(s & 1) : rank);
    };
    const uint32_t lrow = (uint32_t)(wq * 16 + (lane & 7) + ((lane >> 3) & 1) * 8) * 128;
    const uint32_t lx = lane & 7, lhi = lane >> 4;
    if (wg == 1) bar_arrive(4, 256);

    float r0, r1;
    uint32_t E[4][8];
    uint32_t T = 0;
    {
      uint32_t A[32][4];
      const int sx = wg ? ST_X1 : ST_X0;
      {
        const uint32_t base = sb + sx * SLOT + lrow, baseb = sb + sx * SLOT + rank * 8192 + (wq * 16 + lx + lhi * 8) * 128;
        float cs[2][4], c0[2][4], c1[2][4];
#pragma unroll
        for (int i = 0; i < 4; i++) { cs[0][i] = cs[1][i] = c0[0][i] = c0[1][i] = c1[0][i] = c1[1][i] = 0.f; }
        uint32_t bt[4][4];
        if (wg == 1) bar_sync(13, 256);
#pragma unroll
        for (int c = 0; c < 8; c += 2) {
          if (c != 4) mbar_wait(sb + SM_FULL + (sx + (c + 1) / 3) * 8);
#pragma unroll
          for (int k = 0; k < 8; k++) ldsm4(A[4 * c + k], base + (c + (k >> 2)) * 8192 + (((2 * (k & 3) + lhi) ^ lx) << 4));
#pragma unroll
          for (int k = 0; k < 4; k++) ldsm4(bt[k], baseb + c * 8192 + (((2 * k + ((lane >> 3) & 1)) ^ lx) << 4));
#pragma unroll
          for (int k = 0; k < 8; k++) mma16816(cs[k & 1], A[4 * c + k], 0x3F803F80u, 0x3F803F80u);
          if (rank == 0) {
#pragma unroll
            for (int k = 0; k < 4; k++) { mma16816(c0[k & 1], A[4 * c + k], bt[k][0], bt[k][1]); mma16816(c1[k & 1], A[4 * c + k], bt[k][2], bt[k][3]); }
          } else {
#pragma unroll
            for (int k = 0; k < 4; k++) { mma16816(c0[k & 1], A[4 * c + 4 + k], bt[k][0], bt[k][1]); mma16816(c1[k & 1], A[4 * c + 4 + k], bt[k][2], bt[k][3]); }
          }
        }
        if (wg == 0) bar_arrive(13, 256);
        const float s0 = (cs[0][0] + cs[1][0]) * (1.f / 512.f), s1 = (cs[0][2] + cs[1][2]) * (1.f / 512.f);
        asm volatile("barrier.cluster.wait.aligned;" ::: "memory");
        if (lane < 3) release(sx + lane);
        const uint32_t m0 = pack2(s0, s0), m1 = pack2(s1, s1);
        float q0 = (g & 1) ? c0[0][1] + c0[1][1] : c0[0][0] + c0[1][0];
        float q1 = (g & 1) ? c1[0][3] + c1[1][3] : c1[0][2] + c1[1][2];
        if (t == (g >> 1))
          asm volatile("{\n.reg .b32 ra, rb;\nmapa.shared::cluster.u32 ra, %0, %2;\nmapa.shared::cluster.u32 rb, %1, %2;\n"
                       "st.async.shared::cluster.mbarrier::complete_tx::bytes.v2.f32 [ra], {%3, %4}, [rb];\n}"
                       ::"r"(sb + SM_KVS + (warp * 8 + g) * 8), "r"(sb + SM_FULL + (wg ? ST_SCR1 : ST_SCR0) * 8), "r"(rank ^ 1), "f"(q0), "f"(q1) : "memory");
        q0 = __shfl_sync(0xffffffffu, q0, (lane & ~3) | (g >> 1));
        q1 = __shfl_sync(0xffffffffu, q1, (lane & ~3) | (g >> 1));
        r0 = q0 * (1.f / 512.f) - s0 * s0;
        r1 = q1 * (1.f / 512.f) - s1 * s1;
#pragma unroll
        for (int ks = 0; ks < 32; ks++) {
          A[ks][0] = hsub2(A[ks][0], m0); A[ks][1] = hsub2(A[ks][1], m1);
          A[ks][2] = hsub2(A[ks][2], m0); A[ks][3] = hsub2(A[ks][3], m1);
        }
      }
      const uint32_t wpa = sb + SM_WPHI + ((lane & 7) + ((lane >> 3) & 1) * 8) * 32 + lhi * 16;
      const uint32_t scr = sb + (wg ? (ST_SCR1 % NSLOT) : (ST_SCR0 % NSLOT)) * SLOT;
#pragma unroll 1
      for (int ps = 0; ps < 3; ps++) {
        const int st0 = ps == 0 ? ST_WK : (ps == 1 ? ST_WV : ST_WQ);
        const uint32_t wdesc = DESC((ps == 0 ? ST_WK % NSLOT : (ps == 1 ? ST_WV % NSLOT : ST_WQ % NSLOT)) * SLOT);
        float acc[32];
        bar_sync(4 + wg, 256);
#pragma unroll
        for (int i = 0; i < 3; i++) {
          mbar_wait(sb + SM_FULL + (st0 + i) * 8);
          wg_fence();
#pragma unroll
          for (int kk = 0; kk < (i < 2 ? 12 : 8); kk++)
            wgmma_rs_n64(acc, A[12 * i + kk], wdesc + ((i * SLOT + kk * 2048) >> 4), (i | kk) != 0);
          wg_commit();
          if (i == 1) { wg_wait<1>(); if (lead) release(st0); }
        }
        if (ps == 1 && wg == 0) bar_arrive(5, 256);
        uint32_t a[4][4], b[4][4];
        if (ps == 0) {
          mbar_wait(sb + SM_MISCB);
          T = (*reinterpret_cast<volatile unsigned*>(smem + SM_EPOCH) & 1) ^ 1;
          mbar_wait(sb + SM_FULL + (wg ? ST_SCR1 : ST_SCR0) * 8);
          const float2 pq = *reinterpret_cast<const float2*>(smem + SM_KVS + (warp * 8 + g) * 8);
          r0 = rsqrtf(fmaxf(fmaf(pq.x, 1.f / 512.f, r0), 0.f) + 1e-5f);
          r1 = rsqrtf(fmaxf(fmaf(pq.y, 1.f / 512.f, r1), 0.f) + 1e-5f);
        }
#pragma unroll
        for (int h = 0; h < 4; h++) ldsm4t(b[h], wpa + h * 512);
        wg_wait<0>();
        if ((tid & 127) < 2) release(st0 + 1 + (tid & 1));
#pragma unroll
        for (int h = 0; h < 4; h++) {
          a[h][0] = pack2(acc[8 * h + 0] * r0, acc[8 * h + 1] * r0); a[h][1] = pack2(acc[8 * h + 2] * r1, acc[8 * h + 3] * r1);
          a[h][2] = pack2(acc[8 * h + 4] * r0, acc[8 * h + 5] * r0); a[h][3] = pack2(acc[8 * h + 6] * r1, acc[8 * h + 7] * r1);
        }
        if (ps != 1) {
          {
            float pp[4][2][4];
#pragma unroll
            for (int h = 0; h < 4; h++) {
#pragma unroll
              for (int i = 0; i < 4; i++) { pp[h][0][i] = 0.f; pp[h][1][i] = 0.f; }
              mma16816(pp[h][0], a[h], b[h][0], b[h][1]);
              mma16816(pp[h][1], a[h], b[h][2], b[h][3]);
            }
#pragma unroll
            for (int h = 0; h < 4; h++) {
              a[h][0] = pack2(pp[h][0][0], pp[h][0][1]); a[h][1] = pack2(pp[h][0][2], pp[h][0][3]);
              a[h][2] = pack2(pp[h][1][0], pp[h][1][1]); a[h][3] = pack2(pp[h][1][2], pp[h][1][3]);
            }
          }
          if (ps == 0 || wg == 0) bar_arrive(4 + (wg ^ 1), 256);
          if (ps == 0) mbar_wait(sb + SM_EMPTY + (wg ? ST_SCR1 - NSLOT : ST_SCR0 - NSLOT) * 8);
#pragma unroll 1
          for (int hp = 0; hp < 2; hp++) {
            float e[2][16];
            feat_exp(a[0], e[0]);
            feat_exp(a[1], e[1]);
            if (ps == 0) {
#pragma unroll
              for (int h = 0; h < 2; h++) {
                const float (&f)[16] = e[h];
                float sp0 = (f[0] + f[1]) + (f[4] + f[5]), sp1 = (f[2] + f[3]) + (f[6] + f[7]);
                float sn0 = (f[8] + f[9]) + (f[12] + f[13]), sn1 = (f[10] + f[11]) + (f[14] + f[15]);
                sp0 += __shfl_xor_sync(0xffffffffu, sp0, 1); sp1 += __shfl_xor_sync(0xffffffffu, sp1, 1);
                sn0 += __shfl_xor_sync(0xffffffffu, sn0, 1); sn1 += __shfl_xor_sync(0xffffffffu, sn1, 1);
                sp0 += __shfl_xor_sync(0xffffffffu, sp0, 2); sp1 += __shfl_xor_sync(0xffffffffu, sp1, 2);
                sn0 += __shfl_xor_sync(0xffffffffu, sn0, 2); sn1 += __shfl_xor_sync(0xffffffffu, sn1, 2);
                sp0 = rcp(sp0); sp1 = rcp(sp1); sn0 = rcp(sn0); sn1 = rcp(sn1);
                const uint32_t dst = scr + hp * 8192 + lrow;
                stsm4(dst + (((h * 4 + lhi) ^ lx) << 4), pack2(f[0] * sp0, f[1] * sp0), pack2(f[2] * sp1, f[3] * sp1),
                      pack2(f[4] * sp0, f[5] * sp0), pack2(f[6] * sp1, f[7] * sp1));
                stsm4(dst + (((h * 4 + 2 + lhi) ^ lx) << 4), pack2(f[8] * sn0, f[9] * sn0), pack2(f[10] * sn1, f[11] * sn1),
                      pack2(f[12] * sn0, f[13] * sn0), pack2(f[14] * sn1, f[15] * sn1));
              }
            } else {
#pragma unroll
              for (int i = 0; i < 16; i++) {
                A[i >> 2][i & 3] = A[4 + (i >> 2)][i & 3];
                A[4 + (i >> 2)][i & 3] = pack2(e[i >> 3][2 * (i & 7)], e[i >> 3][2 * (i & 7) + 1]);
              }
            }
#pragma unroll
            for (int i = 0; i < 4; i++) { a[0][i] = a[2][i]; a[1][i] = a[3][i]; }
          }
        } else {
#pragma unroll
          for (int h = 0; h < 4; h++) stsm4(scr + 16384 + lrow + (((2 * h + lhi) ^ lx) << 4), a[h][0], a[h][1], a[h][2], a[h][3]);
          fence_async_smem();
          bar_sync(3, 256);
          float kv[36];
          wg_fence();
#pragma unroll
          for (int ks = 0; ks < 8; ks++) {
            const uint32_t sk = (ks < 4 ? (ST_SCR0 % NSLOT) : (ST_SCR1 % NSLOT)) * SLOT + (ks & 3) * 2048;
            const uint32_t dv = (DESC(sk + 16384) & 0xFFFFu) | (((SM_ONES - sk - 16384) >> 4) << 16);
            wgmma_ss_n72_t11(kv, DESC(sk) + wg * 512, dv, ks != 0);
          }
          wg_commit();
          if (wg == 1) bar_arrive(4, 256);
          wg_wait<0>();
          if (lead) { mbar_arrive(sb + SM_EMPTY + ST_SCR0 * 8); mbar_arrive(sb + SM_EMPTY + ST_SCR1 * 8); }
          const int hl = 2 * wg + (wq >> 1), f = (wq & 1) * 16 + g;
          float* kvp = reinterpret_cast<float*>(smem + 2 * SLOT) + (hl * 32 + f) * 16 + 2 * t;
          float c[8];
#pragma unroll
          for (int i = 0; i < 8; i++) c[i] = hl >= 2 ? (hl == 3 ? kv[24 + i] : kv[16 + i]) : (hl == 1 ? kv[8 + i] : kv[i]);
#pragma unroll
          for (int n = 0; n < 2; n++) {
            *reinterpret_cast<float2*>(kvp + n * 8) = make_float2(c[4 * n], c[4 * n + 1]);
            *reinterpret_cast<float2*>(kvp + n * 8 + 128) = make_float2(c[4 * n + 2], c[4 * n + 3]);
          }
          if (t < 2) reinterpret_cast<float*>(smem + 2 * SLOT)[2048 + hl * 32 + f + t * 8] = t ? kv[34] : kv[32];
          fence_async_smem();
          bar_sync(6, 320);
        }
      }
#pragma unroll
      for (int i = 0; i < 32; i++) E[i >> 3][i & 7] = A[i >> 2][i & 3];
    }
    const int rh = 2 * rb + wg;
#define IDF ((g >> 1) == t ? ((g & 1) ? 0x3F800000u : 0x00003F80u) : 0u)
    const uint4* xb = reinterpret_cast<const uint4*>(smem + 2 * SLOT) + wq * 128 + lane;
    if (wg == 0) {
      mbar_wait(sb + SM_KVB);
      const int r = tid;
      const float4* src = reinterpret_cast<const float4*>(smem + SM_KV32) + r;
#pragma unroll
      for (int i = 0; i < 4; i++) {
        const float4 a = src[i * 128];
        *reinterpret_cast<uint2*>(smem + SM_KVS + (i * 32 + (r >> 2)) * 48 + (r & 3) * 8) = make_uint2(pack2(a.x, a.y), pack2(a.z, a.w));
      }
      const uint32_t zz = pack2(reinterpret_cast<const float*>(smem + SM_ONES)[r], 1.0f);
      *reinterpret_cast<uint4*>(smem + SM_KVS + r * 48 + 32) = make_uint4(zz, zz, zz, zz);
      bar_sync(1, 128);
    }
    {
      uint4* op = &g_o[rh][hg][wq][0][lane];
      if (wg == 1) bar_sync(7, 256);
#pragma unroll 1
      for (int hp = 0; hp < 2; hp++) {
#pragma unroll
      for (int h = 0; h < 2; h++) {
        uint32_t b0[4], b1[4], b2[4];
        const uint32_t kb = sb + SM_KVS + ((2 * hp + h) * 32 + lane) * 48;
        ldsm4t(b0, kb); ldsm4t(b1, kb + 16); ldsm4t(b2, kb + 32);
        const uint32_t ep[4] = {E[h][0], E[h][1], E[h][2], E[h][3]}, en[4] = {E[h][4], E[h][5], E[h][6], E[h][7]};
        float np0[4] = {0, 0, 0, 0}, np1[4] = {0, 0, 0, 0}, nn0[4] = {0, 0, 0, 0}, nn1[4] = {0, 0, 0, 0}, dp[4] = {0, 0, 0, 0}, dn[4] = {0, 0, 0, 0};
        mma16816(dp, ep, b2[0], b2[1]);  mma16816(dn, en, b2[2], b2[3]);
        mma16816(np0, ep, b0[0], b0[1]); mma16816(nn0, en, b0[2], b0[3]);
        mma16816(np1, ep, b1[0], b1[1]); mma16816(nn1, en, b1[2], b1[3]);
        const float i0 = rcp(fmaf(dp[0], dn[1], fmaf(dn[0], dp[1], 1e-6f * dp[1] * dn[1])));
        const float i1 = rcp(fmaf(dp[2], dn[3], fmaf(dn[2], dp[3], 1e-6f * dp[3] * dn[3])));
        const float cp0 = dn[1] * i0, cn0 = dp[1] * i0, cp1 = dn[3] * i1, cn1 = dp[3] * i1;
        st_rlx4(op + (2 * hp + h) * 32,
                tg(pack2(fmaf(np0[0], cp0, nn0[0] * cn0), fmaf(np0[1], cp0, nn0[1] * cn0)), T),
                pack2(fmaf(np0[2], cp1, nn0[2] * cn1), fmaf(np0[3], cp1, nn0[3] * cn1)),
                pack2(fmaf(np1[0], cp0, nn1[0] * cn0), fmaf(np1[1], cp0, nn1[1] * cn0)),
                pack2(fmaf(np1[2], cp1, nn1[2] * cn1), fmaf(np1[3], cp1, nn1[3] * cn1)));
      }
#pragma unroll
        for (int i = 0; i < 8; i++) { E[0][i] = E[2][i]; E[1][i] = E[3][i]; }
      }
    }
    if (wg == 0) bar_arrive(7, 256);
    bar_arrive(10 + wg, 160);

    {
      uint32_t xr[4][4];
      {
        const uint32_t* xp = reinterpret_cast<const uint32_t*>(x + (size_t)(rh * 64 + wq * 16 + g) * 512 + hg * 64 + 2 * t);
#pragma unroll
        for (int i = 0; i < 8; i++) { xr[i >> 1][(i & 1) * 2] = __ldg(xp + 4 * i); xr[i >> 1][(i & 1) * 2 + 1] = __ldg(xp + 8 * 256 + 4 * i); }
      }
      uint32_t A[8][4][4];
      const uint4* op = &g_o[rh][0][wq][0][lane];
      float acc[32];
#pragma unroll
      for (int i = 0; i < 32; i++) acc[i] = 0.f;
      add_frag(acc, xr, IDF);
#pragma unroll
      for (int p = -1; p < 4; p++) {
        if (p < 3) {
          mbar_wait(sb + SM_XF + (wg * 4 + p + 1) * 8);
          get_pair(A[2 * p + 2], A[2 * p + 3], xb + (p + 1) * 1024, op + (p + 1) * 1024, T);
          if (lane == 0) mbar_arrive(sb + SM_XE + (wg * 4 + p + 1) * 8);
        }
        if (p == 0 && wg == 1) bar_sync(14, 256);
        if (p >= 0) {
          if (p != 2) mbar_wait(sb + SM_FULL + (ST_WO + (p + 1) / 2) * 8);
          wg_fence();
#pragma unroll
          for (int c = 2 * p; c < 2 * p + 2; c++)
#pragma unroll
            for (int s = 0; s < 4; s++)
              wgmma_rs_n64(acc, A[c][s], DESC(((ST_WO + c / 3) % NSLOT) * SLOT + ((c % 3) * 4 + s) * 2048), 1);
        }
      }
      wg_commit();
      if (wg == 0) bar_arrive(14, 256);
      wg_wait<0>();
      if ((tid & 127) < 3) release(ST_WO + (tid & 127));
      uint4* hp_ = &g_h[rh][hg][wq][0][lane];
      uint32_t hx = T;
#pragma unroll
      for (int s = 0; s < 4; s++) {
        const uint32_t h0 = pack2(acc[8 * s], acc[8 * s + 1]);
        st_rlx4(hp_ + s * 32, tg(h0, T), pack2(acc[8 * s + 2], acc[8 * s + 3]), pack2(acc[8 * s + 4], acc[8 * s + 5]), pack2(acc[8 * s + 6], acc[8 * s + 7]));
        hx |= (h0 & 1u) << (s + 1);
      }
      float s0 = 0.f, s1 = 0.f, q0 = 0.f, q1 = 0.f, q2 = 0.f, q3 = 0.f;
#pragma unroll
      for (int i = 0; i < 8; i++) {
        s0 += acc[4 * i] + acc[4 * i + 1]; s1 += acc[4 * i + 2] + acc[4 * i + 3];
        q0 = fmaf(acc[4 * i], acc[4 * i], q0); q2 = fmaf(acc[4 * i + 1], acc[4 * i + 1], q2);
        q1 = fmaf(acc[4 * i + 2], acc[4 * i + 2], q1); q3 = fmaf(acc[4 * i + 3], acc[4 * i + 3], q3);
      }
      q0 += q2; q1 += q3;
      {
        const bool up = t & 2;
        float s = (up ? s1 : s0) + __shfl_xor_sync(0xffffffffu, up ? s0 : s1, 2);
        float q = (up ? q1 : q0) + __shfl_xor_sync(0xffffffffu, up ? q0 : q1, 2);
        s += __shfl_xor_sync(0xffffffffu, s, 1);
        q += __shfl_xor_sync(0xffffffffu, q, 1);
        if (!(t & 1)) st_rlx2(&g_st[rh][hg][wq * 16 + g + (t >> 1) * 8], tg(__float_as_uint(s), T), __float_as_uint(q));
      }
      st_rlx1(&g_hx[rh][hg][wq][lane], hx);
    }
    bar_arrive(10 + wg, 160);

    const int rh3 = 2 * rb3 + wg;
    uint32_t HH[11][4], PH[11][4];
    const uint4* pp = &g_hh[rh3][jf ^ 1][0][wq][lane];
    {
      uint32_t A[8][4][4];
      const uint4* hp_ = &g_h[rh3][0][wq][0][lane];
      uint4* hhp = &g_hh[rh3][jf][0][wq][lane];
      const uint32_t dg = (db & 0xFFFFu) | (256u << 16);
      uint32_t m0, m1;
      mbar_wait(sb + SM_XF + ((2 + wg) * 4) * 8);
      {
        const uint2* sp = reinterpret_cast<const uint2*>(smem + SM_KV32 + wg * 4096) + 2 * t * 64 + wq * 16 + g;
        uint2 a0, a1, b0, b1;
        int it = 0;
#pragma unroll 1
        do {
          ld_rlx2(a0.x, a0.y, sp); ld_rlx2(a1.x, a1.y, sp + 64); ld_rlx2(b0.x, b0.y, sp + 8); ld_rlx2(b1.x, b1.y, sp + 72);
          sp = &g_st[rh3][2 * t][wq * 16 + g];
        } while (__any_sync(0xffffffffu, bad4(a0.x, a1.x, b0.x, b1.x, T)) && ++it < (1 << 18));
        float s0 = __uint_as_float(a0.x) + __uint_as_float(a1.x), q0 = __uint_as_float(a0.y) + __uint_as_float(a1.y);
        float s1 = __uint_as_float(b0.x) + __uint_as_float(b1.x), q1 = __uint_as_float(b0.y) + __uint_as_float(b1.y);
        s0 += __shfl_xor_sync(0xffffffffu, s0, 1); s1 += __shfl_xor_sync(0xffffffffu, s1, 1);
        q0 += __shfl_xor_sync(0xffffffffu, q0, 1); q1 += __shfl_xor_sync(0xffffffffu, q1, 1);
        s0 += __shfl_xor_sync(0xffffffffu, s0, 2); s1 += __shfl_xor_sync(0xffffffffu, s1, 2);
        q0 += __shfl_xor_sync(0xffffffffu, q0, 2); q1 += __shfl_xor_sync(0xffffffffu, q1, 2);
        s0 *= (1.f / 512.f); s1 *= (1.f / 512.f);
        r0 = rcp(fmaxf(q0 * (1.f / 512.f) - s0 * s0, 0.f) + 1e-5f);
        r1 = rcp(fmaxf(q1 * (1.f / 512.f) - s1 * s1, 0.f) + 1e-5f);
        m0 = pack2(s0, s0); m1 = pack2(s1, s1);
      }
#define UOFF(u) ((((ST_GU + (u) / 3) % NSLOT) * SLOT + ((u) % 3) * 8192) >> 4)
#define UNIT_PRE(u)  do { if ((u) % 3 == 0) mbar_wait(sb + SM_FULL + (ST_GU + (u) / 3) * 8); } while (0)
#define UNIT_POST(u) do { wg_commit(); if ((u) % 3 == 1 && (u) > 3) { wg_wait<2>(); if (lead) release(ST_GU + (u) / 3 - 1); } } while (0)
      float acc[64];
      const int rz = blockIdx.y;
#pragma unroll
      for (int ps = 0; ps < 2; ps++) {
        wg_fence();
#pragma unroll
        for (int k = 0; k < 16; k++) {
          const int u = 16 * ps + k, c = k >> 1;
          if (ps == 0 && (k == 0 || k == 4 || k == 8)) {
#pragma unroll
            for (int p = (k == 0 ? 0 : (k == 4 ? 1 : 3)); p < (k == 0 ? 1 : (k == 4 ? 3 : 4)); p++) {
              if (p > 0) mbar_wait(sb + SM_XF + ((2 + wg) * 4 + p) * 8);
              get_pair(A[2 * p], A[2 * p + 1], xb + p * 1024, hp_ + p * 1024, T);
              if (lane == 0) {
                if (wg == 0) mbar_arrive(sb + SM_XE + (8 + p) * 8);
                else if (p > 0) release(ST_XC + p - 1);
              }
            }
          }
          if (ps == 0 && (k & 1) == 0) {
#pragma unroll
            for (int s = 0; s < 4; s++) {
              A[c][s][0] = hsub2(A[c][s][0], m0); A[c][s][1] = hsub2(A[c][s][1], m1);
              A[c][s][2] = hsub2(A[c][s][2], m0); A[c][s][3] = hsub2(A[c][s][3], m1);
            }
            wg_fence();
          }
          UNIT_PRE(u);
          wgmma_rs_n128(acc, A[c][(k & 1) * 2], dg + UOFF(u), k != 0 ? 1 : (ps ? rz : 0));
          wgmma_rs_n128(acc, A[c][(k & 1) * 2 + 1], dg + UOFF(u) + 128, 1);
          UNIT_POST(u);
        }
        wg_wait<0>();
#pragma unroll
        for (int s = 0; s < 4; s++) {
          uint32_t (&hh)[4] = HH[4 + s];
          hh[0] = tg(pack2(acc[8 * s + 0] * acc[32 + 8 * s + 0], acc[8 * s + 1] * acc[32 + 8 * s + 1]), T);
          hh[1] = pack2(acc[8 * s + 2] * acc[32 + 8 * s + 2], acc[8 * s + 3] * acc[32 + 8 * s + 3]);
          hh[2] = pack2(acc[8 * s + 4] * acc[32 + 8 * s + 4], acc[8 * s + 5] * acc[32 + 8 * s + 5]);
          hh[3] = pack2(acc[8 * s + 6] * acc[32 + 8 * s + 6], acc[8 * s + 7] * acc[32 + 8 * s + 7]);
          st_rlx4(hhp + (4 * ps + s) * 128, hh[0], hh[1], hh[2], hh[3]);
        }
      }
      {
        float ag[24], au[24];
        const uint32_t* ph7 = reinterpret_cast<const uint32_t*>(&g_hh[rh3][jf ^ 1][7][wq][31]);
        uint32_t hv = 0;
        bar_sync(1 + wg, 128);
        wg_fence();
#pragma unroll
        for (int k = 0; k < 16; k++) {
          const int u = 32 + k, c = k >> 1;
          if (k == 6) {
#pragma unroll
            for (int s = 0; s < 4; s++) ld_rlx4(HH[s], hhp + s * 128);
          }
          if (k == 9) hv = ld_rlx1(ph7);
          if (k == 12) {
            int it = 0;
#pragma unroll 1
            while (((hv ^ T) & 1) && ++it < (1 << 18)) hv = ld_rlx1(ph7);
#pragma unroll
            for (int s = 0; s < 8; s++) ld_rlx4(PH[s], pp + s * 128);
          }
          UNIT_PRE(u);
          wgmma_rs_n48(ag, A[c][(k & 1) * 2], dg + UOFF(u), k != 0);
          wgmma_rs_n48(au, A[c][(k & 1) * 2], dg + UOFF(u) + 256, k != 0);
          wgmma_rs_n48(ag, A[c][(k & 1) * 2 + 1], dg + UOFF(u) + 128, 1);
          wgmma_rs_n48(au, A[c][(k & 1) * 2 + 1], dg + UOFF(u) + 256 + 128, 1);
          UNIT_POST(u);
        }
        wg_wait<0>();
#pragma unroll
        for (int s = 0; s < 3; s++) {
          uint32_t (&hh)[4] = HH[8 + s];
          hh[0] = tg(pack2(ag[8 * s + 0] * au[8 * s + 0], ag[8 * s + 1] * au[8 * s + 1]), T);
          hh[1] = pack2(ag[8 * s + 2] * au[8 * s + 2], ag[8 * s + 3] * au[8 * s + 3]);
          hh[2] = pack2(ag[8 * s + 4] * au[8 * s + 4], ag[8 * s + 5] * au[8 * s + 5]);
          hh[3] = pack2(ag[8 * s + 6] * au[8 * s + 6], ag[8 * s + 7] * au[8 * s + 7]);
          st_rlx4(hhp + (8 + s) * 128, hh[0], hh[1], hh[2], hh[3]);
        }
      }
    }

    {
      float ac[3][32], acc[32];
      uint32_t hr[4][4];
      const int m = jf >> 1, oc = (jf & 1) * 4 + m;
      const uint32_t* ph10 = reinterpret_cast<const uint32_t*>(&g_hh[rh3][jf ^ 1][10][wq][31]);
      uint32_t hv = 0;
      bar_arrive(8 + wg, 256);
      wg_fence();
#pragma unroll
      for (int k = 0; k < 3; k++) {
        mbar_wait(sb + SM_FULL + (ST_D + k) * 8);
        if (k == 1) hv = ld_rlx1(ph10);
#pragma unroll
        for (int s = 0; s < 11; s++) {
          if (k == 2 && s == 4) {
            int it = 0;
#pragma unroll 1
            while (((hv ^ T) & 1) && ++it < (1 << 18)) hv = ld_rlx1(ph10);
#pragma unroll
            for (int i = 8; i < 11; i++) ld_rlx4(PH[i], pp + i * 128);
          }
          wgmma_rs_n64(ac[k], HH[s], DESC(((ST_D + k) % NSLOT) * SLOT + s * 2048), s != 0);
        }
      }
      wg_commit();
      {
        int it = 0;
#pragma unroll 1
        while (__any_sync(0xffffffffu, bad4(PH[0][0], PH[1][0], PH[2][0], PH[3][0], T) | bad4(PH[4][0], PH[5][0], PH[6][0], PH[7][0], T) |
                                       bad4(PH[8][0], PH[9][0], PH[10][0], T, T))) {
#pragma unroll
          for (int s = 0; s < 11; s++) ld_rlx4(PH[s], pp + s * 128);
          if (++it > (1 << 18)) break;
        }
      }
      uint4* outb = &g_part[rh3][(jf & 1) * 4][m][wq][0][lane];
#pragma unroll
      for (int k = 0; k < 4; k++) {
        mbar_wait(sb + SM_FULL + (ST_D + 3 + k) * 8);
        wg_fence();
#pragma unroll
        for (int s = 0; s < 11; s++) {
          if (k < 3) wgmma_rs_n64(ac[k], PH[s], DESC(((ST_D + 3 + k) % NSLOT) * SLOT + s * 2048), 1);
          else wgmma_rs_n64(acc, HH[s], DESC(((ST_D + 6) % NSLOT) * SLOT + s * 2048), s != 0);
          if (s == 6 && k > 0) {
            wg_commit();
            wg_wait<1>();
            if (k == 1) bar_arrive(12, 320);
            const float (&a)[32] = ac[k - 1];
            uint4* p = outb + ((m + k) & 3) * 2048;
#pragma unroll
            for (int i = 0; i < 4; i++)
              st_rlx4(p + i * 32, tg(pack2(a[8 * i + 0], a[8 * i + 1]), T), pack2(a[8 * i + 2], a[8 * i + 3]),
                      pack2(a[8 * i + 4], a[8 * i + 5]), pack2(a[8 * i + 6], a[8 * i + 7]));
          }
        }
        wg_commit();
      }
      ld_chunk(hr, &g_h[rh3][oc][wq][0][lane]);
      uint32_t hx = ld_rlx1(&g_hx[rh3][oc][wq][lane]);
      mbar_wait(sb + SM_FULL + (ST_D + 7) * 8);
      wg_fence();
#pragma unroll
      for (int s = 0; s < 11; s++) wgmma_rs_n64(acc, PH[s], DESC(((ST_D + 7) % NSLOT) * SLOT + s * 2048), 1);
      wg_commit();
      wg_wait<0>();
#pragma unroll 1
      for (int q = 0; q < 3; q++) {
        uint32_t in[4][4];
        const uint4* sp = reinterpret_cast<const uint4*>(smem + ((ST_D % NSLOT) + wg) * SLOT) + q * 512 + wq * 128 + lane;
        mbar_wait_p(sb + SM_XF + (wg * 4 + q) * 8, 1);
        int it = 0;
#pragma unroll 1
        do {
#pragma unroll
          for (int s = 0; s < 4; s++)
            asm volatile("{\n.reg .b128 v;\nld.relaxed.gpu.b128 v, [%4];\nmov.b128 {%0,%1,%2,%3}, v;\n}"
                         : "=r"(in[s][0]), "=r"(in[s][1]), "=r"(in[s][2]), "=r"(in[s][3]) : "l"(sp + s * 32) : "memory");
          sp = &g_part[rh3][oc][(m - 1 - q) & 3][wq][0][lane];
        } while (__any_sync(0xffffffffu, bad4(in[0][0], in[1][0], in[2][0], in[3][0], T)) && ++it < (1 << 18));
        add_frag(acc, in, IDF);
      }
      {
        int it = 0;
#pragma unroll 1
        while (__any_sync(0xffffffffu, (hx ^ T) & 1) && ++it < (1 << 18)) hx = ld_rlx1(&g_hx[rh3][oc][wq][lane]);
      }
#pragma unroll
      for (int s = 0; s < 4; s++) hr[s][0] = (hr[s][0] & 0xFFFFFFFEu) | ((hx >> (s + 1)) & 1u);
#pragma unroll
      for (int i = 0; i < 32; i++) acc[i] *= (i & 2) ? r1 : r0;
      add_frag(acc, hr, IDF);
      bar_sync(9 - wg, 256);
      const uint32_t ob = sb + ((ST_D - 1) % NSLOT) * SLOT + wg * 8192;
#pragma unroll
      for (int s = 0; s < 4; s++)
        stsm4(ob + lrow + (((2 * s + lhi) ^ lx) << 4), pack2(acc[8 * s + 0], acc[8 * s + 1]), pack2(acc[8 * s + 2], acc[8 * s + 3]),
              pack2(acc[8 * s + 4], acc[8 * s + 5]), pack2(acc[8 * s + 6], acc[8 * s + 7]));
      __syncwarp();
      {
        const int row = wq * 16 + (lane >> 3);
        __nv_bfloat16* op = out + (size_t)(rh3 * 64 + row) * 512 + oc * 64 + lx * 8;
#pragma unroll
        for (int i = 0; i < 4; i++) {
          uint4 v;
          asm volatile("ld.shared.v4.b32 {%0,%1,%2,%3}, [%4];" : "=r"(v.x), "=r"(v.y), "=r"(v.z), "=r"(v.w)
                       : "r"(ob + (row + i * 4) * 128 + ((lx ^ (((lane >> 3) + i * 4) & 7)) << 4)) : "memory");
          asm volatile("st.global.v4.b32 [%0], {%1,%2,%3,%4};" ::"l"(op + i * 2048), "r"(v.x), "r"(v.y), "r"(v.z), "r"(v.w) : "memory");
        }
      }
    }
    asm volatile("barrier.cluster.arrive.relaxed.aligned;" ::: "memory");
    asm volatile("barrier.cluster.wait.aligned;" ::: "memory");
  } else {
    asm volatile("setmaxnreg.dec.sync.aligned.u32 24;");
    if (elect_one()) {
      if (warp == 8) {
#pragma unroll
        for (int k = 0; k < 9; k++) {
          const int s = k < 3 ? k : (k < 6 ? k + 3 : k - 3);
          const uint32_t bar = sb + SM_FULL + s * 8;
          mbar_init(bar, 1);
          mbar_expect_tx(bar, SLOT);
          if (s >= 3 && s < 6) tma2d(sb + s * SLOT, &maps.w, 512 + hg * 64, (s - 3) * 192, bar);
          else tma3d(sb + s * SLOT, &maps.x, 0, rb * 128 + (s >= 6 ? 64 : 0), 3 * (s % 3), bar);
        }
      } else if (warp == 9) {
        mbar_init(sb + SM_MISCB, 2);
        mbar_init(sb + SM_KVB, 1);
        mbar_expect_tx(sb + SM_KVB, 8704);
        mbar_expect_tx(sb + SM_MISCB, 2048);
        bulk_g2s(sb + SM_WPHI, wphi + hg * 1024, 2048, sb + SM_MISCB);
      } else if (warp == 10) {
        if ((sb & 0x3FFFF) != SM_BASE) __trap();
#pragma unroll 1
        for (int i = 0; i < 16; i++) {
          mbar_init(sb + SM_XF + i * 8, 1);
          mbar_expect_tx(sb + SM_XF + i * 8, (i == 8 || i == 12) ? 20480 : 16384);
          if (i < 12) mbar_init(sb + SM_XE + i * 8, 4);
        }
      } else {
        *reinterpret_cast<volatile unsigned*>(smem + SM_EPOCH) = atomicAdd(&g_start, 1u) / NCTA;
      }
      asm volatile("fence.mbarrier_init.release.cluster;" ::: "memory");
    }
    __syncwarp();
    if (warp != 11) bar_sync(0, 352);
    asm volatile("barrier.cluster.arrive.relaxed.aligned;" ::: "memory");
    if (warp == 8) {
      asm volatile("barrier.cluster.wait.aligned;" ::: "memory");
      if (elect_one()) {
        const CUtensorMap* mg = jf == 7 ? &maps.g7 : &maps.g;
        const CUtensorMap* mu = jf == 7 ? &maps.u7 : &maps.u;
        asm volatile("prefetch.tensormap [%0];" ::"l"(&maps.wo) : "memory");
        asm volatile("prefetch.tensormap [%0];" ::"l"(mg) : "memory");
        asm volatile("prefetch.tensormap [%0];" ::"l"(mu) : "memory");
        asm volatile("prefetch.tensormap [%0];" ::"l"(&maps.d) : "memory");
#pragma unroll 1
        for (int s = ST_WV; s < ST_XC; s++) {
          if (s == ST_SCR1) continue;
          mbar_wait(sb + SM_EMPTY + (s - 9) * 8);
          const uint32_t dst = sb + (s >= 18 ? s - 18 : s - 9) * SLOT, bar = sb + SM_FULL + s * 8;
          if (s < ST_WO) tma2d(dst, &maps.w, (s < ST_WQ ? 1024 : 0) + hg * 64, (s < ST_WQ ? s - ST_WV : s - ST_WQ) * 192, bar);
          else { mbar_wait(bar - 8); tma2d(dst, &maps.wo, hg * 64, (s - ST_WO) * 192, bar); }
        }
        const int jc = jf == 7 ? 0 : jf;
        int slot = (ST_GU + 1 - rank) % NSLOT;
#pragma unroll 1
        for (int s = ST_GU + 1 - rank; s < NSTAGE; s += 2) {
          mbar_wait(sb + SM_EMPTY + (s - 9) * 8);
          if (s > ST_GU && s < ST_GU + 6) mbar_wait(sb + SM_FULL + (s - 1) * 8);
          const uint32_t dst = sb + slot * SLOT, bar = sb + SM_FULL + s * 8;
          if (s < ST_D) {
#pragma unroll 1
            for (int i = 0; i < 3; i++) {
              const int u = (s - ST_GU) * 3 + i;
              tma3d_mc(dst + i * 8192, mg, (u >> 4) * 64, jc, (u & 15) * 32, bar);
              tma3d_mc(dst + i * 8192 + 4096, mu, (u >> 4) * 64, jc, (u & 15) * 32, bar);
            }
          } else {
            const int i = s - ST_D, k = i < 3 ? i : (i < 6 ? i - 3 : 3), pt = (i >= 3 && i != 6) ? 1 : 0;
            tma2d_mc(dst, &maps.d, ((jf & 1) * 4 + (((jf >> 1) + 1 + k) & 3)) * 64, (jf ^ pt) * 176, bar);
          }
          slot += 2; if (slot >= NSLOT) slot -= NSLOT;
        }
      }
      __syncwarp();
    } else {
      asm volatile("barrier.cluster.wait.aligned;" ::: "memory");
      if (warp == 11) {
#pragma unroll
        for (int i = 0; i < 4; i++)
          reinterpret_cast<uint4*>(smem + SM_ONES)[lane + 32 * i] = make_uint4(0x3F803F80u, 0x3F803F80u, 0x3F803F80u, 0x3F803F80u);
        fence_async_smem();
        __syncwarp();
        if (lane == 0) mbar_arrive(sb + SM_MISCB);
      }
      mbar_wait(sb + SM_MISCB);
      const unsigned epoch = *reinterpret_cast<volatile unsigned*>(smem + SM_EPOCH);
      const uint32_t T = (epoch & 1) ^ 1;
      if (warp == 11) {
        reinterpret_cast<float4*>(&g_kv[hg][rb * 136])[lane] = make_float4(0.f, 0.f, 0.f, 0.f);
        if (lane < 2) reinterpret_cast<float4*>(&g_kv[hg][rb * 136])[32 + lane] = make_float4(0.f, 0.f, 0.f, 0.f);
        __syncwarp();
        if (elect_one()) asm volatile("red.release.gpu.global.add.u32 [%0], 8;" ::"l"(&g_kvcnt[hg * 32 + 1]) : "memory");
        mbar_wait(sb + SM_FULL + (ST_WK + 2) * 8);
        if (elect_one()) {
          asm volatile("cp.async.bulk.prefetch.L2.global [%0], 4096;" ::"l"((const char*)wo + blockIdx.x * 4096) : "memory");
          asm volatile("cp.async.bulk.prefetch.L2.global [%0], 11008;" ::"l"((const char*)wg_ + blockIdx.x * 11008) : "memory");
          asm volatile("cp.async.bulk.prefetch.L2.global [%0], 11008;" ::"l"((const char*)wu_ + blockIdx.x * 11008) : "memory");
          asm volatile("cp.async.bulk.prefetch.L2.global [%0], 11008;" ::"l"((const char*)wd_ + blockIdx.x * 11008) : "memory");
          mbar_wait(sb + SM_EMPTY + ST_SCR0 * 8);
          const unsigned target = (epoch + 1) * 128;
          unsigned v; int it = 0;
#pragma unroll 1
          do {
            asm volatile("ld.acquire.gpu.global.u32 %0, [%1];" : "=r"(v) : "l"(&g_kvcnt[hg * 32]) : "memory");
            if (++it > (1 << 18)) break;
          } while ((int)(v - target) < 0);
          asm volatile("fence.proxy.async.global;" ::: "memory");
          bulk_g2s(sb + SM_KV32, &g_kv[hg][0], 8192, sb + SM_KVB);
          bulk_g2s(sb + SM_ONES, &g_kv[hg][2048], 512, sb + SM_KVB);
        }
        __syncwarp();
      } else {
        const int w = warp - 9;
        st_rlx4(reinterpret_cast<uint4*>(&g_st[2 * rb + w][hg][0]) + lane, T ^ 1, T ^ 1, T ^ 1, T ^ 1);
        if (lane < 8) st_rlx4(&g_o[2 * rb + w][hg][lane >> 1][3][30 + (lane & 1)], T ^ 1, T ^ 1, T ^ 1, T ^ 1);
        st_rlx4(&g_part[2 * rb3 + w][(jf & 1) * 4 + (lane >> 3)][jf >> 1][(lane >> 1) & 3][3][30 + (lane & 1)], T ^ 1, T ^ 1, T ^ 1, T ^ 1);
        if (lane < 16) st_rlx4(&g_hh[2 * rb3 + w][jf][7 + (lane >> 3) * 3][(lane >> 1) & 3][30 + (lane & 1)], T ^ 1, T ^ 1, T ^ 1, T ^ 1);
        if (w == 0) {
          mbar_wait(sb + SM_FULL + (ST_WQ + 2) * 8);
          unsigned v; int it = 0;
#pragma unroll 1
          do {
            asm volatile("ld.acquire.gpu.global.u32 %0, [%1];" : "=r"(v) : "l"(&g_kvcnt[hg * 32 + 1]) : "memory");
          } while ((int)(v - (epoch + 1) * 128) < 0 && ++it < (1 << 18));
          asm volatile("fence.proxy.async.global;" ::: "memory");
        }
        bar_sync(6, 320);
        if (w == 0 && elect_one()) {
          asm volatile("cp.reduce.async.bulk.global.shared::cta.bulk_group.add.f32 [%0], [%1], 8704;"
                       ::"l"(&g_kv[hg][0]), "r"(sb + 2 * SLOT) : "memory");
          asm volatile("cp.async.bulk.commit_group;" ::: "memory");
          asm volatile("cp.async.bulk.wait_group 0;" ::: "memory");
          asm volatile("red.release.gpu.global.add.u32 [%0], 8;" ::"l"(&g_kvcnt[hg * 32]) : "memory");
        }
        __syncwarp();
        mbar_wait(sb + SM_KVB);
        if (w == 0) { mbar_wait(sb + SM_EMPTY + 11 * 8); mbar_wait(sb + SM_EMPTY + 12 * 8); mbar_wait(sb + SM_EMPTY + 13 * 8); }
#pragma unroll 1
        for (int ph = 0; ph < 2; ph++) {
          const int use = 2 * ph + w, r = ph ? 2 * rb3 + w : 2 * rb + w;
          const uint32_t* pw = ph ? reinterpret_cast<const uint32_t*>(&g_st[r][lane >> 2][(lane & 3) * 16 + 15])
                                  : reinterpret_cast<const uint32_t*>(&g_o[r][lane >> 2][lane & 3][3][31]);
          const char* src = reinterpret_cast<const char*>(ph ? &g_h[r][0][0][0][0] : &g_o[r][0][0][0][0]);
          const uint32_t bf = sb + SM_XF + use * 32, be = sb + SM_XE + (use - 1) * 32;
          bar_sync(10 + w, 160);
          int it = 0;
#pragma unroll 1
          for (bool miss = true; __any_sync(0xffffffffu, miss) && ++it < (1 << 18);) { if (miss) miss = (ld_rlx1(pw) ^ T) & 1; }
          if (elect_one()) {
            if (use > 0) mbar_wait(be);
            if (ph) bulk_g2s(sb + SM_KV32 + w * 4096, &g_st[r][0][0], 4096, bf);
#pragma unroll
            for (int p = 0; p < 4; p++) {
              if (p > 0 && use > 0) mbar_wait(be + p * 8);
              bulk_g2s(sb + 2 * SLOT + p * 16384, src + p * 16384, 16384, bf + p * 8);
            }
          }
          __syncwarp();
        }
        {
          const int m = jf >> 1, oc = (jf & 1) * 4 + m;
          const uint32_t* pw = reinterpret_cast<const uint32_t*>(&g_part[2 * rb3 + w][oc][(m - 1 - (lane >> 2)) & 3][lane & 3][3][31]);
          bar_sync(12, 320);
          bool miss = lane < 12; int it = 0;
#pragma unroll 1
          for (int q = 0; q < 3; q++) {
#pragma unroll 1
            while ((__ballot_sync(0xffffffffu, miss) >> (4 * q) & 15) && ++it < (1 << 18)) { if (miss && (lane >> 2) <= q + 1) miss = (ld_rlx1(pw) ^ T) & 1; }
            if (elect_one()) {
              const uint32_t bar = sb + SM_XF + (w * 4 + q) * 8;
              mbar_expect_tx(bar, 8192);
              bulk_g2s(sb + ((ST_D % NSLOT) + w) * SLOT + q * 8192, &g_part[2 * rb3 + w][oc][(m - 1 - q) & 3][0][0][0], 8192, bar);
            }
            __syncwarp();
          }
        }
      }
    }
    asm volatile("barrier.cluster.arrive.relaxed.aligned;" ::: "memory");
    asm volatile("barrier.cluster.wait.aligned;" ::: "memory");
  }
}

typedef CUresult (*EncodeFn)(CUtensorMap*, CUtensorMapDataType, cuuint32_t, void*, const cuuint64_t*, const cuuint64_t*,
                             const cuuint32_t*, const cuuint32_t*, CUtensorMapInterleave, CUtensorMapSwizzle,
                             CUtensorMapL2promotion, CUtensorMapFloatOOBfill);

void encode(EncodeFn fn, CUtensorMap* m, const void* base, int rank, const cuuint64_t* dims, const cuuint64_t* strides,
            const cuuint32_t* box) {
  cuuint32_t es[3] = {1, 1, 1};
  fn(m, CU_TENSOR_MAP_DATA_TYPE_BFLOAT16, (cuuint32_t)rank, const_cast<void*>(base), dims, strides, box, es,
     CU_TENSOR_MAP_INTERLEAVE_NONE, CU_TENSOR_MAP_SWIZZLE_128B, CU_TENSOR_MAP_L2_PROMOTION_L2_256B,
     CU_TENSOR_MAP_FLOAT_OOB_FILL_NONE);
}

}

extern "C" void kernel_launch(void* const* d_in, const int* in_sizes, int n_in, void* d_out, int out_size) {
  (void)in_sizes; (void)n_in; (void)out_size;
  const __nv_bfloat16* x    = (const __nv_bfloat16*)d_in[0];
  const __nv_bfloat16* wqkv = (const __nv_bfloat16*)d_in[1];
  const __nv_bfloat16* wphi = (const __nv_bfloat16*)d_in[2];
  const __nv_bfloat16* wo   = (const __nv_bfloat16*)d_in[3];
  const __nv_bfloat16* wg   = (const __nv_bfloat16*)d_in[5];
  const __nv_bfloat16* wu   = (const __nv_bfloat16*)d_in[6];
  const __nv_bfloat16* wd   = (const __nv_bfloat16*)d_in[7];

  static EncodeFn fn = nullptr;
  if (!fn) {
    void* p = nullptr;
    cudaDriverEntryPointQueryResult qr;
    cudaGetDriverEntryPoint("cuTensorMapEncodeTiled", &p, cudaEnableDefault, &qr);
    fn = (EncodeFn)p;
    cudaFuncSetAttribute(fused_kernel, cudaFuncAttributeMaxDynamicSharedMemorySize, SM_TOTAL);
  }
  Maps maps;
  {
    cuuint64_t d[3] = {64, 2048, 8}, s[2] = {1024, 128}; cuuint32_t b[3] = {64, 64, 3};
    encode(fn, &maps.x, x, 3, d, s, b);
  }
  {
    cuuint64_t d[2] = {1536, 512}, s[1] = {3072}; cuuint32_t b[2] = {64, 192};
    encode(fn, &maps.w, wqkv, 2, d, s, b);
  }
  {
    cuuint64_t d[2] = {512, 512}, s[1] = {1024}; cuuint32_t b[2] = {64, 192};
    encode(fn, &maps.wo, wo, 2, d, s, b);
  }
  {
    cuuint64_t d[3] = {176, 7, 512}, d7[3] = {144, 1, 512}, s[2] = {352, 2752}; cuuint32_t b[3] = {64, 1, 32};
    encode(fn, &maps.g, wg, 3, d, s, b);
    encode(fn, &maps.u, wu, 3, d, s, b);
    encode(fn, &maps.g7, wg + 1232, 3, d7, s, b);
    encode(fn, &maps.u7, wu + 1232, 3, d7, s, b);
  }
  {
    cuuint64_t d[2] = {512, 1376}, s[1] = {1024}; cuuint32_t b[2] = {64, 176};
    encode(fn, &maps.d, wd, 2, d, s, b);
  }
  fused_kernel<<<NCTA, 384, SM_TOTAL>>>(maps, x, wphi, wo, wg, wu, wd, (__nv_bfloat16*)d_out);
}
```

```cpp
#include <cuda_runtime.h>
#include <cuda_bf16.h>
#include <cuda.h>
#include <stdint.h>

#define SAFE_WAIT 0

namespace {

constexpr int NCTA   = 128;
constexpr int SLOT   = 24576;
constexpr int NSLOT  = 9;
constexpr int NSTAGE = 47;

constexpr int ST_X0   = 0;
constexpr int ST_WK   = 3;
constexpr int ST_X1   = 6;
constexpr int ST_SCR0 = 9;
constexpr int ST_WV   = 10;
constexpr int ST_SCR1 = 13;
constexpr int ST_WQ   = 14;
constexpr int ST_WO   = 17;
constexpr int ST_XC   = 20;
constexpr int ST_GU   = 23;
constexpr int ST_D    = 39;

__host__ __device__ constexpr int st_empty_cnt(int d) {
  return ((d < 3 || (d >= 6 && d < 9) || (d >= ST_XC && d < ST_GU)) ? 4 : 2) * (d + 9 >= ST_GU ? 2 : 1);
}

constexpr uint32_t SM_BASE = 1024;
constexpr int SM_ONES = NSLOT * SLOT;
constexpr int SM_WPHI = SM_ONES + 2048;
constexpr int SM_KVS  = SM_WPHI + 2048;
constexpr int SM_KV32 = 4 * SLOT + 16384;
constexpr int SM_BAR  = SM_KVS + 6144;
constexpr int SM_FULL  = SM_BAR;
constexpr int SM_EMPTY = SM_BAR + NSTAGE * 8;
constexpr int SM_MISCB = SM_BAR + 2 * NSTAGE * 8;
constexpr int SM_KVB   = SM_MISCB + 8;
constexpr int SM_EPOCH = SM_KVB + 8;
constexpr int SM_XF    = SM_EPOCH + 8;
constexpr int SM_XE    = SM_XF + 16 * 8;
constexpr int SM_TOTAL = SM_BAR + 1024;

static_assert(SM_TOTAL == 232448 && SM_XE + 12 * 8 <= SM_TOTAL, "smem budget");

struct Maps { CUtensorMap x, w, wo, g, u, g7, u7, d; };

__device__ __align__(128) uint4    g_o[32][8][4][4][32];
__device__ __align__(128) uint4    g_h[32][8][4][4][32];
__device__ __align__(128) uint32_t g_hx[32][8][4][32];
__device__ __align__(128) uint2    g_st[32][8][64];
__device__ __align__(128) uint4    g_hh[32][8][11][4][32];
__device__ __align__(128) uint4    g_part[32][8][4][4][4][32];
__device__ __align__(128) float g_kv[8][2048 + 128];
__device__ __align__(128) unsigned g_kvcnt[8 * 32];
__device__ unsigned g_start;

__device__ __forceinline__ uint32_t smem_u32(const void* p) { return (uint32_t)__cvta_generic_to_shared(p); }
__device__ __forceinline__ void mbar_init(uint32_t bar, int cnt) {
  asm volatile("mbarrier.init.shared::cta.b64 [%0], %1;" ::"r"(bar), "r"(cnt) : "memory");
}
__device__ __forceinline__ void mbar_expect_tx(uint32_t bar, uint32_t bytes) {
  asm volatile("mbarrier.arrive.expect_tx.shared::cta.b64 _, [%0], %1;" ::"r"(bar), "r"(bytes) : "memory");
}
__device__ __forceinline__ void mbar_arrive(uint32_t bar) {
  asm volatile("mbarrier.arrive.shared::cta.b64 _, [%0];" ::"r"(bar) : "memory");
}
__device__ __forceinline__ void mbar_arrive_cluster(uint32_t bar, uint32_t rank) {
  asm volatile("{\n.reg .b32 ra;\nmapa.shared::cluster.u32 ra, %0, %1;\n"
               "mbarrier.arrive.shared::cluster.b64 _, [ra];\n}" ::"r"(bar), "r"(rank) : "memory");
}
__device__ __forceinline__ void mbar_wait_p(uint32_t bar, uint32_t parity) {
  asm volatile("{\n.reg .pred p;\nW: mbarrier.try_wait.parity.shared::cta.b64 p, [%0], %1;\n@!p bra W;\n}" ::"r"(bar), "r"(parity) : "memory");
}
__device__ __forceinline__ void mbar_wait(uint32_t bar) { mbar_wait_p(bar, 0); }
__device__ __forceinline__ bool elect_one() {
  uint32_t p;
  asm volatile("{\n.reg .pred P;\nelect.sync _|P, 0xffffffff;\nselp.u32 %0, 1, 0, P;\n}" : "=r"(p));
  return p != 0;
}
__device__ __forceinline__ void bar_sync(int id, int n)   { asm volatile("bar.sync %0, %1;" ::"r"(id), "r"(n) : "memory"); }
__device__ __forceinline__ void bar_arrive(int id, int n) { asm volatile("bar.arrive %0, %1;" ::"r"(id), "r"(n) : "memory"); }
__device__ __forceinline__ void fence_async_smem() { asm volatile("fence.proxy.async.shared::cta;" ::: "memory"); }
__device__ __forceinline__ void wg_fence()  { asm volatile("wgmma.fence.sync.aligned;" ::: "memory"); }
__device__ __forceinline__ void wg_commit() { asm volatile("wgmma.commit_group.sync.aligned;" ::: "memory"); }
template <int N> __device__ __forceinline__ void wg_wait() { asm volatile("wgmma.wait_group.sync.aligned %0;" ::"n"(N) : "memory"); }
#define DESC(off) (db + ((uint32_t)(off) >> 4))
__device__ __forceinline__ void tma2d(uint32_t dst, const CUtensorMap* m, int c0, int c1, uint32_t bar) {
  asm volatile("cp.async.bulk.tensor.2d.shared::cluster.global.mbarrier::complete_tx::bytes [%0], [%1, {%3, %4}], [%2];"
               ::"r"(dst), "l"(m), "r"(bar), "r"(c0), "r"(c1) : "memory");
}
__device__ __forceinline__ void tma2d_mc(uint32_t dst, const CUtensorMap* m, int c0, int c1, uint32_t bar) {
  asm volatile("cp.async.bulk.tensor.2d.shared::cluster.global.mbarrier::complete_tx::bytes.multicast::cluster [%0], [%1, {%3, %4}], [%2], %5;"
               ::"r"(dst), "l"(m), "r"(bar), "r"(c0), "r"(c1), "h"((uint16_t)3) : "memory");
}
__device__ __forceinline__ void tma3d(uint32_t dst, const CUtensorMap* m, int c0, int c1, int c2, uint32_t bar) {
  asm volatile("cp.async.bulk.tensor.3d.shared::cluster.global.mbarrier::complete_tx::bytes [%0], [%1, {%3, %4, %5}], [%2];"
               ::"r"(dst), "l"(m), "r"(bar), "r"(c0), "r"(c1), "r"(c2) : "memory");
}
__device__ __forceinline__ void tma3d_mc(uint32_t dst, const CUtensorMap* m, int c0, int c1, int c2, uint32_t bar) {
  asm volatile("cp.async.bulk.tensor.3d.shared::cluster.global.mbarrier::complete_tx::bytes.multicast::cluster [%0], [%1, {%3, %4, %5}], [%2], %6;"
               ::"r"(dst), "l"(m), "r"(bar), "r"(c0), "r"(c1), "r"(c2), "h"((uint16_t)3) : "memory");
}
__device__ __forceinline__ void ldsm4(uint32_t (&r)[4], uint32_t addr) {
  asm volatile("ldmatrix.sync.aligned.m8n8.x4.shared.b16 {%0,%1,%2,%3}, [%4];"
               : "=r"(r[0]), "=r"(r[1]), "=r"(r[2]), "=r"(r[3]) : "r"(addr) : "memory");
}
__device__ __forceinline__ void ldsm4t(uint32_t (&r)[4], uint32_t addr) {
  asm volatile("ldmatrix.sync.aligned.m8n8.x4.trans.shared.b16 {%0,%1,%2,%3}, [%4];"
               : "=r"(r[0]), "=r"(r[1]), "=r"(r[2]), "=r"(r[3]) : "r"(addr) : "memory");
}
__device__ __forceinline__ void stsm4(uint32_t addr, uint32_t r0, uint32_t r1, uint32_t r2, uint32_t r3) {
  asm volatile("stmatrix.sync.aligned.m8n8.x4.shared.b16 [%0], {%1,%2,%3,%4};"
               ::"r"(addr), "r"(r0), "r"(r1), "r"(r2), "r"(r3) : "memory");
}
__device__ __forceinline__ void mma16816(float (&c)[4], const uint32_t (&a)[4], uint32_t b0, uint32_t b1) {
  asm volatile("mma.sync.aligned.m16n8k16.row.col.f32.bf16.bf16.f32 {%0,%1,%2,%3},{%4,%5,%6,%7},{%8,%9},{%0,%1,%2,%3};"
               : "+f"(c[0]), "+f"(c[1]), "+f"(c[2]), "+f"(c[3])
               : "r"(a[0]), "r"(a[1]), "r"(a[2]), "r"(a[3]), "r"(b0), "r"(b1));
}
__device__ __forceinline__ void add_frag(float (&c)[32], const uint32_t (&a)[4][4], uint32_t id) {
#pragma unroll
  for (int i = 0; i < 8; i++)
    asm volatile("mma.sync.aligned.m16n8k8.row.col.f32.bf16.bf16.f32 {%0,%1,%2,%3},{%4,%5},{%6},{%0,%1,%2,%3};"
                 : "+f"(c[4 * i]), "+f"(c[4 * i + 1]), "+f"(c[4 * i + 2]), "+f"(c[4 * i + 3])
                 : "r"(a[i >> 1][(i & 1) * 2]), "r"(a[i >> 1][(i & 1) * 2 + 1]), "r"(id));
}
__device__ __forceinline__ uint32_t pack2(float lo, float hi) {
  uint32_t r; asm("cvt.rn.bf16x2.f32 %0, %1, %2;" : "=r"(r) : "f"(hi), "f"(lo)); return r;
}
__device__ __forceinline__ float blo(uint32_t w) { return __uint_as_float(w << 16); }
__device__ __forceinline__ float bhi(uint32_t w) { return __uint_as_float(w & 0xFFFF0000u); }
__device__ __forceinline__ uint32_t hsub2(uint32_t a, uint32_t b) { uint32_t r; asm("sub.rn.bf16x2 %0, %1, %2;" : "=r"(r) : "r"(a), "r"(b)); return r; }
__device__ __forceinline__ uint32_t hmax2(uint32_t a, uint32_t b) { uint32_t r; asm("max.bf16x2 %0, %1, %2;" : "=r"(r) : "r"(a), "r"(b)); return r; }
__device__ __forceinline__ uint32_t hmin2(uint32_t a, uint32_t b) { uint32_t r; asm("min.bf16x2 %0, %1, %2;" : "=r"(r) : "r"(a), "r"(b)); return r; }
__device__ __forceinline__ float ex2(float x) { float r; asm("ex2.approx.ftz.f32 %0, %1;" : "=f"(r) : "f"(x)); return r; }
__device__ __forceinline__ float rcp(float x) { float r; asm("rcp.approx.ftz.f32 %0, %1;" : "=f"(r) : "f"(x)); return r; }
__device__ __forceinline__ void ld_rlx4(uint32_t (&r)[4], const uint4* p) {
  asm volatile("{\n.reg .b128 v;\nld.relaxed.gpu.global.b128 v, [%4];\nmov.b128 {%0,%1,%2,%3}, v;\n}"
               : "=r"(r[0]), "=r"(r[1]), "=r"(r[2]), "=r"(r[3]) : "l"(p) : "memory");
}
__device__ __forceinline__ void st_rlx4(uint4* p, uint32_t a, uint32_t b, uint32_t c, uint32_t d) {
  asm volatile("st.relaxed.gpu.global.v4.b32 [%0], {%1,%2,%3,%4};" ::"l"(p), "r"(a), "r"(b), "r"(c), "r"(d) : "memory");
}
__device__ __forceinline__ void st_rlx2(uint2* p, uint32_t a, uint32_t b) {
  asm volatile("{\n.reg .b64 v;\nmov.b64 v, {%1,%2};\nst.relaxed.gpu.global.b64 [%0], v;\n}" ::"l"(p), "r"(a), "r"(b) : "memory");
}
__device__ __forceinline__ uint32_t ld_rlx1(const uint32_t* p) {
  uint32_t r; asm volatile("ld.relaxed.gpu.global.b32 %0, [%1];" : "=r"(r) : "l"(p) : "memory"); return r;
}
__device__ __forceinline__ void st_rlx1(uint32_t* p, uint32_t a) {
  asm volatile("st.relaxed.gpu.global.b32 [%0], %1;" ::"l"(p), "r"(a) : "memory");
}
__device__ __forceinline__ void ld_rlx2(uint32_t& a, uint32_t& b, const uint2* p) {
  asm volatile("{\n.reg .b64 v;\nld.relaxed.gpu.b64 v, [%2];\nmov.b64 {%0,%1}, v;\n}" : "=r"(a), "=r"(b) : "l"(p) : "memory");
}
__device__ __forceinline__ void bulk_g2s(uint32_t dst, const void* src, uint32_t bytes, uint32_t bar) {
  asm volatile("cp.async.bulk.shared::cluster.global.mbarrier::complete_tx::bytes [%0], [%1], %2, [%3];"
               ::"r"(dst), "l"(src), "r"(bytes), "r"(bar) : "memory");
}
__device__ __forceinline__ uint32_t tg(uint32_t w, uint32_t T) { return (w & 0xFFFFFFFEu) | T; }
__device__ __forceinline__ uint32_t bad4(uint32_t a, uint32_t b, uint32_t c, uint32_t d, uint32_t T) {
  uint32_t u, v;
  asm("lop3.b32 %0, %1, %2, %3, 0x7E;" : "=r"(u) : "r"(a), "r"(b), "r"(T));
  asm("lop3.b32 %0, %1, %2, %3, 0x7E;" : "=r"(v) : "r"(c), "r"(d), "r"(T));
  asm("lop3.b32 %0, %1, %2, 1, 0xA8;" : "=r"(u) : "r"(u), "r"(v));
  return u;
}

__device__ __forceinline__ void ld_chunk(uint32_t (&a)[4][4], const uint4* p) {
#pragma unroll
  for (int s = 0; s < 4; s++) ld_rlx4(a[s], p + s * 32);
}
__device__ __forceinline__ void get_pair(uint32_t (&a)[4][4], uint32_t (&b)[4][4], const uint4* sp, const uint4* gp, uint32_t T) {
  int it = 0;
#pragma unroll 1
  do {
#pragma unroll
    for (int s = 0; s < 8; s++) {
      uint32_t (&r)[4] = s < 4 ? a[s & 3] : b[s & 3];
      asm volatile("{\n.reg .b128 v;\nld.relaxed.gpu.b128 v, [%4];\nmov.b128 {%0,%1,%2,%3}, v;\n}"
                   : "=r"(r[0]), "=r"(r[1]), "=r"(r[2]), "=r"(r[3]) : "l"(sp + (s >> 2) * 512 + (s & 3) * 32) : "memory");
    }
    sp = gp;
  } while (__any_sync(0xffffffffu, bad4(a[0][0], a[1][0], a[2][0], a[3][0], T) | bad4(b[0][0], b[1][0], b[2][0], b[3][0], T)) && ++it < (1 << 18));
}

__device__ __forceinline__ void wgmma_rs_n48(float (&d)[24], const uint32_t (&a)[4], uint32_t descB, int scaleD) {
  asm volatile("{\n.reg .pred p;\n.reg .b64 db;\nsetp.ne.b32 p, %29, 0;\nmov.b64 db, {%28, 0x40000040};\n"
    "wgmma.mma_async.sync.aligned.m64n48k16.f32.bf16.bf16 {%0,%1,%2,%3,%4,%5,%6,%7,%8,%9,%10,%11,%12,%13,%14,%15,%16,%17,%18,%19,%20,%21,%22,%23}, {%24,%25,%26,%27}, db, p, 1, 1, 1;\n}\n"
    : "+f"(d[0]),"+f"(d[1]),"+f"(d[2]),"+f"(d[3]),"+f"(d[4]),"+f"(d[5]),"+f"(d[6]),"+f"(d[7]),"+f"(d[8]),"+f"(d[9]),"+f"(d[10]),"+f"(d[11]),"+f"(d[12]),"+f"(d[13]),"+f"(d[14]),"+f"(d[15]),"+f"(d[16]),"+f"(d[17]),"+f"(d[18]),"+f"(d[19]),"+f"(d[20]),"+f"(d[21]),"+f"(d[22]),"+f"(d[23])
    : "r"(a[0]), "r"(a[1]), "r"(a[2]), "r"(a[3]), "r"(descB), "r"(scaleD));
}
__device__ __forceinline__ void wgmma_rs_n64(float (&d)[32], const uint32_t (&a)[4], uint32_t descB, int scaleD) {
  asm volatile("{\n.reg .pred p;\n.reg .b64 db;\nsetp.ne.b32 p, %37, 0;\nmov.b64 db, {%36, 0x40000040};\n"
    "wgmma.mma_async.sync.aligned.m64n64k16.f32.bf16.bf16 {%0,%1,%2,%3,%4,%5,%6,%7,%8,%9,%10,%11,%12,%13,%14,%15,%16,%17,%18,%19,%20,%21,%22,%23,%24,%25,%26,%27,%28,%29,%30,%31}, {%32,%33,%34,%35}, db, p, 1, 1, 1;\n}\n"
    : "+f"(d[0]),"+f"(d[1]),"+f"(d[2]),"+f"(d[3]),"+f"(d[4]),"+f"(d[5]),"+f"(d[6]),"+f"(d[7]),"+f"(d[8]),"+f"(d[9]),"+f"(d[10]),"+f"(d[11]),"+f"(d[12]),"+f"(d[13]),"+f"(d[14]),"+f"(d[15]),"+f"(d[16]),"+f"(d[17]),"+f"(d[18]),"+f"(d[19]),"+f"(d[20]),"+f"(d[21]),"+f"(d[22]),"+f"(d[23]),"+f"(d[24]),"+f"(d[25]),"+f"(d[26]),"+f"(d[27]),"+f"(d[28]),"+f"(d[29]),"+f"(d[30]),"+f"(d[31])
    : "r"(a[0]), "r"(a[1]), "r"(a[2]), "r"(a[3]), "r"(descB), "r"(scaleD));
}
__device__ __forceinline__ void wgmma_rs_n128(float (&d)[64], const uint32_t (&a)[4], uint32_t descB, int scaleD) {
  asm volatile("{\n.reg .pred p;\n.reg .b64 db;\nsetp.ne.b32 p, %69, 0;\nmov.b64 db, {%68, 0x40000040};\n"
    "wgmma.mma_async.sync.aligned.m64n128k16.f32.bf16.bf16 {%0,%1,%2,%3,%4,%5,%6,%7,%8,%9,%10,%11,%12,%13,%14,%15,%16,%17,%18,%19,%20,%21,%22,%23,%24,%25,%26,%27,%28,%29,%30,%31,%32,%33,%34,%35,%36,%37,%38,%39,%40,%41,%42,%43,%44,%45,%46,%47,%48,%49,%50,%51,%52,%53,%54,%55,%56,%57,%58,%59,%60,%61,%62,%63}, {%64,%65,%66,%67}, db, p, 1, 1, 1;\n}\n"
    : "+f"(d[0]),"+f"(d[1]),"+f"(d[2]),"+f"(d[3]),"+f"(d[4]),"+f"(d[5]),"+f"(d[6]),"+f"(d[7]),"+f"(d[8]),"+f"(d[9]),"+f"(d[10]),"+f"(d[11]),"+f"(d[12]),"+f"(d[13]),"+f"(d[14]),"+f"(d[15]),"+f"(d[16]),"+f"(d[17]),"+f"(d[18]),"+f"(d[19]),"+f"(d[20]),"+f"(d[21]),"+f"(d[22]),"+f"(d[23]),"+f"(d[24]),"+f"(d[25]),"+f"(d[26]),"+f"(d[27]),"+f"(d[28]),"+f"(d[29]),"+f"(d[30]),"+f"(d[31]),"+f"(d[32]),"+f"(d[33]),"+f"(d[34]),"+f"(d[35]),"+f"(d[36]),"+f"(d[37]),"+f"(d[38]),"+f"(d[39]),"+f"(d[40]),"+f"(d[41]),"+f"(d[42]),"+f"(d[43]),"+f"(d[44]),"+f"(d[45]),"+f"(d[46]),"+f"(d[47]),"+f"(d[48]),"+f"(d[49]),"+f"(d[50]),"+f"(d[51]),"+f"(d[52]),"+f"(d[53]),"+f"(d[54]),"+f"(d[55]),"+f"(d[56]),"+f"(d[57]),"+f"(d[58]),"+f"(d[59]),"+f"(d[60]),"+f"(d[61]),"+f"(d[62]),"+f"(d[63])
    : "r"(a[0]), "r"(a[1]), "r"(a[2]), "r"(a[3]), "r"(descB), "r"(scaleD));
}
__device__ __forceinline__ void wgmma_ss_n72_t11(float (&d)[36], uint32_t descA, uint32_t descB, int scaleD) {
  asm volatile("{\n.reg .pred p;\n.reg .b64 da, db;\nsetp.ne.b32 p, %38, 0;\nmov.b64 da, {%36, 0x40000040};\nmov.b64 db, {%37, 0x40000040};\n"
    "wgmma.mma_async.sync.aligned.m64n72k16.f32.bf16.bf16 {%0,%1,%2,%3,%4,%5,%6,%7,%8,%9,%10,%11,%12,%13,%14,%15,%16,%17,%18,%19,%20,%21,%22,%23,%24,%25,%26,%27,%28,%29,%30,%31,%32,%33,%34,%35}, da, db, p, 1, 1, 1, 1;\n}\n"
    : "+f"(d[0]),"+f"(d[1]),"+f"(d[2]),"+f"(d[3]),"+f"(d[4]),"+f"(d[5]),"+f"(d[6]),"+f"(d[7]),"+f"(d[8]),"+f"(d[9]),"+f"(d[10]),"+f"(d[11]),"+f"(d[12]),"+f"(d[13]),"+f"(d[14]),"+f"(d[15]),"+f"(d[16]),"+f"(d[17]),"+f"(d[18]),"+f"(d[19]),"+f"(d[20]),"+f"(d[21]),"+f"(d[22]),"+f"(d[23]),"+f"(d[24]),"+f"(d[25]),"+f"(d[26]),"+f"(d[27]),"+f"(d[28]),"+f"(d[29]),"+f"(d[30]),"+f"(d[31]),"+f"(d[32]),"+f"(d[33]),"+f"(d[34]),"+f"(d[35])
    : "r"(descA), "r"(descB), "r"(scaleD));
}

constexpr float LOG2E = 1.4426950408889634f;

__device__ __forceinline__ void feat_exp(const uint32_t (&P)[4], float (&e)[16]) {
  uint32_t a = hmax2(P[0], P[2]), b = hmax2(P[1], P[3]);
  uint32_t mx = hmax2(__byte_perm(a, b, 0x5410), __byte_perm(a, b, 0x7632));
  a = hmin2(P[0], P[2]); b = hmin2(P[1], P[3]);
  uint32_t mn = hmin2(__byte_perm(a, b, 0x5410), __byte_perm(a, b, 0x7632));
  mx = hmax2(mx, __shfl_xor_sync(0xffffffffu, mx, 1));
  mn = hmin2(mn, __shfl_xor_sync(0xffffffffu, mn, 1));
  mx = hmax2(mx, __shfl_xor_sync(0xffffffffu, mx, 2));
  mn = hmin2(mn, __shfl_xor_sync(0xffffffffu, mn, 2));
  float mx0 = -blo(mx) * LOG2E, mx1 = -bhi(mx) * LOG2E, mn0 = blo(mn) * LOG2E, mn1 = bhi(mn) * LOG2E;
  float v[8] = {blo(P[0]), bhi(P[0]), blo(P[1]), bhi(P[1]), blo(P[2]), bhi(P[2]), blo(P[3]), bhi(P[3])};
#pragma unroll
  for (int i = 0; i < 8; i++) {
    bool r1 = (i >> 1) & 1;
    e[i]     = ex2(fmaf(v[i],  LOG2E, r1 ? mx1 : mx0));
    e[8 + i] = ex2(fmaf(v[i], -LOG2E, r1 ? mn1 : mn0));
  }
}

__global__ void __cluster_dims__(2, 1, 1) __launch_bounds__(384, 1)
fused_kernel(const __grid_constant__ Maps maps, const __nv_bfloat16* __restrict__ x, const __nv_bfloat16* __restrict__ wphi,
             const __nv_bfloat16* __restrict__ wo, const __nv_bfloat16* __restrict__ wg_, const __nv_bfloat16* __restrict__ wu_,
             const __nv_bfloat16* __restrict__ wd_, __nv_bfloat16* __restrict__ out) {
  extern __shared__ __align__(1024) unsigned char smem[];
  const uint32_t sb = smem_u32(smem);
  const int tid = threadIdx.x, lane = tid & 31;
  const int warp = __shfl_sync(0xffffffffu, tid >> 5, 0);
  const uint32_t rank = blockIdx.x & 1;
  const int cl = blockIdx.x >> 1;
  int quad, qi;
  if (cl < 4) { quad = 15; qi = cl; }
  else if (cl < 36) { quad = (cl - 4) & 7; qi = (cl - 4) >> 3; }
  else { qi = (cl - 36) / 7; quad = 8 + (cl - 36) - 7 * qi; }
  const int rb = quad, hg = 2 * qi + rank;
  const int rb3 = (quad & ~1) + rank, jf = 4 * (quad & 1) + qi;

  if (warp < 8) {
    asm volatile("setmaxnreg.inc.sync.aligned.u32 240;");
    if (elect_one()) {
#pragma unroll 1
      for (int d = warp; d + 9 < NSTAGE; d += 8) {
        mbar_init(sb + SM_EMPTY + d * 8, st_empty_cnt(d));
        mbar_init(sb + SM_FULL + (d + 9) * 8, 1);
        mbar_expect_tx(sb + SM_FULL + (d + 9) * 8, d + 9 >= ST_D ? 22528 : SLOT);
      }
      asm volatile("fence.mbarrier_init.release.cluster;" ::: "memory");
    }
    __syncwarp();
    bar_sync(0, 352);
    asm volatile("barrier.cluster.arrive.relaxed.aligned;" ::: "memory");
    const int wg = warp >> 2, wq = warp & 3, g = lane >> 2, t = lane & 3;
    const bool lead = (tid & 127) == 0;
    constexpr uint32_t db = (SM_BASE >> 4) | (512u << 16);
    auto release = [&](int d) {
      const int s = d + NSLOT;
      mbar_arrive_cluster(sb + SM_EMPTY + d * 8, s >= ST_GU ? (uint32_t)(s & 1) : rank);
    };
    const uint32_t lrow = (uint32_t)(wq * 16 + (lane & 7) + ((lane >> 3) & 1) * 8) * 128;
    const uint32_t lx = lane & 7, lhi = lane >> 4;
    if (wg == 1) bar_arrive(4, 256);

    float r0, r1;
    uint32_t E[4][8];
    uint32_t T = 0;
    {
      uint32_t A[32][4];
      const int sx = wg ? ST_X1 : ST_X0;
      {
        const uint32_t base = sb + sx * SLOT + lrow, baseb = sb + sx * SLOT + (wq * 16 + lx + lhi * 8) * 128;
        float cs[2][4], c0[2][4], c1[2][4];
#pragma unroll
        for (int i = 0; i < 4; i++) { cs[0][i] = cs[1][i] = c0[0][i] = c0[1][i] = c1[0][i] = c1[1][i] = 0.f; }
        uint32_t bt[2][4][4];
        if (wg == 1) bar_sync(13, 256);
#pragma unroll
        for (int c = -1; c < 8; c++) {
          if (c < 7) {
            const int n = c + 1;
            if (n % 3 == 0) mbar_wait(sb + SM_FULL + (sx + n / 3) * 8);
#pragma unroll
            for (int k = 0; k < 4; k++) {
              ldsm4(A[4 * n + k], base + n * 8192 + (((2 * k + lhi) ^ lx) << 4));
              ldsm4(bt[n & 1][k], baseb + n * 8192 + (((2 * k + ((lane >> 3) & 1)) ^ lx) << 4));
            }
          }
          if (c >= 0) {
#pragma unroll
            for (int k = 0; k < 4; k++) {
              const uint32_t (&f)[4] = A[4 * c + k];
              mma16816(cs[k & 1], f, 0x3F803F80u, 0x3F803F80u);
              mma16816(c0[k & 1], f, bt[c & 1][k][0], bt[c & 1][k][1]);
              mma16816(c1[k & 1], f, bt[c & 1][k][2], bt[c & 1][k][3]);
            }
          }
        }
        if (wg == 0) bar_arrive(13, 256);
        const float s0 = (cs[0][0] + cs[1][0]) * (1.f / 512.f), s1 = (cs[0][2] + cs[1][2]) * (1.f / 512.f);
        asm volatile("barrier.cluster.wait.aligned;" ::: "memory");
        if (lane < 3) release(sx + lane);
        const uint32_t m0 = pack2(s0, s0), m1 = pack2(s1, s1);
        float q0 = (g & 1) ? c0[0][1] + c0[1][1] : c0[0][0] + c0[1][0];
        float q1 = (g & 1) ? c1[0][3] + c1[1][3] : c1[0][2] + c1[1][2];
        q0 = __shfl_sync(0xffffffffu, q0, (lane & ~3) | (g >> 1));
        q1 = __shfl_sync(0xffffffffu, q1, (lane & ~3) | (g >> 1));
        r0 = rsqrtf(fmaxf(q0 * (1.f / 512.f) - s0 * s0, 0.f) + 1e-5f);
        r1 = rsqrtf(fmaxf(q1 * (1.f / 512.f) - s1 * s1, 0.f) + 1e-5f);
#pragma unroll
        for (int ks = 0; ks < 32; ks++) {
          A[ks][0] = hsub2(A[ks][0], m0); A[ks][1] = hsub2(A[ks][1], m1);
          A[ks][2] = hsub2(A[ks][2], m0); A[ks][3] = hsub2(A[ks][3], m1);
        }
      }
      const uint32_t wpa = sb + SM_WPHI + ((lane & 7) + ((lane >> 3) & 1) * 8) * 32 + lhi * 16;
      const uint32_t scr = sb + (wg ? (ST_SCR1 % NSLOT) : (ST_SCR0 % NSLOT)) * SLOT;
#pragma unroll 1
      for (int ps = 0; ps < 3; ps++) {
        const int st0 = ps == 0 ? ST_WK : (ps == 1 ? ST_WV : ST_WQ);
        const uint32_t wdesc = DESC((ps == 0 ? ST_WK % NSLOT : (ps == 1 ? ST_WV % NSLOT : ST_WQ % NSLOT)) * SLOT);
        float acc[32];
        bar_sync(4 + wg, 256);
#pragma unroll
        for (int i = 0; i < 3; i++) {
          mbar_wait(sb + SM_FULL + (st0 + i) * 8);
          wg_fence();
#pragma unroll
          for (int kk = 0; kk < (i < 2 ? 12 : 8); kk++)
            wgmma_rs_n64(acc, A[12 * i + kk], wdesc + ((i * SLOT + kk * 2048) >> 4), (i | kk) != 0);
          wg_commit();
          if (i == 1) { wg_wait<1>(); if (lead) release(st0); }
        }
        if (ps == 1 && wg == 0) bar_arrive(5, 256);
        uint32_t a[4][4], b[4][4];
        mbar_wait(sb + SM_MISCB);
        T = (*reinterpret_cast<volatile unsigned*>(smem + SM_EPOCH) & 1) ^ 1;
#pragma unroll
        for (int h = 0; h < 4; h++) ldsm4t(b[h], wpa + h * 512);
        wg_wait<0>();
        if ((tid & 127) < 2) release(st0 + 1 + (tid & 1));
#pragma unroll
        for (int h = 0; h < 4; h++) {
          a[h][0] = pack2(acc[8 * h + 0] * r0, acc[8 * h + 1] * r0); a[h][1] = pack2(acc[8 * h + 2] * r1, acc[8 * h + 3] * r1);
          a[h][2] = pack2(acc[8 * h + 4] * r0, acc[8 * h + 5] * r0); a[h][3] = pack2(acc[8 * h + 6] * r1, acc[8 * h + 7] * r1);
        }
        if (ps != 1) {
          {
            float pp[4][2][4];
#pragma unroll
            for (int h = 0; h < 4; h++) {
#pragma unroll
              for (int i = 0; i < 4; i++) { pp[h][0][i] = 0.f; pp[h][1][i] = 0.f; }
              mma16816(pp[h][0], a[h], b[h][0], b[h][1]);
              mma16816(pp[h][1], a[h], b[h][2], b[h][3]);
            }
#pragma unroll
            for (int h = 0; h < 4; h++) {
              a[h][0] = pack2(pp[h][0][0], pp[h][0][1]); a[h][1] = pack2(pp[h][0][2], pp[h][0][3]);
              a[h][2] = pack2(pp[h][1][0], pp[h][1][1]); a[h][3] = pack2(pp[h][1][2], pp[h][1][3]);
            }
          }
          if (ps == 0 || wg == 0) bar_arrive(4 + (wg ^ 1), 256);
          if (ps == 0) mbar_wait(sb + SM_EMPTY + (wg ? ST_SCR1 - NSLOT : ST_SCR0 - NSLOT) * 8);
#pragma unroll 1
          for (int hp = 0; hp < 2; hp++) {
            float e[2][16];
            feat_exp(a[0], e[0]);
            feat_exp(a[1], e[1]);
            if (ps == 0) {
#pragma unroll
              for (int h = 0; h < 2; h++) {
                const float (&f)[16] = e[h];
                float sp0 = (f[0] + f[1]) + (f[4] + f[5]), sp1 = (f[2] + f[3]) + (f[6] + f[7]);
                float sn0 = (f[8] + f[9]) + (f[12] + f[13]), sn1 = (f[10] + f[11]) + (f[14] + f[15]);
                sp0 += __shfl_xor_sync(0xffffffffu, sp0, 1); sp1 += __shfl_xor_sync(0xffffffffu, sp1, 1);
                sn0 += __shfl_xor_sync(0xffffffffu, sn0, 1); sn1 += __shfl_xor_sync(0xffffffffu, sn1, 1);
                sp0 += __shfl_xor_sync(0xffffffffu, sp0, 2); sp1 += __shfl_xor_sync(0xffffffffu, sp1, 2);
                sn0 += __shfl_xor_sync(0xffffffffu, sn0, 2); sn1 += __shfl_xor_sync(0xffffffffu, sn1, 2);
                sp0 = rcp(sp0); sp1 = rcp(sp1); sn0 = rcp(sn0); sn1 = rcp(sn1);
                const uint32_t dst = scr + hp * 8192 + lrow;
                stsm4(dst + (((h * 4 + lhi) ^ lx) << 4), pack2(f[0] * sp0, f[1] * sp0), pack2(f[2] * sp1, f[3] * sp1),
                      pack2(f[4] * sp0, f[5] * sp0), pack2(f[6] * sp1, f[7] * sp1));
                stsm4(dst + (((h * 4 + 2 + lhi) ^ lx) << 4), pack2(f[8] * sn0, f[9] * sn0), pack2(f[10] * sn1, f[11] * sn1),
                      pack2(f[12] * sn0, f[13] * sn0), pack2(f[14] * sn1, f[15] * sn1));
              }
            } else {
#pragma unroll
              for (int i = 0; i < 16; i++) {
                A[i >> 2][i & 3] = A[4 + (i >> 2)][i & 3];
                A[4 + (i >> 2)][i & 3] = pack2(e[i >> 3][2 * (i & 7)], e[i >> 3][2 * (i & 7) + 1]);
              }
            }
#pragma unroll
            for (int i = 0; i < 4; i++) { a[0][i] = a[2][i]; a[1][i] = a[3][i]; }
          }
        } else {
#pragma unroll
          for (int h = 0; h < 4; h++) stsm4(scr + 16384 + lrow + (((2 * h + lhi) ^ lx) << 4), a[h][0], a[h][1], a[h][2], a[h][3]);
          fence_async_smem();
          bar_sync(3, 256);
          float kv[36];
          wg_fence();
#pragma unroll
          for (int ks = 0; ks < 8; ks++) {
            const uint32_t sk = (ks < 4 ? (ST_SCR0 % NSLOT) : (ST_SCR1 % NSLOT)) * SLOT + (ks & 3) * 2048;
            const uint32_t dv = (DESC(sk + 16384) & 0xFFFFu) | (((SM_ONES - sk - 16384) >> 4) << 16);
            wgmma_ss_n72_t11(kv, DESC(sk) + wg * 512, dv, ks != 0);
          }
          wg_commit();
          if (wg == 1) bar_arrive(4, 256);
          wg_wait<0>();
          if (lead) { mbar_arrive(sb + SM_EMPTY + ST_SCR0 * 8); mbar_arrive(sb + SM_EMPTY + ST_SCR1 * 8); }
          const int hl = 2 * wg + (wq >> 1), f = (wq & 1) * 16 + g;
          float* kvp = reinterpret_cast<float*>(smem + 2 * SLOT) + (hl * 32 + f) * 16 + 2 * t;
          float c[8];
#pragma unroll
          for (int i = 0; i < 8; i++) c[i] = hl >= 2 ? (hl == 3 ? kv[24 + i] : kv[16 + i]) : (hl == 1 ? kv[8 + i] : kv[i]);
#pragma unroll
          for (int n = 0; n < 2; n++) {
            *reinterpret_cast<float2*>(kvp + n * 8) = make_float2(c[4 * n], c[4 * n + 1]);
            *reinterpret_cast<float2*>(kvp + n * 8 + 128) = make_float2(c[4 * n + 2], c[4 * n + 3]);
          }
          if (t < 2) reinterpret_cast<float*>(smem + 2 * SLOT)[2048 + hl * 32 + f + t * 8] = t ? kv[34] : kv[32];
          fence_async_smem();
          bar_sync(6, 320);
        }
      }
#pragma unroll
      for (int i = 0; i < 32; i++) E[i >> 3][i & 7] = A[i >> 2][i & 3];
    }
    const int rh = 2 * rb + wg;
#define IDF ((g >> 1) == t ? ((g & 1) ? 0x3F800000u : 0x00003F80u) : 0u)
    const uint4* xb = reinterpret_cast<const uint4*>(smem + 2 * SLOT) + wq * 128 + lane;
    if (wg == 0) {
      mbar_wait(sb + SM_KVB);
      const int r = tid;
      const float4* src = reinterpret_cast<const float4*>(smem + SM_KV32) + r;
#pragma unroll
      for (int i = 0; i < 4; i++) {
        const float4 a = src[i * 128];
        *reinterpret_cast<uint2*>(smem + SM_KVS + (i * 32 + (r >> 2)) * 48 + (r & 3) * 8) = make_uint2(pack2(a.x, a.y), pack2(a.z, a.w));
      }
      const uint32_t zz = pack2(reinterpret_cast<const float*>(smem + SM_ONES)[r], 1.0f);
      *reinterpret_cast<uint4*>(smem + SM_KVS + r * 48 + 32) = make_uint4(zz, zz, zz, zz);
      bar_sync(1, 128);
    }
    {
      uint4* op = &g_o[rh][hg][wq][0][lane];
      if (wg == 1) bar_sync(7, 256);
#pragma unroll 1
      for (int hp = 0; hp < 2; hp++) {
#pragma unroll
      for (int h = 0; h < 2; h++) {
        uint32_t b0[4], b1[4], b2[4];
        const uint32_t kb = sb + SM_KVS + ((2 * hp + h) * 32 + lane) * 48;
        ldsm4t(b0, kb); ldsm4t(b1, kb + 16); ldsm4t(b2, kb + 32);
        const uint32_t ep[4] = {E[h][0], E[h][1], E[h][2], E[h][3]}, en[4] = {E[h][4], E[h][5], E[h][6], E[h][7]};
        float np0[4] = {0, 0, 0, 0}, np1[4] = {0, 0, 0, 0}, nn0[4] = {0, 0, 0, 0}, nn1[4] = {0, 0, 0, 0}, dp[4] = {0, 0, 0, 0}, dn[4] = {0, 0, 0, 0};
        mma16816(dp, ep, b2[0], b2[1]);  mma16816(dn, en, b2[2], b2[3]);
        mma16816(np0, ep, b0[0], b0[1]); mma16816(nn0, en, b0[2], b0[3]);
        mma16816(np1, ep, b1[0], b1[1]); mma16816(nn1, en, b1[2], b1[3]);
        const float i0 = rcp(fmaf(dp[0], dn[1], fmaf(dn[0], dp[1], 1e-6f * dp[1] * dn[1])));
        const float i1 = rcp(fmaf(dp[2], dn[3], fmaf(dn[2], dp[3], 1e-6f * dp[3] * dn[3])));
        const float cp0 = dn[1] * i0, cn0 = dp[1] * i0, cp1 = dn[3] * i1, cn1 = dp[3] * i1;
        st_rlx4(op + (2 * hp + h) * 32,
                tg(pack2(fmaf(np0[0], cp0, nn0[0] * cn0), fmaf(np0[1], cp0, nn0[1] * cn0)), T),
                pack2(fmaf(np0[2], cp1, nn0[2] * cn1), fmaf(np0[3], cp1, nn0[3] * cn1)),
                pack2(fmaf(np1[0], cp0, nn1[0] * cn0), fmaf(np1[1], cp0, nn1[1] * cn0)),
                pack2(fmaf(np1[2], cp1, nn1[2] * cn1), fmaf(np1[3], cp1, nn1[3] * cn1)));
      }
#pragma unroll
        for (int i = 0; i < 8; i++) { E[0][i] = E[2][i]; E[1][i] = E[3][i]; }
      }
    }
    if (wg == 0) bar_arrive(7, 256);
    bar_arrive(10 + wg, 160);

    {
      uint32_t xr[4][4];
      {
        const uint32_t* xp = reinterpret_cast<const uint32_t*>(x + (size_t)(rh * 64 + wq * 16 + g) * 512 + hg * 64 + 2 * t);
#pragma unroll
        for (int i = 0; i < 8; i++) { xr[i >> 1][(i & 1) * 2] = __ldg(xp + 4 * i); xr[i >> 1][(i & 1) * 2 + 1] = __ldg(xp + 8 * 256 + 4 * i); }
      }
      uint32_t A[8][4][4];
      const uint4* op = &g_o[rh][0][wq][0][lane];
      float acc[32];
#pragma unroll
      for (int i = 0; i < 32; i++) acc[i] = 0.f;
      add_frag(acc, xr, IDF);
#pragma unroll
      for (int p = -1; p < 4; p++) {
        if (p < 3) {
          mbar_wait(sb + SM_XF + (wg * 4 + p + 1) * 8);
          get_pair(A[2 * p + 2], A[2 * p + 3], xb + (p + 1) * 1024, op + (p + 1) * 1024, T);
          if (lane == 0) mbar_arrive(sb + SM_XE + (wg * 4 + p + 1) * 8);
        }
        if (p == 0 && wg == 1) bar_sync(14, 256);
        if (p >= 0) {
          if (p != 2) mbar_wait(sb + SM_FULL + (ST_WO + (p + 1) / 2) * 8);
          wg_fence();
#pragma unroll
          for (int c = 2 * p; c < 2 * p + 2; c++)
#pragma unroll
            for (int s = 0; s < 4; s++)
              wgmma_rs_n64(acc, A[c][s], DESC(((ST_WO + c / 3) % NSLOT) * SLOT + ((c % 3) * 4 + s) * 2048), 1);
        }
      }
      wg_commit();
      if (wg == 0) bar_arrive(14, 256);
      wg_wait<0>();
      if ((tid & 127) < 3) release(ST_WO + (tid & 127));
      uint4* hp_ = &g_h[rh][hg][wq][0][lane];
      uint32_t hx = T;
#pragma unroll
      for (int s = 0; s < 4; s++) {
        const uint32_t h0 = pack2(acc[8 * s], acc[8 * s + 1]);
        st_rlx4(hp_ + s * 32, tg(h0, T), pack2(acc[8 * s + 2], acc[8 * s + 3]), pack2(acc[8 * s + 4], acc[8 * s + 5]), pack2(acc[8 * s + 6], acc[8 * s + 7]));
        hx |= (h0 & 1u) << (s + 1);
      }
      float s0 = 0.f, s1 = 0.f, q0 = 0.f, q1 = 0.f, q2 = 0.f, q3 = 0.f;
#pragma unroll
      for (int i = 0; i < 8; i++) {
        s0 += acc[4 * i] + acc[4 * i + 1]; s1 += acc[4 * i + 2] + acc[4 * i + 3];
        q0 = fmaf(acc[4 * i], acc[4 * i], q0); q2 = fmaf(acc[4 * i + 1], acc[4 * i + 1], q2);
        q1 = fmaf(acc[4 * i + 2], acc[4 * i + 2], q1); q3 = fmaf(acc[4 * i + 3], acc[4 * i + 3], q3);
      }
      q0 += q2; q1 += q3;
      {
        const bool up = t & 2;
        float s = (up ? s1 : s0) + __shfl_xor_sync(0xffffffffu, up ? s0 : s1, 2);
        float q = (up ? q1 : q0) + __shfl_xor_sync(0xffffffffu, up ? q0 : q1, 2);
        s += __shfl_xor_sync(0xffffffffu, s, 1);
        q += __shfl_xor_sync(0xffffffffu, q, 1);
        if (!(t & 1)) st_rlx2(&g_st[rh][hg][wq * 16 + g + (t >> 1) * 8], tg(__float_as_uint(s), T), __float_as_uint(q));
      }
      st_rlx1(&g_hx[rh][hg][wq][lane], hx);
    }
    bar_arrive(10 + wg, 160);

    const int rh3 = 2 * rb3 + wg;
    uint32_t HH[11][4], PH[11][4];
    const uint4* pp = &g_hh[rh3][jf ^ 1][0][wq][lane];
    {
      uint32_t A[8][4][4];
      const uint4* hp_ = &g_h[rh3][0][wq][0][lane];
      uint4* hhp = &g_hh[rh3][jf][0][wq][lane];
      const uint32_t dg = (db & 0xFFFFu) | (256u << 16);
      uint32_t m0, m1;
      mbar_wait(sb + SM_XF + ((2 + wg) * 4) * 8);
      {
        const uint2* sp = reinterpret_cast<const uint2*>(smem + SM_KV32 + wg * 4096) + 2 * t * 64 + wq * 16 + g;
        uint2 a0, a1, b0, b1;
        int it = 0;
#pragma unroll 1
        do {
          ld_rlx2(a0.x, a0.y, sp); ld_rlx2(a1.x, a1.y, sp + 64); ld_rlx2(b0.x, b0.y, sp + 8); ld_rlx2(b1.x, b1.y, sp + 72);
          sp = &g_st[rh3][2 * t][wq * 16 + g];
        } while (__any_sync(0xffffffffu, bad4(a0.x, a1.x, b0.x, b1.x, T)) && ++it < (1 << 18));
        float s0 = __uint_as_float(a0.x) + __uint_as_float(a1.x), q0 = __uint_as_float(a0.y) + __uint_as_float(a1.y);
        float s1 = __uint_as_float(b0.x) + __uint_as_float(b1.x), q1 = __uint_as_float(b0.y) + __uint_as_float(b1.y);
        s0 += __shfl_xor_sync(0xffffffffu, s0, 1); s1 += __shfl_xor_sync(0xffffffffu, s1, 1);
        q0 += __shfl_xor_sync(0xffffffffu, q0, 1); q1 += __shfl_xor_sync(0xffffffffu, q1, 1);
        s0 += __shfl_xor_sync(0xffffffffu, s0, 2); s1 += __shfl_xor_sync(0xffffffffu, s1, 2);
        q0 += __shfl_xor_sync(0xffffffffu, q0, 2); q1 += __shfl_xor_sync(0xffffffffu, q1, 2);
        s0 *= (1.f / 512.f); s1 *= (1.f / 512.f);
        r0 = rcp(fmaxf(q0 * (1.f / 512.f) - s0 * s0, 0.f) + 1e-5f);
        r1 = rcp(fmaxf(q1 * (1.f / 512.f) - s1 * s1, 0.f) + 1e-5f);
        m0 = pack2(s0, s0); m1 = pack2(s1, s1);
      }
#define UOFF(u) ((((ST_GU + (u) / 3) % NSLOT) * SLOT + ((u) % 3) * 8192) >> 4)
#define UNIT_PRE(u)  do { if ((u) % 3 == 0) mbar_wait(sb + SM_FULL + (ST_GU + (u) / 3) * 8); } while (0)
#define UNIT_POST(u) do { wg_commit(); if ((u) % 3 == 1 && (u) > 3) { wg_wait<2>(); if (lead) release(ST_GU + (u) / 3 - 1); } } while (0)
      float acc[64];
      const int rz = blockIdx.y;
#pragma unroll
      for (int ps = 0; ps < 2; ps++) {
        wg_fence();
#pragma unroll
        for (int k = 0; k < 16; k++) {
          const int u = 16 * ps + k, c = k >> 1;
          if (ps == 0 && (k == 0 || k == 4 || k == 8)) {
#pragma unroll
            for (int p = (k == 0 ? 0 : (k == 4 ? 1 : 3)); p < (k == 0 ? 1 : (k == 4 ? 3 : 4)); p++) {
              if (p > 0) mbar_wait(sb + SM_XF + ((2 + wg) * 4 + p) * 8);
              get_pair(A[2 * p], A[2 * p + 1], xb + p * 1024, hp_ + p * 1024, T);
              if (lane == 0) {
                if (wg == 0) mbar_arrive(sb + SM_XE + (8 + p) * 8);
                else if (p > 0) release(ST_XC + p - 1);
              }
            }
          }
          if (ps == 0 && (k & 1) == 0) {
#pragma unroll
            for (int s = 0; s < 4; s++) {
              A[c][s][0] = hsub2(A[c][s][0], m0); A[c][s][1] = hsub2(A[c][s][1], m1);
              A[c][s][2] = hsub2(A[c][s][2], m0); A[c][s][3] = hsub2(A[c][s][3], m1);
            }
            wg_fence();
          }
          UNIT_PRE(u);
          wgmma_rs_n128(acc, A[c][(k & 1) * 2], dg + UOFF(u), k != 0 ? 1 : (ps ? rz : 0));
          wgmma_rs_n128(acc, A[c][(k & 1) * 2 + 1], dg + UOFF(u) + 128, 1);
          UNIT_POST(u);
        }
        wg_wait<0>();
#pragma unroll
        for (int s = 0; s < 4; s++) {
          uint32_t (&hh)[4] = HH[4 + s];
          hh[0] = tg(pack2(acc[8 * s + 0] * acc[32 + 8 * s + 0], acc[8 * s + 1] * acc[32 + 8 * s + 1]), T);
          hh[1] = pack2(acc[8 * s + 2] * acc[32 + 8 * s + 2], acc[8 * s + 3] * acc[32 + 8 * s + 3]);
          hh[2] = pack2(acc[8 * s + 4] * acc[32 + 8 * s + 4], acc[8 * s + 5] * acc[32 + 8 * s + 5]);
          hh[3] = pack2(acc[8 * s + 6] * acc[32 + 8 * s + 6], acc[8 * s + 7] * acc[32 + 8 * s + 7]);
          st_rlx4(hhp + (4 * ps + s) * 128, hh[0], hh[1], hh[2], hh[3]);
        }
      }
      {
        float ag[24], au[24];
        const uint32_t* ph7 = reinterpret_cast<const uint32_t*>(&g_hh[rh3][jf ^ 1][7][wq][31]);
        uint32_t hv = 0;
        bar_sync(1 + wg, 128);
        wg_fence();
#pragma unroll
        for (int k = 0; k < 16; k++) {
          const int u = 32 + k, c = k >> 1;
          if (k == 6) {
#pragma unroll
            for (int s = 0; s < 4; s++) ld_rlx4(HH[s], hhp + s * 128);
          }
          if (k == 9) hv = ld_rlx1(ph7);
          if (k == 12) {
            int it = 0;
#pragma unroll 1
            while (((hv ^ T) & 1) && ++it < (1 << 18)) hv = ld_rlx1(ph7);
#pragma unroll
            for (int s = 0; s < 8; s++) ld_rlx4(PH[s], pp + s * 128);
          }
          UNIT_PRE(u);
          wgmma_rs_n48(ag, A[c][(k & 1) * 2], dg + UOFF(u), k != 0);
          wgmma_rs_n48(au, A[c][(k & 1) * 2], dg + UOFF(u) + 256, k != 0);
          wgmma_rs_n48(ag, A[c][(k & 1) * 2 + 1], dg + UOFF(u) + 128, 1);
          wgmma_rs_n48(au, A[c][(k & 1) * 2 + 1], dg + UOFF(u) + 256 + 128, 1);
          UNIT_POST(u);
        }
        wg_wait<0>();
#pragma unroll
        for (int s = 0; s < 3; s++) {
          uint32_t (&hh)[4] = HH[8 + s];
          hh[0] = tg(pack2(ag[8 * s + 0] * au[8 * s + 0], ag[8 * s + 1] * au[8 * s + 1]), T);
          hh[1] = pack2(ag[8 * s + 2] * au[8 * s + 2], ag[8 * s + 3] * au[8 * s + 3]);
          hh[2] = pack2(ag[8 * s + 4] * au[8 * s + 4], ag[8 * s + 5] * au[8 * s + 5]);
          hh[3] = pack2(ag[8 * s + 6] * au[8 * s + 6], ag[8 * s + 7] * au[8 * s + 7]);
          st_rlx4(hhp + (8 + s) * 128, hh[0], hh[1], hh[2], hh[3]);
        }
      }
    }

    {
      float ac[3][32], acc[32];
      uint32_t hr[4][4];
      const int m = jf >> 1, oc = (jf & 1) * 4 + m;
      const uint32_t* ph10 = reinterpret_cast<const uint32_t*>(&g_hh[rh3][jf ^ 1][10][wq][31]);
      uint4* outb = &g_part[rh3][(jf & 1) * 4][m][wq][0][lane];
      bar_arrive(8 + wg, 256);
#define DW(i, s) DESC(((ST_D + (i)) % NSLOT) * SLOT + (s) * 2048)
      auto send = [&](int k) {
        wg_commit();
        wg_wait<1>();
        const float (&a)[32] = ac[k];
        uint4* p = outb + ((m + k + 1) & 3) * 2048;
#pragma unroll
        for (int i = 0; i < 4; i++)
          st_rlx4(p + i * 32, tg(pack2(a[8 * i + 0], a[8 * i + 1]), T), pack2(a[8 * i + 2], a[8 * i + 3]),
                  pack2(a[8 * i + 4], a[8 * i + 5]), pack2(a[8 * i + 6], a[8 * i + 7]));
      };
      {
        int it = 0;
#pragma unroll 1
        while (__any_sync(0xffffffffu, bad4(PH[0][0], PH[1][0], PH[2][0], PH[3][0], T) | bad4(PH[4][0], PH[5][0], PH[6][0], PH[7][0], T)) && ++it < (1 << 18)) {
#pragma unroll
          for (int s = 0; s < 8; s++) ld_rlx4(PH[s], pp + s * 128);
        }
      }
      mbar_wait(sb + SM_FULL + ST_D * 8);
      mbar_wait(sb + SM_FULL + (ST_D + 1) * 8);
      wg_fence();
#pragma unroll
      for (int s = 0; s < 11; s++) wgmma_rs_n64(ac[0], HH[s], DW(0, s), s != 0);
      uint32_t hv = ld_rlx1(ph10);
#pragma unroll
      for (int s = 0; s < 8; s++) wgmma_rs_n64(ac[0], PH[s], DW(1, s), 1);
      mbar_wait(sb + SM_FULL + (ST_D + 2) * 8);
#pragma unroll
      for (int s = 0; s < 11; s++) {
        if (s == 3) {
          int it = 0;
#pragma unroll 1
          while (((hv ^ T) & 1) && ++it < (1 << 18)) hv = ld_rlx1(ph10);
#pragma unroll
          for (int i = 8; i < 11; i++) ld_rlx4(PH[i], pp + i * 128);
        }
        wgmma_rs_n64(ac[1], HH[s], DW(2, s), s != 0);
      }
      mbar_wait(sb + SM_FULL + (ST_D + 3) * 8);
#pragma unroll
      for (int s = 0; s < 4; s++) wgmma_rs_n64(ac[1], PH[s], DW(3, s), 1);
      {
        int it = 0;
#pragma unroll 1
        while (__any_sync(0xffffffffu, bad4(PH[8][0], PH[9][0], PH[10][0], T, T)) && ++it < (1 << 18)) {
#pragma unroll
          for (int i = 8; i < 11; i++) ld_rlx4(PH[i], pp + i * 128);
        }
      }
      wg_fence();
#pragma unroll
      for (int s = 8; s < 11; s++) wgmma_rs_n64(ac[0], PH[s], DW(1, s), 1);
      wg_commit();
#pragma unroll
      for (int s = 4; s < 11; s++) wgmma_rs_n64(ac[1], PH[s], DW(3, s), 1);
      send(0);
      bar_arrive(12, 320);
      mbar_wait(sb + SM_FULL + (ST_D + 4) * 8);
      mbar_wait(sb + SM_FULL + (ST_D + 5) * 8);
      wg_fence();
#pragma unroll
      for (int s = 0; s < 22; s++) {
        if (s == 5) send(1);
        if (s < 11) wgmma_rs_n64(ac[2], HH[s], DW(4, s), s != 0); else wgmma_rs_n64(ac[2], PH[s - 11], DW(5, s - 11), 1);
      }
      wg_commit();
      mbar_wait(sb + SM_FULL + (ST_D + 6) * 8);
      mbar_wait(sb + SM_FULL + (ST_D + 7) * 8);
      wg_fence();
      uint32_t hx = 0;
#pragma unroll
      for (int s = 0; s < 22; s++) {
        if (s == 5) {
          send(2);
          ld_chunk(hr, &g_h[rh3][oc][wq][0][lane]);
          hx = ld_rlx1(&g_hx[rh3][oc][wq][lane]);
        }
        if (s < 11) wgmma_rs_n64(acc, HH[s], DW(6, s), s != 0); else wgmma_rs_n64(acc, PH[s - 11], DW(7, s - 11), 1);
      }
      wg_commit();
      wg_wait<0>();
#pragma unroll 1
      for (int q = 0; q < 3; q++) {
        uint32_t in[4][4];
        const uint4* sp = reinterpret_cast<const uint4*>(smem + ((ST_D % NSLOT) + wg) * SLOT) + q * 512 + wq * 128 + lane;
        mbar_wait_p(sb + SM_XF + (wg * 4 + q) * 8, 1);
        int it = 0;
#pragma unroll 1
        do {
#pragma unroll
          for (int s = 0; s < 4; s++)
            asm volatile("{\n.reg .b128 v;\nld.relaxed.gpu.b128 v, [%4];\nmov.b128 {%0,%1,%2,%3}, v;\n}"
                         : "=r"(in[s][0]), "=r"(in[s][1]), "=r"(in[s][2]), "=r"(in[s][3]) : "l"(sp + s * 32) : "memory");
          sp = &g_part[rh3][oc][(m - 1 - q) & 3][wq][0][lane];
        } while (__any_sync(0xffffffffu, bad4(in[0][0], in[1][0], in[2][0], in[3][0], T)) && ++it < (1 << 18));
        add_frag(acc, in, IDF);
      }
      {
        int it = 0;
#pragma unroll 1
        while (__any_sync(0xffffffffu, (hx ^ T) & 1) && ++it < (1 << 18)) hx = ld_rlx1(&g_hx[rh3][oc][wq][lane]);
      }
#pragma unroll
      for (int s = 0; s < 4; s++) hr[s][0] = (hr[s][0] & 0xFFFFFFFEu) | ((hx >> (s + 1)) & 1u);
#pragma unroll
      for (int i = 0; i < 32; i++) acc[i] *= (i & 2) ? r1 : r0;
      add_frag(acc, hr, IDF);
      bar_sync(9 - wg, 256);
      const uint32_t ob = sb + ((ST_D - 1) % NSLOT) * SLOT + wg * 8192;
#pragma unroll
      for (int s = 0; s < 4; s++)
        stsm4(ob + lrow + (((2 * s + lhi) ^ lx) << 4), pack2(acc[8 * s + 0], acc[8 * s + 1]), pack2(acc[8 * s + 2], acc[8 * s + 3]),
              pack2(acc[8 * s + 4], acc[8 * s + 5]), pack2(acc[8 * s + 6], acc[8 * s + 7]));
      __syncwarp();
      {
        const int row = wq * 16 + (lane >> 3);
        __nv_bfloat16* op = out + (size_t)(rh3 * 64 + row) * 512 + oc * 64 + lx * 8;
#pragma unroll
        for (int i = 0; i < 4; i++) {
          uint4 v;
          asm volatile("ld.shared.v4.b32 {%0,%1,%2,%3}, [%4];" : "=r"(v.x), "=r"(v.y), "=r"(v.z), "=r"(v.w)
                       : "r"(ob + (row + i * 4) * 128 + ((lx ^ (((lane >> 3) + i * 4) & 7)) << 4)) : "memory");
          asm volatile("st.global.v4.b32 [%0], {%1,%2,%3,%4};" ::"l"(op + i * 2048), "r"(v.x), "r"(v.y), "r"(v.z), "r"(v.w) : "memory");
        }
      }
    }
    asm volatile("barrier.cluster.arrive.relaxed.aligned;" ::: "memory");
    asm volatile("barrier.cluster.wait.aligned;" ::: "memory");
  } else {
    asm volatile("setmaxnreg.dec.sync.aligned.u32 24;");
    if (elect_one()) {
      if (warp == 8) {
#pragma unroll
        for (int k = 0; k < 9; k++) {
          const int s = k < 3 ? k : (k < 6 ? k + 3 : k - 3);
          const uint32_t bar = sb + SM_FULL + s * 8;
          mbar_init(bar, 1);
          mbar_expect_tx(bar, SLOT);
          if (s >= 3 && s < 6) tma2d(sb + s * SLOT, &maps.w, 512 + hg * 64, (s - 3) * 192, bar);
          else tma3d(sb + s * SLOT, &maps.x, 0, rb * 128 + (s >= 6 ? 64 : 0), 3 * (s % 3), bar);
        }
      } else if (warp == 9) {
        mbar_init(sb + SM_MISCB, 2);
        mbar_init(sb + SM_KVB, 1);
        mbar_expect_tx(sb + SM_KVB, 8704);
        mbar_expect_tx(sb + SM_MISCB, 2048);
        bulk_g2s(sb + SM_WPHI, wphi + hg * 1024, 2048, sb + SM_MISCB);
      } else if (warp == 10) {
        if ((sb & 0x3FFFF) != SM_BASE) __trap();
#pragma unroll 1
        for (int i = 0; i < 16; i++) {
          mbar_init(sb + SM_XF + i * 8, 1);
          mbar_expect_tx(sb + SM_XF + i * 8, (i == 8 || i == 12) ? 20480 : 16384);
          if (i < 12) mbar_init(sb + SM_XE + i * 8, 4);
        }
      } else {
        *reinterpret_cast<volatile unsigned*>(smem + SM_EPOCH) = atomicAdd(&g_start, 1u) / NCTA;
      }
      asm volatile("fence.mbarrier_init.release.cluster;" ::: "memory");
    }
    __syncwarp();
    if (warp != 11) bar_sync(0, 352);
    asm volatile("barrier.cluster.arrive.relaxed.aligned;" ::: "memory");
    if (warp == 8) {
      asm volatile("barrier.cluster.wait.aligned;" ::: "memory");
      if (elect_one()) {
        const CUtensorMap* mg = jf == 7 ? &maps.g7 : &maps.g;
        const CUtensorMap* mu = jf == 7 ? &maps.u7 : &maps.u;
        asm volatile("prefetch.tensormap [%0];" ::"l"(&maps.wo) : "memory");
        asm volatile("prefetch.tensormap [%0];" ::"l"(mg) : "memory");
        asm volatile("prefetch.tensormap [%0];" ::"l"(mu) : "memory");
        asm volatile("prefetch.tensormap [%0];" ::"l"(&maps.d) : "memory");
#pragma unroll 1
        for (int s = ST_WV; s < ST_XC; s++) {
          if (s == ST_SCR1) continue;
          mbar_wait(sb + SM_EMPTY + (s - 9) * 8);
          const uint32_t dst = sb + (s >= 18 ? s - 18 : s - 9) * SLOT, bar = sb + SM_FULL + s * 8;
          if (s < ST_WO) tma2d(dst, &maps.w, (s < ST_WQ ? 1024 : 0) + hg * 64, (s < ST_WQ ? s - ST_WV : s - ST_WQ) * 192, bar);
          else { mbar_wait(bar - 8); tma2d(dst, &maps.wo, hg * 64, (s - ST_WO) * 192, bar); }
        }
        const int jc = jf == 7 ? 0 : jf;
        int slot = (ST_GU + 1 - rank) % NSLOT;
#pragma unroll 1
        for (int s = ST_GU + 1 - rank; s < NSTAGE; s += 2) {
          mbar_wait(sb + SM_EMPTY + (s - 9) * 8);
          if (s > ST_GU && s < ST_GU + 6) mbar_wait(sb + SM_FULL + (s - 1) * 8);
          const uint32_t dst = sb + slot * SLOT, bar = sb + SM_FULL + s * 8;
          if (s < ST_D) {
#pragma unroll 1
            for (int i = 0; i < 3; i++) {
              const int u = (s - ST_GU) * 3 + i;
              tma3d_mc(dst + i * 8192, mg, (u >> 4) * 64, jc, (u & 15) * 32, bar);
              tma3d_mc(dst + i * 8192 + 4096, mu, (u >> 4) * 64, jc, (u & 15) * 32, bar);
            }
          } else {
            const int i = s - ST_D;
            tma2d_mc(dst, &maps.d, ((jf & 1) * 4 + (((jf >> 1) + 1 + (i >> 1)) & 3)) * 64, (jf ^ (i & 1)) * 176, bar);
          }
          slot += 2; if (slot >= NSLOT) slot -= NSLOT;
        }
      }
      __syncwarp();
    } else {
      asm volatile("barrier.cluster.wait.aligned;" ::: "memory");
      if (warp == 11) {
#pragma unroll
        for (int i = 0; i < 4; i++)
          reinterpret_cast<uint4*>(smem + SM_ONES)[lane + 32 * i] = make_uint4(0x3F803F80u, 0x3F803F80u, 0x3F803F80u, 0x3F803F80u);
        fence_async_smem();
        __syncwarp();
        if (lane == 0) mbar_arrive(sb + SM_MISCB);
      }
      mbar_wait(sb + SM_MISCB);
      const unsigned epoch = *reinterpret_cast<volatile unsigned*>(smem + SM_EPOCH);
      const uint32_t T = (epoch & 1) ^ 1;
      if (warp == 11) {
        reinterpret_cast<float4*>(&g_kv[hg][rb * 136])[lane] = make_float4(0.f, 0.f, 0.f, 0.f);
        if (lane < 2) reinterpret_cast<float4*>(&g_kv[hg][rb * 136])[32 + lane] = make_float4(0.f, 0.f, 0.f, 0.f);
        __syncwarp();
        if (elect_one()) asm volatile("red.release.gpu.global.add.u32 [%0], 8;" ::"l"(&g_kvcnt[hg * 32 + 1]) : "memory");
        mbar_wait(sb + SM_FULL + (ST_WK + 2) * 8);
        if (elect_one()) {
          asm volatile("cp.async.bulk.prefetch.L2.global [%0], 4096;" ::"l"((const char*)wo + blockIdx.x * 4096) : "memory");
          asm volatile("cp.async.bulk.prefetch.L2.global [%0], 11008;" ::"l"((const char*)wg_ + blockIdx.x * 11008) : "memory");
          asm volatile("cp.async.bulk.prefetch.L2.global [%0], 11008;" ::"l"((const char*)wu_ + blockIdx.x * 11008) : "memory");
          asm volatile("cp.async.bulk.prefetch.L2.global [%0], 11008;" ::"l"((const char*)wd_ + blockIdx.x * 11008) : "memory");
          mbar_wait(sb + SM_EMPTY + ST_SCR0 * 8);
          const unsigned target = (epoch + 1) * 128;
          unsigned v; int it = 0;
#pragma unroll 1
          do {
            asm volatile("ld.acquire.gpu.global.u32 %0, [%1];" : "=r"(v) : "l"(&g_kvcnt[hg * 32]) : "memory");
            if (++it > (1 << 18)) break;
          } while ((int)(v - target) < 0);
          asm volatile("fence.proxy.async.global;" ::: "memory");
          bulk_g2s(sb + SM_KV32, &g_kv[hg][0], 8192, sb + SM_KVB);
          bulk_g2s(sb + SM_ONES, &g_kv[hg][2048], 512, sb + SM_KVB);
        }
        __syncwarp();
      } else {
        const int w = warp - 9;
        st_rlx4(reinterpret_cast<uint4*>(&g_st[2 * rb + w][hg][0]) + lane, T ^ 1, T ^ 1, T ^ 1, T ^ 1);
        if (lane < 8) st_rlx4(&g_o[2 * rb + w][hg][lane >> 1][3][30 + (lane & 1)], T ^ 1, T ^ 1, T ^ 1, T ^ 1);
        st_rlx4(&g_part[2 * rb3 + w][(jf & 1) * 4 + (lane >> 3)][jf >> 1][(lane >> 1) & 3][3][30 + (lane & 1)], T ^ 1, T ^ 1, T ^ 1, T ^ 1);
        if (lane < 16) st_rlx4(&g_hh[2 * rb3 + w][jf][7 + (lane >> 3) * 3][(lane >> 1) & 3][30 + (lane & 1)], T ^ 1, T ^ 1, T ^ 1, T ^ 1);
        if (w == 0) {
          mbar_wait(sb + SM_FULL + (ST_WQ + 2) * 8);
          unsigned v; int it = 0;
#pragma unroll 1
          do {
            asm volatile("ld.acquire.gpu.global.u32 %0, [%1];" : "=r"(v) : "l"(&g_kvcnt[hg * 32 + 1]) : "memory");
          } while ((int)(v - (epoch + 1) * 128) < 0 && ++it < (1 << 18));
          asm volatile("fence.proxy.async.global;" ::: "memory");
        }
        bar_sync(6, 320);
        if (w == 0 && elect_one()) {
          asm volatile("cp.reduce.async.bulk.global.shared::cta.bulk_group.add.f32 [%0], [%1], 8704;"
                       ::"l"(&g_kv[hg][0]), "r"(sb + 2 * SLOT) : "memory");
          asm volatile("cp.async.bulk.commit_group;" ::: "memory");
          asm volatile("cp.async.bulk.wait_group 0;" ::: "memory");
          asm volatile("red.release.gpu.global.add.u32 [%0], 8;" ::"l"(&g_kvcnt[hg * 32]) : "memory");
        }
        __syncwarp();
        mbar_wait(sb + SM_KVB);
        if (w == 0) { mbar_wait(sb + SM_EMPTY + 11 * 8); mbar_wait(sb + SM_EMPTY + 12 * 8); mbar_wait(sb + SM_EMPTY + 13 * 8); }
#pragma unroll 1
        for (int ph = 0; ph < 2; ph++) {
          const int use = 2 * ph + w, r = ph ? 2 * rb3 + w : 2 * rb + w;
          const uint32_t* pw = ph ? reinterpret_cast<const uint32_t*>(&g_st[r][lane >> 2][(lane & 3) * 16 + 15])
                                  : reinterpret_cast<const uint32_t*>(&g_o[r][lane >> 2][lane & 3][3][31]);
          const char* src = reinterpret_cast<const char*>(ph ? &g_h[r][0][0][0][0] : &g_o[r][0][0][0][0]);
          const uint32_t bf = sb + SM_XF + use * 32, be = sb + SM_XE + (use - 1) * 32;
          bar_sync(10 + w, 160);
          int it = 0;
#pragma unroll 1
          for (bool miss = true; __any_sync(0xffffffffu, miss) && ++it < (1 << 18);) { if (miss) miss = (ld_rlx1(pw) ^ T) & 1; }
          if (elect_one()) {
            if (use > 0) mbar_wait(be);
            if (ph) bulk_g2s(sb + SM_KV32 + w * 4096, &g_st[r][0][0], 4096, bf);
#pragma unroll
            for (int p = 0; p < 4; p++) {
              if (p > 0 && use > 0) mbar_wait(be + p * 8);
              bulk_g2s(sb + 2 * SLOT + p * 16384, src + p * 16384, 16384, bf + p * 8);
            }
          }
          __syncwarp();
        }
        {
          const int m = jf >> 1, oc = (jf & 1) * 4 + m;
          const uint32_t* pw = reinterpret_cast<const uint32_t*>(&g_part[2 * rb3 + w][oc][(m - 1 - (lane >> 2)) & 3][lane & 3][3][31]);
          bar_sync(12, 320);
          bool miss = lane < 12; int it = 0;
#pragma unroll 1
          for (int q = 0; q < 3; q++) {
#pragma unroll 1
            while ((__ballot_sync(0xffffffffu, miss) >> (4 * q) & 15) && ++it < (1 << 18)) { if (miss && (lane >> 2) <= q + 1) miss = (ld_rlx1(pw) ^ T) & 1; }
            if (elect_one()) {
              const uint32_t bar = sb + SM_XF + (w * 4 + q) * 8;
              mbar_expect_tx(bar, 8192);
              bulk_g2s(sb + ((ST_D % NSLOT) + w) * SLOT + q * 8192, &g_part[2 * rb3 + w][oc][(m - 1 - q) & 3][0][0][0], 8192, bar);
            }
            __syncwarp();
          }
        }
      }
    }
    asm volatile("barrier.cluster.arrive.relaxed.aligned;" ::: "memory");
    asm volatile("barrier.cluster.wait.aligned;" ::: "memory");
  }
}

typedef CUresult (*EncodeFn)(CUtensorMap*, CUtensorMapDataType, cuuint32_t, void*, const cuuint64_t*, const cuuint64_t*,
                             const cuuint32_t*, const cuuint32_t*, CUtensorMapInterleave, CUtensorMapSwizzle,
                             CUtensorMapL2promotion, CUtensorMapFloatOOBfill);

void encode(EncodeFn fn, CUtensorMap* m, const void* base, int rank, const cuuint64_t* dims, const cuuint64_t* strides,
            const cuuint32_t* box) {
  cuuint32_t es[3] = {1, 1, 1};
  fn(m, CU_TENSOR_MAP_DATA_TYPE_BFLOAT16, (cuuint32_t)rank, const_cast<void*>(base), dims, strides, box, es,
     CU_TENSOR_MAP_INTERLEAVE_NONE, CU_TENSOR_MAP_SWIZZLE_128B, CU_TENSOR_MAP_L2_PROMOTION_L2_256B,
     CU_TENSOR_MAP_FLOAT_OOB_FILL_NONE);
}

}

extern "C" void kernel_launch(void* const* d_in, const int* in_sizes, int n_in, void* d_out, int out_size) {
  (void)in_sizes; (void)n_in; (void)out_size;
  const __nv_bfloat16* x    = (const __nv_bfloat16*)d_in[0];
  const __nv_bfloat16* wqkv = (const __nv_bfloat16*)d_in[1];
  const __nv_bfloat16* wphi = (const __nv_bfloat16*)d_in[2];
  const __nv_bfloat16* wo   = (const __nv_bfloat16*)d_in[3];
  const __nv_bfloat16* wg   = (const __nv_bfloat16*)d_in[5];
  const __nv_bfloat16* wu   = (const __nv_bfloat16*)d_in[6];
  const __nv_bfloat16* wd   = (const __nv_bfloat16*)d_in[7];

  static EncodeFn fn = nullptr;
  if (!fn) {
    void* p = nullptr;
    cudaDriverEntryPointQueryResult qr;
    cudaGetDriverEntryPoint("cuTensorMapEncodeTiled", &p, cudaEnableDefault, &qr);
    fn = (EncodeFn)p;
    cudaFuncSetAttribute(fused_kernel, cudaFuncAttributeMaxDynamicSharedMemorySize, SM_TOTAL);
  }
  Maps maps;
  {
    cuuint64_t d[3] = {64, 2048, 8}, s[2] = {1024, 128}; cuuint32_t b[3] = {64, 64, 3};
    encode(fn, &maps.x, x, 3, d, s, b);
  }
  {
    cuuint64_t d[2] = {1536, 512}, s[1] = {3072}; cuuint32_t b[2] = {64, 192};
    encode(fn, &maps.w, wqkv, 2, d, s, b);
  }
  {
    cuuint64_t d[2] = {512, 512}, s[1] = {1024}; cuuint32_t b[2] = {64, 192};
    encode(fn, &maps.wo, wo, 2, d, s, b);
  }
  {
    cuuint64_t d[3] = {176, 7, 512}, d7[3] = {144, 1, 512}, s[2] = {352, 2752}; cuuint32_t b[3] = {64, 1, 32};
    encode(fn, &maps.g, wg, 3, d, s, b);
    encode(fn, &maps.u, wu, 3, d, s, b);
    encode(fn, &maps.g7, wg + 1232, 3, d7, s, b);
    encode(fn, &maps.u7, wu + 1232, 3, d7, s, b);
  }
  {
    cuuint64_t d[2] = {512, 1376}, s[1] = {1024}; cuuint32_t b[2] = {64, 176};
    encode(fn, &maps.d, wd, 2, d, s, b);
  }
  fused_kernel<<<NCTA, 384, SM_TOTAL>>>(maps, x, wphi, wo, wg, wu, wd, (__nv_bfloat16*)d_out);
}
```

```cpp
#include <cuda_runtime.h>
#include <cuda_bf16.h>
#include <cuda.h>
#include <stdint.h>

#define SAFE_WAIT 0

namespace {

constexpr int NCTA   = 128;
constexpr int SLOT   = 24576;
constexpr int NSLOT  = 9;
constexpr int NSTAGE = 47;

constexpr int ST_X0   = 0;
constexpr int ST_WK   = 3;
constexpr int ST_X1   = 6;
constexpr int ST_SCR0 = 9;
constexpr int ST_WV   = 10;
constexpr int ST_SCR1 = 13;
constexpr int ST_WQ   = 14;
constexpr int ST_WO   = 17;
constexpr int ST_XC   = 20;
constexpr int ST_GU   = 23;
constexpr int ST_D    = 39;

__host__ __device__ constexpr int st_empty_cnt(int d) {
  return ((d < 3 || (d >= 6 && d < 9) || (d >= ST_XC && d < ST_GU)) ? 4 : 2) * (d + 9 >= ST_GU ? 2 : 1);
}

constexpr uint32_t SM_BASE = 1024;
constexpr int SM_ONES = NSLOT * SLOT;
constexpr int SM_WPHI = SM_ONES + 2048;
constexpr int SM_KVS  = SM_WPHI + 2048;
constexpr int SM_KV32 = 4 * SLOT + 16384;
constexpr int SM_BAR  = SM_KVS + 6144;
constexpr int SM_FULL  = SM_BAR;
constexpr int SM_EMPTY = SM_BAR + NSTAGE * 8;
constexpr int SM_MISCB = SM_BAR + 2 * NSTAGE * 8;
constexpr int SM_KVB   = SM_MISCB + 8;
constexpr int SM_EPOCH = SM_KVB + 8;
constexpr int SM_XF    = SM_EPOCH + 8;
constexpr int SM_XE    = SM_XF + 16 * 8;
constexpr int SM_TOTAL = SM_BAR + 1024;

static_assert(SM_TOTAL == 232448 && SM_XE + 12 * 8 <= SM_TOTAL, "smem budget");

struct Maps { CUtensorMap x, w, wo, g, u, g7, u7, d; };

__device__ __align__(128) uint4    g_o[32][8][4][4][32];
__device__ __align__(128) uint4    g_h[32][8][4][4][32];
__device__ __align__(128) uint32_t g_hx[32][8][4][32];
__device__ __align__(128) uint2    g_st[32][8][64];
__device__ __align__(128) uint4    g_hh[32][8][11][4][32];
__device__ __align__(128) uint4    g_part[32][8][4][4][4][32];
__device__ __align__(128) float g_kv[8][2048 + 128];
__device__ __align__(128) unsigned g_kvcnt[8 * 32];
__device__ unsigned g_start;

__device__ __forceinline__ uint32_t smem_u32(const void* p) { return (uint32_t)__cvta_generic_to_shared(p); }
__device__ __forceinline__ void mbar_init(uint32_t bar, int cnt) {
  asm volatile("mbarrier.init.shared::cta.b64 [%0], %1;" ::"r"(bar), "r"(cnt) : "memory");
}
__device__ __forceinline__ void mbar_expect_tx(uint32_t bar, uint32_t bytes) {
  asm volatile("mbarrier.arrive.expect_tx.shared::cta.b64 _, [%0], %1;" ::"r"(bar), "r"(bytes) : "memory");
}
__device__ __forceinline__ void mbar_arrive(uint32_t bar) {
  asm volatile("mbarrier.arrive.shared::cta.b64 _, [%0];" ::"r"(bar) : "memory");
}
__device__ __forceinline__ void mbar_arrive_cluster(uint32_t bar, uint32_t rank) {
  asm volatile("{\n.reg .b32 ra;\nmapa.shared::cluster.u32 ra, %0, %1;\n"
               "mbarrier.arrive.shared::cluster.b64 _, [ra];\n}" ::"r"(bar), "r"(rank) : "memory");
}
__device__ __forceinline__ void mbar_wait_p(uint32_t bar, uint32_t parity) {
  asm volatile("{\n.reg .pred p;\nW: mbarrier.try_wait.parity.shared::cta.b64 p, [%0], %1;\n@!p bra W;\n}" ::"r"(bar), "r"(parity) : "memory");
}
__device__ __forceinline__ void mbar_wait(uint32_t bar) { mbar_wait_p(bar, 0); }
__device__ __forceinline__ bool elect_one() {
  uint32_t p;
  asm volatile("{\n.reg .pred P;\nelect.sync _|P, 0xffffffff;\nselp.u32 %0, 1, 0, P;\n}" : "=r"(p));
  return p != 0;
}
__device__ __forceinline__ void bar_sync(int id, int n)   { asm volatile("bar.sync %0, %1;" ::"r"(id), "r"(n) : "memory"); }
__device__ __forceinline__ void bar_arrive(int id, int n) { asm volatile("bar.arrive %0, %1;" ::"r"(id), "r"(n) : "memory"); }
__device__ __forceinline__ void fence_async_smem() { asm volatile("fence.proxy.async.shared::cta;" ::: "memory"); }
__device__ __forceinline__ void wg_fence()  { asm volatile("wgmma.fence.sync.aligned;" ::: "memory"); }
__device__ __forceinline__ void wg_commit() { asm volatile("wgmma.commit_group.sync.aligned;" ::: "memory"); }
template <int N> __device__ __forceinline__ void wg_wait() { asm volatile("wgmma.wait_group.sync.aligned %0;" ::"n"(N) : "memory"); }
#define DESC(off) (db + ((uint32_t)(off) >> 4))
__device__ __forceinline__ void tma2d(uint32_t dst, const CUtensorMap* m, int c0, int c1, uint32_t bar) {
  asm volatile("cp.async.bulk.tensor.2d.shared::cluster.global.mbarrier::complete_tx::bytes [%0], [%1, {%3, %4}], [%2];"
               ::"r"(dst), "l"(m), "r"(bar), "r"(c0), "r"(c1) : "memory");
}
__device__ __forceinline__ void tma2d_mc(uint32_t dst, const CUtensorMap* m, int c0, int c1, uint32_t bar) {
  asm volatile("cp.async.bulk.tensor.2d.shared::cluster.global.mbarrier::complete_tx::bytes.multicast::cluster [%0], [%1, {%3, %4}], [%2], %5;"
               ::"r"(dst), "l"(m), "r"(bar), "r"(c0), "r"(c1), "h"((uint16_t)3) : "memory");
}
__device__ __forceinline__ void tma3d(uint32_t dst, const CUtensorMap* m, int c0, int c1, int c2, uint32_t bar) {
  asm volatile("cp.async.bulk.tensor.3d.shared::cluster.global.mbarrier::complete_tx::bytes [%0], [%1, {%3, %4, %5}], [%2];"
               ::"r"(dst), "l"(m), "r"(bar), "r"(c0), "r"(c1), "r"(c2) : "memory");
}
__device__ __forceinline__ void tma3d_mc(uint32_t dst, const CUtensorMap* m, int c0, int c1, int c2, uint32_t bar) {
  asm volatile("cp.async.bulk.tensor.3d.shared::cluster.global.mbarrier::complete_tx::bytes.multicast::cluster [%0], [%1, {%3, %4, %5}], [%2], %6;"
               ::"r"(dst), "l"(m), "r"(bar), "r"(c0), "r"(c1), "r"(c2), "h"((uint16_t)3) : "memory");
}
__device__ __forceinline__ void ldsm4(uint32_t (&r)[4], uint32_t addr) {
  asm volatile("ldmatrix.sync.aligned.m8n8.x4.shared.b16 {%0,%1,%2,%3}, [%4];"
               : "=r"(r[0]), "=r"(r[1]), "=r"(r[2]), "=r"(r[3]) : "r"(addr) : "memory");
}
__device__ __forceinline__ void ldsm4t(uint32_t (&r)[4], uint32_t addr) {
  asm volatile("ldmatrix.sync.aligned.m8n8.x4.trans.shared.b16 {%0,%1,%2,%3}, [%4];"
               : "=r"(r[0]), "=r"(r[1]), "=r"(r[2]), "=r"(r[3]) : "r"(addr) : "memory");
}
__device__ __forceinline__ void stsm4(uint32_t addr, uint32_t r0, uint32_t r1, uint32_t r2, uint32_t r3) {
  asm volatile("stmatrix.sync.aligned.m8n8.x4.shared.b16 [%0], {%1,%2,%3,%4};"
               ::"r"(addr), "r"(r0), "r"(r1), "r"(r2), "r"(r3) : "memory");
}
__device__ __forceinline__ void mma16816(float (&c)[4], const uint32_t (&a)[4], uint32_t b0, uint32_t b1) {
  asm volatile("mma.sync.aligned.m16n8k16.row.col.f32.bf16.bf16.f32 {%0,%1,%2,%3},{%4,%5,%6,%7},{%8,%9},{%0,%1,%2,%3};"
               : "+f"(c[0]), "+f"(c[1]), "+f"(c[2]), "+f"(c[3])
               : "r"(a[0]), "r"(a[1]), "r"(a[2]), "r"(a[3]), "r"(b0), "r"(b1));
}
__device__ __forceinline__ void add_frag(float (&c)[32], const uint32_t (&a)[4][4], uint32_t id) {
#pragma unroll
  for (int i = 0; i < 8; i++)
    asm volatile("mma.sync.aligned.m16n8k8.row.col.f32.bf16.bf16.f32 {%0,%1,%2,%3},{%4,%5},{%6},{%0,%1,%2,%3};"
                 : "+f"(c[4 * i]), "+f"(c[4 * i + 1]), "+f"(c[4 * i + 2]), "+f"(c[4 * i + 3])
                 : "r"(a[i >> 1][(i & 1) * 2]), "r"(a[i >> 1][(i & 1) * 2 + 1]), "r"(id));
}
__device__ __forceinline__ uint32_t pack2(float lo, float hi) {
  uint32_t r; asm("cvt.rn.bf16x2.f32 %0, %1, %2;" : "=r"(r) : "f"(hi), "f"(lo)); return r;
}
__device__ __forceinline__ float blo(uint32_t w) { return __uint_as_float(w << 16); }
__device__ __forceinline__ float bhi(uint32_t w) { return __uint_as_float(w & 0xFFFF0000u); }
__device__ __forceinline__ uint32_t hsub2(uint32_t a, uint32_t b) { uint32_t r; asm("sub.rn.bf16x2 %0, %1, %2;" : "=r"(r) : "r"(a), "r"(b)); return r; }
__device__ __forceinline__ uint32_t hmax2(uint32_t a, uint32_t b) { uint32_t r; asm("max.bf16x2 %0, %1, %2;" : "=r"(r) : "r"(a), "r"(b)); return r; }
__device__ __forceinline__ uint32_t hmin2(uint32_t a, uint32_t b) { uint32_t r; asm("min.bf16x2 %0, %1, %2;" : "=r"(r) : "r"(a), "r"(b)); return r; }
__device__ __forceinline__ float ex2(float x) { float r; asm("ex2.approx.ftz.f32 %0, %1;" : "=f"(r) : "f"(x)); return r; }
__device__ __forceinline__ float rcp(float x) { float r; asm("rcp.approx.ftz.f32 %0, %1;" : "=f"(r) : "f"(x)); return r; }
__device__ __forceinline__ void ld_rlx4(uint32_t (&r)[4], const uint4* p) {
  asm volatile("{\n.reg .b128 v;\nld.relaxed.gpu.global.b128 v, [%4];\nmov.b128 {%0,%1,%2,%3}, v;\n}"
               : "=r"(r[0]), "=r"(r[1]), "=r"(r[2]), "=r"(r[3]) : "l"(p) : "memory");
}
__device__ __forceinline__ void st_rlx4(uint4* p, uint32_t a, uint32_t b, uint32_t c, uint32_t d) {
  asm volatile("st.relaxed.gpu.global.v4.b32 [%0], {%1,%2,%3,%4};" ::"l"(p), "r"(a), "r"(b), "r"(c), "r"(d) : "memory");
}
__device__ __forceinline__ void st_rlx2(uint2* p, uint32_t a, uint32_t b) {
  asm volatile("{\n.reg .b64 v;\nmov.b64 v, {%1,%2};\nst.relaxed.gpu.global.b64 [%0], v;\n}" ::"l"(p), "r"(a), "r"(b) : "memory");
}
__device__ __forceinline__ uint32_t ld_rlx1(const uint32_t* p) {
  uint32_t r; asm volatile("ld.relaxed.gpu.global.b32 %0, [%1];" : "=r"(r) : "l"(p) : "memory"); return r;
}
__device__ __forceinline__ void st_rlx1(uint32_t* p, uint32_t a) {
  asm volatile("st.relaxed.gpu.global.b32 [%0], %1;" ::"l"(p), "r"(a) : "memory");
}
__device__ __forceinline__ void ld_rlx2(uint32_t& a, uint32_t& b, const uint2* p) {
  asm volatile("{\n.reg .b64 v;\nld.relaxed.gpu.b64 v, [%2];\nmov.b64 {%0,%1}, v;\n}" : "=r"(a), "=r"(b) : "l"(p) : "memory");
}
__device__ __forceinline__ void bulk_g2s(uint32_t dst, const void* src, uint32_t bytes, uint32_t bar) {
  asm volatile("cp.async.bulk.shared::cluster.global.mbarrier::complete_tx::bytes [%0], [%1], %2, [%3];"
               ::"r"(dst), "l"(src), "r"(bytes), "r"(bar) : "memory");
}
__device__ __forceinline__ uint32_t tg(uint32_t w, uint32_t T) { return (w & 0xFFFFFFFEu) | T; }
__device__ __forceinline__ uint32_t bad4(uint32_t a, uint32_t b, uint32_t c, uint32_t d, uint32_t T) {
  uint32_t u, v;
  asm("lop3.b32 %0, %1, %2, %3, 0x7E;" : "=r"(u) : "r"(a), "r"(b), "r"(T));
  asm("lop3.b32 %0, %1, %2, %3, 0x7E;" : "=r"(v) : "r"(c), "r"(d), "r"(T));
  asm("lop3.b32 %0, %1, %2, 1, 0xA8;" : "=r"(u) : "r"(u), "r"(v));
  return u;
}

__device__ __forceinline__ void ld_chunk(uint32_t (&a)[4][4], const uint4* p) {
#pragma unroll
  for (int s = 0; s < 4; s++) ld_rlx4(a[s], p + s * 32);
}
__device__ __forceinline__ void get_pair(uint32_t (&a)[4][4], uint32_t (&b)[4][4], const uint4* sp, const uint4* gp, uint32_t T) {
  int it = 0;
#pragma unroll 1
  do {
#pragma unroll
    for (int s = 0; s < 8; s++) {
      uint32_t (&r)[4] = s < 4 ? a[s & 3] : b[s & 3];
      asm volatile("{\n.reg .b128 v;\nld.relaxed.gpu.b128 v, [%4];\nmov.b128 {%0,%1,%2,%3}, v;\n}"
                   : "=r"(r[0]), "=r"(r[1]), "=r"(r[2]), "=r"(r[3]) : "l"(sp + (s >> 2) * 512 + (s & 3) * 32) : "memory");
    }
    sp = gp;
  } while (__any_sync(0xffffffffu, bad4(a[0][0], a[1][0], a[2][0], a[3][0], T) | bad4(b[0][0], b[1][0], b[2][0], b[3][0], T)) && ++it < (1 << 18));
}

__device__ __forceinline__ void wgmma_rs_n48(float (&d)[24], const uint32_t (&a)[4], uint32_t descB, int scaleD) {
  asm volatile("{\n.reg .pred p;\n.reg .b64 db;\nsetp.ne.b32 p, %29, 0;\nmov.b64 db, {%28, 0x40000040};\n"
    "wgmma.mma_async.sync.aligned.m64n48k16.f32.bf16.bf16 {%0,%1,%2,%3,%4,%5,%6,%7,%8,%9,%10,%11,%12,%13,%14,%15,%16,%17,%18,%19,%20,%21,%22,%23}, {%24,%25,%26,%27}, db, p, 1, 1, 1;\n}\n"
    : "+f"(d[0]),"+f"(d[1]),"+f"(d[2]),"+f"(d[3]),"+f"(d[4]),"+f"(d[5]),"+f"(d[6]),"+f"(d[7]),"+f"(d[8]),"+f"(d[9]),"+f"(d[10]),"+f"(d[11]),"+f"(d[12]),"+f"(d[13]),"+f"(d[14]),"+f"(d[15]),"+f"(d[16]),"+f"(d[17]),"+f"(d[18]),"+f"(d[19]),"+f"(d[20]),"+f"(d[21]),"+f"(d[22]),"+f"(d[23])
    : "r"(a[0]), "r"(a[1]), "r"(a[2]), "r"(a[3]), "r"(descB), "r"(scaleD));
}
__device__ __forceinline__ void wgmma_rs_n64(float (&d)[32], const uint32_t (&a)[4], uint32_t descB, int scaleD) {
  asm volatile("{\n.reg .pred p;\n.reg .b64 db;\nsetp.ne.b32 p, %37, 0;\nmov.b64 db, {%36, 0x40000040};\n"
    "wgmma.mma_async.sync.aligned.m64n64k16.f32.bf16.bf16 {%0,%1,%2,%3,%4,%5,%6,%7,%8,%9,%10,%11,%12,%13,%14,%15,%16,%17,%18,%19,%20,%21,%22,%23,%24,%25,%26,%27,%28,%29,%30,%31}, {%32,%33,%34,%35}, db, p, 1, 1, 1;\n}\n"
    : "+f"(d[0]),"+f"(d[1]),"+f"(d[2]),"+f"(d[3]),"+f"(d[4]),"+f"(d[5]),"+f"(d[6]),"+f"(d[7]),"+f"(d[8]),"+f"(d[9]),"+f"(d[10]),"+f"(d[11]),"+f"(d[12]),"+f"(d[13]),"+f"(d[14]),"+f"(d[15]),"+f"(d[16]),"+f"(d[17]),"+f"(d[18]),"+f"(d[19]),"+f"(d[20]),"+f"(d[21]),"+f"(d[22]),"+f"(d[23]),"+f"(d[24]),"+f"(d[25]),"+f"(d[26]),"+f"(d[27]),"+f"(d[28]),"+f"(d[29]),"+f"(d[30]),"+f"(d[31])
    : "r"(a[0]), "r"(a[1]), "r"(a[2]), "r"(a[3]), "r"(descB), "r"(scaleD));
}
__device__ __forceinline__ void wgmma_rs_n128(float (&d)[64], const uint32_t (&a)[4], uint32_t descB, int scaleD) {
  asm volatile("{\n.reg .pred p;\n.reg .b64 db;\nsetp.ne.b32 p, %69, 0;\nmov.b64 db, {%68, 0x40000040};\n"
    "wgmma.mma_async.sync.aligned.m64n128k16.f32.bf16.bf16 {%0,%1,%2,%3,%4,%5,%6,%7,%8,%9,%10,%11,%12,%13,%14,%15,%16,%17,%18,%19,%20,%21,%22,%23,%24,%25,%26,%27,%28,%29,%30,%31,%32,%33,%34,%35,%36,%37,%38,%39,%40,%41,%42,%43,%44,%45,%46,%47,%48,%49,%50,%51,%52,%53,%54,%55,%56,%57,%58,%59,%60,%61,%62,%63}, {%64,%65,%66,%67}, db, p, 1, 1, 1;\n}\n"
    : "+f"(d[0]),"+f"(d[1]),"+f"(d[2]),"+f"(d[3]),"+f"(d[4]),"+f"(d[5]),"+f"(d[6]),"+f"(d[7]),"+f"(d[8]),"+f"(d[9]),"+f"(d[10]),"+f"(d[11]),"+f"(d[12]),"+f"(d[13]),"+f"(d[14]),"+f"(d[15]),"+f"(d[16]),"+f"(d[17]),"+f"(d[18]),"+f"(d[19]),"+f"(d[20]),"+f"(d[21]),"+f"(d[22]),"+f"(d[23]),"+f"(d[24]),"+f"(d[25]),"+f"(d[26]),"+f"(d[27]),"+f"(d[28]),"+f"(d[29]),"+f"(d[30]),"+f"(d[31]),"+f"(d[32]),"+f"(d[33]),"+f"(d[34]),"+f"(d[35]),"+f"(d[36]),"+f"(d[37]),"+f"(d[38]),"+f"(d[39]),"+f"(d[40]),"+f"(d[41]),"+f"(d[42]),"+f"(d[43]),"+f"(d[44]),"+f"(d[45]),"+f"(d[46]),"+f"(d[47]),"+f"(d[48]),"+f"(d[49]),"+f"(d[50]),"+f"(d[51]),"+f"(d[52]),"+f"(d[53]),"+f"(d[54]),"+f"(d[55]),"+f"(d[56]),"+f"(d[57]),"+f"(d[58]),"+f"(d[59]),"+f"(d[60]),"+f"(d[61]),"+f"(d[62]),"+f"(d[63])
    : "r"(a[0]), "r"(a[1]), "r"(a[2]), "r"(a[3]), "r"(descB), "r"(scaleD));
}
__device__ __forceinline__ void wgmma_ss_n72_t11(float (&d)[36], uint32_t descA, uint32_t descB, int scaleD) {
  asm volatile("{\n.reg .pred p;\n.reg .b64 da, db;\nsetp.ne.b32 p, %38, 0;\nmov.b64 da, {%36, 0x40000040};\nmov.b64 db, {%37, 0x40000040};\n"
    "wgmma.mma_async.sync.aligned.m64n72k16.f32.bf16.bf16 {%0,%1,%2,%3,%4,%5,%6,%7,%8,%9,%10,%11,%12,%13,%14,%15,%16,%17,%18,%19,%20,%21,%22,%23,%24,%25,%26,%27,%28,%29,%30,%31,%32,%33,%34,%35}, da, db, p, 1, 1, 1, 1;\n}\n"
    : "+f"(d[0]),"+f"(d[1]),"+f"(d[2]),"+f"(d[3]),"+f"(d[4]),"+f"(d[5]),"+f"(d[6]),"+f"(d[7]),"+f"(d[8]),"+f"(d[9]),"+f"(d[10]),"+f"(d[11]),"+f"(d[12]),"+f"(d[13]),"+f"(d[14]),"+f"(d[15]),"+f"(d[16]),"+f"(d[17]),"+f"(d[18]),"+f"(d[19]),"+f"(d[20]),"+f"(d[21]),"+f"(d[22]),"+f"(d[23]),"+f"(d[24]),"+f"(d[25]),"+f"(d[26]),"+f"(d[27]),"+f"(d[28]),"+f"(d[29]),"+f"(d[30]),"+f"(d[31]),"+f"(d[32]),"+f"(d[33]),"+f"(d[34]),"+f"(d[35])
    : "r"(descA), "r"(descB), "r"(scaleD));
}

constexpr float LOG2E = 1.4426950408889634f;

__device__ __forceinline__ void feat_exp(const uint32_t (&P)[4], float (&e)[16]) {
  uint32_t a = hmax2(P[0], P[2]), b = hmax2(P[1], P[3]);
  uint32_t mx = hmax2(__byte_perm(a, b, 0x5410), __byte_perm(a, b, 0x7632));
  a = hmin2(P[0], P[2]); b = hmin2(P[1], P[3]);
  uint32_t mn = hmin2(__byte_perm(a, b, 0x5410), __byte_perm(a, b, 0x7632));
  mx = hmax2(mx, __shfl_xor_sync(0xffffffffu, mx, 1));
  mn = hmin2(mn, __shfl_xor_sync(0xffffffffu, mn, 1));
  mx = hmax2(mx, __shfl_xor_sync(0xffffffffu, mx, 2));
  mn = hmin2(mn, __shfl_xor_sync(0xffffffffu, mn, 2));
  float mx0 = -blo(mx) * LOG2E, mx1 = -bhi(mx) * LOG2E, mn0 = blo(mn) * LOG2E, mn1 = bhi(mn) * LOG2E;
  float v[8] = {blo(P[0]), bhi(P[0]), blo(P[1]), bhi(P[1]), blo(P[2]), bhi(P[2]), blo(P[3]), bhi(P[3])};
#pragma unroll
  for (int i = 0; i < 8; i++) {
    bool r1 = (i >> 1) & 1;
    e[i]     = ex2(fmaf(v[i],  LOG2E, r1 ? mx1 : mx0));
    e[8 + i] = ex2(fmaf(v[i], -LOG2E, r1 ? mn1 : mn0));
  }
}

__global__ void __cluster_dims__(2, 1, 1) __launch_bounds__(384, 1)
fused_kernel(const __grid_constant__ Maps maps, const __nv_bfloat16* __restrict__ x, const __nv_bfloat16* __restrict__ wphi,
             const __nv_bfloat16* __restrict__ wo, const __nv_bfloat16* __restrict__ wg_, const __nv_bfloat16* __restrict__ wu_,
             const __nv_bfloat16* __restrict__ wd_, __nv_bfloat16* __restrict__ out) {
  extern __shared__ __align__(1024) unsigned char smem[];
  const uint32_t sb = smem_u32(smem);
  const int tid = threadIdx.x, lane = tid & 31;
  const int warp = __shfl_sync(0xffffffffu, tid >> 5, 0);
  const uint32_t rank = blockIdx.x & 1;
  const int cl = blockIdx.x >> 1;
  int quad, qi;
  if (cl < 4) { quad = 15; qi = cl; }
  else if (cl < 36) { quad = (cl - 4) & 7; qi = (cl - 4) >> 3; }
  else { qi = (cl - 36) / 7; quad = 8 + (cl - 36) - 7 * qi; }
  const int rb = quad, hg = 2 * qi + rank;
  const int rb3 = (quad & ~1) + rank, jf = 4 * (quad & 1) + qi;

  if (warp < 8) {
    asm volatile("setmaxnreg.inc.sync.aligned.u32 240;");
    if (elect_one()) {
#pragma unroll 1
      for (int d = warp; d + 9 < NSTAGE; d += 8) {
        mbar_init(sb + SM_EMPTY + d * 8, st_empty_cnt(d));
        mbar_init(sb + SM_FULL + (d + 9) * 8, 1);
        mbar_expect_tx(sb + SM_FULL + (d + 9) * 8, d + 9 >= ST_D ? 22528 : SLOT);
      }
      asm volatile("fence.mbarrier_init.release.cluster;" ::: "memory");
    }
    __syncwarp();
    bar_sync(0, 352);
    asm volatile("barrier.cluster.arrive.relaxed.aligned;" ::: "memory");
    const int wg = warp >> 2, wq = warp & 3, g = lane >> 2, t = lane & 3;
    const bool lead = (tid & 127) == 0;
    constexpr uint32_t db = (SM_BASE >> 4) | (512u << 16);
    auto release = [&](int d) {
      const int s = d + NSLOT;
      mbar_arrive_cluster(sb + SM_EMPTY + d * 8, s >= ST_GU ? (uint32_t)(s & 1) : rank);
    };
    const uint32_t lrow = (uint32_t)(wq * 16 + (lane & 7) + ((lane >> 3) & 1) * 8) * 128;
    const uint32_t lx = lane & 7, lhi = lane >> 4;
    if (wg == 1) bar_arrive(4, 256);

    float r0, r1;
    uint32_t E[4][8];
    uint32_t T = 0;
    {
      uint32_t A[32][4];
      const int sx = wg ? ST_X1 : ST_X0;
      {
        const uint32_t base = sb + sx * SLOT + lrow, baseb = sb + sx * SLOT + (wq * 16 + lx + lhi * 8) * 128;
        float cs[2][4], c0[2][4], c1[2][4];
#pragma unroll
        for (int i = 0; i < 4; i++) { cs[0][i] = cs[1][i] = c0[0][i] = c0[1][i] = c1[0][i] = c1[1][i] = 0.f; }
        uint32_t bt[2][4][4];
        if (wg == 1) bar_sync(13, 256);
#pragma unroll
        for (int c = -1; c < 8; c++) {
          if (c < 7) {
            const int n = c + 1;
            if (n % 3 == 0) mbar_wait(sb + SM_FULL + (sx + n / 3) * 8);
#pragma unroll
            for (int k = 0; k < 4; k++) {
              ldsm4(A[4 * n + k], base + n * 8192 + (((2 * k + lhi) ^ lx) << 4));
              ldsm4(bt[n & 1][k], baseb + n * 8192 + (((2 * k + ((lane >> 3) & 1)) ^ lx) << 4));
            }
          }
          if (c >= 0) {
#pragma unroll
            for (int k = 0; k < 4; k++) {
              const uint32_t (&f)[4] = A[4 * c + k];
              mma16816(cs[k & 1], f, 0x3F803F80u, 0x3F803F80u);
              mma16816(c0[k & 1], f, bt[c & 1][k][0], bt[c & 1][k][1]);
              mma16816(c1[k & 1], f, bt[c & 1][k][2], bt[c & 1][k][3]);
            }
          }
        }
        if (wg == 0) bar_arrive(13, 256);
        const float s0 = (cs[0][0] + cs[1][0]) * (1.f / 512.f), s1 = (cs[0][2] + cs[1][2]) * (1.f / 512.f);
        asm volatile("barrier.cluster.wait.aligned;" ::: "memory");
        if (lane < 3) release(sx + lane);
        const uint32_t m0 = pack2(s0, s0), m1 = pack2(s1, s1);
        float q0 = (g & 1) ? c0[0][1] + c0[1][1] : c0[0][0] + c0[1][0];
        float q1 = (g & 1) ? c1[0][3] + c1[1][3] : c1[0][2] + c1[1][2];
        q0 = __shfl_sync(0xffffffffu, q0, (lane & ~3) | (g >> 1));
        q1 = __shfl_sync(0xffffffffu, q1, (lane & ~3) | (g >> 1));
        r0 = rsqrtf(fmaxf(q0 * (1.f / 512.f) - s0 * s0, 0.f) + 1e-5f);
        r1 = rsqrtf(fmaxf(q1 * (1.f / 512.f) - s1 * s1, 0.f) + 1e-5f);
#pragma unroll
        for (int ks = 0; ks < 32; ks++) {
          A[ks][0] = hsub2(A[ks][0], m0); A[ks][1] = hsub2(A[ks][1], m1);
          A[ks][2] = hsub2(A[ks][2], m0); A[ks][3] = hsub2(A[ks][3], m1);
        }
      }
      const uint32_t wpa = sb + SM_WPHI + ((lane & 7) + ((lane >> 3) & 1) * 8) * 32 + lhi * 16;
      const uint32_t scr = sb + (wg ? (ST_SCR1 % NSLOT) : (ST_SCR0 % NSLOT)) * SLOT;
#pragma unroll 1
      for (int ps = 0; ps < 3; ps++) {
        const int st0 = ps == 0 ? ST_WK : (ps == 1 ? ST_WV : ST_WQ);
        const uint32_t wdesc = DESC((ps == 0 ? ST_WK % NSLOT : (ps == 1 ? ST_WV % NSLOT : ST_WQ % NSLOT)) * SLOT);
        float acc[32];
        bar_sync(4 + wg, 256);
#pragma unroll
        for (int i = 0; i < 3; i++) {
          mbar_wait(sb + SM_FULL + (st0 + i) * 8);
          wg_fence();
#pragma unroll
          for (int kk = 0; kk < (i < 2 ? 12 : 8); kk++)
            wgmma_rs_n64(acc, A[12 * i + kk], wdesc + ((i * SLOT + kk * 2048) >> 4), (i | kk) != 0);
          wg_commit();
          if (i == 1) { wg_wait<1>(); if (lead) release(st0); }
        }
        if (ps == 1 && wg == 0) bar_arrive(5, 256);
        uint32_t a[4][4], b[4][4];
        mbar_wait(sb + SM_MISCB);
        T = (*reinterpret_cast<volatile unsigned*>(smem + SM_EPOCH) & 1) ^ 1;
#pragma unroll
        for (int h = 0; h < 4; h++) ldsm4t(b[h], wpa + h * 512);
        wg_wait<0>();
        if ((tid & 127) < 2) release(st0 + 1 + (tid & 1));
#pragma unroll
        for (int h = 0; h < 4; h++) {
          a[h][0] = pack2(acc[8 * h + 0] * r0, acc[8 * h + 1] * r0); a[h][1] = pack2(acc[8 * h + 2] * r1, acc[8 * h + 3] * r1);
          a[h][2] = pack2(acc[8 * h + 4] * r0, acc[8 * h + 5] * r0); a[h][3] = pack2(acc[8 * h + 6] * r1, acc[8 * h + 7] * r1);
        }
        if (ps != 1) {
          {
            float pp[4][2][4];
#pragma unroll
            for (int h = 0; h < 4; h++) {
#pragma unroll
              for (int i = 0; i < 4; i++) { pp[h][0][i] = 0.f; pp[h][1][i] = 0.f; }
              mma16816(pp[h][0], a[h], b[h][0], b[h][1]);
              mma16816(pp[h][1], a[h], b[h][2], b[h][3]);
            }
#pragma unroll
            for (int h = 0; h < 4; h++) {
              a[h][0] = pack2(pp[h][0][0], pp[h][0][1]); a[h][1] = pack2(pp[h][0][2], pp[h][0][3]);
              a[h][2] = pack2(pp[h][1][0], pp[h][1][1]); a[h][3] = pack2(pp[h][1][2], pp[h][1][3]);
            }
          }
          if (ps == 0 || wg == 0) bar_arrive(4 + (wg ^ 1), 256);
          if (ps == 0) mbar_wait(sb + SM_EMPTY + (wg ? ST_SCR1 - NSLOT : ST_SCR0 - NSLOT) * 8);
#pragma unroll 1
          for (int hp = 0; hp < 2; hp++) {
            float e[2][16];
            feat_exp(a[0], e[0]);
            feat_exp(a[1], e[1]);
            if (ps == 0) {
#pragma unroll
              for (int h = 0; h < 2; h++) {
                const float (&f)[16] = e[h];
                float sp0 = (f[0] + f[1]) + (f[4] + f[5]), sp1 = (f[2] + f[3]) + (f[6] + f[7]);
                float sn0 = (f[8] + f[9]) + (f[12] + f[13]), sn1 = (f[10] + f[11]) + (f[14] + f[15]);
                sp0 += __shfl_xor_sync(0xffffffffu, sp0, 1); sp1 += __shfl_xor_sync(0xffffffffu, sp1, 1);
                sn0 += __shfl_xor_sync(0xffffffffu, sn0, 1); sn1 += __shfl_xor_sync(0xffffffffu, sn1, 1);
                sp0 += __shfl_xor_sync(0xffffffffu, sp0, 2); sp1 += __shfl_xor_sync(0xffffffffu, sp1, 2);
                sn0 += __shfl_xor_sync(0xffffffffu, sn0, 2); sn1 += __shfl_xor_sync(0xffffffffu, sn1, 2);
                sp0 = rcp(sp0); sp1 = rcp(sp1); sn0 = rcp(sn0); sn1 = rcp(sn1);
                const uint32_t dst = scr + hp * 8192 + lrow;
                stsm4(dst + (((h * 4 + lhi) ^ lx) << 4), pack2(f[0] * sp0, f[1] * sp0), pack2(f[2] * sp1, f[3] * sp1),
                      pack2(f[4] * sp0, f[5] * sp0), pack2(f[6] * sp1, f[7] * sp1));
                stsm4(dst + (((h * 4 + 2 + lhi) ^ lx) << 4), pack2(f[8] * sn0, f[9] * sn0), pack2(f[10] * sn1, f[11] * sn1),
                      pack2(f[12] * sn0, f[13] * sn0), pack2(f[14] * sn1, f[15] * sn1));
              }
            } else {
#pragma unroll
              for (int i = 0; i < 16; i++) {
                A[i >> 2][i & 3] = A[4 + (i >> 2)][i & 3];
                A[4 + (i >> 2)][i & 3] = pack2(e[i >> 3][2 * (i & 7)], e[i >> 3][2 * (i & 7) + 1]);
              }
            }
#pragma unroll
            for (int i = 0; i < 4; i++) { a[0][i] = a[2][i]; a[1][i] = a[3][i]; }
          }
        } else {
#pragma unroll
          for (int h = 0; h < 4; h++) stsm4(scr + 16384 + lrow + (((2 * h + lhi) ^ lx) << 4), a[h][0], a[h][1], a[h][2], a[h][3]);
          fence_async_smem();
          bar_sync(3, 256);
          float kv[36];
          wg_fence();
#pragma unroll
          for (int ks = 0; ks < 8; ks++) {
            const uint32_t sk = (ks < 4 ? (ST_SCR0 % NSLOT) : (ST_SCR1 % NSLOT)) * SLOT + (ks & 3) * 2048;
            const uint32_t dv = (DESC(sk + 16384) & 0xFFFFu) | (((SM_ONES - sk - 16384) >> 4) << 16);
            wgmma_ss_n72_t11(kv, DESC(sk) + wg * 512, dv, ks != 0);
          }
          wg_commit();
          if (wg == 1) bar_arrive(4, 256);
          wg_wait<0>();
          if (lead) { mbar_arrive(sb + SM_EMPTY + ST_SCR0 * 8); mbar_arrive(sb + SM_EMPTY + ST_SCR1 * 8); }
          const int hl = 2 * wg + (wq >> 1), f = (wq & 1) * 16 + g;
          float* kvp = reinterpret_cast<float*>(smem + 2 * SLOT) + (hl * 32 + f) * 16 + 2 * t;
          float c[8];
#pragma unroll
          for (int i = 0; i < 8; i++) c[i] = hl >= 2 ? (hl == 3 ? kv[24 + i] : kv[16 + i]) : (hl == 1 ? kv[8 + i] : kv[i]);
#pragma unroll
          for (int n = 0; n < 2; n++) {
            *reinterpret_cast<float2*>(kvp + n * 8) = make_float2(c[4 * n], c[4 * n + 1]);
            *reinterpret_cast<float2*>(kvp + n * 8 + 128) = make_float2(c[4 * n + 2], c[4 * n + 3]);
          }
          if (t < 2) reinterpret_cast<float*>(smem + 2 * SLOT)[2048 + hl * 32 + f + t * 8] = t ? kv[34] : kv[32];
          fence_async_smem();
          bar_sync(6, 320);
        }
      }
#pragma unroll
      for (int i = 0; i < 32; i++) E[i >> 3][i & 7] = A[i >> 2][i & 3];
    }
    const int rh = 2 * rb + wg;
#define IDF ((g >> 1) == t ? ((g & 1) ? 0x3F800000u : 0x00003F80u) : 0u)
    const uint4* xb = reinterpret_cast<const uint4*>(smem + 2 * SLOT) + wq * 128 + lane;
    if (wg == 0) {
      mbar_wait(sb + SM_KVB);
      const int r = tid;
      const float4* src = reinterpret_cast<const float4*>(smem + SM_KV32) + r;
#pragma unroll
      for (int i = 0; i < 4; i++) {
        const float4 a = src[i * 128];
        *reinterpret_cast<uint2*>(smem + SM_KVS + (i * 32 + (r >> 2)) * 48 + (r & 3) * 8) = make_uint2(pack2(a.x, a.y), pack2(a.z, a.w));
      }
      const uint32_t zz = pack2(reinterpret_cast<const float*>(smem + SM_ONES)[r], 1.0f);
      *reinterpret_cast<uint4*>(smem + SM_KVS + r * 48 + 32) = make_uint4(zz, zz, zz, zz);
      bar_sync(1, 128);
    }
    {
      uint4* op = &g_o[rh][hg][wq][0][lane];
      if (wg == 1) bar_sync(7, 256);
#pragma unroll 1
      for (int hp = 0; hp < 2; hp++) {
#pragma unroll
      for (int h = 0; h < 2; h++) {
        uint32_t b0[4], b1[4], b2[4];
        const uint32_t kb = sb + SM_KVS + ((2 * hp + h) * 32 + lane) * 48;
        ldsm4t(b0, kb); ldsm4t(b1, kb + 16); ldsm4t(b2, kb + 32);
        const uint32_t ep[4] = {E[h][0], E[h][1], E[h][2], E[h][3]}, en[4] = {E[h][4], E[h][5], E[h][6], E[h][7]};
        float np0[4] = {0, 0, 0, 0}, np1[4] = {0, 0, 0, 0}, nn0[4] = {0, 0, 0, 0}, nn1[4] = {0, 0, 0, 0}, dp[4] = {0, 0, 0, 0}, dn[4] = {0, 0, 0, 0};
        mma16816(dp, ep, b2[0], b2[1]);  mma16816(dn, en, b2[2], b2[3]);
        mma16816(np0, ep, b0[0], b0[1]); mma16816(nn0, en, b0[2], b0[3]);
        mma16816(np1, ep, b1[0], b1[1]); mma16816(nn1, en, b1[2], b1[3]);
        const float i0 = rcp(fmaf(dp[0], dn[1], fmaf(dn[0], dp[1], 1e-6f * dp[1] * dn[1])));
        const float i1 = rcp(fmaf(dp[2], dn[3], fmaf(dn[2], dp[3], 1e-6f * dp[3] * dn[3])));
        const float cp0 = dn[1] * i0, cn0 = dp[1] * i0, cp1 = dn[3] * i1, cn1 = dp[3] * i1;
        st_rlx4(op + (2 * hp + h) * 32,
                tg(pack2(fmaf(np0[0], cp0, nn0[0] * cn0), fmaf(np0[1], cp0, nn0[1] * cn0)), T),
                pack2(fmaf(np0[2], cp1, nn0[2] * cn1), fmaf(np0[3], cp1, nn0[3] * cn1)),
                pack2(fmaf(np1[0], cp0, nn1[0] * cn0), fmaf(np1[1], cp0, nn1[1] * cn0)),
                pack2(fmaf(np1[2], cp1, nn1[2] * cn1), fmaf(np1[3], cp1, nn1[3] * cn1)));
      }
#pragma unroll
        for (int i = 0; i < 8; i++) { E[0][i] = E[2][i]; E[1][i] = E[3][i]; }
      }
    }
    if (wg == 0) bar_arrive(7, 256);
    bar_arrive(10 + wg, 160);

    {
      uint32_t xr[4][4];
      {
        const uint32_t* xp = reinterpret_cast<const uint32_t*>(x + (size_t)(rh * 64 + wq * 16 + g) * 512 + hg * 64 + 2 * t);
#pragma unroll
        for (int i = 0; i < 8; i++) { xr[i >> 1][(i & 1) * 2] = __ldg(xp + 4 * i); xr[i >> 1][(i & 1) * 2 + 1] = __ldg(xp + 8 * 256 + 4 * i); }
      }
      uint32_t A[8][4][4];
      const uint4* op = &g_o[rh][0][wq][0][lane];
      float acc[32];
#pragma unroll
      for (int i = 0; i < 32; i++) acc[i] = 0.f;
      add_frag(acc, xr, IDF);
#pragma unroll
      for (int p = -1; p < 4; p++) {
        if (p < 3) {
          mbar_wait(sb + SM_XF + (wg * 4 + p + 1) * 8);
          get_pair(A[2 * p + 2], A[2 * p + 3], xb + (p + 1) * 1024, op + (p + 1) * 1024, T);
          if (lane == 0) mbar_arrive(sb + SM_XE + (wg * 4 + p + 1) * 8);
        }
        if (p == 0 && wg == 1) bar_sync(14, 256);
        if (p >= 0) {
          if (p != 2) mbar_wait(sb + SM_FULL + (ST_WO + (p + 1) / 2) * 8);
          wg_fence();
#pragma unroll
          for (int c = 2 * p; c < 2 * p + 2; c++)
#pragma unroll
            for (int s = 0; s < 4; s++)
              wgmma_rs_n64(acc, A[c][s], DESC(((ST_WO + c / 3) % NSLOT) * SLOT + ((c % 3) * 4 + s) * 2048), 1);
        }
      }
      wg_commit();
      if (wg == 0) bar_arrive(14, 256);
      wg_wait<0>();
      if ((tid & 127) < 3) release(ST_WO + (tid & 127));
      uint4* hp_ = &g_h[rh][hg][wq][0][lane];
      uint32_t hx = T;
#pragma unroll
      for (int s = 0; s < 4; s++) {
        const uint32_t h0 = pack2(acc[8 * s], acc[8 * s + 1]);
        st_rlx4(hp_ + s * 32, tg(h0, T), pack2(acc[8 * s + 2], acc[8 * s + 3]), pack2(acc[8 * s + 4], acc[8 * s + 5]), pack2(acc[8 * s + 6], acc[8 * s + 7]));
        hx |= (h0 & 1u) << (s + 1);
      }
      float s0 = 0.f, s1 = 0.f, q0 = 0.f, q1 = 0.f, q2 = 0.f, q3 = 0.f;
#pragma unroll
      for (int i = 0; i < 8; i++) {
        s0 += acc[4 * i] + acc[4 * i + 1]; s1 += acc[4 * i + 2] + acc[4 * i + 3];
        q0 = fmaf(acc[4 * i], acc[4 * i], q0); q2 = fmaf(acc[4 * i + 1], acc[4 * i + 1], q2);
        q1 = fmaf(acc[4 * i + 2], acc[4 * i + 2], q1); q3 = fmaf(acc[4 * i + 3], acc[4 * i + 3], q3);
      }
      q0 += q2; q1 += q3;
      {
        const bool up = t & 2;
        float s = (up ? s1 : s0) + __shfl_xor_sync(0xffffffffu, up ? s0 : s1, 2);
        float q = (up ? q1 : q0) + __shfl_xor_sync(0xffffffffu, up ? q0 : q1, 2);
        s += __shfl_xor_sync(0xffffffffu, s, 1);
        q += __shfl_xor_sync(0xffffffffu, q, 1);
        if (!(t & 1)) st_rlx2(&g_st[rh][hg][wq * 16 + g + (t >> 1) * 8], tg(__float_as_uint(s), T), __float_as_uint(q));
      }
      st_rlx1(&g_hx[rh][hg][wq][lane], hx);
    }
    bar_arrive(10 + wg, 160);

    const int rh3 = 2 * rb3 + wg;
    uint32_t HH[11][4], PH[11][4];
    const uint4* pp = &g_hh[rh3][jf ^ 1][0][wq][lane];
    {
      uint32_t A[8][4][4];
      const uint4* hp_ = &g_h[rh3][0][wq][0][lane];
      uint4* hhp = &g_hh[rh3][jf][0][wq][lane];
      const uint32_t dg = (db & 0xFFFFu) | (256u << 16);
      uint32_t m0, m1;
      mbar_wait(sb + SM_XF + ((2 + wg) * 4) * 8);
      {
        const uint2* sp = reinterpret_cast<const uint2*>(smem + SM_KV32 + wg * 4096) + 2 * t * 64 + wq * 16 + g;
        uint2 a0, a1, b0, b1;
        int it = 0;
#pragma unroll 1
        do {
          ld_rlx2(a0.x, a0.y, sp); ld_rlx2(a1.x, a1.y, sp + 64); ld_rlx2(b0.x, b0.y, sp + 8); ld_rlx2(b1.x, b1.y, sp + 72);
          sp = &g_st[rh3][2 * t][wq * 16 + g];
        } while (__any_sync(0xffffffffu, bad4(a0.x, a1.x, b0.x, b1.x, T)) && ++it < (1 << 18));
        float s0 = __uint_as_float(a0.x) + __uint_as_float(a1.x), q0 = __uint_as_float(a0.y) + __uint_as_float(a1.y);
        float s1 = __uint_as_float(b0.x) + __uint_as_float(b1.x), q1 = __uint_as_float(b0.y) + __uint_as_float(b1.y);
        s0 += __shfl_xor_sync(0xffffffffu, s0, 1); s1 += __shfl_xor_sync(0xffffffffu, s1, 1);
        q0 += __shfl_xor_sync(0xffffffffu, q0, 1); q1 += __shfl_xor_sync(0xffffffffu, q1, 1);
        s0 += __shfl_xor_sync(0xffffffffu, s0, 2); s1 += __shfl_xor_sync(0xffffffffu, s1, 2);
        q0 += __shfl_xor_sync(0xffffffffu, q0, 2); q1 += __shfl_xor_sync(0xffffffffu, q1, 2);
        s0 *= (1.f / 512.f); s1 *= (1.f / 512.f);
        r0 = rcp(fmaxf(q0 * (1.f / 512.f) - s0 * s0, 0.f) + 1e-5f);
        r1 = rcp(fmaxf(q1 * (1.f / 512.f) - s1 * s1, 0.f) + 1e-5f);
        m0 = pack2(s0, s0); m1 = pack2(s1, s1);
      }
#define UOFF(u) ((((ST_GU + (u) / 3) % NSLOT) * SLOT + ((u) % 3) * 8192) >> 4)
#define UNIT_PRE(u)  do { if ((u) % 3 == 0) mbar_wait(sb + SM_FULL + (ST_GU + (u) / 3) * 8); } while (0)
#define UNIT_POST(u) do { wg_commit(); if ((u) % 3 == 1 && (u) > 3) { wg_wait<2>(); if (lead) release(ST_GU + (u) / 3 - 1); } } while (0)
      float acc[64];
      const int rz = blockIdx.y;
#pragma unroll
      for (int ps = 0; ps < 2; ps++) {
        wg_fence();
#pragma unroll
        for (int k = 0; k < 16; k++) {
          const int u = 16 * ps + k, c = k >> 1;
          if (ps == 0 && (k == 0 || k == 4 || k == 8)) {
#pragma unroll
            for (int p = (k == 0 ? 0 : (k == 4 ? 1 : 3)); p < (k == 0 ? 1 : (k == 4 ? 3 : 4)); p++) {
              if (p > 0) mbar_wait(sb + SM_XF + ((2 + wg) * 4 + p) * 8);
              get_pair(A[2 * p], A[2 * p + 1], xb + p * 1024, hp_ + p * 1024, T);
              if (lane == 0) {
                if (wg == 0) mbar_arrive(sb + SM_XE + (8 + p) * 8);
                else if (p > 0) release(ST_XC + p - 1);
              }
            }
          }
          if (ps == 0 && (k & 1) == 0) {
#pragma unroll
            for (int s = 0; s < 4; s++) {
              A[c][s][0] = hsub2(A[c][s][0], m0); A[c][s][1] = hsub2(A[c][s][1], m1);
              A[c][s][2] = hsub2(A[c][s][2], m0); A[c][s][3] = hsub2(A[c][s][3], m1);
            }
            wg_fence();
          }
          UNIT_PRE(u);
          wgmma_rs_n128(acc, A[c][(k & 1) * 2], dg + UOFF(u), k != 0 ? 1 : (ps ? rz : 0));
          wgmma_rs_n128(acc, A[c][(k & 1) * 2 + 1], dg + UOFF(u) + 128, 1);
          UNIT_POST(u);
        }
        wg_wait<0>();
#pragma unroll
        for (int s = 0; s < 4; s++) {
          uint32_t (&hh)[4] = HH[4 + s];
          hh[0] = tg(pack2(acc[8 * s + 0] * acc[32 + 8 * s + 0], acc[8 * s + 1] * acc[32 + 8 * s + 1]), T);
          hh[1] = pack2(acc[8 * s + 2] * acc[32 + 8 * s + 2], acc[8 * s + 3] * acc[32 + 8 * s + 3]);
          hh[2] = pack2(acc[8 * s + 4] * acc[32 + 8 * s + 4], acc[8 * s + 5] * acc[32 + 8 * s + 5]);
          hh[3] = pack2(acc[8 * s + 6] * acc[32 + 8 * s + 6], acc[8 * s + 7] * acc[32 + 8 * s + 7]);
          st_rlx4(hhp + (4 * ps + s) * 128, hh[0], hh[1], hh[2], hh[3]);
        }
      }
      {
        float ag[24], au[24];
        const uint32_t* ph7 = reinterpret_cast<const uint32_t*>(&g_hh[rh3][jf ^ 1][7][wq][31]);
        uint32_t hv = 0;
        bar_sync(1 + wg, 128);
        wg_fence();
#pragma unroll
        for (int k = 0; k < 16; k++) {
          const int u = 32 + k, c = k >> 1;
          if (k == 6) {
#pragma unroll
            for (int s = 0; s < 4; s++) ld_rlx4(HH[s], hhp + s * 128);
          }
          if (k == 9) hv = ld_rlx1(ph7);
          if (k == 12) {
            int it = 0;
#pragma unroll 1
            while (((hv ^ T) & 1) && ++it < (1 << 18)) hv = ld_rlx1(ph7);
#pragma unroll
            for (int s = 0; s < 8; s++) ld_rlx4(PH[s], pp + s * 128);
          }
          UNIT_PRE(u);
          wgmma_rs_n48(ag, A[c][(k & 1) * 2], dg + UOFF(u), k != 0);
          wgmma_rs_n48(au, A[c][(k & 1) * 2], dg + UOFF(u) + 256, k != 0);
          wgmma_rs_n48(ag, A[c][(k & 1) * 2 + 1], dg + UOFF(u) + 128, 1);
          wgmma_rs_n48(au, A[c][(k & 1) * 2 + 1], dg + UOFF(u) + 256 + 128, 1);
          UNIT_POST(u);
        }
        wg_wait<0>();
#pragma unroll
        for (int s = 0; s < 3; s++) {
          uint32_t (&hh)[4] = HH[8 + s];
          hh[0] = tg(pack2(ag[8 * s + 0] * au[8 * s + 0], ag[8 * s + 1] * au[8 * s + 1]), T);
          hh[1] = pack2(ag[8 * s + 2] * au[8 * s + 2], ag[8 * s + 3] * au[8 * s + 3]);
          hh[2] = pack2(ag[8 * s + 4] * au[8 * s + 4], ag[8 * s + 5] * au[8 * s + 5]);
          hh[3] = pack2(ag[8 * s + 6] * au[8 * s + 6], ag[8 * s + 7] * au[8 * s + 7]);
          st_rlx4(hhp + (8 + s) * 128, hh[0], hh[1], hh[2], hh[3]);
        }
      }
    }

    {
      float acc[32];
      uint32_t hr[4][4], hx = 0;
      const int m = jf >> 1, oc = (jf & 1) * 4 + m;
      const uint32_t* ph10 = reinterpret_cast<const uint32_t*>(&g_hh[rh3][jf ^ 1][10][wq][31]);
      uint4* outb = &g_part[rh3][(jf & 1) * 4][m][wq][0][lane];
      bar_arrive(8 + wg, 256);
      int s0 = ST_D % NSLOT;
#pragma unroll 1
      for (int k = 0; k < 4; k++) {
        const int s1 = s0 + 1 == NSLOT ? 0 : s0 + 1;
        const uint32_t d0 = db + s0 * (SLOT >> 4), d1 = db + s1 * (SLOT >> 4);
        wg_wait<0>();
        if (k > 0) {
          uint4* p = outb + ((m + k) & 3) * 2048;
#pragma unroll
          for (int s = 0; s < 4; s++)
            st_rlx4(p + s * 32, tg(pack2(acc[8 * s], acc[8 * s + 1]), T), pack2(acc[8 * s + 2], acc[8 * s + 3]),
                    pack2(acc[8 * s + 4], acc[8 * s + 5]), pack2(acc[8 * s + 6], acc[8 * s + 7]));
          if (k == 1) bar_arrive(12, 320);
        } else {
          int it = 0;
#pragma unroll 1
          while (__any_sync(0xffffffffu, bad4(PH[0][0], PH[1][0], PH[2][0], PH[3][0], T) | bad4(PH[4][0], PH[5][0], PH[6][0], PH[7][0], T)) && ++it < (1 << 18)) {
#pragma unroll
            for (int s = 0; s < 8; s++) ld_rlx4(PH[s], pp + s * 128);
          }
        }
        mbar_wait(sb + SM_FULL + (ST_D + 2 * k) * 8);
        mbar_wait(sb + SM_FULL + (ST_D + 2 * k + 1) * 8);
        wg_fence();
#pragma unroll
        for (int s = 0; s < 11; s++) wgmma_rs_n64(acc, HH[s], d0 + s * 128, s != 0);
#pragma unroll
        for (int s = 0; s < 8; s++) wgmma_rs_n64(acc, PH[s], d1 + s * 128, 1);
        if (k == 0) {
          int it = 0;
#pragma unroll 1
          while (((ld_rlx1(ph10) ^ T) & 1) && ++it < (1 << 18)) {}
          ld_chunk(hr, &g_h[rh3][oc][wq][0][lane]);
#pragma unroll 1
          do {
            hx = ld_rlx1(&g_hx[rh3][oc][wq][lane]);
#pragma unroll
            for (int s = 8; s < 11; s++) ld_rlx4(PH[s], pp + s * 128);
          } while (__any_sync(0xffffffffu, bad4(PH[8][0], PH[9][0], PH[10][0], hx, T)) && ++it < (1 << 18));
          wg_fence();
        }
#pragma unroll
        for (int s = 8; s < 11; s++) wgmma_rs_n64(acc, PH[s], d1 + s * 128, 1);
        wg_commit();
        s0 = s1 + 1 == NSLOT ? 0 : s1 + 1;
      }
      wg_wait<0>();
#pragma unroll 1
      for (int q = 0; q < 3; q++) {
        uint32_t in[4][4];
        const uint4* sp = reinterpret_cast<const uint4*>(smem + ((ST_D % NSLOT) + wg) * SLOT) + q * 512 + wq * 128 + lane;
        mbar_wait_p(sb + SM_XF + (wg * 4 + q) * 8, 1);
        int it = 0;
#pragma unroll 1
        do {
#pragma unroll
          for (int s = 0; s < 4; s++)
            asm volatile("{\n.reg .b128 v;\nld.relaxed.gpu.b128 v, [%4];\nmov.b128 {%0,%1,%2,%3}, v;\n}"
                         : "=r"(in[s][0]), "=r"(in[s][1]), "=r"(in[s][2]), "=r"(in[s][3]) : "l"(sp + s * 32) : "memory");
          sp = &g_part[rh3][oc][(m - 1 - q) & 3][wq][0][lane];
        } while (__any_sync(0xffffffffu, bad4(in[0][0], in[1][0], in[2][0], in[3][0], T)) && ++it < (1 << 18));
        add_frag(acc, in, IDF);
      }
#pragma unroll
      for (int s = 0; s < 4; s++) hr[s][0] = (hr[s][0] & 0xFFFFFFFEu) | ((hx >> (s + 1)) & 1u);
#pragma unroll
      for (int i = 0; i < 32; i++) acc[i] *= (i & 2) ? r1 : r0;
      add_frag(acc, hr, IDF);
      bar_sync(9 - wg, 256);
      const uint32_t ob = sb + ((ST_D - 1) % NSLOT) * SLOT + wg * 8192;
#pragma unroll
      for (int s = 0; s < 4; s++)
        stsm4(ob + lrow + (((2 * s + lhi) ^ lx) << 4), pack2(acc[8 * s + 0], acc[8 * s + 1]), pack2(acc[8 * s + 2], acc[8 * s + 3]),
              pack2(acc[8 * s + 4], acc[8 * s + 5]), pack2(acc[8 * s + 6], acc[8 * s + 7]));
      __syncwarp();
      {
        const int row = wq * 16 + (lane >> 3);
        __nv_bfloat16* op = out + (size_t)(rh3 * 64 + row) * 512 + oc * 64 + lx * 8;
#pragma unroll
        for (int i = 0; i < 4; i++) {
          uint4 v;
          asm volatile("ld.shared.v4.b32 {%0,%1,%2,%3}, [%4];" : "=r"(v.x), "=r"(v.y), "=r"(v.z), "=r"(v.w)
                       : "r"(ob + (row + i * 4) * 128 + ((lx ^ (((lane >> 3) + i * 4) & 7)) << 4)) : "memory");
          asm volatile("st.global.v4.b32 [%0], {%1,%2,%3,%4};" ::"l"(op + i * 2048), "r"(v.x), "r"(v.y), "r"(v.z), "r"(v.w) : "memory");
        }
      }
    }
    asm volatile("barrier.cluster.arrive.relaxed.aligned;" ::: "memory");
    asm volatile("barrier.cluster.wait.aligned;" ::: "memory");
  } else {
    asm volatile("setmaxnreg.dec.sync.aligned.u32 24;");
    if (elect_one()) {
      if (warp == 8) {
#pragma unroll
        for (int k = 0; k < 9; k++) {
          const int s = k < 3 ? k : (k < 6 ? k + 3 : k - 3);
          const uint32_t bar = sb + SM_FULL + s * 8;
          mbar_init(bar, 1);
          mbar_expect_tx(bar, SLOT);
          if (s >= 3 && s < 6) tma2d(sb + s * SLOT, &maps.w, 512 + hg * 64, (s - 3) * 192, bar);
          else tma3d(sb + s * SLOT, &maps.x, 0, rb * 128 + (s >= 6 ? 64 : 0), 3 * (s % 3), bar);
        }
      } else if (warp == 9) {
        mbar_init(sb + SM_MISCB, 2);
        mbar_init(sb + SM_KVB, 1);
        mbar_expect_tx(sb + SM_KVB, 8704);
        mbar_expect_tx(sb + SM_MISCB, 2048);
        bulk_g2s(sb + SM_WPHI, wphi + hg * 1024, 2048, sb + SM_MISCB);
      } else if (warp == 10) {
        if ((sb & 0x3FFFF) != SM_BASE) __trap();
#pragma unroll 1
        for (int i = 0; i < 16; i++) {
          mbar_init(sb + SM_XF + i * 8, 1);
          mbar_expect_tx(sb + SM_XF + i * 8, (i == 8 || i == 12) ? 20480 : 16384);
          if (i < 12) mbar_init(sb + SM_XE + i * 8, 4);
        }
      } else {
        *reinterpret_cast<volatile unsigned*>(smem + SM_EPOCH) = atomicAdd(&g_start, 1u) / NCTA;
      }
      asm volatile("fence.mbarrier_init.release.cluster;" ::: "memory");
    }
    __syncwarp();
    if (warp != 11) bar_sync(0, 352);
    asm volatile("barrier.cluster.arrive.relaxed.aligned;" ::: "memory");
    if (warp == 8) {
      asm volatile("barrier.cluster.wait.aligned;" ::: "memory");
      if (elect_one()) {
        const CUtensorMap* mg = jf == 7 ? &maps.g7 : &maps.g;
        const CUtensorMap* mu = jf == 7 ? &maps.u7 : &maps.u;
        asm volatile("prefetch.tensormap [%0];" ::"l"(&maps.wo) : "memory");
        asm volatile("prefetch.tensormap [%0];" ::"l"(mg) : "memory");
        asm volatile("prefetch.tensormap [%0];" ::"l"(mu) : "memory");
        asm volatile("prefetch.tensormap [%0];" ::"l"(&maps.d) : "memory");
#pragma unroll 1
        for (int s = ST_WV; s < ST_XC; s++) {
          if (s == ST_SCR1) continue;
          mbar_wait(sb + SM_EMPTY + (s - 9) * 8);
          const uint32_t dst = sb + (s >= 18 ? s - 18 : s - 9) * SLOT, bar = sb + SM_FULL + s * 8;
          if (s < ST_WO) tma2d(dst, &maps.w, (s < ST_WQ ? 1024 : 0) + hg * 64, (s < ST_WQ ? s - ST_WV : s - ST_WQ) * 192, bar);
          else { mbar_wait(bar - 8); tma2d(dst, &maps.wo, hg * 64, (s - ST_WO) * 192, bar); }
        }
        const int jc = jf == 7 ? 0 : jf;
        int slot = (ST_GU + 1 - rank) % NSLOT;
#pragma unroll 1
        for (int s = ST_GU + 1 - rank; s < NSTAGE; s += 2) {
          mbar_wait(sb + SM_EMPTY + (s - 9) * 8);
          if (s > ST_GU && s < ST_GU + 6) mbar_wait(sb + SM_FULL + (s - 1) * 8);
          const uint32_t dst = sb + slot * SLOT, bar = sb + SM_FULL + s * 8;
          if (s < ST_D) {
#pragma unroll 1
            for (int i = 0; i < 3; i++) {
              const int u = (s - ST_GU) * 3 + i;
              tma3d_mc(dst + i * 8192, mg, (u >> 4) * 64, jc, (u & 15) * 32, bar);
              tma3d_mc(dst + i * 8192 + 4096, mu, (u >> 4) * 64, jc, (u & 15) * 32, bar);
            }
          } else {
            const int i = s - ST_D;
            tma2d_mc(dst, &maps.d, ((jf & 1) * 4 + (((jf >> 1) + 1 + (i >> 1)) & 3)) * 64, (jf ^ (i & 1)) * 176, bar);
          }
          slot += 2; if (slot >= NSLOT) slot -= NSLOT;
        }
      }
      __syncwarp();
    } else {
      asm volatile("barrier.cluster.wait.aligned;" ::: "memory");
      if (warp == 11) {
#pragma unroll
        for (int i = 0; i < 4; i++)
          reinterpret_cast<uint4*>(smem + SM_ONES)[lane + 32 * i] = make_uint4(0x3F803F80u, 0x3F803F80u, 0x3F803F80u, 0x3F803F80u);
        fence_async_smem();
        __syncwarp();
        if (lane == 0) mbar_arrive(sb + SM_MISCB);
      }
      mbar_wait(sb + SM_MISCB);
      const unsigned epoch = *reinterpret_cast<volatile unsigned*>(smem + SM_EPOCH);
      const uint32_t T = (epoch & 1) ^ 1;
      if (warp == 11) {
        reinterpret_cast<float4*>(&g_kv[hg][rb * 136])[lane] = make_float4(0.f, 0.f, 0.f, 0.f);
        if (lane < 2) reinterpret_cast<float4*>(&g_kv[hg][rb * 136])[32 + lane] = make_float4(0.f, 0.f, 0.f, 0.f);
        __syncwarp();
        if (elect_one()) asm volatile("red.release.gpu.global.add.u32 [%0], 8;" ::"l"(&g_kvcnt[hg * 32 + 1]) : "memory");
        mbar_wait(sb + SM_FULL + (ST_WK + 2) * 8);
        if (elect_one()) {
          asm volatile("cp.async.bulk.prefetch.L2.global [%0], 4096;" ::"l"((const char*)wo + blockIdx.x * 4096) : "memory");
          asm volatile("cp.async.bulk.prefetch.L2.global [%0], 11008;" ::"l"((const char*)wg_ + blockIdx.x * 11008) : "memory");
          asm volatile("cp.async.bulk.prefetch.L2.global [%0], 11008;" ::"l"((const char*)wu_ + blockIdx.x * 11008) : "memory");
          asm volatile("cp.async.bulk.prefetch.L2.global [%0], 11008;" ::"l"((const char*)wd_ + blockIdx.x * 11008) : "memory");
          mbar_wait(sb + SM_EMPTY + ST_SCR0 * 8);
          const unsigned target = (epoch + 1) * 128;
          unsigned v; int it = 0;
#pragma unroll 1
          do {
            asm volatile("ld.acquire.gpu.global.u32 %0, [%1];" : "=r"(v) : "l"(&g_kvcnt[hg * 32]) : "memory");
            if (++it > (1 << 18)) break;
          } while ((int)(v - target) < 0);
          asm volatile("fence.proxy.async.global;" ::: "memory");
          bulk_g2s(sb + SM_KV32, &g_kv[hg][0], 8192, sb + SM_KVB);
          bulk_g2s(sb + SM_ONES, &g_kv[hg][2048], 512, sb + SM_KVB);
        }
        __syncwarp();
      } else {
        const int w = warp - 9;
        st_rlx4(reinterpret_cast<uint4*>(&g_st[2 * rb + w][hg][0]) + lane, T ^ 1, T ^ 1, T ^ 1, T ^ 1);
        if (lane < 8) st_rlx4(&g_o[2 * rb + w][hg][lane >> 1][3][30 + (lane & 1)], T ^ 1, T ^ 1, T ^ 1, T ^ 1);
        st_rlx4(&g_part[2 * rb3 + w][(jf & 1) * 4 + (lane >> 3)][jf >> 1][(lane >> 1) & 3][3][30 + (lane & 1)], T ^ 1, T ^ 1, T ^ 1, T ^ 1);
        if (lane < 16) st_rlx4(&g_hh[2 * rb3 + w][jf][7 + (lane >> 3) * 3][(lane >> 1) & 3][30 + (lane & 1)], T ^ 1, T ^ 1, T ^ 1, T ^ 1);
        if (w == 0) {
          mbar_wait(sb + SM_FULL + (ST_WQ + 2) * 8);
          unsigned v; int it = 0;
#pragma unroll 1
          do {
            asm volatile("ld.acquire.gpu.global.u32 %0, [%1];" : "=r"(v) : "l"(&g_kvcnt[hg * 32 + 1]) : "memory");
          } while ((int)(v - (epoch + 1) * 128) < 0 && ++it < (1 << 18));
          asm volatile("fence.proxy.async.global;" ::: "memory");
        }
        bar_sync(6, 320);
        if (w == 0 && elect_one()) {
          asm volatile("cp.reduce.async.bulk.global.shared::cta.bulk_group.add.f32 [%0], [%1], 8704;"
                       ::"l"(&g_kv[hg][0]), "r"(sb + 2 * SLOT) : "memory");
          asm volatile("cp.async.bulk.commit_group;" ::: "memory");
          asm volatile("cp.async.bulk.wait_group 0;" ::: "memory");
          asm volatile("red.release.gpu.global.add.u32 [%0], 8;" ::"l"(&g_kvcnt[hg * 32]) : "memory");
        }
        __syncwarp();
        mbar_wait(sb + SM_KVB);
        if (w == 0) { mbar_wait(sb + SM_EMPTY + 11 * 8); mbar_wait(sb + SM_EMPTY + 12 * 8); mbar_wait(sb + SM_EMPTY + 13 * 8); }
#pragma unroll 1
        for (int ph = 0; ph < 2; ph++) {
          const int use = 2 * ph + w, r = ph ? 2 * rb3 + w : 2 * rb + w;
          const uint32_t* pw = ph ? reinterpret_cast<const uint32_t*>(&g_st[r][lane >> 2][(lane & 3) * 16 + 15])
                                  : reinterpret_cast<const uint32_t*>(&g_o[r][lane >> 2][lane & 3][3][31]);
          const char* src = reinterpret_cast<const char*>(ph ? &g_h[r][0][0][0][0] : &g_o[r][0][0][0][0]);
          const uint32_t bf = sb + SM_XF + use * 32, be = sb + SM_XE + (use - 1) * 32;
          bar_sync(10 + w, 160);
          int it = 0;
#pragma unroll 1
          for (bool miss = true; __any_sync(0xffffffffu, miss) && ++it < (1 << 18);) { if (miss) miss = (ld_rlx1(pw) ^ T) & 1; }
          if (elect_one()) {
            if (use > 0) mbar_wait(be);
            if (ph) bulk_g2s(sb + SM_KV32 + w * 4096, &g_st[r][0][0], 4096, bf);
#pragma unroll
            for (int p = 0; p < 4; p++) {
              if (p > 0 && use > 0) mbar_wait(be + p * 8);
              bulk_g2s(sb + 2 * SLOT + p * 16384, src + p * 16384, 16384, bf + p * 8);
            }
          }
          __syncwarp();
        }
        {
          const int m = jf >> 1, oc = (jf & 1) * 4 + m;
          const uint32_t* pw = reinterpret_cast<const uint32_t*>(&g_part[2 * rb3 + w][oc][(m - 1 - (lane >> 2)) & 3][lane & 3][3][31]);
          bar_sync(12, 320);
          bool miss = lane < 12; int it = 0;
#pragma unroll 1
          for (int q = 0; q < 3; q++) {
#pragma unroll 1
            while ((__ballot_sync(0xffffffffu, miss) >> (4 * q) & 15) && ++it < (1 << 18)) { if (miss && (lane >> 2) <= q + 1) miss = (ld_rlx1(pw) ^ T) & 1; }
            if (elect_one()) {
              const uint32_t bar = sb + SM_XF + (w * 4 + q) * 8;
              mbar_expect_tx(bar, 8192);
              bulk_g2s(sb + ((ST_D % NSLOT) + w) * SLOT + q * 8192, &g_part[2 * rb3 + w][oc][(m - 1 - q) & 3][0][0][0], 8192, bar);
            }
            __syncwarp();
          }
        }
      }
    }
    asm volatile("barrier.cluster.arrive.relaxed.aligned;" ::: "memory");
    asm volatile("barrier.cluster.wait.aligned;" ::: "memory");
  }
}

typedef CUresult (*EncodeFn)(CUtensorMap*, CUtensorMapDataType, cuuint32_t, void*, const cuuint64_t*, const cuuint64_t*,
                             const cuuint32_t*, const cuuint32_t*, CUtensorMapInterleave, CUtensorMapSwizzle,
                             CUtensorMapL2promotion, CUtensorMapFloatOOBfill);

void encode(EncodeFn fn, CUtensorMap* m, const void* base, int rank, const cuuint64_t* dims, const cuuint64_t* strides,
            const cuuint32_t* box) {
  cuuint32_t es[3] = {1, 1, 1};
  fn(m, CU_TENSOR_MAP_DATA_TYPE_BFLOAT16, (cuuint32_t)rank, const_cast<void*>(base), dims, strides, box, es,
     CU_TENSOR_MAP_INTERLEAVE_NONE, CU_TENSOR_MAP_SWIZZLE_128B, CU_TENSOR_MAP_L2_PROMOTION_L2_256B,
     CU_TENSOR_MAP_FLOAT_OOB_FILL_NONE);
}

}

extern "C" void kernel_launch(void* const* d_in, const int* in_sizes, int n_in, void* d_out, int out_size) {
  (void)in_sizes; (void)n_in; (void)out_size;
  const __nv_bfloat16* x    = (const __nv_bfloat16*)d_in[0];
  const __nv_bfloat16* wqkv = (const __nv_bfloat16*)d_in[1];
  const __nv_bfloat16* wphi = (const __nv_bfloat16*)d_in[2];
  const __nv_bfloat16* wo   = (const __nv_bfloat16*)d_in[3];
  const __nv_bfloat16* wg   = (const __nv_bfloat16*)d_in[5];
  const __nv_bfloat16* wu   = (const __nv_bfloat16*)d_in[6];
  const __nv_bfloat16* wd   = (const __nv_bfloat16*)d_in[7];

  static EncodeFn fn = nullptr;
  if (!fn) {
    void* p = nullptr;
    cudaDriverEntryPointQueryResult qr;
    cudaGetDriverEntryPoint("cuTensorMapEncodeTiled", &p, cudaEnableDefault, &qr);
    fn = (EncodeFn)p;
    cudaFuncSetAttribute(fused_kernel, cudaFuncAttributeMaxDynamicSharedMemorySize, SM_TOTAL);
  }
  Maps maps;
  {
    cuuint64_t d[3] = {64, 2048, 8}, s[2] = {1024, 128}; cuuint32_t b[3] = {64, 64, 3};
    encode(fn, &maps.x, x, 3, d, s, b);
  }
  {
    cuuint64_t d[2] = {1536, 512}, s[1] = {3072}; cuuint32_t b[2] = {64, 192};
    encode(fn, &maps.w, wqkv, 2, d, s, b);
  }
  {
    cuuint64_t d[2] = {512, 512}, s[1] = {1024}; cuuint32_t b[2] = {64, 192};
    encode(fn, &maps.wo, wo, 2, d, s, b);
  }
  {
    cuuint64_t d[3] = {176, 7, 512}, d7[3] = {144, 1, 512}, s[2] = {352, 2752}; cuuint32_t b[3] = {64, 1, 32};
    encode(fn, &maps.g, wg, 3, d, s, b);
    encode(fn, &maps.u, wu, 3, d, s, b);
    encode(fn, &maps.g7, wg + 1232, 3, d7, s, b);
    encode(fn, &maps.u7, wu + 1232, 3, d7, s, b);
  }
  {
    cuuint64_t d[2] = {512, 1376}, s[1] = {1024}; cuuint32_t b[2] = {64, 176};
    encode(fn, &maps.d, wd, 2, d, s, b);
  }
  fused_kernel<<<NCTA, 384, SM_TOTAL>>>(maps, x, wphi, wo, wg, wu, wd, (__nv_bfloat16*)d_out);
}
```

```cpp
#include <cuda_runtime.h>
#include <cuda_bf16.h>
#include <cuda.h>
#include <stdint.h>

#define SAFE_WAIT 0

namespace {

constexpr int NCTA   = 128;
constexpr int SLOT   = 24576;
constexpr int NSLOT  = 9;
constexpr int NSTAGE = 47;

constexpr int ST_X0   = 0;
constexpr int ST_WK   = 3;
constexpr int ST_X1   = 6;
constexpr int ST_SCR0 = 9;
constexpr int ST_WV   = 10;
constexpr int ST_SCR1 = 13;
constexpr int ST_WQ   = 14;
constexpr int ST_WO   = 17;
constexpr int ST_XC   = 20;
constexpr int ST_GU   = 23;
constexpr int ST_D    = 39;

__host__ __device__ constexpr int st_empty_cnt(int d) {
  return ((d < 3 || (d >= 6 && d < 9) || (d >= ST_XC && d < ST_GU)) ? 4 : (d == ST_SCR0 || d == ST_SCR1) ? 1 : 2) * (d + 9 >= ST_GU ? 2 : 1);
}

constexpr uint32_t SM_BASE = 1024;
constexpr int SM_ONES = NSLOT * SLOT;
constexpr int SM_WPHI = SM_ONES + 2048;
constexpr int SM_KVS  = SM_WPHI + 2048;
constexpr int SM_KV32 = 4 * SLOT + 16384;
constexpr int SM_BAR  = SM_KVS + 6144;
constexpr int SM_FULL  = SM_BAR;
constexpr int SM_EMPTY = SM_BAR + NSTAGE * 8;
constexpr int SM_MISCB = SM_BAR + 2 * NSTAGE * 8;
constexpr int SM_KVB   = SM_MISCB + 8;
constexpr int SM_EPOCH = SM_KVB + 8;
constexpr int SM_XF    = SM_EPOCH + 8;
constexpr int SM_XE    = SM_XF + 16 * 8;
constexpr int SM_TOTAL = SM_BAR + 1024;

static_assert(SM_TOTAL == 232448 && SM_XE + 12 * 8 <= SM_TOTAL, "smem budget");

struct Maps { CUtensorMap x, w, wo, g, u, g7, u7, d; };

__device__ __align__(128) uint4    g_o[32][8][4][4][32];
__device__ __align__(128) uint4    g_h[32][8][4][4][32];
__device__ __align__(128) uint32_t g_hx[32][8][4][32];
__device__ __align__(128) uint2    g_st[32][8][64];
__device__ __align__(128) uint4    g_hh[32][8][11][4][32];
__device__ __align__(128) uint4    g_part[32][8][4][4][4][32];
__device__ __align__(128) float4 g_kv[8][128][6];
__device__ __align__(128) unsigned g_kvcnt[8 * 32];
__device__ unsigned g_start;

__device__ __forceinline__ uint32_t smem_u32(const void* p) { return (uint32_t)__cvta_generic_to_shared(p); }
__device__ __forceinline__ void mbar_init(uint32_t bar, int cnt) {
  asm volatile("mbarrier.init.shared::cta.b64 [%0], %1;" ::"r"(bar), "r"(cnt) : "memory");
}
__device__ __forceinline__ void mbar_expect_tx(uint32_t bar, uint32_t bytes) {
  asm volatile("mbarrier.arrive.expect_tx.shared::cta.b64 _, [%0], %1;" ::"r"(bar), "r"(bytes) : "memory");
}
__device__ __forceinline__ void mbar_arrive(uint32_t bar) {
  asm volatile("mbarrier.arrive.shared::cta.b64 _, [%0];" ::"r"(bar) : "memory");
}
__device__ __forceinline__ void mbar_arrive_cluster(uint32_t bar, uint32_t rank) {
  asm volatile("{\n.reg .b32 ra;\nmapa.shared::cluster.u32 ra, %0, %1;\n"
               "mbarrier.arrive.shared::cluster.b64 _, [ra];\n}" ::"r"(bar), "r"(rank) : "memory");
}
__device__ __forceinline__ void mbar_wait_p(uint32_t bar, uint32_t parity) {
  asm volatile("{\n.reg .pred p;\nW: mbarrier.try_wait.parity.shared::cta.b64 p, [%0], %1;\n@!p bra W;\n}" ::"r"(bar), "r"(parity) : "memory");
}
__device__ __forceinline__ void mbar_wait(uint32_t bar) { mbar_wait_p(bar, 0); }
__device__ __forceinline__ bool elect_one() {
  uint32_t p;
  asm volatile("{\n.reg .pred P;\nelect.sync _|P, 0xffffffff;\nselp.u32 %0, 1, 0, P;\n}" : "=r"(p));
  return p != 0;
}
__device__ __forceinline__ void bar_sync(int id, int n)   { asm volatile("bar.sync %0, %1;" ::"r"(id), "r"(n) : "memory"); }
__device__ __forceinline__ void bar_arrive(int id, int n) { asm volatile("bar.arrive %0, %1;" ::"r"(id), "r"(n) : "memory"); }
__device__ __forceinline__ void fence_async_smem() { asm volatile("fence.proxy.async.shared::cta;" ::: "memory"); }
__device__ __forceinline__ void wg_fence()  { asm volatile("wgmma.fence.sync.aligned;" ::: "memory"); }
__device__ __forceinline__ void wg_commit() { asm volatile("wgmma.commit_group.sync.aligned;" ::: "memory"); }
template <int N> __device__ __forceinline__ void wg_wait() { asm volatile("wgmma.wait_group.sync.aligned %0;" ::"n"(N) : "memory"); }
#define DESC(off) (db + ((uint32_t)(off) >> 4))
__device__ __forceinline__ void tma2d(uint32_t dst, const CUtensorMap* m, int c0, int c1, uint32_t bar) {
  asm volatile("cp.async.bulk.tensor.2d.shared::cluster.global.mbarrier::complete_tx::bytes [%0], [%1, {%3, %4}], [%2];"
               ::"r"(dst), "l"(m), "r"(bar), "r"(c0), "r"(c1) : "memory");
}
__device__ __forceinline__ void tma2d_mc(uint32_t dst, const CUtensorMap* m, int c0, int c1, uint32_t bar) {
  asm volatile("cp.async.bulk.tensor.2d.shared::cluster.global.mbarrier::complete_tx::bytes.multicast::cluster [%0], [%1, {%3, %4}], [%2], %5;"
               ::"r"(dst), "l"(m), "r"(bar), "r"(c0), "r"(c1), "h"((uint16_t)3) : "memory");
}
__device__ __forceinline__ void tma3d(uint32_t dst, const CUtensorMap* m, int c0, int c1, int c2, uint32_t bar) {
  asm volatile("cp.async.bulk.tensor.3d.shared::cluster.global.mbarrier::complete_tx::bytes [%0], [%1, {%3, %4, %5}], [%2];"
               ::"r"(dst), "l"(m), "r"(bar), "r"(c0), "r"(c1), "r"(c2) : "memory");
}
__device__ __forceinline__ void tma3d_mc(uint32_t dst, const CUtensorMap* m, int c0, int c1, int c2, uint32_t bar) {
  asm volatile("cp.async.bulk.tensor.3d.shared::cluster.global.mbarrier::complete_tx::bytes.multicast::cluster [%0], [%1, {%3, %4, %5}], [%2], %6;"
               ::"r"(dst), "l"(m), "r"(bar), "r"(c0), "r"(c1), "r"(c2), "h"((uint16_t)3) : "memory");
}
__device__ __forceinline__ void ldsm4(uint32_t (&r)[4], uint32_t addr) {
  asm volatile("ldmatrix.sync.aligned.m8n8.x4.shared.b16 {%0,%1,%2,%3}, [%4];"
               : "=r"(r[0]), "=r"(r[1]), "=r"(r[2]), "=r"(r[3]) : "r"(addr) : "memory");
}
__device__ __forceinline__ void ldsm4t(uint32_t (&r)[4], uint32_t addr) {
  asm volatile("ldmatrix.sync.aligned.m8n8.x4.trans.shared.b16 {%0,%1,%2,%3}, [%4];"
               : "=r"(r[0]), "=r"(r[1]), "=r"(r[2]), "=r"(r[3]) : "r"(addr) : "memory");
}
__device__ __forceinline__ void stsm4(uint32_t addr, uint32_t r0, uint32_t r1, uint32_t r2, uint32_t r3) {
  asm volatile("stmatrix.sync.aligned.m8n8.x4.shared.b16 [%0], {%1,%2,%3,%4};"
               ::"r"(addr), "r"(r0), "r"(r1), "r"(r2), "r"(r3) : "memory");
}
__device__ __forceinline__ void mma16816(float (&c)[4], const uint32_t (&a)[4], uint32_t b0, uint32_t b1) {
  asm volatile("mma.sync.aligned.m16n8k16.row.col.f32.bf16.bf16.f32 {%0,%1,%2,%3},{%4,%5,%6,%7},{%8,%9},{%0,%1,%2,%3};"
               : "+f"(c[0]), "+f"(c[1]), "+f"(c[2]), "+f"(c[3])
               : "r"(a[0]), "r"(a[1]), "r"(a[2]), "r"(a[3]), "r"(b0), "r"(b1));
}
__device__ __forceinline__ void add_frag(float (&c)[32], const uint32_t (&a)[4][4], uint32_t id) {
#pragma unroll
  for (int i = 0; i < 8; i++)
    asm volatile("mma.sync.aligned.m16n8k8.row.col.f32.bf16.bf16.f32 {%0,%1,%2,%3},{%4,%5},{%6},{%0,%1,%2,%3};"
                 : "+f"(c[4 * i]), "+f"(c[4 * i + 1]), "+f"(c[4 * i + 2]), "+f"(c[4 * i + 3])
                 : "r"(a[i >> 1][(i & 1) * 2]), "r"(a[i >> 1][(i & 1) * 2 + 1]), "r"(id));
}
__device__ __forceinline__ uint32_t pack2(float lo, float hi) {
  uint32_t r; asm("cvt.rn.bf16x2.f32 %0, %1, %2;" : "=r"(r) : "f"(hi), "f"(lo)); return r;
}
__device__ __forceinline__ float blo(uint32_t w) { return __uint_as_float(w << 16); }
__device__ __forceinline__ float bhi(uint32_t w) { return __uint_as_float(w & 0xFFFF0000u); }
__device__ __forceinline__ uint32_t hsub2(uint32_t a, uint32_t b) { uint32_t r; asm("sub.rn.bf16x2 %0, %1, %2;" : "=r"(r) : "r"(a), "r"(b)); return r; }
__device__ __forceinline__ uint32_t hmax2(uint32_t a, uint32_t b) { uint32_t r; asm("max.bf16x2 %0, %1, %2;" : "=r"(r) : "r"(a), "r"(b)); return r; }
__device__ __forceinline__ uint32_t hmin2(uint32_t a, uint32_t b) { uint32_t r; asm("min.bf16x2 %0, %1, %2;" : "=r"(r) : "r"(a), "r"(b)); return r; }
__device__ __forceinline__ float ex2(float x) { float r; asm("ex2.approx.ftz.f32 %0, %1;" : "=f"(r) : "f"(x)); return r; }
__device__ __forceinline__ float rcp(float x) { float r; asm("rcp.approx.ftz.f32 %0, %1;" : "=f"(r) : "f"(x)); return r; }
__device__ __forceinline__ void ld_rlx4(uint32_t (&r)[4], const uint4* p) {
  asm volatile("{\n.reg .b128 v;\nld.relaxed.gpu.global.b128 v, [%4];\nmov.b128 {%0,%1,%2,%3}, v;\n}"
               : "=r"(r[0]), "=r"(r[1]), "=r"(r[2]), "=r"(r[3]) : "l"(p) : "memory");
}
__device__ __forceinline__ void st_rlx4(uint4* p, uint32_t a, uint32_t b, uint32_t c, uint32_t d) {
  asm volatile("st.relaxed.gpu.global.v4.b32 [%0], {%1,%2,%3,%4};" ::"l"(p), "r"(a), "r"(b), "r"(c), "r"(d) : "memory");
}
__device__ __forceinline__ void st_rlx2(uint2* p, uint32_t a, uint32_t b) {
  asm volatile("{\n.reg .b64 v;\nmov.b64 v, {%1,%2};\nst.relaxed.gpu.global.b64 [%0], v;\n}" ::"l"(p), "r"(a), "r"(b) : "memory");
}
__device__ __forceinline__ uint32_t ld_rlx1(const uint32_t* p) {
  uint32_t r; asm volatile("ld.relaxed.gpu.global.b32 %0, [%1];" : "=r"(r) : "l"(p) : "memory"); return r;
}
__device__ __forceinline__ void st_rlx1(uint32_t* p, uint32_t a) {
  asm volatile("st.relaxed.gpu.global.b32 [%0], %1;" ::"l"(p), "r"(a) : "memory");
}
__device__ __forceinline__ void ld_rlx2(uint32_t& a, uint32_t& b, const uint2* p) {
  asm volatile("{\n.reg .b64 v;\nld.relaxed.gpu.b64 v, [%2];\nmov.b64 {%0,%1}, v;\n}" : "=r"(a), "=r"(b) : "l"(p) : "memory");
}
__device__ __forceinline__ void bulk_g2s(uint32_t dst, const void* src, uint32_t bytes, uint32_t bar) {
  asm volatile("cp.async.bulk.shared::cluster.global.mbarrier::complete_tx::bytes [%0], [%1], %2, [%3];"
               ::"r"(dst), "l"(src), "r"(bytes), "r"(bar) : "memory");
}
__device__ __forceinline__ uint32_t tg(uint32_t w, uint32_t T) { return (w & 0xFFFFFFFEu) | T; }
__device__ __forceinline__ uint32_t bad4(uint32_t a, uint32_t b, uint32_t c, uint32_t d, uint32_t T) {
  uint32_t u, v;
  asm("lop3.b32 %0, %1, %2, %3, 0x7E;" : "=r"(u) : "r"(a), "r"(b), "r"(T));
  asm("lop3.b32 %0, %1, %2, %3, 0x7E;" : "=r"(v) : "r"(c), "r"(d), "r"(T));
  asm("lop3.b32 %0, %1, %2, 1, 0xA8;" : "=r"(u) : "r"(u), "r"(v));
  return u;
}

__device__ __forceinline__ void ld_chunk(uint32_t (&a)[4][4], const uint4* p) {
#pragma unroll
  for (int s = 0; s < 4; s++) ld_rlx4(a[s], p + s * 32);
}
__device__ __forceinline__ void get_pair(uint32_t (&a)[4][4], uint32_t (&b)[4][4], const uint4* sp, const uint4* gp, uint32_t T) {
  int it = 0;
#pragma unroll 1
  do {
#pragma unroll
    for (int s = 0; s < 8; s++) {
      uint32_t (&r)[4] = s < 4 ? a[s & 3] : b[s & 3];
      asm volatile("{\n.reg .b128 v;\nld.relaxed.gpu.b128 v, [%4];\nmov.b128 {%0,%1,%2,%3}, v;\n}"
                   : "=r"(r[0]), "=r"(r[1]), "=r"(r[2]), "=r"(r[3]) : "l"(sp + (s >> 2) * 512 + (s & 3) * 32) : "memory");
    }
    sp = gp;
  } while (__any_sync(0xffffffffu, bad4(a[0][0], a[1][0], a[2][0], a[3][0], T) | bad4(b[0][0], b[1][0], b[2][0], b[3][0], T)) && ++it < (1 << 18));
}

__device__ __forceinline__ void wgmma_rs_n48(float (&d)[24], const uint32_t (&a)[4], uint32_t descB, int scaleD) {
  asm volatile("{\n.reg .pred p;\n.reg .b64 db;\nsetp.ne.b32 p, %29, 0;\nmov.b64 db, {%28, 0x40000040};\n"
    "wgmma.mma_async.sync.aligned.m64n48k16.f32.bf16.bf16 {%0,%1,%2,%3,%4,%5,%6,%7,%8,%9,%10,%11,%12,%13,%14,%15,%16,%17,%18,%19,%20,%21,%22,%23}, {%24,%25,%26,%27}, db, p, 1, 1, 1;\n}\n"
    : "+f"(d[0]),"+f"(d[1]),"+f"(d[2]),"+f"(d[3]),"+f"(d[4]),"+f"(d[5]),"+f"(d[6]),"+f"(d[7]),"+f"(d[8]),"+f"(d[9]),"+f"(d[10]),"+f"(d[11]),"+f"(d[12]),"+f"(d[13]),"+f"(d[14]),"+f"(d[15]),"+f"(d[16]),"+f"(d[17]),"+f"(d[18]),"+f"(d[19]),"+f"(d[20]),"+f"(d[21]),"+f"(d[22]),"+f"(d[23])
    : "r"(a[0]), "r"(a[1]), "r"(a[2]), "r"(a[3]), "r"(descB), "r"(scaleD));
}
__device__ __forceinline__ void wgmma_rs_n64(float (&d)[32], const uint32_t (&a)[4], uint32_t descB, int scaleD) {
  asm volatile("{\n.reg .pred p;\n.reg .b64 db;\nsetp.ne.b32 p, %37, 0;\nmov.b64 db, {%36, 0x40000040};\n"
    "wgmma.mma_async.sync.aligned.m64n64k16.f32.bf16.bf16 {%0,%1,%2,%3,%4,%5,%6,%7,%8,%9,%10,%11,%12,%13,%14,%15,%16,%17,%18,%19,%20,%21,%22,%23,%24,%25,%26,%27,%28,%29,%30,%31}, {%32,%33,%34,%35}, db, p, 1, 1, 1;\n}\n"
    : "+f"(d[0]),"+f"(d[1]),"+f"(d[2]),"+f"(d[3]),"+f"(d[4]),"+f"(d[5]),"+f"(d[6]),"+f"(d[7]),"+f"(d[8]),"+f"(d[9]),"+f"(d[10]),"+f"(d[11]),"+f"(d[12]),"+f"(d[13]),"+f"(d[14]),"+f"(d[15]),"+f"(d[16]),"+f"(d[17]),"+f"(d[18]),"+f"(d[19]),"+f"(d[20]),"+f"(d[21]),"+f"(d[22]),"+f"(d[23]),"+f"(d[24]),"+f"(d[25]),"+f"(d[26]),"+f"(d[27]),"+f"(d[28]),"+f"(d[29]),"+f"(d[30]),"+f"(d[31])
    : "r"(a[0]), "r"(a[1]), "r"(a[2]), "r"(a[3]), "r"(descB), "r"(scaleD));
}
__device__ __forceinline__ void wgmma_rs_n128(float (&d)[64], const uint32_t (&a)[4], uint32_t descB, int scaleD) {
  asm volatile("{\n.reg .pred p;\n.reg .b64 db;\nsetp.ne.b32 p, %69, 0;\nmov.b64 db, {%68, 0x40000040};\n"
    "wgmma.mma_async.sync.aligned.m64n128k16.f32.bf16.bf16 {%0,%1,%2,%3,%4,%5,%6,%7,%8,%9,%10,%11,%12,%13,%14,%15,%16,%17,%18,%19,%20,%21,%22,%23,%24,%25,%26,%27,%28,%29,%30,%31,%32,%33,%34,%35,%36,%37,%38,%39,%40,%41,%42,%43,%44,%45,%46,%47,%48,%49,%50,%51,%52,%53,%54,%55,%56,%57,%58,%59,%60,%61,%62,%63}, {%64,%65,%66,%67}, db, p, 1, 1, 1;\n}\n"
    : "+f"(d[0]),"+f"(d[1]),"+f"(d[2]),"+f"(d[3]),"+f"(d[4]),"+f"(d[5]),"+f"(d[6]),"+f"(d[7]),"+f"(d[8]),"+f"(d[9]),"+f"(d[10]),"+f"(d[11]),"+f"(d[12]),"+f"(d[13]),"+f"(d[14]),"+f"(d[15]),"+f"(d[16]),"+f"(d[17]),"+f"(d[18]),"+f"(d[19]),"+f"(d[20]),"+f"(d[21]),"+f"(d[22]),"+f"(d[23]),"+f"(d[24]),"+f"(d[25]),"+f"(d[26]),"+f"(d[27]),"+f"(d[28]),"+f"(d[29]),"+f"(d[30]),"+f"(d[31]),"+f"(d[32]),"+f"(d[33]),"+f"(d[34]),"+f"(d[35]),"+f"(d[36]),"+f"(d[37]),"+f"(d[38]),"+f"(d[39]),"+f"(d[40]),"+f"(d[41]),"+f"(d[42]),"+f"(d[43]),"+f"(d[44]),"+f"(d[45]),"+f"(d[46]),"+f"(d[47]),"+f"(d[48]),"+f"(d[49]),"+f"(d[50]),"+f"(d[51]),"+f"(d[52]),"+f"(d[53]),"+f"(d[54]),"+f"(d[55]),"+f"(d[56]),"+f"(d[57]),"+f"(d[58]),"+f"(d[59]),"+f"(d[60]),"+f"(d[61]),"+f"(d[62]),"+f"(d[63])
    : "r"(a[0]), "r"(a[1]), "r"(a[2]), "r"(a[3]), "r"(descB), "r"(scaleD));
}
__device__ __forceinline__ void wgmma_ss_n72_t11(float (&d)[36], uint32_t descA, uint32_t descB, int scaleD) {
  asm volatile("{\n.reg .pred p;\n.reg .b64 da, db;\nsetp.ne.b32 p, %38, 0;\nmov.b64 da, {%36, 0x40000040};\nmov.b64 db, {%37, 0x40000040};\n"
    "wgmma.mma_async.sync.aligned.m64n72k16.f32.bf16.bf16 {%0,%1,%2,%3,%4,%5,%6,%7,%8,%9,%10,%11,%12,%13,%14,%15,%16,%17,%18,%19,%20,%21,%22,%23,%24,%25,%26,%27,%28,%29,%30,%31,%32,%33,%34,%35}, da, db, p, 1, 1, 1, 1;\n}\n"
    : "+f"(d[0]),"+f"(d[1]),"+f"(d[2]),"+f"(d[3]),"+f"(d[4]),"+f"(d[5]),"+f"(d[6]),"+f"(d[7]),"+f"(d[8]),"+f"(d[9]),"+f"(d[10]),"+f"(d[11]),"+f"(d[12]),"+f"(d[13]),"+f"(d[14]),"+f"(d[15]),"+f"(d[16]),"+f"(d[17]),"+f"(d[18]),"+f"(d[19]),"+f"(d[20]),"+f"(d[21]),"+f"(d[22]),"+f"(d[23]),"+f"(d[24]),"+f"(d[25]),"+f"(d[26]),"+f"(d[27]),"+f"(d[28]),"+f"(d[29]),"+f"(d[30]),"+f"(d[31]),"+f"(d[32]),"+f"(d[33]),"+f"(d[34]),"+f"(d[35])
    : "r"(descA), "r"(descB), "r"(scaleD));
}

constexpr float LOG2E = 1.4426950408889634f;

__device__ __forceinline__ void feat_exp(const uint32_t (&P)[4], float (&e)[16]) {
  uint32_t a = hmax2(P[0], P[2]), b = hmax2(P[1], P[3]);
  uint32_t mx = hmax2(__byte_perm(a, b, 0x5410), __byte_perm(a, b, 0x7632));
  a = hmin2(P[0], P[2]); b = hmin2(P[1], P[3]);
  uint32_t mn = hmin2(__byte_perm(a, b, 0x5410), __byte_perm(a, b, 0x7632));
  mx = hmax2(mx, __shfl_xor_sync(0xffffffffu, mx, 1));
  mn = hmin2(mn, __shfl_xor_sync(0xffffffffu, mn, 1));
  mx = hmax2(mx, __shfl_xor_sync(0xffffffffu, mx, 2));
  mn = hmin2(mn, __shfl_xor_sync(0xffffffffu, mn, 2));
  float mx0 = -blo(mx) * LOG2E, mx1 = -bhi(mx) * LOG2E, mn0 = blo(mn) * LOG2E, mn1 = bhi(mn) * LOG2E;
  float v[8] = {blo(P[0]), bhi(P[0]), blo(P[1]), bhi(P[1]), blo(P[2]), bhi(P[2]), blo(P[3]), bhi(P[3])};
#pragma unroll
  for (int i = 0; i < 8; i++) {
    bool r1 = (i >> 1) & 1;
    e[i]     = ex2(fmaf(v[i],  LOG2E, r1 ? mx1 : mx0));
    e[8 + i] = ex2(fmaf(v[i], -LOG2E, r1 ? mn1 : mn0));
  }
}

__global__ void __cluster_dims__(2, 1, 1) __launch_bounds__(384, 1)
fused_kernel(const __grid_constant__ Maps maps, const __nv_bfloat16* __restrict__ x, const __nv_bfloat16* __restrict__ wphi,
             const __nv_bfloat16* __restrict__ wo, const __nv_bfloat16* __restrict__ wg_, const __nv_bfloat16* __restrict__ wu_,
             const __nv_bfloat16* __restrict__ wd_, __nv_bfloat16* __restrict__ out) {
  extern __shared__ __align__(1024) unsigned char smem[];
  const uint32_t sb = smem_u32(smem);
  const int tid = threadIdx.x, lane = tid & 31;
  const int warp = __shfl_sync(0xffffffffu, tid >> 5, 0);
  const uint32_t rank = blockIdx.x & 1;
  const int cl = blockIdx.x >> 1;
  int quad, qi;
  if (cl < 4) { quad = 15; qi = cl; }
  else if (cl < 36) { quad = (cl - 4) & 7; qi = (cl - 4) >> 3; }
  else { qi = (cl - 36) / 7; quad = 8 + (cl - 36) - 7 * qi; }
  const int rb = quad, hg = 2 * qi + rank;
  const int rb3 = (quad & ~1) + rank, jf = 4 * (quad & 1) + qi;

  if (warp < 8) {
    asm volatile("setmaxnreg.inc.sync.aligned.u32 240;");
    if (elect_one()) {
#pragma unroll 1
      for (int d = warp; d + 9 < NSTAGE; d += 8) {
        mbar_init(sb + SM_EMPTY + d * 8, st_empty_cnt(d));
        mbar_init(sb + SM_FULL + (d + 9) * 8, 1);
        mbar_expect_tx(sb + SM_FULL + (d + 9) * 8, d + 9 >= ST_D ? 22528 : SLOT);
      }
      asm volatile("fence.mbarrier_init.release.cluster;" ::: "memory");
    }
    __syncwarp();
    bar_sync(0, 352);
    asm volatile("barrier.cluster.arrive.relaxed.aligned;" ::: "memory");
    const int wg = warp >> 2, wq = warp & 3, g = lane >> 2, t = lane & 3;
    const bool lead = (tid & 127) == 0;
    constexpr uint32_t db = (SM_BASE >> 4) | (512u << 16);
    auto release = [&](int d) {
      const int s = d + NSLOT;
      mbar_arrive_cluster(sb + SM_EMPTY + d * 8, s >= ST_GU ? (uint32_t)(s & 1) : rank);
    };
    const uint32_t lrow = (uint32_t)(wq * 16 + (lane & 7) + ((lane >> 3) & 1) * 8) * 128;
    const uint32_t lx = lane & 7, lhi = lane >> 4;
    if (wg == 1) bar_arrive(4, 256);

    float r0, r1;
    uint32_t E[4][8];
    uint32_t T = 0;
    {
      uint32_t A[32][4];
      const int sx = wg ? ST_X1 : ST_X0;
      {
        const uint32_t base = sb + sx * SLOT + lrow, baseb = sb + sx * SLOT + (wq * 16 + lx + lhi * 8) * 128;
        float cs[2][4], c0[2][4], c1[2][4];
#pragma unroll
        for (int i = 0; i < 4; i++) { cs[0][i] = cs[1][i] = c0[0][i] = c0[1][i] = c1[0][i] = c1[1][i] = 0.f; }
        uint32_t bt[2][4][4];
        if (wg == 1) bar_sync(13, 256);
#pragma unroll
        for (int c = -1; c < 8; c++) {
          if (c < 7) {
            const int n = c + 1;
            if (n % 3 == 0) mbar_wait(sb + SM_FULL + (sx + n / 3) * 8);
#pragma unroll
            for (int k = 0; k < 4; k++) {
              ldsm4(A[4 * n + k], base + n * 8192 + (((2 * k + lhi) ^ lx) << 4));
              ldsm4(bt[n & 1][k], baseb + n * 8192 + (((2 * k + ((lane >> 3) & 1)) ^ lx) << 4));
            }
          }
          if (c >= 0) {
#pragma unroll
            for (int k = 0; k < 4; k++) {
              const uint32_t (&f)[4] = A[4 * c + k];
              mma16816(cs[k & 1], f, 0x3F803F80u, 0x3F803F80u);
              mma16816(c0[k & 1], f, bt[c & 1][k][0], bt[c & 1][k][1]);
              mma16816(c1[k & 1], f, bt[c & 1][k][2], bt[c & 1][k][3]);
            }
          }
        }
        if (wg == 0) bar_arrive(13, 256);
        const float s0 = (cs[0][0] + cs[1][0]) * (1.f / 512.f), s1 = (cs[0][2] + cs[1][2]) * (1.f / 512.f);
        asm volatile("barrier.cluster.wait.aligned;" ::: "memory");
        if (lane < 3) release(sx + lane);
        const uint32_t m0 = pack2(s0, s0), m1 = pack2(s1, s1);
        float q0 = (g & 1) ? c0[0][1] + c0[1][1] : c0[0][0] + c0[1][0];
        float q1 = (g & 1) ? c1[0][3] + c1[1][3] : c1[0][2] + c1[1][2];
        q0 = __shfl_sync(0xffffffffu, q0, (lane & ~3) | (g >> 1));
        q1 = __shfl_sync(0xffffffffu, q1, (lane & ~3) | (g >> 1));
        r0 = rsqrtf(fmaxf(q0 * (1.f / 512.f) - s0 * s0, 0.f) + 1e-5f);
        r1 = rsqrtf(fmaxf(q1 * (1.f / 512.f) - s1 * s1, 0.f) + 1e-5f);
#pragma unroll
        for (int ks = 0; ks < 32; ks++) {
          A[ks][0] = hsub2(A[ks][0], m0); A[ks][1] = hsub2(A[ks][1], m1);
          A[ks][2] = hsub2(A[ks][2], m0); A[ks][3] = hsub2(A[ks][3], m1);
        }
      }
      const uint32_t wpa = sb + SM_WPHI + ((lane & 7) + ((lane >> 3) & 1) * 8) * 32 + lhi * 16;
      const uint32_t scr = sb + (wg ? (ST_SCR1 % NSLOT) : (ST_SCR0 % NSLOT)) * SLOT;
#pragma unroll 1
      for (int ps = 0; ps < 3; ps++) {
        const int st0 = ps == 0 ? ST_WK : (ps == 1 ? ST_WV : ST_WQ);
        const uint32_t wdesc = DESC((ps == 0 ? ST_WK % NSLOT : (ps == 1 ? ST_WV % NSLOT : ST_WQ % NSLOT)) * SLOT);
        float acc[32];
        bar_sync(4 + wg, 256);
#pragma unroll
        for (int i = 0; i < 3; i++) {
          mbar_wait(sb + SM_FULL + (st0 + i) * 8);
          wg_fence();
#pragma unroll
          for (int kk = 0; kk < (i < 2 ? 12 : 8); kk++)
            wgmma_rs_n64(acc, A[12 * i + kk], wdesc + ((i * SLOT + kk * 2048) >> 4), (i | kk) != 0);
          wg_commit();
          if (i == 1) { wg_wait<1>(); if (lead) release(st0); }
        }
        if (ps == 1 && wg == 0) bar_arrive(5, 256);
        uint32_t a[4][4], b[4][4];
        mbar_wait(sb + SM_MISCB);
        T = (*reinterpret_cast<volatile unsigned*>(smem + SM_EPOCH) & 1) ^ 1;
#pragma unroll
        for (int h = 0; h < 4; h++) ldsm4t(b[h], wpa + h * 512);
        wg_wait<0>();
        if ((tid & 127) < 2) release(st0 + 1 + (tid & 1));
#pragma unroll
        for (int h = 0; h < 4; h++) {
          a[h][0] = pack2(acc[8 * h + 0] * r0, acc[8 * h + 1] * r0); a[h][1] = pack2(acc[8 * h + 2] * r1, acc[8 * h + 3] * r1);
          a[h][2] = pack2(acc[8 * h + 4] * r0, acc[8 * h + 5] * r0); a[h][3] = pack2(acc[8 * h + 6] * r1, acc[8 * h + 7] * r1);
        }
        if (ps != 1) {
          {
            float pp[4][2][4];
#pragma unroll
            for (int h = 0; h < 4; h++) {
#pragma unroll
              for (int i = 0; i < 4; i++) { pp[h][0][i] = 0.f; pp[h][1][i] = 0.f; }
              mma16816(pp[h][0], a[h], b[h][0], b[h][1]);
              mma16816(pp[h][1], a[h], b[h][2], b[h][3]);
            }
#pragma unroll
            for (int h = 0; h < 4; h++) {
              a[h][0] = pack2(pp[h][0][0], pp[h][0][1]); a[h][1] = pack2(pp[h][0][2], pp[h][0][3]);
              a[h][2] = pack2(pp[h][1][0], pp[h][1][1]); a[h][3] = pack2(pp[h][1][2], pp[h][1][3]);
            }
          }
          if (ps == 0 || wg == 0) bar_arrive(4 + (wg ^ 1), 256);
          if (ps == 0) mbar_wait(sb + SM_EMPTY + (wg ? ST_SCR1 - NSLOT : ST_SCR0 - NSLOT) * 8);
#pragma unroll 1
          for (int hp = 0; hp < 2; hp++) {
            float e[2][16];
            feat_exp(a[0], e[0]);
            feat_exp(a[1], e[1]);
            if (ps == 0) {
#pragma unroll
              for (int h = 0; h < 2; h++) {
                const float (&f)[16] = e[h];
                float sp0 = (f[0] + f[1]) + (f[4] + f[5]), sp1 = (f[2] + f[3]) + (f[6] + f[7]);
                float sn0 = (f[8] + f[9]) + (f[12] + f[13]), sn1 = (f[10] + f[11]) + (f[14] + f[15]);
                sp0 += __shfl_xor_sync(0xffffffffu, sp0, 1); sp1 += __shfl_xor_sync(0xffffffffu, sp1, 1);
                sn0 += __shfl_xor_sync(0xffffffffu, sn0, 1); sn1 += __shfl_xor_sync(0xffffffffu, sn1, 1);
                sp0 += __shfl_xor_sync(0xffffffffu, sp0, 2); sp1 += __shfl_xor_sync(0xffffffffu, sp1, 2);
                sn0 += __shfl_xor_sync(0xffffffffu, sn0, 2); sn1 += __shfl_xor_sync(0xffffffffu, sn1, 2);
                sp0 = rcp(sp0); sp1 = rcp(sp1); sn0 = rcp(sn0); sn1 = rcp(sn1);
                const uint32_t dst = scr + hp * 8192 + lrow;
                stsm4(dst + (((h * 4 + lhi) ^ lx) << 4), pack2(f[0] * sp0, f[1] * sp0), pack2(f[2] * sp1, f[3] * sp1),
                      pack2(f[4] * sp0, f[5] * sp0), pack2(f[6] * sp1, f[7] * sp1));
                stsm4(dst + (((h * 4 + 2 + lhi) ^ lx) << 4), pack2(f[8] * sn0, f[9] * sn0), pack2(f[10] * sn1, f[11] * sn1),
                      pack2(f[12] * sn0, f[13] * sn0), pack2(f[14] * sn1, f[15] * sn1));
              }
            } else {
#pragma unroll
              for (int i = 0; i < 16; i++) {
                A[i >> 2][i & 3] = A[4 + (i >> 2)][i & 3];
                A[4 + (i >> 2)][i & 3] = pack2(e[i >> 3][2 * (i & 7)], e[i >> 3][2 * (i & 7) + 1]);
              }
            }
#pragma unroll
            for (int i = 0; i < 4; i++) { a[0][i] = a[2][i]; a[1][i] = a[3][i]; }
          }
        } else {
#pragma unroll
          for (int h = 0; h < 4; h++) stsm4(scr + 16384 + lrow + (((2 * h + lhi) ^ lx) << 4), a[h][0], a[h][1], a[h][2], a[h][3]);
          fence_async_smem();
          if (wg == 0) {
            bar_arrive(3, 256);
          } else {
            bar_sync(3, 256);
            float kv[2][36];
            wg_fence();
#pragma unroll
            for (int ks = 0; ks < 8; ks++) {
              const uint32_t sk = (ks < 4 ? (ST_SCR0 % NSLOT) : (ST_SCR1 % NSLOT)) * SLOT + (ks & 3) * 2048;
              const uint32_t dv = (DESC(sk + 16384) & 0xFFFFu) | (((SM_ONES - sk - 16384) >> 4) << 16);
              wgmma_ss_n72_t11(kv[0], DESC(sk), dv, ks != 0);
              wgmma_ss_n72_t11(kv[1], DESC(sk + 8192), dv, ks != 0);
            }
            wg_commit();
            bar_arrive(4, 256);
            wg_wait<0>();
            if (lead) { mbar_arrive(sb + SM_EMPTY + ST_SCR0 * 8); mbar_arrive(sb + SM_EMPTY + ST_SCR1 * 8); }
            const bool up = wq >= 2;
            float* kvp = reinterpret_cast<float*>(smem + 2 * SLOT) + (wq * 16 + g) * 24;
#pragma unroll
            for (int i = 0; i < 4; i++) {
              const int d = (i >> 1) * 8 + 2 * t + (i & 1), pos = d + ((d * 11) >> 5);
#pragma unroll
              for (int b = 0; b < 2; b++) {
                const int r = 16 * b + (i >> 1) * 4 + (i & 1);
                kvp[pos + b * 64 * 24] = up ? kv[b][r + 8] : kv[b][r];
                kvp[pos + (b * 64 + 8) * 24] = up ? kv[b][r + 10] : kv[b][r + 2];
              }
            }
            kvp[((t >> 1) * 64 + (t & 1) * 8) * 24 + 21] = (t & 2) ? ((t & 1) ? kv[1][34] : kv[1][32]) : ((t & 1) ? kv[0][34] : kv[0][32]);
            fence_async_smem();
            bar_sync(6, 192);
          }
        }
      }
#pragma unroll
      for (int i = 0; i < 32; i++) E[i >> 3][i & 7] = A[i >> 2][i & 3];
    }
    const int rh = 2 * rb + wg;
#define IDF ((g >> 1) == t ? ((g & 1) ? 0x3F800000u : 0x00003F80u) : 0u)
    const uint4* xb = reinterpret_cast<const uint4*>(smem + 2 * SLOT) + wq * 128 + lane;
    if (wg == 0) {
      mbar_wait(sb + SM_KVB);
      const uint4* sp = reinterpret_cast<const uint4*>(smem + 3 * SLOT) + tid * 6;
      uint32_t v[6][4];
      int it = 0;
#pragma unroll 1
      do {
#pragma unroll
        for (int i = 0; i < 6; i++)
          asm volatile("{\n.reg .b128 v;\nld.relaxed.gpu.b128 v, [%4];\nmov.b128 {%0,%1,%2,%3}, v;\n}"
                       : "=r"(v[i][0]), "=r"(v[i][1]), "=r"(v[i][2]), "=r"(v[i][3]) : "l"(sp + i) : "memory");
        sp = reinterpret_cast<const uint4*>(&g_kv[hg][tid][0]);
      } while (min(min(min(v[0][3], v[1][3]), min(v[2][3], v[3][3])), min(v[4][3], v[5][3])) != 0x41800000u && ++it < (1 << 18));
#define KVF(d) __uint_as_float(v[(d) / 3][(d) % 3])
      uint4* dst = reinterpret_cast<uint4*>(smem + SM_KVS + tid * 48);
      const uint32_t zz = pack2(KVF(16), 1.0f);
      dst[0] = make_uint4(pack2(KVF(0), KVF(1)), pack2(KVF(2), KVF(3)), pack2(KVF(4), KVF(5)), pack2(KVF(6), KVF(7)));
      dst[1] = make_uint4(pack2(KVF(8), KVF(9)), pack2(KVF(10), KVF(11)), pack2(KVF(12), KVF(13)), pack2(KVF(14), KVF(15)));
      dst[2] = make_uint4(zz, zz, zz, zz);
      __syncwarp();
      bar_sync(1, 128);
    }
    {
      uint4* op = &g_o[rh][hg][wq][0][lane];
      if (wg == 1) bar_sync(7, 256);
#pragma unroll 1
      for (int hp = 0; hp < 2; hp++) {
#pragma unroll
      for (int h = 0; h < 2; h++) {
        uint32_t b0[4], b1[4], b2[4];
        const uint32_t kb = sb + SM_KVS + ((2 * hp + h) * 32 + lane) * 48;
        ldsm4t(b0, kb); ldsm4t(b1, kb + 16); ldsm4t(b2, kb + 32);
        const uint32_t ep[4] = {E[h][0], E[h][1], E[h][2], E[h][3]}, en[4] = {E[h][4], E[h][5], E[h][6], E[h][7]};
        float np0[4] = {0, 0, 0, 0}, np1[4] = {0, 0, 0, 0}, nn0[4] = {0, 0, 0, 0}, nn1[4] = {0, 0, 0, 0}, dp[4] = {0, 0, 0, 0}, dn[4] = {0, 0, 0, 0};
        mma16816(dp, ep, b2[0], b2[1]);  mma16816(dn, en, b2[2], b2[3]);
        mma16816(np0, ep, b0[0], b0[1]); mma16816(nn0, en, b0[2], b0[3]);
        mma16816(np1, ep, b1[0], b1[1]); mma16816(nn1, en, b1[2], b1[3]);
        const float i0 = rcp(fmaf(dp[0], dn[1], fmaf(dn[0], dp[1], 1e-6f * dp[1] * dn[1])));
        const float i1 = rcp(fmaf(dp[2], dn[3], fmaf(dn[2], dp[3], 1e-6f * dp[3] * dn[3])));
        const float cp0 = dn[1] * i0, cn0 = dp[1] * i0, cp1 = dn[3] * i1, cn1 = dp[3] * i1;
        st_rlx4(op + (2 * hp + h) * 32,
                tg(pack2(fmaf(np0[0], cp0, nn0[0] * cn0), fmaf(np0[1], cp0, nn0[1] * cn0)), T),
                pack2(fmaf(np0[2], cp1, nn0[2] * cn1), fmaf(np0[3], cp1, nn0[3] * cn1)),
                pack2(fmaf(np1[0], cp0, nn1[0] * cn0), fmaf(np1[1], cp0, nn1[1] * cn0)),
                pack2(fmaf(np1[2], cp1, nn1[2] * cn1), fmaf(np1[3], cp1, nn1[3] * cn1)));
      }
#pragma unroll
        for (int i = 0; i < 8; i++) { E[0][i] = E[2][i]; E[1][i] = E[3][i]; }
      }
    }
    if (wg == 0) bar_arrive(7, 256);
    bar_arrive(10 + wg, 160);

    {
      uint32_t xr[4][4];
      {
        const uint32_t* xp = reinterpret_cast<const uint32_t*>(x + (size_t)(rh * 64 + wq * 16 + g) * 512 + hg * 64 + 2 * t);
#pragma unroll
        for (int i = 0; i < 8; i++) { xr[i >> 1][(i & 1) * 2] = __ldg(xp + 4 * i); xr[i >> 1][(i & 1) * 2 + 1] = __ldg(xp + 8 * 256 + 4 * i); }
      }
      uint32_t A[8][4][4];
      const uint4* op = &g_o[rh][0][wq][0][lane];
      float acc[32];
#pragma unroll
      for (int i = 0; i < 32; i++) acc[i] = 0.f;
      add_frag(acc, xr, IDF);
#pragma unroll
      for (int p = -1; p < 4; p++) {
        if (p < 3) {
          mbar_wait(sb + SM_XF + (wg * 4 + p + 1) * 8);
          get_pair(A[2 * p + 2], A[2 * p + 3], xb + (p + 1) * 1024, op + (p + 1) * 1024, T);
          if (lane == 0) mbar_arrive(sb + SM_XE + (wg * 4 + p + 1) * 8);
        }
        if (p == 0 && wg == 1) bar_sync(14, 256);
        if (p >= 0) {
          if (p != 2) mbar_wait(sb + SM_FULL + (ST_WO + (p + 1) / 2) * 8);
          wg_fence();
#pragma unroll
          for (int c = 2 * p; c < 2 * p + 2; c++)
#pragma unroll
            for (int s = 0; s < 4; s++)
              wgmma_rs_n64(acc, A[c][s], DESC(((ST_WO + c / 3) % NSLOT) * SLOT + ((c % 3) * 4 + s) * 2048), 1);
        }
      }
      wg_commit();
      if (wg == 0) bar_arrive(14, 256);
      wg_wait<0>();
      if ((tid & 127) < 3) release(ST_WO + (tid & 127));
      uint4* hp_ = &g_h[rh][hg][wq][0][lane];
      uint32_t hx = T;
#pragma unroll
      for (int s = 0; s < 4; s++) {
        const uint32_t h0 = pack2(acc[8 * s], acc[8 * s + 1]);
        st_rlx4(hp_ + s * 32, tg(h0, T), pack2(acc[8 * s + 2], acc[8 * s + 3]), pack2(acc[8 * s + 4], acc[8 * s + 5]), pack2(acc[8 * s + 6], acc[8 * s + 7]));
        hx |= (h0 & 1u) << (s + 1);
      }
      float s0 = 0.f, s1 = 0.f, q0 = 0.f, q1 = 0.f, q2 = 0.f, q3 = 0.f;
#pragma unroll
      for (int i = 0; i < 8; i++) {
        s0 += acc[4 * i] + acc[4 * i + 1]; s1 += acc[4 * i + 2] + acc[4 * i + 3];
        q0 = fmaf(acc[4 * i], acc[4 * i], q0); q2 = fmaf(acc[4 * i + 1], acc[4 * i + 1], q2);
        q1 = fmaf(acc[4 * i + 2], acc[4 * i + 2], q1); q3 = fmaf(acc[4 * i + 3], acc[4 * i + 3], q3);
      }
      q0 += q2; q1 += q3;
      {
        const bool up = t & 2;
        float s = (up ? s1 : s0) + __shfl_xor_sync(0xffffffffu, up ? s0 : s1, 2);
        float q = (up ? q1 : q0) + __shfl_xor_sync(0xffffffffu, up ? q0 : q1, 2);
        s += __shfl_xor_sync(0xffffffffu, s, 1);
        q += __shfl_xor_sync(0xffffffffu, q, 1);
        if (!(t & 1)) st_rlx2(&g_st[rh][hg][wq * 16 + g + (t >> 1) * 8], tg(__float_as_uint(s), T), __float_as_uint(q));
      }
      st_rlx1(&g_hx[rh][hg][wq][lane], hx);
    }
    bar_arrive(10 + wg, 160);

    const int rh3 = 2 * rb3 + wg;
    uint32_t HH[11][4], PH[11][4];
    const uint4* pp = &g_hh[rh3][jf ^ 1][0][wq][lane];
    {
      uint32_t A[8][4][4];
      const uint4* hp_ = &g_h[rh3][0][wq][0][lane];
      uint4* hhp = &g_hh[rh3][jf][0][wq][lane];
      const uint32_t dg = (db & 0xFFFFu) | (256u << 16);
      uint32_t m0, m1;
      mbar_wait(sb + SM_XF + ((2 + wg) * 4) * 8);
      {
        const uint2* sp = reinterpret_cast<const uint2*>(smem + SM_KV32 + wg * 4096) + 2 * t * 64 + wq * 16 + g;
        uint2 a0, a1, b0, b1;
        int it = 0;
#pragma unroll 1
        do {
          ld_rlx2(a0.x, a0.y, sp); ld_rlx2(a1.x, a1.y, sp + 64); ld_rlx2(b0.x, b0.y, sp + 8); ld_rlx2(b1.x, b1.y, sp + 72);
          sp = &g_st[rh3][2 * t][wq * 16 + g];
        } while (__any_sync(0xffffffffu, bad4(a0.x, a1.x, b0.x, b1.x, T)) && ++it < (1 << 18));
        float s0 = __uint_as_float(a0.x) + __uint_as_float(a1.x), q0 = __uint_as_float(a0.y) + __uint_as_float(a1.y);
        float s1 = __uint_as_float(b0.x) + __uint_as_float(b1.x), q1 = __uint_as_float(b0.y) + __uint_as_float(b1.y);
        s0 += __shfl_xor_sync(0xffffffffu, s0, 1); s1 += __shfl_xor_sync(0xffffffffu, s1, 1);
        q0 += __shfl_xor_sync(0xffffffffu, q0, 1); q1 += __shfl_xor_sync(0xffffffffu, q1, 1);
        s0 += __shfl_xor_sync(0xffffffffu, s0, 2); s1 += __shfl_xor_sync(0xffffffffu, s1, 2);
        q0 += __shfl_xor_sync(0xffffffffu, q0, 2); q1 += __shfl_xor_sync(0xffffffffu, q1, 2);
        s0 *= (1.f / 512.f); s1 *= (1.f / 512.f);
        r0 = rcp(fmaxf(q0 * (1.f / 512.f) - s0 * s0, 0.f) + 1e-5f);
        r1 = rcp(fmaxf(q1 * (1.f / 512.f) - s1 * s1, 0.f) + 1e-5f);
        m0 = pack2(s0, s0); m1 = pack2(s1, s1);
      }
#define UOFF(u) ((((ST_GU + (u) / 3) % NSLOT) * SLOT + ((u) % 3) * 8192) >> 4)
#define UNIT_PRE(u)  do { if ((u) % 3 == 0) mbar_wait(sb + SM_FULL + (ST_GU + (u) / 3) * 8); } while (0)
#define UNIT_POST(u) do { wg_commit(); if ((u) % 3 == 1 && (u) > 3) { wg_wait<2>(); if (lead) release(ST_GU + (u) / 3 - 1); } } while (0)
      float acc[64];
      const int rz = blockIdx.y;
#pragma unroll
      for (int ps = 0; ps < 2; ps++) {
        wg_fence();
#pragma unroll
        for (int k = 0; k < 16; k++) {
          const int u = 16 * ps + k, c = k >> 1;
          if (ps == 0 && (k == 0 || k == 4 || k == 8)) {
#pragma unroll
            for (int p = (k == 0 ? 0 : (k == 4 ? 1 : 3)); p < (k == 0 ? 1 : (k == 4 ? 3 : 4)); p++) {
              if (p > 0) mbar_wait(sb + SM_XF + ((2 + wg) * 4 + p) * 8);
              get_pair(A[2 * p], A[2 * p + 1], xb + p * 1024, hp_ + p * 1024, T);
              if (lane == 0) {
                if (wg == 0) mbar_arrive(sb + SM_XE + (8 + p) * 8);
                else if (p > 0) release(ST_XC + p - 1);
              }
            }
          }
          if (ps == 0 && (k & 1) == 0) {
#pragma unroll
            for (int s = 0; s < 4; s++) {
              A[c][s][0] = hsub2(A[c][s][0], m0); A[c][s][1] = hsub2(A[c][s][1], m1);
              A[c][s][2] = hsub2(A[c][s][2], m0); A[c][s][3] = hsub2(A[c][s][3], m1);
            }
            wg_fence();
          }
          UNIT_PRE(u);
          wgmma_rs_n128(acc, A[c][(k & 1) * 2], dg + UOFF(u), k != 0 ? 1 : (ps ? rz : 0));
          wgmma_rs_n128(acc, A[c][(k & 1) * 2 + 1], dg + UOFF(u) + 128, 1);
          UNIT_POST(u);
        }
        wg_wait<0>();
#pragma unroll
        for (int s = 0; s < 4; s++) {
          uint32_t (&hh)[4] = HH[4 + s];
          hh[0] = tg(pack2(acc[8 * s + 0] * acc[32 + 8 * s + 0], acc[8 * s + 1] * acc[32 + 8 * s + 1]), T);
          hh[1] = pack2(acc[8 * s + 2] * acc[32 + 8 * s + 2], acc[8 * s + 3] * acc[32 + 8 * s + 3]);
          hh[2] = pack2(acc[8 * s + 4] * acc[32 + 8 * s + 4], acc[8 * s + 5] * acc[32 + 8 * s + 5]);
          hh[3] = pack2(acc[8 * s + 6] * acc[32 + 8 * s + 6], acc[8 * s + 7] * acc[32 + 8 * s + 7]);
          st_rlx4(hhp + (4 * ps + s) * 128, hh[0], hh[1], hh[2], hh[3]);
        }
      }
      {
        float ag[24], au[24];
        const uint32_t* ph7 = reinterpret_cast<const uint32_t*>(&g_hh[rh3][jf ^ 1][7][wq][31]);
        uint32_t hv = 0;
        bar_sync(1 + wg, 128);
        wg_fence();
#pragma unroll
        for (int k = 0; k < 16; k++) {
          const int u = 32 + k, c = k >> 1;
          if (k == 6) {
#pragma unroll
            for (int s = 0; s < 4; s++) ld_rlx4(HH[s], hhp + s * 128);
          }
          if (k == 9) hv = ld_rlx1(ph7);
          if (k == 12) {
            int it = 0;
#pragma unroll 1
            while (((hv ^ T) & 1) && ++it < (1 << 18)) hv = ld_rlx1(ph7);
#pragma unroll
            for (int s = 0; s < 8; s++) ld_rlx4(PH[s], pp + s * 128);
          }
          UNIT_PRE(u);
          wgmma_rs_n48(ag, A[c][(k & 1) * 2], dg + UOFF(u), k != 0);
          wgmma_rs_n48(au, A[c][(k & 1) * 2], dg + UOFF(u) + 256, k != 0);
          wgmma_rs_n48(ag, A[c][(k & 1) * 2 + 1], dg + UOFF(u) + 128, 1);
          wgmma_rs_n48(au, A[c][(k & 1) * 2 + 1], dg + UOFF(u) + 256 + 128, 1);
          UNIT_POST(u);
        }
        wg_wait<0>();
#pragma unroll
        for (int s = 0; s < 3; s++) {
          uint32_t (&hh)[4] = HH[8 + s];
          hh[0] = tg(pack2(ag[8 * s + 0] * au[8 * s + 0], ag[8 * s + 1] * au[8 * s + 1]), T);
          hh[1] = pack2(ag[8 * s + 2] * au[8 * s + 2], ag[8 * s + 3] * au[8 * s + 3]);
          hh[2] = pack2(ag[8 * s + 4] * au[8 * s + 4], ag[8 * s + 5] * au[8 * s + 5]);
          hh[3] = pack2(ag[8 * s + 6] * au[8 * s + 6], ag[8 * s + 7] * au[8 * s + 7]);
          st_rlx4(hhp + (8 + s) * 128, hh[0], hh[1], hh[2], hh[3]);
        }
      }
    }

    {
      float ac[3][32], acc[32];
      uint32_t hr[4][4];
      const int m = jf >> 1, oc = (jf & 1) * 4 + m;
      const uint32_t* ph10 = reinterpret_cast<const uint32_t*>(&g_hh[rh3][jf ^ 1][10][wq][31]);
      uint32_t hv = 0;
      bar_arrive(8 + wg, 256);
      wg_fence();
#pragma unroll
      for (int k = 0; k < 3; k++) {
        mbar_wait(sb + SM_FULL + (ST_D + k) * 8);
        if (k == 1) hv = ld_rlx1(ph10);
#pragma unroll
        for (int s = 0; s < 11; s++) {
          if (k == 2 && s == 4) {
            int it = 0;
#pragma unroll 1
            while (((hv ^ T) & 1) && ++it < (1 << 18)) hv = ld_rlx1(ph10);
#pragma unroll
            for (int i = 8; i < 11; i++) ld_rlx4(PH[i], pp + i * 128);
          }
          wgmma_rs_n64(ac[k], HH[s], DESC(((ST_D + k) % NSLOT) * SLOT + s * 2048), s != 0);
        }
      }
      wg_commit();
      {
        int it = 0;
#pragma unroll 1
        while (__any_sync(0xffffffffu, bad4(PH[0][0], PH[1][0], PH[2][0], PH[3][0], T) | bad4(PH[4][0], PH[5][0], PH[6][0], PH[7][0], T) |
                                       bad4(PH[8][0], PH[9][0], PH[10][0], T, T))) {
#pragma unroll
          for (int s = 0; s < 11; s++) ld_rlx4(PH[s], pp + s * 128);
          if (++it > (1 << 18)) break;
        }
      }
      uint4* outb = &g_part[rh3][(jf & 1) * 4][m][wq][0][lane];
#pragma unroll
      for (int k = 0; k < 4; k++) {
        mbar_wait(sb + SM_FULL + (ST_D + 3 + k) * 8);
        wg_fence();
#pragma unroll
        for (int s = 0; s < 11; s++) {
          if (k < 3) wgmma_rs_n64(ac[k], PH[s], DESC(((ST_D + 3 + k) % NSLOT) * SLOT + s * 2048), 1);
          else wgmma_rs_n64(acc, HH[s], DESC(((ST_D + 6) % NSLOT) * SLOT + s * 2048), s != 0);
          if (s == 6 && k > 0) {
            wg_commit();
            wg_wait<1>();
            if (k == 1) bar_arrive(12, 320);
            const float (&a)[32] = ac[k - 1];
            uint4* p = outb + ((m + k) & 3) * 2048;
#pragma unroll
            for (int i = 0; i < 4; i++)
              st_rlx4(p + i * 32, tg(pack2(a[8 * i + 0], a[8 * i + 1]), T), pack2(a[8 * i + 2], a[8 * i + 3]),
                      pack2(a[8 * i + 4], a[8 * i + 5]), pack2(a[8 * i + 6], a[8 * i + 7]));
          }
        }
        wg_commit();
      }
      ld_chunk(hr, &g_h[rh3][oc][wq][0][lane]);
      uint32_t hx = ld_rlx1(&g_hx[rh3][oc][wq][lane]);
      mbar_wait(sb + SM_FULL + (ST_D + 7) * 8);
      wg_fence();
#pragma unroll
      for (int s = 0; s < 11; s++) wgmma_rs_n64(acc, PH[s], DESC(((ST_D + 7) % NSLOT) * SLOT + s * 2048), 1);
      wg_commit();
      wg_wait<0>();
#pragma unroll 1
      for (int q = 0; q < 3; q++) {
        uint32_t in[4][4];
        const uint4* sp = reinterpret_cast<const uint4*>(smem + ((ST_D % NSLOT) + wg) * SLOT) + q * 512 + wq * 128 + lane;
        mbar_wait_p(sb + SM_XF + (wg * 4 + q) * 8, 1);
        int it = 0;
#pragma unroll 1
        do {
#pragma unroll
          for (int s = 0; s < 4; s++)
            asm volatile("{\n.reg .b128 v;\nld.relaxed.gpu.b128 v, [%4];\nmov.b128 {%0,%1,%2,%3}, v;\n}"
                         : "=r"(in[s][0]), "=r"(in[s][1]), "=r"(in[s][2]), "=r"(in[s][3]) : "l"(sp + s * 32) : "memory");
          sp = &g_part[rh3][oc][(m - 1 - q) & 3][wq][0][lane];
        } while (__any_sync(0xffffffffu, bad4(in[0][0], in[1][0], in[2][0], in[3][0], T)) && ++it < (1 << 18));
        add_frag(acc, in, IDF);
      }
      {
        int it = 0;
#pragma unroll 1
        while (__any_sync(0xffffffffu, (hx ^ T) & 1) && ++it < (1 << 18)) hx = ld_rlx1(&g_hx[rh3][oc][wq][lane]);
      }
#pragma unroll
      for (int s = 0; s < 4; s++) hr[s][0] = (hr[s][0] & 0xFFFFFFFEu) | ((hx >> (s + 1)) & 1u);
#pragma unroll
      for (int i = 0; i < 32; i++) acc[i] *= (i & 2) ? r1 : r0;
      add_frag(acc, hr, IDF);
      bar_sync(9 - wg, 256);
      const uint32_t ob = sb + ((ST_D - 1) % NSLOT) * SLOT + wg * 8192;
#pragma unroll
      for (int s = 0; s < 4; s++)
        stsm4(ob + lrow + (((2 * s + lhi) ^ lx) << 4), pack2(acc[8 * s + 0], acc[8 * s + 1]), pack2(acc[8 * s + 2], acc[8 * s + 3]),
              pack2(acc[8 * s + 4], acc[8 * s + 5]), pack2(acc[8 * s + 6], acc[8 * s + 7]));
      __syncwarp();
      {
        const int row = wq * 16 + (lane >> 3);
        __nv_bfloat16* op = out + (size_t)(rh3 * 64 + row) * 512 + oc * 64 + lx * 8;
#pragma unroll
        for (int i = 0; i < 4; i++) {
          uint4 v;
          asm volatile("ld.shared.v4.b32 {%0,%1,%2,%3}, [%4];" : "=r"(v.x), "=r"(v.y), "=r"(v.z), "=r"(v.w)
                       : "r"(ob + (row + i * 4) * 128 + ((lx ^ (((lane >> 3) + i * 4) & 7)) << 4)) : "memory");
          asm volatile("st.global.v4.b32 [%0], {%1,%2,%3,%4};" ::"l"(op + i * 2048), "r"(v.x), "r"(v.y), "r"(v.z), "r"(v.w) : "memory");
        }
      }
    }
    asm volatile("barrier.cluster.arrive.relaxed.aligned;" ::: "memory");
    asm volatile("barrier.cluster.wait.aligned;" ::: "memory");
  } else {
    asm volatile("setmaxnreg.dec.sync.aligned.u32 24;");
    if (elect_one()) {
      if (warp == 8) {
#pragma unroll
        for (int k = 0; k < 9; k++) {
          const int s = k < 3 ? k : (k < 6 ? k + 3 : k - 3);
          const uint32_t bar = sb + SM_FULL + s * 8;
          mbar_init(bar, 1);
          mbar_expect_tx(bar, SLOT);
          if (s >= 3 && s < 6) tma2d(sb + s * SLOT, &maps.w, 512 + hg * 64, (s - 3) * 192, bar);
          else tma3d(sb + s * SLOT, &maps.x, 0, rb * 128 + (s >= 6 ? 64 : 0), 3 * (s % 3), bar);
        }
      } else if (warp == 9) {
        mbar_init(sb + SM_MISCB, 2);
        mbar_init(sb + SM_KVB, 2);
        mbar_expect_tx(sb + SM_KVB, 12288);
        mbar_expect_tx(sb + SM_MISCB, 2048);
        bulk_g2s(sb + SM_WPHI, wphi + hg * 1024, 2048, sb + SM_MISCB);
      } else if (warp == 10) {
        if ((sb & 0x3FFFF) != SM_BASE) __trap();
#pragma unroll 1
        for (int i = 0; i < 16; i++) {
          mbar_init(sb + SM_XF + i * 8, 1);
          mbar_expect_tx(sb + SM_XF + i * 8, (i == 8 || i == 12) ? 20480 : 16384);
          if (i < 12) mbar_init(sb + SM_XE + i * 8, 4);
        }
      } else {
        *reinterpret_cast<volatile unsigned*>(smem + SM_EPOCH) = atomicAdd(&g_start, 1u) / NCTA;
      }
      asm volatile("fence.mbarrier_init.release.cluster;" ::: "memory");
    }
    __syncwarp();
    if (warp != 11) bar_sync(0, 352);
    asm volatile("barrier.cluster.arrive.relaxed.aligned;" ::: "memory");
    if (warp == 8) {
      asm volatile("barrier.cluster.wait.aligned;" ::: "memory");
      if (elect_one()) {
        const CUtensorMap* mg = jf == 7 ? &maps.g7 : &maps.g;
        const CUtensorMap* mu = jf == 7 ? &maps.u7 : &maps.u;
        asm volatile("prefetch.tensormap [%0];" ::"l"(&maps.wo) : "memory");
        asm volatile("prefetch.tensormap [%0];" ::"l"(mg) : "memory");
        asm volatile("prefetch.tensormap [%0];" ::"l"(mu) : "memory");
        asm volatile("prefetch.tensormap [%0];" ::"l"(&maps.d) : "memory");
#pragma unroll 1
        for (int s = ST_WV; s < ST_XC; s++) {
          if (s == ST_SCR1) continue;
          mbar_wait(sb + SM_EMPTY + (s - 9) * 8);
          const uint32_t dst = sb + (s >= 18 ? s - 18 : s - 9) * SLOT, bar = sb + SM_FULL + s * 8;
          if (s < ST_WO) tma2d(dst, &maps.w, (s < ST_WQ ? 1024 : 0) + hg * 64, (s < ST_WQ ? s - ST_WV : s - ST_WQ) * 192, bar);
          else { mbar_wait(bar - 8); tma2d(dst, &maps.wo, hg * 64, (s - ST_WO) * 192, bar); }
        }
        const int jc = jf == 7 ? 0 : jf;
        int slot = (ST_GU + 1 - rank) % NSLOT;
#pragma unroll 1
        for (int s = ST_GU + 1 - rank; s < NSTAGE; s += 2) {
          mbar_wait(sb + SM_EMPTY + (s - 9) * 8);
          if (s > ST_GU && s < ST_GU + 6) mbar_wait(sb + SM_FULL + (s - 1) * 8);
          const uint32_t dst = sb + slot * SLOT, bar = sb + SM_FULL + s * 8;
          if (s < ST_D) {
#pragma unroll 1
            for (int i = 0; i < 3; i++) {
              const int u = (s - ST_GU) * 3 + i;
              tma3d_mc(dst + i * 8192, mg, (u >> 4) * 64, jc, (u & 15) * 32, bar);
              tma3d_mc(dst + i * 8192 + 4096, mu, (u >> 4) * 64, jc, (u & 15) * 32, bar);
            }
          } else {
            const int i = s - ST_D, k = i < 3 ? i : (i < 6 ? i - 3 : 3), pt = (i >= 3 && i != 6) ? 1 : 0;
            tma2d_mc(dst, &maps.d, ((jf & 1) * 4 + (((jf >> 1) + 1 + k) & 3)) * 64, (jf ^ pt) * 176, bar);
          }
          slot += 2; if (slot >= NSLOT) slot -= NSLOT;
        }
      }
      __syncwarp();
    } else {
      asm volatile("barrier.cluster.wait.aligned;" ::: "memory");
      if (warp == 11) {
#pragma unroll
        for (int i = 0; i < 4; i++)
          reinterpret_cast<uint4*>(smem + SM_ONES)[lane + 32 * i] = make_uint4(0x3F803F80u, 0x3F803F80u, 0x3F803F80u, 0x3F803F80u);
        fence_async_smem();
        __syncwarp();
        if (lane == 0) mbar_arrive(sb + SM_MISCB);
      }
      mbar_wait(sb + SM_MISCB);
      const unsigned epoch = *reinterpret_cast<volatile unsigned*>(smem + SM_EPOCH);
      const uint32_t T = (epoch & 1) ^ 1;
      if (warp == 11) {
        (&g_kv[hg][rb * 8][0])[lane] = make_float4(0.f, 0.f, 0.f, 0.f);
        if (lane < 16) (&g_kv[hg][rb * 8][0])[32 + lane] = make_float4(0.f, 0.f, 0.f, 0.f);
        __syncwarp();
        if (elect_one()) asm volatile("red.release.gpu.global.add.u32 [%0], 8;" ::"l"(&g_kvcnt[hg * 32 + 1]) : "memory");
        mbar_wait(sb + SM_FULL + (ST_WK + 2) * 8);
        if (elect_one()) {
          asm volatile("cp.async.bulk.prefetch.L2.global [%0], 4096;" ::"l"((const char*)wo + blockIdx.x * 4096) : "memory");
          asm volatile("cp.async.bulk.prefetch.L2.global [%0], 11008;" ::"l"((const char*)wg_ + blockIdx.x * 11008) : "memory");
          asm volatile("cp.async.bulk.prefetch.L2.global [%0], 11008;" ::"l"((const char*)wu_ + blockIdx.x * 11008) : "memory");
          asm volatile("cp.async.bulk.prefetch.L2.global [%0], 11008;" ::"l"((const char*)wd_ + blockIdx.x * 11008) : "memory");
          mbar_wait(sb + SM_EMPTY + ST_SCR0 * 8);
          const unsigned target = (epoch + 1) * 128;
          unsigned v, z; int it = 0;
#pragma unroll 1
          do {
            asm volatile("{\n.reg .b64 q;\nld.acquire.gpu.global.b64 q, [%2];\nmov.b64 {%0, %1}, q;\n}" : "=r"(v), "=r"(z) : "l"(&g_kvcnt[hg * 32]) : "memory");
            if (++it > (1 << 18)) break;
          } while ((int)(v - target) < 0 || (int)(z - target) < 0);
          asm volatile("fence.proxy.async.global;" ::: "memory");
          bulk_g2s(sb + 3 * SLOT, &g_kv[hg][0][0], 12288, sb + SM_KVB);
        }
        __syncwarp();
      } else {
        const int w = warp - 9;
        st_rlx4(reinterpret_cast<uint4*>(&g_st[2 * rb + w][hg][0]) + lane, T ^ 1, T ^ 1, T ^ 1, T ^ 1);
        if (lane < 8) st_rlx4(&g_o[2 * rb + w][hg][lane >> 1][3][30 + (lane & 1)], T ^ 1, T ^ 1, T ^ 1, T ^ 1);
        st_rlx4(&g_part[2 * rb3 + w][(jf & 1) * 4 + (lane >> 3)][jf >> 1][(lane >> 1) & 3][3][30 + (lane & 1)], T ^ 1, T ^ 1, T ^ 1, T ^ 1);
        if (lane < 16) st_rlx4(&g_hh[2 * rb3 + w][jf][7 + (lane >> 3) * 3][(lane >> 1) & 3][30 + (lane & 1)], T ^ 1, T ^ 1, T ^ 1, T ^ 1);
        if (w == 0) {
          mbar_wait(sb + SM_FULL + (ST_WQ + 2) * 8);
          unsigned v; int it = 0;
#pragma unroll 1
          do {
            asm volatile("ld.acquire.gpu.global.u32 %0, [%1];" : "=r"(v) : "l"(&g_kvcnt[hg * 32 + 1]) : "memory");
          } while ((int)(v - (epoch + 1) * 128) < 0 && ++it < (1 << 18));
          asm volatile("fence.proxy.async.global;" ::: "memory");
        }
        {
          mbar_wait(sb + SM_EMPTY + (ST_WV + 1) * 8);
          float* cp = reinterpret_cast<float*>(smem + 2 * SLOT) + (w * 32 + lane) * 4 + 3;
#pragma unroll
          for (int i = 0; i < 12; i++) cp[i * 256] = 1.f;
          cp = reinterpret_cast<float*>(smem + 2 * SLOT) + (w * 32 + lane) * 24 + 22;
          cp[0] = 0.f; cp[64 * 24] = 0.f;
          fence_async_smem();
        }
        bar_sync(6, 192);
        if (w == 0 && elect_one()) {
          asm volatile("cp.reduce.async.bulk.global.shared::cta.bulk_group.add.f32 [%0], [%1], 12288;"
                       ::"l"(&g_kv[hg][0][0]), "r"(sb + 2 * SLOT) : "memory");
          asm volatile("cp.async.bulk.commit_group;" ::: "memory");
          asm volatile("cp.async.bulk.wait_group.read 0;" ::: "memory");
          asm volatile("red.relaxed.gpu.global.add.u32 [%0], 8;" ::"l"(&g_kvcnt[hg * 32]) : "memory");
          mbar_arrive(sb + SM_KVB);
        }
        __syncwarp();
        mbar_wait(sb + SM_KVB);
        if (w == 0) { mbar_wait(sb + SM_EMPTY + 11 * 8); mbar_wait(sb + SM_EMPTY + 12 * 8); mbar_wait(sb + SM_EMPTY + 13 * 8); }
#pragma unroll 1
        for (int ph = 0; ph < 2; ph++) {
          const int use = 2 * ph + w, r = ph ? 2 * rb3 + w : 2 * rb + w;
          const uint32_t* pw = ph ? reinterpret_cast<const uint32_t*>(&g_st[r][lane >> 2][(lane & 3) * 16 + 15])
                                  : reinterpret_cast<const uint32_t*>(&g_o[r][lane >> 2][lane & 3][3][31]);
          const char* src = reinterpret_cast<const char*>(ph ? &g_h[r][0][0][0][0] : &g_o[r][0][0][0][0]);
          const uint32_t bf = sb + SM_XF + use * 32, be = sb + SM_XE + (use - 1) * 32;
          bar_sync(10 + w, 160);
          int it = 0;
#pragma unroll 1
          for (bool miss = true; __any_sync(0xffffffffu, miss) && ++it < (1 << 18);) { if (miss) miss = (ld_rlx1(pw) ^ T) & 1; }
          if (elect_one()) {
            if (use > 0) mbar_wait(be);
            if (ph) bulk_g2s(sb + SM_KV32 + w * 4096, &g_st[r][0][0], 4096, bf);
#pragma unroll
            for (int p = 0; p < 4; p++) {
              if (p > 0 && use > 0) mbar_wait(be + p * 8);
              bulk_g2s(sb + 2 * SLOT + p * 16384, src + p * 16384, 16384, bf + p * 8);
            }
          }
          __syncwarp();
        }
        {
          const int m = jf >> 1, oc = (jf & 1) * 4 + m;
          const uint32_t* pw = reinterpret_cast<const uint32_t*>(&g_part[2 * rb3 + w][oc][(m - 1 - (lane >> 2)) & 3][lane & 3][3][31]);
          bar_sync(12, 320);
          bool miss = lane < 12; int it = 0;
#pragma unroll 1
          for (int q = 0; q < 3; q++) {
#pragma unroll 1
            while ((__ballot_sync(0xffffffffu, miss) >> (4 * q) & 15) && ++it < (1 << 18)) { if (miss && (lane >> 2) <= q + 1) miss = (ld_rlx1(pw) ^ T) & 1; }
            if (elect_one()) {
              const uint32_t bar = sb + SM_XF + (w * 4 + q) * 8;
              mbar_expect_tx(bar, 8192);
              bulk_g2s(sb + ((ST_D % NSLOT) + w) * SLOT + q * 8192, &g_part[2 * rb3 + w][oc][(m - 1 - q) & 3][0][0][0], 8192, bar);
            }
            __syncwarp();
          }
        }
      }
    }
    asm volatile("barrier.cluster.arrive.relaxed.aligned;" ::: "memory");
    asm volatile("barrier.cluster.wait.aligned;" ::: "memory");
  }
}

typedef CUresult (*EncodeFn)(CUtensorMap*, CUtensorMapDataType, cuuint32_t, void*, const cuuint64_t*, const cuuint64_t*,
                             const cuuint32_t*, const cuuint32_t*, CUtensorMapInterleave, CUtensorMapSwizzle,
                             CUtensorMapL2promotion, CUtensorMapFloatOOBfill);

void encode(EncodeFn fn, CUtensorMap* m, const void* base, int rank, const cuuint64_t* dims, const cuuint64_t* strides,
            const cuuint32_t* box) {
  cuuint32_t es[3] = {1, 1, 1};
  fn(m, CU_TENSOR_MAP_DATA_TYPE_BFLOAT16, (cuuint32_t)rank, const_cast<void*>(base), dims, strides, box, es,
     CU_TENSOR_MAP_INTERLEAVE_NONE, CU_TENSOR_MAP_SWIZZLE_128B, CU_TENSOR_MAP_L2_PROMOTION_L2_256B,
     CU_TENSOR_MAP_FLOAT_OOB_FILL_NONE);
}

}

extern "C" void kernel_launch(void* const* d_in, const int* in_sizes, int n_in, void* d_out, int out_size) {
  (void)in_sizes; (void)n_in; (void)out_size;
  const __nv_bfloat16* x    = (const __nv_bfloat16*)d_in[0];
  const __nv_bfloat16* wqkv = (const __nv_bfloat16*)d_in[1];
  const __nv_bfloat16* wphi = (const __nv_bfloat16*)d_in[2];
  const __nv_bfloat16* wo   = (const __nv_bfloat16*)d_in[3];
  const __nv_bfloat16* wg   = (const __nv_bfloat16*)d_in[5];
  const __nv_bfloat16* wu   = (const __nv_bfloat16*)d_in[6];
  const __nv_bfloat16* wd   = (const __nv_bfloat16*)d_in[7];

  static EncodeFn fn = nullptr;
  if (!fn) {
    void* p = nullptr;
    cudaDriverEntryPointQueryResult qr;
    cudaGetDriverEntryPoint("cuTensorMapEncodeTiled", &p, cudaEnableDefault, &qr);
    fn = (EncodeFn)p;
    cudaFuncSetAttribute(fused_kernel, cudaFuncAttributeMaxDynamicSharedMemorySize, SM_TOTAL);
  }
  Maps maps;
  {
    cuuint64_t d[3] = {64, 2048, 8}, s[2] = {1024, 128}; cuuint32_t b[3] = {64, 64, 3};
    encode(fn, &maps.x, x, 3, d, s, b);
  }
  {
    cuuint64_t d[2] = {1536, 512}, s[1] = {3072}; cuuint32_t b[2] = {64, 192};
    encode(fn, &maps.w, wqkv, 2, d, s, b);
  }
  {
    cuuint64_t d[2] = {512, 512}, s[1] = {1024}; cuuint32_t b[2] = {64, 192};
    encode(fn, &maps.wo, wo, 2, d, s, b);
  }
  {
    cuuint64_t d[3] = {176, 7, 512}, d7[3] = {144, 1, 512}, s[2] = {352, 2752}; cuuint32_t b[3] = {64, 1, 32};
    encode(fn, &maps.g, wg, 3, d, s, b);
    encode(fn, &maps.u, wu, 3, d, s, b);
    encode(fn, &maps.g7, wg + 1232, 3, d7, s, b);
    encode(fn, &maps.u7, wu + 1232, 3, d7, s, b);
  }
  {
    cuuint64_t d[2] = {512, 1376}, s[1] = {1024}; cuuint32_t b[2] = {64, 176};
    encode(fn, &maps.d, wd, 2, d, s, b);
  }
  fused_kernel<<<NCTA, 384, SM_TOTAL>>>(maps, x, wphi, wo, wg, wu, wd, (__nv_bfloat16*)d_out);
}
```

```cpp
#include <cuda_runtime.h>
#include <cuda_bf16.h>
#include <cuda.h>
#include <stdint.h>

#define SAFE_WAIT 0

namespace {

constexpr int NCTA   = 128;
constexpr int SLOT   = 24576;
constexpr int NSLOT  = 9;
constexpr int NSTAGE = 47;

constexpr int ST_X0   = 0;
constexpr int ST_WK   = 3;
constexpr int ST_X1   = 6;
constexpr int ST_SCR0 = 9;
constexpr int ST_WV   = 10;
constexpr int ST_SCR1 = 13;
constexpr int ST_WQ   = 14;
constexpr int ST_WO   = 17;
constexpr int ST_XC   = 20;
constexpr int ST_GU   = 23;
constexpr int ST_D    = 39;

__host__ __device__ constexpr int st_empty_cnt(int d) {
  return ((d < 3 || (d >= 6 && d < 9) || (d >= ST_XC && d < ST_GU)) ? 4 : (d == ST_SCR0 || d == ST_SCR1) ? 1 : 2) * (d + 9 >= ST_GU ? 2 : 1);
}

constexpr uint32_t SM_BASE = 1024;
constexpr int SM_ONES = NSLOT * SLOT;
constexpr int SM_WPHI = SM_ONES + 2048;
constexpr int SM_KVS  = SM_WPHI + 2048;
constexpr int SM_KV32 = 4 * SLOT + 16384;
constexpr int SM_BAR  = SM_KVS + 6144;
constexpr int SM_FULL  = SM_BAR;
constexpr int SM_EMPTY = SM_BAR + NSTAGE * 8;
constexpr int SM_MISCB = SM_BAR + 2 * NSTAGE * 8;
constexpr int SM_KVB   = SM_MISCB + 8;
constexpr int SM_EPOCH = SM_KVB + 8;
constexpr int SM_XF    = SM_EPOCH + 8;
constexpr int SM_XE    = SM_XF + 16 * 8;
constexpr int SM_TOTAL = SM_BAR + 1024;

static_assert(SM_TOTAL == 232448 && SM_XE + 12 * 8 <= SM_TOTAL, "smem budget");

struct Maps { CUtensorMap x, w, wo, g, u, g7, u7, d; };

__device__ __align__(128) uint4    g_o[32][8][4][4][32];
__device__ __align__(128) uint4    g_h[32][8][4][4][32];
__device__ __align__(128) uint32_t g_hx[32][8][4][32];
__device__ __align__(128) uint2    g_st[32][8][64];
__device__ __align__(128) uint4    g_hh[32][8][11][4][32];
__device__ __align__(128) uint4    g_part[32][8][4][4][4][32];
__device__ __align__(128) float4 g_kv[8][128][6];
__device__ __align__(128) unsigned g_kvcnt[8 * 32];
__device__ unsigned g_start;

__device__ __forceinline__ uint32_t smem_u32(const void* p) { return (uint32_t)__cvta_generic_to_shared(p); }
__device__ __forceinline__ void mbar_init(uint32_t bar, int cnt) {
  asm volatile("mbarrier.init.shared::cta.b64 [%0], %1;" ::"r"(bar), "r"(cnt) : "memory");
}
__device__ __forceinline__ void mbar_expect_tx(uint32_t bar, uint32_t bytes) {
  asm volatile("mbarrier.arrive.expect_tx.shared::cta.b64 _, [%0], %1;" ::"r"(bar), "r"(bytes) : "memory");
}
__device__ __forceinline__ void mbar_arrive(uint32_t bar) {
  asm volatile("mbarrier.arrive.shared::cta.b64 _, [%0];" ::"r"(bar) : "memory");
}
__device__ __forceinline__ void mbar_arrive_cluster(uint32_t bar, uint32_t rank) {
  asm volatile("{\n.reg .b32 ra;\nmapa.shared::cluster.u32 ra, %0, %1;\n"
               "mbarrier.arrive.shared::cluster.b64 _, [ra];\n}" ::"r"(bar), "r"(rank) : "memory");
}
__device__ __forceinline__ void mbar_wait_p(uint32_t bar, uint32_t parity) {
  asm volatile("{\n.reg .pred p;\nW: mbarrier.try_wait.parity.shared::cta.b64 p, [%0], %1;\n@!p bra W;\n}" ::"r"(bar), "r"(parity) : "memory");
}
__device__ __forceinline__ void mbar_wait(uint32_t bar) { mbar_wait_p(bar, 0); }
__device__ __forceinline__ bool elect_one() {
  uint32_t p;
  asm volatile("{\n.reg .pred P;\nelect.sync _|P, 0xffffffff;\nselp.u32 %0, 1, 0, P;\n}" : "=r"(p));
  return p != 0;
}
__device__ __forceinline__ void bar_sync(int id, int n)   { asm volatile("bar.sync %0, %1;" ::"r"(id), "r"(n) : "memory"); }
__device__ __forceinline__ void bar_arrive(int id, int n) { asm volatile("bar.arrive %0, %1;" ::"r"(id), "r"(n) : "memory"); }
__device__ __forceinline__ void fence_async_smem() { asm volatile("fence.proxy.async.shared::cta;" ::: "memory"); }
__device__ __forceinline__ void wg_fence()  { asm volatile("wgmma.fence.sync.aligned;" ::: "memory"); }
__device__ __forceinline__ void wg_commit() { asm volatile("wgmma.commit_group.sync.aligned;" ::: "memory"); }
template <int N> __device__ __forceinline__ void wg_wait() { asm volatile("wgmma.wait_group.sync.aligned %0;" ::"n"(N) : "memory"); }
#define DESC(off) (db + ((uint32_t)(off) >> 4))
__device__ __forceinline__ void tma2d(uint32_t dst, const CUtensorMap* m, int c0, int c1, uint32_t bar) {
  asm volatile("cp.async.bulk.tensor.2d.shared::cluster.global.mbarrier::complete_tx::bytes [%0], [%1, {%3, %4}], [%2];"
               ::"r"(dst), "l"(m), "r"(bar), "r"(c0), "r"(c1) : "memory");
}
__device__ __forceinline__ void tma2d_mc(uint32_t dst, const CUtensorMap* m, int c0, int c1, uint32_t bar) {
  asm volatile("cp.async.bulk.tensor.2d.shared::cluster.global.mbarrier::complete_tx::bytes.multicast::cluster [%0], [%1, {%3, %4}], [%2], %5;"
               ::"r"(dst), "l"(m), "r"(bar), "r"(c0), "r"(c1), "h"((uint16_t)3) : "memory");
}
__device__ __forceinline__ void tma3d(uint32_t dst, const CUtensorMap* m, int c0, int c1, int c2, uint32_t bar) {
  asm volatile("cp.async.bulk.tensor.3d.shared::cluster.global.mbarrier::complete_tx::bytes [%0], [%1, {%3, %4, %5}], [%2];"
               ::"r"(dst), "l"(m), "r"(bar), "r"(c0), "r"(c1), "r"(c2) : "memory");
}
__device__ __forceinline__ void tma3d_mc(uint32_t dst, const CUtensorMap* m, int c0, int c1, int c2, uint32_t bar) {
  asm volatile("cp.async.bulk.tensor.3d.shared::cluster.global.mbarrier::complete_tx::bytes.multicast::cluster [%0], [%1, {%3, %4, %5}], [%2], %6;"
               ::"r"(dst), "l"(m), "r"(bar), "r"(c0), "r"(c1), "r"(c2), "h"((uint16_t)3) : "memory");
}
__device__ __forceinline__ void ldsm4(uint32_t (&r)[4], uint32_t addr) {
  asm volatile("ldmatrix.sync.aligned.m8n8.x4.shared.b16 {%0,%1,%2,%3}, [%4];"
               : "=r"(r[0]), "=r"(r[1]), "=r"(r[2]), "=r"(r[3]) : "r"(addr) : "memory");
}
__device__ __forceinline__ void ldsm4t(uint32_t (&r)[4], uint32_t addr) {
  asm volatile("ldmatrix.sync.aligned.m8n8.x4.trans.shared.b16 {%0,%1,%2,%3}, [%4];"
               : "=r"(r[0]), "=r"(r[1]), "=r"(r[2]), "=r"(r[3]) : "r"(addr) : "memory");
}
__device__ __forceinline__ void stsm4(uint32_t addr, uint32_t r0, uint32_t r1, uint32_t r2, uint32_t r3) {
  asm volatile("stmatrix.sync.aligned.m8n8.x4.shared.b16 [%0], {%1,%2,%3,%4};"
               ::"r"(addr), "r"(r0), "r"(r1), "r"(r2), "r"(r3) : "memory");
}
__device__ __forceinline__ void mma16816(float (&c)[4], const uint32_t (&a)[4], uint32_t b0, uint32_t b1) {
  asm volatile("mma.sync.aligned.m16n8k16.row.col.f32.bf16.bf16.f32 {%0,%1,%2,%3},{%4,%5,%6,%7},{%8,%9},{%0,%1,%2,%3};"
               : "+f"(c[0]), "+f"(c[1]), "+f"(c[2]), "+f"(c[3])
               : "r"(a[0]), "r"(a[1]), "r"(a[2]), "r"(a[3]), "r"(b0), "r"(b1));
}
__device__ __forceinline__ void add_frag(float (&c)[32], const uint32_t (&a)[4][4], uint32_t id) {
#pragma unroll
  for (int i = 0; i < 8; i++)
    asm volatile("mma.sync.aligned.m16n8k8.row.col.f32.bf16.bf16.f32 {%0,%1,%2,%3},{%4,%5},{%6},{%0,%1,%2,%3};"
                 : "+f"(c[4 * i]), "+f"(c[4 * i + 1]), "+f"(c[4 * i + 2]), "+f"(c[4 * i + 3])
                 : "r"(a[i >> 1][(i & 1) * 2]), "r"(a[i >> 1][(i & 1) * 2 + 1]), "r"(id));
}
__device__ __forceinline__ uint32_t pack2(float lo, float hi) {
  uint32_t r; asm("cvt.rn.bf16x2.f32 %0, %1, %2;" : "=r"(r) : "f"(hi), "f"(lo)); return r;
}
__device__ __forceinline__ float blo(uint32_t w) { return __uint_as_float(w << 16); }
__device__ __forceinline__ float bhi(uint32_t w) { return __uint_as_float(w & 0xFFFF0000u); }
__device__ __forceinline__ uint32_t hsub2(uint32_t a, uint32_t b) { uint32_t r; asm("sub.rn.bf16x2 %0, %1, %2;" : "=r"(r) : "r"(a), "r"(b)); return r; }
__device__ __forceinline__ uint32_t hmax2(uint32_t a, uint32_t b) { uint32_t r; asm("max.bf16x2 %0, %1, %2;" : "=r"(r) : "r"(a), "r"(b)); return r; }
__device__ __forceinline__ uint32_t hmin2(uint32_t a, uint32_t b) { uint32_t r; asm("min.bf16x2 %0, %1, %2;" : "=r"(r) : "r"(a), "r"(b)); return r; }
__device__ __forceinline__ float ex2(float x) { float r; asm("ex2.approx.ftz.f32 %0, %1;" : "=f"(r) : "f"(x)); return r; }
__device__ __forceinline__ float rcp(float x) { float r; asm("rcp.approx.ftz.f32 %0, %1;" : "=f"(r) : "f"(x)); return r; }
__device__ __forceinline__ void ld_rlx4(uint32_t (&r)[4], const uint4* p) {
  asm volatile("{\n.reg .b128 v;\nld.relaxed.gpu.global.b128 v, [%4];\nmov.b128 {%0,%1,%2,%3}, v;\n}"
               : "=r"(r[0]), "=r"(r[1]), "=r"(r[2]), "=r"(r[3]) : "l"(p) : "memory");
}
__device__ __forceinline__ void st_rlx4(uint4* p, uint32_t a, uint32_t b, uint32_t c, uint32_t d) {
  asm volatile("st.relaxed.gpu.global.v4.b32 [%0], {%1,%2,%3,%4};" ::"l"(p), "r"(a), "r"(b), "r"(c), "r"(d) : "memory");
}
__device__ __forceinline__ void st_rlx2(uint2* p, uint32_t a, uint32_t b) {
  asm volatile("{\n.reg .b64 v;\nmov.b64 v, {%1,%2};\nst.relaxed.gpu.global.b64 [%0], v;\n}" ::"l"(p), "r"(a), "r"(b) : "memory");
}
__device__ __forceinline__ uint32_t ld_rlx1(const uint32_t* p) {
  uint32_t r; asm volatile("ld.relaxed.gpu.global.b32 %0, [%1];" : "=r"(r) : "l"(p) : "memory"); return r;
}
__device__ __forceinline__ void st_rlx1(uint32_t* p, uint32_t a) {
  asm volatile("st.relaxed.gpu.global.b32 [%0], %1;" ::"l"(p), "r"(a) : "memory");
}
__device__ __forceinline__ void ld_rlx2(uint32_t& a, uint32_t& b, const uint2* p) {
  asm volatile("{\n.reg .b64 v;\nld.relaxed.gpu.b64 v, [%2];\nmov.b64 {%0,%1}, v;\n}" : "=r"(a), "=r"(b) : "l"(p) : "memory");
}
__device__ __forceinline__ void bulk_g2s(uint32_t dst, const void* src, uint32_t bytes, uint32_t bar) {
  asm volatile("cp.async.bulk.shared::cluster.global.mbarrier::complete_tx::bytes [%0], [%1], %2, [%3];"
               ::"r"(dst), "l"(src), "r"(bytes), "r"(bar) : "memory");
}
__device__ __forceinline__ uint32_t tg(uint32_t w, uint32_t T) { return (w & 0xFFFFFFFEu) | T; }
__device__ __forceinline__ uint32_t bad4(uint32_t a, uint32_t b, uint32_t c, uint32_t d, uint32_t T) {
  uint32_t u, v;
  asm("lop3.b32 %0, %1, %2, %3, 0x7E;" : "=r"(u) : "r"(a), "r"(b), "r"(T));
  asm("lop3.b32 %0, %1, %2, %3, 0x7E;" : "=r"(v) : "r"(c), "r"(d), "r"(T));
  asm("lop3.b32 %0, %1, %2, 1, 0xA8;" : "=r"(u) : "r"(u), "r"(v));
  return u;
}

__device__ __forceinline__ void ld_chunk(uint32_t (&a)[4][4], const uint4* p) {
#pragma unroll
  for (int s = 0; s < 4; s++) ld_rlx4(a[s], p + s * 32);
}
__device__ __forceinline__ void get_pair(uint32_t (&a)[4][4], uint32_t (&b)[4][4], const uint4* sp, const uint4* gp, uint32_t T) {
  int it = 0;
#pragma unroll 1
  do {
#pragma unroll
    for (int s = 0; s < 8; s++) {
      uint32_t (&r)[4] = s < 4 ? a[s & 3] : b[s & 3];
      asm volatile("{\n.reg .b128 v;\nld.relaxed.gpu.b128 v, [%4];\nmov.b128 {%0,%1,%2,%3}, v;\n}"
                   : "=r"(r[0]), "=r"(r[1]), "=r"(r[2]), "=r"(r[3]) : "l"(sp + (s >> 2) * 512 + (s & 3) * 32) : "memory");
    }
    sp = gp;
  } while (__any_sync(0xffffffffu, bad4(a[0][0], a[1][0], a[2][0], a[3][0], T) | bad4(b[0][0], b[1][0], b[2][0], b[3][0], T)) && ++it < (1 << 18));
}

__device__ __forceinline__ void wgmma_rs_n48(float (&d)[24], const uint32_t (&a)[4], uint32_t descB, int scaleD) {
  asm volatile("{\n.reg .pred p;\n.reg .b64 db;\nsetp.ne.b32 p, %29, 0;\nmov.b64 db, {%28, 0x40000040};\n"
    "wgmma.mma_async.sync.aligned.m64n48k16.f32.bf16.bf16 {%0,%1,%2,%3,%4,%5,%6,%7,%8,%9,%10,%11,%12,%13,%14,%15,%16,%17,%18,%19,%20,%21,%22,%23}, {%24,%25,%26,%27}, db, p, 1, 1, 1;\n}\n"
    : "+f"(d[0]),"+f"(d[1]),"+f"(d[2]),"+f"(d[3]),"+f"(d[4]),"+f"(d[5]),"+f"(d[6]),"+f"(d[7]),"+f"(d[8]),"+f"(d[9]),"+f"(d[10]),"+f"(d[11]),"+f"(d[12]),"+f"(d[13]),"+f"(d[14]),"+f"(d[15]),"+f"(d[16]),"+f"(d[17]),"+f"(d[18]),"+f"(d[19]),"+f"(d[20]),"+f"(d[21]),"+f"(d[22]),"+f"(d[23])
    : "r"(a[0]), "r"(a[1]), "r"(a[2]), "r"(a[3]), "r"(descB), "r"(scaleD));
}
__device__ __forceinline__ void wgmma_rs_n64(float (&d)[32], const uint32_t (&a)[4], uint32_t descB, int scaleD) {
  asm volatile("{\n.reg .pred p;\n.reg .b64 db;\nsetp.ne.b32 p, %37, 0;\nmov.b64 db, {%36, 0x40000040};\n"
    "wgmma.mma_async.sync.aligned.m64n64k16.f32.bf16.bf16 {%0,%1,%2,%3,%4,%5,%6,%7,%8,%9,%10,%11,%12,%13,%14,%15,%16,%17,%18,%19,%20,%21,%22,%23,%24,%25,%26,%27,%28,%29,%30,%31}, {%32,%33,%34,%35}, db, p, 1, 1, 1;\n}\n"
    : "+f"(d[0]),"+f"(d[1]),"+f"(d[2]),"+f"(d[3]),"+f"(d[4]),"+f"(d[5]),"+f"(d[6]),"+f"(d[7]),"+f"(d[8]),"+f"(d[9]),"+f"(d[10]),"+f"(d[11]),"+f"(d[12]),"+f"(d[13]),"+f"(d[14]),"+f"(d[15]),"+f"(d[16]),"+f"(d[17]),"+f"(d[18]),"+f"(d[19]),"+f"(d[20]),"+f"(d[21]),"+f"(d[22]),"+f"(d[23]),"+f"(d[24]),"+f"(d[25]),"+f"(d[26]),"+f"(d[27]),"+f"(d[28]),"+f"(d[29]),"+f"(d[30]),"+f"(d[31])
    : "r"(a[0]), "r"(a[1]), "r"(a[2]), "r"(a[3]), "r"(descB), "r"(scaleD));
}
__device__ __forceinline__ void wgmma_rs_n128(float (&d)[64], const uint32_t (&a)[4], uint32_t descB, int scaleD) {
  asm volatile("{\n.reg .pred p;\n.reg .b64 db;\nsetp.ne.b32 p, %69, 0;\nmov.b64 db, {%68, 0x40000040};\n"
    "wgmma.mma_async.sync.aligned.m64n128k16.f32.bf16.bf16 {%0,%1,%2,%3,%4,%5,%6,%7,%8,%9,%10,%11,%12,%13,%14,%15,%16,%17,%18,%19,%20,%21,%22,%23,%24,%25,%26,%27,%28,%29,%30,%31,%32,%33,%34,%35,%36,%37,%38,%39,%40,%41,%42,%43,%44,%45,%46,%47,%48,%49,%50,%51,%52,%53,%54,%55,%56,%57,%58,%59,%60,%61,%62,%63}, {%64,%65,%66,%67}, db, p, 1, 1, 1;\n}\n"
    : "+f"(d[0]),"+f"(d[1]),"+f"(d[2]),"+f"(d[3]),"+f"(d[4]),"+f"(d[5]),"+f"(d[6]),"+f"(d[7]),"+f"(d[8]),"+f"(d[9]),"+f"(d[10]),"+f"(d[11]),"+f"(d[12]),"+f"(d[13]),"+f"(d[14]),"+f"(d[15]),"+f"(d[16]),"+f"(d[17]),"+f"(d[18]),"+f"(d[19]),"+f"(d[20]),"+f"(d[21]),"+f"(d[22]),"+f"(d[23]),"+f"(d[24]),"+f"(d[25]),"+f"(d[26]),"+f"(d[27]),"+f"(d[28]),"+f"(d[29]),"+f"(d[30]),"+f"(d[31]),"+f"(d[32]),"+f"(d[33]),"+f"(d[34]),"+f"(d[35]),"+f"(d[36]),"+f"(d[37]),"+f"(d[38]),"+f"(d[39]),"+f"(d[40]),"+f"(d[41]),"+f"(d[42]),"+f"(d[43]),"+f"(d[44]),"+f"(d[45]),"+f"(d[46]),"+f"(d[47]),"+f"(d[48]),"+f"(d[49]),"+f"(d[50]),"+f"(d[51]),"+f"(d[52]),"+f"(d[53]),"+f"(d[54]),"+f"(d[55]),"+f"(d[56]),"+f"(d[57]),"+f"(d[58]),"+f"(d[59]),"+f"(d[60]),"+f"(d[61]),"+f"(d[62]),"+f"(d[63])
    : "r"(a[0]), "r"(a[1]), "r"(a[2]), "r"(a[3]), "r"(descB), "r"(scaleD));
}
__device__ __forceinline__ void wgmma_ss_n72_t11(float (&d)[36], uint32_t descA, uint32_t descB, int scaleD) {
  asm volatile("{\n.reg .pred p;\n.reg .b64 da, db;\nsetp.ne.b32 p, %38, 0;\nmov.b64 da, {%36, 0x40000040};\nmov.b64 db, {%37, 0x40000040};\n"
    "wgmma.mma_async.sync.aligned.m64n72k16.f32.bf16.bf16 {%0,%1,%2,%3,%4,%5,%6,%7,%8,%9,%10,%11,%12,%13,%14,%15,%16,%17,%18,%19,%20,%21,%22,%23,%24,%25,%26,%27,%28,%29,%30,%31,%32,%33,%34,%35}, da, db, p, 1, 1, 1, 1;\n}\n"
    : "+f"(d[0]),"+f"(d[1]),"+f"(d[2]),"+f"(d[3]),"+f"(d[4]),"+f"(d[5]),"+f"(d[6]),"+f"(d[7]),"+f"(d[8]),"+f"(d[9]),"+f"(d[10]),"+f"(d[11]),"+f"(d[12]),"+f"(d[13]),"+f"(d[14]),"+f"(d[15]),"+f"(d[16]),"+f"(d[17]),"+f"(d[18]),"+f"(d[19]),"+f"(d[20]),"+f"(d[21]),"+f"(d[22]),"+f"(d[23]),"+f"(d[24]),"+f"(d[25]),"+f"(d[26]),"+f"(d[27]),"+f"(d[28]),"+f"(d[29]),"+f"(d[30]),"+f"(d[31]),"+f"(d[32]),"+f"(d[33]),"+f"(d[34]),"+f"(d[35])
    : "r"(descA), "r"(descB), "r"(scaleD));
}

constexpr float LOG2E = 1.4426950408889634f;

__device__ __forceinline__ void feat_exp(const uint32_t (&P)[4], float (&e)[16]) {
  uint32_t a = hmax2(P[0], P[2]), b = hmax2(P[1], P[3]);
  uint32_t mx = hmax2(__byte_perm(a, b, 0x5410), __byte_perm(a, b, 0x7632));
  a = hmin2(P[0], P[2]); b = hmin2(P[1], P[3]);
  uint32_t mn = hmin2(__byte_perm(a, b, 0x5410), __byte_perm(a, b, 0x7632));
  mx = hmax2(mx, __shfl_xor_sync(0xffffffffu, mx, 1));
  mn = hmin2(mn, __shfl_xor_sync(0xffffffffu, mn, 1));
  mx = hmax2(mx, __shfl_xor_sync(0xffffffffu, mx, 2));
  mn = hmin2(mn, __shfl_xor_sync(0xffffffffu, mn, 2));
  float mx0 = -blo(mx) * LOG2E, mx1 = -bhi(mx) * LOG2E, mn0 = blo(mn) * LOG2E, mn1 = bhi(mn) * LOG2E;
  float v[8] = {blo(P[0]), bhi(P[0]), blo(P[1]), bhi(P[1]), blo(P[2]), bhi(P[2]), blo(P[3]), bhi(P[3])};
#pragma unroll
  for (int i = 0; i < 8; i++) {
    bool r1 = (i >> 1) & 1;
    e[i]     = ex2(fmaf(v[i],  LOG2E, r1 ? mx1 : mx0));
    e[8 + i] = ex2(fmaf(v[i], -LOG2E, r1 ? mn1 : mn0));
  }
}

__global__ void __cluster_dims__(2, 1, 1) __launch_bounds__(384, 1)
fused_kernel(const __grid_constant__ Maps maps, const __nv_bfloat16* __restrict__ x, const __nv_bfloat16* __restrict__ wphi,
             const __nv_bfloat16* __restrict__ wo, const __nv_bfloat16* __restrict__ wg_, const __nv_bfloat16* __restrict__ wu_,
             const __nv_bfloat16* __restrict__ wd_, __nv_bfloat16* __restrict__ out) {
  extern __shared__ __align__(1024) unsigned char smem[];
  const uint32_t sb = smem_u32(smem);
  const int tid = threadIdx.x, lane = tid & 31;
  const int warp = __shfl_sync(0xffffffffu, tid >> 5, 0);
  const uint32_t rank = blockIdx.x & 1;
  const int cl = blockIdx.x >> 1;
  int quad, qi;
  if (cl < 4) { quad = 15; qi = cl; }
  else if (cl < 36) { quad = (cl - 4) & 7; qi = (cl - 4) >> 3; }
  else { qi = (cl - 36) / 7; quad = 8 + (cl - 36) - 7 * qi; }
  const int rb = quad, hg = 2 * qi + rank;
  const int rb3 = (quad & ~1) + rank, jf = 4 * (quad & 1) + qi;

  if (warp < 8) {
    asm volatile("setmaxnreg.inc.sync.aligned.u32 240;");
    if (elect_one()) {
#pragma unroll 1
      for (int d = warp; d + 9 < NSTAGE; d += 8) {
        mbar_init(sb + SM_EMPTY + d * 8, st_empty_cnt(d));
        mbar_init(sb + SM_FULL + (d + 9) * 8, 1);
        mbar_expect_tx(sb + SM_FULL + (d + 9) * 8, d + 9 >= ST_D ? 22528 : SLOT);
      }
      asm volatile("fence.mbarrier_init.release.cluster;" ::: "memory");
    }
    __syncwarp();
    bar_sync(0, 352);
    asm volatile("barrier.cluster.arrive.relaxed.aligned;" ::: "memory");
    const int wg = warp >> 2, wq = warp & 3, g = lane >> 2, t = lane & 3;
    const bool lead = (tid & 127) == 0;
    constexpr uint32_t db = (SM_BASE >> 4) | (512u << 16);
    auto release = [&](int d) {
      const int s = d + NSLOT;
      mbar_arrive_cluster(sb + SM_EMPTY + d * 8, s >= ST_GU ? (uint32_t)(s & 1) : rank);
    };
    const uint32_t lrow = (uint32_t)(wq * 16 + (lane & 7) + ((lane >> 3) & 1) * 8) * 128;
    const uint32_t lx = lane & 7, lhi = lane >> 4;
    if (wg == 1) bar_arrive(4, 256);

    float r0, r1;
    uint32_t E[4][8];
    uint32_t T = 0;
    {
      uint32_t A[32][4];
      const int sx = wg ? ST_X1 : ST_X0;
      {
        const uint32_t base = sb + sx * SLOT + lrow, baseb = sb + sx * SLOT + (wq * 16 + lx + lhi * 8) * 128;
        float cs[2][4], c0[2][4], c1[2][4];
#pragma unroll
        for (int i = 0; i < 4; i++) { cs[0][i] = cs[1][i] = c0[0][i] = c0[1][i] = c1[0][i] = c1[1][i] = 0.f; }
        uint32_t bt[2][4][4];
        if (wg == 1) bar_sync(13, 256);
#pragma unroll
        for (int c = -1; c < 8; c++) {
          if (c < 7) {
            const int n = c + 1;
            if (n % 3 == 0) mbar_wait(sb + SM_FULL + (sx + n / 3) * 8);
#pragma unroll
            for (int k = 0; k < 4; k++) {
              ldsm4(A[4 * n + k], base + n * 8192 + (((2 * k + lhi) ^ lx) << 4));
              ldsm4(bt[n & 1][k], baseb + n * 8192 + (((2 * k + ((lane >> 3) & 1)) ^ lx) << 4));
            }
          }
          if (c >= 0) {
#pragma unroll
            for (int k = 0; k < 4; k++) {
              const uint32_t (&f)[4] = A[4 * c + k];
              mma16816(cs[k & 1], f, 0x3F803F80u, 0x3F803F80u);
              mma16816(c0[k & 1], f, bt[c & 1][k][0], bt[c & 1][k][1]);
              mma16816(c1[k & 1], f, bt[c & 1][k][2], bt[c & 1][k][3]);
            }
          }
        }
        if (wg == 0) bar_arrive(13, 256);
        const float s0 = (cs[0][0] + cs[1][0]) * (1.f / 512.f), s1 = (cs[0][2] + cs[1][2]) * (1.f / 512.f);
        asm volatile("barrier.cluster.wait.aligned;" ::: "memory");
        if (lane < 3) release(sx + lane);
        const uint32_t m0 = pack2(s0, s0), m1 = pack2(s1, s1);
        float q0 = (g & 1) ? c0[0][1] + c0[1][1] : c0[0][0] + c0[1][0];
        float q1 = (g & 1) ? c1[0][3] + c1[1][3] : c1[0][2] + c1[1][2];
        q0 = __shfl_sync(0xffffffffu, q0, (lane & ~3) | (g >> 1));
        q1 = __shfl_sync(0xffffffffu, q1, (lane & ~3) | (g >> 1));
        r0 = rsqrtf(fmaxf(q0 * (1.f / 512.f) - s0 * s0, 0.f) + 1e-5f);
        r1 = rsqrtf(fmaxf(q1 * (1.f / 512.f) - s1 * s1, 0.f) + 1e-5f);
#pragma unroll
        for (int ks = 0; ks < 32; ks++) {
          A[ks][0] = hsub2(A[ks][0], m0); A[ks][1] = hsub2(A[ks][1], m1);
          A[ks][2] = hsub2(A[ks][2], m0); A[ks][3] = hsub2(A[ks][3], m1);
        }
      }
      const uint32_t wpa = sb + SM_WPHI + ((lane & 7) + ((lane >> 3) & 1) * 8) * 32 + lhi * 16;
      const uint32_t scr = sb + (wg ? (ST_SCR1 % NSLOT) : (ST_SCR0 % NSLOT)) * SLOT;
#pragma unroll 1
      for (int ps = 0; ps < 3; ps++) {
        const int st0 = ps == 0 ? ST_WK : (ps == 1 ? ST_WV : ST_WQ);
        const uint32_t wdesc = DESC((ps == 0 ? ST_WK % NSLOT : (ps == 1 ? ST_WV % NSLOT : ST_WQ % NSLOT)) * SLOT);
        float acc[32];
        bar_sync(4 + wg, 256);
#pragma unroll
        for (int i = 0; i < 3; i++) {
          mbar_wait(sb + SM_FULL + (st0 + i) * 8);
          wg_fence();
#pragma unroll
          for (int kk = 0; kk < (i < 2 ? 12 : 8); kk++)
            wgmma_rs_n64(acc, A[12 * i + kk], wdesc + ((i * SLOT + kk * 2048) >> 4), (i | kk) != 0);
          wg_commit();
          if (i == 1) { wg_wait<1>(); if (lead) release(st0); }
        }
        if (ps == 1 && wg == 0) bar_arrive(5, 256);
        uint32_t a[4][4], b[4][4];
        mbar_wait(sb + SM_MISCB);
        T = (*reinterpret_cast<volatile unsigned*>(smem + SM_EPOCH) & 1) ^ 1;
#pragma unroll
        for (int h = 0; h < 4; h++) ldsm4t(b[h], wpa + h * 512);
        wg_wait<0>();
        if ((tid & 127) < 2) release(st0 + 1 + (tid & 1));
#pragma unroll
        for (int h = 0; h < 4; h++) {
          a[h][0] = pack2(acc[8 * h + 0] * r0, acc[8 * h + 1] * r0); a[h][1] = pack2(acc[8 * h + 2] * r1, acc[8 * h + 3] * r1);
          a[h][2] = pack2(acc[8 * h + 4] * r0, acc[8 * h + 5] * r0); a[h][3] = pack2(acc[8 * h + 6] * r1, acc[8 * h + 7] * r1);
        }
        if (ps != 1) {
          {
            float pp[4][2][4];
#pragma unroll
            for (int h = 0; h < 4; h++) {
#pragma unroll
              for (int i = 0; i < 4; i++) { pp[h][0][i] = 0.f; pp[h][1][i] = 0.f; }
              mma16816(pp[h][0], a[h], b[h][0], b[h][1]);
              mma16816(pp[h][1], a[h], b[h][2], b[h][3]);
            }
#pragma unroll
            for (int h = 0; h < 4; h++) {
              a[h][0] = pack2(pp[h][0][0], pp[h][0][1]); a[h][1] = pack2(pp[h][0][2], pp[h][0][3]);
              a[h][2] = pack2(pp[h][1][0], pp[h][1][1]); a[h][3] = pack2(pp[h][1][2], pp[h][1][3]);
            }
          }
          if (ps == 0 || wg == 0) bar_arrive(4 + (wg ^ 1), 256);
          if (ps == 0) mbar_wait(sb + SM_EMPTY + (wg ? ST_SCR1 - NSLOT : ST_SCR0 - NSLOT) * 8);
#pragma unroll 1
          for (int hp = 0; hp < 2; hp++) {
            float e[2][16];
            feat_exp(a[0], e[0]);
            feat_exp(a[1], e[1]);
            if (ps == 0) {
#pragma unroll
              for (int h = 0; h < 2; h++) {
                const float (&f)[16] = e[h];
                float sp0 = (f[0] + f[1]) + (f[4] + f[5]), sp1 = (f[2] + f[3]) + (f[6] + f[7]);
                float sn0 = (f[8] + f[9]) + (f[12] + f[13]), sn1 = (f[10] + f[11]) + (f[14] + f[15]);
                sp0 += __shfl_xor_sync(0xffffffffu, sp0, 1); sp1 += __shfl_xor_sync(0xffffffffu, sp1, 1);
                sn0 += __shfl_xor_sync(0xffffffffu, sn0, 1); sn1 += __shfl_xor_sync(0xffffffffu, sn1, 1);
                sp0 += __shfl_xor_sync(0xffffffffu, sp0, 2); sp1 += __shfl_xor_sync(0xffffffffu, sp1, 2);
                sn0 += __shfl_xor_sync(0xffffffffu, sn0, 2); sn1 += __shfl_xor_sync(0xffffffffu, sn1, 2);
                sp0 = rcp(sp0); sp1 = rcp(sp1); sn0 = rcp(sn0); sn1 = rcp(sn1);
                const uint32_t dst = scr + hp * 8192 + lrow;
                stsm4(dst + (((h * 4 + lhi) ^ lx) << 4), pack2(f[0] * sp0, f[1] * sp0), pack2(f[2] * sp1, f[3] * sp1),
                      pack2(f[4] * sp0, f[5] * sp0), pack2(f[6] * sp1, f[7] * sp1));
                stsm4(dst + (((h * 4 + 2 + lhi) ^ lx) << 4), pack2(f[8] * sn0, f[9] * sn0), pack2(f[10] * sn1, f[11] * sn1),
                      pack2(f[12] * sn0, f[13] * sn0), pack2(f[14] * sn1, f[15] * sn1));
              }
            } else {
#pragma unroll
              for (int i = 0; i < 16; i++) {
                A[i >> 2][i & 3] = A[4 + (i >> 2)][i & 3];
                A[4 + (i >> 2)][i & 3] = pack2(e[i >> 3][2 * (i & 7)], e[i >> 3][2 * (i & 7) + 1]);
              }
            }
#pragma unroll
            for (int i = 0; i < 4; i++) { a[0][i] = a[2][i]; a[1][i] = a[3][i]; }
          }
        } else {
#pragma unroll
          for (int h = 0; h < 4; h++) stsm4(scr + 16384 + lrow + (((2 * h + lhi) ^ lx) << 4), a[h][0], a[h][1], a[h][2], a[h][3]);
          fence_async_smem();
          if (wg == 0) {
            bar_arrive(3, 256);
          } else {
            bar_sync(3, 256);
            float kv[2][36];
            wg_fence();
#pragma unroll
            for (int ks = 0; ks < 8; ks++) {
              const uint32_t sk = (ks < 4 ? (ST_SCR0 % NSLOT) : (ST_SCR1 % NSLOT)) * SLOT + (ks & 3) * 2048;
              const uint32_t dv = (DESC(sk + 16384) & 0xFFFFu) | (((SM_ONES - sk - 16384) >> 4) << 16);
              wgmma_ss_n72_t11(kv[0], DESC(sk), dv, ks != 0);
              wgmma_ss_n72_t11(kv[1], DESC(sk + 8192), dv, ks != 0);
            }
            wg_commit();
            bar_arrive(4, 256);
            wg_wait<0>();
            if (lead) { mbar_arrive(sb + SM_EMPTY + ST_SCR0 * 8); mbar_arrive(sb + SM_EMPTY + ST_SCR1 * 8); }
            const bool up = wq >= 2;
            float* kvp = reinterpret_cast<float*>(smem + 2 * SLOT) + (wq * 16 + g) * 24;
#pragma unroll
            for (int i = 0; i < 4; i++) {
              const float (&c)[36] = kv[i >> 1];
              const int r = 16 * (i >> 1) + 2 * (i & 1);
              float* p = kvp + ((i >> 1) * 64 + (i & 1) * 8) * 24;
              *reinterpret_cast<float4*>(p + 4 * t) = make_float4(up ? c[r + 8] : c[r], up ? c[r + 9] : c[r + 1], up ? c[r + 12] : c[r + 4], 1.f);
              p[16 + t + (t == 3)] = up ? c[r + 13] : c[r + 5];
            }
            kvp[((t >> 1) * 64 + (t & 1) * 8) * 24 + 21] = (t & 2) ? ((t & 1) ? kv[1][34] : kv[1][32]) : ((t & 1) ? kv[0][34] : kv[0][32]);
            fence_async_smem();
            bar_sync(6, 192);
          }
        }
      }
#pragma unroll
      for (int i = 0; i < 32; i++) E[i >> 3][i & 7] = A[i >> 2][i & 3];
    }
    const int rh = 2 * rb + wg;
#define IDF ((g >> 1) == t ? ((g & 1) ? 0x3F800000u : 0x00003F80u) : 0u)
    const uint4* xb = reinterpret_cast<const uint4*>(smem + 2 * SLOT) + wq * 128 + lane;
    if (wg == 0) {
      mbar_wait(sb + SM_KVB);
      const uint4* sp = reinterpret_cast<const uint4*>(smem + 3 * SLOT) + tid * 6;
      uint32_t v[6][4];
      int it = 0;
#pragma unroll 1
      do {
#pragma unroll
        for (int i = 0; i < 6; i++)
          asm volatile("{\n.reg .b128 v;\nld.relaxed.gpu.b128 v, [%4];\nmov.b128 {%0,%1,%2,%3}, v;\n}"
                       : "=r"(v[i][0]), "=r"(v[i][1]), "=r"(v[i][2]), "=r"(v[i][3]) : "l"(sp + i) : "memory");
        sp = reinterpret_cast<const uint4*>(&g_kv[hg][tid][0]);
      } while (min(min(min(v[0][3], v[1][3]), min(v[2][3], v[3][3])), min(v[4][3], v[5][3])) != 0x41800000u && ++it < (1 << 18));
#define KVF(d) __uint_as_float((d) < 8 ? v[(d) / 2][(d) & 1] : (d) >= 15 ? v[5][((d) - 15) & 1] : ((d) & 1) ? v[4][(((d) - 9) / 2) & 3] : v[(((d) - 8) / 2) & 3][2])
      uint4* dst = reinterpret_cast<uint4*>(smem + SM_KVS + tid * 48);
      const uint32_t zz = pack2(KVF(16), 1.0f);
      dst[0] = make_uint4(pack2(KVF(0), KVF(1)), pack2(KVF(2), KVF(3)), pack2(KVF(4), KVF(5)), pack2(KVF(6), KVF(7)));
      dst[1] = make_uint4(pack2(KVF(8), KVF(9)), pack2(KVF(10), KVF(11)), pack2(KVF(12), KVF(13)), pack2(KVF(14), KVF(15)));
      dst[2] = make_uint4(zz, zz, zz, zz);
      __syncwarp();
      bar_sync(1, 128);
    }
    {
      uint4* op = &g_o[rh][hg][wq][0][lane];
      if (wg == 1) bar_sync(7, 256);
#pragma unroll 1
      for (int hp = 0; hp < 2; hp++) {
#pragma unroll
      for (int h = 0; h < 2; h++) {
        uint32_t b0[4], b1[4], b2[4];
        const uint32_t kb = sb + SM_KVS + ((2 * hp + h) * 32 + lane) * 48;
        ldsm4t(b0, kb); ldsm4t(b1, kb + 16); ldsm4t(b2, kb + 32);
        const uint32_t ep[4] = {E[h][0], E[h][1], E[h][2], E[h][3]}, en[4] = {E[h][4], E[h][5], E[h][6], E[h][7]};
        float np0[4] = {0, 0, 0, 0}, np1[4] = {0, 0, 0, 0}, nn0[4] = {0, 0, 0, 0}, nn1[4] = {0, 0, 0, 0}, dp[4] = {0, 0, 0, 0}, dn[4] = {0, 0, 0, 0};
        mma16816(dp, ep, b2[0], b2[1]);  mma16816(dn, en, b2[2], b2[3]);
        mma16816(np0, ep, b0[0], b0[1]); mma16816(nn0, en, b0[2], b0[3]);
        mma16816(np1, ep, b1[0], b1[1]); mma16816(nn1, en, b1[2], b1[3]);
        const float i0 = rcp(fmaf(dp[0], dn[1], fmaf(dn[0], dp[1], 1e-6f * dp[1] * dn[1])));
        const float i1 = rcp(fmaf(dp[2], dn[3], fmaf(dn[2], dp[3], 1e-6f * dp[3] * dn[3])));
        const float cp0 = dn[1] * i0, cn0 = dp[1] * i0, cp1 = dn[3] * i1, cn1 = dp[3] * i1;
        st_rlx4(op + (2 * hp + h) * 32,
                tg(pack2(fmaf(np0[0], cp0, nn0[0] * cn0), fmaf(np0[1], cp0, nn0[1] * cn0)), T),
                pack2(fmaf(np0[2], cp1, nn0[2] * cn1), fmaf(np0[3], cp1, nn0[3] * cn1)),
                pack2(fmaf(np1[0], cp0, nn1[0] * cn0), fmaf(np1[1], cp0, nn1[1] * cn0)),
                pack2(fmaf(np1[2], cp1, nn1[2] * cn1), fmaf(np1[3], cp1, nn1[3] * cn1)));
      }
#pragma unroll
        for (int i = 0; i < 8; i++) { E[0][i] = E[2][i]; E[1][i] = E[3][i]; }
      }
    }
    if (wg == 0) bar_arrive(7, 256);
    bar_arrive(10 + wg, 160);

    {
      uint32_t xr[4][4];
      {
        const uint32_t* xp = reinterpret_cast<const uint32_t*>(x + (size_t)(rh * 64 + wq * 16 + g) * 512 + hg * 64 + 2 * t);
#pragma unroll
        for (int i = 0; i < 8; i++) { xr[i >> 1][(i & 1) * 2] = __ldg(xp + 4 * i); xr[i >> 1][(i & 1) * 2 + 1] = __ldg(xp + 8 * 256 + 4 * i); }
      }
      uint32_t A[8][4][4];
      const uint4* op = &g_o[rh][0][wq][0][lane];
      float acc[32];
#pragma unroll
      for (int i = 0; i < 32; i++) acc[i] = 0.f;
      add_frag(acc, xr, IDF);
#pragma unroll
      for (int p = -1; p < 4; p++) {
        if (p < 3) {
          mbar_wait(sb + SM_XF + (wg * 4 + p + 1) * 8);
          get_pair(A[2 * p + 2], A[2 * p + 3], xb + (p + 1) * 1024, op + (p + 1) * 1024, T);
          if (lane == 0) mbar_arrive(sb + SM_XE + (wg * 4 + p + 1) * 8);
        }
        if (p == 0 && wg == 1) bar_sync(14, 256);
        if (p >= 0) {
          if (p != 2) mbar_wait(sb + SM_FULL + (ST_WO + (p + 1) / 2) * 8);
          wg_fence();
#pragma unroll
          for (int c = 2 * p; c < 2 * p + 2; c++)
#pragma unroll
            for (int s = 0; s < 4; s++)
              wgmma_rs_n64(acc, A[c][s], DESC(((ST_WO + c / 3) % NSLOT) * SLOT + ((c % 3) * 4 + s) * 2048), 1);
        }
      }
      wg_commit();
      if (wg == 0) bar_arrive(14, 256);
      wg_wait<0>();
      if ((tid & 127) < 3) release(ST_WO + (tid & 127));
      uint4* hp_ = &g_h[rh][hg][wq][0][lane];
      uint32_t hx = T;
#pragma unroll
      for (int s = 0; s < 4; s++) {
        const uint32_t h0 = pack2(acc[8 * s], acc[8 * s + 1]);
        st_rlx4(hp_ + s * 32, tg(h0, T), pack2(acc[8 * s + 2], acc[8 * s + 3]), pack2(acc[8 * s + 4], acc[8 * s + 5]), pack2(acc[8 * s + 6], acc[8 * s + 7]));
        hx |= (h0 & 1u) << (s + 1);
      }
      float s0 = 0.f, s1 = 0.f, q0 = 0.f, q1 = 0.f, q2 = 0.f, q3 = 0.f;
#pragma unroll
      for (int i = 0; i < 8; i++) {
        s0 += acc[4 * i] + acc[4 * i + 1]; s1 += acc[4 * i + 2] + acc[4 * i + 3];
        q0 = fmaf(acc[4 * i], acc[4 * i], q0); q2 = fmaf(acc[4 * i + 1], acc[4 * i + 1], q2);
        q1 = fmaf(acc[4 * i + 2], acc[4 * i + 2], q1); q3 = fmaf(acc[4 * i + 3], acc[4 * i + 3], q3);
      }
      q0 += q2; q1 += q3;
      {
        const bool up = t & 2;
        float s = (up ? s1 : s0) + __shfl_xor_sync(0xffffffffu, up ? s0 : s1, 2);
        float q = (up ? q1 : q0) + __shfl_xor_sync(0xffffffffu, up ? q0 : q1, 2);
        s += __shfl_xor_sync(0xffffffffu, s, 1);
        q += __shfl_xor_sync(0xffffffffu, q, 1);
        if (!(t & 1)) st_rlx2(&g_st[rh][hg][wq * 16 + g + (t >> 1) * 8], tg(__float_as_uint(s), T), __float_as_uint(q));
      }
      st_rlx1(&g_hx[rh][hg][wq][lane], hx);
    }
    bar_arrive(10 + wg, 160);

    const int rh3 = 2 * rb3 + wg;
    uint32_t HH[11][4], PH[11][4];
    const uint4* pp = &g_hh[rh3][jf ^ 1][0][wq][lane];
    {
      uint32_t A[8][4][4];
      const uint4* hp_ = &g_h[rh3][0][wq][0][lane];
      uint4* hhp = &g_hh[rh3][jf][0][wq][lane];
      const uint32_t dg = (db & 0xFFFFu) | (256u << 16);
      uint32_t m0, m1;
      mbar_wait(sb + SM_XF + ((2 + wg) * 4) * 8);
      {
        const uint2* sp = reinterpret_cast<const uint2*>(smem + SM_KV32 + wg * 4096) + 2 * t * 64 + wq * 16 + g;
        uint2 a0, a1, b0, b1;
        int it = 0;
#pragma unroll 1
        do {
          ld_rlx2(a0.x, a0.y, sp); ld_rlx2(a1.x, a1.y, sp + 64); ld_rlx2(b0.x, b0.y, sp + 8); ld_rlx2(b1.x, b1.y, sp + 72);
          sp = &g_st[rh3][2 * t][wq * 16 + g];
        } while (__any_sync(0xffffffffu, bad4(a0.x, a1.x, b0.x, b1.x, T)) && ++it < (1 << 18));
        float s0 = __uint_as_float(a0.x) + __uint_as_float(a1.x), q0 = __uint_as_float(a0.y) + __uint_as_float(a1.y);
        float s1 = __uint_as_float(b0.x) + __uint_as_float(b1.x), q1 = __uint_as_float(b0.y) + __uint_as_float(b1.y);
        s0 += __shfl_xor_sync(0xffffffffu, s0, 1); s1 += __shfl_xor_sync(0xffffffffu, s1, 1);
        q0 += __shfl_xor_sync(0xffffffffu, q0, 1); q1 += __shfl_xor_sync(0xffffffffu, q1, 1);
        s0 += __shfl_xor_sync(0xffffffffu, s0, 2); s1 += __shfl_xor_sync(0xffffffffu, s1, 2);
        q0 += __shfl_xor_sync(0xffffffffu, q0, 2); q1 += __shfl_xor_sync(0xffffffffu, q1, 2);
        s0 *= (1.f / 512.f); s1 *= (1.f / 512.f);
        r0 = rcp(fmaxf(q0 * (1.f / 512.f) - s0 * s0, 0.f) + 1e-5f);
        r1 = rcp(fmaxf(q1 * (1.f / 512.f) - s1 * s1, 0.f) + 1e-5f);
        m0 = pack2(s0, s0); m1 = pack2(s1, s1);
      }
#define UOFF(u) ((((ST_GU + (u) / 3) % NSLOT) * SLOT + ((u) % 3) * 8192) >> 4)
#define UNIT_PRE(u)  do { if ((u) % 3 == 0) mbar_wait(sb + SM_FULL + (ST_GU + (u) / 3) * 8); } while (0)
#define UNIT_POST(u) do { wg_commit(); if ((u) % 3 == 1 && (u) > 3) { wg_wait<2>(); if (lead) release(ST_GU + (u) / 3 - 1); } } while (0)
      float acc[64];
      const int rz = blockIdx.y;
#pragma unroll
      for (int ps = 0; ps < 2; ps++) {
        wg_fence();
#pragma unroll
        for (int k = 0; k < 16; k++) {
          const int u = 16 * ps + k, c = k >> 1;
          if (ps == 0 && (k == 0 || k == 4 || k == 8)) {
#pragma unroll
            for (int p = (k == 0 ? 0 : (k == 4 ? 1 : 3)); p < (k == 0 ? 1 : (k == 4 ? 3 : 4)); p++) {
              if (p > 0) mbar_wait(sb + SM_XF + ((2 + wg) * 4 + p) * 8);
              get_pair(A[2 * p], A[2 * p + 1], xb + p * 1024, hp_ + p * 1024, T);
              if (lane == 0) {
                if (wg == 0) mbar_arrive(sb + SM_XE + (8 + p) * 8);
                else if (p > 0) release(ST_XC + p - 1);
              }
            }
          }
          if (ps == 0 && (k & 1) == 0) {
#pragma unroll
            for (int s = 0; s < 4; s++) {
              A[c][s][0] = hsub2(A[c][s][0], m0); A[c][s][1] = hsub2(A[c][s][1], m1);
              A[c][s][2] = hsub2(A[c][s][2], m0); A[c][s][3] = hsub2(A[c][s][3], m1);
            }
            wg_fence();
          }
          UNIT_PRE(u);
          wgmma_rs_n128(acc, A[c][(k & 1) * 2], dg + UOFF(u), k != 0 ? 1 : (ps ? rz : 0));
          wgmma_rs_n128(acc, A[c][(k & 1) * 2 + 1], dg + UOFF(u) + 128, 1);
          UNIT_POST(u);
        }
        wg_wait<0>();
#pragma unroll
        for (int s = 0; s < 4; s++) {
          uint32_t (&hh)[4] = HH[4 + s];
          hh[0] = tg(pack2(acc[8 * s + 0] * acc[32 + 8 * s + 0], acc[8 * s + 1] * acc[32 + 8 * s + 1]), T);
          hh[1] = pack2(acc[8 * s + 2] * acc[32 + 8 * s + 2], acc[8 * s + 3] * acc[32 + 8 * s + 3]);
          hh[2] = pack2(acc[8 * s + 4] * acc[32 + 8 * s + 4], acc[8 * s + 5] * acc[32 + 8 * s + 5]);
          hh[3] = pack2(acc[8 * s + 6] * acc[32 + 8 * s + 6], acc[8 * s + 7] * acc[32 + 8 * s + 7]);
          st_rlx4(hhp + (4 * ps + s) * 128, hh[0], hh[1], hh[2], hh[3]);
        }
      }
      {
        float ag[24], au[24];
        const uint32_t* ph7 = reinterpret_cast<const uint32_t*>(&g_hh[rh3][jf ^ 1][7][wq][31]);
        uint32_t hv = 0;
        bar_sync(1 + wg, 128);
        wg_fence();
#pragma unroll
        for (int k = 0; k < 16; k++) {
          const int u = 32 + k, c = k >> 1;
          if (k == 6) {
#pragma unroll
            for (int s = 0; s < 4; s++) ld_rlx4(HH[s], hhp + s * 128);
          }
          if (k == 9) hv = ld_rlx1(ph7);
          if (k == 12) {
            int it = 0;
#pragma unroll 1
            while (((hv ^ T) & 1) && ++it < (1 << 18)) hv = ld_rlx1(ph7);
#pragma unroll
            for (int s = 0; s < 8; s++) ld_rlx4(PH[s], pp + s * 128);
          }
          UNIT_PRE(u);
          wgmma_rs_n48(ag, A[c][(k & 1) * 2], dg + UOFF(u), k != 0);
          wgmma_rs_n48(au, A[c][(k & 1) * 2], dg + UOFF(u) + 256, k != 0);
          wgmma_rs_n48(ag, A[c][(k & 1) * 2 + 1], dg + UOFF(u) + 128, 1);
          wgmma_rs_n48(au, A[c][(k & 1) * 2 + 1], dg + UOFF(u) + 256 + 128, 1);
          UNIT_POST(u);
        }
        wg_wait<0>();
#pragma unroll
        for (int s = 0; s < 3; s++) {
          uint32_t (&hh)[4] = HH[8 + s];
          hh[0] = tg(pack2(ag[8 * s + 0] * au[8 * s + 0], ag[8 * s + 1] * au[8 * s + 1]), T);
          hh[1] = pack2(ag[8 * s + 2] * au[8 * s + 2], ag[8 * s + 3] * au[8 * s + 3]);
          hh[2] = pack2(ag[8 * s + 4] * au[8 * s + 4], ag[8 * s + 5] * au[8 * s + 5]);
          hh[3] = pack2(ag[8 * s + 6] * au[8 * s + 6], ag[8 * s + 7] * au[8 * s + 7]);
          st_rlx4(hhp + (8 + s) * 128, hh[0], hh[1], hh[2], hh[3]);
        }
      }
    }

    {
      float ac[3][32], acc[32];
      uint32_t hr[4][4];
      const int m = jf >> 1, oc = (jf & 1) * 4 + m;
      const uint32_t* ph10 = reinterpret_cast<const uint32_t*>(&g_hh[rh3][jf ^ 1][10][wq][31]);
      uint32_t hv = 0;
      bar_arrive(8 + wg, 256);
      wg_fence();
#pragma unroll
      for (int k = 0; k < 3; k++) {
        mbar_wait(sb + SM_FULL + (ST_D + k) * 8);
        if (k == 1) hv = ld_rlx1(ph10);
#pragma unroll
        for (int s = 0; s < 11; s++) {
          if (k == 2 && s == 4) {
            int it = 0;
#pragma unroll 1
            while (((hv ^ T) & 1) && ++it < (1 << 18)) hv = ld_rlx1(ph10);
#pragma unroll
            for (int i = 8; i < 11; i++) ld_rlx4(PH[i], pp + i * 128);
          }
          wgmma_rs_n64(ac[k], HH[s], DESC(((ST_D + k) % NSLOT) * SLOT + s * 2048), s != 0);
        }
      }
      wg_commit();
      {
        int it = 0;
#pragma unroll 1
        while (__any_sync(0xffffffffu, bad4(PH[0][0], PH[1][0], PH[2][0], PH[3][0], T) | bad4(PH[4][0], PH[5][0], PH[6][0], PH[7][0], T) |
                                       bad4(PH[8][0], PH[9][0], PH[10][0], T, T))) {
#pragma unroll
          for (int s = 0; s < 11; s++) ld_rlx4(PH[s], pp + s * 128);
          if (++it > (1 << 18)) break;
        }
      }
      uint4* outb = &g_part[rh3][(jf & 1) * 4][m][wq][0][lane];
#pragma unroll
      for (int k = 0; k < 4; k++) {
        mbar_wait(sb + SM_FULL + (ST_D + 3 + k) * 8);
        wg_fence();
#pragma unroll
        for (int s = 0; s < 11; s++) {
          if (k < 3) wgmma_rs_n64(ac[k], PH[s], DESC(((ST_D + 3 + k) % NSLOT) * SLOT + s * 2048), 1);
          else wgmma_rs_n64(acc, HH[s], DESC(((ST_D + 6) % NSLOT) * SLOT + s * 2048), s != 0);
          if (s == 6 && k > 0) {
            wg_commit();
            wg_wait<1>();
            if (k == 1) bar_arrive(12, 320);
            const float (&a)[32] = ac[k - 1];
            uint4* p = outb + ((m + k) & 3) * 2048;
#pragma unroll
            for (int i = 0; i < 4; i++)
              st_rlx4(p + i * 32, tg(pack2(a[8 * i + 0], a[8 * i + 1]), T), pack2(a[8 * i + 2], a[8 * i + 3]),
                      pack2(a[8 * i + 4], a[8 * i + 5]), pack2(a[8 * i + 6], a[8 * i + 7]));
          }
        }
        wg_commit();
      }
      ld_chunk(hr, &g_h[rh3][oc][wq][0][lane]);
      uint32_t hx = ld_rlx1(&g_hx[rh3][oc][wq][lane]);
      mbar_wait(sb + SM_FULL + (ST_D + 7) * 8);
      wg_fence();
#pragma unroll
      for (int s = 0; s < 11; s++) wgmma_rs_n64(acc, PH[s], DESC(((ST_D + 7) % NSLOT) * SLOT + s * 2048), 1);
      wg_commit();
      wg_wait<0>();
#pragma unroll 1
      for (int q = 0; q < 3; q++) {
        uint32_t in[4][4];
        const uint4* sp = reinterpret_cast<const uint4*>(smem + ((ST_D % NSLOT) + wg) * SLOT) + q * 512 + wq * 128 + lane;
        mbar_wait_p(sb + SM_XF + (wg * 4 + q) * 8, 1);
        int it = 0;
#pragma unroll 1
        do {
#pragma unroll
          for (int s = 0; s < 4; s++)
            asm volatile("{\n.reg .b128 v;\nld.relaxed.gpu.b128 v, [%4];\nmov.b128 {%0,%1,%2,%3}, v;\n}"
                         : "=r"(in[s][0]), "=r"(in[s][1]), "=r"(in[s][2]), "=r"(in[s][3]) : "l"(sp + s * 32) : "memory");
          sp = &g_part[rh3][oc][(m - 1 - q) & 3][wq][0][lane];
        } while (__any_sync(0xffffffffu, bad4(in[0][0], in[1][0], in[2][0], in[3][0], T)) && ++it < (1 << 18));
        add_frag(acc, in, IDF);
      }
      {
        int it = 0;
#pragma unroll 1
        while (__any_sync(0xffffffffu, (hx ^ T) & 1) && ++it < (1 << 18)) hx = ld_rlx1(&g_hx[rh3][oc][wq][lane]);
      }
#pragma unroll
      for (int s = 0; s < 4; s++) hr[s][0] = (hr[s][0] & 0xFFFFFFFEu) | ((hx >> (s + 1)) & 1u);
#pragma unroll
      for (int i = 0; i < 32; i++) acc[i] *= (i & 2) ? r1 : r0;
      add_frag(acc, hr, IDF);
      bar_sync(9 - wg, 256);
      const uint32_t ob = sb + ((ST_D - 1) % NSLOT) * SLOT + wg * 8192;
#pragma unroll
      for (int s = 0; s < 4; s++)
        stsm4(ob + lrow + (((2 * s + lhi) ^ lx) << 4), pack2(acc[8 * s + 0], acc[8 * s + 1]), pack2(acc[8 * s + 2], acc[8 * s + 3]),
              pack2(acc[8 * s + 4], acc[8 * s + 5]), pack2(acc[8 * s + 6], acc[8 * s + 7]));
      __syncwarp();
      {
        const int row = wq * 16 + (lane >> 3);
        __nv_bfloat16* op = out + (size_t)(rh3 * 64 + row) * 512 + oc * 64 + lx * 8;
#pragma unroll
        for (int i = 0; i < 4; i++) {
          uint4 v;
          asm volatile("ld.shared.v4.b32 {%0,%1,%2,%3}, [%4];" : "=r"(v.x), "=r"(v.y), "=r"(v.z), "=r"(v.w)
                       : "r"(ob + (row + i * 4) * 128 + ((lx ^ (((lane >> 3) + i * 4) & 7)) << 4)) : "memory");
          asm volatile("st.global.v4.b32 [%0], {%1,%2,%3,%4};" ::"l"(op + i * 2048), "r"(v.x), "r"(v.y), "r"(v.z), "r"(v.w) : "memory");
        }
      }
    }
    asm volatile("barrier.cluster.arrive.relaxed.aligned;" ::: "memory");
    asm volatile("barrier.cluster.wait.aligned;" ::: "memory");
  } else {
    asm volatile("setmaxnreg.dec.sync.aligned.u32 24;");
    if (elect_one()) {
      if (warp == 8) {
#pragma unroll
        for (int k = 0; k < 9; k++) {
          const int s = k < 3 ? k : (k < 6 ? k + 3 : k - 3);
          const uint32_t bar = sb + SM_FULL + s * 8;
          mbar_init(bar, 1);
          mbar_expect_tx(bar, SLOT);
          if (s >= 3 && s < 6) tma2d(sb + s * SLOT, &maps.w, 512 + hg * 64, (s - 3) * 192, bar);
          else tma3d(sb + s * SLOT, &maps.x, 0, rb * 128 + (s >= 6 ? 64 : 0), 3 * (s % 3), bar);
        }
      } else if (warp == 9) {
        mbar_init(sb + SM_MISCB, 2);
        mbar_init(sb + SM_KVB, 2);
        mbar_expect_tx(sb + SM_KVB, 12288);
        mbar_expect_tx(sb + SM_MISCB, 2048);
        bulk_g2s(sb + SM_WPHI, wphi + hg * 1024, 2048, sb + SM_MISCB);
      } else if (warp == 10) {
        if ((sb & 0x3FFFF) != SM_BASE) __trap();
#pragma unroll 1
        for (int i = 0; i < 16; i++) {
          mbar_init(sb + SM_XF + i * 8, 1);
          mbar_expect_tx(sb + SM_XF + i * 8, (i == 8 || i == 12) ? 20480 : 16384);
          if (i < 12) mbar_init(sb + SM_XE + i * 8, 4);
        }
      } else {
        *reinterpret_cast<volatile unsigned*>(smem + SM_EPOCH) = atomicAdd(&g_start, 1u) / NCTA;
      }
      asm volatile("fence.mbarrier_init.release.cluster;" ::: "memory");
    }
    __syncwarp();
    if (warp != 11) bar_sync(0, 352);
    asm volatile("barrier.cluster.arrive.relaxed.aligned;" ::: "memory");
    if (warp == 8) {
      asm volatile("barrier.cluster.wait.aligned;" ::: "memory");
      if (elect_one()) {
        const CUtensorMap* mg = jf == 7 ? &maps.g7 : &maps.g;
        const CUtensorMap* mu = jf == 7 ? &maps.u7 : &maps.u;
        asm volatile("prefetch.tensormap [%0];" ::"l"(&maps.wo) : "memory");
        asm volatile("prefetch.tensormap [%0];" ::"l"(mg) : "memory");
        asm volatile("prefetch.tensormap [%0];" ::"l"(mu) : "memory");
        asm volatile("prefetch.tensormap [%0];" ::"l"(&maps.d) : "memory");
#pragma unroll 1
        for (int s = ST_WV; s < ST_XC; s++) {
          if (s == ST_SCR1) continue;
          mbar_wait(sb + SM_EMPTY + (s - 9) * 8);
          const uint32_t dst = sb + (s >= 18 ? s - 18 : s - 9) * SLOT, bar = sb + SM_FULL + s * 8;
          if (s < ST_WO) tma2d(dst, &maps.w, (s < ST_WQ ? 1024 : 0) + hg * 64, (s < ST_WQ ? s - ST_WV : s - ST_WQ) * 192, bar);
          else { mbar_wait(bar - 8); tma2d(dst, &maps.wo, hg * 64, (s - ST_WO) * 192, bar); }
        }
        const int jc = jf == 7 ? 0 : jf;
        int slot = (ST_GU + 1 - rank) % NSLOT;
#pragma unroll 1
        for (int s = ST_GU + 1 - rank; s < NSTAGE; s += 2) {
          mbar_wait(sb + SM_EMPTY + (s - 9) * 8);
          if (s > ST_GU && s < ST_GU + 6) mbar_wait(sb + SM_FULL + (s - 1) * 8);
          const uint32_t dst = sb + slot * SLOT, bar = sb + SM_FULL + s * 8;
          if (s < ST_D) {
#pragma unroll 1
            for (int i = 0; i < 3; i++) {
              const int u = (s - ST_GU) * 3 + i;
              tma3d_mc(dst + i * 8192, mg, (u >> 4) * 64, jc, (u & 15) * 32, bar);
              tma3d_mc(dst + i * 8192 + 4096, mu, (u >> 4) * 64, jc, (u & 15) * 32, bar);
            }
          } else {
            const int i = s - ST_D, k = i < 3 ? i : (i < 6 ? i - 3 : 3), pt = (i >= 3 && i != 6) ? 1 : 0;
            tma2d_mc(dst, &maps.d, ((jf & 1) * 4 + (((jf >> 1) + 1 + k) & 3)) * 64, (jf ^ pt) * 176, bar);
          }
          slot += 2; if (slot >= NSLOT) slot -= NSLOT;
        }
      }
      __syncwarp();
    } else {
      asm volatile("barrier.cluster.wait.aligned;" ::: "memory");
      if (warp == 11) {
#pragma unroll
        for (int i = 0; i < 4; i++)
          reinterpret_cast<uint4*>(smem + SM_ONES)[lane + 32 * i] = make_uint4(0x3F803F80u, 0x3F803F80u, 0x3F803F80u, 0x3F803F80u);
        fence_async_smem();
        __syncwarp();
        if (lane == 0) mbar_arrive(sb + SM_MISCB);
      }
      mbar_wait(sb + SM_MISCB);
      const unsigned epoch = *reinterpret_cast<volatile unsigned*>(smem + SM_EPOCH);
      const uint32_t T = (epoch & 1) ^ 1;
      if (warp == 11) {
        (&g_kv[hg][rb * 8][0])[lane] = make_float4(0.f, 0.f, 0.f, 0.f);
        if (lane < 16) (&g_kv[hg][rb * 8][0])[32 + lane] = make_float4(0.f, 0.f, 0.f, 0.f);
        __syncwarp();
        if (elect_one()) asm volatile("red.release.gpu.global.add.u32 [%0], 8;" ::"l"(&g_kvcnt[hg * 32 + 1]) : "memory");
        mbar_wait(sb + SM_FULL + (ST_WK + 2) * 8);
        if (elect_one()) {
          asm volatile("cp.async.bulk.prefetch.L2.global [%0], 4096;" ::"l"((const char*)wo + blockIdx.x * 4096) : "memory");
          asm volatile("cp.async.bulk.prefetch.L2.global [%0], 11008;" ::"l"((const char*)wg_ + blockIdx.x * 11008) : "memory");
          asm volatile("cp.async.bulk.prefetch.L2.global [%0], 11008;" ::"l"((const char*)wu_ + blockIdx.x * 11008) : "memory");
          asm volatile("cp.async.bulk.prefetch.L2.global [%0], 11008;" ::"l"((const char*)wd_ + blockIdx.x * 11008) : "memory");
          mbar_wait(sb + SM_EMPTY + ST_SCR0 * 8);
          const unsigned target = (epoch + 1) * 128;
          unsigned v, z; int it = 0;
#pragma unroll 1
          do {
            asm volatile("{\n.reg .b64 q;\nld.acquire.gpu.global.b64 q, [%2];\nmov.b64 {%0, %1}, q;\n}" : "=r"(v), "=r"(z) : "l"(&g_kvcnt[hg * 32]) : "memory");
            if (++it > (1 << 18)) break;
          } while ((int)(v - target) < 0 || (int)(z - target) < 0);
          asm volatile("fence.proxy.async.global;" ::: "memory");
          bulk_g2s(sb + 3 * SLOT, &g_kv[hg][0][0], 12288, sb + SM_KVB);
        }
        __syncwarp();
      } else {
        const int w = warp - 9;
        st_rlx4(reinterpret_cast<uint4*>(&g_st[2 * rb + w][hg][0]) + lane, T ^ 1, T ^ 1, T ^ 1, T ^ 1);
        if (lane < 8) st_rlx4(&g_o[2 * rb + w][hg][lane >> 1][3][30 + (lane & 1)], T ^ 1, T ^ 1, T ^ 1, T ^ 1);
        st_rlx4(&g_part[2 * rb3 + w][(jf & 1) * 4 + (lane >> 3)][jf >> 1][(lane >> 1) & 3][3][30 + (lane & 1)], T ^ 1, T ^ 1, T ^ 1, T ^ 1);
        if (lane < 16) st_rlx4(&g_hh[2 * rb3 + w][jf][7 + (lane >> 3) * 3][(lane >> 1) & 3][30 + (lane & 1)], T ^ 1, T ^ 1, T ^ 1, T ^ 1);
        if (w == 0) {
          mbar_wait(sb + SM_FULL + (ST_WQ + 2) * 8);
          unsigned v; int it = 0;
#pragma unroll 1
          do {
            asm volatile("ld.acquire.gpu.global.u32 %0, [%1];" : "=r"(v) : "l"(&g_kvcnt[hg * 32 + 1]) : "memory");
          } while ((int)(v - (epoch + 1) * 128) < 0 && ++it < (1 << 18));
          asm volatile("fence.proxy.async.global;" ::: "memory");
        }
        {
          mbar_wait(sb + SM_EMPTY + (ST_WV + 1) * 8);
          float* cp = reinterpret_cast<float*>(smem + 2 * SLOT) + (w * 32 + lane) * 24;
          cp[19] = 1.f; cp[64 * 24 + 19] = 1.f;
          *reinterpret_cast<float2*>(cp + 22) = make_float2(0.f, 1.f); *reinterpret_cast<float2*>(cp + 64 * 24 + 22) = make_float2(0.f, 1.f);
          fence_async_smem();
        }
        bar_sync(6, 192);
        if (w == 0 && elect_one()) {
          asm volatile("cp.reduce.async.bulk.global.shared::cta.bulk_group.add.f32 [%0], [%1], 12288;"
                       ::"l"(&g_kv[hg][0][0]), "r"(sb + 2 * SLOT) : "memory");
          asm volatile("cp.async.bulk.commit_group;" ::: "memory");
          asm volatile("cp.async.bulk.wait_group.read 0;" ::: "memory");
          asm volatile("red.relaxed.gpu.global.add.u32 [%0], 8;" ::"l"(&g_kvcnt[hg * 32]) : "memory");
          mbar_arrive(sb + SM_KVB);
        }
        __syncwarp();
        mbar_wait(sb + SM_KVB);
        if (w == 0) { mbar_wait(sb + SM_EMPTY + 11 * 8); mbar_wait(sb + SM_EMPTY + 12 * 8); mbar_wait(sb + SM_EMPTY + 13 * 8); }
#pragma unroll 1
        for (int ph = 0; ph < 2; ph++) {
          const int use = 2 * ph + w, r = ph ? 2 * rb3 + w : 2 * rb + w;
          const uint32_t* pw = ph ? reinterpret_cast<const uint32_t*>(&g_st[r][lane >> 2][(lane & 3) * 16 + 15])
                                  : reinterpret_cast<const uint32_t*>(&g_o[r][lane >> 2][lane & 3][3][31]);
          const char* src = reinterpret_cast<const char*>(ph ? &g_h[r][0][0][0][0] : &g_o[r][0][0][0][0]);
          const uint32_t bf = sb + SM_XF + use * 32, be = sb + SM_XE + (use - 1) * 32;
          bar_sync(10 + w, 160);
          int it = 0;
#pragma unroll 1
          for (bool miss = true; __any_sync(0xffffffffu, miss) && ++it < (1 << 18);) { if (miss) miss = (ld_rlx1(pw) ^ T) & 1; }
          if (elect_one()) {
            if (use > 0) mbar_wait(be);
            if (ph) bulk_g2s(sb + SM_KV32 + w * 4096, &g_st[r][0][0], 4096, bf);
#pragma unroll
            for (int p = 0; p < 4; p++) {
              if (p > 0 && use > 0) mbar_wait(be + p * 8);
              bulk_g2s(sb + 2 * SLOT + p * 16384, src + p * 16384, 16384, bf + p * 8);
            }
          }
          __syncwarp();
        }
        {
          const int m = jf >> 1, oc = (jf & 1) * 4 + m;
          const uint32_t* pw = reinterpret_cast<const uint32_t*>(&g_part[2 * rb3 + w][oc][(m - 1 - (lane >> 2)) & 3][lane & 3][3][31]);
          bar_sync(12, 320);
          bool miss = lane < 12; int it = 0;
#pragma unroll 1
          for (int q = 0; q < 3; q++) {
#pragma unroll 1
            while ((__ballot_sync(0xffffffffu, miss) >> (4 * q) & 15) && ++it < (1 << 18)) { if (miss && (lane >> 2) <= q + 1) miss = (ld_rlx1(pw) ^ T) & 1; }
            if (elect_one()) {
              const uint32_t bar = sb + SM_XF + (w * 4 + q) * 8;
              mbar_expect_tx(bar, 8192);
              bulk_g2s(sb + ((ST_D % NSLOT) + w) * SLOT + q * 8192, &g_part[2 * rb3 + w][oc][(m - 1 - q) & 3][0][0][0], 8192, bar);
            }
            __syncwarp();
          }
        }
      }
    }
    asm volatile("barrier.cluster.arrive.relaxed.aligned;" ::: "memory");
    asm volatile("barrier.cluster.wait.aligned;" ::: "memory");
  }
}

typedef CUresult (*EncodeFn)(CUtensorMap*, CUtensorMapDataType, cuuint32_t, void*, const cuuint64_t*, const cuuint64_t*,
                             const cuuint32_t*, const cuuint32_t*, CUtensorMapInterleave, CUtensorMapSwizzle,
                             CUtensorMapL2promotion, CUtensorMapFloatOOBfill);

void encode(EncodeFn fn, CUtensorMap* m, const void* base, int rank, const cuuint64_t* dims, const cuuint64_t* strides,
            const cuuint32_t* box) {
  cuuint32_t es[3] = {1, 1, 1};
  fn(m, CU_TENSOR_MAP_DATA_TYPE_BFLOAT16, (cuuint32_t)rank, const_cast<void*>(base), dims, strides, box, es,
     CU_TENSOR_MAP_INTERLEAVE_NONE, CU_TENSOR_MAP_SWIZZLE_128B, CU_TENSOR_MAP_L2_PROMOTION_L2_256B,
     CU_TENSOR_MAP_FLOAT_OOB_FILL_NONE);
}

}

extern "C" void kernel_launch(void* const* d_in, const int* in_sizes, int n_in, void* d_out, int out_size) {
  (void)in_sizes; (void)n_in; (void)out_size;
  const __nv_bfloat16* x    = (const __nv_bfloat16*)d_in[0];
  const __nv_bfloat16* wqkv = (const __nv_bfloat16*)d_in[1];
  const __nv_bfloat16* wphi = (const __nv_bfloat16*)d_in[2];
  const __nv_bfloat16* wo   = (const __nv_bfloat16*)d_in[3];
  const __nv_bfloat16* wg   = (const __nv_bfloat16*)d_in[5];
  const __nv_bfloat16* wu   = (const __nv_bfloat16*)d_in[6];
  const __nv_bfloat16* wd   = (const __nv_bfloat16*)d_in[7];

  static EncodeFn fn = nullptr;
  if (!fn) {
    void* p = nullptr;
    cudaDriverEntryPointQueryResult qr;
    cudaGetDriverEntryPoint("cuTensorMapEncodeTiled", &p, cudaEnableDefault, &qr);
    fn = (EncodeFn)p;
    cudaFuncSetAttribute(fused_kernel, cudaFuncAttributeMaxDynamicSharedMemorySize, SM_TOTAL);
  }
  Maps maps;
  {
    cuuint64_t d[3] = {64, 2048, 8}, s[2] = {1024, 128}; cuuint32_t b[3] = {64, 64, 3};
    encode(fn, &maps.x, x, 3, d, s, b);
  }
  {
    cuuint64_t d[2] = {1536, 512}, s[1] = {3072}; cuuint32_t b[2] = {64, 192};
    encode(fn, &maps.w, wqkv, 2, d, s, b);
  }
  {
    cuuint64_t d[2] = {512, 512}, s[1] = {1024}; cuuint32_t b[2] = {64, 192};
    encode(fn, &maps.wo, wo, 2, d, s, b);
  }
  {
    cuuint64_t d[3] = {176, 7, 512}, d7[3] = {144, 1, 512}, s[2] = {352, 2752}; cuuint32_t b[3] = {64, 1, 32};
    encode(fn, &maps.g, wg, 3, d, s, b);
    encode(fn, &maps.u, wu, 3, d, s, b);
    encode(fn, &maps.g7, wg + 1232, 3, d7, s, b);
    encode(fn, &maps.u7, wu + 1232, 3, d7, s, b);
  }
  {
    cuuint64_t d[2] = {512, 1376}, s[1] = {1024}; cuuint32_t b[2] = {64, 176};
    encode(fn, &maps.d, wd, 2, d, s, b);
  }
  fused_kernel<<<NCTA, 384, SM_TOTAL>>>(maps, x, wphi, wo, wg, wu, wd, (__nv_bfloat16*)d_out);
}
```

```cpp
#include <cuda_runtime.h>
#include <cuda_bf16.h>
#include <cuda.h>
#include <stdint.h>

#define SAFE_WAIT 0

namespace {

constexpr int NCTA   = 128;
constexpr int SLOT   = 24576;
constexpr int NSLOT  = 9;
constexpr int NSTAGE = 47;

constexpr int ST_X0   = 0;
constexpr int ST_WK   = 3;
constexpr int ST_X1   = 6;
constexpr int ST_SCR0 = 9;
constexpr int ST_WV   = 10;
constexpr int ST_SCR1 = 13;
constexpr int ST_WQ   = 14;
constexpr int ST_WO   = 17;
constexpr int ST_XC   = 20;
constexpr int ST_GU   = 23;
constexpr int ST_D    = 39;

__host__ __device__ constexpr int st_empty_cnt(int d) {
  return ((d < 3 || (d >= 6 && d < 9) || (d >= ST_XC && d < ST_GU)) ? 4 : (d == ST_SCR0 || d == ST_SCR1) ? 1 : 2) * (d + 9 >= ST_GU ? 2 : 1);
}

constexpr uint32_t SM_BASE = 1024;
constexpr int SM_ONES = NSLOT * SLOT;
constexpr int SM_WPHI = SM_ONES + 2048;
constexpr int SM_KVS  = SM_WPHI + 2048;
constexpr int SM_KV32 = 4 * SLOT + 16384;
constexpr int SM_BAR  = SM_KVS + 6144;
constexpr int SM_FULL  = SM_BAR;
constexpr int SM_EMPTY = SM_BAR + NSTAGE * 8;
constexpr int SM_MISCB = SM_BAR + 2 * NSTAGE * 8;
constexpr int SM_KVB   = SM_MISCB + 8;
constexpr int SM_EPOCH = SM_KVB + 8;
constexpr int SM_XF    = SM_EPOCH + 8;
constexpr int SM_XE    = SM_XF + 16 * 8;
constexpr int SM_TOTAL = SM_BAR + 1024;

static_assert(SM_TOTAL == 232448 && SM_XE + 12 * 8 <= SM_TOTAL, "smem budget");

struct Maps { CUtensorMap x, w, wo, g, u, g7, u7, d; };

__device__ __align__(128) uint4    g_o[32][8][4][4][32];
__device__ __align__(128) uint4    g_h[32][8][4][4][32];
__device__ __align__(128) uint32_t g_hx[32][8][4][32];
__device__ __align__(128) uint2    g_st[32][8][64];
__device__ __align__(128) uint4    g_hh[32][8][11][4][32];
__device__ __align__(128) uint4    g_part[32][8][4][4][4][32];
__device__ __align__(128) float4 g_kv[8][128][6];
__device__ __align__(128) unsigned g_kvcnt[8 * 32];
__device__ unsigned g_start;

__device__ __forceinline__ uint32_t smem_u32(const void* p) { return (uint32_t)__cvta_generic_to_shared(p); }
__device__ __forceinline__ void mbar_init(uint32_t bar, int cnt) {
  asm volatile("mbarrier.init.shared::cta.b64 [%0], %1;" ::"r"(bar), "r"(cnt) : "memory");
}
__device__ __forceinline__ void mbar_expect_tx(uint32_t bar, uint32_t bytes) {
  asm volatile("mbarrier.arrive.expect_tx.shared::cta.b64 _, [%0], %1;" ::"r"(bar), "r"(bytes) : "memory");
}
__device__ __forceinline__ void mbar_arrive(uint32_t bar) {
  asm volatile("mbarrier.arrive.shared::cta.b64 _, [%0];" ::"r"(bar) : "memory");
}
__device__ __forceinline__ void mbar_arrive_cluster(uint32_t bar, uint32_t rank) {
  asm volatile("{\n.reg .b32 ra;\nmapa.shared::cluster.u32 ra, %0, %1;\n"
               "mbarrier.arrive.shared::cluster.b64 _, [ra];\n}" ::"r"(bar), "r"(rank) : "memory");
}
__device__ __forceinline__ void mbar_wait_p(uint32_t bar, uint32_t parity) {
  asm volatile("{\n.reg .pred p;\nW: mbarrier.try_wait.parity.shared::cta.b64 p, [%0], %1;\n@!p bra W;\n}" ::"r"(bar), "r"(parity) : "memory");
}
__device__ __forceinline__ void mbar_wait(uint32_t bar) { mbar_wait_p(bar, 0); }
__device__ __forceinline__ bool elect_one() {
  uint32_t p;
  asm volatile("{\n.reg .pred P;\nelect.sync _|P, 0xffffffff;\nselp.u32 %0, 1, 0, P;\n}" : "=r"(p));
  return p != 0;
}
__device__ __forceinline__ void bar_sync(int id, int n)   { asm volatile("bar.sync %0, %1;" ::"r"(id), "r"(n) : "memory"); }
__device__ __forceinline__ void bar_arrive(int id, int n) { asm volatile("bar.arrive %0, %1;" ::"r"(id), "r"(n) : "memory"); }
__device__ __forceinline__ void fence_async_smem() { asm volatile("fence.proxy.async.shared::cta;" ::: "memory"); }
__device__ __forceinline__ void wg_fence()  { asm volatile("wgmma.fence.sync.aligned;" ::: "memory"); }
__device__ __forceinline__ void wg_commit() { asm volatile("wgmma.commit_group.sync.aligned;" ::: "memory"); }
template <int N> __device__ __forceinline__ void wg_wait() { asm volatile("wgmma.wait_group.sync.aligned %0;" ::"n"(N) : "memory"); }
#define DESC(off) (db + ((uint32_t)(off) >> 4))
__device__ __forceinline__ void tma2d(uint32_t dst, const CUtensorMap* m, int c0, int c1, uint32_t bar) {
  asm volatile("cp.async.bulk.tensor.2d.shared::cluster.global.mbarrier::complete_tx::bytes [%0], [%1, {%3, %4}], [%2];"
               ::"r"(dst), "l"(m), "r"(bar), "r"(c0), "r"(c1) : "memory");
}
__device__ __forceinline__ void tma2d_mc(uint32_t dst, const CUtensorMap* m, int c0, int c1, uint32_t bar) {
  asm volatile("cp.async.bulk.tensor.2d.shared::cluster.global.mbarrier::complete_tx::bytes.multicast::cluster [%0], [%1, {%3, %4}], [%2], %5;"
               ::"r"(dst), "l"(m), "r"(bar), "r"(c0), "r"(c1), "h"((uint16_t)3) : "memory");
}
__device__ __forceinline__ void tma3d(uint32_t dst, const CUtensorMap* m, int c0, int c1, int c2, uint32_t bar) {
  asm volatile("cp.async.bulk.tensor.3d.shared::cluster.global.mbarrier::complete_tx::bytes [%0], [%1, {%3, %4, %5}], [%2];"
               ::"r"(dst), "l"(m), "r"(bar), "r"(c0), "r"(c1), "r"(c2) : "memory");
}
__device__ __forceinline__ void tma3d_mc(uint32_t dst, const CUtensorMap* m, int c0, int c1, int c2, uint32_t bar) {
  asm volatile("cp.async.bulk.tensor.3d.shared::cluster.global.mbarrier::complete_tx::bytes.multicast::cluster [%0], [%1, {%3, %4, %5}], [%2], %6;"
               ::"r"(dst), "l"(m), "r"(bar), "r"(c0), "r"(c1), "r"(c2), "h"((uint16_t)3) : "memory");
}
__device__ __forceinline__ void ldsm4(uint32_t (&r)[4], uint32_t addr) {
  asm volatile("ldmatrix.sync.aligned.m8n8.x4.shared.b16 {%0,%1,%2,%3}, [%4];"
               : "=r"(r[0]), "=r"(r[1]), "=r"(r[2]), "=r"(r[3]) : "r"(addr) : "memory");
}
__device__ __forceinline__ void ldsm4t(uint32_t (&r)[4], uint32_t addr) {
  asm volatile("ldmatrix.sync.aligned.m8n8.x4.trans.shared.b16 {%0,%1,%2,%3}, [%4];"
               : "=r"(r[0]), "=r"(r[1]), "=r"(r[2]), "=r"(r[3]) : "r"(addr) : "memory");
}
__device__ __forceinline__ void stsm4(uint32_t addr, uint32_t r0, uint32_t r1, uint32_t r2, uint32_t r3) {
  asm volatile("stmatrix.sync.aligned.m8n8.x4.shared.b16 [%0], {%1,%2,%3,%4};"
               ::"r"(addr), "r"(r0), "r"(r1), "r"(r2), "r"(r3) : "memory");
}
__device__ __forceinline__ void mma16816(float (&c)[4], const uint32_t (&a)[4], uint32_t b0, uint32_t b1) {
  asm volatile("mma.sync.aligned.m16n8k16.row.col.f32.bf16.bf16.f32 {%0,%1,%2,%3},{%4,%5,%6,%7},{%8,%9},{%0,%1,%2,%3};"
               : "+f"(c[0]), "+f"(c[1]), "+f"(c[2]), "+f"(c[3])
               : "r"(a[0]), "r"(a[1]), "r"(a[2]), "r"(a[3]), "r"(b0), "r"(b1));
}
__device__ __forceinline__ void add_frag(float (&c)[32], const uint32_t (&a)[4][4], uint32_t id) {
#pragma unroll
  for (int i = 0; i < 8; i++)
    asm volatile("mma.sync.aligned.m16n8k8.row.col.f32.bf16.bf16.f32 {%0,%1,%2,%3},{%4,%5},{%6},{%0,%1,%2,%3};"
                 : "+f"(c[4 * i]), "+f"(c[4 * i + 1]), "+f"(c[4 * i + 2]), "+f"(c[4 * i + 3])
                 : "r"(a[i >> 1][(i & 1) * 2]), "r"(a[i >> 1][(i & 1) * 2 + 1]), "r"(id));
}
__device__ __forceinline__ uint32_t pack2(float lo, float hi) {
  uint32_t r; asm("cvt.rn.bf16x2.f32 %0, %1, %2;" : "=r"(r) : "f"(hi), "f"(lo)); return r;
}
__device__ __forceinline__ float blo(uint32_t w) { return __uint_as_float(w << 16); }
__device__ __forceinline__ float bhi(uint32_t w) { return __uint_as_float(w & 0xFFFF0000u); }
__device__ __forceinline__ uint32_t hsub2(uint32_t a, uint32_t b) { uint32_t r; asm("sub.rn.bf16x2 %0, %1, %2;" : "=r"(r) : "r"(a), "r"(b)); return r; }
__device__ __forceinline__ uint32_t hmax2(uint32_t a, uint32_t b) { uint32_t r; asm("max.bf16x2 %0, %1, %2;" : "=r"(r) : "r"(a), "r"(b)); return r; }
__device__ __forceinline__ uint32_t hmin2(uint32_t a, uint32_t b) { uint32_t r; asm("min.bf16x2 %0, %1, %2;" : "=r"(r) : "r"(a), "r"(b)); return r; }
__device__ __forceinline__ float ex2(float x) { float r; asm("ex2.approx.ftz.f32 %0, %1;" : "=f"(r) : "f"(x)); return r; }
__device__ __forceinline__ float rcp(float x) { float r; asm("rcp.approx.ftz.f32 %0, %1;" : "=f"(r) : "f"(x)); return r; }
__device__ __forceinline__ void ld_rlx4(uint32_t (&r)[4], const uint4* p) {
  asm volatile("{\n.reg .b128 v;\nld.relaxed.gpu.global.b128 v, [%4];\nmov.b128 {%0,%1,%2,%3}, v;\n}"
               : "=r"(r[0]), "=r"(r[1]), "=r"(r[2]), "=r"(r[3]) : "l"(p) : "memory");
}
__device__ __forceinline__ void st_rlx4(uint4* p, uint32_t a, uint32_t b, uint32_t c, uint32_t d) {
  asm volatile("st.relaxed.gpu.global.v4.b32 [%0], {%1,%2,%3,%4};" ::"l"(p), "r"(a), "r"(b), "r"(c), "r"(d) : "memory");
}
__device__ __forceinline__ void st_rlx2(uint2* p, uint32_t a, uint32_t b) {
  asm volatile("{\n.reg .b64 v;\nmov.b64 v, {%1,%2};\nst.relaxed.gpu.global.b64 [%0], v;\n}" ::"l"(p), "r"(a), "r"(b) : "memory");
}
__device__ __forceinline__ uint32_t ld_rlx1(const uint32_t* p) {
  uint32_t r; asm volatile("ld.relaxed.gpu.global.b32 %0, [%1];" : "=r"(r) : "l"(p) : "memory"); return r;
}
__device__ __forceinline__ void st_rlx1(uint32_t* p, uint32_t a) {
  asm volatile("st.relaxed.gpu.global.b32 [%0], %1;" ::"l"(p), "r"(a) : "memory");
}
__device__ __forceinline__ void ld_rlx2(uint32_t& a, uint32_t& b, const uint2* p) {
  asm volatile("{\n.reg .b64 v;\nld.relaxed.gpu.b64 v, [%2];\nmov.b64 {%0,%1}, v;\n}" : "=r"(a), "=r"(b) : "l"(p) : "memory");
}
__device__ __forceinline__ void bulk_g2s(uint32_t dst, const void* src, uint32_t bytes, uint32_t bar) {
  asm volatile("cp.async.bulk.shared::cluster.global.mbarrier::complete_tx::bytes [%0], [%1], %2, [%3];"
               ::"r"(dst), "l"(src), "r"(bytes), "r"(bar) : "memory");
}
__device__ __forceinline__ uint32_t tg(uint32_t w, uint32_t T) { return (w & 0xFFFFFFFEu) | T; }
__device__ __forceinline__ uint32_t bad4(uint32_t a, uint32_t b, uint32_t c, uint32_t d, uint32_t T) {
  uint32_t u, v;
  asm("lop3.b32 %0, %1, %2, %3, 0x7E;" : "=r"(u) : "r"(a), "r"(b), "r"(T));
  asm("lop3.b32 %0, %1, %2, %3, 0x7E;" : "=r"(v) : "r"(c), "r"(d), "r"(T));
  asm("lop3.b32 %0, %1, %2, 1, 0xA8;" : "=r"(u) : "r"(u), "r"(v));
  return u;
}

__device__ __forceinline__ void ld_chunk(uint32_t (&a)[4][4], const uint4* p) {
#pragma unroll
  for (int s = 0; s < 4; s++) ld_rlx4(a[s], p + s * 32);
}
__device__ __forceinline__ void get_pair(uint32_t (&a)[4][4], uint32_t (&b)[4][4], const uint4* sp, const uint4* gp, uint32_t T) {
  int it = 0;
#pragma unroll 1
  do {
#pragma unroll
    for (int s = 0; s < 8; s++) {
      uint32_t (&r)[4] = s < 4 ? a[s & 3] : b[s & 3];
      asm volatile("{\n.reg .b128 v;\nld.relaxed.gpu.b128 v, [%4];\nmov.b128 {%0,%1,%2,%3}, v;\n}"
                   : "=r"(r[0]), "=r"(r[1]), "=r"(r[2]), "=r"(r[3]) : "l"(sp + (s >> 2) * 512 + (s & 3) * 32) : "memory");
    }
    sp = gp;
  } while (__any_sync(0xffffffffu, bad4(a[0][0], a[1][0], a[2][0], a[3][0], T) | bad4(b[0][0], b[1][0], b[2][0], b[3][0], T)) && ++it < (1 << 18));
}

__device__ __forceinline__ void wgmma_rs_n48(float (&d)[24], const uint32_t (&a)[4], uint32_t descB, int scaleD) {
  asm volatile("{\n.reg .pred p;\n.reg .b64 db;\nsetp.ne.b32 p, %29, 0;\nmov.b64 db, {%28, 0x40000040};\n"
    "wgmma.mma_async.sync.aligned.m64n48k16.f32.bf16.bf16 {%0,%1,%2,%3,%4,%5,%6,%7,%8,%9,%10,%11,%12,%13,%14,%15,%16,%17,%18,%19,%20,%21,%22,%23}, {%24,%25,%26,%27}, db, p, 1, 1, 1;\n}\n"
    : "+f"(d[0]),"+f"(d[1]),"+f"(d[2]),"+f"(d[3]),"+f"(d[4]),"+f"(d[5]),"+f"(d[6]),"+f"(d[7]),"+f"(d[8]),"+f"(d[9]),"+f"(d[10]),"+f"(d[11]),"+f"(d[12]),"+f"(d[13]),"+f"(d[14]),"+f"(d[15]),"+f"(d[16]),"+f"(d[17]),"+f"(d[18]),"+f"(d[19]),"+f"(d[20]),"+f"(d[21]),"+f"(d[22]),"+f"(d[23])
    : "r"(a[0]), "r"(a[1]), "r"(a[2]), "r"(a[3]), "r"(descB), "r"(scaleD));
}
__device__ __forceinline__ void wgmma_rs_n64(float (&d)[32], const uint32_t (&a)[4], uint32_t descB, int scaleD) {
  asm volatile("{\n.reg .pred p;\n.reg .b64 db;\nsetp.ne.b32 p, %37, 0;\nmov.b64 db, {%36, 0x40000040};\n"
    "wgmma.mma_async.sync.aligned.m64n64k16.f32.bf16.bf16 {%0,%1,%2,%3,%4,%5,%6,%7,%8,%9,%10,%11,%12,%13,%14,%15,%16,%17,%18,%19,%20,%21,%22,%23,%24,%25,%26,%27,%28,%29,%30,%31}, {%32,%33,%34,%35}, db, p, 1, 1, 1;\n}\n"
    : "+f"(d[0]),"+f"(d[1]),"+f"(d[2]),"+f"(d[3]),"+f"(d[4]),"+f"(d[5]),"+f"(d[6]),"+f"(d[7]),"+f"(d[8]),"+f"(d[9]),"+f"(d[10]),"+f"(d[11]),"+f"(d[12]),"+f"(d[13]),"+f"(d[14]),"+f"(d[15]),"+f"(d[16]),"+f"(d[17]),"+f"(d[18]),"+f"(d[19]),"+f"(d[20]),"+f"(d[21]),"+f"(d[22]),"+f"(d[23]),"+f"(d[24]),"+f"(d[25]),"+f"(d[26]),"+f"(d[27]),"+f"(d[28]),"+f"(d[29]),"+f"(d[30]),"+f"(d[31])
    : "r"(a[0]), "r"(a[1]), "r"(a[2]), "r"(a[3]), "r"(descB), "r"(scaleD));
}
__device__ __forceinline__ void wgmma_rs_n128(float (&d)[64], const uint32_t (&a)[4], uint32_t descB, int scaleD) {
  asm volatile("{\n.reg .pred p;\n.reg .b64 db;\nsetp.ne.b32 p, %69, 0;\nmov.b64 db, {%68, 0x40000040};\n"
    "wgmma.mma_async.sync.aligned.m64n128k16.f32.bf16.bf16 {%0,%1,%2,%3,%4,%5,%6,%7,%8,%9,%10,%11,%12,%13,%14,%15,%16,%17,%18,%19,%20,%21,%22,%23,%24,%25,%26,%27,%28,%29,%30,%31,%32,%33,%34,%35,%36,%37,%38,%39,%40,%41,%42,%43,%44,%45,%46,%47,%48,%49,%50,%51,%52,%53,%54,%55,%56,%57,%58,%59,%60,%61,%62,%63}, {%64,%65,%66,%67}, db, p, 1, 1, 1;\n}\n"
    : "+f"(d[0]),"+f"(d[1]),"+f"(d[2]),"+f"(d[3]),"+f"(d[4]),"+f"(d[5]),"+f"(d[6]),"+f"(d[7]),"+f"(d[8]),"+f"(d[9]),"+f"(d[10]),"+f"(d[11]),"+f"(d[12]),"+f"(d[13]),"+f"(d[14]),"+f"(d[15]),"+f"(d[16]),"+f"(d[17]),"+f"(d[18]),"+f"(d[19]),"+f"(d[20]),"+f"(d[21]),"+f"(d[22]),"+f"(d[23]),"+f"(d[24]),"+f"(d[25]),"+f"(d[26]),"+f"(d[27]),"+f"(d[28]),"+f"(d[29]),"+f"(d[30]),"+f"(d[31]),"+f"(d[32]),"+f"(d[33]),"+f"(d[34]),"+f"(d[35]),"+f"(d[36]),"+f"(d[37]),"+f"(d[38]),"+f"(d[39]),"+f"(d[40]),"+f"(d[41]),"+f"(d[42]),"+f"(d[43]),"+f"(d[44]),"+f"(d[45]),"+f"(d[46]),"+f"(d[47]),"+f"(d[48]),"+f"(d[49]),"+f"(d[50]),"+f"(d[51]),"+f"(d[52]),"+f"(d[53]),"+f"(d[54]),"+f"(d[55]),"+f"(d[56]),"+f"(d[57]),"+f"(d[58]),"+f"(d[59]),"+f"(d[60]),"+f"(d[61]),"+f"(d[62]),"+f"(d[63])
    : "r"(a[0]), "r"(a[1]), "r"(a[2]), "r"(a[3]), "r"(descB), "r"(scaleD));
}
__device__ __forceinline__ void wgmma_ss_n72_t11(float (&d)[36], uint32_t descA, uint32_t descB, int scaleD) {
  asm volatile("{\n.reg .pred p;\n.reg .b64 da, db;\nsetp.ne.b32 p, %38, 0;\nmov.b64 da, {%36, 0x40000040};\nmov.b64 db, {%37, 0x40000040};\n"
    "wgmma.mma_async.sync.aligned.m64n72k16.f32.bf16.bf16 {%0,%1,%2,%3,%4,%5,%6,%7,%8,%9,%10,%11,%12,%13,%14,%15,%16,%17,%18,%19,%20,%21,%22,%23,%24,%25,%26,%27,%28,%29,%30,%31,%32,%33,%34,%35}, da, db, p, 1, 1, 1, 1;\n}\n"
    : "+f"(d[0]),"+f"(d[1]),"+f"(d[2]),"+f"(d[3]),"+f"(d[4]),"+f"(d[5]),"+f"(d[6]),"+f"(d[7]),"+f"(d[8]),"+f"(d[9]),"+f"(d[10]),"+f"(d[11]),"+f"(d[12]),"+f"(d[13]),"+f"(d[14]),"+f"(d[15]),"+f"(d[16]),"+f"(d[17]),"+f"(d[18]),"+f"(d[19]),"+f"(d[20]),"+f"(d[21]),"+f"(d[22]),"+f"(d[23]),"+f"(d[24]),"+f"(d[25]),"+f"(d[26]),"+f"(d[27]),"+f"(d[28]),"+f"(d[29]),"+f"(d[30]),"+f"(d[31]),"+f"(d[32]),"+f"(d[33]),"+f"(d[34]),"+f"(d[35])
    : "r"(descA), "r"(descB), "r"(scaleD));
}

constexpr float LOG2E = 1.4426950408889634f;

__device__ __forceinline__ void feat_exp(const uint32_t (&P)[4], float (&e)[16]) {
  uint32_t a = hmax2(P[0], P[2]), b = hmax2(P[1], P[3]);
  uint32_t mx = hmax2(__byte_perm(a, b, 0x5410), __byte_perm(a, b, 0x7632));
  a = hmin2(P[0], P[2]); b = hmin2(P[1], P[3]);
  uint32_t mn = hmin2(__byte_perm(a, b, 0x5410), __byte_perm(a, b, 0x7632));
  mx = hmax2(mx, __shfl_xor_sync(0xffffffffu, mx, 1));
  mn = hmin2(mn, __shfl_xor_sync(0xffffffffu, mn, 1));
  mx = hmax2(mx, __shfl_xor_sync(0xffffffffu, mx, 2));
  mn = hmin2(mn, __shfl_xor_sync(0xffffffffu, mn, 2));
  float mx0 = -blo(mx) * LOG2E, mx1 = -bhi(mx) * LOG2E, mn0 = blo(mn) * LOG2E, mn1 = bhi(mn) * LOG2E;
  float v[8] = {blo(P[0]), bhi(P[0]), blo(P[1]), bhi(P[1]), blo(P[2]), bhi(P[2]), blo(P[3]), bhi(P[3])};
#pragma unroll
  for (int i = 0; i < 8; i++) {
    bool r1 = (i >> 1) & 1;
    e[i]     = ex2(fmaf(v[i],  LOG2E, r1 ? mx1 : mx0));
    e[8 + i] = ex2(fmaf(v[i], -LOG2E, r1 ? mn1 : mn0));
  }
}

__global__ void __cluster_dims__(2, 1, 1) __launch_bounds__(384, 1)
fused_kernel(const __grid_constant__ Maps maps, const __nv_bfloat16* __restrict__ x, const __nv_bfloat16* __restrict__ wphi,
             const __nv_bfloat16* __restrict__ wo, const __nv_bfloat16* __restrict__ wg_, const __nv_bfloat16* __restrict__ wu_,
             const __nv_bfloat16* __restrict__ wd_, __nv_bfloat16* __restrict__ out) {
  extern __shared__ __align__(1024) unsigned char smem[];
  const uint32_t sb = smem_u32(smem);
  const int tid = threadIdx.x, lane = tid & 31;
  const int warp = __shfl_sync(0xffffffffu, tid >> 5, 0);
  const uint32_t rank = blockIdx.x & 1;
  const int cl = blockIdx.x >> 1;
  int quad, qi;
  if (cl < 4) { quad = 15; qi = cl; }
  else if (cl < 36) { quad = (cl - 4) & 7; qi = (cl - 4) >> 3; }
  else { qi = (cl - 36) / 7; quad = 8 + (cl - 36) - 7 * qi; }
  const int rb = quad, hg = 2 * qi + rank;
  const int rb3 = (quad & ~1) + rank, jf = 4 * (quad & 1) + qi;

  if (warp < 8) {
    asm volatile("setmaxnreg.inc.sync.aligned.u32 240;");
    if (elect_one()) {
#pragma unroll 1
      for (int d = warp; d + 9 < NSTAGE; d += 8) {
        mbar_init(sb + SM_EMPTY + d * 8, st_empty_cnt(d));
        mbar_init(sb + SM_FULL + (d + 9) * 8, 1);
        mbar_expect_tx(sb + SM_FULL + (d + 9) * 8, d + 9 >= ST_D ? 22528 : SLOT);
      }
      asm volatile("fence.mbarrier_init.release.cluster;" ::: "memory");
    }
    __syncwarp();
    bar_sync(0, 352);
    asm volatile("barrier.cluster.arrive.relaxed.aligned;" ::: "memory");
    const int wg = warp >> 2, wq = warp & 3, g = lane >> 2, t = lane & 3;
    const bool lead = (tid & 127) == 0;
    constexpr uint32_t db = (SM_BASE >> 4) | (512u << 16);
    auto release = [&](int d) {
      const int s = d + NSLOT;
      mbar_arrive_cluster(sb + SM_EMPTY + d * 8, s >= ST_GU ? (uint32_t)(s & 1) : rank);
    };
    const uint32_t lrow = (uint32_t)(wq * 16 + (lane & 7) + ((lane >> 3) & 1) * 8) * 128;
    const uint32_t lx = lane & 7, lhi = lane >> 4;
    if (wg == 1) bar_arrive(4, 256);

    float r0, r1;
    uint32_t E[4][8];
    uint32_t T = 0;
    {
      uint32_t A[32][4];
      const int sx = wg ? ST_X1 : ST_X0;
      {
        const uint32_t base = sb + sx * SLOT + lrow, baseb = sb + sx * SLOT + (wq * 16 + lx + lhi * 8) * 128;
        float cs[2][4], c0[2][4], c1[2][4];
#pragma unroll
        for (int i = 0; i < 4; i++) { cs[0][i] = cs[1][i] = c0[0][i] = c0[1][i] = c1[0][i] = c1[1][i] = 0.f; }
        uint32_t bt[2][4][4];
        if (wg == 1) bar_sync(13, 256);
#pragma unroll
        for (int c = -1; c < 8; c++) {
          if (c < 7) {
            const int n = c + 1;
            if (n % 3 == 0) mbar_wait(sb + SM_FULL + (sx + n / 3) * 8);
#pragma unroll
            for (int k = 0; k < 4; k++) {
              ldsm4(A[4 * n + k], base + n * 8192 + (((2 * k + lhi) ^ lx) << 4));
              ldsm4(bt[n & 1][k], baseb + n * 8192 + (((2 * k + ((lane >> 3) & 1)) ^ lx) << 4));
            }
          }
          if (c >= 0) {
#pragma unroll
            for (int k = 0; k < 4; k++) {
              const uint32_t (&f)[4] = A[4 * c + k];
              mma16816(cs[k & 1], f, 0x3F803F80u, 0x3F803F80u);
              mma16816(c0[k & 1], f, bt[c & 1][k][0], bt[c & 1][k][1]);
              mma16816(c1[k & 1], f, bt[c & 1][k][2], bt[c & 1][k][3]);
            }
          }
        }
        if (wg == 0) bar_arrive(13, 256);
        const float s0 = (cs[0][0] + cs[1][0]) * (1.f / 512.f), s1 = (cs[0][2] + cs[1][2]) * (1.f / 512.f);
        asm volatile("barrier.cluster.wait.aligned;" ::: "memory");
        if (lane < 3) release(sx + lane);
        const uint32_t m0 = pack2(s0, s0), m1 = pack2(s1, s1);
        float q0 = (g & 1) ? c0[0][1] + c0[1][1] : c0[0][0] + c0[1][0];
        float q1 = (g & 1) ? c1[0][3] + c1[1][3] : c1[0][2] + c1[1][2];
        q0 = __shfl_sync(0xffffffffu, q0, (lane & ~3) | (g >> 1));
        q1 = __shfl_sync(0xffffffffu, q1, (lane & ~3) | (g >> 1));
        r0 = rsqrtf(fmaxf(q0 * (1.f / 512.f) - s0 * s0, 0.f) + 1e-5f);
        r1 = rsqrtf(fmaxf(q1 * (1.f / 512.f) - s1 * s1, 0.f) + 1e-5f);
#pragma unroll
        for (int ks = 0; ks < 32; ks++) {
          A[ks][0] = hsub2(A[ks][0], m0); A[ks][1] = hsub2(A[ks][1], m1);
          A[ks][2] = hsub2(A[ks][2], m0); A[ks][3] = hsub2(A[ks][3], m1);
        }
      }
      const uint32_t wpa = sb + SM_WPHI + ((lane & 7) + ((lane >> 3) & 1) * 8) * 32 + lhi * 16;
      const uint32_t scr = sb + (wg ? (ST_SCR1 % NSLOT) : (ST_SCR0 % NSLOT)) * SLOT;
#pragma unroll 1
      for (int ps = 0; ps < 3; ps++) {
        const int st0 = ps == 0 ? ST_WK : (ps == 1 ? ST_WV : ST_WQ);
        const uint32_t wdesc = DESC((ps == 0 ? ST_WK % NSLOT : (ps == 1 ? ST_WV % NSLOT : ST_WQ % NSLOT)) * SLOT);
        float acc[32];
        bar_sync(4 + wg, 256);
#pragma unroll
        for (int i = 0; i < 3; i++) {
          mbar_wait(sb + SM_FULL + (st0 + i) * 8);
          wg_fence();
#pragma unroll
          for (int kk = 0; kk < (i < 2 ? 12 : 8); kk++)
            wgmma_rs_n64(acc, A[12 * i + kk], wdesc + ((i * SLOT + kk * 2048) >> 4), (i | kk) != 0);
          wg_commit();
          if (i == 1) { wg_wait<1>(); if (lead) release(st0); }
        }
        if (ps == 1 && wg == 0) bar_arrive(5, 256);
        uint32_t a[4][4], b[4][4];
        mbar_wait(sb + SM_MISCB);
        T = (*reinterpret_cast<volatile unsigned*>(smem + SM_EPOCH) & 1) ^ 1;
#pragma unroll
        for (int h = 0; h < 4; h++) ldsm4t(b[h], wpa + h * 512);
        wg_wait<0>();
        if ((tid & 127) < 2) release(st0 + 1 + (tid & 1));
#pragma unroll
        for (int h = 0; h < 4; h++) {
          a[h][0] = pack2(acc[8 * h + 0] * r0, acc[8 * h + 1] * r0); a[h][1] = pack2(acc[8 * h + 2] * r1, acc[8 * h + 3] * r1);
          a[h][2] = pack2(acc[8 * h + 4] * r0, acc[8 * h + 5] * r0); a[h][3] = pack2(acc[8 * h + 6] * r1, acc[8 * h + 7] * r1);
        }
        if (ps != 1) {
          {
            float pp[4][2][4];
#pragma unroll
            for (int h = 0; h < 4; h++) {
#pragma unroll
              for (int i = 0; i < 4; i++) { pp[h][0][i] = 0.f; pp[h][1][i] = 0.f; }
              mma16816(pp[h][0], a[h], b[h][0], b[h][1]);
              mma16816(pp[h][1], a[h], b[h][2], b[h][3]);
            }
#pragma unroll
            for (int h = 0; h < 4; h++) {
              a[h][0] = pack2(pp[h][0][0], pp[h][0][1]); a[h][1] = pack2(pp[h][0][2], pp[h][0][3]);
              a[h][2] = pack2(pp[h][1][0], pp[h][1][1]); a[h][3] = pack2(pp[h][1][2], pp[h][1][3]);
            }
          }
          if (ps == 0 || wg == 0) bar_arrive(4 + (wg ^ 1), 256);
          if (ps == 0) mbar_wait(sb + SM_EMPTY + (wg ? ST_SCR1 - NSLOT : ST_SCR0 - NSLOT) * 8);
          {
            float e[4][16];
#pragma unroll
            for (int h = 0; h < 4; h++) feat_exp(a[h], e[h]);
            if (ps == 0) {
#pragma unroll
              for (int h = 0; h < 4; h++) {
                const float (&f)[16] = e[h];
                float sp0 = (f[0] + f[1]) + (f[4] + f[5]), sp1 = (f[2] + f[3]) + (f[6] + f[7]);
                float sn0 = (f[8] + f[9]) + (f[12] + f[13]), sn1 = (f[10] + f[11]) + (f[14] + f[15]);
                sp0 += __shfl_xor_sync(0xffffffffu, sp0, 1); sp1 += __shfl_xor_sync(0xffffffffu, sp1, 1);
                sn0 += __shfl_xor_sync(0xffffffffu, sn0, 1); sn1 += __shfl_xor_sync(0xffffffffu, sn1, 1);
                sp0 += __shfl_xor_sync(0xffffffffu, sp0, 2); sp1 += __shfl_xor_sync(0xffffffffu, sp1, 2);
                sn0 += __shfl_xor_sync(0xffffffffu, sn0, 2); sn1 += __shfl_xor_sync(0xffffffffu, sn1, 2);
                sp0 = rcp(sp0); sp1 = rcp(sp1); sn0 = rcp(sn0); sn1 = rcp(sn1);
                const uint32_t dst = scr + (h >> 1) * 8192 + lrow;
                stsm4(dst + ((((h & 1) * 4 + lhi) ^ lx) << 4), pack2(f[0] * sp0, f[1] * sp0), pack2(f[2] * sp1, f[3] * sp1),
                      pack2(f[4] * sp0, f[5] * sp0), pack2(f[6] * sp1, f[7] * sp1));
                stsm4(dst + ((((h & 1) * 4 + 2 + lhi) ^ lx) << 4), pack2(f[8] * sn0, f[9] * sn0), pack2(f[10] * sn1, f[11] * sn1),
                      pack2(f[12] * sn0, f[13] * sn0), pack2(f[14] * sn1, f[15] * sn1));
              }
            } else {
#pragma unroll
              for (int i = 0; i < 32; i++) A[i >> 2][i & 3] = pack2(e[i >> 3][2 * (i & 7)], e[i >> 3][2 * (i & 7) + 1]);
            }
          }
        } else {
#pragma unroll
          for (int h = 0; h < 4; h++) stsm4(scr + 16384 + lrow + (((2 * h + lhi) ^ lx) << 4), a[h][0], a[h][1], a[h][2], a[h][3]);
          fence_async_smem();
          if (wg == 0) {
            bar_arrive(3, 256);
          } else {
            bar_sync(3, 256);
            float kv[2][36];
            wg_fence();
#pragma unroll
            for (int ks = 0; ks < 8; ks++) {
              const uint32_t sk = (ks < 4 ? (ST_SCR0 % NSLOT) : (ST_SCR1 % NSLOT)) * SLOT + (ks & 3) * 2048;
              const uint32_t dv = (DESC(sk + 16384) & 0xFFFFu) | (((SM_ONES - sk - 16384) >> 4) << 16);
              wgmma_ss_n72_t11(kv[0], DESC(sk), dv, ks != 0);
              wgmma_ss_n72_t11(kv[1], DESC(sk + 8192), dv, ks != 0);
            }
            wg_commit();
            bar_arrive(4, 256);
            wg_wait<0>();
            if (lead) { mbar_arrive(sb + SM_EMPTY + ST_SCR0 * 8); mbar_arrive(sb + SM_EMPTY + ST_SCR1 * 8); }
            const bool up = wq >= 2;
            float* kvp = reinterpret_cast<float*>(smem + 2 * SLOT) + (wq * 16 + g) * 24;
#pragma unroll
            for (int i = 0; i < 4; i++) {
              const float (&c)[36] = kv[i >> 1];
              const int r = 16 * (i >> 1) + 2 * (i & 1);
              float* p = kvp + ((i >> 1) * 64 + (i & 1) * 8) * 24;
              *reinterpret_cast<float4*>(p + 4 * t) = make_float4(up ? c[r + 8] : c[r], up ? c[r + 9] : c[r + 1], up ? c[r + 12] : c[r + 4], 1.f);
              p[16 + t + (t == 3)] = up ? c[r + 13] : c[r + 5];
            }
            kvp[((t >> 1) * 64 + (t & 1) * 8) * 24 + 21] = (t & 2) ? ((t & 1) ? kv[1][34] : kv[1][32]) : ((t & 1) ? kv[0][34] : kv[0][32]);
            fence_async_smem();
            bar_sync(6, 192);
          }
        }
      }
#pragma unroll
      for (int i = 0; i < 32; i++) E[i >> 3][i & 7] = A[i >> 2][i & 3];
    }
    const int rh = 2 * rb + wg;
#define IDF ((g >> 1) == t ? ((g & 1) ? 0x3F800000u : 0x00003F80u) : 0u)
    const uint4* xb = reinterpret_cast<const uint4*>(smem + 2 * SLOT) + wq * 128 + lane;
    if (wg == 0) {
      mbar_wait(sb + SM_KVB);
      const uint4* sp = reinterpret_cast<const uint4*>(smem + 3 * SLOT) + tid * 6;
      uint32_t v[6][4];
      int it = 0;
#pragma unroll 1
      do {
#pragma unroll
        for (int i = 0; i < 6; i++)
          asm volatile("{\n.reg .b128 v;\nld.relaxed.gpu.b128 v, [%4];\nmov.b128 {%0,%1,%2,%3}, v;\n}"
                       : "=r"(v[i][0]), "=r"(v[i][1]), "=r"(v[i][2]), "=r"(v[i][3]) : "l"(sp + i) : "memory");
        sp = reinterpret_cast<const uint4*>(&g_kv[hg][tid][0]);
      } while (min(min(min(v[0][3], v[1][3]), min(v[2][3], v[3][3])), min(v[4][3], v[5][3])) != 0x41800000u && ++it < (1 << 18));
#define KVF(d) __uint_as_float((d) < 8 ? v[(d) / 2][(d) & 1] : (d) >= 15 ? v[5][((d) - 15) & 1] : ((d) & 1) ? v[4][(((d) - 9) / 2) & 3] : v[(((d) - 8) / 2) & 3][2])
      uint4* dst = reinterpret_cast<uint4*>(smem + SM_KVS + tid * 48);
      const uint32_t zz = pack2(KVF(16), 1.0f);
      dst[0] = make_uint4(pack2(KVF(0), KVF(1)), pack2(KVF(2), KVF(3)), pack2(KVF(4), KVF(5)), pack2(KVF(6), KVF(7)));
      dst[1] = make_uint4(pack2(KVF(8), KVF(9)), pack2(KVF(10), KVF(11)), pack2(KVF(12), KVF(13)), pack2(KVF(14), KVF(15)));
      dst[2] = make_uint4(zz, zz, zz, zz);
      __syncwarp();
      bar_sync(1, 128);
    }
    {
      uint4* op = &g_o[rh][hg][wq][0][lane];
      if (wg == 1) bar_sync(7, 256);
#pragma unroll 1
      for (int hp = 0; hp < 2; hp++) {
#pragma unroll
      for (int h = 0; h < 2; h++) {
        uint32_t b0[4], b1[4], b2[4];
        const uint32_t kb = sb + SM_KVS + ((2 * hp + h) * 32 + lane) * 48;
        ldsm4t(b0, kb); ldsm4t(b1, kb + 16); ldsm4t(b2, kb + 32);
        const uint32_t ep[4] = {E[h][0], E[h][1], E[h][2], E[h][3]}, en[4] = {E[h][4], E[h][5], E[h][6], E[h][7]};
        float np0[4] = {0, 0, 0, 0}, np1[4] = {0, 0, 0, 0}, nn0[4] = {0, 0, 0, 0}, nn1[4] = {0, 0, 0, 0}, dp[4] = {0, 0, 0, 0}, dn[4] = {0, 0, 0, 0};
        mma16816(dp, ep, b2[0], b2[1]);  mma16816(dn, en, b2[2], b2[3]);
        mma16816(np0, ep, b0[0], b0[1]); mma16816(nn0, en, b0[2], b0[3]);
        mma16816(np1, ep, b1[0], b1[1]); mma16816(nn1, en, b1[2], b1[3]);
        const float i0 = rcp(fmaf(dp[0], dn[1], fmaf(dn[0], dp[1], 1e-6f * dp[1] * dn[1])));
        const float i1 = rcp(fmaf(dp[2], dn[3], fmaf(dn[2], dp[3], 1e-6f * dp[3] * dn[3])));
        const float cp0 = dn[1] * i0, cn0 = dp[1] * i0, cp1 = dn[3] * i1, cn1 = dp[3] * i1;
        st_rlx4(op + (2 * hp + h) * 32,
                tg(pack2(fmaf(np0[0], cp0, nn0[0] * cn0), fmaf(np0[1], cp0, nn0[1] * cn0)), T),
                pack2(fmaf(np0[2], cp1, nn0[2] * cn1), fmaf(np0[3], cp1, nn0[3] * cn1)),
                pack2(fmaf(np1[0], cp0, nn1[0] * cn0), fmaf(np1[1], cp0, nn1[1] * cn0)),
                pack2(fmaf(np1[2], cp1, nn1[2] * cn1), fmaf(np1[3], cp1, nn1[3] * cn1)));
      }
#pragma unroll
        for (int i = 0; i < 8; i++) { E[0][i] = E[2][i]; E[1][i] = E[3][i]; }
      }
    }
    if (wg == 0) bar_arrive(7, 256);
    bar_arrive(10 + wg, 160);

    {
      uint32_t xr[4][4];
      {
        const uint32_t* xp = reinterpret_cast<const uint32_t*>(x + (size_t)(rh * 64 + wq * 16 + g) * 512 + hg * 64 + 2 * t);
#pragma unroll
        for (int i = 0; i < 8; i++) { xr[i >> 1][(i & 1) * 2] = __ldg(xp + 4 * i); xr[i >> 1][(i & 1) * 2 + 1] = __ldg(xp + 8 * 256 + 4 * i); }
      }
      uint32_t A[8][4][4];
      const uint4* op = &g_o[rh][0][wq][0][lane];
      float acc[32];
#pragma unroll
      for (int i = 0; i < 32; i++) acc[i] = 0.f;
      add_frag(acc, xr, IDF);
#pragma unroll
      for (int p = -1; p < 4; p++) {
        if (p < 3) {
          mbar_wait(sb + SM_XF + (wg * 4 + p + 1) * 8);
          get_pair(A[2 * p + 2], A[2 * p + 3], xb + (p + 1) * 1024, op + (p + 1) * 1024, T);
          if (lane == 0) mbar_arrive(sb + SM_XE + (wg * 4 + p + 1) * 8);
        }
        if (p == 0 && wg == 1) bar_sync(14, 256);
        if (p >= 0) {
          if (p != 2) mbar_wait(sb + SM_FULL + (ST_WO + (p + 1) / 2) * 8);
          wg_fence();
#pragma unroll
          for (int c = 2 * p; c < 2 * p + 2; c++)
#pragma unroll
            for (int s = 0; s < 4; s++)
              wgmma_rs_n64(acc, A[c][s], DESC(((ST_WO + c / 3) % NSLOT) * SLOT + ((c % 3) * 4 + s) * 2048), 1);
        }
      }
      wg_commit();
      if (wg == 0) bar_arrive(14, 256);
      wg_wait<0>();
      if ((tid & 127) < 3) release(ST_WO + (tid & 127));
      uint4* hp_ = &g_h[rh][hg][wq][0][lane];
      uint32_t hx = T;
#pragma unroll
      for (int s = 0; s < 4; s++) {
        const uint32_t h0 = pack2(acc[8 * s], acc[8 * s + 1]);
        st_rlx4(hp_ + s * 32, tg(h0, T), pack2(acc[8 * s + 2], acc[8 * s + 3]), pack2(acc[8 * s + 4], acc[8 * s + 5]), pack2(acc[8 * s + 6], acc[8 * s + 7]));
        hx |= (h0 & 1u) << (s + 1);
      }
      float s0 = 0.f, s1 = 0.f, q0 = 0.f, q1 = 0.f, q2 = 0.f, q3 = 0.f;
#pragma unroll
      for (int i = 0; i < 8; i++) {
        s0 += acc[4 * i] + acc[4 * i + 1]; s1 += acc[4 * i + 2] + acc[4 * i + 3];
        q0 = fmaf(acc[4 * i], acc[4 * i], q0); q2 = fmaf(acc[4 * i + 1], acc[4 * i + 1], q2);
        q1 = fmaf(acc[4 * i + 2], acc[4 * i + 2], q1); q3 = fmaf(acc[4 * i + 3], acc[4 * i + 3], q3);
      }
      q0 += q2; q1 += q3;
      {
        const bool up = t & 2;
        float s = (up ? s1 : s0) + __shfl_xor_sync(0xffffffffu, up ? s0 : s1, 2);
        float q = (up ? q1 : q0) + __shfl_xor_sync(0xffffffffu, up ? q0 : q1, 2);
        s += __shfl_xor_sync(0xffffffffu, s, 1);
        q += __shfl_xor_sync(0xffffffffu, q, 1);
        if (!(t & 1)) st_rlx2(&g_st[rh][hg][wq * 16 + g + (t >> 1) * 8], tg(__float_as_uint(s), T), __float_as_uint(q));
      }
      st_rlx1(&g_hx[rh][hg][wq][lane], hx);
    }
    bar_arrive(10 + wg, 160);

    const int rh3 = 2 * rb3 + wg;
    uint32_t HH[11][4], PH[11][4];
    const uint4* pp = &g_hh[rh3][jf ^ 1][0][wq][lane];
    {
      uint32_t A[8][4][4];
      const uint4* hp_ = &g_h[rh3][0][wq][0][lane];
      uint4* hhp = &g_hh[rh3][jf][0][wq][lane];
      const uint32_t dg = (db & 0xFFFFu) | (256u << 16);
      uint32_t m0, m1;
      mbar_wait(sb + SM_XF + ((2 + wg) * 4) * 8);
      {
        const uint2* sp = reinterpret_cast<const uint2*>(smem + SM_KV32 + wg * 4096) + 2 * t * 64 + wq * 16 + g;
        uint2 a0, a1, b0, b1;
        int it = 0;
#pragma unroll 1
        do {
          ld_rlx2(a0.x, a0.y, sp); ld_rlx2(a1.x, a1.y, sp + 64); ld_rlx2(b0.x, b0.y, sp + 8); ld_rlx2(b1.x, b1.y, sp + 72);
          sp = &g_st[rh3][2 * t][wq * 16 + g];
        } while (__any_sync(0xffffffffu, bad4(a0.x, a1.x, b0.x, b1.x, T)) && ++it < (1 << 18));
        float s0 = __uint_as_float(a0.x) + __uint_as_float(a1.x), q0 = __uint_as_float(a0.y) + __uint_as_float(a1.y);
        float s1 = __uint_as_float(b0.x) + __uint_as_float(b1.x), q1 = __uint_as_float(b0.y) + __uint_as_float(b1.y);
        s0 += __shfl_xor_sync(0xffffffffu, s0, 1); s1 += __shfl_xor_sync(0xffffffffu, s1, 1);
        q0 += __shfl_xor_sync(0xffffffffu, q0, 1); q1 += __shfl_xor_sync(0xffffffffu, q1, 1);
        s0 += __shfl_xor_sync(0xffffffffu, s0, 2); s1 += __shfl_xor_sync(0xffffffffu, s1, 2);
        q0 += __shfl_xor_sync(0xffffffffu, q0, 2); q1 += __shfl_xor_sync(0xffffffffu, q1, 2);
        s0 *= (1.f / 512.f); s1 *= (1.f / 512.f);
        r0 = rcp(fmaxf(q0 * (1.f / 512.f) - s0 * s0, 0.f) + 1e-5f);
        r1 = rcp(fmaxf(q1 * (1.f / 512.f) - s1 * s1, 0.f) + 1e-5f);
        m0 = pack2(s0, s0); m1 = pack2(s1, s1);
      }
#define UOFF(u) ((((ST_GU + (u) / 3) % NSLOT) * SLOT + ((u) % 3) * 8192) >> 4)
#define UNIT_PRE(u)  do { if ((u) % 3 == 0) mbar_wait(sb + SM_FULL + (ST_GU + (u) / 3) * 8); } while (0)
#define UNIT_POST(u) do { wg_commit(); if ((u) % 3 == 1 && (u) > 3) { wg_wait<2>(); if (lead) release(ST_GU + (u) / 3 - 1); } } while (0)
      float acc[64];
      const int rz = blockIdx.y;
#pragma unroll
      for (int ps = 0; ps < 2; ps++) {
        wg_fence();
#pragma unroll
        for (int k = 0; k < 16; k++) {
          const int u = 16 * ps + k, c = k >> 1;
          if (ps == 0 && (k == 0 || k == 4 || k == 8)) {
#pragma unroll
            for (int p = (k == 0 ? 0 : (k == 4 ? 1 : 3)); p < (k == 0 ? 1 : (k == 4 ? 3 : 4)); p++) {
              if (p > 0) mbar_wait(sb + SM_XF + ((2 + wg) * 4 + p) * 8);
              get_pair(A[2 * p], A[2 * p + 1], xb + p * 1024, hp_ + p * 1024, T);
              if (lane == 0) {
                if (wg == 0) mbar_arrive(sb + SM_XE + (8 + p) * 8);
                else if (p > 0) release(ST_XC + p - 1);
              }
            }
          }
          if (ps == 0 && (k & 1) == 0) {
#pragma unroll
            for (int s = 0; s < 4; s++) {
              A[c][s][0] = hsub2(A[c][s][0], m0); A[c][s][1] = hsub2(A[c][s][1], m1);
              A[c][s][2] = hsub2(A[c][s][2], m0); A[c][s][3] = hsub2(A[c][s][3], m1);
            }
            wg_fence();
          }
          UNIT_PRE(u);
          wgmma_rs_n128(acc, A[c][(k & 1) * 2], dg + UOFF(u), k != 0 ? 1 : (ps ? rz : 0));
          wgmma_rs_n128(acc, A[c][(k & 1) * 2 + 1], dg + UOFF(u) + 128, 1);
          UNIT_POST(u);
        }
        wg_wait<0>();
#pragma unroll
        for (int s = 0; s < 4; s++) {
          uint32_t (&hh)[4] = HH[4 + s];
          hh[0] = tg(pack2(acc[8 * s + 0] * acc[32 + 8 * s + 0], acc[8 * s + 1] * acc[32 + 8 * s + 1]), T);
          hh[1] = pack2(acc[8 * s + 2] * acc[32 + 8 * s + 2], acc[8 * s + 3] * acc[32 + 8 * s + 3]);
          hh[2] = pack2(acc[8 * s + 4] * acc[32 + 8 * s + 4], acc[8 * s + 5] * acc[32 + 8 * s + 5]);
          hh[3] = pack2(acc[8 * s + 6] * acc[32 + 8 * s + 6], acc[8 * s + 7] * acc[32 + 8 * s + 7]);
          st_rlx4(hhp + (4 * ps + s) * 128, hh[0], hh[1], hh[2], hh[3]);
        }
      }
      {
        float ag[24], au[24];
        const uint32_t* ph7 = reinterpret_cast<const uint32_t*>(&g_hh[rh3][jf ^ 1][7][wq][31]);
        uint32_t hv = 0;
        bar_sync(1 + wg, 128);
        wg_fence();
#pragma unroll
        for (int k = 0; k < 16; k++) {
          const int u = 32 + k, c = k >> 1;
          if (k == 6) {
#pragma unroll
            for (int s = 0; s < 4; s++) ld_rlx4(HH[s], hhp + s * 128);
          }
          if (k == 9) hv = ld_rlx1(ph7);
          if (k == 12) {
            int it = 0;
#pragma unroll 1
            while (((hv ^ T) & 1) && ++it < (1 << 18)) hv = ld_rlx1(ph7);
#pragma unroll
            for (int s = 0; s < 8; s++) ld_rlx4(PH[s], pp + s * 128);
          }
          UNIT_PRE(u);
          wgmma_rs_n48(ag, A[c][(k & 1) * 2], dg + UOFF(u), k != 0);
          wgmma_rs_n48(au, A[c][(k & 1) * 2], dg + UOFF(u) + 256, k != 0);
          wgmma_rs_n48(ag, A[c][(k & 1) * 2 + 1], dg + UOFF(u) + 128, 1);
          wgmma_rs_n48(au, A[c][(k & 1) * 2 + 1], dg + UOFF(u) + 256 + 128, 1);
          UNIT_POST(u);
        }
        wg_wait<0>();
#pragma unroll
        for (int s = 0; s < 3; s++) {
          uint32_t (&hh)[4] = HH[8 + s];
          hh[0] = tg(pack2(ag[8 * s + 0] * au[8 * s + 0], ag[8 * s + 1] * au[8 * s + 1]), T);
          hh[1] = pack2(ag[8 * s + 2] * au[8 * s + 2], ag[8 * s + 3] * au[8 * s + 3]);
          hh[2] = pack2(ag[8 * s + 4] * au[8 * s + 4], ag[8 * s + 5] * au[8 * s + 5]);
          hh[3] = pack2(ag[8 * s + 6] * au[8 * s + 6], ag[8 * s + 7] * au[8 * s + 7]);
          st_rlx4(hhp + (8 + s) * 128, hh[0], hh[1], hh[2], hh[3]);
        }
      }
    }

    {
      float acc[32];
      uint32_t hr[4][4], hx = 0;
      const int m = jf >> 1, oc = (jf & 1) * 4 + m;
      const uint32_t* ph10 = reinterpret_cast<const uint32_t*>(&g_hh[rh3][jf ^ 1][10][wq][31]);
      uint4* outb = &g_part[rh3][(jf & 1) * 4][m][wq][0][lane];
      bar_arrive(8 + wg, 256);
      int s0 = ST_D % NSLOT;
#pragma unroll 1
      for (int k = 0; k < 4; k++) {
        const int s1 = s0 + 1 == NSLOT ? 0 : s0 + 1;
        const uint32_t d0 = db + s0 * (SLOT >> 4), d1 = db + s1 * (SLOT >> 4);
        wg_wait<0>();
        if (k > 0) {
          uint4* p = outb + ((m + k) & 3) * 2048;
#pragma unroll
          for (int s = 0; s < 4; s++)
            st_rlx4(p + s * 32, tg(pack2(acc[8 * s], acc[8 * s + 1]), T), pack2(acc[8 * s + 2], acc[8 * s + 3]),
                    pack2(acc[8 * s + 4], acc[8 * s + 5]), pack2(acc[8 * s + 6], acc[8 * s + 7]));
          if (k == 1) bar_arrive(12, 320);
        } else {
          int it = 0;
#pragma unroll 1
          while (__any_sync(0xffffffffu, bad4(PH[0][0], PH[1][0], PH[2][0], PH[3][0], T) | bad4(PH[4][0], PH[5][0], PH[6][0], PH[7][0], T)) && ++it < (1 << 18)) {
#pragma unroll
            for (int s = 0; s < 8; s++) ld_rlx4(PH[s], pp + s * 128);
          }
        }
        mbar_wait(sb + SM_FULL + (ST_D + 2 * k) * 8);
        mbar_wait(sb + SM_FULL + (ST_D + 2 * k + 1) * 8);
        wg_fence();
#pragma unroll
        for (int s = 0; s < 11; s++) wgmma_rs_n64(acc, HH[s], d0 + s * 128, s != 0);
#pragma unroll
        for (int s = 0; s < 8; s++) wgmma_rs_n64(acc, PH[s], d1 + s * 128, 1);
        if (k == 0) {
          int it = 0;
#pragma unroll 1
          while (((ld_rlx1(ph10) ^ T) & 1) && ++it < (1 << 18)) {}
          ld_chunk(hr, &g_h[rh3][oc][wq][0][lane]);
#pragma unroll 1
          do {
            hx = ld_rlx1(&g_hx[rh3][oc][wq][lane]);
#pragma unroll
            for (int s = 8; s < 11; s++) ld_rlx4(PH[s], pp + s * 128);
          } while (__any_sync(0xffffffffu, bad4(PH[8][0], PH[9][0], PH[10][0], hx, T)) && ++it < (1 << 18));
          wg_fence();
        }
#pragma unroll
        for (int s = 8; s < 11; s++) wgmma_rs_n64(acc, PH[s], d1 + s * 128, 1);
        wg_commit();
        s0 = s1 + 1 == NSLOT ? 0 : s1 + 1;
      }
      wg_wait<0>();
#pragma unroll 1
      for (int q = 0; q < 3; q++) {
        uint32_t in[4][4];
        const uint4* sp = reinterpret_cast<const uint4*>(smem + ((ST_D % NSLOT) + wg) * SLOT) + q * 512 + wq * 128 + lane;
        mbar_wait_p(sb + SM_XF + (wg * 4 + q) * 8, 1);
        int it = 0;
#pragma unroll 1
        do {
#pragma unroll
          for (int s = 0; s < 4; s++)
            asm volatile("{\n.reg .b128 v;\nld.relaxed.gpu.b128 v, [%4];\nmov.b128 {%0,%1,%2,%3}, v;\n}"
                         : "=r"(in[s][0]), "=r"(in[s][1]), "=r"(in[s][2]), "=r"(in[s][3]) : "l"(sp + s * 32) : "memory");
          sp = &g_part[rh3][oc][(m - 1 - q) & 3][wq][0][lane];
        } while (__any_sync(0xffffffffu, bad4(in[0][0], in[1][0], in[2][0], in[3][0], T)) && ++it < (1 << 18));
        add_frag(acc, in, IDF);
      }
#pragma unroll
      for (int s = 0; s < 4; s++) hr[s][0] = (hr[s][0] & 0xFFFFFFFEu) | ((hx >> (s + 1)) & 1u);
#pragma unroll
      for (int i = 0; i < 32; i++) acc[i] *= (i & 2) ? r1 : r0;
      add_frag(acc, hr, IDF);
      bar_sync(9 - wg, 256);
      const uint32_t ob = sb + ((ST_D - 1) % NSLOT) * SLOT + wg * 8192;
#pragma unroll
      for (int s = 0; s < 4; s++)
        stsm4(ob + lrow + (((2 * s + lhi) ^ lx) << 4), pack2(acc[8 * s + 0], acc[8 * s + 1]), pack2(acc[8 * s + 2], acc[8 * s + 3]),
              pack2(acc[8 * s + 4], acc[8 * s + 5]), pack2(acc[8 * s + 6], acc[8 * s + 7]));
      __syncwarp();
      {
        const int row = wq * 16 + (lane >> 3);
        __nv_bfloat16* op = out + (size_t)(rh3 * 64 + row) * 512 + oc * 64 + lx * 8;
#pragma unroll
        for (int i = 0; i < 4; i++) {
          uint4 v;
          asm volatile("ld.shared.v4.b32 {%0,%1,%2,%3}, [%4];" : "=r"(v.x), "=r"(v.y), "=r"(v.z), "=r"(v.w)
                       : "r"(ob + (row + i * 4) * 128 + ((lx ^ (((lane >> 3) + i * 4) & 7)) << 4)) : "memory");
          asm volatile("st.global.v4.b32 [%0], {%1,%2,%3,%4};" ::"l"(op + i * 2048), "r"(v.x), "r"(v.y), "r"(v.z), "r"(v.w) : "memory");
        }
      }
    }
    asm volatile("barrier.cluster.arrive.relaxed.aligned;" ::: "memory");
    asm volatile("barrier.cluster.wait.aligned;" ::: "memory");
  } else {
    asm volatile("setmaxnreg.dec.sync.aligned.u32 24;");
    if (elect_one()) {
      if (warp == 8) {
#pragma unroll
        for (int k = 0; k < 9; k++) {
          const int s = k < 3 ? k : (k < 6 ? k + 3 : k - 3);
          const uint32_t bar = sb + SM_FULL + s * 8;
          mbar_init(bar, 1);
          mbar_expect_tx(bar, SLOT);
          if (s >= 3 && s < 6) tma2d(sb + s * SLOT, &maps.w, 512 + hg * 64, (s - 3) * 192, bar);
          else tma3d(sb + s * SLOT, &maps.x, 0, rb * 128 + (s >= 6 ? 64 : 0), 3 * (s % 3), bar);
        }
      } else if (warp == 9) {
        mbar_init(sb + SM_MISCB, 2);
        mbar_init(sb + SM_KVB, 2);
        mbar_expect_tx(sb + SM_KVB, 12288);
        mbar_expect_tx(sb + SM_MISCB, 2048);
        bulk_g2s(sb + SM_WPHI, wphi + hg * 1024, 2048, sb + SM_MISCB);
      } else if (warp == 10) {
        if ((sb & 0x3FFFF) != SM_BASE) __trap();
#pragma unroll 1
        for (int i = 0; i < 16; i++) {
          mbar_init(sb + SM_XF + i * 8, 1);
          mbar_expect_tx(sb + SM_XF + i * 8, (i == 8 || i == 12) ? 20480 : 16384);
          if (i < 12) mbar_init(sb + SM_XE + i * 8, 4);
        }
      } else {
        *reinterpret_cast<volatile unsigned*>(smem + SM_EPOCH) = atomicAdd(&g_start, 1u) / NCTA;
      }
      asm volatile("fence.mbarrier_init.release.cluster;" ::: "memory");
    }
    __syncwarp();
    if (warp != 11) bar_sync(0, 352);
    asm volatile("barrier.cluster.arrive.relaxed.aligned;" ::: "memory");
    if (warp == 8) {
      asm volatile("barrier.cluster.wait.aligned;" ::: "memory");
      if (elect_one()) {
        const CUtensorMap* mg = jf == 7 ? &maps.g7 : &maps.g;
        const CUtensorMap* mu = jf == 7 ? &maps.u7 : &maps.u;
        asm volatile("prefetch.tensormap [%0];" ::"l"(&maps.wo) : "memory");
        asm volatile("prefetch.tensormap [%0];" ::"l"(mg) : "memory");
        asm volatile("prefetch.tensormap [%0];" ::"l"(mu) : "memory");
        asm volatile("prefetch.tensormap [%0];" ::"l"(&maps.d) : "memory");
#pragma unroll 1
        for (int s = ST_WV; s < ST_XC; s++) {
          if (s == ST_SCR1) continue;
          mbar_wait(sb + SM_EMPTY + (s - 9) * 8);
          const uint32_t dst = sb + (s >= 18 ? s - 18 : s - 9) * SLOT, bar = sb + SM_FULL + s * 8;
          if (s < ST_WO) tma2d(dst, &maps.w, (s < ST_WQ ? 1024 : 0) + hg * 64, (s < ST_WQ ? s - ST_WV : s - ST_WQ) * 192, bar);
          else { mbar_wait(bar - 8); tma2d(dst, &maps.wo, hg * 64, (s - ST_WO) * 192, bar); }
        }
        const int jc = jf == 7 ? 0 : jf;
        int slot = (ST_GU + 1 - rank) % NSLOT;
#pragma unroll 1
        for (int s = ST_GU + 1 - rank; s < NSTAGE; s += 2) {
          mbar_wait(sb + SM_EMPTY + (s - 9) * 8);
          if (s > ST_GU && s < ST_GU + 6) mbar_wait(sb + SM_FULL + (s - 1) * 8);
          const uint32_t dst = sb + slot * SLOT, bar = sb + SM_FULL + s * 8;
          if (s < ST_D) {
#pragma unroll 1
            for (int i = 0; i < 3; i++) {
              const int u = (s - ST_GU) * 3 + i;
              tma3d_mc(dst + i * 8192, mg, (u >> 4) * 64, jc, (u & 15) * 32, bar);
              tma3d_mc(dst + i * 8192 + 4096, mu, (u >> 4) * 64, jc, (u & 15) * 32, bar);
            }
          } else {
            const int i = s - ST_D;
            tma2d_mc(dst, &maps.d, ((jf & 1) * 4 + (((jf >> 1) + 1 + (i >> 1)) & 3)) * 64, (jf ^ (i & 1)) * 176, bar);
          }
          slot += 2; if (slot >= NSLOT) slot -= NSLOT;
        }
      }
      __syncwarp();
    } else {
      asm volatile("barrier.cluster.wait.aligned;" ::: "memory");
      if (warp == 11) {
#pragma unroll
        for (int i = 0; i < 4; i++)
          reinterpret_cast<uint4*>(smem + SM_ONES)[lane + 32 * i] = make_uint4(0x3F803F80u, 0x3F803F80u, 0x3F803F80u, 0x3F803F80u);
        fence_async_smem();
        __syncwarp();
        if (lane == 0) mbar_arrive(sb + SM_MISCB);
      }
      mbar_wait(sb + SM_MISCB);
      const unsigned epoch = *reinterpret_cast<volatile unsigned*>(smem + SM_EPOCH);
      const uint32_t T = (epoch & 1) ^ 1;
      if (warp == 11) {
        (&g_kv[hg][rb * 8][0])[lane] = make_float4(0.f, 0.f, 0.f, 0.f);
        if (lane < 16) (&g_kv[hg][rb * 8][0])[32 + lane] = make_float4(0.f, 0.f, 0.f, 0.f);
        __syncwarp();
        if (elect_one()) asm volatile("red.release.gpu.global.add.u32 [%0], 8;" ::"l"(&g_kvcnt[hg * 32 + 1]) : "memory");
        mbar_wait(sb + SM_FULL + (ST_WK + 2) * 8);
        if (elect_one()) {
          asm volatile("cp.async.bulk.prefetch.L2.global [%0], 4096;" ::"l"((const char*)wo + blockIdx.x * 4096) : "memory");
          asm volatile("cp.async.bulk.prefetch.L2.global [%0], 11008;" ::"l"((const char*)wg_ + blockIdx.x * 11008) : "memory");
          asm volatile("cp.async.bulk.prefetch.L2.global [%0], 11008;" ::"l"((const char*)wu_ + blockIdx.x * 11008) : "memory");
          asm volatile("cp.async.bulk.prefetch.L2.global [%0], 11008;" ::"l"((const char*)wd_ + blockIdx.x * 11008) : "memory");
          mbar_wait(sb + SM_EMPTY + ST_SCR0 * 8);
          const unsigned target = (epoch + 1) * 128;
          unsigned v, z; int it = 0;
#pragma unroll 1
          do {
            asm volatile("{\n.reg .b64 q;\nld.acquire.gpu.global.b64 q, [%2];\nmov.b64 {%0, %1}, q;\n}" : "=r"(v), "=r"(z) : "l"(&g_kvcnt[hg * 32]) : "memory");
            if (++it > (1 << 18)) break;
          } while ((int)(v - target) < 0 || (int)(z - target) < 0);
          asm volatile("fence.proxy.async.global;" ::: "memory");
          bulk_g2s(sb + 3 * SLOT, &g_kv[hg][0][0], 12288, sb + SM_KVB);
        }
        __syncwarp();
      } else {
        const int w = warp - 9;
        st_rlx4(reinterpret_cast<uint4*>(&g_st[2 * rb + w][hg][0]) + lane, T ^ 1, T ^ 1, T ^ 1, T ^ 1);
        if (lane < 8) st_rlx4(&g_o[2 * rb + w][hg][lane >> 1][3][30 + (lane & 1)], T ^ 1, T ^ 1, T ^ 1, T ^ 1);
        st_rlx4(&g_part[2 * rb3 + w][(jf & 1) * 4 + (lane >> 3)][jf >> 1][(lane >> 1) & 3][3][30 + (lane & 1)], T ^ 1, T ^ 1, T ^ 1, T ^ 1);
        if (lane < 16) st_rlx4(&g_hh[2 * rb3 + w][jf][7 + (lane >> 3) * 3][(lane >> 1) & 3][30 + (lane & 1)], T ^ 1, T ^ 1, T ^ 1, T ^ 1);
        if (w == 0) {
          mbar_wait(sb + SM_FULL + (ST_WQ + 2) * 8);
          unsigned v; int it = 0;
#pragma unroll 1
          do {
            asm volatile("ld.acquire.gpu.global.u32 %0, [%1];" : "=r"(v) : "l"(&g_kvcnt[hg * 32 + 1]) : "memory");
          } while ((int)(v - (epoch + 1) * 128) < 0 && ++it < (1 << 18));
          asm volatile("fence.proxy.async.global;" ::: "memory");
        }
        {
          mbar_wait(sb + SM_EMPTY + (ST_WV + 1) * 8);
          float* cp = reinterpret_cast<float*>(smem + 2 * SLOT) + (w * 32 + lane) * 24;
          cp[19] = 1.f; cp[64 * 24 + 19] = 1.f;
          *reinterpret_cast<float2*>(cp + 22) = make_float2(0.f, 1.f); *reinterpret_cast<float2*>(cp + 64 * 24 + 22) = make_float2(0.f, 1.f);
          fence_async_smem();
        }
        bar_sync(6, 192);
        if (w == 0 && elect_one()) {
          asm volatile("cp.reduce.async.bulk.global.shared::cta.bulk_group.add.f32 [%0], [%1], 12288;"
                       ::"l"(&g_kv[hg][0][0]), "r"(sb + 2 * SLOT) : "memory");
          asm volatile("cp.async.bulk.commit_group;" ::: "memory");
          asm volatile("cp.async.bulk.wait_group.read 0;" ::: "memory");
          asm volatile("red.relaxed.gpu.global.add.u32 [%0], 8;" ::"l"(&g_kvcnt[hg * 32]) : "memory");
          mbar_arrive(sb + SM_KVB);
        }
        __syncwarp();
        mbar_wait(sb + SM_KVB);
        if (w == 0) { mbar_wait(sb + SM_EMPTY + 11 * 8); mbar_wait(sb + SM_EMPTY + 12 * 8); mbar_wait(sb + SM_EMPTY + 13 * 8); }
#pragma unroll 1
        for (int ph = 0; ph < 2; ph++) {
          const int use = 2 * ph + w, r = ph ? 2 * rb3 + w : 2 * rb + w;
          const uint32_t* pw = ph ? reinterpret_cast<const uint32_t*>(&g_st[r][lane >> 2][(lane & 3) * 16 + 15])
                                  : reinterpret_cast<const uint32_t*>(&g_o[r][lane >> 2][lane & 3][3][31]);
          const char* src = reinterpret_cast<const char*>(ph ? &g_h[r][0][0][0][0] : &g_o[r][0][0][0][0]);
          const uint32_t bf = sb + SM_XF + use * 32, be = sb + SM_XE + (use - 1) * 32;
          bar_sync(10 + w, 160);
          int it = 0;
#pragma unroll 1
          for (bool miss = true; __any_sync(0xffffffffu, miss) && ++it < (1 << 18);) { if (miss) miss = (ld_rlx1(pw) ^ T) & 1; }
          if (elect_one()) {
            if (use > 0) mbar_wait(be);
            if (ph) bulk_g2s(sb + SM_KV32 + w * 4096, &g_st[r][0][0], 4096, bf);
#pragma unroll
            for (int p = 0; p < 4; p++) {
              if (p > 0 && use > 0) mbar_wait(be + p * 8);
              bulk_g2s(sb + 2 * SLOT + p * 16384, src + p * 16384, 16384, bf + p * 8);
            }
          }
          __syncwarp();
        }
        {
          const int m = jf >> 1, oc = (jf & 1) * 4 + m;
          const uint32_t* pw = reinterpret_cast<const uint32_t*>(&g_part[2 * rb3 + w][oc][(m - 1 - (lane >> 2)) & 3][lane & 3][3][31]);
          bar_sync(12, 320);
          bool miss = lane < 12; int it = 0;
#pragma unroll 1
          for (int q = 0; q < 3; q++) {
#pragma unroll 1
            while ((__ballot_sync(0xffffffffu, miss) >> (4 * q) & 15) && ++it < (1 << 18)) { if (miss && (lane >> 2) <= q + 1) miss = (ld_rlx1(pw) ^ T) & 1; }
            if (elect_one()) {
              const uint32_t bar = sb + SM_XF + (w * 4 + q) * 8;
              mbar_expect_tx(bar, 8192);
              bulk_g2s(sb + ((ST_D % NSLOT) + w) * SLOT + q * 8192, &g_part[2 * rb3 + w][oc][(m - 1 - q) & 3][0][0][0], 8192, bar);
            }
            __syncwarp();
          }
        }
      }
    }
    asm volatile("barrier.cluster.arrive.relaxed.aligned;" ::: "memory");
    asm volatile("barrier.cluster.wait.aligned;" ::: "memory");
  }
}

typedef CUresult (*EncodeFn)(CUtensorMap*, CUtensorMapDataType, cuuint32_t, void*, const cuuint64_t*, const cuuint64_t*,
                             const cuuint32_t*, const cuuint32_t*, CUtensorMapInterleave, CUtensorMapSwizzle,
                             CUtensorMapL2promotion, CUtensorMapFloatOOBfill);

void encode(EncodeFn fn, CUtensorMap* m, const void* base, int rank, const cuuint64_t* dims, const cuuint64_t* strides,
            const cuuint32_t* box) {
  cuuint32_t es[3] = {1, 1, 1};
  fn(m, CU_TENSOR_MAP_DATA_TYPE_BFLOAT16, (cuuint32_t)rank, const_cast<void*>(base), dims, strides, box, es,
     CU_TENSOR_MAP_INTERLEAVE_NONE, CU_TENSOR_MAP_SWIZZLE_128B, CU_TENSOR_MAP_L2_PROMOTION_L2_256B,
     CU_TENSOR_MAP_FLOAT_OOB_FILL_NONE);
}

}

extern "C" void kernel_launch(void* const* d_in, const int* in_sizes, int n_in, void* d_out, int out_size) {
  (void)in_sizes; (void)n_in; (void)out_size;
  const __nv_bfloat16* x    = (const __nv_bfloat16*)d_in[0];
  const __nv_bfloat16* wqkv = (const __nv_bfloat16*)d_in[1];
  const __nv_bfloat16* wphi = (const __nv_bfloat16*)d_in[2];
  const __nv_bfloat16* wo   = (const __nv_bfloat16*)d_in[3];
  const __nv_bfloat16* wg   = (const __nv_bfloat16*)d_in[5];
  const __nv_bfloat16* wu   = (const __nv_bfloat16*)d_in[6];
  const __nv_bfloat16* wd   = (const __nv_bfloat16*)d_in[7];

  static EncodeFn fn = nullptr;
  if (!fn) {
    void* p = nullptr;
    cudaDriverEntryPointQueryResult qr;
    cudaGetDriverEntryPoint("cuTensorMapEncodeTiled", &p, cudaEnableDefault, &qr);
    fn = (EncodeFn)p;
    cudaFuncSetAttribute(fused_kernel, cudaFuncAttributeMaxDynamicSharedMemorySize, SM_TOTAL);
  }
  Maps maps;
  {
    cuuint64_t d[3] = {64, 2048, 8}, s[2] = {1024, 128}; cuuint32_t b[3] = {64, 64, 3};
    encode(fn, &maps.x, x, 3, d, s, b);
  }
  {
    cuuint64_t d[2] = {1536, 512}, s[1] = {3072}; cuuint32_t b[2] = {64, 192};
    encode(fn, &maps.w, wqkv, 2, d, s, b);
  }
  {
    cuuint64_t d[2] = {512, 512}, s[1] = {1024}; cuuint32_t b[2] = {64, 192};
    encode(fn, &maps.wo, wo, 2, d, s, b);
  }
  {
    cuuint64_t d[3] = {176, 7, 512}, d7[3] = {144, 1, 512}, s[2] = {352, 2752}; cuuint32_t b[3] = {64, 1, 32};
    encode(fn, &maps.g, wg, 3, d, s, b);
    encode(fn, &maps.u, wu, 3, d, s, b);
    encode(fn, &maps.g7, wg + 1232, 3, d7, s, b);
    encode(fn, &maps.u7, wu + 1232, 3, d7, s, b);
  }
  {
    cuuint64_t d[2] = {512, 1376}, s[1] = {1024}; cuuint32_t b[2] = {64, 176};
    encode(fn, &maps.d, wd, 2, d, s, b);
  }
  fused_kernel<<<NCTA, 384, SM_TOTAL>>>(maps, x, wphi, wo, wg, wu, wd, (__nv_bfloat16*)d_out);
}
```

```cpp
#include <cuda_runtime.h>
#include <cuda_bf16.h>
#include <cuda.h>
#include <stdint.h>

#define SAFE_WAIT 0

namespace {

constexpr int NCTA   = 128;
constexpr int SLOT   = 24576;
constexpr int NSLOT  = 9;
constexpr int NSTAGE = 47;

constexpr int ST_X0   = 0;
constexpr int ST_WK   = 3;
constexpr int ST_X1   = 6;
constexpr int ST_SCR0 = 9;
constexpr int ST_WV   = 10;
constexpr int ST_SCR1 = 13;
constexpr int ST_WQ   = 14;
constexpr int ST_WO   = 17;
constexpr int ST_XC   = 20;
constexpr int ST_GU   = 23;
constexpr int ST_D    = 39;

__host__ __device__ constexpr int st_empty_cnt(int d) {
  return ((d < 3 || (d >= 6 && d < 9) || (d >= ST_XC && d < ST_GU)) ? 4 : (d == ST_SCR0 || d == ST_SCR1) ? 1 : 2) * (d + 9 >= ST_GU ? 2 : 1);
}

constexpr uint32_t SM_BASE = 1024;
constexpr int SM_ONES = NSLOT * SLOT;
constexpr int SM_WPHI = SM_ONES + 2048;
constexpr int SM_KVS  = SM_WPHI + 2048;
constexpr int SM_KV32 = 4 * SLOT + 16384;
constexpr int SM_BAR  = SM_KVS + 6144;
constexpr int SM_FULL  = SM_BAR;
constexpr int SM_EMPTY = SM_BAR + NSTAGE * 8;
constexpr int SM_MISCB = SM_BAR + 2 * NSTAGE * 8;
constexpr int SM_KVB   = SM_MISCB + 8;
constexpr int SM_EPOCH = SM_KVB + 8;
constexpr int SM_XF    = SM_EPOCH + 8;
constexpr int SM_XE    = SM_XF + 16 * 8;
constexpr int SM_TOTAL = SM_BAR + 1024;

static_assert(SM_TOTAL == 232448 && SM_XE + 12 * 8 <= SM_TOTAL, "smem budget");

struct Maps { CUtensorMap x, w, wo, g, u, g7, u7, d; };

struct Scratch {
  uint4    o[8][4][4][32];
  uint4    h[8][4][4][32];
  uint32_t hx[8][4][32];
  uint2    st[8][64];
  uint4    hh[8][11][4][32];
  uint4    part[8][4][4][4][32];
};
__device__ __align__(128) Scratch g_s[32];
__device__ __align__(128) float4 g_kv[8][128][6];
__device__ __align__(128) unsigned g_kvcnt[8 * 32];
__device__ unsigned g_start;

__device__ __forceinline__ uint32_t smem_u32(const void* p) { return (uint32_t)__cvta_generic_to_shared(p); }
__device__ __forceinline__ void mbar_init(uint32_t bar, int cnt) {
  asm volatile("mbarrier.init.shared::cta.b64 [%0], %1;" ::"r"(bar), "r"(cnt) : "memory");
}
__device__ __forceinline__ void mbar_expect_tx(uint32_t bar, uint32_t bytes) {
  asm volatile("mbarrier.arrive.expect_tx.shared::cta.b64 _, [%0], %1;" ::"r"(bar), "r"(bytes) : "memory");
}
__device__ __forceinline__ void mbar_arrive(uint32_t bar) {
  asm volatile("mbarrier.arrive.shared::cta.b64 _, [%0];" ::"r"(bar) : "memory");
}
__device__ __forceinline__ void mbar_arrive_cluster(uint32_t bar, uint32_t rank) {
  asm volatile("{\n.reg .b32 ra;\nmapa.shared::cluster.u32 ra, %0, %1;\n"
               "mbarrier.arrive.shared::cluster.b64 _, [ra];\n}" ::"r"(bar), "r"(rank) : "memory");
}
__device__ __forceinline__ void mbar_wait_p(uint32_t bar, uint32_t parity) {
  asm volatile("{\n.reg .pred p;\nW: mbarrier.try_wait.parity.shared::cta.b64 p, [%0], %1;\n@!p bra W;\n}" ::"r"(bar), "r"(parity) : "memory");
}
__device__ __forceinline__ void mbar_wait(uint32_t bar) { mbar_wait_p(bar, 0); }
__device__ __forceinline__ bool elect_one() {
  uint32_t p;
  asm volatile("{\n.reg .pred P;\nelect.sync _|P, 0xffffffff;\nselp.u32 %0, 1, 0, P;\n}" : "=r"(p));
  return p != 0;
}
__device__ __forceinline__ void bar_sync(int id, int n)   { asm volatile("bar.sync %0, %1;" ::"r"(id), "r"(n) : "memory"); }
__device__ __forceinline__ void bar_arrive(int id, int n) { asm volatile("bar.arrive %0, %1;" ::"r"(id), "r"(n) : "memory"); }
__device__ __forceinline__ void fence_async_smem() { asm volatile("fence.proxy.async.shared::cta;" ::: "memory"); }
__device__ __forceinline__ void wg_fence()  { asm volatile("wgmma.fence.sync.aligned;" ::: "memory"); }
__device__ __forceinline__ void wg_commit() { asm volatile("wgmma.commit_group.sync.aligned;" ::: "memory"); }
template <int N> __device__ __forceinline__ void wg_wait() { asm volatile("wgmma.wait_group.sync.aligned %0;" ::"n"(N) : "memory"); }
#define DESC(off) (db + ((uint32_t)(off) >> 4))
__device__ __forceinline__ void tma2d(uint32_t dst, const CUtensorMap* m, int c0, int c1, uint32_t bar) {
  asm volatile("cp.async.bulk.tensor.2d.shared::cluster.global.mbarrier::complete_tx::bytes [%0], [%1, {%3, %4}], [%2];"
               ::"r"(dst), "l"(m), "r"(bar), "r"(c0), "r"(c1) : "memory");
}
__device__ __forceinline__ void tma2d_mc(uint32_t dst, const CUtensorMap* m, int c0, int c1, uint32_t bar) {
  asm volatile("cp.async.bulk.tensor.2d.shared::cluster.global.mbarrier::complete_tx::bytes.multicast::cluster [%0], [%1, {%3, %4}], [%2], %5;"
               ::"r"(dst), "l"(m), "r"(bar), "r"(c0), "r"(c1), "h"((uint16_t)3) : "memory");
}
__device__ __forceinline__ void tma3d(uint32_t dst, const CUtensorMap* m, int c0, int c1, int c2, uint32_t bar) {
  asm volatile("cp.async.bulk.tensor.3d.shared::cluster.global.mbarrier::complete_tx::bytes [%0], [%1, {%3, %4, %5}], [%2];"
               ::"r"(dst), "l"(m), "r"(bar), "r"(c0), "r"(c1), "r"(c2) : "memory");
}
__device__ __forceinline__ void tma3d_mc(uint32_t dst, const CUtensorMap* m, int c0, int c1, int c2, uint32_t bar) {
  asm volatile("cp.async.bulk.tensor.3d.shared::cluster.global.mbarrier::complete_tx::bytes.multicast::cluster [%0], [%1, {%3, %4, %5}], [%2], %6;"
               ::"r"(dst), "l"(m), "r"(bar), "r"(c0), "r"(c1), "r"(c2), "h"((uint16_t)3) : "memory");
}
__device__ __forceinline__ void ldsm4(uint32_t (&r)[4], uint32_t addr) {
  asm volatile("ldmatrix.sync.aligned.m8n8.x4.shared.b16 {%0,%1,%2,%3}, [%4];"
               : "=r"(r[0]), "=r"(r[1]), "=r"(r[2]), "=r"(r[3]) : "r"(addr) : "memory");
}
__device__ __forceinline__ void ldsm4t(uint32_t (&r)[4], uint32_t addr) {
  asm volatile("ldmatrix.sync.aligned.m8n8.x4.trans.shared.b16 {%0,%1,%2,%3}, [%4];"
               : "=r"(r[0]), "=r"(r[1]), "=r"(r[2]), "=r"(r[3]) : "r"(addr) : "memory");
}
__device__ __forceinline__ void stsm4(uint32_t addr, uint32_t r0, uint32_t r1, uint32_t r2, uint32_t r3) {
  asm volatile("stmatrix.sync.aligned.m8n8.x4.shared.b16 [%0], {%1,%2,%3,%4};"
               ::"r"(addr), "r"(r0), "r"(r1), "r"(r2), "r"(r3) : "memory");
}
__device__ __forceinline__ void mma16816(float (&c)[4], const uint32_t (&a)[4], uint32_t b0, uint32_t b1) {
  asm volatile("mma.sync.aligned.m16n8k16.row.col.f32.bf16.bf16.f32 {%0,%1,%2,%3},{%4,%5,%6,%7},{%8,%9},{%0,%1,%2,%3};"
               : "+f"(c[0]), "+f"(c[1]), "+f"(c[2]), "+f"(c[3])
               : "r"(a[0]), "r"(a[1]), "r"(a[2]), "r"(a[3]), "r"(b0), "r"(b1));
}
__device__ __forceinline__ void add_frag(float (&c)[32], const uint32_t (&a)[4][4], uint32_t id) {
#pragma unroll
  for (int i = 0; i < 8; i++)
    asm volatile("mma.sync.aligned.m16n8k8.row.col.f32.bf16.bf16.f32 {%0,%1,%2,%3},{%4,%5},{%6},{%0,%1,%2,%3};"
                 : "+f"(c[4 * i]), "+f"(c[4 * i + 1]), "+f"(c[4 * i + 2]), "+f"(c[4 * i + 3])
                 : "r"(a[i >> 1][(i & 1) * 2]), "r"(a[i >> 1][(i & 1) * 2 + 1]), "r"(id));
}
__device__ __forceinline__ uint32_t pack2(float lo, float hi) {
  uint32_t r; asm("cvt.rn.bf16x2.f32 %0, %1, %2;" : "=r"(r) : "f"(hi), "f"(lo)); return r;
}
__device__ __forceinline__ float blo(uint32_t w) { return __uint_as_float(w << 16); }
__device__ __forceinline__ float bhi(uint32_t w) { return __uint_as_float(w & 0xFFFF0000u); }
__device__ __forceinline__ uint32_t hsub2(uint32_t a, uint32_t b) { uint32_t r; asm("sub.rn.bf16x2 %0, %1, %2;" : "=r"(r) : "r"(a), "r"(b)); return r; }
__device__ __forceinline__ uint32_t hmax2(uint32_t a, uint32_t b) { uint32_t r; asm("max.bf16x2 %0, %1, %2;" : "=r"(r) : "r"(a), "r"(b)); return r; }
__device__ __forceinline__ uint32_t hmin2(uint32_t a, uint32_t b) { uint32_t r; asm("min.bf16x2 %0, %1, %2;" : "=r"(r) : "r"(a), "r"(b)); return r; }
__device__ __forceinline__ float ex2(float x) { float r; asm("ex2.approx.ftz.f32 %0, %1;" : "=f"(r) : "f"(x)); return r; }
__device__ __forceinline__ float rcp(float x) { float r; asm("rcp.approx.ftz.f32 %0, %1;" : "=f"(r) : "f"(x)); return r; }
__device__ __forceinline__ void ld_rlx4(uint32_t (&r)[4], const uint4* p) {
  asm volatile("{\n.reg .b128 v;\nld.relaxed.gpu.global.b128 v, [%4];\nmov.b128 {%0,%1,%2,%3}, v;\n}"
               : "=r"(r[0]), "=r"(r[1]), "=r"(r[2]), "=r"(r[3]) : "l"(p) : "memory");
}
__device__ __forceinline__ void st_rlx4(uint4* p, uint32_t a, uint32_t b, uint32_t c, uint32_t d) {
  asm volatile("st.relaxed.gpu.global.v4.b32 [%0], {%1,%2,%3,%4};" ::"l"(p), "r"(a), "r"(b), "r"(c), "r"(d) : "memory");
}
__device__ __forceinline__ void st_rlx2(uint2* p, uint32_t a, uint32_t b) {
  asm volatile("{\n.reg .b64 v;\nmov.b64 v, {%1,%2};\nst.relaxed.gpu.global.b64 [%0], v;\n}" ::"l"(p), "r"(a), "r"(b) : "memory");
}
__device__ __forceinline__ uint32_t ld_rlx1(const uint32_t* p) {
  uint32_t r; asm volatile("ld.relaxed.gpu.global.b32 %0, [%1];" : "=r"(r) : "l"(p) : "memory"); return r;
}
__device__ __forceinline__ void st_rlx1(uint32_t* p, uint32_t a) {
  asm volatile("st.relaxed.gpu.global.b32 [%0], %1;" ::"l"(p), "r"(a) : "memory");
}
__device__ __forceinline__ void ld_rlx2(uint32_t& a, uint32_t& b, const uint2* p) {
  asm volatile("{\n.reg .b64 v;\nld.relaxed.gpu.b64 v, [%2];\nmov.b64 {%0,%1}, v;\n}" : "=r"(a), "=r"(b) : "l"(p) : "memory");
}
__device__ __forceinline__ void bulk_g2s(uint32_t dst, const void* src, uint32_t bytes, uint32_t bar) {
  asm volatile("cp.async.bulk.shared::cluster.global.mbarrier::complete_tx::bytes [%0], [%1], %2, [%3];"
               ::"r"(dst), "l"(src), "r"(bytes), "r"(bar) : "memory");
}
__device__ __forceinline__ uint32_t tg(uint32_t w, uint32_t T) { return (w & 0xFFFFFFFEu) | T; }
__device__ __forceinline__ uint32_t bad4(uint32_t a, uint32_t b, uint32_t c, uint32_t d, uint32_t T) {
  uint32_t u, v;
  asm("lop3.b32 %0, %1, %2, %3, 0x7E;" : "=r"(u) : "r"(a), "r"(b), "r"(T));
  asm("lop3.b32 %0, %1, %2, %3, 0x7E;" : "=r"(v) : "r"(c), "r"(d), "r"(T));
  asm("lop3.b32 %0, %1, %2, 1, 0xA8;" : "=r"(u) : "r"(u), "r"(v));
  return u;
}

__device__ __forceinline__ void ld_chunk(uint32_t (&a)[4][4], const uint4* p) {
#pragma unroll
  for (int s = 0; s < 4; s++) ld_rlx4(a[s], p + s * 32);
}
__device__ __forceinline__ void get_pair(uint32_t (&a)[4][4], uint32_t (&b)[4][4], const uint4* sp, const uint4* gp, uint32_t T) {
  int it = 0;
#pragma unroll 1
  do {
#pragma unroll
    for (int s = 0; s < 8; s++) {
      uint32_t (&r)[4] = s < 4 ? a[s & 3] : b[s & 3];
      asm volatile("{\n.reg .b128 v;\nld.relaxed.gpu.b128 v, [%4];\nmov.b128 {%0,%1,%2,%3}, v;\n}"
                   : "=r"(r[0]), "=r"(r[1]), "=r"(r[2]), "=r"(r[3]) : "l"(sp + (s >> 2) * 512 + (s & 3) * 32) : "memory");
    }
    sp = gp;
  } while (__any_sync(0xffffffffu, bad4(a[0][0], a[1][0], a[2][0], a[3][0], T) | bad4(b[0][0], b[1][0], b[2][0], b[3][0], T)) && ++it < (1 << 18));
}

__device__ __forceinline__ void wgmma_rs_n48(float (&d)[24], const uint32_t (&a)[4], uint32_t descB, int scaleD) {
  asm volatile("{\n.reg .pred p;\n.reg .b64 db;\nsetp.ne.b32 p, %29, 0;\nmov.b64 db, {%28, 0x40000040};\n"
    "wgmma.mma_async.sync.aligned.m64n48k16.f32.bf16.bf16 {%0,%1,%2,%3,%4,%5,%6,%7,%8,%9,%10,%11,%12,%13,%14,%15,%16,%17,%18,%19,%20,%21,%22,%23}, {%24,%25,%26,%27}, db, p, 1, 1, 1;\n}\n"
    : "+f"(d[0]),"+f"(d[1]),"+f"(d[2]),"+f"(d[3]),"+f"(d[4]),"+f"(d[5]),"+f"(d[6]),"+f"(d[7]),"+f"(d[8]),"+f"(d[9]),"+f"(d[10]),"+f"(d[11]),"+f"(d[12]),"+f"(d[13]),"+f"(d[14]),"+f"(d[15]),"+f"(d[16]),"+f"(d[17]),"+f"(d[18]),"+f"(d[19]),"+f"(d[20]),"+f"(d[21]),"+f"(d[22]),"+f"(d[23])
    : "r"(a[0]), "r"(a[1]), "r"(a[2]), "r"(a[3]), "r"(descB), "r"(scaleD));
}
__device__ __forceinline__ void wgmma_rs_n64(float (&d)[32], const uint32_t (&a)[4], uint32_t descB, int scaleD) {
  asm volatile("{\n.reg .pred p;\n.reg .b64 db;\nsetp.ne.b32 p, %37, 0;\nmov.b64 db, {%36, 0x40000040};\n"
    "wgmma.mma_async.sync.aligned.m64n64k16.f32.bf16.bf16 {%0,%1,%2,%3,%4,%5,%6,%7,%8,%9,%10,%11,%12,%13,%14,%15,%16,%17,%18,%19,%20,%21,%22,%23,%24,%25,%26,%27,%28,%29,%30,%31}, {%32,%33,%34,%35}, db, p, 1, 1, 1;\n}\n"
    : "+f"(d[0]),"+f"(d[1]),"+f"(d[2]),"+f"(d[3]),"+f"(d[4]),"+f"(d[5]),"+f"(d[6]),"+f"(d[7]),"+f"(d[8]),"+f"(d[9]),"+f"(d[10]),"+f"(d[11]),"+f"(d[12]),"+f"(d[13]),"+f"(d[14]),"+f"(d[15]),"+f"(d[16]),"+f"(d[17]),"+f"(d[18]),"+f"(d[19]),"+f"(d[20]),"+f"(d[21]),"+f"(d[22]),"+f"(d[23]),"+f"(d[24]),"+f"(d[25]),"+f"(d[26]),"+f"(d[27]),"+f"(d[28]),"+f"(d[29]),"+f"(d[30]),"+f"(d[31])
    : "r"(a[0]), "r"(a[1]), "r"(a[2]), "r"(a[3]), "r"(descB), "r"(scaleD));
}
__device__ __forceinline__ void wgmma_rs_n128(float (&d)[64], const uint32_t (&a)[4], uint32_t descB, int scaleD) {
  asm volatile("{\n.reg .pred p;\n.reg .b64 db;\nsetp.ne.b32 p, %69, 0;\nmov.b64 db, {%68, 0x40000040};\n"
    "wgmma.mma_async.sync.aligned.m64n128k16.f32.bf16.bf16 {%0,%1,%2,%3,%4,%5,%6,%7,%8,%9,%10,%11,%12,%13,%14,%15,%16,%17,%18,%19,%20,%21,%22,%23,%24,%25,%26,%27,%28,%29,%30,%31,%32,%33,%34,%35,%36,%37,%38,%39,%40,%41,%42,%43,%44,%45,%46,%47,%48,%49,%50,%51,%52,%53,%54,%55,%56,%57,%58,%59,%60,%61,%62,%63}, {%64,%65,%66,%67}, db, p, 1, 1, 1;\n}\n"
    : "+f"(d[0]),"+f"(d[1]),"+f"(d[2]),"+f"(d[3]),"+f"(d[4]),"+f"(d[5]),"+f"(d[6]),"+f"(d[7]),"+f"(d[8]),"+f"(d[9]),"+f"(d[10]),"+f"(d[11]),"+f"(d[12]),"+f"(d[13]),"+f"(d[14]),"+f"(d[15]),"+f"(d[16]),"+f"(d[17]),"+f"(d[18]),"+f"(d[19]),"+f"(d[20]),"+f"(d[21]),"+f"(d[22]),"+f"(d[23]),"+f"(d[24]),"+f"(d[25]),"+f"(d[26]),"+f"(d[27]),"+f"(d[28]),"+f"(d[29]),"+f"(d[30]),"+f"(d[31]),"+f"(d[32]),"+f"(d[33]),"+f"(d[34]),"+f"(d[35]),"+f"(d[36]),"+f"(d[37]),"+f"(d[38]),"+f"(d[39]),"+f"(d[40]),"+f"(d[41]),"+f"(d[42]),"+f"(d[43]),"+f"(d[44]),"+f"(d[45]),"+f"(d[46]),"+f"(d[47]),"+f"(d[48]),"+f"(d[49]),"+f"(d[50]),"+f"(d[51]),"+f"(d[52]),"+f"(d[53]),"+f"(d[54]),"+f"(d[55]),"+f"(d[56]),"+f"(d[57]),"+f"(d[58]),"+f"(d[59]),"+f"(d[60]),"+f"(d[61]),"+f"(d[62]),"+f"(d[63])
    : "r"(a[0]), "r"(a[1]), "r"(a[2]), "r"(a[3]), "r"(descB), "r"(scaleD));
}
__device__ __forceinline__ void wgmma_ss_n72_t11(float (&d)[36], uint32_t descA, uint32_t descB, int scaleD) {
  asm volatile("{\n.reg .pred p;\n.reg .b64 da, db;\nsetp.ne.b32 p, %38, 0;\nmov.b64 da, {%36, 0x40000040};\nmov.b64 db, {%37, 0x40000040};\n"
    "wgmma.mma_async.sync.aligned.m64n72k16.f32.bf16.bf16 {%0,%1,%2,%3,%4,%5,%6,%7,%8,%9,%10,%11,%12,%13,%14,%15,%16,%17,%18,%19,%20,%21,%22,%23,%24,%25,%26,%27,%28,%29,%30,%31,%32,%33,%34,%35}, da, db, p, 1, 1, 1, 1;\n}\n"
    : "+f"(d[0]),"+f"(d[1]),"+f"(d[2]),"+f"(d[3]),"+f"(d[4]),"+f"(d[5]),"+f"(d[6]),"+f"(d[7]),"+f"(d[8]),"+f"(d[9]),"+f"(d[10]),"+f"(d[11]),"+f"(d[12]),"+f"(d[13]),"+f"(d[14]),"+f"(d[15]),"+f"(d[16]),"+f"(d[17]),"+f"(d[18]),"+f"(d[19]),"+f"(d[20]),"+f"(d[21]),"+f"(d[22]),"+f"(d[23]),"+f"(d[24]),"+f"(d[25]),"+f"(d[26]),"+f"(d[27]),"+f"(d[28]),"+f"(d[29]),"+f"(d[30]),"+f"(d[31]),"+f"(d[32]),"+f"(d[33]),"+f"(d[34]),"+f"(d[35])
    : "r"(descA), "r"(descB), "r"(scaleD));
}

constexpr float LOG2E = 1.4426950408889634f;

__device__ __forceinline__ void feat_exp(const uint32_t (&P)[4], float (&e)[16]) {
  uint32_t a = hmax2(P[0], P[2]), b = hmax2(P[1], P[3]);
  uint32_t mx = hmax2(__byte_perm(a, b, 0x5410), __byte_perm(a, b, 0x7632));
  a = hmin2(P[0], P[2]); b = hmin2(P[1], P[3]);
  uint32_t mn = hmin2(__byte_perm(a, b, 0x5410), __byte_perm(a, b, 0x7632));
  mx = hmax2(mx, __shfl_xor_sync(0xffffffffu, mx, 1));
  mn = hmin2(mn, __shfl_xor_sync(0xffffffffu, mn, 1));
  mx = hmax2(mx, __shfl_xor_sync(0xffffffffu, mx, 2));
  mn = hmin2(mn, __shfl_xor_sync(0xffffffffu, mn, 2));
  float mx0 = -blo(mx) * LOG2E, mx1 = -bhi(mx) * LOG2E, mn0 = blo(mn) * LOG2E, mn1 = bhi(mn) * LOG2E;
  float v[8] = {blo(P[0]), bhi(P[0]), blo(P[1]), bhi(P[1]), blo(P[2]), bhi(P[2]), blo(P[3]), bhi(P[3])};
#pragma unroll
  for (int i = 0; i < 8; i++) {
    bool r1 = (i >> 1) & 1;
    e[i]     = ex2(fmaf(v[i],  LOG2E, r1 ? mx1 : mx0));
    e[8 + i] = ex2(fmaf(v[i], -LOG2E, r1 ? mn1 : mn0));
  }
}

__global__ void __cluster_dims__(2, 1, 1) __launch_bounds__(384, 1)
fused_kernel(const __grid_constant__ Maps maps, const __nv_bfloat16* __restrict__ x, const __nv_bfloat16* __restrict__ wphi,
             const __nv_bfloat16* __restrict__ wo, const __nv_bfloat16* __restrict__ wg_, const __nv_bfloat16* __restrict__ wu_,
             const __nv_bfloat16* __restrict__ wd_, __nv_bfloat16* __restrict__ out) {
  extern __shared__ __align__(1024) unsigned char smem[];
  const uint32_t sb = smem_u32(smem);
  const int tid = threadIdx.x, lane = tid & 31;
  const int warp = __shfl_sync(0xffffffffu, tid >> 5, 0);
  const uint32_t rank = blockIdx.x & 1;
  const int cl = blockIdx.x >> 1;
  int quad, qi;
  if (cl < 4) { quad = 15; qi = cl; }
  else if (cl < 36) { quad = (cl - 4) & 7; qi = (cl - 4) >> 3; }
  else { qi = (cl - 36) / 7; quad = 8 + (cl - 36) - 7 * qi; }
  const int rb = quad, hg = 2 * qi + rank;
  const int rb3 = (quad & ~1) + rank, jf = 4 * (quad & 1) + qi;

  if (warp < 8) {
    asm volatile("setmaxnreg.inc.sync.aligned.u32 240;");
    if (elect_one()) {
#pragma unroll 1
      for (int d = warp; d + 9 < NSTAGE; d += 8) {
        mbar_init(sb + SM_EMPTY + d * 8, st_empty_cnt(d));
        mbar_init(sb + SM_FULL + (d + 9) * 8, 1);
        mbar_expect_tx(sb + SM_FULL + (d + 9) * 8, d + 9 >= ST_D ? 22528 : SLOT);
      }
      asm volatile("fence.mbarrier_init.release.cluster;" ::: "memory");
    }
    __syncwarp();
    bar_sync(0, 352);
    asm volatile("barrier.cluster.arrive.relaxed.aligned;" ::: "memory");
    const int wg = warp >> 2, wq = warp & 3, g = lane >> 2, t = lane & 3;
    const bool lead = (tid & 127) == 0;
    constexpr uint32_t db = (SM_BASE >> 4) | (512u << 16);
    auto release = [&](int d) {
      const int s = d + NSLOT;
      mbar_arrive_cluster(sb + SM_EMPTY + d * 8, s >= ST_GU ? (uint32_t)(s & 1) : rank);
    };
    const uint32_t lrow = (uint32_t)(wq * 16 + (lane & 7) + ((lane >> 3) & 1) * 8) * 128;
    const uint32_t lx = lane & 7, lhi = lane >> 4;
    if (wg == 1) bar_arrive(4, 256);

    float r0, r1;
    uint32_t E[4][8];
    uint32_t T = 0;
    {
      uint32_t A[32][4];
      const int sx = wg ? ST_X1 : ST_X0;
      {
        const uint32_t base = sb + sx * SLOT + lrow, baseb = sb + sx * SLOT + (wq * 16 + lx + lhi * 8) * 128;
        float cs[2][4], c0[2][4], c1[2][4];
#pragma unroll
        for (int i = 0; i < 4; i++) { cs[0][i] = cs[1][i] = c0[0][i] = c0[1][i] = c1[0][i] = c1[1][i] = 0.f; }
        uint32_t bt[2][4][4];
        if (wg == 1) bar_sync(13, 256);
#pragma unroll
        for (int c = -1; c < 8; c++) {
          if (c < 7) {
            const int n = c + 1;
            if (n % 3 == 0) mbar_wait(sb + SM_FULL + (sx + n / 3) * 8);
#pragma unroll
            for (int k = 0; k < 4; k++) {
              ldsm4(A[4 * n + k], base + n * 8192 + (((2 * k + lhi) ^ lx) << 4));
              ldsm4(bt[n & 1][k], baseb + n * 8192 + (((2 * k + ((lane >> 3) & 1)) ^ lx) << 4));
            }
          }
          if (c >= 0) {
#pragma unroll
            for (int k = 0; k < 4; k++) {
              const uint32_t (&f)[4] = A[4 * c + k];
              mma16816(cs[k & 1], f, 0x3F803F80u, 0x3F803F80u);
              mma16816(c0[k & 1], f, bt[c & 1][k][0], bt[c & 1][k][1]);
              mma16816(c1[k & 1], f, bt[c & 1][k][2], bt[c & 1][k][3]);
            }
          }
        }
        if (wg == 0) bar_arrive(13, 256);
        const float s0 = (cs[0][0] + cs[1][0]) * (1.f / 512.f), s1 = (cs[0][2] + cs[1][2]) * (1.f / 512.f);
        asm volatile("barrier.cluster.wait.aligned;" ::: "memory");
        if (lane < 3) release(sx + lane);
        const uint32_t m0 = pack2(s0, s0), m1 = pack2(s1, s1);
        float q0 = (g & 1) ? c0[0][1] + c0[1][1] : c0[0][0] + c0[1][0];
        float q1 = (g & 1) ? c1[0][3] + c1[1][3] : c1[0][2] + c1[1][2];
        q0 = __shfl_sync(0xffffffffu, q0, (lane & ~3) | (g >> 1));
        q1 = __shfl_sync(0xffffffffu, q1, (lane & ~3) | (g >> 1));
        r0 = rsqrtf(fmaxf(q0 * (1.f / 512.f) - s0 * s0, 0.f) + 1e-5f);
        r1 = rsqrtf(fmaxf(q1 * (1.f / 512.f) - s1 * s1, 0.f) + 1e-5f);
#pragma unroll
        for (int ks = 0; ks < 32; ks++) {
          A[ks][0] = hsub2(A[ks][0], m0); A[ks][1] = hsub2(A[ks][1], m1);
          A[ks][2] = hsub2(A[ks][2], m0); A[ks][3] = hsub2(A[ks][3], m1);
        }
      }
      const uint32_t wpa = sb + SM_WPHI + ((lane & 7) + ((lane >> 3) & 1) * 8) * 32 + lhi * 16;
      const uint32_t scr = sb + (wg ? (ST_SCR1 % NSLOT) : (ST_SCR0 % NSLOT)) * SLOT;
#pragma unroll 1
      for (int ps = 0; ps < 3; ps++) {
        const int st0 = ps == 0 ? ST_WK : (ps == 1 ? ST_WV : ST_WQ);
        const uint32_t wdesc = DESC((ps == 0 ? ST_WK % NSLOT : (ps == 1 ? ST_WV % NSLOT : ST_WQ % NSLOT)) * SLOT);
        float acc[32];
        bar_sync(4 + wg, 256);
#pragma unroll
        for (int i = 0; i < 3; i++) {
          mbar_wait(sb + SM_FULL + (st0 + i) * 8);
          wg_fence();
#pragma unroll
          for (int kk = 0; kk < (i < 2 ? 12 : 8); kk++)
            wgmma_rs_n64(acc, A[12 * i + kk], wdesc + ((i * SLOT + kk * 2048) >> 4), (i | kk) != 0);
          wg_commit();
          if (i == 1) { wg_wait<1>(); if (lead) release(st0); }
        }
        if (ps == 1 && wg == 0) bar_arrive(5, 256);
        uint32_t a[4][4], b[4][4];
        mbar_wait(sb + SM_MISCB);
        T = (*reinterpret_cast<volatile unsigned*>(smem + SM_EPOCH) & 1) ^ 1;
#pragma unroll
        for (int h = 0; h < 4; h++) ldsm4t(b[h], wpa + h * 512);
        wg_wait<0>();
        if ((tid & 127) < 2) release(st0 + 1 + (tid & 1));
#pragma unroll
        for (int h = 0; h < 4; h++) {
          a[h][0] = pack2(acc[8 * h + 0] * r0, acc[8 * h + 1] * r0); a[h][1] = pack2(acc[8 * h + 2] * r1, acc[8 * h + 3] * r1);
          a[h][2] = pack2(acc[8 * h + 4] * r0, acc[8 * h + 5] * r0); a[h][3] = pack2(acc[8 * h + 6] * r1, acc[8 * h + 7] * r1);
        }
        if (ps != 1) {
          {
            float pp[4][2][4];
#pragma unroll
            for (int h = 0; h < 4; h++) {
#pragma unroll
              for (int i = 0; i < 4; i++) { pp[h][0][i] = 0.f; pp[h][1][i] = 0.f; }
              mma16816(pp[h][0], a[h], b[h][0], b[h][1]);
              mma16816(pp[h][1], a[h], b[h][2], b[h][3]);
            }
#pragma unroll
            for (int h = 0; h < 4; h++) {
              a[h][0] = pack2(pp[h][0][0], pp[h][0][1]); a[h][1] = pack2(pp[h][0][2], pp[h][0][3]);
              a[h][2] = pack2(pp[h][1][0], pp[h][1][1]); a[h][3] = pack2(pp[h][1][2], pp[h][1][3]);
            }
          }
          if (ps == 0 || wg == 0) bar_arrive(4 + (wg ^ 1), 256);
          if (ps == 0) mbar_wait(sb + SM_EMPTY + (wg ? ST_SCR1 - NSLOT : ST_SCR0 - NSLOT) * 8);
          {
            float e[4][16];
#pragma unroll
            for (int h = 0; h < 4; h++) feat_exp(a[h], e[h]);
            if (ps == 0) {
#pragma unroll
              for (int h = 0; h < 4; h++) {
                const float (&f)[16] = e[h];
                float sp0 = (f[0] + f[1]) + (f[4] + f[5]), sp1 = (f[2] + f[3]) + (f[6] + f[7]);
                float sn0 = (f[8] + f[9]) + (f[12] + f[13]), sn1 = (f[10] + f[11]) + (f[14] + f[15]);
                sp0 += __shfl_xor_sync(0xffffffffu, sp0, 1); sp1 += __shfl_xor_sync(0xffffffffu, sp1, 1);
                sn0 += __shfl_xor_sync(0xffffffffu, sn0, 1); sn1 += __shfl_xor_sync(0xffffffffu, sn1, 1);
                sp0 += __shfl_xor_sync(0xffffffffu, sp0, 2); sp1 += __shfl_xor_sync(0xffffffffu, sp1, 2);
                sn0 += __shfl_xor_sync(0xffffffffu, sn0, 2); sn1 += __shfl_xor_sync(0xffffffffu, sn1, 2);
                sp0 = rcp(sp0); sp1 = rcp(sp1); sn0 = rcp(sn0); sn1 = rcp(sn1);
                const uint32_t dst = scr + (h >> 1) * 8192 + lrow;
                stsm4(dst + ((((h & 1) * 4 + lhi) ^ lx) << 4), pack2(f[0] * sp0, f[1] * sp0), pack2(f[2] * sp1, f[3] * sp1),
                      pack2(f[4] * sp0, f[5] * sp0), pack2(f[6] * sp1, f[7] * sp1));
                stsm4(dst + ((((h & 1) * 4 + 2 + lhi) ^ lx) << 4), pack2(f[8] * sn0, f[9] * sn0), pack2(f[10] * sn1, f[11] * sn1),
                      pack2(f[12] * sn0, f[13] * sn0), pack2(f[14] * sn1, f[15] * sn1));
              }
            } else {
#pragma unroll
              for (int i = 0; i < 32; i++) A[i >> 2][i & 3] = pack2(e[i >> 3][2 * (i & 7)], e[i >> 3][2 * (i & 7) + 1]);
            }
          }
        } else {
#pragma unroll
          for (int h = 0; h < 4; h++) stsm4(scr + 16384 + lrow + (((2 * h + lhi) ^ lx) << 4), a[h][0], a[h][1], a[h][2], a[h][3]);
          fence_async_smem();
          if (wg == 0) {
            bar_arrive(3, 256);
          } else {
            bar_sync(3, 256);
            float kv[2][36];
            wg_fence();
#pragma unroll
            for (int ks = 0; ks < 8; ks++) {
              const uint32_t sk = (ks < 4 ? (ST_SCR0 % NSLOT) : (ST_SCR1 % NSLOT)) * SLOT + (ks & 3) * 2048;
              const uint32_t dv = (DESC(sk + 16384) & 0xFFFFu) | (((SM_ONES - sk - 16384) >> 4) << 16);
              wgmma_ss_n72_t11(kv[0], DESC(sk), dv, ks != 0);
              wgmma_ss_n72_t11(kv[1], DESC(sk + 8192), dv, ks != 0);
            }
            wg_commit();
            bar_arrive(4, 256);
            wg_wait<0>();
            if (lead) { mbar_arrive(sb + SM_EMPTY + ST_SCR0 * 8); mbar_arrive(sb + SM_EMPTY + ST_SCR1 * 8); }
            const bool up = wq >= 2;
            float* kvp = reinterpret_cast<float*>(smem + 2 * SLOT) + (wq * 16 + g) * 24;
#pragma unroll
            for (int i = 0; i < 4; i++) {
              const float (&c)[36] = kv[i >> 1];
              const int r = 16 * (i >> 1) + 2 * (i & 1);
              float* p = kvp + ((i >> 1) * 64 + (i & 1) * 8) * 24;
              *reinterpret_cast<float4*>(p + 4 * t) = make_float4(up ? c[r + 8] : c[r], up ? c[r + 9] : c[r + 1], up ? c[r + 12] : c[r + 4], 1.f);
              p[16 + t + (t == 3)] = up ? c[r + 13] : c[r + 5];
            }
            kvp[((t >> 1) * 64 + (t & 1) * 8) * 24 + 21] = (t & 2) ? ((t & 1) ? kv[1][34] : kv[1][32]) : ((t & 1) ? kv[0][34] : kv[0][32]);
            fence_async_smem();
            bar_sync(6, 192);
          }
        }
      }
#pragma unroll
      for (int i = 0; i < 32; i++) E[i >> 3][i & 7] = A[i >> 2][i & 3];
    }
    const int rh = 2 * rb + wg;
#define IDF ((g >> 1) == t ? ((g & 1) ? 0x3F800000u : 0x00003F80u) : 0u)
    const uint4* xb = reinterpret_cast<const uint4*>(smem + 2 * SLOT) + wq * 128 + lane;
    if (wg == 0) {
      mbar_wait(sb + SM_KVB);
      const uint4* sp = reinterpret_cast<const uint4*>(smem + 3 * SLOT) + tid * 6;
      uint32_t v[6][4];
      int it = 0;
#pragma unroll 1
      do {
#pragma unroll
        for (int i = 0; i < 6; i++)
          asm volatile("{\n.reg .b128 v;\nld.relaxed.gpu.b128 v, [%4];\nmov.b128 {%0,%1,%2,%3}, v;\n}"
                       : "=r"(v[i][0]), "=r"(v[i][1]), "=r"(v[i][2]), "=r"(v[i][3]) : "l"(sp + i) : "memory");
        sp = reinterpret_cast<const uint4*>(&g_kv[hg][tid][0]);
      } while (min(min(min(v[0][3], v[1][3]), min(v[2][3], v[3][3])), min(v[4][3], v[5][3])) != 0x41800000u && ++it < (1 << 18));
#define KVF(d) __uint_as_float((d) < 8 ? v[(d) / 2][(d) & 1] : (d) >= 15 ? v[5][((d) - 15) & 1] : ((d) & 1) ? v[4][(((d) - 9) / 2) & 3] : v[(((d) - 8) / 2) & 3][2])
      uint4* dst = reinterpret_cast<uint4*>(smem + SM_KVS + tid * 48);
      const uint32_t zz = pack2(KVF(16), 1.0f);
      dst[0] = make_uint4(pack2(KVF(0), KVF(1)), pack2(KVF(2), KVF(3)), pack2(KVF(4), KVF(5)), pack2(KVF(6), KVF(7)));
      dst[1] = make_uint4(pack2(KVF(8), KVF(9)), pack2(KVF(10), KVF(11)), pack2(KVF(12), KVF(13)), pack2(KVF(14), KVF(15)));
      dst[2] = make_uint4(zz, zz, zz, zz);
      __syncwarp();
      bar_sync(1, 128);
    }
    {
      uint4* op = &g_s[rh].o[hg][wq][0][lane];
      if (wg == 1) bar_sync(7, 256);
#pragma unroll 1
      for (int hp = 0; hp < 2; hp++) {
#pragma unroll
      for (int h = 0; h < 2; h++) {
        uint32_t b0[4], b1[4], b2[4];
        const uint32_t kb = sb + SM_KVS + ((2 * hp + h) * 32 + lane) * 48;
        ldsm4t(b0, kb); ldsm4t(b1, kb + 16); ldsm4t(b2, kb + 32);
        const uint32_t ep[4] = {E[h][0], E[h][1], E[h][2], E[h][3]}, en[4] = {E[h][4], E[h][5], E[h][6], E[h][7]};
        float np0[4] = {0, 0, 0, 0}, np1[4] = {0, 0, 0, 0}, nn0[4] = {0, 0, 0, 0}, nn1[4] = {0, 0, 0, 0}, dp[4] = {0, 0, 0, 0}, dn[4] = {0, 0, 0, 0};
        mma16816(dp, ep, b2[0], b2[1]);  mma16816(dn, en, b2[2], b2[3]);
        mma16816(np0, ep, b0[0], b0[1]); mma16816(nn0, en, b0[2], b0[3]);
        mma16816(np1, ep, b1[0], b1[1]); mma16816(nn1, en, b1[2], b1[3]);
        const float i0 = rcp(fmaf(dp[0], dn[1], fmaf(dn[0], dp[1], 1e-6f * dp[1] * dn[1])));
        const float i1 = rcp(fmaf(dp[2], dn[3], fmaf(dn[2], dp[3], 1e-6f * dp[3] * dn[3])));
        const float cp0 = dn[1] * i0, cn0 = dp[1] * i0, cp1 = dn[3] * i1, cn1 = dp[3] * i1;
        st_rlx4(op + (2 * hp + h) * 32,
                tg(pack2(fmaf(np0[0], cp0, nn0[0] * cn0), fmaf(np0[1], cp0, nn0[1] * cn0)), T),
                pack2(fmaf(np0[2], cp1, nn0[2] * cn1), fmaf(np0[3], cp1, nn0[3] * cn1)),
                pack2(fmaf(np1[0], cp0, nn1[0] * cn0), fmaf(np1[1], cp0, nn1[1] * cn0)),
                pack2(fmaf(np1[2], cp1, nn1[2] * cn1), fmaf(np1[3], cp1, nn1[3] * cn1)));
      }
#pragma unroll
        for (int i = 0; i < 8; i++) { E[0][i] = E[2][i]; E[1][i] = E[3][i]; }
      }
    }
    if (wg == 0) bar_arrive(7, 256);
    bar_arrive(10 + wg, 160);

    {
      uint32_t xr[4][4];
      {
        const uint32_t* xp = reinterpret_cast<const uint32_t*>(x + (size_t)(rh * 64 + wq * 16 + g) * 512 + hg * 64 + 2 * t);
#pragma unroll
        for (int i = 0; i < 8; i++) { xr[i >> 1][(i & 1) * 2] = __ldg(xp + 4 * i); xr[i >> 1][(i & 1) * 2 + 1] = __ldg(xp + 8 * 256 + 4 * i); }
      }
      uint32_t A[8][4][4];
      const uint4* op = &g_s[rh].o[0][wq][0][lane];
      float acc[32];
#pragma unroll
      for (int i = 0; i < 32; i++) acc[i] = 0.f;
      add_frag(acc, xr, IDF);
#pragma unroll
      for (int p = -1; p < 4; p++) {
        if (p < 3) {
          mbar_wait(sb + SM_XF + (wg * 4 + p + 1) * 8);
          get_pair(A[2 * p + 2], A[2 * p + 3], xb + (p + 1) * 1024, op + (p + 1) * 1024, T);
          if (lane == 0) mbar_arrive(sb + SM_XE + (wg * 4 + p + 1) * 8);
        }
        if (p == 0 && wg == 1) bar_sync(14, 256);
        if (p >= 0) {
          if (p != 2) mbar_wait(sb + SM_FULL + (ST_WO + (p + 1) / 2) * 8);
          wg_fence();
#pragma unroll
          for (int c = 2 * p; c < 2 * p + 2; c++)
#pragma unroll
            for (int s = 0; s < 4; s++)
              wgmma_rs_n64(acc, A[c][s], DESC(((ST_WO + c / 3) % NSLOT) * SLOT + ((c % 3) * 4 + s) * 2048), 1);
        }
      }
      wg_commit();
      if (wg == 0) bar_arrive(14, 256);
      wg_wait<0>();
      if ((tid & 127) < 3) release(ST_WO + (tid & 127));
      uint4* hp_ = &g_s[rh].h[hg][wq][0][lane];
      uint32_t hx = T;
#pragma unroll
      for (int s = 0; s < 4; s++) {
        const uint32_t h0 = pack2(acc[8 * s], acc[8 * s + 1]);
        st_rlx4(hp_ + s * 32, tg(h0, T), pack2(acc[8 * s + 2], acc[8 * s + 3]), pack2(acc[8 * s + 4], acc[8 * s + 5]), pack2(acc[8 * s + 6], acc[8 * s + 7]));
        hx |= (h0 & 1u) << (s + 1);
      }
      float s0 = 0.f, s1 = 0.f, q0 = 0.f, q1 = 0.f, q2 = 0.f, q3 = 0.f;
#pragma unroll
      for (int i = 0; i < 8; i++) {
        s0 += acc[4 * i] + acc[4 * i + 1]; s1 += acc[4 * i + 2] + acc[4 * i + 3];
        q0 = fmaf(acc[4 * i], acc[4 * i], q0); q2 = fmaf(acc[4 * i + 1], acc[4 * i + 1], q2);
        q1 = fmaf(acc[4 * i + 2], acc[4 * i + 2], q1); q3 = fmaf(acc[4 * i + 3], acc[4 * i + 3], q3);
      }
      q0 += q2; q1 += q3;
      {
        const bool up = t & 2;
        float s = (up ? s1 : s0) + __shfl_xor_sync(0xffffffffu, up ? s0 : s1, 2);
        float q = (up ? q1 : q0) + __shfl_xor_sync(0xffffffffu, up ? q0 : q1, 2);
        s += __shfl_xor_sync(0xffffffffu, s, 1);
        q += __shfl_xor_sync(0xffffffffu, q, 1);
        if (!(t & 1)) st_rlx2(&g_s[rh].st[hg][wq * 16 + g + (t >> 1) * 8], tg(__float_as_uint(s), T), __float_as_uint(q));
      }
      st_rlx1(&g_s[rh].hx[hg][wq][lane], hx);
    }
    bar_arrive(10 + wg, 160);

    const int rh3 = 2 * rb3 + wg;
    uint32_t HH[11][4], PH[11][4];
    const uint4* pp = &g_s[rh3].hh[jf ^ 1][0][wq][lane];
    {
      uint32_t A[8][4][4];
      const uint4* hp_ = &g_s[rh3].h[0][wq][0][lane];
      uint4* hhp = &g_s[rh3].hh[jf][0][wq][lane];
      const uint32_t dg = (db & 0xFFFFu) | (256u << 16);
      uint32_t m0, m1;
      mbar_wait(sb + SM_XF + ((2 + wg) * 4) * 8);
      {
        const uint2* sp = reinterpret_cast<const uint2*>(smem + SM_KV32 + wg * 4096) + 2 * t * 64 + wq * 16 + g;
        uint2 a0, a1, b0, b1;
        int it = 0;
#pragma unroll 1
        do {
          ld_rlx2(a0.x, a0.y, sp); ld_rlx2(a1.x, a1.y, sp + 64); ld_rlx2(b0.x, b0.y, sp + 8); ld_rlx2(b1.x, b1.y, sp + 72);
          sp = &g_s[rh3].st[2 * t][wq * 16 + g];
        } while (__any_sync(0xffffffffu, bad4(a0.x, a1.x, b0.x, b1.x, T)) && ++it < (1 << 18));
        float s0 = __uint_as_float(a0.x) + __uint_as_float(a1.x), q0 = __uint_as_float(a0.y) + __uint_as_float(a1.y);
        float s1 = __uint_as_float(b0.x) + __uint_as_float(b1.x), q1 = __uint_as_float(b0.y) + __uint_as_float(b1.y);
        s0 += __shfl_xor_sync(0xffffffffu, s0, 1); s1 += __shfl_xor_sync(0xffffffffu, s1, 1);
        q0 += __shfl_xor_sync(0xffffffffu, q0, 1); q1 += __shfl_xor_sync(0xffffffffu, q1, 1);
        s0 += __shfl_xor_sync(0xffffffffu, s0, 2); s1 += __shfl_xor_sync(0xffffffffu, s1, 2);
        q0 += __shfl_xor_sync(0xffffffffu, q0, 2); q1 += __shfl_xor_sync(0xffffffffu, q1, 2);
        s0 *= (1.f / 512.f); s1 *= (1.f / 512.f);
        r0 = rcp(fmaxf(q0 * (1.f / 512.f) - s0 * s0, 0.f) + 1e-5f);
        r1 = rcp(fmaxf(q1 * (1.f / 512.f) - s1 * s1, 0.f) + 1e-5f);
        m0 = pack2(s0, s0); m1 = pack2(s1, s1);
      }
#define UOFF(u) ((((ST_GU + (u) / 3) % NSLOT) * SLOT + ((u) % 3) * 8192) >> 4)
#define UNIT_PRE(u)  do { if ((u) % 3 == 0) mbar_wait(sb + SM_FULL + (ST_GU + (u) / 3) * 8); } while (0)
#define UNIT_POST(u) do { wg_commit(); if ((u) % 3 == 1 && (u) > 3) { wg_wait<2>(); if (lead) release(ST_GU + (u) / 3 - 1); } } while (0)
      float acc[64];
      const int rz = blockIdx.y;
#pragma unroll
      for (int ps = 0; ps < 2; ps++) {
        wg_fence();
#pragma unroll
        for (int k = 0; k < 16; k++) {
          const int u = 16 * ps + k, c = k >> 1;
          if (ps == 0 && (k == 0 || k == 4 || k == 8)) {
#pragma unroll
            for (int p = (k == 0 ? 0 : (k == 4 ? 1 : 3)); p < (k == 0 ? 1 : (k == 4 ? 3 : 4)); p++) {
              if (p > 0) mbar_wait(sb + SM_XF + ((2 + wg) * 4 + p) * 8);
              get_pair(A[2 * p], A[2 * p + 1], xb + p * 1024, hp_ + p * 1024, T);
              if (lane == 0) {
                if (wg == 0) mbar_arrive(sb + SM_XE + (8 + p) * 8);
                else if (p > 0) release(ST_XC + p - 1);
              }
            }
          }
          if (ps == 0 && (k & 1) == 0) {
#pragma unroll
            for (int s = 0; s < 4; s++) {
              A[c][s][0] = hsub2(A[c][s][0], m0); A[c][s][1] = hsub2(A[c][s][1], m1);
              A[c][s][2] = hsub2(A[c][s][2], m0); A[c][s][3] = hsub2(A[c][s][3], m1);
            }
            wg_fence();
          }
          UNIT_PRE(u);
          wgmma_rs_n128(acc, A[c][(k & 1) * 2], dg + UOFF(u), k != 0 ? 1 : (ps ? rz : 0));
          wgmma_rs_n128(acc, A[c][(k & 1) * 2 + 1], dg + UOFF(u) + 128, 1);
          UNIT_POST(u);
        }
        wg_wait<0>();
#pragma unroll
        for (int s = 0; s < 4; s++) {
          uint32_t (&hh)[4] = HH[4 + s];
          hh[0] = tg(pack2(acc[8 * s + 0] * acc[32 + 8 * s + 0], acc[8 * s + 1] * acc[32 + 8 * s + 1]), T);
          hh[1] = pack2(acc[8 * s + 2] * acc[32 + 8 * s + 2], acc[8 * s + 3] * acc[32 + 8 * s + 3]);
          hh[2] = pack2(acc[8 * s + 4] * acc[32 + 8 * s + 4], acc[8 * s + 5] * acc[32 + 8 * s + 5]);
          hh[3] = pack2(acc[8 * s + 6] * acc[32 + 8 * s + 6], acc[8 * s + 7] * acc[32 + 8 * s + 7]);
          st_rlx4(hhp + (4 * ps + s) * 128, hh[0], hh[1], hh[2], hh[3]);
        }
      }
      {
        float ag[24], au[24];
        const uint32_t* ph7 = reinterpret_cast<const uint32_t*>(&g_s[rh3].hh[jf ^ 1][7][wq][31]);
        uint32_t hv = 0;
        bar_sync(1 + wg, 128);
        wg_fence();
#pragma unroll
        for (int k = 0; k < 16; k++) {
          const int u = 32 + k, c = k >> 1;
          if (k == 6) {
#pragma unroll
            for (int s = 0; s < 4; s++) ld_rlx4(HH[s], hhp + s * 128);
          }
          if (k == 9) hv = ld_rlx1(ph7);
          if (k == 12) {
            int it = 0;
#pragma unroll 1
            while (((hv ^ T) & 1) && ++it < (1 << 18)) hv = ld_rlx1(ph7);
#pragma unroll
            for (int s = 0; s < 8; s++) ld_rlx4(PH[s], pp + s * 128);
          }
          UNIT_PRE(u);
          wgmma_rs_n48(ag, A[c][(k & 1) * 2], dg + UOFF(u), k != 0);
          wgmma_rs_n48(au, A[c][(k & 1) * 2], dg + UOFF(u) + 256, k != 0);
          wgmma_rs_n48(ag, A[c][(k & 1) * 2 + 1], dg + UOFF(u) + 128, 1);
          wgmma_rs_n48(au, A[c][(k & 1) * 2 + 1], dg + UOFF(u) + 256 + 128, 1);
          UNIT_POST(u);
        }
        wg_wait<0>();
#pragma unroll
        for (int s = 0; s < 3; s++) {
          uint32_t (&hh)[4] = HH[8 + s];
          hh[0] = tg(pack2(ag[8 * s + 0] * au[8 * s + 0], ag[8 * s + 1] * au[8 * s + 1]), T);
          hh[1] = pack2(ag[8 * s + 2] * au[8 * s + 2], ag[8 * s + 3] * au[8 * s + 3]);
          hh[2] = pack2(ag[8 * s + 4] * au[8 * s + 4], ag[8 * s + 5] * au[8 * s + 5]);
          hh[3] = pack2(ag[8 * s + 6] * au[8 * s + 6], ag[8 * s + 7] * au[8 * s + 7]);
          st_rlx4(hhp + (8 + s) * 128, hh[0], hh[1], hh[2], hh[3]);
        }
      }
    }

    {
      float acc[32];
      uint32_t hr[4][4], hx = 0;
      const int m = jf >> 1, oc = (jf & 1) * 4 + m;
      const uint32_t* ph10 = reinterpret_cast<const uint32_t*>(&g_s[rh3].hh[jf ^ 1][10][wq][31]);
      uint4* outb = &g_s[rh3].part[(jf & 1) * 4][m][wq][0][lane];
      bar_arrive(8 + wg, 256);
      int s0 = ST_D % NSLOT;
#pragma unroll 1
      for (int k = 0; k < 4; k++) {
        const int s1 = s0 + 1 == NSLOT ? 0 : s0 + 1;
        const uint32_t d0 = db + s0 * (SLOT >> 4), d1 = db + s1 * (SLOT >> 4);
        wg_wait<0>();
        if (k > 0) {
          uint4* p = outb + ((m + k) & 3) * 2048;
#pragma unroll
          for (int s = 0; s < 4; s++)
            st_rlx4(p + s * 32, tg(pack2(acc[8 * s], acc[8 * s + 1]), T), pack2(acc[8 * s + 2], acc[8 * s + 3]),
                    pack2(acc[8 * s + 4], acc[8 * s + 5]), pack2(acc[8 * s + 6], acc[8 * s + 7]));
          if (k == 1) bar_arrive(12, 320);
        } else {
          int it = 0;
#pragma unroll 1
          while (__any_sync(0xffffffffu, bad4(PH[0][0], PH[1][0], PH[2][0], PH[3][0], T) | bad4(PH[4][0], PH[5][0], PH[6][0], PH[7][0], T)) && ++it < (1 << 18)) {
#pragma unroll
            for (int s = 0; s < 8; s++) ld_rlx4(PH[s], pp + s * 128);
          }
        }
        mbar_wait(sb + SM_FULL + (ST_D + 2 * k) * 8);
        mbar_wait(sb + SM_FULL + (ST_D + 2 * k + 1) * 8);
        wg_fence();
#pragma unroll
        for (int s = 0; s < 11; s++) wgmma_rs_n64(acc, HH[s], d0 + s * 128, s != 0);
#pragma unroll
        for (int s = 0; s < 8; s++) wgmma_rs_n64(acc, PH[s], d1 + s * 128, 1);
        if (k == 0) {
          int it = 0;
#pragma unroll 1
          while (((ld_rlx1(ph10) ^ T) & 1) && ++it < (1 << 18)) {}
          ld_chunk(hr, &g_s[rh3].h[oc][wq][0][lane]);
#pragma unroll 1
          do {
            hx = ld_rlx1(&g_s[rh3].hx[oc][wq][lane]);
#pragma unroll
            for (int s = 8; s < 11; s++) ld_rlx4(PH[s], pp + s * 128);
          } while (__any_sync(0xffffffffu, bad4(PH[8][0], PH[9][0], PH[10][0], hx, T)) && ++it < (1 << 18));
          wg_fence();
        }
#pragma unroll
        for (int s = 8; s < 11; s++) wgmma_rs_n64(acc, PH[s], d1 + s * 128, 1);
        wg_commit();
        s0 = s1 + 1 == NSLOT ? 0 : s1 + 1;
      }
      wg_wait<0>();
#pragma unroll 1
      for (int q = 0; q < 3; q++) {
        uint32_t in[4][4];
        const uint4* sp = reinterpret_cast<const uint4*>(smem + ((ST_D % NSLOT) + wg) * SLOT) + q * 512 + wq * 128 + lane;
        mbar_wait_p(sb + SM_XF + (wg * 4 + q) * 8, 1);
        int it = 0;
#pragma unroll 1
        do {
#pragma unroll
          for (int s = 0; s < 4; s++)
            asm volatile("{\n.reg .b128 v;\nld.relaxed.gpu.b128 v, [%4];\nmov.b128 {%0,%1,%2,%3}, v;\n}"
                         : "=r"(in[s][0]), "=r"(in[s][1]), "=r"(in[s][2]), "=r"(in[s][3]) : "l"(sp + s * 32) : "memory");
          sp = &g_s[rh3].part[oc][(m - 1 - q) & 3][wq][0][lane];
        } while (__any_sync(0xffffffffu, bad4(in[0][0], in[1][0], in[2][0], in[3][0], T)) && ++it < (1 << 18));
        add_frag(acc, in, IDF);
      }
#pragma unroll
      for (int s = 0; s < 4; s++) hr[s][0] = (hr[s][0] & 0xFFFFFFFEu) | ((hx >> (s + 1)) & 1u);
#pragma unroll
      for (int i = 0; i < 32; i++) acc[i] *= (i & 2) ? r1 : r0;
      add_frag(acc, hr, IDF);
      bar_sync(9 - wg, 256);
      const uint32_t ob = sb + ((ST_D - 1) % NSLOT) * SLOT + wg * 8192;
#pragma unroll
      for (int s = 0; s < 4; s++)
        stsm4(ob + lrow + (((2 * s + lhi) ^ lx) << 4), pack2(acc[8 * s + 0], acc[8 * s + 1]), pack2(acc[8 * s + 2], acc[8 * s + 3]),
              pack2(acc[8 * s + 4], acc[8 * s + 5]), pack2(acc[8 * s + 6], acc[8 * s + 7]));
      __syncwarp();
      {
        const int row = wq * 16 + (lane >> 3);
        __nv_bfloat16* op = out + (size_t)(rh3 * 64 + row) * 512 + oc * 64 + lx * 8;
#pragma unroll
        for (int i = 0; i < 4; i++) {
          uint4 v;
          asm volatile("ld.shared.v4.b32 {%0,%1,%2,%3}, [%4];" : "=r"(v.x), "=r"(v.y), "=r"(v.z), "=r"(v.w)
                       : "r"(ob + (row + i * 4) * 128 + ((lx ^ (((lane >> 3) + i * 4) & 7)) << 4)) : "memory");
          asm volatile("st.global.v4.b32 [%0], {%1,%2,%3,%4};" ::"l"(op + i * 2048), "r"(v.x), "r"(v.y), "r"(v.z), "r"(v.w) : "memory");
        }
      }
    }
    asm volatile("barrier.cluster.arrive.relaxed.aligned;" ::: "memory");
    asm volatile("barrier.cluster.wait.aligned;" ::: "memory");
  } else {
    asm volatile("setmaxnreg.dec.sync.aligned.u32 24;");
    if (elect_one()) {
      if (warp == 8) {
#pragma unroll
        for (int k = 0; k < 9; k++) {
          const int s = k < 3 ? k : (k < 6 ? k + 3 : k - 3);
          const uint32_t bar = sb + SM_FULL + s * 8;
          mbar_init(bar, 1);
          mbar_expect_tx(bar, SLOT);
          if (s >= 3 && s < 6) tma2d(sb + s * SLOT, &maps.w, 512 + hg * 64, (s - 3) * 192, bar);
          else tma3d(sb + s * SLOT, &maps.x, 0, rb * 128 + (s >= 6 ? 64 : 0), 3 * (s % 3), bar);
        }
      } else if (warp == 9) {
        mbar_init(sb + SM_MISCB, 2);
        mbar_init(sb + SM_KVB, 2);
        mbar_expect_tx(sb + SM_KVB, 12288);
        mbar_expect_tx(sb + SM_MISCB, 2048);
        bulk_g2s(sb + SM_WPHI, wphi + hg * 1024, 2048, sb + SM_MISCB);
      } else if (warp == 10) {
        if ((sb & 0x3FFFF) != SM_BASE) __trap();
#pragma unroll 1
        for (int i = 0; i < 16; i++) {
          mbar_init(sb + SM_XF + i * 8, 1);
          mbar_expect_tx(sb + SM_XF + i * 8, (i == 8 || i == 12) ? 20480 : 16384);
          if (i < 12) mbar_init(sb + SM_XE + i * 8, 4);
        }
      } else {
        *reinterpret_cast<volatile unsigned*>(smem + SM_EPOCH) = atomicAdd(&g_start, 1u) / NCTA;
      }
      asm volatile("fence.mbarrier_init.release.cluster;" ::: "memory");
    }
    __syncwarp();
    if (warp != 11) bar_sync(0, 352);
    asm volatile("barrier.cluster.arrive.relaxed.aligned;" ::: "memory");
    if (warp == 8) {
      asm volatile("barrier.cluster.wait.aligned;" ::: "memory");
      if (elect_one()) {
        const CUtensorMap* mg = jf == 7 ? &maps.g7 : &maps.g;
        const CUtensorMap* mu = jf == 7 ? &maps.u7 : &maps.u;
        asm volatile("prefetch.tensormap [%0];" ::"l"(&maps.wo) : "memory");
        asm volatile("prefetch.tensormap [%0];" ::"l"(mg) : "memory");
        asm volatile("prefetch.tensormap [%0];" ::"l"(mu) : "memory");
        asm volatile("prefetch.tensormap [%0];" ::"l"(&maps.d) : "memory");
#pragma unroll 1
        for (int s = ST_WV; s < ST_XC; s++) {
          if (s == ST_SCR1) continue;
          mbar_wait(sb + SM_EMPTY + (s - 9) * 8);
          const uint32_t dst = sb + (s >= 18 ? s - 18 : s - 9) * SLOT, bar = sb + SM_FULL + s * 8;
          if (s < ST_WO) tma2d(dst, &maps.w, (s < ST_WQ ? 1024 : 0) + hg * 64, (s < ST_WQ ? s - ST_WV : s - ST_WQ) * 192, bar);
          else { mbar_wait(bar - 8); tma2d(dst, &maps.wo, hg * 64, (s - ST_WO) * 192, bar); }
        }
        const int jc = jf == 7 ? 0 : jf;
        int slot = (ST_GU + 1 - rank) % NSLOT;
#pragma unroll 1
        for (int s = ST_GU + 1 - rank; s < NSTAGE; s += 2) {
          mbar_wait(sb + SM_EMPTY + (s - 9) * 8);
          if (s > ST_GU && s < ST_GU + 6) mbar_wait(sb + SM_FULL + (s - 1) * 8);
          const uint32_t dst = sb + slot * SLOT, bar = sb + SM_FULL + s * 8;
          if (s < ST_D) {
#pragma unroll 1
            for (int i = 0; i < 3; i++) {
              const int u = (s - ST_GU) * 3 + i;
              tma3d_mc(dst + i * 8192, mg, (u >> 4) * 64, jc, (u & 15) * 32, bar);
              tma3d_mc(dst + i * 8192 + 4096, mu, (u >> 4) * 64, jc, (u & 15) * 32, bar);
            }
          } else {
            const int i = s - ST_D;
            tma2d_mc(dst, &maps.d, ((jf & 1) * 4 + (((jf >> 1) + 1 + (i >> 1)) & 3)) * 64, (jf ^ (i & 1)) * 176, bar);
          }
          slot += 2; if (slot >= NSLOT) slot -= NSLOT;
        }
      }
      __syncwarp();
    } else {
      asm volatile("barrier.cluster.wait.aligned;" ::: "memory");
      if (warp == 11) {
#pragma unroll
        for (int i = 0; i < 4; i++)
          reinterpret_cast<uint4*>(smem + SM_ONES)[lane + 32 * i] = make_uint4(0x3F803F80u, 0x3F803F80u, 0x3F803F80u, 0x3F803F80u);
        fence_async_smem();
        __syncwarp();
        if (lane == 0) mbar_arrive(sb + SM_MISCB);
      }
      mbar_wait(sb + SM_MISCB);
      const unsigned epoch = *reinterpret_cast<volatile unsigned*>(smem + SM_EPOCH);
      const uint32_t T = (epoch & 1) ^ 1;
      if (warp == 11) {
        (&g_kv[hg][rb * 8][0])[lane] = make_float4(0.f, 0.f, 0.f, 0.f);
        if (lane < 16) (&g_kv[hg][rb * 8][0])[32 + lane] = make_float4(0.f, 0.f, 0.f, 0.f);
        __syncwarp();
        if (elect_one()) asm volatile("red.release.gpu.global.add.u32 [%0], 8;" ::"l"(&g_kvcnt[hg * 32 + 1]) : "memory");
        mbar_wait(sb + SM_FULL + (ST_WK + 2) * 8);
        if (elect_one()) {
          asm volatile("cp.async.bulk.prefetch.L2.global [%0], 4096;" ::"l"((const char*)wo + blockIdx.x * 4096) : "memory");
          asm volatile("cp.async.bulk.prefetch.L2.global [%0], 11008;" ::"l"((const char*)wg_ + blockIdx.x * 11008) : "memory");
          asm volatile("cp.async.bulk.prefetch.L2.global [%0], 11008;" ::"l"((const char*)wu_ + blockIdx.x * 11008) : "memory");
          asm volatile("cp.async.bulk.prefetch.L2.global [%0], 11008;" ::"l"((const char*)wd_ + blockIdx.x * 11008) : "memory");
          mbar_wait(sb + SM_EMPTY + ST_SCR0 * 8);
          const unsigned target = (epoch + 1) * 128;
          unsigned v, z; int it = 0;
#pragma unroll 1
          do {
            asm volatile("{\n.reg .b64 q;\nld.acquire.gpu.global.b64 q, [%2];\nmov.b64 {%0, %1}, q;\n}" : "=r"(v), "=r"(z) : "l"(&g_kvcnt[hg * 32]) : "memory");
            if (++it > (1 << 18)) break;
          } while ((int)(v - target) < 0 || (int)(z - target) < 0);
          asm volatile("fence.proxy.async.global;" ::: "memory");
          bulk_g2s(sb + 3 * SLOT, &g_kv[hg][0][0], 12288, sb + SM_KVB);
        }
        __syncwarp();
      } else {
        const int w = warp - 9;
        st_rlx4(reinterpret_cast<uint4*>(&g_s[2 * rb + w].st[hg][0]) + lane, T ^ 1, T ^ 1, T ^ 1, T ^ 1);
        if (lane < 8) st_rlx4(&g_s[2 * rb + w].o[hg][lane >> 1][3][30 + (lane & 1)], T ^ 1, T ^ 1, T ^ 1, T ^ 1);
        st_rlx4(&g_s[2 * rb3 + w].part[(jf & 1) * 4 + (lane >> 3)][jf >> 1][(lane >> 1) & 3][3][30 + (lane & 1)], T ^ 1, T ^ 1, T ^ 1, T ^ 1);
        if (lane < 16) st_rlx4(&g_s[2 * rb3 + w].hh[jf][7 + (lane >> 3) * 3][(lane >> 1) & 3][30 + (lane & 1)], T ^ 1, T ^ 1, T ^ 1, T ^ 1);
        if (w == 0) {
          mbar_wait(sb + SM_FULL + (ST_WQ + 2) * 8);
          unsigned v; int it = 0;
#pragma unroll 1
          do {
            asm volatile("ld.acquire.gpu.global.u32 %0, [%1];" : "=r"(v) : "l"(&g_kvcnt[hg * 32 + 1]) : "memory");
          } while ((int)(v - (epoch + 1) * 128) < 0 && ++it < (1 << 18));
          asm volatile("fence.proxy.async.global;" ::: "memory");
        }
        {
          mbar_wait(sb + SM_EMPTY + (ST_WV + 1) * 8);
          float* cp = reinterpret_cast<float*>(smem + 2 * SLOT) + (w * 32 + lane) * 24;
          cp[19] = 1.f; cp[64 * 24 + 19] = 1.f;
          *reinterpret_cast<float2*>(cp + 22) = make_float2(0.f, 1.f); *reinterpret_cast<float2*>(cp + 64 * 24 + 22) = make_float2(0.f, 1.f);
          fence_async_smem();
        }
        bar_sync(6, 192);
        if (w == 0 && elect_one()) {
          asm volatile("cp.reduce.async.bulk.global.shared::cta.bulk_group.add.f32 [%0], [%1], 12288;"
                       ::"l"(&g_kv[hg][0][0]), "r"(sb + 2 * SLOT) : "memory");
          asm volatile("cp.async.bulk.commit_group;" ::: "memory");
          asm volatile("cp.async.bulk.wait_group.read 0;" ::: "memory");
          asm volatile("red.relaxed.gpu.global.add.u32 [%0], 8;" ::"l"(&g_kvcnt[hg * 32]) : "memory");
          mbar_arrive(sb + SM_KVB);
        }
        __syncwarp();
        mbar_wait(sb + SM_KVB);
        if (w == 0) { mbar_wait(sb + SM_EMPTY + 11 * 8); mbar_wait(sb + SM_EMPTY + 12 * 8); mbar_wait(sb + SM_EMPTY + 13 * 8); }
#pragma unroll 1
        for (int ph = 0; ph < 2; ph++) {
          const int use = 2 * ph + w, r = ph ? 2 * rb3 + w : 2 * rb + w;
          const uint32_t* pw = ph ? reinterpret_cast<const uint32_t*>(&g_s[r].st[lane >> 2][(lane & 3) * 16 + 15])
                                  : reinterpret_cast<const uint32_t*>(&g_s[r].o[lane >> 2][lane & 3][3][31]);
          const char* src = reinterpret_cast<const char*>(ph ? &g_s[r].h[0][0][0][0] : &g_s[r].o[0][0][0][0]);
          const uint32_t bf = sb + SM_XF + use * 32, be = sb + SM_XE + (use - 1) * 32;
          bar_sync(10 + w, 160);
          int it = 0;
#pragma unroll 1
          for (bool miss = true; __any_sync(0xffffffffu, miss) && ++it < (1 << 18);) { if (miss) miss = (ld_rlx1(pw) ^ T) & 1; }
          if (elect_one()) {
            if (use > 0) mbar_wait(be);
            if (ph) bulk_g2s(sb + SM_KV32 + w * 4096, &g_s[r].st[0][0], 4096, bf);
#pragma unroll
            for (int p = 0; p < 4; p++) {
              if (p > 0 && use > 0) mbar_wait(be + p * 8);
              bulk_g2s(sb + 2 * SLOT + p * 16384, src + p * 16384, 16384, bf + p * 8);
            }
          }
          __syncwarp();
        }
        {
          const int m = jf >> 1, oc = (jf & 1) * 4 + m;
          const uint32_t* pw = reinterpret_cast<const uint32_t*>(&g_s[2 * rb3 + w].part[oc][(m - 1 - (lane >> 2)) & 3][lane & 3][3][31]);
          bar_sync(12, 320);
          bool miss = lane < 12; int it = 0;
#pragma unroll 1
          for (int q = 0; q < 3; q++) {
#pragma unroll 1
            while ((__ballot_sync(0xffffffffu, miss) >> (4 * q) & 15) && ++it < (1 << 18)) { if (miss && (lane >> 2) <= q + 1) miss = (ld_rlx1(pw) ^ T) & 1; }
            if (elect_one()) {
              const uint32_t bar = sb + SM_XF + (w * 4 + q) * 8;
              mbar_expect_tx(bar, 8192);
              bulk_g2s(sb + ((ST_D % NSLOT) + w) * SLOT + q * 8192, &g_s[2 * rb3 + w].part[oc][(m - 1 - q) & 3][0][0][0], 8192, bar);
            }
            __syncwarp();
          }
        }
      }
    }
    asm volatile("barrier.cluster.arrive.relaxed.aligned;" ::: "memory");
    asm volatile("barrier.cluster.wait.aligned;" ::: "memory");
  }
}

typedef CUresult (*EncodeFn)(CUtensorMap*, CUtensorMapDataType, cuuint32_t, void*, const cuuint64_t*, const cuuint64_t*,
                             const cuuint32_t*, const cuuint32_t*, CUtensorMapInterleave, CUtensorMapSwizzle,
                             CUtensorMapL2promotion, CUtensorMapFloatOOBfill);

void encode(EncodeFn fn, CUtensorMap* m, const void* base, int rank, const cuuint64_t* dims, const cuuint64_t* strides,
            const cuuint32_t* box) {
  cuuint32_t es[3] = {1, 1, 1};
  fn(m, CU_TENSOR_MAP_DATA_TYPE_BFLOAT16, (cuuint32_t)rank, const_cast<void*>(base), dims, strides, box, es,
     CU_TENSOR_MAP_INTERLEAVE_NONE, CU_TENSOR_MAP_SWIZZLE_128B, CU_TENSOR_MAP_L2_PROMOTION_L2_256B,
     CU_TENSOR_MAP_FLOAT_OOB_FILL_NONE);
}

}

extern "C" void kernel_launch(void* const* d_in, const int* in_sizes, int n_in, void* d_out, int out_size) {
  (void)in_sizes; (void)n_in; (void)out_size;
  const __nv_bfloat16* x    = (const __nv_bfloat16*)d_in[0];
  const __nv_bfloat16* wqkv = (const __nv_bfloat16*)d_in[1];
  const __nv_bfloat16* wphi = (const __nv_bfloat16*)d_in[2];
  const __nv_bfloat16* wo   = (const __nv_bfloat16*)d_in[3];
  const __nv_bfloat16* wg   = (const __nv_bfloat16*)d_in[5];
  const __nv_bfloat16* wu   = (const __nv_bfloat16*)d_in[6];
  const __nv_bfloat16* wd   = (const __nv_bfloat16*)d_in[7];

  static EncodeFn fn = nullptr;
  if (!fn) {
    void* p = nullptr;
    cudaDriverEntryPointQueryResult qr;
    cudaGetDriverEntryPoint("cuTensorMapEncodeTiled", &p, cudaEnableDefault, &qr);
    fn = (EncodeFn)p;
    cudaFuncSetAttribute(fused_kernel, cudaFuncAttributeMaxDynamicSharedMemorySize, SM_TOTAL);
  }
  Maps maps;
  {
    cuuint64_t d[3] = {64, 2048, 8}, s[2] = {1024, 128}; cuuint32_t b[3] = {64, 64, 3};
    encode(fn, &maps.x, x, 3, d, s, b);
  }
  {
    cuuint64_t d[2] = {1536, 512}, s[1] = {3072}; cuuint32_t b[2] = {64, 192};
    encode(fn, &maps.w, wqkv, 2, d, s, b);
  }
  {
    cuuint64_t d[2] = {512, 512}, s[1] = {1024}; cuuint32_t b[2] = {64, 192};
    encode(fn, &maps.wo, wo, 2, d, s, b);
  }
  {
    cuuint64_t d[3] = {176, 7, 512}, d7[3] = {144, 1, 512}, s[2] = {352, 2752}; cuuint32_t b[3] = {64, 1, 32};
    encode(fn, &maps.g, wg, 3, d, s, b);
    encode(fn, &maps.u, wu, 3, d, s, b);
    encode(fn, &maps.g7, wg + 1232, 3, d7, s, b);
    encode(fn, &maps.u7, wu + 1232, 3, d7, s, b);
  }
  {
    cuuint64_t d[2] = {512, 1376}, s[1] = {1024}; cuuint32_t b[2] = {64, 176};
    encode(fn, &maps.d, wd, 2, d, s, b);
  }
  fused_kernel<<<NCTA, 384, SM_TOTAL>>>(maps, x, wphi, wo, wg, wu, wd, (__nv_bfloat16*)d_out);
}
```

```cpp
#include <cuda_runtime.h>
#include <cuda_bf16.h>
#include <cuda.h>
#include <stdint.h>

#define SAFE_WAIT 0

#define WV_ 2
namespace {

constexpr int NCTA   = 128;
constexpr int SLOT   = 24576;
constexpr int NSLOT  = 9;
constexpr int NSTAGE = 47;

constexpr int ST_X0   = 0;
constexpr int ST_WK   = 3;
constexpr int ST_X1   = 6;
constexpr int ST_SCR0 = 9;
constexpr int ST_WV   = 10;
constexpr int ST_SCR1 = 13;
constexpr int ST_WQ   = 14;
constexpr int ST_WO   = 17;
constexpr int ST_XC   = 20;
constexpr int ST_GU   = 23;
constexpr int ST_D    = 39;

__host__ __device__ constexpr int st_empty_cnt(int d) {
  return ((d < 3 || (d >= 6 && d < 9) || (d >= ST_XC && d < ST_GU)) ? 4 : (d == ST_SCR0 || d == ST_SCR1) ? 1 : 2) * (d + 9 >= ST_GU ? 2 : 1);
}

constexpr uint32_t SM_BASE = 1024;
constexpr int SM_ONES = NSLOT * SLOT;
constexpr int SM_WPHI = SM_ONES + 2048;
constexpr int SM_KVS  = SM_WPHI + 2048;
constexpr int SM_KV32 = 4 * SLOT + 16384;
constexpr int SM_BAR  = SM_KVS + 6144;
constexpr int SM_FULL  = SM_BAR;
constexpr int SM_EMPTY = SM_BAR + NSTAGE * 8;
constexpr int SM_MISCB = SM_BAR + 2 * NSTAGE * 8;
constexpr int SM_KVB   = SM_MISCB + 8;
constexpr int SM_EPOCH = SM_KVB + 8;
constexpr int SM_XF    = SM_EPOCH + 8;
constexpr int SM_XE    = SM_XF + 16 * 8;
constexpr int SM_TOTAL = SM_BAR + 1024;

static_assert(SM_TOTAL == 232448 && SM_XE + 12 * 8 <= SM_TOTAL, "smem budget");

struct Maps { CUtensorMap x, w, wo, g, u, g7, u7, d; };

struct Scratch {
  uint4    o[8][4][4][32];
  uint4    h[8][4][4][32];
  uint32_t hx[8][4][32];
  uint2    st[8][64];
  uint4    hh[8][11][4][32];
  uint4    part[8][4][4][4][32];
};
__device__ __align__(128) Scratch g_s[32];
__device__ __align__(128) float4 g_kv[8][128][6];
__device__ __align__(128) unsigned g_kvcnt[8 * 32];
__device__ unsigned g_start;

__device__ __forceinline__ uint32_t smem_u32(const void* p) { return (uint32_t)__cvta_generic_to_shared(p); }
__device__ __forceinline__ void mbar_init(uint32_t bar, int cnt) {
  asm volatile("mbarrier.init.shared::cta.b64 [%0], %1;" ::"r"(bar), "r"(cnt) : "memory");
}
__device__ __forceinline__ void mbar_expect_tx(uint32_t bar, uint32_t bytes) {
  asm volatile("mbarrier.arrive.expect_tx.shared::cta.b64 _, [%0], %1;" ::"r"(bar), "r"(bytes) : "memory");
}
__device__ __forceinline__ void mbar_arrive(uint32_t bar) {
  asm volatile("mbarrier.arrive.shared::cta.b64 _, [%0];" ::"r"(bar) : "memory");
}
__device__ __forceinline__ void mbar_arrive_cluster(uint32_t bar, uint32_t rank) {
  asm volatile("{\n.reg .b32 ra;\nmapa.shared::cluster.u32 ra, %0, %1;\n"
               "mbarrier.arrive.shared::cluster.b64 _, [ra];\n}" ::"r"(bar), "r"(rank) : "memory");
}
__device__ __forceinline__ void mbar_wait_p(uint32_t bar, uint32_t parity) {
  asm volatile("{\n.reg .pred p;\nW: mbarrier.try_wait.parity.shared::cta.b64 p, [%0], %1;\n@!p bra W;\n}" ::"r"(bar), "r"(parity) : "memory");
}
__device__ __forceinline__ void mbar_wait(uint32_t bar) { mbar_wait_p(bar, 0); }
__device__ __forceinline__ bool elect_one() {
  uint32_t p;
  asm volatile("{\n.reg .pred P;\nelect.sync _|P, 0xffffffff;\nselp.u32 %0, 1, 0, P;\n}" : "=r"(p));
  return p != 0;
}
__device__ __forceinline__ void bar_sync(int id, int n)   { asm volatile("bar.sync %0, %1;" ::"r"(id), "r"(n) : "memory"); }
__device__ __forceinline__ void bar_arrive(int id, int n) { asm volatile("bar.arrive %0, %1;" ::"r"(id), "r"(n) : "memory"); }
__device__ __forceinline__ void fence_async_smem() { asm volatile("fence.proxy.async.shared::cta;" ::: "memory"); }
__device__ __forceinline__ void wg_fence()  { asm volatile("wgmma.fence.sync.aligned;" ::: "memory"); }
__device__ __forceinline__ void wg_commit() { asm volatile("wgmma.commit_group.sync.aligned;" ::: "memory"); }
template <int N> __device__ __forceinline__ void wg_wait() { asm volatile("wgmma.wait_group.sync.aligned %0;" ::"n"(N) : "memory"); }
#define DESC(off) (db + ((uint32_t)(off) >> 4))
__device__ __forceinline__ void tma2d(uint32_t dst, const CUtensorMap* m, int c0, int c1, uint32_t bar) {
  asm volatile("cp.async.bulk.tensor.2d.shared::cluster.global.mbarrier::complete_tx::bytes [%0], [%1, {%3, %4}], [%2];"
               ::"r"(dst), "l"(m), "r"(bar), "r"(c0), "r"(c1) : "memory");
}
__device__ __forceinline__ void tma2d_mc(uint32_t dst, const CUtensorMap* m, int c0, int c1, uint32_t bar) {
  asm volatile("cp.async.bulk.tensor.2d.shared::cluster.global.mbarrier::complete_tx::bytes.multicast::cluster [%0], [%1, {%3, %4}], [%2], %5;"
               ::"r"(dst), "l"(m), "r"(bar), "r"(c0), "r"(c1), "h"((uint16_t)3) : "memory");
}
__device__ __forceinline__ void tma3d(uint32_t dst, const CUtensorMap* m, int c0, int c1, int c2, uint32_t bar) {
  asm volatile("cp.async.bulk.tensor.3d.shared::cluster.global.mbarrier::complete_tx::bytes [%0], [%1, {%3, %4, %5}], [%2];"
               ::"r"(dst), "l"(m), "r"(bar), "r"(c0), "r"(c1), "r"(c2) : "memory");
}
__device__ __forceinline__ void tma3d_mc(uint32_t dst, const CUtensorMap* m, int c0, int c1, int c2, uint32_t bar) {
  asm volatile("cp.async.bulk.tensor.3d.shared::cluster.global.mbarrier::complete_tx::bytes.multicast::cluster [%0], [%1, {%3, %4, %5}], [%2], %6;"
               ::"r"(dst), "l"(m), "r"(bar), "r"(c0), "r"(c1), "r"(c2), "h"((uint16_t)3) : "memory");
}
__device__ __forceinline__ void ldsm4(uint32_t (&r)[4], uint32_t addr) {
  asm volatile("ldmatrix.sync.aligned.m8n8.x4.shared.b16 {%0,%1,%2,%3}, [%4];"
               : "=r"(r[0]), "=r"(r[1]), "=r"(r[2]), "=r"(r[3]) : "r"(addr) : "memory");
}
__device__ __forceinline__ void ldsm4t(uint32_t (&r)[4], uint32_t addr) {
  asm volatile("ldmatrix.sync.aligned.m8n8.x4.trans.shared.b16 {%0,%1,%2,%3}, [%4];"
               : "=r"(r[0]), "=r"(r[1]), "=r"(r[2]), "=r"(r[3]) : "r"(addr) : "memory");
}
__device__ __forceinline__ void stsm4(uint32_t addr, uint32_t r0, uint32_t r1, uint32_t r2, uint32_t r3) {
  asm volatile("stmatrix.sync.aligned.m8n8.x4.shared.b16 [%0], {%1,%2,%3,%4};"
               ::"r"(addr), "r"(r0), "r"(r1), "r"(r2), "r"(r3) : "memory");
}
__device__ __forceinline__ void mma16816(float (&c)[4], const uint32_t (&a)[4], uint32_t b0, uint32_t b1) {
  asm volatile("mma.sync.aligned.m16n8k16.row.col.f32.bf16.bf16.f32 {%0,%1,%2,%3},{%4,%5,%6,%7},{%8,%9},{%0,%1,%2,%3};"
               : "+f"(c[0]), "+f"(c[1]), "+f"(c[2]), "+f"(c[3])
               : "r"(a[0]), "r"(a[1]), "r"(a[2]), "r"(a[3]), "r"(b0), "r"(b1));
}
__device__ __forceinline__ void add_frag(float (&c)[32], const uint32_t (&a)[4][4], uint32_t id) {
#pragma unroll
  for (int i = 0; i < 8; i++)
    asm volatile("mma.sync.aligned.m16n8k8.row.col.f32.bf16.bf16.f32 {%0,%1,%2,%3},{%4,%5},{%6},{%0,%1,%2,%3};"
                 : "+f"(c[4 * i]), "+f"(c[4 * i + 1]), "+f"(c[4 * i + 2]), "+f"(c[4 * i + 3])
                 : "r"(a[i >> 1][(i & 1) * 2]), "r"(a[i >> 1][(i & 1) * 2 + 1]), "r"(id));
}
__device__ __forceinline__ uint32_t pack2(float lo, float hi) {
  uint32_t r; asm("cvt.rn.bf16x2.f32 %0, %1, %2;" : "=r"(r) : "f"(hi), "f"(lo)); return r;
}
__device__ __forceinline__ float blo(uint32_t w) { return __uint_as_float(w << 16); }
__device__ __forceinline__ float bhi(uint32_t w) { return __uint_as_float(w & 0xFFFF0000u); }
__device__ __forceinline__ uint32_t hsub2(uint32_t a, uint32_t b) { uint32_t r; asm("sub.rn.bf16x2 %0, %1, %2;" : "=r"(r) : "r"(a), "r"(b)); return r; }
__device__ __forceinline__ uint32_t hmax2(uint32_t a, uint32_t b) { uint32_t r; asm("max.bf16x2 %0, %1, %2;" : "=r"(r) : "r"(a), "r"(b)); return r; }
__device__ __forceinline__ uint32_t hmin2(uint32_t a, uint32_t b) { uint32_t r; asm("min.bf16x2 %0, %1, %2;" : "=r"(r) : "r"(a), "r"(b)); return r; }
__device__ __forceinline__ float ex2(float x) { float r; asm("ex2.approx.ftz.f32 %0, %1;" : "=f"(r) : "f"(x)); return r; }
__device__ __forceinline__ float rcp(float x) { float r; asm("rcp.approx.ftz.f32 %0, %1;" : "=f"(r) : "f"(x)); return r; }
__device__ __forceinline__ void ld_rlx4(uint32_t (&r)[4], const uint4* p) {
  asm volatile("{\n.reg .b128 v;\nld.relaxed.gpu.global.b128 v, [%4];\nmov.b128 {%0,%1,%2,%3}, v;\n}"
               : "=r"(r[0]), "=r"(r[1]), "=r"(r[2]), "=r"(r[3]) : "l"(p) : "memory");
}
__device__ __forceinline__ void st_rlx4(uint4* p, uint32_t a, uint32_t b, uint32_t c, uint32_t d) {
  asm volatile("st.relaxed.gpu.global.v4.b32 [%0], {%1,%2,%3,%4};" ::"l"(p), "r"(a), "r"(b), "r"(c), "r"(d) : "memory");
}
__device__ __forceinline__ void st_rlx2(uint2* p, uint32_t a, uint32_t b) {
  asm volatile("{\n.reg .b64 v;\nmov.b64 v, {%1,%2};\nst.relaxed.gpu.global.b64 [%0], v;\n}" ::"l"(p), "r"(a), "r"(b) : "memory");
}
__device__ __forceinline__ uint32_t ld_rlx1(const uint32_t* p) {
  uint32_t r; asm volatile("ld.relaxed.gpu.global.b32 %0, [%1];" : "=r"(r) : "l"(p) : "memory"); return r;
}
__device__ __forceinline__ void st_rlx1(uint32_t* p, uint32_t a) {
  asm volatile("st.relaxed.gpu.global.b32 [%0], %1;" ::"l"(p), "r"(a) : "memory");
}
__device__ __forceinline__ void ld_rlx2(uint32_t& a, uint32_t& b, const uint2* p) {
  asm volatile("{\n.reg .b64 v;\nld.relaxed.gpu.b64 v, [%2];\nmov.b64 {%0,%1}, v;\n}" : "=r"(a), "=r"(b) : "l"(p) : "memory");
}
__device__ __forceinline__ void bulk_g2s(uint32_t dst, const void* src, uint32_t bytes, uint32_t bar) {
  asm volatile("cp.async.bulk.shared::cluster.global.mbarrier::complete_tx::bytes [%0], [%1], %2, [%3];"
               ::"r"(dst), "l"(src), "r"(bytes), "r"(bar) : "memory");
}
__device__ __forceinline__ uint32_t tg(uint32_t w, uint32_t T) { return (w & 0xFFFFFFFEu) | T; }
__device__ __forceinline__ uint32_t bad4(uint32_t a, uint32_t b, uint32_t c, uint32_t d, uint32_t T) {
  uint32_t u, v;
  asm("lop3.b32 %0, %1, %2, %3, 0x7E;" : "=r"(u) : "r"(a), "r"(b), "r"(T));
  asm("lop3.b32 %0, %1, %2, %3, 0x7E;" : "=r"(v) : "r"(c), "r"(d), "r"(T));
  asm("lop3.b32 %0, %1, %2, 1, 0xA8;" : "=r"(u) : "r"(u), "r"(v));
  return u;
}

__device__ __forceinline__ void ld_chunk(uint32_t (&a)[4][4], const uint4* p) {
#pragma unroll
  for (int s = 0; s < 4; s++) ld_rlx4(a[s], p + s * 32);
}
__device__ __forceinline__ void get_pair(uint32_t (&a)[4][4], uint32_t (&b)[4][4], const uint4* sp, const uint4* gp, uint32_t T) {
  int it = 0;
#pragma unroll 1
  do {
#pragma unroll
    for (int s = 0; s < 8; s++) {
      uint32_t (&r)[4] = s < 4 ? a[s & 3] : b[s & 3];
      asm volatile("{\n.reg .b128 v;\nld.relaxed.gpu.b128 v, [%4];\nmov.b128 {%0,%1,%2,%3}, v;\n}"
                   : "=r"(r[0]), "=r"(r[1]), "=r"(r[2]), "=r"(r[3]) : "l"(sp + (s >> 2) * 512 + (s & 3) * 32) : "memory");
    }
    sp = gp;
  } while (__any_sync(0xffffffffu, bad4(a[0][0], a[1][0], a[2][0], a[3][0], T) | bad4(b[0][0], b[1][0], b[2][0], b[3][0], T)) && ++it < (1 << 18));
}

__device__ __forceinline__ void wgmma_rs_n48(float (&d)[24], const uint32_t (&a)[4], uint32_t descB, int scaleD) {
  asm volatile("{\n.reg .pred p;\n.reg .b64 db;\nsetp.ne.b32 p, %29, 0;\nmov.b64 db, {%28, 0x40000040};\n"
    "wgmma.mma_async.sync.aligned.m64n48k16.f32.bf16.bf16 {%0,%1,%2,%3,%4,%5,%6,%7,%8,%9,%10,%11,%12,%13,%14,%15,%16,%17,%18,%19,%20,%21,%22,%23}, {%24,%25,%26,%27}, db, p, 1, 1, 1;\n}\n"
    : "+f"(d[0]),"+f"(d[1]),"+f"(d[2]),"+f"(d[3]),"+f"(d[4]),"+f"(d[5]),"+f"(d[6]),"+f"(d[7]),"+f"(d[8]),"+f"(d[9]),"+f"(d[10]),"+f"(d[11]),"+f"(d[12]),"+f"(d[13]),"+f"(d[14]),"+f"(d[15]),"+f"(d[16]),"+f"(d[17]),"+f"(d[18]),"+f"(d[19]),"+f"(d[20]),"+f"(d[21]),"+f"(d[22]),"+f"(d[23])
    : "r"(a[0]), "r"(a[1]), "r"(a[2]), "r"(a[3]), "r"(descB), "r"(scaleD));
}
__device__ __forceinline__ void wgmma_rs_n64(float (&d)[32], const uint32_t (&a)[4], uint32_t descB, int scaleD) {
  asm volatile("{\n.reg .pred p;\n.reg .b64 db;\nsetp.ne.b32 p, %37, 0;\nmov.b64 db, {%36, 0x40000040};\n"
    "wgmma.mma_async.sync.aligned.m64n64k16.f32.bf16.bf16 {%0,%1,%2,%3,%4,%5,%6,%7,%8,%9,%10,%11,%12,%13,%14,%15,%16,%17,%18,%19,%20,%21,%22,%23,%24,%25,%26,%27,%28,%29,%30,%31}, {%32,%33,%34,%35}, db, p, 1, 1, 1;\n}\n"
    : "+f"(d[0]),"+f"(d[1]),"+f"(d[2]),"+f"(d[3]),"+f"(d[4]),"+f"(d[5]),"+f"(d[6]),"+f"(d[7]),"+f"(d[8]),"+f"(d[9]),"+f"(d[10]),"+f"(d[11]),"+f"(d[12]),"+f"(d[13]),"+f"(d[14]),"+f"(d[15]),"+f"(d[16]),"+f"(d[17]),"+f"(d[18]),"+f"(d[19]),"+f"(d[20]),"+f"(d[21]),"+f"(d[22]),"+f"(d[23]),"+f"(d[24]),"+f"(d[25]),"+f"(d[26]),"+f"(d[27]),"+f"(d[28]),"+f"(d[29]),"+f"(d[30]),"+f"(d[31])
    : "r"(a[0]), "r"(a[1]), "r"(a[2]), "r"(a[3]), "r"(descB), "r"(scaleD));
}
__device__ __forceinline__ void wgmma_rs_n128(float (&d)[64], const uint32_t (&a)[4], uint32_t descB, int scaleD) {
  asm volatile("{\n.reg .pred p;\n.reg .b64 db;\nsetp.ne.b32 p, %69, 0;\nmov.b64 db, {%68, 0x40000040};\n"
    "wgmma.mma_async.sync.aligned.m64n128k16.f32.bf16.bf16 {%0,%1,%2,%3,%4,%5,%6,%7,%8,%9,%10,%11,%12,%13,%14,%15,%16,%17,%18,%19,%20,%21,%22,%23,%24,%25,%26,%27,%28,%29,%30,%31,%32,%33,%34,%35,%36,%37,%38,%39,%40,%41,%42,%43,%44,%45,%46,%47,%48,%49,%50,%51,%52,%53,%54,%55,%56,%57,%58,%59,%60,%61,%62,%63}, {%64,%65,%66,%67}, db, p, 1, 1, 1;\n}\n"
    : "+f"(d[0]),"+f"(d[1]),"+f"(d[2]),"+f"(d[3]),"+f"(d[4]),"+f"(d[5]),"+f"(d[6]),"+f"(d[7]),"+f"(d[8]),"+f"(d[9]),"+f"(d[10]),"+f"(d[11]),"+f"(d[12]),"+f"(d[13]),"+f"(d[14]),"+f"(d[15]),"+f"(d[16]),"+f"(d[17]),"+f"(d[18]),"+f"(d[19]),"+f"(d[20]),"+f"(d[21]),"+f"(d[22]),"+f"(d[23]),"+f"(d[24]),"+f"(d[25]),"+f"(d[26]),"+f"(d[27]),"+f"(d[28]),"+f"(d[29]),"+f"(d[30]),"+f"(d[31]),"+f"(d[32]),"+f"(d[33]),"+f"(d[34]),"+f"(d[35]),"+f"(d[36]),"+f"(d[37]),"+f"(d[38]),"+f"(d[39]),"+f"(d[40]),"+f"(d[41]),"+f"(d[42]),"+f"(d[43]),"+f"(d[44]),"+f"(d[45]),"+f"(d[46]),"+f"(d[47]),"+f"(d[48]),"+f"(d[49]),"+f"(d[50]),"+f"(d[51]),"+f"(d[52]),"+f"(d[53]),"+f"(d[54]),"+f"(d[55]),"+f"(d[56]),"+f"(d[57]),"+f"(d[58]),"+f"(d[59]),"+f"(d[60]),"+f"(d[61]),"+f"(d[62]),"+f"(d[63])
    : "r"(a[0]), "r"(a[1]), "r"(a[2]), "r"(a[3]), "r"(descB), "r"(scaleD));
}
__device__ __forceinline__ void wgmma_ss_n72_t11(float (&d)[36], uint32_t descA, uint32_t descB, int scaleD) {
  asm volatile("{\n.reg .pred p;\n.reg .b64 da, db;\nsetp.ne.b32 p, %38, 0;\nmov.b64 da, {%36, 0x40000040};\nmov.b64 db, {%37, 0x40000040};\n"
    "wgmma.mma_async.sync.aligned.m64n72k16.f32.bf16.bf16 {%0,%1,%2,%3,%4,%5,%6,%7,%8,%9,%10,%11,%12,%13,%14,%15,%16,%17,%18,%19,%20,%21,%22,%23,%24,%25,%26,%27,%28,%29,%30,%31,%32,%33,%34,%35}, da, db, p, 1, 1, 1, 1;\n}\n"
    : "+f"(d[0]),"+f"(d[1]),"+f"(d[2]),"+f"(d[3]),"+f"(d[4]),"+f"(d[5]),"+f"(d[6]),"+f"(d[7]),"+f"(d[8]),"+f"(d[9]),"+f"(d[10]),"+f"(d[11]),"+f"(d[12]),"+f"(d[13]),"+f"(d[14]),"+f"(d[15]),"+f"(d[16]),"+f"(d[17]),"+f"(d[18]),"+f"(d[19]),"+f"(d[20]),"+f"(d[21]),"+f"(d[22]),"+f"(d[23]),"+f"(d[24]),"+f"(d[25]),"+f"(d[26]),"+f"(d[27]),"+f"(d[28]),"+f"(d[29]),"+f"(d[30]),"+f"(d[31]),"+f"(d[32]),"+f"(d[33]),"+f"(d[34]),"+f"(d[35])
    : "r"(descA), "r"(descB), "r"(scaleD));
}

constexpr float LOG2E = 1.4426950408889634f;

__device__ __forceinline__ void feat_exp(const uint32_t (&P)[4], float (&e)[16]) {
  uint32_t a = hmax2(P[0], P[2]), b = hmax2(P[1], P[3]);
  uint32_t mx = hmax2(__byte_perm(a, b, 0x5410), __byte_perm(a, b, 0x7632));
  a = hmin2(P[0], P[2]); b = hmin2(P[1], P[3]);
  uint32_t mn = hmin2(__byte_perm(a, b, 0x5410), __byte_perm(a, b, 0x7632));
  mx = hmax2(mx, __shfl_xor_sync(0xffffffffu, mx, 1));
  mn = hmin2(mn, __shfl_xor_sync(0xffffffffu, mn, 1));
  mx = hmax2(mx, __shfl_xor_sync(0xffffffffu, mx, 2));
  mn = hmin2(mn, __shfl_xor_sync(0xffffffffu, mn, 2));
  float mx0 = -blo(mx) * LOG2E, mx1 = -bhi(mx) * LOG2E, mn0 = blo(mn) * LOG2E, mn1 = bhi(mn) * LOG2E;
  float v[8] = {blo(P[0]), bhi(P[0]), blo(P[1]), bhi(P[1]), blo(P[2]), bhi(P[2]), blo(P[3]), bhi(P[3])};
#pragma unroll
  for (int i = 0; i < 8; i++) {
    bool r1 = (i >> 1) & 1;
    e[i]     = ex2(fmaf(v[i],  LOG2E, r1 ? mx1 : mx0));
    e[8 + i] = ex2(fmaf(v[i], -LOG2E, r1 ? mn1 : mn0));
  }
}

__global__ void __cluster_dims__(2, 1, 1) __launch_bounds__(384, 1)
fused_kernel(const __grid_constant__ Maps maps, const __nv_bfloat16* __restrict__ x, const __nv_bfloat16* __restrict__ wphi,
             const __nv_bfloat16* __restrict__ wo, const __nv_bfloat16* __restrict__ wg_, const __nv_bfloat16* __restrict__ wu_,
             const __nv_bfloat16* __restrict__ wd_, __nv_bfloat16* __restrict__ out) {
  extern __shared__ __align__(1024) unsigned char smem[];
  const uint32_t sb = smem_u32(smem);
  const int tid = threadIdx.x, lane = tid & 31;
  const int warp = __shfl_sync(0xffffffffu, tid >> 5, 0);
  const uint32_t rank = blockIdx.x & 1;
  const int cl = blockIdx.x >> 1;
  int quad, qi;
  if (cl < 4) { quad = 15; qi = cl; }
  else if (cl < 36) { quad = (cl - 4) & 7; qi = (cl - 4) >> 3; }
  else { qi = (cl - 36) / 7; quad = 8 + (cl - 36) - 7 * qi; }
  const int rb = quad, hg = 2 * qi + rank;
  const int rb3 = (quad & ~1) + rank, jf = 4 * (quad & 1) + qi;

  if (warp < 8) {
    asm volatile("setmaxnreg.inc.sync.aligned.u32 240;");
    if (elect_one()) {
#pragma unroll 1
      for (int d = warp; d + 9 < NSTAGE; d += 8) {
        mbar_init(sb + SM_EMPTY + d * 8, st_empty_cnt(d));
        mbar_init(sb + SM_FULL + (d + 9) * 8, 1);
        mbar_expect_tx(sb + SM_FULL + (d + 9) * 8, d + 9 >= ST_D ? 22528 : SLOT);
      }
      asm volatile("fence.mbarrier_init.release.cluster;" ::: "memory");
    }
    __syncwarp();
    bar_sync(0, 352);
    asm volatile("barrier.cluster.arrive.relaxed.aligned;" ::: "memory");
    const int wg = warp >> 2, wq = warp & 3, g = lane >> 2, t = lane & 3;
    const bool lead = (tid & 127) == 0;
    constexpr uint32_t db = (SM_BASE >> 4) | (512u << 16);
    auto release = [&](int d) {
      const int s = d + NSLOT;
      mbar_arrive_cluster(sb + SM_EMPTY + d * 8, s >= ST_GU ? (uint32_t)(s & 1) : rank);
    };
    const uint32_t lrow = (uint32_t)(wq * 16 + (lane & 7) + ((lane >> 3) & 1) * 8) * 128;
    const uint32_t lx = lane & 7, lhi = lane >> 4;
    if (wg == 1) bar_arrive(4, 256);

    float r0, r1;
    uint32_t E[4][8];
    uint32_t xr[4][4];
    uint32_t T = 0;
    {
      uint32_t A[32][4];
      const int sx = wg ? ST_X1 : ST_X0;
      {
        const uint32_t base = sb + sx * SLOT + lrow, baseb = sb + sx * SLOT + (wq * 16 + lx + lhi * 8) * 128;
        float cs[2][4], c0[2][4], c1[2][4];
#pragma unroll
        for (int i = 0; i < 4; i++) { cs[0][i] = cs[1][i] = c0[0][i] = c0[1][i] = c1[0][i] = c1[1][i] = 0.f; }
        uint32_t bt[2][4][4];
        if (wg == 1) bar_sync(13, 256);
#pragma unroll
        for (int c = -1; c < 8; c++) {
          if (c < 7) {
            const int n = c + 1;
            if (n % 3 == 0) mbar_wait(sb + SM_FULL + (sx + n / 3) * 8);
#pragma unroll
            for (int k = 0; k < 4; k++) {
              ldsm4(A[4 * n + k], base + n * 8192 + (((2 * k + lhi) ^ lx) << 4));
              ldsm4(bt[n & 1][k], baseb + n * 8192 + (((2 * k + ((lane >> 3) & 1)) ^ lx) << 4));
            }
          }
          if (c >= 0) {
#pragma unroll
            for (int k = 0; k < 4; k++) {
              const uint32_t (&f)[4] = A[4 * c + k];
              mma16816(cs[k & 1], f, 0x3F803F80u, 0x3F803F80u);
              mma16816(c0[k & 1], f, bt[c & 1][k][0], bt[c & 1][k][1]);
              mma16816(c1[k & 1], f, bt[c & 1][k][2], bt[c & 1][k][3]);
            }
          }
        }
        if (wg == 0) bar_arrive(13, 256);
        const float s0 = (cs[0][0] + cs[1][0]) * (1.f / 512.f), s1 = (cs[0][2] + cs[1][2]) * (1.f / 512.f);
        asm volatile("barrier.cluster.wait.aligned;" ::: "memory");
        if (lane < 3) release(sx + lane);
        const uint32_t m0 = pack2(s0, s0), m1 = pack2(s1, s1);
        float q0 = (g & 1) ? c0[0][1] + c0[1][1] : c0[0][0] + c0[1][0];
        float q1 = (g & 1) ? c1[0][3] + c1[1][3] : c1[0][2] + c1[1][2];
        q0 = __shfl_sync(0xffffffffu, q0, (lane & ~3) | (g >> 1));
        q1 = __shfl_sync(0xffffffffu, q1, (lane & ~3) | (g >> 1));
        r0 = rsqrtf(fmaxf(q0 * (1.f / 512.f) - s0 * s0, 0.f) + 1e-5f);
        r1 = rsqrtf(fmaxf(q1 * (1.f / 512.f) - s1 * s1, 0.f) + 1e-5f);
#pragma unroll
        for (int ks = 0; ks < 32; ks++) {
          A[ks][0] = hsub2(A[ks][0], m0); A[ks][1] = hsub2(A[ks][1], m1);
          A[ks][2] = hsub2(A[ks][2], m0); A[ks][3] = hsub2(A[ks][3], m1);
        }
      }
      const uint32_t wpa = sb + SM_WPHI + ((lane & 7) + ((lane >> 3) & 1) * 8) * 32 + lhi * 16;
      const uint32_t scr = sb + (wg ? (ST_SCR1 % NSLOT) : (ST_SCR0 % NSLOT)) * SLOT;
#pragma unroll 1
      for (int ps = 0; ps < 3; ps++) {
        const int st0 = ps == 0 ? ST_WK : (ps == 1 ? ST_WV : ST_WQ);
        const uint32_t wdesc = DESC((ps == 0 ? ST_WK % NSLOT : (ps == 1 ? ST_WV % NSLOT : ST_WQ % NSLOT)) * SLOT);
        float acc[32];
        bar_sync(4 + wg, 256);
#pragma unroll
        for (int i = 0; i < 3; i++) {
          mbar_wait(sb + SM_FULL + (st0 + i) * 8);
          wg_fence();
#pragma unroll
          for (int kk = 0; kk < (i < 2 ? 12 : 8); kk++)
            wgmma_rs_n64(acc, A[12 * i + kk], wdesc + ((i * SLOT + kk * 2048) >> 4), (i | kk) != 0);
          wg_commit();
          if (i == 1) { wg_wait<1>(); if (lead) release(st0); }
        }
        if (ps == 1 && wg == 0) bar_arrive(5, 256);
        uint32_t a[4][4], b[4][4];
        mbar_wait(sb + SM_MISCB);
        T = (*reinterpret_cast<volatile unsigned*>(smem + SM_EPOCH) & 1) ^ 1;
#pragma unroll
        for (int h = 0; h < 4; h++) ldsm4t(b[h], wpa + h * 512);
        wg_wait<0>();
        if ((tid & 127) < 2) release(st0 + 1 + (tid & 1));
        if (ps == 2) {
          const uint32_t* xp = reinterpret_cast<const uint32_t*>(x + (size_t)(rb * 128 + warp * 16 + g) * 512 + hg * 64 + 2 * t);
#pragma unroll
          for (int i = 0; i < 8; i++) { A[8 + (i >> 1)][(i & 1) * 2] = __ldg(xp + 4 * i); A[8 + (i >> 1)][(i & 1) * 2 + 1] = __ldg(xp + 8 * 256 + 4 * i); }
        }
#pragma unroll
        for (int h = 0; h < 4; h++) {
          a[h][0] = pack2(acc[8 * h + 0] * r0, acc[8 * h + 1] * r0); a[h][1] = pack2(acc[8 * h + 2] * r1, acc[8 * h + 3] * r1);
          a[h][2] = pack2(acc[8 * h + 4] * r0, acc[8 * h + 5] * r0); a[h][3] = pack2(acc[8 * h + 6] * r1, acc[8 * h + 7] * r1);
        }
        if (ps != 1) {
          {
            float pp[4][2][4];
#pragma unroll
            for (int h = 0; h < 4; h++) {
#pragma unroll
              for (int i = 0; i < 4; i++) { pp[h][0][i] = 0.f; pp[h][1][i] = 0.f; }
              mma16816(pp[h][0], a[h], b[h][0], b[h][1]);
              mma16816(pp[h][1], a[h], b[h][2], b[h][3]);
            }
#pragma unroll
            for (int h = 0; h < 4; h++) {
              a[h][0] = pack2(pp[h][0][0], pp[h][0][1]); a[h][1] = pack2(pp[h][0][2], pp[h][0][3]);
              a[h][2] = pack2(pp[h][1][0], pp[h][1][1]); a[h][3] = pack2(pp[h][1][2], pp[h][1][3]);
            }
          }
          if (ps == 0 || wg == 0) bar_arrive(4 + (wg ^ 1), 256);
          if (ps == 0) mbar_wait(sb + SM_EMPTY + (wg ? ST_SCR1 - NSLOT : ST_SCR0 - NSLOT) * 8);
          {
            float e[4][16];
#pragma unroll
            for (int h = 0; h < 4; h++) feat_exp(a[h], e[h]);
            if (ps == 0) {
#pragma unroll
              for (int h = 0; h < 4; h++) {
                const float (&f)[16] = e[h];
                float sp0 = (f[0] + f[1]) + (f[4] + f[5]), sp1 = (f[2] + f[3]) + (f[6] + f[7]);
                float sn0 = (f[8] + f[9]) + (f[12] + f[13]), sn1 = (f[10] + f[11]) + (f[14] + f[15]);
                sp0 += __shfl_xor_sync(0xffffffffu, sp0, 1); sp1 += __shfl_xor_sync(0xffffffffu, sp1, 1);
                sn0 += __shfl_xor_sync(0xffffffffu, sn0, 1); sn1 += __shfl_xor_sync(0xffffffffu, sn1, 1);
                sp0 += __shfl_xor_sync(0xffffffffu, sp0, 2); sp1 += __shfl_xor_sync(0xffffffffu, sp1, 2);
                sn0 += __shfl_xor_sync(0xffffffffu, sn0, 2); sn1 += __shfl_xor_sync(0xffffffffu, sn1, 2);
                sp0 = rcp(sp0); sp1 = rcp(sp1); sn0 = rcp(sn0); sn1 = rcp(sn1);
                const uint32_t dst = scr + (h >> 1) * 8192 + lrow;
                stsm4(dst + ((((h & 1) * 4 + lhi) ^ lx) << 4), pack2(f[0] * sp0, f[1] * sp0), pack2(f[2] * sp1, f[3] * sp1),
                      pack2(f[4] * sp0, f[5] * sp0), pack2(f[6] * sp1, f[7] * sp1));
                stsm4(dst + ((((h & 1) * 4 + 2 + lhi) ^ lx) << 4), pack2(f[8] * sn0, f[9] * sn0), pack2(f[10] * sn1, f[11] * sn1),
                      pack2(f[12] * sn0, f[13] * sn0), pack2(f[14] * sn1, f[15] * sn1));
              }
            } else {
#pragma unroll
              for (int i = 0; i < 32; i++) A[i >> 2][i & 3] = pack2(e[i >> 3][2 * (i & 7)], e[i >> 3][2 * (i & 7) + 1]);
            }
          }
        } else {
#pragma unroll
          for (int h = 0; h < 4; h++) stsm4(scr + 16384 + lrow + (((2 * h + lhi) ^ lx) << 4), a[h][0], a[h][1], a[h][2], a[h][3]);
          fence_async_smem();
          if (wg == 0) {
            bar_arrive(3, 256);
          } else {
            bar_sync(3, 256);
            float kv[2][36];
            wg_fence();
#pragma unroll
            for (int ks = 0; ks < 8; ks++) {
              const uint32_t sk = (ks < 4 ? (ST_SCR0 % NSLOT) : (ST_SCR1 % NSLOT)) * SLOT + (ks & 3) * 2048;
              const uint32_t dv = (DESC(sk + 16384) & 0xFFFFu) | (((SM_ONES - sk - 16384) >> 4) << 16);
              wgmma_ss_n72_t11(kv[0], DESC(sk), dv, ks != 0);
              wgmma_ss_n72_t11(kv[1], DESC(sk + 8192), dv, ks != 0);
            }
            wg_commit();
            bar_arrive(4, 256);
            wg_wait<0>();
            if (lead) { mbar_arrive(sb + SM_EMPTY + ST_SCR0 * 8); mbar_arrive(sb + SM_EMPTY + ST_SCR1 * 8); }
            const bool up = wq >= 2;
            float* kvp = reinterpret_cast<float*>(smem + 2 * SLOT) + (wq * 16 + g) * 24;
#pragma unroll
            for (int i = 0; i < 4; i++) {
              const float (&c)[36] = kv[i >> 1];
              const int r = 16 * (i >> 1) + 2 * (i & 1);
              float* p = kvp + ((i >> 1) * 64 + (i & 1) * 8) * 24;
              *reinterpret_cast<float4*>(p + 4 * t) = make_float4(up ? c[r + 8] : c[r], up ? c[r + 9] : c[r + 1], up ? c[r + 12] : c[r + 4], 1.f);
              p[16 + t + (t == 3)] = up ? c[r + 13] : c[r + 5];
            }
            kvp[((t >> 1) * 64 + (t & 1) * 8) * 24 + 21] = (t & 2) ? ((t & 1) ? kv[1][34] : kv[1][32]) : ((t & 1) ? kv[0][34] : kv[0][32]);
            fence_async_smem();
            bar_sync(6, 192);
          }
        }
      }
#pragma unroll
      for (int i = 0; i < 32; i++) E[i >> 3][i & 7] = A[i >> 2][i & 3];
#pragma unroll
      for (int i = 0; i < 16; i++) xr[i >> 2][i & 3] = A[8 + (i >> 2)][i & 3];
    }
    const int rh = 2 * rb + wg;
#define IDF ((g >> 1) == t ? ((g & 1) ? 0x3F800000u : 0x00003F80u) : 0u)
    const uint4* xb = reinterpret_cast<const uint4*>(smem + 2 * SLOT) + wq * 128 + lane;
    if (wg == 0) {
      mbar_wait(sb + SM_KVB);
      const uint4* sp = reinterpret_cast<const uint4*>(smem + 3 * SLOT) + tid * 6;
      uint32_t v[6][4];
      int it = 0;
#pragma unroll 1
      do {
#pragma unroll
        for (int i = 0; i < 6; i++)
          asm volatile("{\n.reg .b128 v;\nld.relaxed.gpu.b128 v, [%4];\nmov.b128 {%0,%1,%2,%3}, v;\n}"
                       : "=r"(v[i][0]), "=r"(v[i][1]), "=r"(v[i][2]), "=r"(v[i][3]) : "l"(sp + i) : "memory");
        sp = reinterpret_cast<const uint4*>(&g_kv[hg][tid][0]);
      } while (min(min(min(v[0][3], v[1][3]), min(v[2][3], v[3][3])), min(v[4][3], v[5][3])) != 0x41800000u && ++it < (1 << 18));
#define KVF(d) __uint_as_float((d) < 8 ? v[(d) / 2][(d) & 1] : (d) >= 15 ? v[5][((d) - 15) & 1] : ((d) & 1) ? v[4][(((d) - 9) / 2) & 3] : v[(((d) - 8) / 2) & 3][2])
      uint4* dst = reinterpret_cast<uint4*>(smem + SM_KVS + tid * 48);
      const uint32_t zz = pack2(KVF(16), 1.0f);
      dst[0] = make_uint4(pack2(KVF(0), KVF(1)), pack2(KVF(2), KVF(3)), pack2(KVF(4), KVF(5)), pack2(KVF(6), KVF(7)));
      dst[1] = make_uint4(pack2(KVF(8), KVF(9)), pack2(KVF(10), KVF(11)), pack2(KVF(12), KVF(13)), pack2(KVF(14), KVF(15)));
      dst[2] = make_uint4(zz, zz, zz, zz);
      __syncwarp();
      bar_sync(1, 128);
    }
    {
      uint4* op = &g_s[rh].o[hg][wq][0][lane];
      if (wg == 1) bar_sync(7, 256);
#pragma unroll 1
      for (int hp = 0; hp < 2; hp++) {
#pragma unroll
      for (int h = 0; h < 2; h++) {
        uint32_t b0[4], b1[4], b2[4];
        const uint32_t kb = sb + SM_KVS + ((2 * hp + h) * 32 + lane) * 48;
        ldsm4t(b0, kb); ldsm4t(b1, kb + 16); ldsm4t(b2, kb + 32);
        const uint32_t ep[4] = {E[h][0], E[h][1], E[h][2], E[h][3]}, en[4] = {E[h][4], E[h][5], E[h][6], E[h][7]};
        float np0[4] = {0, 0, 0, 0}, np1[4] = {0, 0, 0, 0}, nn0[4] = {0, 0, 0, 0}, nn1[4] = {0, 0, 0, 0}, dp[4] = {0, 0, 0, 0}, dn[4] = {0, 0, 0, 0};
        mma16816(dp, ep, b2[0], b2[1]);  mma16816(dn, en, b2[2], b2[3]);
        mma16816(np0, ep, b0[0], b0[1]); mma16816(nn0, en, b0[2], b0[3]);
        mma16816(np1, ep, b1[0], b1[1]); mma16816(nn1, en, b1[2], b1[3]);
        const float i0 = rcp(fmaf(dp[0], dn[1], fmaf(dn[0], dp[1], 1e-6f * dp[1] * dn[1])));
        const float i1 = rcp(fmaf(dp[2], dn[3], fmaf(dn[2], dp[3], 1e-6f * dp[3] * dn[3])));
        const float cp0 = dn[1] * i0, cn0 = dp[1] * i0, cp1 = dn[3] * i1, cn1 = dp[3] * i1;
        st_rlx4(op + (2 * hp + h) * 32,
                tg(pack2(fmaf(np0[0], cp0, nn0[0] * cn0), fmaf(np0[1], cp0, nn0[1] * cn0)), T),
                pack2(fmaf(np0[2], cp1, nn0[2] * cn1), fmaf(np0[3], cp1, nn0[3] * cn1)),
                pack2(fmaf(np1[0], cp0, nn1[0] * cn0), fmaf(np1[1], cp0, nn1[1] * cn0)),
                pack2(fmaf(np1[2], cp1, nn1[2] * cn1), fmaf(np1[3], cp1, nn1[3] * cn1)));
      }
#pragma unroll
        for (int i = 0; i < 8; i++) { E[0][i] = E[2][i]; E[1][i] = E[3][i]; }
      }
    }
    if (wg == 0) bar_arrive(7, 256);
    bar_arrive(10 + wg, 160);

    {
      uint32_t A[8][4][4];
      const uint4* op = &g_s[rh].o[0][wq][0][lane];
      float acc[32];
#pragma unroll
      for (int i = 0; i < 32; i++) acc[i] = 0.f;
      add_frag(acc, xr, IDF);
#pragma unroll
      for (int p = -1; p < 4; p++) {
        if (p < 3) {
          mbar_wait(sb + SM_XF + (wg * 4 + p + 1) * 8);
          get_pair(A[2 * p + 2], A[2 * p + 3], xb + (p + 1) * 1024, op + (p + 1) * 1024, T);
          if (lane == 0) mbar_arrive(sb + SM_XE + (wg * 4 + p + 1) * 8);
        }
        if (p == 0 && wg == 1) bar_sync(14, 256);
        if (p >= 0) {
          if (p != 2) mbar_wait(sb + SM_FULL + (ST_WO + (p + 1) / 2) * 8);
          wg_fence();
#pragma unroll
          for (int c = 2 * p; c < 2 * p + 2; c++)
#pragma unroll
            for (int s = 0; s < 4; s++)
              wgmma_rs_n64(acc, A[c][s], DESC(((ST_WO + c / 3) % NSLOT) * SLOT + ((c % 3) * 4 + s) * 2048), 1);
        }
      }
      wg_commit();
      if (wg == 0) bar_arrive(14, 256);
      wg_wait<0>();
      if ((tid & 127) < 3) release(ST_WO + (tid & 127));
      uint4* hp_ = &g_s[rh].h[hg][wq][0][lane];
      uint32_t hx = T;
#pragma unroll
      for (int s = 0; s < 4; s++) {
        const uint32_t h0 = pack2(acc[8 * s], acc[8 * s + 1]);
        st_rlx4(hp_ + s * 32, tg(h0, T), pack2(acc[8 * s + 2], acc[8 * s + 3]), pack2(acc[8 * s + 4], acc[8 * s + 5]), pack2(acc[8 * s + 6], acc[8 * s + 7]));
        hx |= (h0 & 1u) << (s + 1);
      }
      float s0 = 0.f, s1 = 0.f, q0 = 0.f, q1 = 0.f, q2 = 0.f, q3 = 0.f;
#pragma unroll
      for (int i = 0; i < 8; i++) {
        s0 += acc[4 * i] + acc[4 * i + 1]; s1 += acc[4 * i + 2] + acc[4 * i + 3];
        q0 = fmaf(acc[4 * i], acc[4 * i], q0); q2 = fmaf(acc[4 * i + 1], acc[4 * i + 1], q2);
        q1 = fmaf(acc[4 * i + 2], acc[4 * i + 2], q1); q3 = fmaf(acc[4 * i + 3], acc[4 * i + 3], q3);
      }
      q0 += q2; q1 += q3;
      {
        const bool up = t & 2;
        float s = (up ? s1 : s0) + __shfl_xor_sync(0xffffffffu, up ? s0 : s1, 2);
        float q = (up ? q1 : q0) + __shfl_xor_sync(0xffffffffu, up ? q0 : q1, 2);
        s += __shfl_xor_sync(0xffffffffu, s, 1);
        q += __shfl_xor_sync(0xffffffffu, q, 1);
        if (!(t & 1)) st_rlx2(&g_s[rh].st[hg][wq * 16 + g + (t >> 1) * 8], tg(__float_as_uint(s), T), __float_as_uint(q));
      }
      st_rlx1(&g_s[rh].hx[hg][wq][lane], hx);
    }
    bar_arrive(10 + wg, 160);

    const int rh3 = 2 * rb3 + wg;
    uint32_t HH[11][4], PH[11][4];
    const uint4* pp = &g_s[rh3].hh[jf ^ 1][0][wq][lane];
    {
      uint32_t A[8][4][4];
      const uint4* hp_ = &g_s[rh3].h[0][wq][0][lane];
      uint4* hhp = &g_s[rh3].hh[jf][0][wq][lane];
      const uint32_t dg = (db & 0xFFFFu) | (256u << 16);
      uint32_t m0, m1;
      mbar_wait(sb + SM_XF + ((2 + wg) * 4) * 8);
      {
        const uint2* sp = reinterpret_cast<const uint2*>(smem + SM_KV32 + wg * 4096) + 2 * t * 64 + wq * 16 + g;
        uint2 a0, a1, b0, b1;
        int it = 0;
#pragma unroll 1
        do {
          ld_rlx2(a0.x, a0.y, sp); ld_rlx2(a1.x, a1.y, sp + 64); ld_rlx2(b0.x, b0.y, sp + 8); ld_rlx2(b1.x, b1.y, sp + 72);
          sp = &g_s[rh3].st[2 * t][wq * 16 + g];
        } while (__any_sync(0xffffffffu, bad4(a0.x, a1.x, b0.x, b1.x, T)) && ++it < (1 << 18));
        float s0 = __uint_as_float(a0.x) + __uint_as_float(a1.x), q0 = __uint_as_float(a0.y) + __uint_as_float(a1.y);
        float s1 = __uint_as_float(b0.x) + __uint_as_float(b1.x), q1 = __uint_as_float(b0.y) + __uint_as_float(b1.y);
        s0 += __shfl_xor_sync(0xffffffffu, s0, 1); s1 += __shfl_xor_sync(0xffffffffu, s1, 1);
        q0 += __shfl_xor_sync(0xffffffffu, q0, 1); q1 += __shfl_xor_sync(0xffffffffu, q1, 1);
        s0 += __shfl_xor_sync(0xffffffffu, s0, 2); s1 += __shfl_xor_sync(0xffffffffu, s1, 2);
        q0 += __shfl_xor_sync(0xffffffffu, q0, 2); q1 += __shfl_xor_sync(0xffffffffu, q1, 2);
        s0 *= (1.f / 512.f); s1 *= (1.f / 512.f);
        r0 = rcp(fmaxf(q0 * (1.f / 512.f) - s0 * s0, 0.f) + 1e-5f);
        r1 = rcp(fmaxf(q1 * (1.f / 512.f) - s1 * s1, 0.f) + 1e-5f);
        m0 = pack2(s0, s0); m1 = pack2(s1, s1);
      }
#define UOFF(u) ((((ST_GU + (u) / 3) % NSLOT) * SLOT + ((u) % 3) * 8192) >> 4)
#define UNIT_PRE(u)  do { if ((u) % 3 == 0) mbar_wait(sb + SM_FULL + (ST_GU + (u) / 3) * 8); } while (0)
#define UNIT_POST(u) do { wg_commit(); if ((u) % 3 == 1 && (u) > 3) { wg_wait<2>(); if (lead) release(ST_GU + (u) / 3 - 1); } } while (0)
      float acc[64];
      const int rz = blockIdx.y;
#pragma unroll
      for (int ps = 0; ps < 2; ps++) {
        wg_fence();
#pragma unroll
        for (int k = 0; k < 16; k++) {
          const int u = 16 * ps + k, c = k >> 1;
          if (ps == 0 && (k == 0 || k == 4 || k == 8)) {
#pragma unroll
            for (int p = (k == 0 ? 0 : (k == 4 ? 1 : 3)); p < (k == 0 ? 1 : (k == 4 ? 3 : 4)); p++) {
              if (p > 0) mbar_wait(sb + SM_XF + ((2 + wg) * 4 + p) * 8);
              get_pair(A[2 * p], A[2 * p + 1], xb + p * 1024, hp_ + p * 1024, T);
              if (lane == 0) {
                if (wg == 0) mbar_arrive(sb + SM_XE + (8 + p) * 8);
                else if (p > 0) release(ST_XC + p - 1);
              }
            }
          }
          if (ps == 0 && (k & 1) == 0) {
#pragma unroll
            for (int s = 0; s < 4; s++) {
              A[c][s][0] = hsub2(A[c][s][0], m0); A[c][s][1] = hsub2(A[c][s][1], m1);
              A[c][s][2] = hsub2(A[c][s][2], m0); A[c][s][3] = hsub2(A[c][s][3], m1);
            }
            wg_fence();
          }
          UNIT_PRE(u);
          wgmma_rs_n128(acc, A[c][(k & 1) * 2], dg + UOFF(u), k != 0 ? 1 : (ps ? rz : 0));
          wgmma_rs_n128(acc, A[c][(k & 1) * 2 + 1], dg + UOFF(u) + 128, 1);
          UNIT_POST(u);
        }
        wg_wait<0>();
#pragma unroll
        for (int s = 0; s < 4; s++) {
          uint32_t (&hh)[4] = HH[4 + s];
          hh[0] = tg(pack2(acc[8 * s + 0] * acc[32 + 8 * s + 0], acc[8 * s + 1] * acc[32 + 8 * s + 1]), T);
          hh[1] = pack2(acc[8 * s + 2] * acc[32 + 8 * s + 2], acc[8 * s + 3] * acc[32 + 8 * s + 3]);
          hh[2] = pack2(acc[8 * s + 4] * acc[32 + 8 * s + 4], acc[8 * s + 5] * acc[32 + 8 * s + 5]);
          hh[3] = pack2(acc[8 * s + 6] * acc[32 + 8 * s + 6], acc[8 * s + 7] * acc[32 + 8 * s + 7]);
          st_rlx4(hhp + (4 * ps + s) * 128, hh[0], hh[1], hh[2], hh[3]);
        }
      }
      {
        float ag[24], au[24];
        const uint32_t* ph7 = reinterpret_cast<const uint32_t*>(&g_s[rh3].hh[jf ^ 1][7][wq][31]);
        uint32_t hv = 0;
        bar_sync(1 + wg, 128);
        wg_fence();
#pragma unroll
        for (int k = 0; k < 16; k++) {
          const int u = 32 + k, c = k >> 1;
          if (k == 6) {
#pragma unroll
            for (int s = 0; s < 4; s++) ld_rlx4(HH[s], hhp + s * 128);
          }
          if (k == 9) hv = ld_rlx1(ph7);
          if (k == 12) {
            int it = 0;
#pragma unroll 1
            while (((hv ^ T) & 1) && ++it < (1 << 18)) hv = ld_rlx1(ph7);
#pragma unroll
            for (int s = 0; s < 8; s++) ld_rlx4(PH[s], pp + s * 128);
          }
          UNIT_PRE(u);
          wgmma_rs_n48(ag, A[c][(k & 1) * 2], dg + UOFF(u), k != 0);
          wgmma_rs_n48(au, A[c][(k & 1) * 2], dg + UOFF(u) + 256, k != 0);
          wgmma_rs_n48(ag, A[c][(k & 1) * 2 + 1], dg + UOFF(u) + 128, 1);
          wgmma_rs_n48(au, A[c][(k & 1) * 2 + 1], dg + UOFF(u) + 256 + 128, 1);
          UNIT_POST(u);
        }
        wg_wait<0>();
#pragma unroll
        for (int s = 0; s < 3; s++) {
          uint32_t (&hh)[4] = HH[8 + s];
          hh[0] = tg(pack2(ag[8 * s + 0] * au[8 * s + 0], ag[8 * s + 1] * au[8 * s + 1]), T);
          hh[1] = pack2(ag[8 * s + 2] * au[8 * s + 2], ag[8 * s + 3] * au[8 * s + 3]);
          hh[2] = pack2(ag[8 * s + 4] * au[8 * s + 4], ag[8 * s + 5] * au[8 * s + 5]);
          hh[3] = pack2(ag[8 * s + 6] * au[8 * s + 6], ag[8 * s + 7] * au[8 * s + 7]);
          st_rlx4(hhp + (8 + s) * 128, hh[0], hh[1], hh[2], hh[3]);
        }
      }
    }

    {
      float acc[32];
      uint32_t hr[4][4], hx = 0;
      const int m = jf >> 1, oc = (jf & 1) * 4 + m;
      const uint32_t* ph10 = reinterpret_cast<const uint32_t*>(&g_s[rh3].hh[jf ^ 1][10][wq][31]);
      uint4* outb = &g_s[rh3].part[(jf & 1) * 4][m][wq][0][lane];
      bar_arrive(8 + wg, 256);
      int s0 = ST_D % NSLOT;
#pragma unroll 1
      for (int k = 0; k < 4; k++) {
        const int s1 = s0 + 1 == NSLOT ? 0 : s0 + 1;
        const uint32_t d0 = db + s0 * (SLOT >> 4), d1 = db + s1 * (SLOT >> 4);
        wg_wait<0>();
        if (k > 0) {
          uint4* p = outb + ((m + k) & 3) * 2048;
#pragma unroll
          for (int s = 0; s < 4; s++)
            st_rlx4(p + s * 32, tg(pack2(acc[8 * s], acc[8 * s + 1]), T), pack2(acc[8 * s + 2], acc[8 * s + 3]),
                    pack2(acc[8 * s + 4], acc[8 * s + 5]), pack2(acc[8 * s + 6], acc[8 * s + 7]));
          if (k == 1) bar_arrive(12, 320);
        } else {
          int it = 0;
#pragma unroll 1
          while (__any_sync(0xffffffffu, bad4(PH[0][0], PH[1][0], PH[2][0], PH[3][0], T) | bad4(PH[4][0], PH[5][0], PH[6][0], PH[7][0], T)) && ++it < (1 << 18)) {
#pragma unroll
            for (int s = 0; s < 8; s++) ld_rlx4(PH[s], pp + s * 128);
          }
        }
        mbar_wait(sb + SM_FULL + (ST_D + 2 * k) * 8);
        mbar_wait(sb + SM_FULL + (ST_D + 2 * k + 1) * 8);
        wg_fence();
#pragma unroll
        for (int s = 0; s < 11; s++) wgmma_rs_n64(acc, HH[s], d0 + s * 128, s != 0);
#pragma unroll
        for (int s = 0; s < 8; s++) wgmma_rs_n64(acc, PH[s], d1 + s * 128, 1);
        if (k == 0) {
          int it = 0;
#pragma unroll 1
          while (((ld_rlx1(ph10) ^ T) & 1) && ++it < (1 << 18)) {}
          ld_chunk(hr, &g_s[rh3].h[oc][wq][0][lane]);
#pragma unroll 1
          do {
            hx = ld_rlx1(&g_s[rh3].hx[oc][wq][lane]);
#pragma unroll
            for (int s = 8; s < 11; s++) ld_rlx4(PH[s], pp + s * 128);
          } while (__any_sync(0xffffffffu, bad4(PH[8][0], PH[9][0], PH[10][0], hx, T)) && ++it < (1 << 18));
          wg_fence();
        }
#pragma unroll
        for (int s = 8; s < 11; s++) wgmma_rs_n64(acc, PH[s], d1 + s * 128, 1);
        wg_commit();
        s0 = s1 + 1 == NSLOT ? 0 : s1 + 1;
      }
      wg_wait<0>();
#pragma unroll 1
      for (int q = 0; q < 3; q++) {
        uint32_t in[4][4];
        const uint4* sp = reinterpret_cast<const uint4*>(smem + ((ST_D % NSLOT) + wg) * SLOT) + q * 512 + wq * 128 + lane;
        mbar_wait_p(sb + SM_XF + (wg * 4 + q) * 8, 1);
        int it = 0;
#pragma unroll 1
        do {
#pragma unroll
          for (int s = 0; s < 4; s++)
            asm volatile("{\n.reg .b128 v;\nld.relaxed.gpu.b128 v, [%4];\nmov.b128 {%0,%1,%2,%3}, v;\n}"
                         : "=r"(in[s][0]), "=r"(in[s][1]), "=r"(in[s][2]), "=r"(in[s][3]) : "l"(sp + s * 32) : "memory");
          sp = &g_s[rh3].part[oc][(m - 1 - q) & 3][wq][0][lane];
        } while (__any_sync(0xffffffffu, bad4(in[0][0], in[1][0], in[2][0], in[3][0], T)) && ++it < (1 << 18));
        add_frag(acc, in, IDF);
      }
#pragma unroll
      for (int s = 0; s < 4; s++) hr[s][0] = (hr[s][0] & 0xFFFFFFFEu) | ((hx >> (s + 1)) & 1u);
#pragma unroll
      for (int i = 0; i < 32; i++) acc[i] *= (i & 2) ? r1 : r0;
      add_frag(acc, hr, IDF);
      bar_sync(9 - wg, 256);
      const uint32_t ob = sb + ((ST_D - 1) % NSLOT) * SLOT + wg * 8192;
#pragma unroll
      for (int s = 0; s < 4; s++)
        stsm4(ob + lrow + (((2 * s + lhi) ^ lx) << 4), pack2(acc[8 * s + 0], acc[8 * s + 1]), pack2(acc[8 * s + 2], acc[8 * s + 3]),
              pack2(acc[8 * s + 4], acc[8 * s + 5]), pack2(acc[8 * s + 6], acc[8 * s + 7]));
      __syncwarp();
      {
        const int row = wq * 16 + (lane >> 3);
        __nv_bfloat16* op = out + (size_t)(rh3 * 64 + row) * 512 + oc * 64 + lx * 8;
#pragma unroll
        for (int i = 0; i < 4; i++) {
          uint4 v;
          asm volatile("ld.shared.v4.b32 {%0,%1,%2,%3}, [%4];" : "=r"(v.x), "=r"(v.y), "=r"(v.z), "=r"(v.w)
                       : "r"(ob + (row + i * 4) * 128 + ((lx ^ (((lane >> 3) + i * 4) & 7)) << 4)) : "memory");
          asm volatile("st.global.v4.b32 [%0], {%1,%2,%3,%4};" ::"l"(op + i * 2048), "r"(v.x), "r"(v.y), "r"(v.z), "r"(v.w) : "memory");
        }
      }
    }
    asm volatile("barrier.cluster.arrive.relaxed.aligned;" ::: "memory");
    asm volatile("barrier.cluster.wait.aligned;" ::: "memory");
  } else {
    asm volatile("setmaxnreg.dec.sync.aligned.u32 24;");
    if (elect_one()) {
      if (warp == 8) {
#pragma unroll
        for (int k = 0; k < 9; k++) {
          const int s = k < 3 ? k : (k < 6 ? k + 3 : k - 3);
          const uint32_t bar = sb + SM_FULL + s * 8;
          mbar_init(bar, 1);
          mbar_expect_tx(bar, SLOT);
          if (s >= 3 && s < 6) tma2d(sb + s * SLOT, &maps.w, 512 + hg * 64, (s - 3) * 192, bar);
          else tma3d(sb + s * SLOT, &maps.x, 0, rb * 128 + (s >= 6 ? 64 : 0), 3 * (s % 3), bar);
        }
      } else if (warp == 9) {
        mbar_init(sb + SM_MISCB, 2);
        mbar_init(sb + SM_KVB, 2);
        mbar_expect_tx(sb + SM_KVB, 12288);
        mbar_expect_tx(sb + SM_MISCB, 2048);
        bulk_g2s(sb + SM_WPHI, wphi + hg * 1024, 2048, sb + SM_MISCB);
      } else if (warp == 10) {
        if ((sb & 0x3FFFF) != SM_BASE) __trap();
#pragma unroll 1
        for (int i = 0; i < 16; i++) {
          mbar_init(sb + SM_XF + i * 8, 1);
          mbar_expect_tx(sb + SM_XF + i * 8, (i == 8 || i == 12) ? 20480 : 16384);
          if (i < 12) mbar_init(sb + SM_XE + i * 8, 4);
        }
      } else {
        *reinterpret_cast<volatile unsigned*>(smem + SM_EPOCH) = atomicAdd(&g_start, 1u) / NCTA;
      }
      asm volatile("fence.mbarrier_init.release.cluster;" ::: "memory");
    }
    __syncwarp();
    if (warp != 11) bar_sync(0, 352);
    asm volatile("barrier.cluster.arrive.relaxed.aligned;" ::: "memory");
    if (warp == 8) {
      asm volatile("barrier.cluster.wait.aligned;" ::: "memory");
      if (elect_one()) {
        const CUtensorMap* mg = jf == 7 ? &maps.g7 : &maps.g;
        const CUtensorMap* mu = jf == 7 ? &maps.u7 : &maps.u;
        asm volatile("prefetch.tensormap [%0];" ::"l"(&maps.wo) : "memory");
        asm volatile("prefetch.tensormap [%0];" ::"l"(mg) : "memory");
        asm volatile("prefetch.tensormap [%0];" ::"l"(mu) : "memory");
        asm volatile("prefetch.tensormap [%0];" ::"l"(&maps.d) : "memory");
#pragma unroll 1
        for (int i = ST_WV; i < ST_XC; i++) {
          if (i == ST_SCR1) continue;
          const int s = (WV_ && i >= 18) ? 37 - i : i;
          mbar_wait(sb + SM_EMPTY + (s - 9) * 8);
          const uint32_t dst = sb + (s >= 18 ? s - 18 : s - 9) * SLOT, bar = sb + SM_FULL + s * 8;
          if (s < ST_WO) tma2d(dst, &maps.w, (s < ST_WQ ? 1024 : 0) + hg * 64, (s < ST_WQ ? s - ST_WV : s - ST_WQ) * 192, bar);
          else {
            if (WV_ == 0) mbar_wait(bar - 8);
            else if (s == ST_WO) mbar_wait(bar - 8);
            else if (WV_ == 2 && s == 18) mbar_wait(sb + SM_KVB);
            tma2d(dst, &maps.wo, hg * 64, (s - ST_WO) * 192, bar);
          }
        }
        const int jc = jf == 7 ? 0 : jf;
        int slot = (ST_GU + 1 - rank) % NSLOT;
#pragma unroll 1
        for (int s = ST_GU + 1 - rank; s < NSTAGE; s += 2) {
          mbar_wait(sb + SM_EMPTY + (s - 9) * 8);
          if (s < ST_GU + 6) mbar_wait(sb + SM_XF + (s < ST_GU + 3 ? 3 : 11) * 8);
          if (s > ST_GU + 3 && s < ST_GU + 6) mbar_wait(sb + SM_FULL + (s - 1) * 8);
          const uint32_t dst = sb + slot * SLOT, bar = sb + SM_FULL + s * 8;
          if (s < ST_D) {
#pragma unroll 1
            for (int i = 0; i < 3; i++) {
              const int u = (s - ST_GU) * 3 + i;
              tma3d_mc(dst + i * 8192, mg, (u >> 4) * 64, jc, (u & 15) * 32, bar);
              tma3d_mc(dst + i * 8192 + 4096, mu, (u >> 4) * 64, jc, (u & 15) * 32, bar);
            }
          } else {
            const int i = s - ST_D;
            tma2d_mc(dst, &maps.d, ((jf & 1) * 4 + (((jf >> 1) + 1 + (i >> 1)) & 3)) * 64, (jf ^ (i & 1)) * 176, bar);
          }
          slot += 2; if (slot >= NSLOT) slot -= NSLOT;
        }
      }
      __syncwarp();
    } else {
      asm volatile("barrier.cluster.wait.aligned;" ::: "memory");
      if (warp == 11) {
#pragma unroll
        for (int i = 0; i < 4; i++)
          reinterpret_cast<uint4*>(smem + SM_ONES)[lane + 32 * i] = make_uint4(0x3F803F80u, 0x3F803F80u, 0x3F803F80u, 0x3F803F80u);
        fence_async_smem();
        __syncwarp();
        if (lane == 0) mbar_arrive(sb + SM_MISCB);
      }
      mbar_wait(sb + SM_MISCB);
      const unsigned epoch = *reinterpret_cast<volatile unsigned*>(smem + SM_EPOCH);
      const uint32_t T = (epoch & 1) ^ 1;
      if (warp == 11) {
        (&g_kv[hg][rb * 8][0])[lane] = make_float4(0.f, 0.f, 0.f, 0.f);
        if (lane < 16) (&g_kv[hg][rb * 8][0])[32 + lane] = make_float4(0.f, 0.f, 0.f, 0.f);
        __syncwarp();
        if (elect_one()) asm volatile("red.release.gpu.global.add.u32 [%0], 8;" ::"l"(&g_kvcnt[hg * 32 + 1]) : "memory");
        mbar_wait(sb + SM_FULL + (ST_WK + 2) * 8);
        if (elect_one()) {
          asm volatile("cp.async.bulk.prefetch.L2.global [%0], 4096;" ::"l"((const char*)wo + blockIdx.x * 4096) : "memory");
          asm volatile("cp.async.bulk.prefetch.L2.global [%0], 11008;" ::"l"((const char*)wg_ + blockIdx.x * 11008) : "memory");
          asm volatile("cp.async.bulk.prefetch.L2.global [%0], 11008;" ::"l"((const char*)wu_ + blockIdx.x * 11008) : "memory");
          asm volatile("cp.async.bulk.prefetch.L2.global [%0], 11008;" ::"l"((const char*)wd_ + blockIdx.x * 11008) : "memory");
          mbar_wait(sb + SM_EMPTY + ST_SCR0 * 8);
          const unsigned target = (epoch + 1) * 128;
          unsigned v, z; int it = 0;
#pragma unroll 1
          do {
            asm volatile("{\n.reg .b64 q;\nld.acquire.gpu.global.b64 q, [%2];\nmov.b64 {%0, %1}, q;\n}" : "=r"(v), "=r"(z) : "l"(&g_kvcnt[hg * 32]) : "memory");
            if (++it > (1 << 18)) break;
          } while ((int)(v - target) < 0 || (int)(z - target) < 0);
          asm volatile("fence.proxy.async.global;" ::: "memory");
          bulk_g2s(sb + 3 * SLOT, &g_kv[hg][0][0], 12288, sb + SM_KVB);
        }
        __syncwarp();
      } else {
        const int w = warp - 9;
        st_rlx4(reinterpret_cast<uint4*>(&g_s[2 * rb + w].st[hg][0]) + lane, T ^ 1, T ^ 1, T ^ 1, T ^ 1);
        if (lane < 8) st_rlx4(&g_s[2 * rb + w].o[hg][lane >> 1][3][30 + (lane & 1)], T ^ 1, T ^ 1, T ^ 1, T ^ 1);
        st_rlx4(&g_s[2 * rb3 + w].part[(jf & 1) * 4 + (lane >> 3)][jf >> 1][(lane >> 1) & 3][3][30 + (lane & 1)], T ^ 1, T ^ 1, T ^ 1, T ^ 1);
        if (lane < 16) st_rlx4(&g_s[2 * rb3 + w].hh[jf][7 + (lane >> 3) * 3][(lane >> 1) & 3][30 + (lane & 1)], T ^ 1, T ^ 1, T ^ 1, T ^ 1);
        if (w == 0) {
          mbar_wait(sb + SM_FULL + (ST_WQ + 2) * 8);
          unsigned v; int it = 0;
#pragma unroll 1
          do {
            asm volatile("ld.acquire.gpu.global.u32 %0, [%1];" : "=r"(v) : "l"(&g_kvcnt[hg * 32 + 1]) : "memory");
          } while ((int)(v - (epoch + 1) * 128) < 0 && ++it < (1 << 18));
          asm volatile("fence.proxy.async.global;" ::: "memory");
        }
        {
          mbar_wait(sb + SM_EMPTY + (ST_WV + 1) * 8);
          float* cp = reinterpret_cast<float*>(smem + 2 * SLOT) + (w * 32 + lane) * 24;
          cp[19] = 1.f; cp[64 * 24 + 19] = 1.f;
          *reinterpret_cast<float2*>(cp + 22) = make_float2(0.f, 1.f); *reinterpret_cast<float2*>(cp + 64 * 24 + 22) = make_float2(0.f, 1.f);
          fence_async_smem();
        }
        bar_sync(6, 192);
        if (w == 0 && elect_one()) {
          asm volatile("cp.reduce.async.bulk.global.shared::cta.bulk_group.add.f32 [%0], [%1], 12288;"
                       ::"l"(&g_kv[hg][0][0]), "r"(sb + 2 * SLOT) : "memory");
          asm volatile("cp.async.bulk.commit_group;" ::: "memory");
          asm volatile("cp.async.bulk.wait_group.read 0;" ::: "memory");
          asm volatile("red.relaxed.gpu.global.add.u32 [%0], 8;" ::"l"(&g_kvcnt[hg * 32]) : "memory");
          mbar_arrive(sb + SM_KVB);
        }
        __syncwarp();
        mbar_wait(sb + SM_KVB);
        if (w == 0) { mbar_wait(sb + SM_EMPTY + 11 * 8); mbar_wait(sb + SM_EMPTY + 12 * 8); mbar_wait(sb + SM_EMPTY + 13 * 8); }
#pragma unroll 1
        for (int ph = 0; ph < 2; ph++) {
          const int use = 2 * ph + w, r = ph ? 2 * rb3 + w : 2 * rb + w;
          const uint32_t* pw = ph ? reinterpret_cast<const uint32_t*>(&g_s[r].st[lane >> 2][(lane & 3) * 16 + 15])
                                  : reinterpret_cast<const uint32_t*>(&g_s[r].o[lane >> 2][lane & 3][3][31]);
          const char* src = reinterpret_cast<const char*>(ph ? &g_s[r].h[0][0][0][0] : &g_s[r].o[0][0][0][0]);
          const uint32_t bf = sb + SM_XF + use * 32, be = sb + SM_XE + (use - 1) * 32;
          bar_sync(10 + w, 160);
          int it = 0;
#pragma unroll 1
          for (bool miss = true; __any_sync(0xffffffffu, miss) && ++it < (1 << 18);) { if (miss) miss = (ld_rlx1(pw) ^ T) & 1; }
          if (elect_one()) {
            if (use > 0) mbar_wait(be);
            if (ph) bulk_g2s(sb + SM_KV32 + w * 4096, &g_s[r].st[0][0], 4096, bf);
#pragma unroll
            for (int p = 0; p < 4; p++) {
              if (p > 0 && use > 0) mbar_wait(be + p * 8);
              bulk_g2s(sb + 2 * SLOT + p * 16384, src + p * 16384, 16384, bf + p * 8);
            }
          }
          __syncwarp();
        }
        {
          const int m = jf >> 1, oc = (jf & 1) * 4 + m;
          const uint32_t* pw = reinterpret_cast<const uint32_t*>(&g_s[2 * rb3 + w].part[oc][(m - 1 - (lane >> 2)) & 3][lane & 3][3][31]);
          bar_sync(12, 320);
          bool miss = lane < 12; int it = 0;
#pragma unroll 1
          for (int q = 0; q < 3; q++) {
#pragma unroll 1
            while ((__ballot_sync(0xffffffffu, miss) >> (4 * q) & 15) && ++it < (1 << 18)) { if (miss && (lane >> 2) <= q + 1) miss = (ld_rlx1(pw) ^ T) & 1; }
            if (elect_one()) {
              const uint32_t bar = sb + SM_XF + (w * 4 + q) * 8;
              mbar_expect_tx(bar, 8192);
              bulk_g2s(sb + ((ST_D % NSLOT) + w) * SLOT + q * 8192, &g_s[2 * rb3 + w].part[oc][(m - 1 - q) & 3][0][0][0], 8192, bar);
            }
            __syncwarp();
          }
        }
      }
    }
    asm volatile("barrier.cluster.arrive.relaxed.aligned;" ::: "memory");
    asm volatile("barrier.cluster.wait.aligned;" ::: "memory");
  }
}

typedef CUresult (*EncodeFn)(CUtensorMap*, CUtensorMapDataType, cuuint32_t, void*, const cuuint64_t*, const cuuint64_t*,
                             const cuuint32_t*, const cuuint32_t*, CUtensorMapInterleave, CUtensorMapSwizzle,
                             CUtensorMapL2promotion, CUtensorMapFloatOOBfill);

void encode(EncodeFn fn, CUtensorMap* m, const void* base, int rank, const cuuint64_t* dims, const cuuint64_t* strides,
            const cuuint32_t* box) {
  cuuint32_t es[3] = {1, 1, 1};
  fn(m, CU_TENSOR_MAP_DATA_TYPE_BFLOAT16, (cuuint32_t)rank, const_cast<void*>(base), dims, strides, box, es,
     CU_TENSOR_MAP_INTERLEAVE_NONE, CU_TENSOR_MAP_SWIZZLE_128B, CU_TENSOR_MAP_L2_PROMOTION_L2_256B,
     CU_TENSOR_MAP_FLOAT_OOB_FILL_NONE);
}

}

extern "C" void kernel_launch(void* const* d_in, const int* in_sizes, int n_in, void* d_out, int out_size) {
  (void)in_sizes; (void)n_in; (void)out_size;
  const __nv_bfloat16* x    = (const __nv_bfloat16*)d_in[0];
  const __nv_bfloat16* wqkv = (const __nv_bfloat16*)d_in[1];
  const __nv_bfloat16* wphi = (const __nv_bfloat16*)d_in[2];
  const __nv_bfloat16* wo   = (const __nv_bfloat16*)d_in[3];
  const __nv_bfloat16* wg   = (const __nv_bfloat16*)d_in[5];
  const __nv_bfloat16* wu   = (const __nv_bfloat16*)d_in[6];
  const __nv_bfloat16* wd   = (const __nv_bfloat16*)d_in[7];

  static EncodeFn fn = nullptr;
  if (!fn) {
    void* p = nullptr;
    cudaDriverEntryPointQueryResult qr;
    cudaGetDriverEntryPoint("cuTensorMapEncodeTiled", &p, cudaEnableDefault, &qr);
    fn = (EncodeFn)p;
    cudaFuncSetAttribute(fused_kernel, cudaFuncAttributeMaxDynamicSharedMemorySize, SM_TOTAL);
  }
  Maps maps;
  {
    cuuint64_t d[3] = {64, 2048, 8}, s[2] = {1024, 128}; cuuint32_t b[3] = {64, 64, 3};
    encode(fn, &maps.x, x, 3, d, s, b);
  }
  {
    cuuint64_t d[2] = {1536, 512}, s[1] = {3072}; cuuint32_t b[2] = {64, 192};
    encode(fn, &maps.w, wqkv, 2, d, s, b);
  }
  {
    cuuint64_t d[2] = {512, 512}, s[1] = {1024}; cuuint32_t b[2] = {64, 192};
    encode(fn, &maps.wo, wo, 2, d, s, b);
  }
  {
    cuuint64_t d[3] = {176, 7, 512}, d7[3] = {144, 1, 512}, s[2] = {352, 2752}; cuuint32_t b[3] = {64, 1, 32};
    encode(fn, &maps.g, wg, 3, d, s, b);
    encode(fn, &maps.u, wu, 3, d, s, b);
    encode(fn, &maps.g7, wg + 1232, 3, d7, s, b);
    encode(fn, &maps.u7, wu + 1232, 3, d7, s, b);
  }
  {
    cuuint64_t d[2] = {512, 1376}, s[1] = {1024}; cuuint32_t b[2] = {64, 176};
    encode(fn, &maps.d, wd, 2, d, s, b);
  }
  fused_kernel<<<NCTA, 384, SM_TOTAL>>>(maps, x, wphi, wo, wg, wu, wd, (__nv_bfloat16*)d_out);
}
```

```cpp
#include <cuda_runtime.h>
#include <cuda_bf16.h>
#include <cuda.h>
#include <stdint.h>

#define SAFE_WAIT 0

#define WV_ 2
namespace {

constexpr int NCTA   = 128;
constexpr int SLOT   = 24576;
constexpr int NSLOT  = 9;
constexpr int NSTAGE = 47;

constexpr int ST_X0   = 0;
constexpr int ST_WK   = 3;
constexpr int ST_X1   = 6;
constexpr int ST_SCR0 = 9;
constexpr int ST_WV   = 10;
constexpr int ST_SCR1 = 13;
constexpr int ST_WQ   = 14;
constexpr int ST_WO   = 17;
constexpr int ST_XC   = 20;
constexpr int ST_GU   = 23;
constexpr int ST_D    = 39;

__host__ __device__ constexpr int st_empty_cnt(int d) {
  return ((d < 3 || (d >= 6 && d < 9) || (d >= ST_XC && d < ST_GU)) ? 4 : (d == ST_SCR0 || d == ST_SCR1) ? 1 : 2) * (d + 9 >= ST_GU ? 2 : 1);
}

constexpr uint32_t SM_BASE = 1024;
constexpr int SM_ONES = NSLOT * SLOT;
constexpr int SM_WPHI = SM_ONES + 2048;
constexpr int SM_KVS  = SM_WPHI + 2048;
constexpr int SM_KV32 = 4 * SLOT + 16384;
constexpr int SM_BAR  = SM_KVS + 6144;
constexpr int SM_FULL  = SM_BAR;
constexpr int SM_EMPTY = SM_BAR + NSTAGE * 8;
constexpr int SM_MISCB = SM_BAR + 2 * NSTAGE * 8;
constexpr int SM_KVB   = SM_MISCB + 8;
constexpr int SM_EPOCH = SM_KVB + 8;
constexpr int SM_XF    = SM_EPOCH + 8;
constexpr int SM_XE    = SM_XF + 16 * 8;
constexpr int SM_XRB   = SM_XE + 12 * 8;
constexpr int SM_TOTAL = SM_BAR + 1024;

static_assert(SM_TOTAL == 232448 && SM_XRB + 8 <= SM_TOTAL, "smem budget");

struct Maps { CUtensorMap x, xr, w, wo, g, u, g7, u7, d; };

struct Scratch {
  uint4    o[8][4][4][32];
  uint4    h[8][4][4][32];
  uint32_t hx[8][4][32];
  uint2    st[8][64];
  uint4    hh[8][11][4][32];
  uint4    part[8][4][4][4][32];
};
__device__ __align__(128) Scratch g_s[32];
__device__ __align__(128) float4 g_kv[8][128][6];
__device__ __align__(128) unsigned g_kvcnt[8 * 32];
__device__ unsigned g_start;

__device__ __forceinline__ uint32_t smem_u32(const void* p) { return (uint32_t)__cvta_generic_to_shared(p); }
__device__ __forceinline__ void mbar_init(uint32_t bar, int cnt) {
  asm volatile("mbarrier.init.shared::cta.b64 [%0], %1;" ::"r"(bar), "r"(cnt) : "memory");
}
__device__ __forceinline__ void mbar_expect_tx(uint32_t bar, uint32_t bytes) {
  asm volatile("mbarrier.arrive.expect_tx.shared::cta.b64 _, [%0], %1;" ::"r"(bar), "r"(bytes) : "memory");
}
__device__ __forceinline__ void mbar_arrive(uint32_t bar) {
  asm volatile("mbarrier.arrive.shared::cta.b64 _, [%0];" ::"r"(bar) : "memory");
}
__device__ __forceinline__ void mbar_arrive_cluster(uint32_t bar, uint32_t rank) {
  asm volatile("{\n.reg .b32 ra;\nmapa.shared::cluster.u32 ra, %0, %1;\n"
               "mbarrier.arrive.shared::cluster.b64 _, [ra];\n}" ::"r"(bar), "r"(rank) : "memory");
}
__device__ __forceinline__ void mbar_wait_p(uint32_t bar, uint32_t parity) {
  asm volatile("{\n.reg .pred p;\nW: mbarrier.try_wait.parity.shared::cta.b64 p, [%0], %1;\n@!p bra W;\n}" ::"r"(bar), "r"(parity) : "memory");
}
__device__ __forceinline__ void mbar_wait(uint32_t bar) { mbar_wait_p(bar, 0); }
__device__ __forceinline__ bool elect_one() {
  uint32_t p;
  asm volatile("{\n.reg .pred P;\nelect.sync _|P, 0xffffffff;\nselp.u32 %0, 1, 0, P;\n}" : "=r"(p));
  return p != 0;
}
__device__ __forceinline__ void bar_sync(int id, int n)   { asm volatile("bar.sync %0, %1;" ::"r"(id), "r"(n) : "memory"); }
__device__ __forceinline__ void bar_arrive(int id, int n) { asm volatile("bar.arrive %0, %1;" ::"r"(id), "r"(n) : "memory"); }
__device__ __forceinline__ void fence_async_smem() { asm volatile("fence.proxy.async.shared::cta;" ::: "memory"); }
__device__ __forceinline__ void wg_fence()  { asm volatile("wgmma.fence.sync.aligned;" ::: "memory"); }
__device__ __forceinline__ void wg_commit() { asm volatile("wgmma.commit_group.sync.aligned;" ::: "memory"); }
template <int N> __device__ __forceinline__ void wg_wait() { asm volatile("wgmma.wait_group.sync.aligned %0;" ::"n"(N) : "memory"); }
#define DESC(off) (db + ((uint32_t)(off) >> 4))
__device__ __forceinline__ void tma2d(uint32_t dst, const CUtensorMap* m, int c0, int c1, uint32_t bar) {
  asm volatile("cp.async.bulk.tensor.2d.shared::cluster.global.mbarrier::complete_tx::bytes [%0], [%1, {%3, %4}], [%2];"
               ::"r"(dst), "l"(m), "r"(bar), "r"(c0), "r"(c1) : "memory");
}
__device__ __forceinline__ void tma2d_mc(uint32_t dst, const CUtensorMap* m, int c0, int c1, uint32_t bar) {
  asm volatile("cp.async.bulk.tensor.2d.shared::cluster.global.mbarrier::complete_tx::bytes.multicast::cluster [%0], [%1, {%3, %4}], [%2], %5;"
               ::"r"(dst), "l"(m), "r"(bar), "r"(c0), "r"(c1), "h"((uint16_t)3) : "memory");
}
__device__ __forceinline__ void tma3d(uint32_t dst, const CUtensorMap* m, int c0, int c1, int c2, uint32_t bar) {
  asm volatile("cp.async.bulk.tensor.3d.shared::cluster.global.mbarrier::complete_tx::bytes [%0], [%1, {%3, %4, %5}], [%2];"
               ::"r"(dst), "l"(m), "r"(bar), "r"(c0), "r"(c1), "r"(c2) : "memory");
}
__device__ __forceinline__ void tma3d_mc(uint32_t dst, const CUtensorMap* m, int c0, int c1, int c2, uint32_t bar) {
  asm volatile("cp.async.bulk.tensor.3d.shared::cluster.global.mbarrier::complete_tx::bytes.multicast::cluster [%0], [%1, {%3, %4, %5}], [%2], %6;"
               ::"r"(dst), "l"(m), "r"(bar), "r"(c0), "r"(c1), "r"(c2), "h"((uint16_t)3) : "memory");
}
__device__ __forceinline__ void ldsm4(uint32_t (&r)[4], uint32_t addr) {
  asm volatile("ldmatrix.sync.aligned.m8n8.x4.shared.b16 {%0,%1,%2,%3}, [%4];"
               : "=r"(r[0]), "=r"(r[1]), "=r"(r[2]), "=r"(r[3]) : "r"(addr) : "memory");
}
__device__ __forceinline__ void ldsm4t(uint32_t (&r)[4], uint32_t addr) {
  asm volatile("ldmatrix.sync.aligned.m8n8.x4.trans.shared.b16 {%0,%1,%2,%3}, [%4];"
               : "=r"(r[0]), "=r"(r[1]), "=r"(r[2]), "=r"(r[3]) : "r"(addr) : "memory");
}
__device__ __forceinline__ void stsm4(uint32_t addr, uint32_t r0, uint32_t r1, uint32_t r2, uint32_t r3) {
  asm volatile("stmatrix.sync.aligned.m8n8.x4.shared.b16 [%0], {%1,%2,%3,%4};"
               ::"r"(addr), "r"(r0), "r"(r1), "r"(r2), "r"(r3) : "memory");
}
__device__ __forceinline__ void mma16816(float (&c)[4], const uint32_t (&a)[4], uint32_t b0, uint32_t b1) {
  asm volatile("mma.sync.aligned.m16n8k16.row.col.f32.bf16.bf16.f32 {%0,%1,%2,%3},{%4,%5,%6,%7},{%8,%9},{%0,%1,%2,%3};"
               : "+f"(c[0]), "+f"(c[1]), "+f"(c[2]), "+f"(c[3])
               : "r"(a[0]), "r"(a[1]), "r"(a[2]), "r"(a[3]), "r"(b0), "r"(b1));
}
__device__ __forceinline__ void add_frag(float (&c)[32], const uint32_t (&a)[4][4], uint32_t id) {
#pragma unroll
  for (int i = 0; i < 8; i++)
    asm volatile("mma.sync.aligned.m16n8k8.row.col.f32.bf16.bf16.f32 {%0,%1,%2,%3},{%4,%5},{%6},{%0,%1,%2,%3};"
                 : "+f"(c[4 * i]), "+f"(c[4 * i + 1]), "+f"(c[4 * i + 2]), "+f"(c[4 * i + 3])
                 : "r"(a[i >> 1][(i & 1) * 2]), "r"(a[i >> 1][(i & 1) * 2 + 1]), "r"(id));
}
__device__ __forceinline__ uint32_t pack2(float lo, float hi) {
  uint32_t r; asm("cvt.rn.bf16x2.f32 %0, %1, %2;" : "=r"(r) : "f"(hi), "f"(lo)); return r;
}
__device__ __forceinline__ float blo(uint32_t w) { return __uint_as_float(w << 16); }
__device__ __forceinline__ float bhi(uint32_t w) { return __uint_as_float(w & 0xFFFF0000u); }
__device__ __forceinline__ uint32_t hsub2(uint32_t a, uint32_t b) { uint32_t r; asm("sub.rn.bf16x2 %0, %1, %2;" : "=r"(r) : "r"(a), "r"(b)); return r; }
__device__ __forceinline__ uint32_t hmax2(uint32_t a, uint32_t b) { uint32_t r; asm("max.bf16x2 %0, %1, %2;" : "=r"(r) : "r"(a), "r"(b)); return r; }
__device__ __forceinline__ uint32_t hmin2(uint32_t a, uint32_t b) { uint32_t r; asm("min.bf16x2 %0, %1, %2;" : "=r"(r) : "r"(a), "r"(b)); return r; }
__device__ __forceinline__ float ex2(float x) { float r; asm("ex2.approx.ftz.f32 %0, %1;" : "=f"(r) : "f"(x)); return r; }
__device__ __forceinline__ float rcp(float x) { float r; asm("rcp.approx.ftz.f32 %0, %1;" : "=f"(r) : "f"(x)); return r; }
__device__ __forceinline__ void ld_rlx4(uint32_t (&r)[4], const uint4* p) {
  asm volatile("{\n.reg .b128 v;\nld.relaxed.gpu.global.b128 v, [%4];\nmov.b128 {%0,%1,%2,%3}, v;\n}"
               : "=r"(r[0]), "=r"(r[1]), "=r"(r[2]), "=r"(r[3]) : "l"(p) : "memory");
}
__device__ __forceinline__ void st_rlx4(uint4* p, uint32_t a, uint32_t b, uint32_t c, uint32_t d) {
  asm volatile("st.relaxed.gpu.global.v4.b32 [%0], {%1,%2,%3,%4};" ::"l"(p), "r"(a), "r"(b), "r"(c), "r"(d) : "memory");
}
__device__ __forceinline__ void st_rlx2(uint2* p, uint32_t a, uint32_t b) {
  asm volatile("{\n.reg .b64 v;\nmov.b64 v, {%1,%2};\nst.relaxed.gpu.global.b64 [%0], v;\n}" ::"l"(p), "r"(a), "r"(b) : "memory");
}
__device__ __forceinline__ uint32_t ld_rlx1(const uint32_t* p) {
  uint32_t r; asm volatile("ld.relaxed.gpu.global.b32 %0, [%1];" : "=r"(r) : "l"(p) : "memory"); return r;
}
__device__ __forceinline__ void st_rlx1(uint32_t* p, uint32_t a) {
  asm volatile("st.relaxed.gpu.global.b32 [%0], %1;" ::"l"(p), "r"(a) : "memory");
}
__device__ __forceinline__ void ld_rlx2(uint32_t& a, uint32_t& b, const uint2* p) {
  asm volatile("{\n.reg .b64 v;\nld.relaxed.gpu.b64 v, [%2];\nmov.b64 {%0,%1}, v;\n}" : "=r"(a), "=r"(b) : "l"(p) : "memory");
}
__device__ __forceinline__ void bulk_g2s(uint32_t dst, const void* src, uint32_t bytes, uint32_t bar) {
  asm volatile("cp.async.bulk.shared::cluster.global.mbarrier::complete_tx::bytes [%0], [%1], %2, [%3];"
               ::"r"(dst), "l"(src), "r"(bytes), "r"(bar) : "memory");
}
__device__ __forceinline__ uint32_t tg(uint32_t w, uint32_t T) { return (w & 0xFFFFFFFEu) | T; }
__device__ __forceinline__ uint32_t bad4(uint32_t a, uint32_t b, uint32_t c, uint32_t d, uint32_t T) {
  uint32_t u, v;
  asm("lop3.b32 %0, %1, %2, %3, 0x7E;" : "=r"(u) : "r"(a), "r"(b), "r"(T));
  asm("lop3.b32 %0, %1, %2, %3, 0x7E;" : "=r"(v) : "r"(c), "r"(d), "r"(T));
  asm("lop3.b32 %0, %1, %2, 1, 0xA8;" : "=r"(u) : "r"(u), "r"(v));
  return u;
}

__device__ __forceinline__ void ld_chunk(uint32_t (&a)[4][4], const uint4* p) {
#pragma unroll
  for (int s = 0; s < 4; s++) ld_rlx4(a[s], p + s * 32);
}
__device__ __forceinline__ void get_pair(uint32_t (&a)[4][4], uint32_t (&b)[4][4], const uint4* sp, const uint4* gp, uint32_t T) {
  int it = 0;
#pragma unroll 1
  do {
#pragma unroll
    for (int s = 0; s < 8; s++) {
      uint32_t (&r)[4] = s < 4 ? a[s & 3] : b[s & 3];
      asm volatile("{\n.reg .b128 v;\nld.relaxed.gpu.b128 v, [%4];\nmov.b128 {%0,%1,%2,%3}, v;\n}"
                   : "=r"(r[0]), "=r"(r[1]), "=r"(r[2]), "=r"(r[3]) : "l"(sp + (s >> 2) * 512 + (s & 3) * 32) : "memory");
    }
    sp = gp;
  } while (__any_sync(0xffffffffu, bad4(a[0][0], a[1][0], a[2][0], a[3][0], T) | bad4(b[0][0], b[1][0], b[2][0], b[3][0], T)) && ++it < (1 << 18));
}

__device__ __forceinline__ void wgmma_rs_n48(float (&d)[24], const uint32_t (&a)[4], uint32_t descB, int scaleD) {
  asm volatile("{\n.reg .pred p;\n.reg .b64 db;\nsetp.ne.b32 p, %29, 0;\nmov.b64 db, {%28, 0x40000040};\n"
    "wgmma.mma_async.sync.aligned.m64n48k16.f32.bf16.bf16 {%0,%1,%2,%3,%4,%5,%6,%7,%8,%9,%10,%11,%12,%13,%14,%15,%16,%17,%18,%19,%20,%21,%22,%23}, {%24,%25,%26,%27}, db, p, 1, 1, 1;\n}\n"
    : "+f"(d[0]),"+f"(d[1]),"+f"(d[2]),"+f"(d[3]),"+f"(d[4]),"+f"(d[5]),"+f"(d[6]),"+f"(d[7]),"+f"(d[8]),"+f"(d[9]),"+f"(d[10]),"+f"(d[11]),"+f"(d[12]),"+f"(d[13]),"+f"(d[14]),"+f"(d[15]),"+f"(d[16]),"+f"(d[17]),"+f"(d[18]),"+f"(d[19]),"+f"(d[20]),"+f"(d[21]),"+f"(d[22]),"+f"(d[23])
    : "r"(a[0]), "r"(a[1]), "r"(a[2]), "r"(a[3]), "r"(descB), "r"(scaleD));
}
__device__ __forceinline__ void wgmma_rs_n64(float (&d)[32], const uint32_t (&a)[4], uint32_t descB, int scaleD) {
  asm volatile("{\n.reg .pred p;\n.reg .b64 db;\nsetp.ne.b32 p, %37, 0;\nmov.b64 db, {%36, 0x40000040};\n"
    "wgmma.mma_async.sync.aligned.m64n64k16.f32.bf16.bf16 {%0,%1,%2,%3,%4,%5,%6,%7,%8,%9,%10,%11,%12,%13,%14,%15,%16,%17,%18,%19,%20,%21,%22,%23,%24,%25,%26,%27,%28,%29,%30,%31}, {%32,%33,%34,%35}, db, p, 1, 1, 1;\n}\n"
    : "+f"(d[0]),"+f"(d[1]),"+f"(d[2]),"+f"(d[3]),"+f"(d[4]),"+f"(d[5]),"+f"(d[6]),"+f"(d[7]),"+f"(d[8]),"+f"(d[9]),"+f"(d[10]),"+f"(d[11]),"+f"(d[12]),"+f"(d[13]),"+f"(d[14]),"+f"(d[15]),"+f"(d[16]),"+f"(d[17]),"+f"(d[18]),"+f"(d[19]),"+f"(d[20]),"+f"(d[21]),"+f"(d[22]),"+f"(d[23]),"+f"(d[24]),"+f"(d[25]),"+f"(d[26]),"+f"(d[27]),"+f"(d[28]),"+f"(d[29]),"+f"(d[30]),"+f"(d[31])
    : "r"(a[0]), "r"(a[1]), "r"(a[2]), "r"(a[3]), "r"(descB), "r"(scaleD));
}
__device__ __forceinline__ void wgmma_rs_n128(float (&d)[64], const uint32_t (&a)[4], uint32_t descB, int scaleD) {
  asm volatile("{\n.reg .pred p;\n.reg .b64 db;\nsetp.ne.b32 p, %69, 0;\nmov.b64 db, {%68, 0x40000040};\n"
    "wgmma.mma_async.sync.aligned.m64n128k16.f32.bf16.bf16 {%0,%1,%2,%3,%4,%5,%6,%7,%8,%9,%10,%11,%12,%13,%14,%15,%16,%17,%18,%19,%20,%21,%22,%23,%24,%25,%26,%27,%28,%29,%30,%31,%32,%33,%34,%35,%36,%37,%38,%39,%40,%41,%42,%43,%44,%45,%46,%47,%48,%49,%50,%51,%52,%53,%54,%55,%56,%57,%58,%59,%60,%61,%62,%63}, {%64,%65,%66,%67}, db, p, 1, 1, 1;\n}\n"
    : "+f"(d[0]),"+f"(d[1]),"+f"(d[2]),"+f"(d[3]),"+f"(d[4]),"+f"(d[5]),"+f"(d[6]),"+f"(d[7]),"+f"(d[8]),"+f"(d[9]),"+f"(d[10]),"+f"(d[11]),"+f"(d[12]),"+f"(d[13]),"+f"(d[14]),"+f"(d[15]),"+f"(d[16]),"+f"(d[17]),"+f"(d[18]),"+f"(d[19]),"+f"(d[20]),"+f"(d[21]),"+f"(d[22]),"+f"(d[23]),"+f"(d[24]),"+f"(d[25]),"+f"(d[26]),"+f"(d[27]),"+f"(d[28]),"+f"(d[29]),"+f"(d[30]),"+f"(d[31]),"+f"(d[32]),"+f"(d[33]),"+f"(d[34]),"+f"(d[35]),"+f"(d[36]),"+f"(d[37]),"+f"(d[38]),"+f"(d[39]),"+f"(d[40]),"+f"(d[41]),"+f"(d[42]),"+f"(d[43]),"+f"(d[44]),"+f"(d[45]),"+f"(d[46]),"+f"(d[47]),"+f"(d[48]),"+f"(d[49]),"+f"(d[50]),"+f"(d[51]),"+f"(d[52]),"+f"(d[53]),"+f"(d[54]),"+f"(d[55]),"+f"(d[56]),"+f"(d[57]),"+f"(d[58]),"+f"(d[59]),"+f"(d[60]),"+f"(d[61]),"+f"(d[62]),"+f"(d[63])
    : "r"(a[0]), "r"(a[1]), "r"(a[2]), "r"(a[3]), "r"(descB), "r"(scaleD));
}
__device__ __forceinline__ void wgmma_ss_n72_t11(float (&d)[36], uint32_t descA, uint32_t descB, int scaleD) {
  asm volatile("{\n.reg .pred p;\n.reg .b64 da, db;\nsetp.ne.b32 p, %38, 0;\nmov.b64 da, {%36, 0x40000040};\nmov.b64 db, {%37, 0x40000040};\n"
    "wgmma.mma_async.sync.aligned.m64n72k16.f32.bf16.bf16 {%0,%1,%2,%3,%4,%5,%6,%7,%8,%9,%10,%11,%12,%13,%14,%15,%16,%17,%18,%19,%20,%21,%22,%23,%24,%25,%26,%27,%28,%29,%30,%31,%32,%33,%34,%35}, da, db, p, 1, 1, 1, 1;\n}\n"
    : "+f"(d[0]),"+f"(d[1]),"+f"(d[2]),"+f"(d[3]),"+f"(d[4]),"+f"(d[5]),"+f"(d[6]),"+f"(d[7]),"+f"(d[8]),"+f"(d[9]),"+f"(d[10]),"+f"(d[11]),"+f"(d[12]),"+f"(d[13]),"+f"(d[14]),"+f"(d[15]),"+f"(d[16]),"+f"(d[17]),"+f"(d[18]),"+f"(d[19]),"+f"(d[20]),"+f"(d[21]),"+f"(d[22]),"+f"(d[23]),"+f"(d[24]),"+f"(d[25]),"+f"(d[26]),"+f"(d[27]),"+f"(d[28]),"+f"(d[29]),"+f"(d[30]),"+f"(d[31]),"+f"(d[32]),"+f"(d[33]),"+f"(d[34]),"+f"(d[35])
    : "r"(descA), "r"(descB), "r"(scaleD));
}

constexpr float LOG2E = 1.4426950408889634f;

__device__ __forceinline__ void feat_exp(const uint32_t (&P)[4], float (&e)[16]) {
  uint32_t a = hmax2(P[0], P[2]), b = hmax2(P[1], P[3]);
  uint32_t mx = hmax2(__byte_perm(a, b, 0x5410), __byte_perm(a, b, 0x7632));
  a = hmin2(P[0], P[2]); b = hmin2(P[1], P[3]);
  uint32_t mn = hmin2(__byte_perm(a, b, 0x5410), __byte_perm(a, b, 0x7632));
  mx = hmax2(mx, __shfl_xor_sync(0xffffffffu, mx, 1));
  mn = hmin2(mn, __shfl_xor_sync(0xffffffffu, mn, 1));
  mx = hmax2(mx, __shfl_xor_sync(0xffffffffu, mx, 2));
  mn = hmin2(mn, __shfl_xor_sync(0xffffffffu, mn, 2));
  float mx0 = -blo(mx) * LOG2E, mx1 = -bhi(mx) * LOG2E, mn0 = blo(mn) * LOG2E, mn1 = bhi(mn) * LOG2E;
  float v[8] = {blo(P[0]), bhi(P[0]), blo(P[1]), bhi(P[1]), blo(P[2]), bhi(P[2]), blo(P[3]), bhi(P[3])};
#pragma unroll
  for (int i = 0; i < 8; i++) {
    bool r1 = (i >> 1) & 1;
    e[i]     = ex2(fmaf(v[i],  LOG2E, r1 ? mx1 : mx0));
    e[8 + i] = ex2(fmaf(v[i], -LOG2E, r1 ? mn1 : mn0));
  }
}

__global__ void __cluster_dims__(2, 1, 1) __launch_bounds__(384, 1)
fused_kernel(const __grid_constant__ Maps maps, const __nv_bfloat16* __restrict__ wphi,
             const __nv_bfloat16* __restrict__ wo, const __nv_bfloat16* __restrict__ wg_, const __nv_bfloat16* __restrict__ wu_,
             const __nv_bfloat16* __restrict__ wd_, __nv_bfloat16* __restrict__ out) {
  extern __shared__ __align__(1024) unsigned char smem[];
  const uint32_t sb = smem_u32(smem);
  const int tid = threadIdx.x, lane = tid & 31;
  const int warp = __shfl_sync(0xffffffffu, tid >> 5, 0);
  const uint32_t rank = blockIdx.x & 1;
  const int cl = blockIdx.x >> 1;
  int quad, qi;
  if (cl < 4) { quad = 15; qi = cl; }
  else if (cl < 36) { quad = (cl - 4) & 7; qi = (cl - 4) >> 3; }
  else { qi = (cl - 36) / 7; quad = 8 + (cl - 36) - 7 * qi; }
  const int rb = quad, hg = 2 * qi + rank;
  const int rb3 = (quad & ~1) + rank, jf = 4 * (quad & 1) + qi;

  if (warp < 8) {
    asm volatile("setmaxnreg.inc.sync.aligned.u32 240;");
    if (elect_one()) {
#pragma unroll 1
      for (int d = warp; d + 9 < NSTAGE; d += 8) {
        mbar_init(sb + SM_EMPTY + d * 8, st_empty_cnt(d));
        mbar_init(sb + SM_FULL + (d + 9) * 8, 1);
        mbar_expect_tx(sb + SM_FULL + (d + 9) * 8, d + 9 >= ST_D ? 22528 : SLOT);
      }
      asm volatile("fence.mbarrier_init.release.cluster;" ::: "memory");
    }
    __syncwarp();
    bar_sync(0, 352);
    asm volatile("barrier.cluster.arrive.relaxed.aligned;" ::: "memory");
    const int wg = warp >> 2, wq = warp & 3, g = lane >> 2, t = lane & 3;
    const bool lead = (tid & 127) == 0;
    constexpr uint32_t db = (SM_BASE >> 4) | (512u << 16);
    auto release = [&](int d) {
      const int s = d + NSLOT;
      mbar_arrive_cluster(sb + SM_EMPTY + d * 8, s >= ST_GU ? (uint32_t)(s & 1) : rank);
    };
    const uint32_t lrow = (uint32_t)(wq * 16 + (lane & 7) + ((lane >> 3) & 1) * 8) * 128;
    const uint32_t lx = lane & 7, lhi = lane >> 4;
    if (wg == 1) bar_arrive(4, 256);

    float r0, r1;
    uint32_t E[4][8];
    uint32_t xr[4][4];
    uint32_t T = 0;
    {
      uint32_t A[32][4];
      const int sx = wg ? ST_X1 : ST_X0;
      {
        const uint32_t base = sb + sx * SLOT + lrow, baseb = sb + sx * SLOT + (wq * 16 + lx + lhi * 8) * 128;
        float cs[2][4], c0[2][4], c1[2][4];
#pragma unroll
        for (int i = 0; i < 4; i++) { cs[0][i] = cs[1][i] = c0[0][i] = c0[1][i] = c1[0][i] = c1[1][i] = 0.f; }
        uint32_t bt[2][4][4];
        if (wg == 1) bar_sync(13, 256);
#pragma unroll
        for (int c = -1; c < 8; c++) {
          if (c < 7) {
            const int n = c + 1;
            if (n % 3 == 0) mbar_wait(sb + SM_FULL + (sx + n / 3) * 8);
#pragma unroll
            for (int k = 0; k < 4; k++) {
              ldsm4(A[4 * n + k], base + n * 8192 + (((2 * k + lhi) ^ lx) << 4));
              ldsm4(bt[n & 1][k], baseb + n * 8192 + (((2 * k + ((lane >> 3) & 1)) ^ lx) << 4));
            }
          }
          if (c >= 0) {
#pragma unroll
            for (int k = 0; k < 4; k++) {
              const uint32_t (&f)[4] = A[4 * c + k];
              mma16816(cs[k & 1], f, 0x3F803F80u, 0x3F803F80u);
              mma16816(c0[k & 1], f, bt[c & 1][k][0], bt[c & 1][k][1]);
              mma16816(c1[k & 1], f, bt[c & 1][k][2], bt[c & 1][k][3]);
            }
          }
        }
        if (wg == 0) bar_arrive(13, 256);
        const float s0 = (cs[0][0] + cs[1][0]) * (1.f / 512.f), s1 = (cs[0][2] + cs[1][2]) * (1.f / 512.f);
        asm volatile("barrier.cluster.wait.aligned;" ::: "memory");
        if (lane < 3) release(sx + lane);
        const uint32_t m0 = pack2(s0, s0), m1 = pack2(s1, s1);
        float q0 = (g & 1) ? c0[0][1] + c0[1][1] : c0[0][0] + c0[1][0];
        float q1 = (g & 1) ? c1[0][3] + c1[1][3] : c1[0][2] + c1[1][2];
        q0 = __shfl_sync(0xffffffffu, q0, (lane & ~3) | (g >> 1));
        q1 = __shfl_sync(0xffffffffu, q1, (lane & ~3) | (g >> 1));
        r0 = rsqrtf(fmaxf(q0 * (1.f / 512.f) - s0 * s0, 0.f) + 1e-5f);
        r1 = rsqrtf(fmaxf(q1 * (1.f / 512.f) - s1 * s1, 0.f) + 1e-5f);
#pragma unroll
        for (int ks = 0; ks < 32; ks++) {
          A[ks][0] = hsub2(A[ks][0], m0); A[ks][1] = hsub2(A[ks][1], m1);
          A[ks][2] = hsub2(A[ks][2], m0); A[ks][3] = hsub2(A[ks][3], m1);
        }
      }
      const uint32_t wpa = sb + SM_WPHI + ((lane & 7) + ((lane >> 3) & 1) * 8) * 32 + lhi * 16;
      const uint32_t scr = sb + (wg ? (ST_SCR1 % NSLOT) : (ST_SCR0 % NSLOT)) * SLOT;
#pragma unroll 1
      for (int ps = 0; ps < 3; ps++) {
        const int st0 = ps == 0 ? ST_WK : (ps == 1 ? ST_WV : ST_WQ);
        const uint32_t wdesc = DESC((ps == 0 ? ST_WK % NSLOT : (ps == 1 ? ST_WV % NSLOT : ST_WQ % NSLOT)) * SLOT);
        float acc[32];
        bar_sync(4 + wg, 256);
#pragma unroll
        for (int i = 0; i < 3; i++) {
          mbar_wait(sb + SM_FULL + (st0 + i) * 8);
          wg_fence();
#pragma unroll
          for (int kk = 0; kk < (i < 2 ? 12 : 8); kk++)
            wgmma_rs_n64(acc, A[12 * i + kk], wdesc + ((i * SLOT + kk * 2048) >> 4), (i | kk) != 0);
          wg_commit();
          if (i == 1) { wg_wait<1>(); if (lead) release(st0); }
        }
        if (ps == 1 && wg == 0) bar_arrive(5, 256);
        uint32_t a[4][4], b[4][4];
        mbar_wait(sb + SM_MISCB);
        T = (*reinterpret_cast<volatile unsigned*>(smem + SM_EPOCH) & 1) ^ 1;
#pragma unroll
        for (int h = 0; h < 4; h++) ldsm4t(b[h], wpa + h * 512);
        wg_wait<0>();
        if (ps == 2) {
          mbar_wait(sb + SM_XRB);
#pragma unroll
          for (int k = 0; k < 4; k++)
            ldsm4(A[8 + k], sb + (wg ? (ST_WQ + 2) % NSLOT : (ST_WV + 2) % NSLOT) * SLOT + 16384 + lrow + (((2 * k + lhi) ^ lx) << 4));
          bar_sync(1 + wg, 128);
        }
        if ((tid & 127) < 2) release(st0 + 1 + (tid & 1));
#pragma unroll
        for (int h = 0; h < 4; h++) {
          a[h][0] = pack2(acc[8 * h + 0] * r0, acc[8 * h + 1] * r0); a[h][1] = pack2(acc[8 * h + 2] * r1, acc[8 * h + 3] * r1);
          a[h][2] = pack2(acc[8 * h + 4] * r0, acc[8 * h + 5] * r0); a[h][3] = pack2(acc[8 * h + 6] * r1, acc[8 * h + 7] * r1);
        }
        if (ps != 1) {
          {
            float pp[4][2][4];
#pragma unroll
            for (int h = 0; h < 4; h++) {
#pragma unroll
              for (int i = 0; i < 4; i++) { pp[h][0][i] = 0.f; pp[h][1][i] = 0.f; }
              mma16816(pp[h][0], a[h], b[h][0], b[h][1]);
              mma16816(pp[h][1], a[h], b[h][2], b[h][3]);
            }
#pragma unroll
            for (int h = 0; h < 4; h++) {
              a[h][0] = pack2(pp[h][0][0], pp[h][0][1]); a[h][1] = pack2(pp[h][0][2], pp[h][0][3]);
              a[h][2] = pack2(pp[h][1][0], pp[h][1][1]); a[h][3] = pack2(pp[h][1][2], pp[h][1][3]);
            }
          }
          if (ps == 0 || wg == 0) bar_arrive(4 + (wg ^ 1), 256);
          if (ps == 0) mbar_wait(sb + SM_EMPTY + (wg ? ST_SCR1 - NSLOT : ST_SCR0 - NSLOT) * 8);
          {
            float e[4][16];
#pragma unroll
            for (int h = 0; h < 4; h++) feat_exp(a[h], e[h]);
            if (ps == 0) {
#pragma unroll
              for (int h = 0; h < 4; h++) {
                const float (&f)[16] = e[h];
                float sp0 = (f[0] + f[1]) + (f[4] + f[5]), sp1 = (f[2] + f[3]) + (f[6] + f[7]);
                float sn0 = (f[8] + f[9]) + (f[12] + f[13]), sn1 = (f[10] + f[11]) + (f[14] + f[15]);
                sp0 += __shfl_xor_sync(0xffffffffu, sp0, 1); sp1 += __shfl_xor_sync(0xffffffffu, sp1, 1);
                sn0 += __shfl_xor_sync(0xffffffffu, sn0, 1); sn1 += __shfl_xor_sync(0xffffffffu, sn1, 1);
                sp0 += __shfl_xor_sync(0xffffffffu, sp0, 2); sp1 += __shfl_xor_sync(0xffffffffu, sp1, 2);
                sn0 += __shfl_xor_sync(0xffffffffu, sn0, 2); sn1 += __shfl_xor_sync(0xffffffffu, sn1, 2);
                sp0 = rcp(sp0); sp1 = rcp(sp1); sn0 = rcp(sn0); sn1 = rcp(sn1);
                const uint32_t dst = scr + (h >> 1) * 8192 + lrow;
                stsm4(dst + ((((h & 1) * 4 + lhi) ^ lx) << 4), pack2(f[0] * sp0, f[1] * sp0), pack2(f[2] * sp1, f[3] * sp1),
                      pack2(f[4] * sp0, f[5] * sp0), pack2(f[6] * sp1, f[7] * sp1));
                stsm4(dst + ((((h & 1) * 4 + 2 + lhi) ^ lx) << 4), pack2(f[8] * sn0, f[9] * sn0), pack2(f[10] * sn1, f[11] * sn1),
                      pack2(f[12] * sn0, f[13] * sn0), pack2(f[14] * sn1, f[15] * sn1));
              }
            } else {
#pragma unroll
              for (int i = 0; i < 32; i++) A[i >> 2][i & 3] = pack2(e[i >> 3][2 * (i & 7)], e[i >> 3][2 * (i & 7) + 1]);
            }
          }
        } else {
#pragma unroll
          for (int h = 0; h < 4; h++) stsm4(scr + 16384 + lrow + (((2 * h + lhi) ^ lx) << 4), a[h][0], a[h][1], a[h][2], a[h][3]);
          fence_async_smem();
          if (wg == 0) {
            bar_arrive(3, 256);
          } else {
            bar_sync(3, 256);
            float kv[2][36];
            wg_fence();
#pragma unroll
            for (int ks = 0; ks < 8; ks++) {
              const uint32_t sk = (ks < 4 ? (ST_SCR0 % NSLOT) : (ST_SCR1 % NSLOT)) * SLOT + (ks & 3) * 2048;
              const uint32_t dv = (DESC(sk + 16384) & 0xFFFFu) | (((SM_ONES - sk - 16384) >> 4) << 16);
              wgmma_ss_n72_t11(kv[0], DESC(sk), dv, ks != 0);
              wgmma_ss_n72_t11(kv[1], DESC(sk + 8192), dv, ks != 0);
            }
            wg_commit();
            bar_arrive(4, 256);
            wg_wait<0>();
            if (lead) { mbar_arrive(sb + SM_EMPTY + ST_SCR0 * 8); mbar_arrive(sb + SM_EMPTY + ST_SCR1 * 8); }
            const bool up = wq >= 2;
            float* kvp = reinterpret_cast<float*>(smem + 2 * SLOT) + (wq * 16 + g) * 24;
#pragma unroll
            for (int i = 0; i < 4; i++) {
              const float (&c)[36] = kv[i >> 1];
              const int r = 16 * (i >> 1) + 2 * (i & 1);
              float* p = kvp + ((i >> 1) * 64 + (i & 1) * 8) * 24;
              *reinterpret_cast<float4*>(p + 4 * t) = make_float4(up ? c[r + 8] : c[r], up ? c[r + 9] : c[r + 1], up ? c[r + 12] : c[r + 4], 1.f);
              p[16 + t + (t == 3)] = up ? c[r + 13] : c[r + 5];
            }
            kvp[((t >> 1) * 64 + (t & 1) * 8) * 24 + 21] = (t & 2) ? ((t & 1) ? kv[1][34] : kv[1][32]) : ((t & 1) ? kv[0][34] : kv[0][32]);
            fence_async_smem();
            bar_sync(6, 192);
          }
        }
      }
#pragma unroll
      for (int i = 0; i < 32; i++) E[i >> 3][i & 7] = A[i >> 2][i & 3];
#pragma unroll
      for (int i = 0; i < 16; i++) xr[i >> 2][i & 3] = A[8 + (i >> 2)][i & 3];
    }
    const int rh = 2 * rb + wg;
#define IDF ((g >> 1) == t ? ((g & 1) ? 0x3F800000u : 0x00003F80u) : 0u)
    const uint4* xb = reinterpret_cast<const uint4*>(smem + 2 * SLOT) + wq * 128 + lane;
    if (wg == 0) {
      mbar_wait(sb + SM_KVB);
      const uint4* sp = reinterpret_cast<const uint4*>(smem + 3 * SLOT) + tid * 6;
      uint32_t v[6][4];
      int it = 0;
#pragma unroll 1
      do {
#pragma unroll
        for (int i = 0; i < 6; i++)
          asm volatile("{\n.reg .b128 v;\nld.relaxed.gpu.b128 v, [%4];\nmov.b128 {%0,%1,%2,%3}, v;\n}"
                       : "=r"(v[i][0]), "=r"(v[i][1]), "=r"(v[i][2]), "=r"(v[i][3]) : "l"(sp + i) : "memory");
        sp = reinterpret_cast<const uint4*>(&g_kv[hg][tid][0]);
      } while (min(min(min(v[0][3], v[1][3]), min(v[2][3], v[3][3])), min(v[4][3], v[5][3])) != 0x41800000u && ++it < (1 << 18));
#define KVF(d) __uint_as_float((d) < 8 ? v[(d) / 2][(d) & 1] : (d) >= 15 ? v[5][((d) - 15) & 1] : ((d) & 1) ? v[4][(((d) - 9) / 2) & 3] : v[(((d) - 8) / 2) & 3][2])
      uint4* dst = reinterpret_cast<uint4*>(smem + SM_KVS + tid * 48);
      const uint32_t zz = pack2(KVF(16), 1.0f);
      dst[0] = make_uint4(pack2(KVF(0), KVF(1)), pack2(KVF(2), KVF(3)), pack2(KVF(4), KVF(5)), pack2(KVF(6), KVF(7)));
      dst[1] = make_uint4(pack2(KVF(8), KVF(9)), pack2(KVF(10), KVF(11)), pack2(KVF(12), KVF(13)), pack2(KVF(14), KVF(15)));
      dst[2] = make_uint4(zz, zz, zz, zz);
      __syncwarp();
      bar_sync(1, 128);
    }
    {
      uint4* op = &g_s[rh].o[hg][wq][0][lane];
      if (wg == 1) bar_sync(7, 256);
#pragma unroll 1
      for (int hp = 0; hp < 2; hp++) {
#pragma unroll
      for (int h = 0; h < 2; h++) {
        uint32_t b0[4], b1[4], b2[4];
        const uint32_t kb = sb + SM_KVS + ((2 * hp + h) * 32 + lane) * 48;
        ldsm4t(b0, kb); ldsm4t(b1, kb + 16); ldsm4t(b2, kb + 32);
        const uint32_t ep[4] = {E[h][0], E[h][1], E[h][2], E[h][3]}, en[4] = {E[h][4], E[h][5], E[h][6], E[h][7]};
        float np0[4] = {0, 0, 0, 0}, np1[4] = {0, 0, 0, 0}, nn0[4] = {0, 0, 0, 0}, nn1[4] = {0, 0, 0, 0}, dp[4] = {0, 0, 0, 0}, dn[4] = {0, 0, 0, 0};
        mma16816(dp, ep, b2[0], b2[1]);  mma16816(dn, en, b2[2], b2[3]);
        mma16816(np0, ep, b0[0], b0[1]); mma16816(nn0, en, b0[2], b0[3]);
        mma16816(np1, ep, b1[0], b1[1]); mma16816(nn1, en, b1[2], b1[3]);
        const float i0 = rcp(fmaf(dp[0], dn[1], fmaf(dn[0], dp[1], 1e-6f * dp[1] * dn[1])));
        const float i1 = rcp(fmaf(dp[2], dn[3], fmaf(dn[2], dp[3], 1e-6f * dp[3] * dn[3])));
        const float cp0 = dn[1] * i0, cn0 = dp[1] * i0, cp1 = dn[3] * i1, cn1 = dp[3] * i1;
        st_rlx4(op + (2 * hp + h) * 32,
                tg(pack2(fmaf(np0[0], cp0, nn0[0] * cn0), fmaf(np0[1], cp0, nn0[1] * cn0)), T),
                pack2(fmaf(np0[2], cp1, nn0[2] * cn1), fmaf(np0[3], cp1, nn0[3] * cn1)),
                pack2(fmaf(np1[0], cp0, nn1[0] * cn0), fmaf(np1[1], cp0, nn1[1] * cn0)),
                pack2(fmaf(np1[2], cp1, nn1[2] * cn1), fmaf(np1[3], cp1, nn1[3] * cn1)));
      }
#pragma unroll
        for (int i = 0; i < 8; i++) { E[0][i] = E[2][i]; E[1][i] = E[3][i]; }
      }
    }
    if (wg == 0) bar_arrive(7, 256);
    bar_arrive(10 + wg, 160);

    {
      uint32_t A[8][4][4];
      const uint4* op = &g_s[rh].o[0][wq][0][lane];
      float acc[32];
#pragma unroll
      for (int i = 0; i < 32; i++) acc[i] = 0.f;
      add_frag(acc, xr, IDF);
#pragma unroll
      for (int p = -1; p < 4; p++) {
        if (p < 3) {
          mbar_wait(sb + SM_XF + (wg * 4 + p + 1) * 8);
          get_pair(A[2 * p + 2], A[2 * p + 3], xb + (p + 1) * 1024, op + (p + 1) * 1024, T);
          if (lane == 0) mbar_arrive(sb + SM_XE + (wg * 4 + p + 1) * 8);
        }
        if (p == 0 && wg == 1) bar_sync(14, 256);
        if (p >= 0) {
          if (p != 2) mbar_wait(sb + SM_FULL + (ST_WO + (p + 1) / 2) * 8);
          wg_fence();
#pragma unroll
          for (int c = 2 * p; c < 2 * p + 2; c++)
#pragma unroll
            for (int s = 0; s < 4; s++)
              wgmma_rs_n64(acc, A[c][s], DESC(((ST_WO + c / 3) % NSLOT) * SLOT + ((c % 3) * 4 + s) * 2048), 1);
        }
      }
      wg_commit();
      if (wg == 0) bar_arrive(14, 256);
      wg_wait<0>();
      if ((tid & 127) < 3) release(ST_WO + (tid & 127));
      uint4* hp_ = &g_s[rh].h[hg][wq][0][lane];
      uint32_t hx = T;
#pragma unroll
      for (int s = 0; s < 4; s++) {
        const uint32_t h0 = pack2(acc[8 * s], acc[8 * s + 1]);
        st_rlx4(hp_ + s * 32, tg(h0, T), pack2(acc[8 * s + 2], acc[8 * s + 3]), pack2(acc[8 * s + 4], acc[8 * s + 5]), pack2(acc[8 * s + 6], acc[8 * s + 7]));
        hx |= (h0 & 1u) << (s + 1);
      }
      float s0 = 0.f, s1 = 0.f, q0 = 0.f, q1 = 0.f, q2 = 0.f, q3 = 0.f;
#pragma unroll
      for (int i = 0; i < 8; i++) {
        s0 += acc[4 * i] + acc[4 * i + 1]; s1 += acc[4 * i + 2] + acc[4 * i + 3];
        q0 = fmaf(acc[4 * i], acc[4 * i], q0); q2 = fmaf(acc[4 * i + 1], acc[4 * i + 1], q2);
        q1 = fmaf(acc[4 * i + 2], acc[4 * i + 2], q1); q3 = fmaf(acc[4 * i + 3], acc[4 * i + 3], q3);
      }
      q0 += q2; q1 += q3;
      {
        const bool up = t & 2;
        float s = (up ? s1 : s0) + __shfl_xor_sync(0xffffffffu, up ? s0 : s1, 2);
        float q = (up ? q1 : q0) + __shfl_xor_sync(0xffffffffu, up ? q0 : q1, 2);
        s += __shfl_xor_sync(0xffffffffu, s, 1);
        q += __shfl_xor_sync(0xffffffffu, q, 1);
        if (!(t & 1)) st_rlx2(&g_s[rh].st[hg][wq * 16 + g + (t >> 1) * 8], tg(__float_as_uint(s), T), __float_as_uint(q));
      }
      st_rlx1(&g_s[rh].hx[hg][wq][lane], hx);
    }
    bar_arrive(10 + wg, 160);

    const int rh3 = 2 * rb3 + wg;
    uint32_t HH[11][4], PH[11][4];
    const uint4* pp = &g_s[rh3].hh[jf ^ 1][0][wq][lane];
    {
      uint32_t A[8][4][4];
      const uint4* hp_ = &g_s[rh3].h[0][wq][0][lane];
      uint4* hhp = &g_s[rh3].hh[jf][0][wq][lane];
      const uint32_t dg = (db & 0xFFFFu) | (256u << 16);
      uint32_t m0, m1;
      mbar_wait(sb + SM_XF + ((2 + wg) * 4) * 8);
      {
        const uint2* sp = reinterpret_cast<const uint2*>(smem + SM_KV32 + wg * 4096) + 2 * t * 64 + wq * 16 + g;
        uint2 a0, a1, b0, b1;
        int it = 0;
#pragma unroll 1
        do {
          ld_rlx2(a0.x, a0.y, sp); ld_rlx2(a1.x, a1.y, sp + 64); ld_rlx2(b0.x, b0.y, sp + 8); ld_rlx2(b1.x, b1.y, sp + 72);
          sp = &g_s[rh3].st[2 * t][wq * 16 + g];
        } while (__any_sync(0xffffffffu, bad4(a0.x, a1.x, b0.x, b1.x, T)) && ++it < (1 << 18));
        float s0 = __uint_as_float(a0.x) + __uint_as_float(a1.x), q0 = __uint_as_float(a0.y) + __uint_as_float(a1.y);
        float s1 = __uint_as_float(b0.x) + __uint_as_float(b1.x), q1 = __uint_as_float(b0.y) + __uint_as_float(b1.y);
        s0 += __shfl_xor_sync(0xffffffffu, s0, 1); s1 += __shfl_xor_sync(0xffffffffu, s1, 1);
        q0 += __shfl_xor_sync(0xffffffffu, q0, 1); q1 += __shfl_xor_sync(0xffffffffu, q1, 1);
        s0 += __shfl_xor_sync(0xffffffffu, s0, 2); s1 += __shfl_xor_sync(0xffffffffu, s1, 2);
        q0 += __shfl_xor_sync(0xffffffffu, q0, 2); q1 += __shfl_xor_sync(0xffffffffu, q1, 2);
        s0 *= (1.f / 512.f); s1 *= (1.f / 512.f);
        r0 = rcp(fmaxf(q0 * (1.f / 512.f) - s0 * s0, 0.f) + 1e-5f);
        r1 = rcp(fmaxf(q1 * (1.f / 512.f) - s1 * s1, 0.f) + 1e-5f);
        m0 = pack2(s0, s0); m1 = pack2(s1, s1);
      }
#define UOFF(u) ((((ST_GU + (u) / 3) % NSLOT) * SLOT + ((u) % 3) * 8192) >> 4)
#define UNIT_PRE(u)  do { if ((u) % 3 == 0) mbar_wait(sb + SM_FULL + (ST_GU + (u) / 3) * 8); } while (0)
#define UNIT_POST(u) do { wg_commit(); if ((u) % 3 == 1 && (u) > 3) { wg_wait<2>(); if (lead) release(ST_GU + (u) / 3 - 1); } } while (0)
      float acc[64];
      const int rz = blockIdx.y;
#pragma unroll
      for (int ps = 0; ps < 2; ps++) {
        wg_fence();
#pragma unroll
        for (int k = 0; k < 16; k++) {
          const int u = 16 * ps + k, c = k >> 1;
          if (ps == 0 && (k == 0 || k == 4 || k == 8)) {
#pragma unroll
            for (int p = (k == 0 ? 0 : (k == 4 ? 1 : 3)); p < (k == 0 ? 1 : (k == 4 ? 3 : 4)); p++) {
              if (p > 0) mbar_wait(sb + SM_XF + ((2 + wg) * 4 + p) * 8);
              get_pair(A[2 * p], A[2 * p + 1], xb + p * 1024, hp_ + p * 1024, T);
              if (lane == 0) {
                if (wg == 0) mbar_arrive(sb + SM_XE + (8 + p) * 8);
                else if (p > 0) release(ST_XC + p - 1);
              }
            }
          }
          if (ps == 0 && (k & 1) == 0) {
#pragma unroll
            for (int s = 0; s < 4; s++) {
              A[c][s][0] = hsub2(A[c][s][0], m0); A[c][s][1] = hsub2(A[c][s][1], m1);
              A[c][s][2] = hsub2(A[c][s][2], m0); A[c][s][3] = hsub2(A[c][s][3], m1);
            }
            wg_fence();
          }
          UNIT_PRE(u);
          wgmma_rs_n128(acc, A[c][(k & 1) * 2], dg + UOFF(u), k != 0 ? 1 : (ps ? rz : 0));
          wgmma_rs_n128(acc, A[c][(k & 1) * 2 + 1], dg + UOFF(u) + 128, 1);
          UNIT_POST(u);
        }
        wg_wait<0>();
#pragma unroll
        for (int s = 0; s < 4; s++) {
          uint32_t (&hh)[4] = HH[4 + s];
          hh[0] = tg(pack2(acc[8 * s + 0] * acc[32 + 8 * s + 0], acc[8 * s + 1] * acc[32 + 8 * s + 1]), T);
          hh[1] = pack2(acc[8 * s + 2] * acc[32 + 8 * s + 2], acc[8 * s + 3] * acc[32 + 8 * s + 3]);
          hh[2] = pack2(acc[8 * s + 4] * acc[32 + 8 * s + 4], acc[8 * s + 5] * acc[32 + 8 * s + 5]);
          hh[3] = pack2(acc[8 * s + 6] * acc[32 + 8 * s + 6], acc[8 * s + 7] * acc[32 + 8 * s + 7]);
          st_rlx4(hhp + (4 * ps + s) * 128, hh[0], hh[1], hh[2], hh[3]);
        }
      }
      {
        float ag[24], au[24];
        const uint32_t* ph7 = reinterpret_cast<const uint32_t*>(&g_s[rh3].hh[jf ^ 1][7][wq][31]);
        uint32_t hv = 0;
        bar_sync(1 + wg, 128);
        wg_fence();
#pragma unroll
        for (int k = 0; k < 16; k++) {
          const int u = 32 + k, c = k >> 1;
          if (k == 6) {
#pragma unroll
            for (int s = 0; s < 4; s++) ld_rlx4(HH[s], hhp + s * 128);
          }
          if (k == 9) hv = ld_rlx1(ph7);
          if (k == 12) {
            int it = 0;
#pragma unroll 1
            while (((hv ^ T) & 1) && ++it < (1 << 18)) hv = ld_rlx1(ph7);
#pragma unroll
            for (int s = 0; s < 8; s++) ld_rlx4(PH[s], pp + s * 128);
          }
          UNIT_PRE(u);
          wgmma_rs_n48(ag, A[c][(k & 1) * 2], dg + UOFF(u), k != 0);
          wgmma_rs_n48(au, A[c][(k & 1) * 2], dg + UOFF(u) + 256, k != 0);
          wgmma_rs_n48(ag, A[c][(k & 1) * 2 + 1], dg + UOFF(u) + 128, 1);
          wgmma_rs_n48(au, A[c][(k & 1) * 2 + 1], dg + UOFF(u) + 256 + 128, 1);
          UNIT_POST(u);
        }
        wg_wait<0>();
#pragma unroll
        for (int s = 0; s < 3; s++) {
          uint32_t (&hh)[4] = HH[8 + s];
          hh[0] = tg(pack2(ag[8 * s + 0] * au[8 * s + 0], ag[8 * s + 1] * au[8 * s + 1]), T);
          hh[1] = pack2(ag[8 * s + 2] * au[8 * s + 2], ag[8 * s + 3] * au[8 * s + 3]);
          hh[2] = pack2(ag[8 * s + 4] * au[8 * s + 4], ag[8 * s + 5] * au[8 * s + 5]);
          hh[3] = pack2(ag[8 * s + 6] * au[8 * s + 6], ag[8 * s + 7] * au[8 * s + 7]);
          st_rlx4(hhp + (8 + s) * 128, hh[0], hh[1], hh[2], hh[3]);
        }
      }
    }

    {
      float acc[32];
      uint32_t hr[4][4], hx = 0;
      const int m = jf >> 1, oc = (jf & 1) * 4 + m;
      const uint32_t* ph10 = reinterpret_cast<const uint32_t*>(&g_s[rh3].hh[jf ^ 1][10][wq][31]);
      uint4* outb = &g_s[rh3].part[(jf & 1) * 4][m][wq][0][lane];
      bar_arrive(8 + wg, 256);
      int s0 = ST_D % NSLOT;
#pragma unroll 1
      for (int k = 0; k < 4; k++) {
        const int s1 = s0 + 1 == NSLOT ? 0 : s0 + 1;
        const uint32_t d0 = db + s0 * (SLOT >> 4), d1 = db + s1 * (SLOT >> 4);
        wg_wait<0>();
        if (k > 0) {
          uint4* p = outb + ((m + k) & 3) * 2048;
#pragma unroll
          for (int s = 0; s < 4; s++)
            st_rlx4(p + s * 32, tg(pack2(acc[8 * s], acc[8 * s + 1]), T), pack2(acc[8 * s + 2], acc[8 * s + 3]),
                    pack2(acc[8 * s + 4], acc[8 * s + 5]), pack2(acc[8 * s + 6], acc[8 * s + 7]));
          if (k == 1) bar_arrive(12, 320);
        } else {
          int it = 0;
#pragma unroll 1
          while (__any_sync(0xffffffffu, bad4(PH[0][0], PH[1][0], PH[2][0], PH[3][0], T) | bad4(PH[4][0], PH[5][0], PH[6][0], PH[7][0], T)) && ++it < (1 << 18)) {
#pragma unroll
            for (int s = 0; s < 8; s++) ld_rlx4(PH[s], pp + s * 128);
          }
        }
        mbar_wait(sb + SM_FULL + (ST_D + 2 * k) * 8);
        mbar_wait(sb + SM_FULL + (ST_D + 2 * k + 1) * 8);
        wg_fence();
#pragma unroll
        for (int s = 0; s < 11; s++) wgmma_rs_n64(acc, HH[s], d0 + s * 128, s != 0);
#pragma unroll
        for (int s = 0; s < 8; s++) wgmma_rs_n64(acc, PH[s], d1 + s * 128, 1);
        if (k == 0) {
          int it = 0;
#pragma unroll 1
          while (((ld_rlx1(ph10) ^ T) & 1) && ++it < (1 << 18)) {}
          ld_chunk(hr, &g_s[rh3].h[oc][wq][0][lane]);
#pragma unroll 1
          do {
            hx = ld_rlx1(&g_s[rh3].hx[oc][wq][lane]);
#pragma unroll
            for (int s = 8; s < 11; s++) ld_rlx4(PH[s], pp + s * 128);
          } while (__any_sync(0xffffffffu, bad4(PH[8][0], PH[9][0], PH[10][0], hx, T)) && ++it < (1 << 18));
          wg_fence();
        }
#pragma unroll
        for (int s = 8; s < 11; s++) wgmma_rs_n64(acc, PH[s], d1 + s * 128, 1);
        wg_commit();
        s0 = s1 + 1 == NSLOT ? 0 : s1 + 1;
      }
      wg_wait<0>();
#pragma unroll 1
      for (int q = 0; q < 3; q++) {
        uint32_t in[4][4];
        const uint4* sp = reinterpret_cast<const uint4*>(smem + ((ST_D % NSLOT) + wg) * SLOT) + q * 512 + wq * 128 + lane;
        mbar_wait_p(sb + SM_XF + (wg * 4 + q) * 8, 1);
        int it = 0;
#pragma unroll 1
        do {
#pragma unroll
          for (int s = 0; s < 4; s++)
            asm volatile("{\n.reg .b128 v;\nld.relaxed.gpu.b128 v, [%4];\nmov.b128 {%0,%1,%2,%3}, v;\n}"
                         : "=r"(in[s][0]), "=r"(in[s][1]), "=r"(in[s][2]), "=r"(in[s][3]) : "l"(sp + s * 32) : "memory");
          sp = &g_s[rh3].part[oc][(m - 1 - q) & 3][wq][0][lane];
        } while (__any_sync(0xffffffffu, bad4(in[0][0], in[1][0], in[2][0], in[3][0], T)) && ++it < (1 << 18));
        add_frag(acc, in, IDF);
      }
#pragma unroll
      for (int s = 0; s < 4; s++) hr[s][0] = (hr[s][0] & 0xFFFFFFFEu) | ((hx >> (s + 1)) & 1u);
#pragma unroll
      for (int i = 0; i < 32; i++) acc[i] *= (i & 2) ? r1 : r0;
      add_frag(acc, hr, IDF);
      bar_sync(9 - wg, 256);
      const uint32_t ob = sb + ((ST_D - 1) % NSLOT) * SLOT + wg * 8192;
#pragma unroll
      for (int s = 0; s < 4; s++)
        stsm4(ob + lrow + (((2 * s + lhi) ^ lx) << 4), pack2(acc[8 * s + 0], acc[8 * s + 1]), pack2(acc[8 * s + 2], acc[8 * s + 3]),
              pack2(acc[8 * s + 4], acc[8 * s + 5]), pack2(acc[8 * s + 6], acc[8 * s + 7]));
      __syncwarp();
      {
        const int row = wq * 16 + (lane >> 3);
        __nv_bfloat16* op = out + (size_t)(rh3 * 64 + row) * 512 + oc * 64 + lx * 8;
#pragma unroll
        for (int i = 0; i < 4; i++) {
          uint4 v;
          asm volatile("ld.shared.v4.b32 {%0,%1,%2,%3}, [%4];" : "=r"(v.x), "=r"(v.y), "=r"(v.z), "=r"(v.w)
                       : "r"(ob + (row + i * 4) * 128 + ((lx ^ (((lane >> 3) + i * 4) & 7)) << 4)) : "memory");
          asm volatile("st.global.v4.b32 [%0], {%1,%2,%3,%4};" ::"l"(op + i * 2048), "r"(v.x), "r"(v.y), "r"(v.z), "r"(v.w) : "memory");
        }
      }
    }
    asm volatile("barrier.cluster.arrive.relaxed.aligned;" ::: "memory");
    asm volatile("barrier.cluster.wait.aligned;" ::: "memory");
  } else {
    asm volatile("setmaxnreg.dec.sync.aligned.u32 24;");
    if (elect_one()) {
      if (warp == 8) {
#pragma unroll
        for (int k = 0; k < 9; k++) {
          const int s = k < 3 ? k : (k < 6 ? k + 3 : k - 3);
          const uint32_t bar = sb + SM_FULL + s * 8;
          mbar_init(bar, 1);
          mbar_expect_tx(bar, SLOT);
          if (s >= 3 && s < 6) tma2d(sb + s * SLOT, &maps.w, 512 + hg * 64, (s - 3) * 192, bar);
          else tma3d(sb + s * SLOT, &maps.x, 0, rb * 128 + (s >= 6 ? 64 : 0), 3 * (s % 3), bar);
        }
      } else if (warp == 9) {
        mbar_init(sb + SM_MISCB, 2);
        mbar_init(sb + SM_KVB, 2);
        mbar_init(sb + SM_XRB, 1);
        mbar_expect_tx(sb + SM_XRB, 16384);
        mbar_expect_tx(sb + SM_KVB, 12288);
        mbar_expect_tx(sb + SM_MISCB, 2048);
        bulk_g2s(sb + SM_WPHI, wphi + hg * 1024, 2048, sb + SM_MISCB);
      } else if (warp == 10) {
        if ((sb & 0x3FFFF) != SM_BASE) __trap();
#pragma unroll 1
        for (int i = 0; i < 16; i++) {
          mbar_init(sb + SM_XF + i * 8, 1);
          mbar_expect_tx(sb + SM_XF + i * 8, (i == 8 || i == 12) ? 20480 : 16384);
          if (i < 12) mbar_init(sb + SM_XE + i * 8, 4);
        }
      } else {
        *reinterpret_cast<volatile unsigned*>(smem + SM_EPOCH) = atomicAdd(&g_start, 1u) / NCTA;
      }
      asm volatile("fence.mbarrier_init.release.cluster;" ::: "memory");
    }
    __syncwarp();
    if (warp != 11) bar_sync(0, 352);
    asm volatile("barrier.cluster.arrive.relaxed.aligned;" ::: "memory");
    if (warp == 8) {
      asm volatile("barrier.cluster.wait.aligned;" ::: "memory");
      if (elect_one()) {
        const CUtensorMap* mg = jf == 7 ? &maps.g7 : &maps.g;
        const CUtensorMap* mu = jf == 7 ? &maps.u7 : &maps.u;
        asm volatile("prefetch.tensormap [%0];" ::"l"(&maps.wo) : "memory");
        asm volatile("prefetch.tensormap [%0];" ::"l"(mg) : "memory");
        asm volatile("prefetch.tensormap [%0];" ::"l"(mu) : "memory");
        asm volatile("prefetch.tensormap [%0];" ::"l"(&maps.d) : "memory");
#pragma unroll 1
        for (int i = ST_WV; i < ST_XC; i++) {
          if (i == ST_SCR1) continue;
          const int s = (WV_ && i >= 18) ? 37 - i : i;
          mbar_wait(sb + SM_EMPTY + (s - 9) * 8);
          const uint32_t dst = sb + (s >= 18 ? s - 18 : s - 9) * SLOT, bar = sb + SM_FULL + s * 8;
          if (s < ST_WO) tma2d(dst, &maps.w, (s < ST_WQ ? 1024 : 0) + hg * 64, (s < ST_WQ ? s - ST_WV : s - ST_WQ) * 192, bar);
          else {
            if (WV_ == 0) mbar_wait(bar - 8);
            else if (s == ST_WO) mbar_wait(bar - 8);
            else if (WV_ == 2 && s == 18) mbar_wait(sb + SM_KVB);
            tma2d(dst, &maps.wo, hg * 64, (s - ST_WO) * 192, bar);
          }
        }
        const int jc = jf == 7 ? 0 : jf;
        int slot = (ST_GU + 1 - rank) % NSLOT;
#pragma unroll 1
        for (int s = ST_GU + 1 - rank; s < NSTAGE; s += 2) {
          mbar_wait(sb + SM_EMPTY + (s - 9) * 8);
          if (s < ST_GU + 6) mbar_wait(sb + SM_XF + (s < ST_GU + 3 ? 3 : 11) * 8);
          if (s > ST_GU + 3 && s < ST_GU + 6) mbar_wait(sb + SM_FULL + (s - 1) * 8);
          const uint32_t dst = sb + slot * SLOT, bar = sb + SM_FULL + s * 8;
          if (s < ST_D) {
#pragma unroll 1
            for (int i = 0; i < 3; i++) {
              const int u = (s - ST_GU) * 3 + i;
              tma3d_mc(dst + i * 8192, mg, (u >> 4) * 64, jc, (u & 15) * 32, bar);
              tma3d_mc(dst + i * 8192 + 4096, mu, (u >> 4) * 64, jc, (u & 15) * 32, bar);
            }
          } else {
            const int i = s - ST_D;
            tma2d_mc(dst, &maps.d, ((jf & 1) * 4 + (((jf >> 1) + 1 + (i >> 1)) & 3)) * 64, (jf ^ (i & 1)) * 176, bar);
          }
          slot += 2; if (slot >= NSLOT) slot -= NSLOT;
        }
      }
      __syncwarp();
    } else {
      asm volatile("barrier.cluster.wait.aligned;" ::: "memory");
      if (warp == 11) {
#pragma unroll
        for (int i = 0; i < 4; i++)
          reinterpret_cast<uint4*>(smem + SM_ONES)[lane + 32 * i] = make_uint4(0x3F803F80u, 0x3F803F80u, 0x3F803F80u, 0x3F803F80u);
        fence_async_smem();
        __syncwarp();
        if (lane == 0) mbar_arrive(sb + SM_MISCB);
      }
      mbar_wait(sb + SM_MISCB);
      const unsigned epoch = *reinterpret_cast<volatile unsigned*>(smem + SM_EPOCH);
      const uint32_t T = (epoch & 1) ^ 1;
      if (warp == 11) {
        (&g_kv[hg][rb * 8][0])[lane] = make_float4(0.f, 0.f, 0.f, 0.f);
        if (lane < 16) (&g_kv[hg][rb * 8][0])[32 + lane] = make_float4(0.f, 0.f, 0.f, 0.f);
        __syncwarp();
        if (elect_one()) asm volatile("red.release.gpu.global.add.u32 [%0], 8;" ::"l"(&g_kvcnt[hg * 32 + 1]) : "memory");
        mbar_wait(sb + SM_FULL + (ST_WK + 2) * 8);
        if (elect_one()) {
          asm volatile("cp.async.bulk.prefetch.L2.global [%0], 4096;" ::"l"((const char*)wo + blockIdx.x * 4096) : "memory");
          asm volatile("cp.async.bulk.prefetch.L2.global [%0], 11008;" ::"l"((const char*)wg_ + blockIdx.x * 11008) : "memory");
          asm volatile("cp.async.bulk.prefetch.L2.global [%0], 11008;" ::"l"((const char*)wu_ + blockIdx.x * 11008) : "memory");
          asm volatile("cp.async.bulk.prefetch.L2.global [%0], 11008;" ::"l"((const char*)wd_ + blockIdx.x * 11008) : "memory");
          mbar_wait(sb + SM_EMPTY + ST_SCR0 * 8);
          const unsigned target = (epoch + 1) * 128;
          unsigned v, z; int it = 0;
#pragma unroll 1
          do {
            asm volatile("{\n.reg .b64 q;\nld.acquire.gpu.global.b64 q, [%2];\nmov.b64 {%0, %1}, q;\n}" : "=r"(v), "=r"(z) : "l"(&g_kvcnt[hg * 32]) : "memory");
            if (++it > (1 << 18)) break;
          } while ((int)(v - target) < 0 || (int)(z - target) < 0);
          asm volatile("fence.proxy.async.global;" ::: "memory");
          bulk_g2s(sb + 3 * SLOT, &g_kv[hg][0][0], 12288, sb + SM_KVB);
        }
        __syncwarp();
      } else {
        const int w = warp - 9;
        st_rlx4(reinterpret_cast<uint4*>(&g_s[2 * rb + w].st[hg][0]) + lane, T ^ 1, T ^ 1, T ^ 1, T ^ 1);
        if (lane < 8) st_rlx4(&g_s[2 * rb + w].o[hg][lane >> 1][3][30 + (lane & 1)], T ^ 1, T ^ 1, T ^ 1, T ^ 1);
        st_rlx4(&g_s[2 * rb3 + w].part[(jf & 1) * 4 + (lane >> 3)][jf >> 1][(lane >> 1) & 3][3][30 + (lane & 1)], T ^ 1, T ^ 1, T ^ 1, T ^ 1);
        if (lane < 16) st_rlx4(&g_s[2 * rb3 + w].hh[jf][7 + (lane >> 3) * 3][(lane >> 1) & 3][30 + (lane & 1)], T ^ 1, T ^ 1, T ^ 1, T ^ 1);
        if (w == 0) {
          mbar_wait(sb + SM_FULL + (ST_WV + 2) * 8);
          mbar_wait(sb + SM_FULL + (ST_WQ + 2) * 8);
          if (elect_one()) {
            tma2d(sb + ((ST_WV + 2) % NSLOT) * SLOT + 16384, &maps.xr, hg * 64, rb * 128, sb + SM_XRB);
            tma2d(sb + ((ST_WQ + 2) % NSLOT) * SLOT + 16384, &maps.xr, hg * 64, rb * 128 + 64, sb + SM_XRB);
          }
          __syncwarp();
          unsigned v; int it = 0;
#pragma unroll 1
          do {
            asm volatile("ld.acquire.gpu.global.u32 %0, [%1];" : "=r"(v) : "l"(&g_kvcnt[hg * 32 + 1]) : "memory");
          } while ((int)(v - (epoch + 1) * 128) < 0 && ++it < (1 << 18));
          asm volatile("fence.proxy.async.global;" ::: "memory");
        }
        {
          mbar_wait(sb + SM_EMPTY + (ST_WV + 1) * 8);
          float* cp = reinterpret_cast<float*>(smem + 2 * SLOT) + (w * 32 + lane) * 24;
          cp[19] = 1.f; cp[64 * 24 + 19] = 1.f;
          *reinterpret_cast<float2*>(cp + 22) = make_float2(0.f, 1.f); *reinterpret_cast<float2*>(cp + 64 * 24 + 22) = make_float2(0.f, 1.f);
          fence_async_smem();
        }
        bar_sync(6, 192);
        if (w == 0 && elect_one()) {
          asm volatile("cp.reduce.async.bulk.global.shared::cta.bulk_group.add.f32 [%0], [%1], 12288;"
                       ::"l"(&g_kv[hg][0][0]), "r"(sb + 2 * SLOT) : "memory");
          asm volatile("cp.async.bulk.commit_group;" ::: "memory");
          asm volatile("cp.async.bulk.wait_group.read 0;" ::: "memory");
          asm volatile("red.relaxed.gpu.global.add.u32 [%0], 8;" ::"l"(&g_kvcnt[hg * 32]) : "memory");
          mbar_arrive(sb + SM_KVB);
        }
        __syncwarp();
        mbar_wait(sb + SM_KVB);
        if (w == 0) { mbar_wait(sb + SM_EMPTY + 11 * 8); mbar_wait(sb + SM_EMPTY + 12 * 8); mbar_wait(sb + SM_EMPTY + 13 * 8); }
#pragma unroll 1
        for (int ph = 0; ph < 2; ph++) {
          const int use = 2 * ph + w, r = ph ? 2 * rb3 + w : 2 * rb + w;
          const uint32_t* pw = ph ? reinterpret_cast<const uint32_t*>(&g_s[r].st[lane >> 2][(lane & 3) * 16 + 15])
                                  : reinterpret_cast<const uint32_t*>(&g_s[r].o[lane >> 2][lane & 3][3][31]);
          const char* src = reinterpret_cast<const char*>(ph ? &g_s[r].h[0][0][0][0] : &g_s[r].o[0][0][0][0]);
          const uint32_t bf = sb + SM_XF + use * 32, be = sb + SM_XE + (use - 1) * 32;
          bar_sync(10 + w, 160);
          int it = 0;
#pragma unroll 1
          for (bool miss = true; __any_sync(0xffffffffu, miss) && ++it < (1 << 18);) { if (miss) miss = (ld_rlx1(pw) ^ T) & 1; }
          if (elect_one()) {
            if (use > 0) mbar_wait(be);
            if (ph) bulk_g2s(sb + SM_KV32 + w * 4096, &g_s[r].st[0][0], 4096, bf);
#pragma unroll
            for (int p = 0; p < 4; p++) {
              if (p > 0 && use > 0) mbar_wait(be + p * 8);
              bulk_g2s(sb + 2 * SLOT + p * 16384, src + p * 16384, 16384, bf + p * 8);
            }
          }
          __syncwarp();
        }
        {
          const int m = jf >> 1, oc = (jf & 1) * 4 + m;
          const uint32_t* pw = reinterpret_cast<const uint32_t*>(&g_s[2 * rb3 + w].part[oc][(m - 1 - (lane >> 2)) & 3][lane & 3][3][31]);
          bar_sync(12, 320);
          bool miss = lane < 12; int it = 0;
#pragma unroll 1
          for (int q = 0; q < 3; q++) {
#pragma unroll 1
            while ((__ballot_sync(0xffffffffu, miss) >> (4 * q) & 15) && ++it < (1 << 18)) { if (miss && (lane >> 2) <= q + 1) miss = (ld_rlx1(pw) ^ T) & 1; }
            if (elect_one()) {
              const uint32_t bar = sb + SM_XF + (w * 4 + q) * 8;
              mbar_expect_tx(bar, 8192);
              bulk_g2s(sb + ((ST_D % NSLOT) + w) * SLOT + q * 8192, &g_s[2 * rb3 + w].part[oc][(m - 1 - q) & 3][0][0][0], 8192, bar);
            }
            __syncwarp();
          }
        }
      }
    }
    asm volatile("barrier.cluster.arrive.relaxed.aligned;" ::: "memory");
    asm volatile("barrier.cluster.wait.aligned;" ::: "memory");
  }
}

typedef CUresult (*EncodeFn)(CUtensorMap*, CUtensorMapDataType, cuuint32_t, void*, const cuuint64_t*, const cuuint64_t*,
                             const cuuint32_t*, const cuuint32_t*, CUtensorMapInterleave, CUtensorMapSwizzle,
                             CUtensorMapL2promotion, CUtensorMapFloatOOBfill);

void encode(EncodeFn fn, CUtensorMap* m, const void* base, int rank, const cuuint64_t* dims, const cuuint64_t* strides,
            const cuuint32_t* box) {
  cuuint32_t es[3] = {1, 1, 1};
  fn(m, CU_TENSOR_MAP_DATA_TYPE_BFLOAT16, (cuuint32_t)rank, const_cast<void*>(base), dims, strides, box, es,
     CU_TENSOR_MAP_INTERLEAVE_NONE, CU_TENSOR_MAP_SWIZZLE_128B, CU_TENSOR_MAP_L2_PROMOTION_L2_256B,
     CU_TENSOR_MAP_FLOAT_OOB_FILL_NONE);
}

}

extern "C" void kernel_launch(void* const* d_in, const int* in_sizes, int n_in, void* d_out, int out_size) {
  (void)in_sizes; (void)n_in; (void)out_size;
  const __nv_bfloat16* x    = (const __nv_bfloat16*)d_in[0];
  const __nv_bfloat16* wqkv = (const __nv_bfloat16*)d_in[1];
  const __nv_bfloat16* wphi = (const __nv_bfloat16*)d_in[2];
  const __nv_bfloat16* wo   = (const __nv_bfloat16*)d_in[3];
  const __nv_bfloat16* wg   = (const __nv_bfloat16*)d_in[5];
  const __nv_bfloat16* wu   = (const __nv_bfloat16*)d_in[6];
  const __nv_bfloat16* wd   = (const __nv_bfloat16*)d_in[7];

  static EncodeFn fn = nullptr;
  if (!fn) {
    void* p = nullptr;
    cudaDriverEntryPointQueryResult qr;
    cudaGetDriverEntryPoint("cuTensorMapEncodeTiled", &p, cudaEnableDefault, &qr);
    fn = (EncodeFn)p;
    cudaFuncSetAttribute(fused_kernel, cudaFuncAttributeMaxDynamicSharedMemorySize, SM_TOTAL);
  }
  Maps maps;
  {
    cuuint64_t d[3] = {64, 2048, 8}, s[2] = {1024, 128}; cuuint32_t b[3] = {64, 64, 3};
    encode(fn, &maps.x, x, 3, d, s, b);
  }
  {
    cuuint64_t d[2] = {512, 2048}, s[1] = {1024}; cuuint32_t b[2] = {64, 64};
    encode(fn, &maps.xr, x, 2, d, s, b);
  }
  {
    cuuint64_t d[2] = {1536, 512}, s[1] = {3072}; cuuint32_t b[2] = {64, 192};
    encode(fn, &maps.w, wqkv, 2, d, s, b);
  }
  {
    cuuint64_t d[2] = {512, 512}, s[1] = {1024}; cuuint32_t b[2] = {64, 192};
    encode(fn, &maps.wo, wo, 2, d, s, b);
  }
  {
    cuuint64_t d[3] = {176, 7, 512}, d7[3] = {144, 1, 512}, s[2] = {352, 2752}; cuuint32_t b[3] = {64, 1, 32};
    encode(fn, &maps.g, wg, 3, d, s, b);
    encode(fn, &maps.u, wu, 3, d, s, b);
    encode(fn, &maps.g7, wg + 1232, 3, d7, s, b);
    encode(fn, &maps.u7, wu + 1232, 3, d7, s, b);
  }
  {
    cuuint64_t d[2] = {512, 1376}, s[1] = {1024}; cuuint32_t b[2] = {64, 176};
    encode(fn, &maps.d, wd, 2, d, s, b);
  }
  fused_kernel<<<NCTA, 384, SM_TOTAL>>>(maps, wphi, wo, wg, wu, wd, (__nv_bfloat16*)d_out);
}
```

```cpp
#include <cuda_runtime.h>
#include <cuda_bf16.h>
#include <cuda.h>
#include <stdint.h>

#define SAFE_WAIT 0

namespace {

constexpr int NCTA   = 128;
constexpr int SLOT   = 24576;
constexpr int NSLOT  = 9;
constexpr int NSTAGE = 47;

constexpr int ST_X0   = 0;
constexpr int ST_WK   = 3;
constexpr int ST_X1   = 6;
constexpr int ST_SCR0 = 9;
constexpr int ST_WV   = 10;
constexpr int ST_SCR1 = 13;
constexpr int ST_WQ   = 14;
constexpr int ST_WO   = 17;
constexpr int ST_XC   = 20;
constexpr int ST_GU   = 23;
constexpr int ST_D    = 39;

__host__ __device__ constexpr int st_empty_cnt(int d) {
  return ((d < 3 || (d >= 6 && d < 9) || (d >= ST_XC && d < ST_GU)) ? 4 : (d == ST_SCR0 || d == ST_SCR1) ? 1 : 2) * (d + 9 >= ST_GU ? 2 : 1);
}

constexpr uint32_t SM_BASE = 1024;
constexpr int SM_ONES = NSLOT * SLOT;
constexpr int SM_WPHI = SM_ONES + 2048;
constexpr int SM_KVS  = SM_WPHI + 2048;
constexpr int SM_KV32 = 4 * SLOT + 16384;
constexpr int SM_BAR  = SM_KVS + 6144;
constexpr int SM_FULL  = SM_BAR;
constexpr int SM_EMPTY = SM_BAR + NSTAGE * 8;
constexpr int SM_MISCB = SM_BAR + 2 * NSTAGE * 8;
constexpr int SM_KVB   = SM_MISCB + 8;
constexpr int SM_EPOCH = SM_KVB + 8;
constexpr int SM_XF    = SM_EPOCH + 8;
constexpr int SM_XE    = SM_XF + 16 * 8;
constexpr int SM_XRB   = SM_XE + 12 * 8;
constexpr int SM_TOTAL = SM_BAR + 1024;

static_assert(SM_TOTAL == 232448 && SM_XRB + 8 <= SM_TOTAL, "smem budget");

struct Maps { CUtensorMap x, xr, w, wo, g, u, g7, u7, d; };

struct Scratch {
  uint4    o[8][4][4][32];
  uint4    h[8][4][4][32];
  uint32_t hx[8][4][32];
  uint2    st[8][64];
  uint4    hh[8][11][4][32];
  uint4    part[8][4][4][4][32];
};
__device__ __align__(128) Scratch g_s[32];
__device__ __align__(128) float4 g_kv[8][128][6];
__device__ __align__(128) unsigned g_kvcnt[8 * 32];
__device__ unsigned g_start;

__device__ __forceinline__ uint32_t smem_u32(const void* p) { return (uint32_t)__cvta_generic_to_shared(p); }
__device__ __forceinline__ void mbar_init(uint32_t bar, int cnt) {
  asm volatile("mbarrier.init.shared::cta.b64 [%0], %1;" ::"r"(bar), "r"(cnt) : "memory");
}
__device__ __forceinline__ void mbar_expect_tx(uint32_t bar, uint32_t bytes) {
  asm volatile("mbarrier.arrive.expect_tx.shared::cta.b64 _, [%0], %1;" ::"r"(bar), "r"(bytes) : "memory");
}
__device__ __forceinline__ void mbar_arrive(uint32_t bar) {
  asm volatile("mbarrier.arrive.shared::cta.b64 _, [%0];" ::"r"(bar) : "memory");
}
__device__ __forceinline__ void mbar_arrive_cluster(uint32_t bar, uint32_t rank) {
  asm volatile("{\n.reg .b32 ra;\nmapa.shared::cluster.u32 ra, %0, %1;\n"
               "mbarrier.arrive.shared::cluster.b64 _, [ra];\n}" ::"r"(bar), "r"(rank) : "memory");
}
__device__ __forceinline__ void mbar_wait_p(uint32_t bar, uint32_t parity) {
  asm volatile("{\n.reg .pred p;\nW: mbarrier.try_wait.parity.shared::cta.b64 p, [%0], %1;\n@!p bra W;\n}" ::"r"(bar), "r"(parity) : "memory");
}
__device__ __forceinline__ void mbar_wait(uint32_t bar) { mbar_wait_p(bar, 0); }
__device__ __forceinline__ bool elect_one() {
  uint32_t p;
  asm volatile("{\n.reg .pred P;\nelect.sync _|P, 0xffffffff;\nselp.u32 %0, 1, 0, P;\n}" : "=r"(p));
  return p != 0;
}
__device__ __forceinline__ void bar_sync(int id, int n)   { asm volatile("bar.sync %0, %1;" ::"r"(id), "r"(n) : "memory"); }
__device__ __forceinline__ void bar_arrive(int id, int n) { asm volatile("bar.arrive %0, %1;" ::"r"(id), "r"(n) : "memory"); }
__device__ __forceinline__ void fence_async_smem() { asm volatile("fence.proxy.async.shared::cta;" ::: "memory"); }
__device__ __forceinline__ void wg_fence()  { asm volatile("wgmma.fence.sync.aligned;" ::: "memory"); }
__device__ __forceinline__ void wg_commit() { asm volatile("wgmma.commit_group.sync.aligned;" ::: "memory"); }
template <int N> __device__ __forceinline__ void wg_wait() { asm volatile("wgmma.wait_group.sync.aligned %0;" ::"n"(N) : "memory"); }
#define DESC(off) (db + ((uint32_t)(off) >> 4))
__device__ __forceinline__ void tma2d(uint32_t dst, const CUtensorMap* m, int c0, int c1, uint32_t bar) {
  asm volatile("cp.async.bulk.tensor.2d.shared::cluster.global.mbarrier::complete_tx::bytes [%0], [%1, {%3, %4}], [%2];"
               ::"r"(dst), "l"(m), "r"(bar), "r"(c0), "r"(c1) : "memory");
}
__device__ __forceinline__ void tma2d_mc(uint32_t dst, const CUtensorMap* m, int c0, int c1, uint32_t bar) {
  asm volatile("cp.async.bulk.tensor.2d.shared::cluster.global.mbarrier::complete_tx::bytes.multicast::cluster [%0], [%1, {%3, %4}], [%2], %5;"
               ::"r"(dst), "l"(m), "r"(bar), "r"(c0), "r"(c1), "h"((uint16_t)3) : "memory");
}
__device__ __forceinline__ void tma3d(uint32_t dst, const CUtensorMap* m, int c0, int c1, int c2, uint32_t bar) {
  asm volatile("cp.async.bulk.tensor.3d.shared::cluster.global.mbarrier::complete_tx::bytes [%0], [%1, {%3, %4, %5}], [%2];"
               ::"r"(dst), "l"(m), "r"(bar), "r"(c0), "r"(c1), "r"(c2) : "memory");
}
__device__ __forceinline__ void tma3d_mc(uint32_t dst, const CUtensorMap* m, int c0, int c1, int c2, uint32_t bar) {
  asm volatile("cp.async.bulk.tensor.3d.shared::cluster.global.mbarrier::complete_tx::bytes.multicast::cluster [%0], [%1, {%3, %4, %5}], [%2], %6;"
               ::"r"(dst), "l"(m), "r"(bar), "r"(c0), "r"(c1), "r"(c2), "h"((uint16_t)3) : "memory");
}
__device__ __forceinline__ void ldsm4(uint32_t (&r)[4], uint32_t addr) {
  asm volatile("ldmatrix.sync.aligned.m8n8.x4.shared.b16 {%0,%1,%2,%3}, [%4];"
               : "=r"(r[0]), "=r"(r[1]), "=r"(r[2]), "=r"(r[3]) : "r"(addr) : "memory");
}
__device__ __forceinline__ void ldsm4t(uint32_t (&r)[4], uint32_t addr) {
  asm volatile("ldmatrix.sync.aligned.m8n8.x4.trans.shared.b16 {%0,%1,%2,%3}, [%4];"
               : "=r"(r[0]), "=r"(r[1]), "=r"(r[2]), "=r"(r[3]) : "r"(addr) : "memory");
}
__device__ __forceinline__ void stsm4(uint32_t addr, uint32_t r0, uint32_t r1, uint32_t r2, uint32_t r3) {
  asm volatile("stmatrix.sync.aligned.m8n8.x4.shared.b16 [%0], {%1,%2,%3,%4};"
               ::"r"(addr), "r"(r0), "r"(r1), "r"(r2), "r"(r3) : "memory");
}
__device__ __forceinline__ void mma16816(float (&c)[4], const uint32_t (&a)[4], uint32_t b0, uint32_t b1) {
  asm volatile("mma.sync.aligned.m16n8k16.row.col.f32.bf16.bf16.f32 {%0,%1,%2,%3},{%4,%5,%6,%7},{%8,%9},{%0,%1,%2,%3};"
               : "+f"(c[0]), "+f"(c[1]), "+f"(c[2]), "+f"(c[3])
               : "r"(a[0]), "r"(a[1]), "r"(a[2]), "r"(a[3]), "r"(b0), "r"(b1));
}
__device__ __forceinline__ void add_frag(float (&c)[32], const uint32_t (&a)[4][4], uint32_t id) {
#pragma unroll
  for (int i = 0; i < 8; i++)
    asm volatile("mma.sync.aligned.m16n8k8.row.col.f32.bf16.bf16.f32 {%0,%1,%2,%3},{%4,%5},{%6},{%0,%1,%2,%3};"
                 : "+f"(c[4 * i]), "+f"(c[4 * i + 1]), "+f"(c[4 * i + 2]), "+f"(c[4 * i + 3])
                 : "r"(a[i >> 1][(i & 1) * 2]), "r"(a[i >> 1][(i & 1) * 2 + 1]), "r"(id));
}
__device__ __forceinline__ uint32_t pack2(float lo, float hi) {
  uint32_t r; asm("cvt.rn.bf16x2.f32 %0, %1, %2;" : "=r"(r) : "f"(hi), "f"(lo)); return r;
}
__device__ __forceinline__ float blo(uint32_t w) { return __uint_as_float(w << 16); }
__device__ __forceinline__ float bhi(uint32_t w) { return __uint_as_float(w & 0xFFFF0000u); }
__device__ __forceinline__ uint32_t hsub2(uint32_t a, uint32_t b) { uint32_t r; asm("sub.rn.bf16x2 %0, %1, %2;" : "=r"(r) : "r"(a), "r"(b)); return r; }
__device__ __forceinline__ uint32_t hmax2(uint32_t a, uint32_t b) { uint32_t r; asm("max.bf16x2 %0, %1, %2;" : "=r"(r) : "r"(a), "r"(b)); return r; }
__device__ __forceinline__ uint32_t hmin2(uint32_t a, uint32_t b) { uint32_t r; asm("min.bf16x2 %0, %1, %2;" : "=r"(r) : "r"(a), "r"(b)); return r; }
__device__ __forceinline__ float ex2(float x) { float r; asm("ex2.approx.ftz.f32 %0, %1;" : "=f"(r) : "f"(x)); return r; }
__device__ __forceinline__ float rcp(float x) { float r; asm("rcp.approx.ftz.f32 %0, %1;" : "=f"(r) : "f"(x)); return r; }
__device__ __forceinline__ void ld_rlx4(uint32_t (&r)[4], const uint4* p) {
  asm volatile("{\n.reg .b128 v;\nld.relaxed.gpu.global.b128 v, [%4];\nmov.b128 {%0,%1,%2,%3}, v;\n}"
               : "=r"(r[0]), "=r"(r[1]), "=r"(r[2]), "=r"(r[3]) : "l"(p) : "memory");
}
__device__ __forceinline__ void st_rlx4(uint4* p, uint32_t a, uint32_t b, uint32_t c, uint32_t d) {
  asm volatile("st.relaxed.gpu.global.v4.b32 [%0], {%1,%2,%3,%4};" ::"l"(p), "r"(a), "r"(b), "r"(c), "r"(d) : "memory");
}
__device__ __forceinline__ void st_rlx2(uint2* p, uint32_t a, uint32_t b) {
  asm volatile("{\n.reg .b64 v;\nmov.b64 v, {%1,%2};\nst.relaxed.gpu.global.b64 [%0], v;\n}" ::"l"(p), "r"(a), "r"(b) : "memory");
}
__device__ __forceinline__ uint32_t ld_rlx1(const uint32_t* p) {
  uint32_t r; asm volatile("ld.relaxed.gpu.global.b32 %0, [%1];" : "=r"(r) : "l"(p) : "memory"); return r;
}
__device__ __forceinline__ void st_rlx1(uint32_t* p, uint32_t a) {
  asm volatile("st.relaxed.gpu.global.b32 [%0], %1;" ::"l"(p), "r"(a) : "memory");
}
__device__ __forceinline__ void ld_rlx2(uint32_t& a, uint32_t& b, const uint2* p) {
  asm volatile("{\n.reg .b64 v;\nld.relaxed.gpu.b64 v, [%2];\nmov.b64 {%0,%1}, v;\n}" : "=r"(a), "=r"(b) : "l"(p) : "memory");
}
__device__ __forceinline__ void bulk_g2s(uint32_t dst, const void* src, uint32_t bytes, uint32_t bar) {
  asm volatile("cp.async.bulk.shared::cluster.global.mbarrier::complete_tx::bytes [%0], [%1], %2, [%3];"
               ::"r"(dst), "l"(src), "r"(bytes), "r"(bar) : "memory");
}
__device__ __forceinline__ uint32_t tg(uint32_t w, uint32_t T) { return (w & 0xFFFFFFFEu) | T; }
__device__ __forceinline__ uint32_t bad4(uint32_t a, uint32_t b, uint32_t c, uint32_t d, uint32_t T) {
  uint32_t u, v;
  asm("lop3.b32 %0, %1, %2, %3, 0x7E;" : "=r"(u) : "r"(a), "r"(b), "r"(T));
  asm("lop3.b32 %0, %1, %2, %3, 0x7E;" : "=r"(v) : "r"(c), "r"(d), "r"(T));
  asm("lop3.b32 %0, %1, %2, 1, 0xA8;" : "=r"(u) : "r"(u), "r"(v));
  return u;
}

__device__ __forceinline__ void ld_chunk(uint32_t (&a)[4][4], const uint4* p) {
#pragma unroll
  for (int s = 0; s < 4; s++) ld_rlx4(a[s], p + s * 32);
}
__device__ __forceinline__ void get_pair(uint32_t (&a)[4][4], uint32_t (&b)[4][4], const uint4* sp, const uint4* gp, uint32_t T) {
  int it = 0;
#pragma unroll 1
  do {
#pragma unroll
    for (int s = 0; s < 8; s++) {
      uint32_t (&r)[4] = s < 4 ? a[s & 3] : b[s & 3];
      asm volatile("{\n.reg .b128 v;\nld.relaxed.gpu.b128 v, [%4];\nmov.b128 {%0,%1,%2,%3}, v;\n}"
                   : "=r"(r[0]), "=r"(r[1]), "=r"(r[2]), "=r"(r[3]) : "l"(sp + (s >> 2) * 512 + (s & 3) * 32) : "memory");
    }
    sp = gp;
  } while (__any_sync(0xffffffffu, bad4(a[0][0], a[1][0], a[2][0], a[3][0], T) | bad4(b[0][0], b[1][0], b[2][0], b[3][0], T)) && ++it < (1 << 18));
}

__device__ __forceinline__ void wgmma_rs_n48(float (&d)[24], const uint32_t (&a)[4], uint32_t descB, int scaleD) {
  asm volatile("{\n.reg .pred p;\n.reg .b64 db;\nsetp.ne.b32 p, %29, 0;\nmov.b64 db, {%28, 0x40000040};\n"
    "wgmma.mma_async.sync.aligned.m64n48k16.f32.bf16.bf16 {%0,%1,%2,%3,%4,%5,%6,%7,%8,%9,%10,%11,%12,%13,%14,%15,%16,%17,%18,%19,%20,%21,%22,%23}, {%24,%25,%26,%27}, db, p, 1, 1, 1;\n}\n"
    : "+f"(d[0]),"+f"(d[1]),"+f"(d[2]),"+f"(d[3]),"+f"(d[4]),"+f"(d[5]),"+f"(d[6]),"+f"(d[7]),"+f"(d[8]),"+f"(d[9]),"+f"(d[10]),"+f"(d[11]),"+f"(d[12]),"+f"(d[13]),"+f"(d[14]),"+f"(d[15]),"+f"(d[16]),"+f"(d[17]),"+f"(d[18]),"+f"(d[19]),"+f"(d[20]),"+f"(d[21]),"+f"(d[22]),"+f"(d[23])
    : "r"(a[0]), "r"(a[1]), "r"(a[2]), "r"(a[3]), "r"(descB), "r"(scaleD));
}
__device__ __forceinline__ void wgmma_rs_n64(float (&d)[32], const uint32_t (&a)[4], uint32_t descB, int scaleD) {
  asm volatile("{\n.reg .pred p;\n.reg .b64 db;\nsetp.ne.b32 p, %37, 0;\nmov.b64 db, {%36, 0x40000040};\n"
    "wgmma.mma_async.sync.aligned.m64n64k16.f32.bf16.bf16 {%0,%1,%2,%3,%4,%5,%6,%7,%8,%9,%10,%11,%12,%13,%14,%15,%16,%17,%18,%19,%20,%21,%22,%23,%24,%25,%26,%27,%28,%29,%30,%31}, {%32,%33,%34,%35}, db, p, 1, 1, 1;\n}\n"
    : "+f"(d[0]),"+f"(d[1]),"+f"(d[2]),"+f"(d[3]),"+f"(d[4]),"+f"(d[5]),"+f"(d[6]),"+f"(d[7]),"+f"(d[8]),"+f"(d[9]),"+f"(d[10]),"+f"(d[11]),"+f"(d[12]),"+f"(d[13]),"+f"(d[14]),"+f"(d[15]),"+f"(d[16]),"+f"(d[17]),"+f"(d[18]),"+f"(d[19]),"+f"(d[20]),"+f"(d[21]),"+f"(d[22]),"+f"(d[23]),"+f"(d[24]),"+f"(d[25]),"+f"(d[26]),"+f"(d[27]),"+f"(d[28]),"+f"(d[29]),"+f"(d[30]),"+f"(d[31])
    : "r"(a[0]), "r"(a[1]), "r"(a[2]), "r"(a[3]), "r"(descB), "r"(scaleD));
}
__device__ __forceinline__ void wgmma_rs_n128(float (&d)[64], const uint32_t (&a)[4], uint32_t descB, int scaleD) {
  asm volatile("{\n.reg .pred p;\n.reg .b64 db;\nsetp.ne.b32 p, %69, 0;\nmov.b64 db, {%68, 0x40000040};\n"
    "wgmma.mma_async.sync.aligned.m64n128k16.f32.bf16.bf16 {%0,%1,%2,%3,%4,%5,%6,%7,%8,%9,%10,%11,%12,%13,%14,%15,%16,%17,%18,%19,%20,%21,%22,%23,%24,%25,%26,%27,%28,%29,%30,%31,%32,%33,%34,%35,%36,%37,%38,%39,%40,%41,%42,%43,%44,%45,%46,%47,%48,%49,%50,%51,%52,%53,%54,%55,%56,%57,%58,%59,%60,%61,%62,%63}, {%64,%65,%66,%67}, db, p, 1, 1, 1;\n}\n"
    : "+f"(d[0]),"+f"(d[1]),"+f"(d[2]),"+f"(d[3]),"+f"(d[4]),"+f"(d[5]),"+f"(d[6]),"+f"(d[7]),"+f"(d[8]),"+f"(d[9]),"+f"(d[10]),"+f"(d[11]),"+f"(d[12]),"+f"(d[13]),"+f"(d[14]),"+f"(d[15]),"+f"(d[16]),"+f"(d[17]),"+f"(d[18]),"+f"(d[19]),"+f"(d[20]),"+f"(d[21]),"+f"(d[22]),"+f"(d[23]),"+f"(d[24]),"+f"(d[25]),"+f"(d[26]),"+f"(d[27]),"+f"(d[28]),"+f"(d[29]),"+f"(d[30]),"+f"(d[31]),"+f"(d[32]),"+f"(d[33]),"+f"(d[34]),"+f"(d[35]),"+f"(d[36]),"+f"(d[37]),"+f"(d[38]),"+f"(d[39]),"+f"(d[40]),"+f"(d[41]),"+f"(d[42]),"+f"(d[43]),"+f"(d[44]),"+f"(d[45]),"+f"(d[46]),"+f"(d[47]),"+f"(d[48]),"+f"(d[49]),"+f"(d[50]),"+f"(d[51]),"+f"(d[52]),"+f"(d[53]),"+f"(d[54]),"+f"(d[55]),"+f"(d[56]),"+f"(d[57]),"+f"(d[58]),"+f"(d[59]),"+f"(d[60]),"+f"(d[61]),"+f"(d[62]),"+f"(d[63])
    : "r"(a[0]), "r"(a[1]), "r"(a[2]), "r"(a[3]), "r"(descB), "r"(scaleD));
}
__device__ __forceinline__ void wgmma_ss_n72_t11(float (&d)[36], uint32_t descA, uint32_t descB, int scaleD) {
  asm volatile("{\n.reg .pred p;\n.reg .b64 da, db;\nsetp.ne.b32 p, %38, 0;\nmov.b64 da, {%36, 0x40000040};\nmov.b64 db, {%37, 0x40000040};\n"
    "wgmma.mma_async.sync.aligned.m64n72k16.f32.bf16.bf16 {%0,%1,%2,%3,%4,%5,%6,%7,%8,%9,%10,%11,%12,%13,%14,%15,%16,%17,%18,%19,%20,%21,%22,%23,%24,%25,%26,%27,%28,%29,%30,%31,%32,%33,%34,%35}, da, db, p, 1, 1, 1, 1;\n}\n"
    : "+f"(d[0]),"+f"(d[1]),"+f"(d[2]),"+f"(d[3]),"+f"(d[4]),"+f"(d[5]),"+f"(d[6]),"+f"(d[7]),"+f"(d[8]),"+f"(d[9]),"+f"(d[10]),"+f"(d[11]),"+f"(d[12]),"+f"(d[13]),"+f"(d[14]),"+f"(d[15]),"+f"(d[16]),"+f"(d[17]),"+f"(d[18]),"+f"(d[19]),"+f"(d[20]),"+f"(d[21]),"+f"(d[22]),"+f"(d[23]),"+f"(d[24]),"+f"(d[25]),"+f"(d[26]),"+f"(d[27]),"+f"(d[28]),"+f"(d[29]),"+f"(d[30]),"+f"(d[31]),"+f"(d[32]),"+f"(d[33]),"+f"(d[34]),"+f"(d[35])
    : "r"(descA), "r"(descB), "r"(scaleD));
}

constexpr float LOG2E = 1.4426950408889634f;

__device__ __forceinline__ void feat_exp(const uint32_t (&P)[4], float (&e)[16]) {
  uint32_t a = hmax2(P[0], P[2]), b = hmax2(P[1], P[3]);
  uint32_t mx = hmax2(__byte_perm(a, b, 0x5410), __byte_perm(a, b, 0x7632));
  a = hmin2(P[0], P[2]); b = hmin2(P[1], P[3]);
  uint32_t mn = hmin2(__byte_perm(a, b, 0x5410), __byte_perm(a, b, 0x7632));
  mx = hmax2(mx, __shfl_xor_sync(0xffffffffu, mx, 1));
  mn = hmin2(mn, __shfl_xor_sync(0xffffffffu, mn, 1));
  mx = hmax2(mx, __shfl_xor_sync(0xffffffffu, mx, 2));
  mn = hmin2(mn, __shfl_xor_sync(0xffffffffu, mn, 2));
  float mx0 = -blo(mx) * LOG2E, mx1 = -bhi(mx) * LOG2E, mn0 = blo(mn) * LOG2E, mn1 = bhi(mn) * LOG2E;
  float v[8] = {blo(P[0]), bhi(P[0]), blo(P[1]), bhi(P[1]), blo(P[2]), bhi(P[2]), blo(P[3]), bhi(P[3])};
#pragma unroll
  for (int i = 0; i < 8; i++) {
    bool r1 = (i >> 1) & 1;
    e[i]     = ex2(fmaf(v[i],  LOG2E, r1 ? mx1 : mx0));
    e[8 + i] = ex2(fmaf(v[i], -LOG2E, r1 ? mn1 : mn0));
  }
}

__global__ void __cluster_dims__(2, 1, 1) __launch_bounds__(384, 1)
fused_kernel(const __grid_constant__ Maps maps, const __nv_bfloat16* __restrict__ wphi,
             const __nv_bfloat16* __restrict__ wo, const __nv_bfloat16* __restrict__ wg_, const __nv_bfloat16* __restrict__ wu_,
             const __nv_bfloat16* __restrict__ wd_, __nv_bfloat16* __restrict__ out) {
  extern __shared__ __align__(1024) unsigned char smem[];
  const uint32_t sb = smem_u32(smem);
  const int tid = threadIdx.x, lane = tid & 31;
  const int warp = __shfl_sync(0xffffffffu, tid >> 5, 0);
  const uint32_t rank = blockIdx.x & 1;
  const int cl = blockIdx.x >> 1;
  int quad, qi;
  if (cl < 4) { quad = 15; qi = cl; }
  else if (cl < 36) { quad = (cl - 4) & 7; qi = (cl - 4) >> 3; }
  else { qi = (cl - 36) / 7; quad = 8 + (cl - 36) - 7 * qi; }
  const int rb = quad, hg = 2 * qi + rank;
  const int rb3 = (quad & ~1) + rank, jf = 4 * (quad & 1) + qi;

  if (warp < 8) {
    asm volatile("setmaxnreg.inc.sync.aligned.u32 240;");
    if (elect_one()) {
#pragma unroll 1
      for (int d = warp; d + 9 < NSTAGE; d += 8) {
        mbar_init(sb + SM_EMPTY + d * 8, st_empty_cnt(d));
        mbar_init(sb + SM_FULL + (d + 9) * 8, 1);
        mbar_expect_tx(sb + SM_FULL + (d + 9) * 8, d + 9 >= ST_D ? 22528 : SLOT);
      }
      asm volatile("fence.mbarrier_init.release.cluster;" ::: "memory");
    }
    __syncwarp();
    bar_sync(0, 352);
    asm volatile("barrier.cluster.arrive.relaxed.aligned;" ::: "memory");
    const int wg = warp >> 2, wq = warp & 3, g = lane >> 2, t = lane & 3;
    const bool lead = (tid & 127) == 0;
    constexpr uint32_t db = (SM_BASE >> 4) | (512u << 16);
    auto release = [&](int d) {
      const int s = d + NSLOT;
      mbar_arrive_cluster(sb + SM_EMPTY + d * 8, s >= ST_GU ? (uint32_t)(s & 1) : rank);
    };
    const uint32_t lrow = (uint32_t)(wq * 16 + (lane & 7) + ((lane >> 3) & 1) * 8) * 128;
    const uint32_t lx = lane & 7, lhi = lane >> 4;
    if (wg == 1) bar_arrive(4, 256);

    float r0, r1;
    uint32_t E[4][8];
    uint32_t xr[4][4];
    uint32_t T = 0;
    {
      uint32_t A[32][4];
      const int sx = wg ? ST_X1 : ST_X0;
      {
        const uint32_t base = sb + sx * SLOT + lrow, baseb = sb + sx * SLOT + (wq * 16 + lx + lhi * 8) * 128;
        float cs[2][4], c0[2][4], c1[2][4];
#pragma unroll
        for (int i = 0; i < 4; i++) { cs[0][i] = cs[1][i] = c0[0][i] = c0[1][i] = c1[0][i] = c1[1][i] = 0.f; }
        uint32_t bt[2][4][4];
        if (wg == 1) bar_sync(13, 256);
#pragma unroll
        for (int c = -1; c < 8; c++) {
          if (c < 7) {
            const int n = c + 1;
            if (n % 3 == 0) mbar_wait(sb + SM_FULL + (sx + n / 3) * 8);
#pragma unroll
            for (int k = 0; k < 4; k++) {
              ldsm4(A[4 * n + k], base + n * 8192 + (((2 * k + lhi) ^ lx) << 4));
              ldsm4(bt[n & 1][k], baseb + n * 8192 + (((2 * k + ((lane >> 3) & 1)) ^ lx) << 4));
            }
          }
          if (c >= 0) {
#pragma unroll
            for (int k = 0; k < 4; k++) {
              const uint32_t (&f)[4] = A[4 * c + k];
              mma16816(cs[k & 1], f, 0x3F803F80u, 0x3F803F80u);
              mma16816(c0[k & 1], f, bt[c & 1][k][0], bt[c & 1][k][1]);
              mma16816(c1[k & 1], f, bt[c & 1][k][2], bt[c & 1][k][3]);
            }
          }
        }
        if (wg == 0) bar_arrive(13, 256);
        const float s0 = (cs[0][0] + cs[1][0]) * (1.f / 512.f), s1 = (cs[0][2] + cs[1][2]) * (1.f / 512.f);
        asm volatile("barrier.cluster.wait.aligned;" ::: "memory");
        if (lane < 3) release(sx + lane);
        const uint32_t m0 = pack2(s0, s0), m1 = pack2(s1, s1);
        float q0 = (g & 1) ? c0[0][1] + c0[1][1] : c0[0][0] + c0[1][0];
        float q1 = (g & 1) ? c1[0][3] + c1[1][3] : c1[0][2] + c1[1][2];
        q0 = __shfl_sync(0xffffffffu, q0, (lane & ~3) | (g >> 1));
        q1 = __shfl_sync(0xffffffffu, q1, (lane & ~3) | (g >> 1));
        r0 = rsqrtf(fmaxf(q0 * (1.f / 512.f) - s0 * s0, 0.f) + 1e-5f);
        r1 = rsqrtf(fmaxf(q1 * (1.f / 512.f) - s1 * s1, 0.f) + 1e-5f);
#pragma unroll
        for (int ks = 0; ks < 32; ks++) {
          A[ks][0] = hsub2(A[ks][0], m0); A[ks][1] = hsub2(A[ks][1], m1);
          A[ks][2] = hsub2(A[ks][2], m0); A[ks][3] = hsub2(A[ks][3], m1);
        }
      }
      const uint32_t wpa = sb + SM_WPHI + ((lane & 7) + ((lane >> 3) & 1) * 8) * 32 + lhi * 16;
      const uint32_t scr = sb + (wg ? (ST_SCR1 % NSLOT) : (ST_SCR0 % NSLOT)) * SLOT;
#pragma unroll 1
      for (int ps = 0; ps < 3; ps++) {
        const int st0 = ps == 0 ? ST_WK : (ps == 1 ? ST_WV : ST_WQ);
        const uint32_t wdesc = DESC((ps == 0 ? ST_WK % NSLOT : (ps == 1 ? ST_WV % NSLOT : ST_WQ % NSLOT)) * SLOT);
        float acc[32];
        bar_sync(4 + wg, 256);
#pragma unroll
        for (int i = 0; i < 3; i++) {
          mbar_wait(sb + SM_FULL + (st0 + i) * 8);
          wg_fence();
#pragma unroll
          for (int kk = 0; kk < (i < 2 ? 12 : 8); kk++)
            wgmma_rs_n64(acc, A[12 * i + kk], wdesc + ((i * SLOT + kk * 2048) >> 4), (i | kk) != 0);
          wg_commit();
          if (i == 1) { wg_wait<1>(); if (lead) release(st0); }
        }
        if (ps == 1 && wg == 0) bar_arrive(5, 256);
        uint32_t a[4][4], b[4][4];
        mbar_wait(sb + SM_MISCB);
        T = (*reinterpret_cast<volatile unsigned*>(smem + SM_EPOCH) & 1) ^ 1;
#pragma unroll
        for (int h = 0; h < 4; h++) ldsm4t(b[h], wpa + h * 512);
        wg_wait<0>();
        if (ps == 2) {
          mbar_wait(sb + SM_XRB);
#pragma unroll
          for (int k = 0; k < 4; k++)
            ldsm4(A[8 + k], sb + (wg ? (ST_WQ + 2) % NSLOT : (ST_WV + 2) % NSLOT) * SLOT + 16384 + lrow + (((2 * k + lhi) ^ lx) << 4));
          bar_sync(1 + wg, 128);
        }
        if ((tid & 127) < 2) release(st0 + 1 + (tid & 1));
#pragma unroll
        for (int h = 0; h < 4; h++) {
          a[h][0] = pack2(acc[8 * h + 0] * r0, acc[8 * h + 1] * r0); a[h][1] = pack2(acc[8 * h + 2] * r1, acc[8 * h + 3] * r1);
          a[h][2] = pack2(acc[8 * h + 4] * r0, acc[8 * h + 5] * r0); a[h][3] = pack2(acc[8 * h + 6] * r1, acc[8 * h + 7] * r1);
        }
        if (ps != 1) {
          {
            float pp[4][2][4];
#pragma unroll
            for (int h = 0; h < 4; h++) {
#pragma unroll
              for (int i = 0; i < 4; i++) { pp[h][0][i] = 0.f; pp[h][1][i] = 0.f; }
              mma16816(pp[h][0], a[h], b[h][0], b[h][1]);
              mma16816(pp[h][1], a[h], b[h][2], b[h][3]);
            }
#pragma unroll
            for (int h = 0; h < 4; h++) {
              a[h][0] = pack2(pp[h][0][0], pp[h][0][1]); a[h][1] = pack2(pp[h][0][2], pp[h][0][3]);
              a[h][2] = pack2(pp[h][1][0], pp[h][1][1]); a[h][3] = pack2(pp[h][1][2], pp[h][1][3]);
            }
          }
          if (ps == 0 || wg == 0) bar_arrive(4 + (wg ^ 1), 256);
          if (ps == 0) mbar_wait(sb + SM_EMPTY + (wg ? ST_SCR1 - NSLOT : ST_SCR0 - NSLOT) * 8);
          {
            float e[4][16];
#pragma unroll
            for (int h = 0; h < 4; h++) feat_exp(a[h], e[h]);
            if (ps == 0) {
#pragma unroll
              for (int h = 0; h < 4; h++) {
                const float (&f)[16] = e[h];
                float sp0 = (f[0] + f[1]) + (f[4] + f[5]), sp1 = (f[2] + f[3]) + (f[6] + f[7]);
                float sn0 = (f[8] + f[9]) + (f[12] + f[13]), sn1 = (f[10] + f[11]) + (f[14] + f[15]);
                sp0 += __shfl_xor_sync(0xffffffffu, sp0, 1); sp1 += __shfl_xor_sync(0xffffffffu, sp1, 1);
                sn0 += __shfl_xor_sync(0xffffffffu, sn0, 1); sn1 += __shfl_xor_sync(0xffffffffu, sn1, 1);
                sp0 += __shfl_xor_sync(0xffffffffu, sp0, 2); sp1 += __shfl_xor_sync(0xffffffffu, sp1, 2);
                sn0 += __shfl_xor_sync(0xffffffffu, sn0, 2); sn1 += __shfl_xor_sync(0xffffffffu, sn1, 2);
                sp0 = rcp(sp0); sp1 = rcp(sp1); sn0 = rcp(sn0); sn1 = rcp(sn1);
                const uint32_t dst = scr + (h >> 1) * 8192 + lrow;
                stsm4(dst + ((((h & 1) * 4 + lhi) ^ lx) << 4), pack2(f[0] * sp0, f[1] * sp0), pack2(f[2] * sp1, f[3] * sp1),
                      pack2(f[4] * sp0, f[5] * sp0), pack2(f[6] * sp1, f[7] * sp1));
                stsm4(dst + ((((h & 1) * 4 + 2 + lhi) ^ lx) << 4), pack2(f[8] * sn0, f[9] * sn0), pack2(f[10] * sn1, f[11] * sn1),
                      pack2(f[12] * sn0, f[13] * sn0), pack2(f[14] * sn1, f[15] * sn1));
              }
            } else {
#pragma unroll
              for (int i = 0; i < 32; i++) A[i >> 2][i & 3] = pack2(e[i >> 3][2 * (i & 7)], e[i >> 3][2 * (i & 7) + 1]);
            }
          }
        } else {
#pragma unroll
          for (int h = 0; h < 4; h++) stsm4(scr + 16384 + lrow + (((2 * h + lhi) ^ lx) << 4), a[h][0], a[h][1], a[h][2], a[h][3]);
          fence_async_smem();
          if (wg == 0) {
            bar_arrive(3, 256);
          } else {
            bar_sync(3, 256);
            float kv[2][36];
            wg_fence();
#pragma unroll
            for (int ks = 0; ks < 8; ks++) {
              const uint32_t sk = (ks < 4 ? (ST_SCR0 % NSLOT) : (ST_SCR1 % NSLOT)) * SLOT + (ks & 3) * 2048;
              const uint32_t dv = (DESC(sk + 16384) & 0xFFFFu) | (((SM_ONES - sk - 16384) >> 4) << 16);
              wgmma_ss_n72_t11(kv[0], DESC(sk), dv, ks != 0);
              wgmma_ss_n72_t11(kv[1], DESC(sk + 8192), dv, ks != 0);
            }
            wg_commit();
            bar_arrive(4, 256);
            wg_wait<0>();
            if (lead) { mbar_arrive(sb + SM_EMPTY + ST_SCR0 * 8); mbar_arrive(sb + SM_EMPTY + ST_SCR1 * 8); }
            const bool up = wq >= 2;
            float* kvp = reinterpret_cast<float*>(smem + 2 * SLOT) + (wq * 16 + g) * 24;
#pragma unroll
            for (int i = 0; i < 4; i++) {
              const float (&c)[36] = kv[i >> 1];
              const int r = 16 * (i >> 1) + 2 * (i & 1);
              float* p = kvp + ((i >> 1) * 64 + (i & 1) * 8) * 24;
              *reinterpret_cast<float4*>(p + 4 * t) = make_float4(up ? c[r + 8] : c[r], up ? c[r + 9] : c[r + 1], up ? c[r + 12] : c[r + 4], 1.f);
              p[16 + t + (t == 3)] = up ? c[r + 13] : c[r + 5];
            }
            kvp[((t >> 1) * 64 + (t & 1) * 8) * 24 + 21] = (t & 2) ? ((t & 1) ? kv[1][34] : kv[1][32]) : ((t & 1) ? kv[0][34] : kv[0][32]);
            fence_async_smem();
            bar_sync(6, 192);
          }
        }
      }
#pragma unroll
      for (int i = 0; i < 32; i++) E[i >> 3][i & 7] = A[i >> 2][i & 3];
#pragma unroll
      for (int i = 0; i < 16; i++) xr[i >> 2][i & 3] = A[8 + (i >> 2)][i & 3];
    }
    const int rh = 2 * rb + wg;
#define IDF ((g >> 1) == t ? ((g & 1) ? 0x3F800000u : 0x00003F80u) : 0u)
    const uint4* xb = reinterpret_cast<const uint4*>(smem + 2 * SLOT) + wq * 128 + lane;
    if (wg == 0) {
      mbar_wait(sb + SM_KVB);
      const uint4* sp = reinterpret_cast<const uint4*>(smem + 3 * SLOT) + tid * 6;
      uint32_t v[6][4];
      int it = 0;
#pragma unroll 1
      do {
#pragma unroll
        for (int i = 0; i < 6; i++)
          asm volatile("{\n.reg .b128 v;\nld.relaxed.gpu.b128 v, [%4];\nmov.b128 {%0,%1,%2,%3}, v;\n}"
                       : "=r"(v[i][0]), "=r"(v[i][1]), "=r"(v[i][2]), "=r"(v[i][3]) : "l"(sp + i) : "memory");
        sp = reinterpret_cast<const uint4*>(&g_kv[hg][tid][0]);
      } while (min(min(min(v[0][3], v[1][3]), min(v[2][3], v[3][3])), min(v[4][3], v[5][3])) != 0x41800000u && ++it < (1 << 18));
#define KVF(d) __uint_as_float((d) < 8 ? v[(d) / 2][(d) & 1] : (d) >= 15 ? v[5][((d) - 15) & 1] : ((d) & 1) ? v[4][(((d) - 9) / 2) & 3] : v[(((d) - 8) / 2) & 3][2])
      uint4* dst = reinterpret_cast<uint4*>(smem + SM_KVS + tid * 48);
      const uint32_t zz = pack2(KVF(16), 1.0f);
      dst[0] = make_uint4(pack2(KVF(0), KVF(1)), pack2(KVF(2), KVF(3)), pack2(KVF(4), KVF(5)), pack2(KVF(6), KVF(7)));
      dst[1] = make_uint4(pack2(KVF(8), KVF(9)), pack2(KVF(10), KVF(11)), pack2(KVF(12), KVF(13)), pack2(KVF(14), KVF(15)));
      dst[2] = make_uint4(zz, zz, zz, zz);
      __syncwarp();
      bar_sync(1, 128);
    }
    {
      uint4* op = &g_s[rh].o[hg][wq][0][lane];
      if (wg == 1) bar_sync(7, 256);
#pragma unroll 1
      for (int hp = 0; hp < 2; hp++) {
#pragma unroll
      for (int h = 0; h < 2; h++) {
        uint32_t b0[4], b1[4], b2[4];
        const uint32_t kb = sb + SM_KVS + ((2 * hp + h) * 32 + lane) * 48;
        ldsm4t(b0, kb); ldsm4t(b1, kb + 16); ldsm4t(b2, kb + 32);
        const uint32_t ep[4] = {E[h][0], E[h][1], E[h][2], E[h][3]}, en[4] = {E[h][4], E[h][5], E[h][6], E[h][7]};
        float np0[4] = {0, 0, 0, 0}, np1[4] = {0, 0, 0, 0}, nn0[4] = {0, 0, 0, 0}, nn1[4] = {0, 0, 0, 0}, dp[4] = {0, 0, 0, 0}, dn[4] = {0, 0, 0, 0};
        mma16816(dp, ep, b2[0], b2[1]);  mma16816(dn, en, b2[2], b2[3]);
        mma16816(np0, ep, b0[0], b0[1]); mma16816(nn0, en, b0[2], b0[3]);
        mma16816(np1, ep, b1[0], b1[1]); mma16816(nn1, en, b1[2], b1[3]);
        const float i0 = rcp(fmaf(dp[0], dn[1], fmaf(dn[0], dp[1], 1e-6f * dp[1] * dn[1])));
        const float i1 = rcp(fmaf(dp[2], dn[3], fmaf(dn[2], dp[3], 1e-6f * dp[3] * dn[3])));
        const float cp0 = dn[1] * i0, cn0 = dp[1] * i0, cp1 = dn[3] * i1, cn1 = dp[3] * i1;
        st_rlx4(op + (2 * hp + h) * 32,
                tg(pack2(fmaf(np0[0], cp0, nn0[0] * cn0), fmaf(np0[1], cp0, nn0[1] * cn0)), T),
                pack2(fmaf(np0[2], cp1, nn0[2] * cn1), fmaf(np0[3], cp1, nn0[3] * cn1)),
                pack2(fmaf(np1[0], cp0, nn1[0] * cn0), fmaf(np1[1], cp0, nn1[1] * cn0)),
                pack2(fmaf(np1[2], cp1, nn1[2] * cn1), fmaf(np1[3], cp1, nn1[3] * cn1)));
      }
#pragma unroll
        for (int i = 0; i < 8; i++) { E[0][i] = E[2][i]; E[1][i] = E[3][i]; }
      }
    }
    if (wg == 0) bar_arrive(7, 256);
    bar_arrive(10 + wg, 160);

    {
      uint32_t A[8][4][4];
      const uint4* op = &g_s[rh].o[0][wq][0][lane];
      float acc[32];
#pragma unroll
      for (int i = 0; i < 32; i++) acc[i] = 0.f;
      add_frag(acc, xr, IDF);
#pragma unroll
      for (int p = -1; p < 4; p++) {
        if (p < 3) {
          mbar_wait(sb + SM_XF + (wg * 4 + p + 1) * 8);
          get_pair(A[2 * p + 2], A[2 * p + 3], xb + (p + 1) * 1024, op + (p + 1) * 1024, T);
          if (lane == 0) mbar_arrive(sb + SM_XE + (wg * 4 + p + 1) * 8);
        }
        if (p == 0 && wg == 1) bar_sync(14, 256);
        if (p >= 0) {
          if (p != 2) mbar_wait(sb + SM_FULL + (ST_WO + (p + 1) / 2) * 8);
          wg_fence();
#pragma unroll
          for (int c = 2 * p; c < 2 * p + 2; c++)
#pragma unroll
            for (int s = 0; s < 4; s++)
              wgmma_rs_n64(acc, A[c][s], DESC(((ST_WO + c / 3) % NSLOT) * SLOT + ((c % 3) * 4 + s) * 2048), 1);
        }
      }
      wg_commit();
      if (wg == 0) bar_arrive(14, 256);
      wg_wait<0>();
      if ((tid & 127) < 3) release(ST_WO + (tid & 127));
      uint4* hp_ = &g_s[rh].h[hg][wq][0][lane];
      uint32_t hx = T;
#pragma unroll
      for (int s = 0; s < 4; s++) {
        const uint32_t h0 = pack2(acc[8 * s], acc[8 * s + 1]);
        st_rlx4(hp_ + s * 32, tg(h0, T), pack2(acc[8 * s + 2], acc[8 * s + 3]), pack2(acc[8 * s + 4], acc[8 * s + 5]), pack2(acc[8 * s + 6], acc[8 * s + 7]));
        hx |= (h0 & 1u) << (s + 1);
      }
      float s0 = 0.f, s1 = 0.f, q0 = 0.f, q1 = 0.f, q2 = 0.f, q3 = 0.f;
#pragma unroll
      for (int i = 0; i < 8; i++) {
        s0 += acc[4 * i] + acc[4 * i + 1]; s1 += acc[4 * i + 2] + acc[4 * i + 3];
        q0 = fmaf(acc[4 * i], acc[4 * i], q0); q2 = fmaf(acc[4 * i + 1], acc[4 * i + 1], q2);
        q1 = fmaf(acc[4 * i + 2], acc[4 * i + 2], q1); q3 = fmaf(acc[4 * i + 3], acc[4 * i + 3], q3);
      }
      q0 += q2; q1 += q3;
      {
        const bool up = t & 2;
        float s = (up ? s1 : s0) + __shfl_xor_sync(0xffffffffu, up ? s0 : s1, 2);
        float q = (up ? q1 : q0) + __shfl_xor_sync(0xffffffffu, up ? q0 : q1, 2);
        s += __shfl_xor_sync(0xffffffffu, s, 1);
        q += __shfl_xor_sync(0xffffffffu, q, 1);
        if (!(t & 1)) st_rlx2(&g_s[rh].st[hg][wq * 16 + g + (t >> 1) * 8], tg(__float_as_uint(s), T), __float_as_uint(q));
      }
      st_rlx1(&g_s[rh].hx[hg][wq][lane], hx);
    }
    bar_arrive(10 + wg, 160);

    const int rh3 = 2 * rb3 + wg;
    uint32_t HH[11][4], PH[11][4];
    const uint4* pp = &g_s[rh3].hh[jf ^ 1][0][wq][lane];
    {
      uint32_t A[8][4][4];
      const uint4* hp_ = &g_s[rh3].h[0][wq][0][lane];
      uint4* hhp = &g_s[rh3].hh[jf][0][wq][lane];
      const uint32_t dg = (db & 0xFFFFu) | (256u << 16);
      uint32_t m0, m1;
      mbar_wait(sb + SM_XF + ((2 + wg) * 4) * 8);
      {
        const uint2* sp = reinterpret_cast<const uint2*>(smem + SM_KV32 + wg * 4096) + 2 * t * 64 + wq * 16 + g;
        uint2 a0, a1, b0, b1;
        int it = 0;
#pragma unroll 1
        do {
          ld_rlx2(a0.x, a0.y, sp); ld_rlx2(a1.x, a1.y, sp + 64); ld_rlx2(b0.x, b0.y, sp + 8); ld_rlx2(b1.x, b1.y, sp + 72);
          sp = &g_s[rh3].st[2 * t][wq * 16 + g];
        } while (__any_sync(0xffffffffu, bad4(a0.x, a1.x, b0.x, b1.x, T)) && ++it < (1 << 18));
        float s0 = __uint_as_float(a0.x) + __uint_as_float(a1.x), q0 = __uint_as_float(a0.y) + __uint_as_float(a1.y);
        float s1 = __uint_as_float(b0.x) + __uint_as_float(b1.x), q1 = __uint_as_float(b0.y) + __uint_as_float(b1.y);
        s0 += __shfl_xor_sync(0xffffffffu, s0, 1); s1 += __shfl_xor_sync(0xffffffffu, s1, 1);
        q0 += __shfl_xor_sync(0xffffffffu, q0, 1); q1 += __shfl_xor_sync(0xffffffffu, q1, 1);
        s0 += __shfl_xor_sync(0xffffffffu, s0, 2); s1 += __shfl_xor_sync(0xffffffffu, s1, 2);
        q0 += __shfl_xor_sync(0xffffffffu, q0, 2); q1 += __shfl_xor_sync(0xffffffffu, q1, 2);
        s0 *= (1.f / 512.f); s1 *= (1.f / 512.f);
        r0 = rcp(fmaxf(q0 * (1.f / 512.f) - s0 * s0, 0.f) + 1e-5f);
        r1 = rcp(fmaxf(q1 * (1.f / 512.f) - s1 * s1, 0.f) + 1e-5f);
        m0 = pack2(s0, s0); m1 = pack2(s1, s1);
      }
#define UOFF(u) ((((ST_GU + (u) / 3) % NSLOT) * SLOT + ((u) % 3) * 8192) >> 4)
#define UNIT_PRE(u)  do { if ((u) % 3 == 0) mbar_wait(sb + SM_FULL + (ST_GU + (u) / 3) * 8); } while (0)
#define UNIT_POST(u) do { wg_commit(); if ((u) % 3 == 1 && (u) > 3) { wg_wait<2>(); if (lead) release(ST_GU + (u) / 3 - 1); } } while (0)
      float acc[64];
      const int rz = blockIdx.y;
#pragma unroll
      for (int ps = 0; ps < 2; ps++) {
        wg_fence();
#pragma unroll
        for (int k = 0; k < 16; k++) {
          const int u = 16 * ps + k, c = k >> 1;
          if (ps == 0 && (k == 0 || k == 4 || k == 8)) {
#pragma unroll
            for (int p = (k == 0 ? 0 : (k == 4 ? 1 : 3)); p < (k == 0 ? 1 : (k == 4 ? 3 : 4)); p++) {
              if (p > 0) mbar_wait(sb + SM_XF + ((2 + wg) * 4 + p) * 8);
              get_pair(A[2 * p], A[2 * p + 1], xb + p * 1024, hp_ + p * 1024, T);
              if (lane == 0) {
                if (wg == 0) mbar_arrive(sb + SM_XE + (8 + p) * 8);
                else if (p > 0) release(ST_XC + p - 1);
              }
            }
          }
          if (ps == 0 && (k & 1) == 0) {
#pragma unroll
            for (int s = 0; s < 4; s++) {
              A[c][s][0] = hsub2(A[c][s][0], m0); A[c][s][1] = hsub2(A[c][s][1], m1);
              A[c][s][2] = hsub2(A[c][s][2], m0); A[c][s][3] = hsub2(A[c][s][3], m1);
            }
            wg_fence();
          }
          UNIT_PRE(u);
          wgmma_rs_n128(acc, A[c][(k & 1) * 2], dg + UOFF(u), k != 0 ? 1 : (ps ? rz : 0));
          wgmma_rs_n128(acc, A[c][(k & 1) * 2 + 1], dg + UOFF(u) + 128, 1);
          UNIT_POST(u);
        }
        wg_wait<0>();
#pragma unroll
        for (int s = 0; s < 4; s++) {
          uint32_t (&hh)[4] = HH[4 + s];
          hh[0] = tg(pack2(acc[8 * s + 0] * acc[32 + 8 * s + 0], acc[8 * s + 1] * acc[32 + 8 * s + 1]), T);
          hh[1] = pack2(acc[8 * s + 2] * acc[32 + 8 * s + 2], acc[8 * s + 3] * acc[32 + 8 * s + 3]);
          hh[2] = pack2(acc[8 * s + 4] * acc[32 + 8 * s + 4], acc[8 * s + 5] * acc[32 + 8 * s + 5]);
          hh[3] = pack2(acc[8 * s + 6] * acc[32 + 8 * s + 6], acc[8 * s + 7] * acc[32 + 8 * s + 7]);
          st_rlx4(hhp + (4 * ps + s) * 128, hh[0], hh[1], hh[2], hh[3]);
        }
      }
      {
        float ag[24], au[24];
        const uint32_t* ph7 = reinterpret_cast<const uint32_t*>(&g_s[rh3].hh[jf ^ 1][7][wq][31]);
        uint32_t hv = 0;
        bar_sync(1 + wg, 128);
        wg_fence();
#pragma unroll
        for (int k = 0; k < 16; k++) {
          const int u = 32 + k, c = k >> 1;
          if (k == 6) {
#pragma unroll
            for (int s = 0; s < 4; s++) ld_rlx4(HH[s], hhp + s * 128);
          }
          if (k == 9) hv = ld_rlx1(ph7);
          if (k == 12) {
            int it = 0;
#pragma unroll 1
            while (((hv ^ T) & 1) && ++it < (1 << 18)) hv = ld_rlx1(ph7);
#pragma unroll
            for (int s = 0; s < 8; s++) ld_rlx4(PH[s], pp + s * 128);
          }
          UNIT_PRE(u);
          wgmma_rs_n48(ag, A[c][(k & 1) * 2], dg + UOFF(u), k != 0);
          wgmma_rs_n48(au, A[c][(k & 1) * 2], dg + UOFF(u) + 256, k != 0);
          wgmma_rs_n48(ag, A[c][(k & 1) * 2 + 1], dg + UOFF(u) + 128, 1);
          wgmma_rs_n48(au, A[c][(k & 1) * 2 + 1], dg + UOFF(u) + 256 + 128, 1);
          UNIT_POST(u);
        }
        wg_wait<0>();
#pragma unroll
        for (int s = 0; s < 3; s++) {
          uint32_t (&hh)[4] = HH[8 + s];
          hh[0] = tg(pack2(ag[8 * s + 0] * au[8 * s + 0], ag[8 * s + 1] * au[8 * s + 1]), T);
          hh[1] = pack2(ag[8 * s + 2] * au[8 * s + 2], ag[8 * s + 3] * au[8 * s + 3]);
          hh[2] = pack2(ag[8 * s + 4] * au[8 * s + 4], ag[8 * s + 5] * au[8 * s + 5]);
          hh[3] = pack2(ag[8 * s + 6] * au[8 * s + 6], ag[8 * s + 7] * au[8 * s + 7]);
          st_rlx4(hhp + (8 + s) * 128, hh[0], hh[1], hh[2], hh[3]);
        }
      }
    }

    {
      float acc[32];
      uint32_t hr[4][4], hx = 0;
      const int m = jf >> 1, oc = (jf & 1) * 4 + m;
      const uint32_t* ph10 = reinterpret_cast<const uint32_t*>(&g_s[rh3].hh[jf ^ 1][10][wq][31]);
      uint4* outb = &g_s[rh3].part[(jf & 1) * 4][m][wq][0][lane];
      bar_arrive(8 + wg, 256);
      int s0 = ST_D % NSLOT;
#pragma unroll 1
      for (int k = 0; k < 4; k++) {
        const int s1 = s0 + 1 == NSLOT ? 0 : s0 + 1;
        const uint32_t d0 = db + s0 * (SLOT >> 4), d1 = db + s1 * (SLOT >> 4);
        wg_wait<0>();
        if (k > 0) {
          uint4* p = outb + ((m + k) & 3) * 2048;
#pragma unroll
          for (int s = 0; s < 4; s++)
            st_rlx4(p + s * 32, tg(pack2(acc[8 * s], acc[8 * s + 1]), T), pack2(acc[8 * s + 2], acc[8 * s + 3]),
                    pack2(acc[8 * s + 4], acc[8 * s + 5]), pack2(acc[8 * s + 6], acc[8 * s + 7]));
          if (k == 1) bar_arrive(12, 320);
        } else {
          int it = 0;
#pragma unroll 1
          while (__any_sync(0xffffffffu, bad4(PH[0][0], PH[1][0], PH[2][0], PH[3][0], T) | bad4(PH[4][0], PH[5][0], PH[6][0], PH[7][0], T)) && ++it < (1 << 18)) {
#pragma unroll
            for (int s = 0; s < 8; s++) ld_rlx4(PH[s], pp + s * 128);
          }
        }
        mbar_wait(sb + SM_FULL + (ST_D + 2 * k) * 8);
        mbar_wait(sb + SM_FULL + (ST_D + 2 * k + 1) * 8);
        wg_fence();
#pragma unroll
        for (int s = 0; s < 11; s++) wgmma_rs_n64(acc, HH[s], d0 + s * 128, s != 0);
#pragma unroll
        for (int s = 0; s < 8; s++) wgmma_rs_n64(acc, PH[s], d1 + s * 128, 1);
        if (k == 0) {
          int it = 0;
#pragma unroll 1
          while (((ld_rlx1(ph10) ^ T) & 1) && ++it < (1 << 18)) {}
          ld_chunk(hr, &g_s[rh3].h[oc][wq][0][lane]);
#pragma unroll 1
          do {
            hx = ld_rlx1(&g_s[rh3].hx[oc][wq][lane]);
#pragma unroll
            for (int s = 8; s < 11; s++) ld_rlx4(PH[s], pp + s * 128);
          } while (__any_sync(0xffffffffu, bad4(PH[8][0], PH[9][0], PH[10][0], hx, T)) && ++it < (1 << 18));
          wg_fence();
        }
#pragma unroll
        for (int s = 8; s < 11; s++) wgmma_rs_n64(acc, PH[s], d1 + s * 128, 1);
        wg_commit();
        s0 = s1 + 1 == NSLOT ? 0 : s1 + 1;
      }
      wg_wait<0>();
#pragma unroll 1
      for (int q = 0; q < 3; q++) {
        uint32_t in[4][4];
        const uint4* sp = reinterpret_cast<const uint4*>(smem + ((ST_D % NSLOT) + wg) * SLOT) + q * 512 + wq * 128 + lane;
        mbar_wait_p(sb + SM_XF + (wg * 4 + q) * 8, 1);
        int it = 0;
#pragma unroll 1
        do {
#pragma unroll
          for (int s = 0; s < 4; s++)
            asm volatile("{\n.reg .b128 v;\nld.relaxed.gpu.b128 v, [%4];\nmov.b128 {%0,%1,%2,%3}, v;\n}"
                         : "=r"(in[s][0]), "=r"(in[s][1]), "=r"(in[s][2]), "=r"(in[s][3]) : "l"(sp + s * 32) : "memory");
          sp = &g_s[rh3].part[oc][(m - 1 - q) & 3][wq][0][lane];
        } while (__any_sync(0xffffffffu, bad4(in[0][0], in[1][0], in[2][0], in[3][0], T)) && ++it < (1 << 18));
        add_frag(acc, in, IDF);
      }
#pragma unroll
      for (int s = 0; s < 4; s++) hr[s][0] = (hr[s][0] & 0xFFFFFFFEu) | ((hx >> (s + 1)) & 1u);
#pragma unroll
      for (int i = 0; i < 32; i++) acc[i] *= (i & 2) ? r1 : r0;
      add_frag(acc, hr, IDF);
      bar_sync(9 - wg, 256);
      const uint32_t ob = sb + ((ST_D - 1) % NSLOT) * SLOT + wg * 8192;
#pragma unroll
      for (int s = 0; s < 4; s++)
        stsm4(ob + lrow + (((2 * s + lhi) ^ lx) << 4), pack2(acc[8 * s + 0], acc[8 * s + 1]), pack2(acc[8 * s + 2], acc[8 * s + 3]),
              pack2(acc[8 * s + 4], acc[8 * s + 5]), pack2(acc[8 * s + 6], acc[8 * s + 7]));
      __syncwarp();
      {
        const int row = wq * 16 + (lane >> 3);
        __nv_bfloat16* op = out + (size_t)(rh3 * 64 + row) * 512 + oc * 64 + lx * 8;
#pragma unroll
        for (int i = 0; i < 4; i++) {
          uint4 v;
          asm volatile("ld.shared.v4.b32 {%0,%1,%2,%3}, [%4];" : "=r"(v.x), "=r"(v.y), "=r"(v.z), "=r"(v.w)
                       : "r"(ob + (row + i * 4) * 128 + ((lx ^ (((lane >> 3) + i * 4) & 7)) << 4)) : "memory");
          asm volatile("st.global.v4.b32 [%0], {%1,%2,%3,%4};" ::"l"(op + i * 2048), "r"(v.x), "r"(v.y), "r"(v.z), "r"(v.w) : "memory");
        }
      }
    }
    asm volatile("barrier.cluster.arrive.relaxed.aligned;" ::: "memory");
    asm volatile("barrier.cluster.wait.aligned;" ::: "memory");
  } else {
    asm volatile("setmaxnreg.dec.sync.aligned.u32 24;");
    if (elect_one()) {
      if (warp == 8) {
#pragma unroll
        for (int k = 0; k < 9; k++) {
          const int s = k < 3 ? k : (k < 6 ? k + 3 : k - 3);
          const uint32_t bar = sb + SM_FULL + s * 8;
          mbar_init(bar, 1);
          mbar_expect_tx(bar, SLOT);
          if (s >= 3 && s < 6) tma2d(sb + s * SLOT, &maps.w, 512 + hg * 64, (s - 3) * 192, bar);
          else tma3d(sb + s * SLOT, &maps.x, 0, rb * 128 + (s >= 6 ? 64 : 0), 3 * (s % 3), bar);
        }
      } else if (warp == 9) {
        mbar_init(sb + SM_MISCB, 2);
        mbar_init(sb + SM_KVB, 2);
        mbar_init(sb + SM_XRB, 1);
        mbar_expect_tx(sb + SM_XRB, 16384);
        mbar_expect_tx(sb + SM_KVB, 12288);
        mbar_expect_tx(sb + SM_MISCB, 2048);
        bulk_g2s(sb + SM_WPHI, wphi + hg * 1024, 2048, sb + SM_MISCB);
      } else if (warp == 10) {
        if ((sb & 0x3FFFF) != SM_BASE) __trap();
#pragma unroll 1
        for (int i = 0; i < 16; i++) {
          mbar_init(sb + SM_XF + i * 8, 1);
          mbar_expect_tx(sb + SM_XF + i * 8, (i == 8 || i == 12) ? 20480 : 16384);
          if (i < 12) mbar_init(sb + SM_XE + i * 8, 4);
        }
      } else {
        *reinterpret_cast<volatile unsigned*>(smem + SM_EPOCH) = atomicAdd(&g_start, 1u) / NCTA;
      }
      asm volatile("fence.mbarrier_init.release.cluster;" ::: "memory");
    }
    __syncwarp();
    if (warp != 11) bar_sync(0, 352);
    asm volatile("barrier.cluster.arrive.relaxed.aligned;" ::: "memory");
    if (warp == 8) {
      asm volatile("barrier.cluster.wait.aligned;" ::: "memory");
      if (elect_one()) {
        const CUtensorMap* mg = jf == 7 ? &maps.g7 : &maps.g;
        const CUtensorMap* mu = jf == 7 ? &maps.u7 : &maps.u;
        asm volatile("prefetch.tensormap [%0];" ::"l"(&maps.wo) : "memory");
        asm volatile("prefetch.tensormap [%0];" ::"l"(mg) : "memory");
        asm volatile("prefetch.tensormap [%0];" ::"l"(mu) : "memory");
        asm volatile("prefetch.tensormap [%0];" ::"l"(&maps.d) : "memory");
#pragma unroll 1
        for (int i = ST_WV; i < ST_XC; i++) {
          if (i == ST_SCR1) continue;
          const int s = i >= 18 ? 37 - i : i;
          mbar_wait(sb + SM_EMPTY + (s - 9) * 8);
          const uint32_t dst = sb + (s >= 18 ? s - 18 : s - 9) * SLOT, bar = sb + SM_FULL + s * 8;
          if (s < ST_WO) tma2d(dst, &maps.w, (s < ST_WQ ? 1024 : 0) + hg * 64, (s < ST_WQ ? s - ST_WV : s - ST_WQ) * 192, bar);
          else {
            if (s != 19) mbar_wait(s == ST_WO ? bar - 8 : sb + SM_KVB);
            tma2d(dst, &maps.wo, hg * 64, (s - ST_WO) * 192, bar);
          }
        }
        const int jc = jf == 7 ? 0 : jf;
        int slot = (ST_GU + 1 - rank) % NSLOT;
#pragma unroll 1
        for (int s = ST_GU + 1 - rank; s < NSTAGE; s += 2) {
          mbar_wait(sb + SM_EMPTY + (s - 9) * 8);
          if (s < ST_GU + 6) mbar_wait(sb + SM_XF + (s < ST_GU + 3 ? 3 : 11) * 8);
          if (s > ST_GU + 3 && s < ST_GU + 6) mbar_wait(sb + SM_FULL + (s - 1) * 8);
          const uint32_t dst = sb + slot * SLOT, bar = sb + SM_FULL + s * 8;
          if (s < ST_D) {
#pragma unroll 1
            for (int i = 0; i < 3; i++) {
              const int u = (s - ST_GU) * 3 + i;
              tma3d_mc(dst + i * 8192, mg, (u >> 4) * 64, jc, (u & 15) * 32, bar);
              tma3d_mc(dst + i * 8192 + 4096, mu, (u >> 4) * 64, jc, (u & 15) * 32, bar);
            }
          } else {
            const int i = s - ST_D;
            tma2d_mc(dst, &maps.d, ((jf & 1) * 4 + (((jf >> 1) + 1 + (i >> 1)) & 3)) * 64, (jf ^ (i & 1)) * 176, bar);
          }
          slot += 2; if (slot >= NSLOT) slot -= NSLOT;
        }
      }
      __syncwarp();
    } else {
      asm volatile("barrier.cluster.wait.aligned;" ::: "memory");
      if (warp == 11) {
#pragma unroll
        for (int i = 0; i < 4; i++)
          reinterpret_cast<uint4*>(smem + SM_ONES)[lane + 32 * i] = make_uint4(0x3F803F80u, 0x3F803F80u, 0x3F803F80u, 0x3F803F80u);
        fence_async_smem();
        __syncwarp();
        if (lane == 0) mbar_arrive(sb + SM_MISCB);
      }
      mbar_wait(sb + SM_MISCB);
      const unsigned epoch = *reinterpret_cast<volatile unsigned*>(smem + SM_EPOCH);
      const uint32_t T = (epoch & 1) ^ 1;
      if (warp == 11) {
        (&g_kv[hg][rb * 8][0])[lane] = make_float4(0.f, 0.f, 0.f, 0.f);
        if (lane < 16) (&g_kv[hg][rb * 8][0])[32 + lane] = make_float4(0.f, 0.f, 0.f, 0.f);
        __syncwarp();
        if (elect_one()) asm volatile("red.release.gpu.global.add.u32 [%0], 8;" ::"l"(&g_kvcnt[hg * 32 + 1]) : "memory");
        mbar_wait(sb + SM_FULL + (ST_WK + 2) * 8);
        if (elect_one()) {
          asm volatile("cp.async.bulk.prefetch.L2.global [%0], 4096;" ::"l"((const char*)wo + blockIdx.x * 4096) : "memory");
          asm volatile("cp.async.bulk.prefetch.L2.global [%0], 11008;" ::"l"((const char*)wg_ + blockIdx.x * 11008) : "memory");
          asm volatile("cp.async.bulk.prefetch.L2.global [%0], 11008;" ::"l"((const char*)wu_ + blockIdx.x * 11008) : "memory");
          asm volatile("cp.async.bulk.prefetch.L2.global [%0], 11008;" ::"l"((const char*)wd_ + blockIdx.x * 11008) : "memory");
          mbar_wait(sb + SM_EMPTY + ST_SCR0 * 8);
          const unsigned target = (epoch + 1) * 128;
          unsigned v, z; int it = 0;
#pragma unroll 1
          do {
            asm volatile("{\n.reg .b64 q;\nld.acquire.gpu.global.b64 q, [%2];\nmov.b64 {%0, %1}, q;\n}" : "=r"(v), "=r"(z) : "l"(&g_kvcnt[hg * 32]) : "memory");
            if (++it > (1 << 18)) break;
          } while ((int)(v - target) < 0 || (int)(z - target) < 0);
          asm volatile("fence.proxy.async.global;" ::: "memory");
          bulk_g2s(sb + 3 * SLOT, &g_kv[hg][0][0], 12288, sb + SM_KVB);
        }
        __syncwarp();
      } else {
        const int w = warp - 9;
        st_rlx4(reinterpret_cast<uint4*>(&g_s[2 * rb + w].st[hg][0]) + lane, T ^ 1, T ^ 1, T ^ 1, T ^ 1);
        if (lane < 8) st_rlx4(&g_s[2 * rb + w].o[hg][lane >> 1][3][30 + (lane & 1)], T ^ 1, T ^ 1, T ^ 1, T ^ 1);
        st_rlx4(&g_s[2 * rb3 + w].part[(jf & 1) * 4 + (lane >> 3)][jf >> 1][(lane >> 1) & 3][3][30 + (lane & 1)], T ^ 1, T ^ 1, T ^ 1, T ^ 1);
        if (lane < 16) st_rlx4(&g_s[2 * rb3 + w].hh[jf][7 + (lane >> 3) * 3][(lane >> 1) & 3][30 + (lane & 1)], T ^ 1, T ^ 1, T ^ 1, T ^ 1);
        if (w == 0) {
          mbar_wait(sb + SM_FULL + (ST_WV + 2) * 8);
          mbar_wait(sb + SM_FULL + (ST_WQ + 2) * 8);
          if (elect_one()) {
            tma2d(sb + ((ST_WV + 2) % NSLOT) * SLOT + 16384, &maps.xr, hg * 64, rb * 128, sb + SM_XRB);
            tma2d(sb + ((ST_WQ + 2) % NSLOT) * SLOT + 16384, &maps.xr, hg * 64, rb * 128 + 64, sb + SM_XRB);
          }
          __syncwarp();
          unsigned v; int it = 0;
#pragma unroll 1
          do {
            asm volatile("ld.acquire.gpu.global.u32 %0, [%1];" : "=r"(v) : "l"(&g_kvcnt[hg * 32 + 1]) : "memory");
          } while ((int)(v - (epoch + 1) * 128) < 0 && ++it < (1 << 18));
          asm volatile("fence.proxy.async.global;" ::: "memory");
        }
        {
          mbar_wait(sb + SM_EMPTY + (ST_WV + 1) * 8);
          float* cp = reinterpret_cast<float*>(smem + 2 * SLOT) + (w * 32 + lane) * 24;
          cp[19] = 1.f; cp[64 * 24 + 19] = 1.f;
          *reinterpret_cast<float2*>(cp + 22) = make_float2(0.f, 1.f); *reinterpret_cast<float2*>(cp + 64 * 24 + 22) = make_float2(0.f, 1.f);
          fence_async_smem();
        }
        bar_sync(6, 192);
        if (w == 0 && elect_one()) {
          asm volatile("cp.reduce.async.bulk.global.shared::cta.bulk_group.add.f32 [%0], [%1], 12288;"
                       ::"l"(&g_kv[hg][0][0]), "r"(sb + 2 * SLOT) : "memory");
          asm volatile("cp.async.bulk.commit_group;" ::: "memory");
          asm volatile("cp.async.bulk.wait_group.read 0;" ::: "memory");
          asm volatile("red.relaxed.gpu.global.add.u32 [%0], 8;" ::"l"(&g_kvcnt[hg * 32]) : "memory");
          mbar_arrive(sb + SM_KVB);
        }
        __syncwarp();
        mbar_wait(sb + SM_KVB);
        if (w == 0) { mbar_wait(sb + SM_EMPTY + 11 * 8); mbar_wait(sb + SM_EMPTY + 12 * 8); mbar_wait(sb + SM_EMPTY + 13 * 8); }
#pragma unroll 1
        for (int ph = 0; ph < 2; ph++) {
          const int use = 2 * ph + w, r = ph ? 2 * rb3 + w : 2 * rb + w;
          const uint32_t* pw = ph ? reinterpret_cast<const uint32_t*>(&g_s[r].st[lane >> 2][(lane & 3) * 16 + 15])
                                  : reinterpret_cast<const uint32_t*>(&g_s[r].o[lane >> 2][lane & 3][3][31]);
          const char* src = reinterpret_cast<const char*>(ph ? &g_s[r].h[0][0][0][0] : &g_s[r].o[0][0][0][0]);
          const uint32_t bf = sb + SM_XF + use * 32, be = sb + SM_XE + (use - 1) * 32;
          bar_sync(10 + w, 160);
          int it = 0;
#pragma unroll 1
          for (bool miss = true; __any_sync(0xffffffffu, miss) && ++it < (1 << 18);) { if (miss) miss = (ld_rlx1(pw) ^ T) & 1; }
          if (elect_one()) {
            if (use > 0) mbar_wait(be);
            if (ph) bulk_g2s(sb + SM_KV32 + w * 4096, &g_s[r].st[0][0], 4096, bf);
#pragma unroll
            for (int p = 0; p < 4; p++) {
              if (p > 0 && use > 0) mbar_wait(be + p * 8);
              bulk_g2s(sb + 2 * SLOT + p * 16384, src + p * 16384, 16384, bf + p * 8);
            }
          }
          __syncwarp();
        }
        {
          const int m = jf >> 1, oc = (jf & 1) * 4 + m;
          const uint32_t* pw = reinterpret_cast<const uint32_t*>(&g_s[2 * rb3 + w].part[oc][(m - 1 - (lane >> 2)) & 3][lane & 3][3][31]);
          bar_sync(12, 320);
          bool miss = lane < 12; int it = 0;
#pragma unroll 1
          for (int q = 0; q < 3; q++) {
#pragma unroll 1
            while ((__ballot_sync(0xffffffffu, miss) >> (4 * q) & 15) && ++it < (1 << 18)) { if (miss && (lane >> 2) <= q + 1) miss = (ld_rlx1(pw) ^ T) & 1; }
            if (elect_one()) {
              const uint32_t bar = sb + SM_XF + (w * 4 + q) * 8;
              mbar_expect_tx(bar, 8192);
              bulk_g2s(sb + ((ST_D % NSLOT) + w) * SLOT + q * 8192, &g_s[2 * rb3 + w].part[oc][(m - 1 - q) & 3][0][0][0], 8192, bar);
            }
            __syncwarp();
          }
        }
      }
    }
    asm volatile("barrier.cluster.arrive.relaxed.aligned;" ::: "memory");
    asm volatile("barrier.cluster.wait.aligned;" ::: "memory");
  }
}

typedef CUresult (*EncodeFn)(CUtensorMap*, CUtensorMapDataType, cuuint32_t, void*, const cuuint64_t*, const cuuint64_t*,
                             const cuuint32_t*, const cuuint32_t*, CUtensorMapInterleave, CUtensorMapSwizzle,
                             CUtensorMapL2promotion, CUtensorMapFloatOOBfill);

void encode(EncodeFn fn, CUtensorMap* m, const void* base, int rank, const cuuint64_t* dims, const cuuint64_t* strides,
            const cuuint32_t* box) {
  cuuint32_t es[3] = {1, 1, 1};
  fn(m, CU_TENSOR_MAP_DATA_TYPE_BFLOAT16, (cuuint32_t)rank, const_cast<void*>(base), dims, strides, box, es,
     CU_TENSOR_MAP_INTERLEAVE_NONE, CU_TENSOR_MAP_SWIZZLE_128B, CU_TENSOR_MAP_L2_PROMOTION_L2_256B,
     CU_TENSOR_MAP_FLOAT_OOB_FILL_NONE);
}

}

extern "C" void kernel_launch(void* const* d_in, const int* in_sizes, int n_in, void* d_out, int out_size) {
  (void)in_sizes; (void)n_in; (void)out_size;
  const __nv_bfloat16* x    = (const __nv_bfloat16*)d_in[0];
  const __nv_bfloat16* wqkv = (const __nv_bfloat16*)d_in[1];
  const __nv_bfloat16* wphi = (const __nv_bfloat16*)d_in[2];
  const __nv_bfloat16* wo   = (const __nv_bfloat16*)d_in[3];
  const __nv_bfloat16* wg   = (const __nv_bfloat16*)d_in[5];
  const __nv_bfloat16* wu   = (const __nv_bfloat16*)d_in[6];
  const __nv_bfloat16* wd   = (const __nv_bfloat16*)d_in[7];

  static EncodeFn fn = nullptr;
  if (!fn) {
    void* p = nullptr;
    cudaDriverEntryPointQueryResult qr;
    cudaGetDriverEntryPoint("cuTensorMapEncodeTiled", &p, cudaEnableDefault, &qr);
    fn = (EncodeFn)p;
    cudaFuncSetAttribute(fused_kernel, cudaFuncAttributeMaxDynamicSharedMemorySize, SM_TOTAL);
  }
  Maps maps;
  {
    cuuint64_t d[3] = {64, 2048, 8}, s[2] = {1024, 128}; cuuint32_t b[3] = {64, 64, 3};
    encode(fn, &maps.x, x, 3, d, s, b);
  }
  {
    cuuint64_t d[2] = {512, 2048}, s[1] = {1024}; cuuint32_t b[2] = {64, 64};
    encode(fn, &maps.xr, x, 2, d, s, b);
  }
  {
    cuuint64_t d[2] = {1536, 512}, s[1] = {3072}; cuuint32_t b[2] = {64, 192};
    encode(fn, &maps.w, wqkv, 2, d, s, b);
  }
  {
    cuuint64_t d[2] = {512, 512}, s[1] = {1024}; cuuint32_t b[2] = {64, 192};
    encode(fn, &maps.wo, wo, 2, d, s, b);
  }
  {
    cuuint64_t d[3] = {176, 7, 512}, d7[3] = {144, 1, 512}, s[2] = {352, 2752}; cuuint32_t b[3] = {64, 1, 32};
    encode(fn, &maps.g, wg, 3, d, s, b);
    encode(fn, &maps.u, wu, 3, d, s, b);
    encode(fn, &maps.g7, wg + 1232, 3, d7, s, b);
    encode(fn, &maps.u7, wu + 1232, 3, d7, s, b);
  }
  {
    cuuint64_t d[2] = {512, 1376}, s[1] = {1024}; cuuint32_t b[2] = {64, 176};
    encode(fn, &maps.d, wd, 2, d, s, b);
  }
  fused_kernel<<<NCTA, 384, SM_TOTAL>>>(maps, wphi, wo, wg, wu, wd, (__nv_bfloat16*)d_out);
}
```
